```python
import torch

def _softmax(x, axis=-1):
    return torch.softmax(x, dim=axis)
def _gelu(x):
    return torch.nn.functional.gelu(x, approximate="tanh")
def _silu(x):
    return torch.nn.functional.silu(x)
def _sigmoid(x):
    return torch.sigmoid(x)
def _layernorm(x, axis=-1, eps=1e-5):
    m = x.mean(dim=axis, keepdim=True)
    v = x.var(dim=axis, keepdim=True, unbiased=False)
    return (x - m) / torch.sqrt(v + eps)
def _scatter_add(tgt, idx, src, axis=0):
    return tgt.clone().index_add_(axis, idx, src)
def _segment_sum(src, seg, n):
    out = torch.zeros((n,) + src.shape[1:], dtype=src.dtype)
    return out.index_add_(0, seg, src)
def _pad(x, pw):
    flat = tuple(v for pair in reversed(pw) for v in pair)
    return torch.nn.functional.pad(x, flat)

kernel_name = 'interleave_layers__linear_kernel_hedgehog__sliding_local_dilated__prompt'

def setup_inputs():

    _w = (lambda a: (lambda t: t.to(torch.bfloat16) if t.is_floating_point() else t)(torch.as_tensor(a)))
    def _A_setup():
        B, S, D, H = 1, 2048, 1024, 32
        Dh = D // H
        return {
            "x": _w((lambda *s: torch.randn(*s, dtype=torch.bfloat16) * 0.05)(B, S, D)),
            "wqkv": _w((lambda *s: torch.randn(*s, dtype=torch.bfloat16) * 0.2)(D, 3 * D)),
            "w_phi": _w((lambda *s: torch.randn(*s, dtype=torch.bfloat16) * 0.2)(H, Dh, Dh) * (Dh ** -0.5)),
            "wo": _w((lambda *s: torch.randn(*s, dtype=torch.bfloat16) * 0.05)(D, D)),
        }
    _A_in = _A_setup()

    def _B_setup():
        B, S, D = 1, 2048, 1024
        return {
            "x": _w((lambda *s: torch.randn(*s, dtype=torch.bfloat16) * 0.05)(B, S, D)),
            "wqkv": _w((lambda *s: torch.randn(*s, dtype=torch.bfloat16) * 0.1)(D, 3 * D)),
            "wo": _w((lambda *s: torch.randn(*s, dtype=torch.bfloat16) * 0.05)(D, D)),
        }
    _B_in = _B_setup()

    return {
        "A_x": _A_in["x"],
        "A_wqkv": _A_in["wqkv"],
        "A_w_phi": _A_in["w_phi"],
        "A_wo": _A_in["wo"],
        "B_x": _B_in["x"],
        "B_wqkv": _B_in["wqkv"],
        "B_wo": _B_in["wo"],
    }

def reference(A_x, A_wqkv, A_w_phi, A_wo, B_x, B_wqkv, B_wo):
    def _A_ref(x, wqkv, w_phi, wo):
        B, S, D = x.shape
        H = 32; Dh = D // H
        qkv = (lambda x, *d: x.permute(*d))((x @ wqkv).reshape(B, S, 3, H, Dh), 2, 0, 3, 1, 4)
        q, k, v = qkv[0], qkv[1], qkv[2]
        pq = torch.einsum("bhsd,hdf->bhsf", q, w_phi)
        pk = torch.einsum("bhsd,hdf->bhsf", k, w_phi)
        phi_q = torch.concatenate([_softmax(pq, axis=-1), _softmax(-pq, axis=-1)], axis=-1)
        phi_k = torch.concatenate([_softmax(pk, axis=-1), _softmax(-pk, axis=-1)], axis=-1)
        kv = torch.einsum("bhsf,bhsd->bhfd", phi_k, v)
        z  = torch.einsum("bhsf->bhf", phi_k)
        num = torch.einsum("bhqf,bhfd->bhqd", phi_q, kv)
        den = torch.einsum("bhqf,bhf->bhq", phi_q, z)[..., None] + 1e-6
        o = num / den
        return (lambda x, *d: x.permute(*d))(o, 0, 2, 1, 3).reshape(B, S, D) @ wo

    def _B_ref(x, wqkv, wo):
        B, S, D = x.shape
        H = 32; Dh = D // H
        W, dil = 8, 2
        qkv = (lambda x, *d: x.permute(*d))((x @ wqkv).reshape(B, S, 3, H, Dh), 2, 0, 3, 1, 4)
        q, k, v = qkv[0], qkv[1], qkv[2]
        scale = Dh ** -0.5
        pos = torch.arange(S)
        off = torch.arange(W) * dil
        idx = pos[:, None] - off[None, :]
        mask = idx >= 0
        idx_c = torch.where(mask, idx, 0).reshape(-1)
        kg = k[:, :, idx_c, :].reshape(B, H, S, W, Dh)
        vg = v[:, :, idx_c, :].reshape(B, H, S, W, Dh)
        logits = torch.einsum("bhsd,bhswd->bhsw", q, kg) * scale
        logits = torch.where(mask[None, None, :, :], logits, -1e9)
        attn = _softmax(logits, axis=-1)
        o = torch.einsum("bhsw,bhswd->bhsd", attn, vg)
        return (lambda x, *d: x.permute(*d))(o, 0, 2, 1, 3).reshape(B, S, D) @ wo

    x = A_x
    x = x + _A_ref(_layernorm(x, axis=-1), A_wqkv, A_w_phi, A_wo)
    x = x + _B_ref(_layernorm(x, axis=-1), B_wqkv, B_wo)
    x = x + _A_ref(_layernorm(x, axis=-1), A_wqkv, A_w_phi, A_wo)
    x = x + _B_ref(_layernorm(x, axis=-1), B_wqkv, B_wo)
    return x
```

```cpp
#include <cuda_runtime.h>
#include <cuda_bf16.h>
#include <cuda.h>
#include <stdint.h>

typedef __nv_bfloat16 bf16;

constexpr int S_ = 2048, D_ = 1024;

struct __align__(128) Flag { unsigned int v; unsigned int pad[31]; };
__device__ __align__(1024) bf16 g_x[S_ * D_];
__device__ __align__(1024) bf16 g_o[S_ * D_];
__device__ __align__(1024) uint32_t g_halo[2 * 17 * 8 * 2048];
__device__ __align__(1024) float g_kv[2 * 2 * 8 * 8448];
__device__ __align__(1024) float2 g_stats[2 * 4 * S_];
__device__ __align__(1024) float g_cs[2 * 2 * 3072];
__device__ __align__(1024) bf16 g_wf[D_ * 2048];
__device__ Flag g_kvflag[16], g_csflag[13];
__device__ __align__(128) unsigned int g_xf[16 * 32], g_of[16 * 32];
__device__ __align__(128) unsigned int g_hf[16 * 32];
__device__ __align__(128) unsigned int g_wff[8 * 32];
__device__ unsigned int g_epoch, g_err;
#define PROFT(cond, idx) asm volatile("" ::: "memory")

__device__ __forceinline__ uint32_t smem_u32(const void* p) { return (uint32_t)__cvta_generic_to_shared(p); }
__device__ __forceinline__ void mbar_init(uint32_t bar, uint32_t count) {
  asm volatile("mbarrier.init.shared::cta.b64 [%0], %1;" ::"r"(bar), "r"(count) : "memory");
}
__device__ __forceinline__ void mbar_expect_tx(uint32_t bar, uint32_t bytes) {
  asm volatile("mbarrier.arrive.expect_tx.shared::cta.b64 _, [%0], %1;" ::"r"(bar), "r"(bytes) : "memory");
}
__device__ __forceinline__ void mbar_arrive(uint32_t bar) {
  asm volatile("mbarrier.arrive.shared::cta.b64 _, [%0];" ::"r"(bar) : "memory");
}
__device__ __forceinline__ bool mbar_try_wait(uint32_t bar, uint32_t parity) {
  uint32_t ok;
  asm volatile("{\n.reg .pred p;\nmbarrier.try_wait.parity.shared::cta.b64 p, [%1], %2;\nselp.b32 %0, 1, 0, p;\n}\n"
               : "=r"(ok) : "r"(bar), "r"(parity) : "memory");
  return ok != 0;
}
__device__ __forceinline__ bool mbar_test_wait(uint32_t bar, uint32_t parity) {
  uint32_t ok;
  asm volatile("{\n.reg .pred p;\nmbarrier.test_wait.parity.shared::cta.b64 p, [%1], %2;\nselp.b32 %0, 1, 0, p;\n}\n"
               : "=r"(ok) : "r"(bar), "r"(parity) : "memory");
  return ok != 0;
}
__device__ __forceinline__ uint64_t gtimer() {
  uint64_t t; asm volatile("mov.u64 %0, %globaltimer;" : "=l"(t)); return t;
}
__device__ __forceinline__ void mbar_wait(uint32_t bar, uint32_t parity) {
  uint32_t n = 0;
#pragma unroll 1
  while (!mbar_try_wait(bar, parity)) {
    if (++n > (1u << 22)) { g_err = 1u; break; }
  }
}
__device__ __forceinline__ unsigned int ld_acquire(const unsigned int* p) {
  unsigned int v; asm volatile("ld.acquire.gpu.global.u32 %0, [%1];" : "=r"(v) : "l"(p) : "memory"); return v;
}
__device__ __forceinline__ void flag_add(unsigned int* p) {
  asm volatile("red.release.gpu.global.add.u32 [%0], 1;" ::"l"(p) : "memory");
}
__device__ __forceinline__ void flag_set(unsigned int* p, unsigned int v) {
  asm volatile("st.release.gpu.global.u32 [%0], %1;" ::"l"(p), "r"(v) : "memory");
}
template <int SLEEP>
__device__ __forceinline__ void src_wait(const unsigned int* f, unsigned int target, uint32_t need, uint32_t& ready, int lane) {
  uint32_t n = 0;
#pragma unroll 1
  while ((ready & need) != need) {
    const unsigned int v = ld_acquire(f + (lane & 15));
    ready = __ballot_sync(0xffffffffu, (int)(v - target) >= 0);
    if (SLEEP) { if ((ready & need) != need) __nanosleep(SLEEP); }
    if (++n > (1u << 20)) { g_err = 3u; break; }
  }
  __syncwarp();
}
__device__ __forceinline__ unsigned int ld_relaxed(const unsigned int* p) {
  unsigned int v; asm volatile("ld.relaxed.gpu.global.u32 %0, [%1];" : "=r"(v) : "l"(p) : "memory"); return v;
}
__device__ __forceinline__ uint4 ld_relaxed4(const uint4* p) {
  uint4 v; asm volatile("ld.relaxed.gpu.global.v4.u32 {%0,%1,%2,%3}, [%4];" : "=r"(v.x), "=r"(v.y), "=r"(v.z), "=r"(v.w) : "l"(p) : "memory"); return v;
}
__device__ __forceinline__ void st_relaxed4(uint4* p, uint32_t a, uint32_t b, uint32_t c, uint32_t d) {
  asm volatile("st.relaxed.gpu.global.v4.u32 [%0], {%1,%2,%3,%4};" ::"l"(p), "r"(a), "r"(b), "r"(c), "r"(d) : "memory");
}
__device__ __forceinline__ void st_relaxed4_p(bool on, uint4* p, uint32_t a, uint32_t b, uint32_t c, uint32_t d) {
  asm volatile("{\n.reg .pred p;\nsetp.ne.b32 p, %5, 0;\n@p st.relaxed.gpu.global.v4.u32 [%0], {%1,%2,%3,%4};\n}\n" ::"l"(p), "r"(a), "r"(b), "r"(c), "r"(d), "r"((int)on) : "memory");
}
template <int SLEEP>
__device__ __forceinline__ void flag_wait_t(const unsigned int* p, unsigned int target) {
  uint32_t n = 0;
#pragma unroll 1
  while ((int)(ld_acquire(p) - target) < 0) {
    if (SLEEP) __nanosleep(SLEEP);
    if (++n > (1u << 20)) { g_err = 2u; break; }
  }
}
__device__ __forceinline__ void flag_wait(const unsigned int* p, unsigned int target) { flag_wait_t<0>(p, target); }
__device__ __forceinline__ void flag_wait_slow(const unsigned int* p, unsigned int target) { flag_wait_t<256>(p, target); }
__device__ __forceinline__ void tma_load_2d(uint32_t dst, const CUtensorMap* tm, int c0, int c1, uint32_t bar) {
  asm volatile("cp.async.bulk.tensor.2d.shared::cluster.global.mbarrier::complete_tx::bytes [%0], [%1, {%2, %3}], [%4];"
               ::"r"(dst), "l"(tm), "r"(c0), "r"(c1), "r"(bar) : "memory");
}
__device__ __forceinline__ void tma_load_2d_mc(uint32_t dst, const CUtensorMap* tm, int c0, int c1, uint32_t bar, uint16_t mask) {
  asm volatile("cp.async.bulk.tensor.2d.shared::cluster.global.mbarrier::complete_tx::bytes.multicast::cluster [%0], [%1, {%2, %3}], [%4], %5;"
               ::"r"(dst), "l"(tm), "r"(c0), "r"(c1), "r"(bar), "h"(mask) : "memory");
}
__device__ __forceinline__ void mbar_wait_u(uint32_t bar, uint32_t parity) {
  uint32_t n = 0;
#pragma unroll 1
  while (!__all_sync(0xffffffffu, mbar_try_wait(bar, parity))) {
    if (++n > (1u << 22)) { g_err = 1u; break; }
  }
}
__device__ __forceinline__ void expect_tx_e(uint32_t bar, uint32_t bytes) {
  asm volatile("{\n.reg .pred p;\nelect.sync _|p, 0xffffffff;\n@p mbarrier.arrive.expect_tx.shared::cta.b64 _, [%0], %1;\n}\n" ::"r"(bar), "r"(bytes) : "memory");
}
__device__ __forceinline__ void tma_2d_e(uint32_t dst, const CUtensorMap* tm, int c0, int c1, uint32_t bar) {
  asm volatile("{\n.reg .pred p;\nelect.sync _|p, 0xffffffff;\n"
               "@p cp.async.bulk.tensor.2d.shared::cluster.global.mbarrier::complete_tx::bytes [%0], [%1, {%2, %3}], [%4];\n}\n"
               ::"r"(dst), "l"(tm), "r"(c0), "r"(c1), "r"(bar) : "memory");
}
__device__ __forceinline__ void tma_2d_mc_e(uint32_t dst, const CUtensorMap* tm, int c0, int c1, uint32_t bar) {
  asm volatile("{\n.reg .pred p;\nelect.sync _|p, 0xffffffff;\n"
               "@p cp.async.bulk.tensor.2d.shared::cluster.global.mbarrier::complete_tx::bytes.multicast::cluster [%0], [%1, {%2, %3}], [%4], %5;\n}\n"
               ::"r"(dst), "l"(tm), "r"(c0), "r"(c1), "r"(bar), "h"((uint16_t)3) : "memory");
}
__device__ __forceinline__ void tma_5d(uint32_t dst, const CUtensorMap* tm, int c0, int c4, uint32_t bar) {
  asm volatile("cp.async.bulk.tensor.5d.shared::cluster.global.mbarrier::complete_tx::bytes [%0], [%1, {%2, %5, %5, %5, %3}], [%4];"
               ::"r"(dst), "l"(tm), "r"(c0), "r"(c4), "r"(bar), "r"(0) : "memory");
}
__device__ __forceinline__ void tma_5d_e(uint32_t dst, const CUtensorMap* tm, int c0, int c4, uint32_t bar) {
  asm volatile("{\n.reg .pred p;\nelect.sync _|p, 0xffffffff;\n"
               "@p cp.async.bulk.tensor.5d.shared::cluster.global.mbarrier::complete_tx::bytes [%0], [%1, {%2, %5, %5, %5, %3}], [%4];\n}\n"
               ::"r"(dst), "l"(tm), "r"(c0), "r"(c4), "r"(bar), "r"(0) : "memory");
}
__device__ __forceinline__ void tma_5d_mc_e(uint32_t dst, const CUtensorMap* tm, int c0, int c4, uint32_t bar) {
  asm volatile("{\n.reg .pred p;\nelect.sync _|p, 0xffffffff;\n"
               "@p cp.async.bulk.tensor.5d.shared::cluster.global.mbarrier::complete_tx::bytes.multicast::cluster [%0], [%1, {%2, %6, %6, %6, %3}], [%4], %5;\n}\n"
               ::"r"(dst), "l"(tm), "r"(c0), "r"(c4), "r"(bar), "h"((uint16_t)3), "r"(0) : "memory");
}
__device__ __forceinline__ void wait_tma_2d(bool w, uint32_t eb, uint32_t par, uint32_t dst, const CUtensorMap* tm, int c0, int c1, uint32_t fb) {
  asm volatile("" : "+r"(dst), "+l"(tm), "+r"(c0), "+r"(fb));
  if (w) mbar_wait_u(eb, par);
  tma_2d_e(dst, tm, c0, c1, fb);
}
__device__ __forceinline__ void wait_tma_5d_mc(bool w, uint32_t eb, uint32_t par, uint32_t dst, const CUtensorMap* tm, int c0, int c4, uint32_t fb) {
  asm volatile("" : "+r"(dst), "+l"(tm), "+r"(c0), "+r"(c4), "+r"(fb));
  if (w) mbar_wait_u(eb, par);
  tma_5d_mc_e(dst, tm, c0, c4, fb);
}
__device__ __forceinline__ void stg128(void* p, uint32_t a, uint32_t b, uint32_t c, uint32_t d) {
  asm volatile("st.global.v4.u32 [%0], {%1,%2,%3,%4};" ::"l"(p), "r"(a), "r"(b), "r"(c), "r"(d) : "memory");
}
__device__ __forceinline__ void stg128_p(bool on, void* p, uint32_t a, uint32_t b, uint32_t c, uint32_t d) {
  asm volatile("{\n.reg .pred p;\nsetp.ne.b32 p, %5, 0;\n@p st.global.v4.u32 [%0], {%1,%2,%3,%4};\n}\n" ::"l"(p), "r"(a), "r"(b), "r"(c), "r"(d), "r"((int)on) : "memory");
}
__device__ __forceinline__ void ldg128(const void* p, uint32_t& a, uint32_t& b, uint32_t& c, uint32_t& d) {
  asm volatile("ld.global.cg.v4.u32 {%0,%1,%2,%3}, [%4];" : "=r"(a), "=r"(b), "=r"(c), "=r"(d) : "l"(p) : "memory");
}
__device__ __forceinline__ uint32_t ldg32(const void* p) {
  uint32_t v; asm volatile("ld.global.nc.u32 %0, [%1];" : "=r"(v) : "l"(p) : "memory"); return v;
}
__device__ __forceinline__ void tma_pf_e(const CUtensorMap* tm, int c0, int c1) {
  asm volatile("{\n.reg .pred p;\nelect.sync _|p, 0xffffffff;\n"
               "@p cp.async.bulk.prefetch.tensor.2d.L2.global.tile [%0, {%1, %2}];\n}\n" ::"l"(tm), "r"(c0), "r"(c1) : "memory");
}
__device__ __forceinline__ void tma_2d_to_e(uint32_t dst, const CUtensorMap* tm, int c0, int c1, uint32_t bar, uint32_t mask) {
  asm volatile("{\n.reg .pred p;\nelect.sync _|p, 0xffffffff;\n"
               "@p cp.async.bulk.tensor.2d.shared::cluster.global.mbarrier::complete_tx::bytes.multicast::cluster [%0], [%1, {%2, %3}], [%4], %5;\n}\n"
               ::"r"(dst), "l"(tm), "r"(c0), "r"(c1), "r"(bar), "h"((uint16_t)mask) : "memory");
}
__device__ __forceinline__ void tma_3d_mc_e(uint32_t dst, const CUtensorMap* tm, int c1, int c2, uint32_t bar) {
  asm volatile("{\n.reg .pred p;\nelect.sync _|p, 0xffffffff;\n"
               "@p cp.async.bulk.tensor.3d.shared::cluster.global.mbarrier::complete_tx::bytes.multicast::cluster [%0], [%1, {%6, %2, %3}], [%4], %5;\n}\n"
               ::"r"(dst), "l"(tm), "r"(c1), "r"(c2), "r"(bar), "h"((uint16_t)3), "r"(0) : "memory");
}
__device__ __forceinline__ uint32_t poll_flags(const unsigned int* f, unsigned int target, int lane) {
  const unsigned int v = ld_acquire(f + (lane & 15));
  const uint32_t r = __ballot_sync(0xffffffffu, (int)(v - target) >= 0);
  __syncwarp();
  return r;
}
__device__ __forceinline__ void mbar_arrive_cluster(uint32_t local_bar, uint32_t rank) {
  asm volatile("{\n.reg .b32 ra;\nmapa.shared::cluster.u32 ra, %0, %1;\nmbarrier.arrive.shared::cluster.b64 _, [ra];\n}\n"
               ::"r"(local_bar), "r"(rank) : "memory");
}
__device__ __forceinline__ void release2(uint32_t bar) { mbar_arrive_cluster(bar, 0); mbar_arrive_cluster(bar, 1); }
__device__ __forceinline__ void release2c(uint32_t off) {
  asm volatile("mbarrier.arrive.shared::cluster.b64 _, [%0];\nmbarrier.arrive.shared::cluster.b64 _, [%1];" ::"r"(off), "r"(off + (1u << 24)) : "memory");
}
__device__ __forceinline__ void tma_store_2d(const CUtensorMap* tm, uint32_t src, int c0, int c1) {
  asm volatile("cp.async.bulk.tensor.2d.global.shared::cta.bulk_group [%0, {%2, %3}], [%1];"
               ::"l"(tm), "r"(src), "r"(c0), "r"(c1) : "memory");
}
__device__ __forceinline__ void tma_store_5d(const CUtensorMap* tm, uint32_t src, int c0, int c4) {
  asm volatile("cp.async.bulk.tensor.5d.global.shared::cta.bulk_group [%0, {%2, %4, %4, %4, %3}], [%1];"
               ::"l"(tm), "r"(src), "r"(c0), "r"(c4), "r"(0) : "memory");
}
__device__ __forceinline__ void bulk_store(void* dst, uint32_t src, uint32_t bytes) {
  asm volatile("cp.async.bulk.global.shared::cta.bulk_group [%0], [%1], %2;" ::"l"(dst), "r"(src), "r"(bytes) : "memory");
}
__device__ __forceinline__ void bulk_load(uint32_t dst, const void* src, uint32_t bytes, uint32_t bar) {
  asm volatile("cp.async.bulk.shared::cluster.global.mbarrier::complete_tx::bytes [%0], [%1], %2, [%3];" ::"r"(dst), "l"(src), "r"(bytes), "r"(bar) : "memory");
}
__device__ __forceinline__ void bulk_red_add(void* dst, uint32_t src, uint32_t bytes) {
  asm volatile("cp.reduce.async.bulk.global.shared::cta.bulk_group.add.f32 [%0], [%1], %2;" ::"l"(dst), "r"(src), "r"(bytes) : "memory");
}
__device__ __forceinline__ void bulk_commit() { asm volatile("cp.async.bulk.commit_group;" ::: "memory"); }
__device__ __forceinline__ void bulk_wait0() { asm volatile("cp.async.bulk.wait_group 0;" ::: "memory"); }
__device__ __forceinline__ void fence_async_smem() { asm volatile("fence.proxy.async.shared::cta;" ::: "memory"); }
__device__ __forceinline__ void fence_async_all() { asm volatile("fence.proxy.async.global;" ::: "memory"); }
__device__ __forceinline__ void wgmma_fence() { asm volatile("wgmma.fence.sync.aligned;" ::: "memory"); }
__device__ __forceinline__ void wgmma_commit() { asm volatile("wgmma.commit_group.sync.aligned;" ::: "memory"); }
template <int N> __device__ __forceinline__ void wgmma_wait() { asm volatile("wgmma.wait_group.sync.aligned %0;" ::"n"(N) : "memory"); }
__device__ __forceinline__ void cluster_arrive() { asm volatile("barrier.cluster.arrive.release.aligned;" ::: "memory"); }
__device__ __forceinline__ void cluster_wait() { asm volatile("barrier.cluster.wait.acquire.aligned;" ::: "memory"); }
template <int ID, int N> __device__ __forceinline__ void nbar() { asm volatile("bar.sync %0, %1;" ::"n"(ID), "n"(N) : "memory"); }
__device__ __forceinline__ uint64_t make_desc(uint32_t addr, uint32_t lbo_bytes, uint32_t sbo_bytes) {
  uint64_t d = 0;
  d |= (uint64_t)((addr & 0x3FFFF) >> 4);
  d |= (uint64_t)((lbo_bytes >> 4) & 0x3FFF) << 16;
  d |= (uint64_t)((sbo_bytes >> 4) & 0x3FFF) << 32;
  d |= (uint64_t)1 << 62;
  return d;
}
__device__ __forceinline__ uint64_t desc64(uint32_t lo, uint32_t hi) { return (uint64_t)lo | ((uint64_t)hi << 32); }
__device__ __forceinline__ uint32_t pack_bf16(float lo, float hi) {
  uint32_t r; asm("cvt.rn.bf16x2.f32 %0, %1, %2;" : "=r"(r) : "f"(hi), "f"(lo)); return r;
}
__device__ __forceinline__ uint32_t add_bf16x2(uint32_t a, uint32_t b) {
  uint32_t r; asm("add.rn.bf16x2 %0, %1, %2;" : "=r"(r) : "r"(a), "r"(b)); return r;
}
__device__ __forceinline__ float bf16r(float x) { return __bfloat162float(__float2bfloat16_rn(x)); }
__device__ __forceinline__ float bf_lo(uint32_t u) { return __uint_as_float(u << 16); }
__device__ __forceinline__ float bf_hi(uint32_t u) { return __uint_as_float(u & 0xFFFF0000u); }
__device__ __forceinline__ float ex2(float x) { float r; asm("ex2.approx.ftz.f32 %0, %1;" : "=f"(r) : "f"(x)); return r; }
__device__ __forceinline__ float rcp(float x) { float r; asm("rcp.approx.ftz.f32 %0, %1;" : "=f"(r) : "f"(x)); return r; }
__device__ __forceinline__ void mma_bf16(float (&d)[4], uint32_t a0, uint32_t a1, uint32_t a2, uint32_t a3, uint32_t b0, uint32_t b1) {
  asm("mma.sync.aligned.m16n8k16.row.col.f32.bf16.bf16.f32 {%0,%1,%2,%3}, {%4,%5,%6,%7}, {%8,%9}, {%0,%1,%2,%3};"
               : "+f"(d[0]), "+f"(d[1]), "+f"(d[2]), "+f"(d[3]) : "r"(a0), "r"(a1), "r"(a2), "r"(a3), "r"(b0), "r"(b1));
}
__device__ __forceinline__ void ldsm_x4(uint32_t& r0, uint32_t& r1, uint32_t& r2, uint32_t& r3, uint32_t addr) {
  asm volatile("ldmatrix.sync.aligned.m8n8.x4.shared.b16 {%0,%1,%2,%3}, [%4];"
               : "=r"(r0), "=r"(r1), "=r"(r2), "=r"(r3) : "r"(addr) : "memory");
}
__device__ __forceinline__ void ldsm_x4_t(uint32_t& r0, uint32_t& r1, uint32_t& r2, uint32_t& r3, uint32_t addr) {
  asm volatile("ldmatrix.sync.aligned.m8n8.x4.trans.shared.b16 {%0,%1,%2,%3}, [%4];"
               : "=r"(r0), "=r"(r1), "=r"(r2), "=r"(r3) : "r"(addr) : "memory");
}
__device__ __forceinline__ void ldsm_x2_t(uint32_t& r0, uint32_t& r1, uint32_t addr) {
  asm volatile("ldmatrix.sync.aligned.m8n8.x2.trans.shared.b16 {%0,%1}, [%2];"
               : "=r"(r0), "=r"(r1) : "r"(addr) : "memory");
}
__device__ __forceinline__ void stsm_x4(uint32_t addr, uint32_t r0, uint32_t r1, uint32_t r2, uint32_t r3) {
  asm volatile("stmatrix.sync.aligned.m8n8.x4.shared.b16 [%0], {%1,%2,%3,%4};"
               ::"r"(addr), "r"(r0), "r"(r1), "r"(r2), "r"(r3) : "memory");
}
__device__ __forceinline__ void stsm_x4_p(bool on, uint32_t addr, uint32_t r0, uint32_t r1, uint32_t r2, uint32_t r3) {
  asm volatile("{\n.reg .pred p;\nsetp.ne.b32 p, %5, 0;\n@p stmatrix.sync.aligned.m8n8.x4.shared.b16 [%0], {%1,%2,%3,%4};\n}\n"
               ::"r"(addr), "r"(r0), "r"(r1), "r"(r2), "r"(r3), "r"((int)on) : "memory");
}
__device__ __forceinline__ float2 lds_f2(uint32_t addr) {
  float2 v; asm volatile("ld.shared.v2.f32 {%0,%1}, [%2];" : "=f"(v.x), "=f"(v.y) : "r"(addr) : "memory"); return v;
}
__device__ __forceinline__ uint4 lds128(uint32_t addr) {
  uint4 v; asm volatile("ld.shared.v4.b32 {%0,%1,%2,%3}, [%4];" : "=r"(v.x), "=r"(v.y), "=r"(v.z), "=r"(v.w) : "r"(addr) : "memory"); return v;
}
__device__ __forceinline__ void sts128(uint32_t addr, uint4 v) {
  asm volatile("st.shared.v4.b32 [%0], {%1,%2,%3,%4};" ::"r"(addr), "r"(v.x), "r"(v.y), "r"(v.z), "r"(v.w) : "memory");
}
__device__ __forceinline__ float lds_f(uint32_t addr) {
  float v; asm volatile("ld.shared.f32 %0, [%1];" : "=f"(v) : "r"(addr) : "memory"); return v;
}
__device__ __forceinline__ void sts16(uint32_t addr, uint32_t v) {
  asm volatile("st.shared.u16 [%0], %1;" ::"r"(addr), "h"((unsigned short)v) : "memory");
}
__device__ __forceinline__ void nbar_dyn(int id, int n) { asm volatile("bar.sync %0, %1;" ::"r"(id), "r"(n) : "memory"); }
__device__ __forceinline__ uint64_t make_desc_ns(uint32_t addr, uint32_t lbo_bytes, uint32_t sbo_bytes) {
  return (uint64_t)((addr & 0x3FFFF) >> 4) | ((uint64_t)(lbo_bytes >> 4) << 16) | ((uint64_t)(sbo_bytes >> 4) << 32);
}
__device__ __forceinline__ void sts_f(uint32_t addr, float v) { asm volatile("st.shared.f32 [%0], %1;" ::"r"(addr), "f"(v) : "memory"); }
__device__ __forceinline__ void sts64(uint32_t addr, uint32_t a, uint32_t b) {
  asm volatile("st.shared.v2.b32 [%0], {%1,%2};" ::"r"(addr), "r"(a), "r"(b) : "memory");
}
__device__ __forceinline__ void sts_f2(uint32_t addr, float a, float b) {
  asm volatile("st.shared.v2.f32 [%0], {%1,%2};" ::"r"(addr), "f"(a), "f"(b) : "memory");
}
__device__ __forceinline__ void red_add2(float* p, float a, float b) {
  asm volatile("red.global.add.v2.f32 [%0], {%1,%2};" ::"l"(p), "f"(a), "f"(b) : "memory");
}
__device__ __forceinline__ void red_add2_p(bool on, float* p, float a, float b) {
  asm volatile("{\n.reg .pred p;\nsetp.ne.b32 p, %3, 0;\n@p red.global.add.v2.f32 [%0], {%1,%2};\n}\n" ::"l"(p), "f"(a), "f"(b), "r"((int)on) : "memory");
}
__device__ __forceinline__ void red_add4(float* p, float a, float b, float c, float d) {
  asm volatile("red.global.add.v4.f32 [%0], {%1,%2,%3,%4};" ::"l"(p), "f"(a), "f"(b), "f"(c), "f"(d) : "memory");
}
__device__ __forceinline__ void red_add1(float* p, float a) {
  asm volatile("red.global.add.f32 [%0], %1;" ::"l"(p), "f"(a) : "memory");
}
__device__ __forceinline__ void l2_prefetch(const void* p, uint32_t bytes) {
  asm volatile("cp.async.bulk.prefetch.L2.global [%0], %1;" ::"l"(p), "r"(bytes) : "memory");
}

__device__ __forceinline__ void wgmma_n256(float (&d)[192], uint64_t da, uint64_t db, int scale_d) {
  asm volatile("{\n.reg .pred p;\nsetp.ne.b32 p, %130, 0;\n"
    "wgmma.mma_async.sync.aligned.m64n256k16.f32.bf16.bf16 {%0, %1, %2, %3, %4, %5, %6, %7, %8, %9, %10, %11, %12, %13, %14, %15, %16, %17, %18, %19, %20, %21, %22, %23, %24, %25, %26, %27, %28, %29, %30, %31, %32, %33, %34, %35, %36, %37, %38, %39, %40, %41, %42, %43, %44, %45, %46, %47, %48, %49, %50, %51, %52, %53, %54, %55, %56, %57, %58, %59, %60, %61, %62, %63, %64, %65, %66, %67, %68, %69, %70, %71, %72, %73, %74, %75, %76, %77, %78, %79, %80, %81, %82, %83, %84, %85, %86, %87, %88, %89, %90, %91, %92, %93, %94, %95, %96, %97, %98, %99, %100, %101, %102, %103, %104, %105, %106, %107, %108, %109, %110, %111, %112, %113, %114, %115, %116, %117, %118, %119, %120, %121, %122, %123, %124, %125, %126, %127}, %128, %129, p, 1, 1, 0, 1;\n}\n"
    : "+f"(d[0]), "+f"(d[1]), "+f"(d[2]), "+f"(d[3]), "+f"(d[4]), "+f"(d[5]), "+f"(d[6]), "+f"(d[7]), "+f"(d[8]), "+f"(d[9]), "+f"(d[10]), "+f"(d[11]), "+f"(d[12]), "+f"(d[13]), "+f"(d[14]), "+f"(d[15]), "+f"(d[16]), "+f"(d[17]), "+f"(d[18]), "+f"(d[19]), "+f"(d[20]), "+f"(d[21]), "+f"(d[22]), "+f"(d[23]), "+f"(d[24]), "+f"(d[25]), "+f"(d[26]), "+f"(d[27]), "+f"(d[28]), "+f"(d[29]), "+f"(d[30]), "+f"(d[31]), "+f"(d[32]), "+f"(d[33]), "+f"(d[34]), "+f"(d[35]), "+f"(d[36]), "+f"(d[37]), "+f"(d[38]), "+f"(d[39]), "+f"(d[40]), "+f"(d[41]), "+f"(d[42]), "+f"(d[43]), "+f"(d[44]), "+f"(d[45]), "+f"(d[46]), "+f"(d[47]), "+f"(d[48]), "+f"(d[49]), "+f"(d[50]), "+f"(d[51]), "+f"(d[52]), "+f"(d[53]), "+f"(d[54]), "+f"(d[55]), "+f"(d[56]), "+f"(d[57]), "+f"(d[58]), "+f"(d[59]), "+f"(d[60]), "+f"(d[61]), "+f"(d[62]), "+f"(d[63]), "+f"(d[64]), "+f"(d[65]), "+f"(d[66]), "+f"(d[67]), "+f"(d[68]), "+f"(d[69]), "+f"(d[70]), "+f"(d[71]), "+f"(d[72]), "+f"(d[73]), "+f"(d[74]), "+f"(d[75]), "+f"(d[76]), "+f"(d[77]), "+f"(d[78]), "+f"(d[79]), "+f"(d[80]), "+f"(d[81]), "+f"(d[82]), "+f"(d[83]), "+f"(d[84]), "+f"(d[85]), "+f"(d[86]), "+f"(d[87]), "+f"(d[88]), "+f"(d[89]), "+f"(d[90]), "+f"(d[91]), "+f"(d[92]), "+f"(d[93]), "+f"(d[94]), "+f"(d[95]), "+f"(d[96]), "+f"(d[97]), "+f"(d[98]), "+f"(d[99]), "+f"(d[100]), "+f"(d[101]), "+f"(d[102]), "+f"(d[103]), "+f"(d[104]), "+f"(d[105]), "+f"(d[106]), "+f"(d[107]), "+f"(d[108]), "+f"(d[109]), "+f"(d[110]), "+f"(d[111]), "+f"(d[112]), "+f"(d[113]), "+f"(d[114]), "+f"(d[115]), "+f"(d[116]), "+f"(d[117]), "+f"(d[118]), "+f"(d[119]), "+f"(d[120]), "+f"(d[121]), "+f"(d[122]), "+f"(d[123]), "+f"(d[124]), "+f"(d[125]), "+f"(d[126]), "+f"(d[127])
    : "l"(da), "l"(db), "r"(scale_d));
}
__device__ __forceinline__ void wgmma_n128(float (&d)[192], uint64_t da, uint64_t db, int scale_d) {
  asm volatile("{\n.reg .pred p;\nsetp.ne.b32 p, %66, 0;\n"
    "wgmma.mma_async.sync.aligned.m64n128k16.f32.bf16.bf16 {%0, %1, %2, %3, %4, %5, %6, %7, %8, %9, %10, %11, %12, %13, %14, %15, %16, %17, %18, %19, %20, %21, %22, %23, %24, %25, %26, %27, %28, %29, %30, %31, %32, %33, %34, %35, %36, %37, %38, %39, %40, %41, %42, %43, %44, %45, %46, %47, %48, %49, %50, %51, %52, %53, %54, %55, %56, %57, %58, %59, %60, %61, %62, %63}, %64, %65, p, 1, 1, 0, 1;\n}\n"
    : "+f"(d[128]), "+f"(d[129]), "+f"(d[130]), "+f"(d[131]), "+f"(d[132]), "+f"(d[133]), "+f"(d[134]), "+f"(d[135]), "+f"(d[136]), "+f"(d[137]), "+f"(d[138]), "+f"(d[139]), "+f"(d[140]), "+f"(d[141]), "+f"(d[142]), "+f"(d[143]), "+f"(d[144]), "+f"(d[145]), "+f"(d[146]), "+f"(d[147]), "+f"(d[148]), "+f"(d[149]), "+f"(d[150]), "+f"(d[151]), "+f"(d[152]), "+f"(d[153]), "+f"(d[154]), "+f"(d[155]), "+f"(d[156]), "+f"(d[157]), "+f"(d[158]), "+f"(d[159]), "+f"(d[160]), "+f"(d[161]), "+f"(d[162]), "+f"(d[163]), "+f"(d[164]), "+f"(d[165]), "+f"(d[166]), "+f"(d[167]), "+f"(d[168]), "+f"(d[169]), "+f"(d[170]), "+f"(d[171]), "+f"(d[172]), "+f"(d[173]), "+f"(d[174]), "+f"(d[175]), "+f"(d[176]), "+f"(d[177]), "+f"(d[178]), "+f"(d[179]), "+f"(d[180]), "+f"(d[181]), "+f"(d[182]), "+f"(d[183]), "+f"(d[184]), "+f"(d[185]), "+f"(d[186]), "+f"(d[187]), "+f"(d[188]), "+f"(d[189]), "+f"(d[190]), "+f"(d[191])
    : "l"(da), "l"(db), "r"(scale_d));
}
__device__ __forceinline__ void wgmma_n256_k(float (&d)[192], uint64_t da, uint64_t db, int scale_d) {
  asm volatile("{\n.reg .pred p;\nsetp.ne.b32 p, %130, 0;\n"
    "wgmma.mma_async.sync.aligned.m64n256k16.f32.bf16.bf16 {%0, %1, %2, %3, %4, %5, %6, %7, %8, %9, %10, %11, %12, %13, %14, %15, %16, %17, %18, %19, %20, %21, %22, %23, %24, %25, %26, %27, %28, %29, %30, %31, %32, %33, %34, %35, %36, %37, %38, %39, %40, %41, %42, %43, %44, %45, %46, %47, %48, %49, %50, %51, %52, %53, %54, %55, %56, %57, %58, %59, %60, %61, %62, %63, %64, %65, %66, %67, %68, %69, %70, %71, %72, %73, %74, %75, %76, %77, %78, %79, %80, %81, %82, %83, %84, %85, %86, %87, %88, %89, %90, %91, %92, %93, %94, %95, %96, %97, %98, %99, %100, %101, %102, %103, %104, %105, %106, %107, %108, %109, %110, %111, %112, %113, %114, %115, %116, %117, %118, %119, %120, %121, %122, %123, %124, %125, %126, %127}, %128, %129, p, 1, 1, 0, 0;\n}\n"
    : "+f"(d[0]), "+f"(d[1]), "+f"(d[2]), "+f"(d[3]), "+f"(d[4]), "+f"(d[5]), "+f"(d[6]), "+f"(d[7]), "+f"(d[8]), "+f"(d[9]), "+f"(d[10]), "+f"(d[11]), "+f"(d[12]), "+f"(d[13]), "+f"(d[14]), "+f"(d[15]), "+f"(d[16]), "+f"(d[17]), "+f"(d[18]), "+f"(d[19]), "+f"(d[20]), "+f"(d[21]), "+f"(d[22]), "+f"(d[23]), "+f"(d[24]), "+f"(d[25]), "+f"(d[26]), "+f"(d[27]), "+f"(d[28]), "+f"(d[29]), "+f"(d[30]), "+f"(d[31]), "+f"(d[32]), "+f"(d[33]), "+f"(d[34]), "+f"(d[35]), "+f"(d[36]), "+f"(d[37]), "+f"(d[38]), "+f"(d[39]), "+f"(d[40]), "+f"(d[41]), "+f"(d[42]), "+f"(d[43]), "+f"(d[44]), "+f"(d[45]), "+f"(d[46]), "+f"(d[47]), "+f"(d[48]), "+f"(d[49]), "+f"(d[50]), "+f"(d[51]), "+f"(d[52]), "+f"(d[53]), "+f"(d[54]), "+f"(d[55]), "+f"(d[56]), "+f"(d[57]), "+f"(d[58]), "+f"(d[59]), "+f"(d[60]), "+f"(d[61]), "+f"(d[62]), "+f"(d[63]), "+f"(d[64]), "+f"(d[65]), "+f"(d[66]), "+f"(d[67]), "+f"(d[68]), "+f"(d[69]), "+f"(d[70]), "+f"(d[71]), "+f"(d[72]), "+f"(d[73]), "+f"(d[74]), "+f"(d[75]), "+f"(d[76]), "+f"(d[77]), "+f"(d[78]), "+f"(d[79]), "+f"(d[80]), "+f"(d[81]), "+f"(d[82]), "+f"(d[83]), "+f"(d[84]), "+f"(d[85]), "+f"(d[86]), "+f"(d[87]), "+f"(d[88]), "+f"(d[89]), "+f"(d[90]), "+f"(d[91]), "+f"(d[92]), "+f"(d[93]), "+f"(d[94]), "+f"(d[95]), "+f"(d[96]), "+f"(d[97]), "+f"(d[98]), "+f"(d[99]), "+f"(d[100]), "+f"(d[101]), "+f"(d[102]), "+f"(d[103]), "+f"(d[104]), "+f"(d[105]), "+f"(d[106]), "+f"(d[107]), "+f"(d[108]), "+f"(d[109]), "+f"(d[110]), "+f"(d[111]), "+f"(d[112]), "+f"(d[113]), "+f"(d[114]), "+f"(d[115]), "+f"(d[116]), "+f"(d[117]), "+f"(d[118]), "+f"(d[119]), "+f"(d[120]), "+f"(d[121]), "+f"(d[122]), "+f"(d[123]), "+f"(d[124]), "+f"(d[125]), "+f"(d[126]), "+f"(d[127])
    : "l"(da), "l"(db), "r"(scale_d));
}
__device__ __forceinline__ void wgmma_n128_k(float (&d)[192], uint64_t da, uint64_t db, int scale_d) {
  asm volatile("{\n.reg .pred p;\nsetp.ne.b32 p, %66, 0;\n"
    "wgmma.mma_async.sync.aligned.m64n128k16.f32.bf16.bf16 {%0, %1, %2, %3, %4, %5, %6, %7, %8, %9, %10, %11, %12, %13, %14, %15, %16, %17, %18, %19, %20, %21, %22, %23, %24, %25, %26, %27, %28, %29, %30, %31, %32, %33, %34, %35, %36, %37, %38, %39, %40, %41, %42, %43, %44, %45, %46, %47, %48, %49, %50, %51, %52, %53, %54, %55, %56, %57, %58, %59, %60, %61, %62, %63}, %64, %65, p, 1, 1, 0, 0;\n}\n"
    : "+f"(d[128]), "+f"(d[129]), "+f"(d[130]), "+f"(d[131]), "+f"(d[132]), "+f"(d[133]), "+f"(d[134]), "+f"(d[135]), "+f"(d[136]), "+f"(d[137]), "+f"(d[138]), "+f"(d[139]), "+f"(d[140]), "+f"(d[141]), "+f"(d[142]), "+f"(d[143]), "+f"(d[144]), "+f"(d[145]), "+f"(d[146]), "+f"(d[147]), "+f"(d[148]), "+f"(d[149]), "+f"(d[150]), "+f"(d[151]), "+f"(d[152]), "+f"(d[153]), "+f"(d[154]), "+f"(d[155]), "+f"(d[156]), "+f"(d[157]), "+f"(d[158]), "+f"(d[159]), "+f"(d[160]), "+f"(d[161]), "+f"(d[162]), "+f"(d[163]), "+f"(d[164]), "+f"(d[165]), "+f"(d[166]), "+f"(d[167]), "+f"(d[168]), "+f"(d[169]), "+f"(d[170]), "+f"(d[171]), "+f"(d[172]), "+f"(d[173]), "+f"(d[174]), "+f"(d[175]), "+f"(d[176]), "+f"(d[177]), "+f"(d[178]), "+f"(d[179]), "+f"(d[180]), "+f"(d[181]), "+f"(d[182]), "+f"(d[183]), "+f"(d[184]), "+f"(d[185]), "+f"(d[186]), "+f"(d[187]), "+f"(d[188]), "+f"(d[189]), "+f"(d[190]), "+f"(d[191])
    : "l"(da), "l"(db), "r"(scale_d));
}
__device__ __forceinline__ void wgmma_n40_tt(float (&d)[20], uint64_t da, uint64_t db, int scale_d) {
  asm volatile("{\n.reg .pred p;\nsetp.ne.b32 p, %22, 0;\n"
    "wgmma.mma_async.sync.aligned.m64n40k16.f32.bf16.bf16 {%0, %1, %2, %3, %4, %5, %6, %7, %8, %9, %10, %11, %12, %13, %14, %15, %16, %17, %18, %19}, %20, %21, p, 1, 1, 1, 1;\n}\n"
    : "+f"(d[0]), "+f"(d[1]), "+f"(d[2]), "+f"(d[3]), "+f"(d[4]), "+f"(d[5]), "+f"(d[6]), "+f"(d[7]), "+f"(d[8]), "+f"(d[9]), "+f"(d[10]), "+f"(d[11]), "+f"(d[12]), "+f"(d[13]), "+f"(d[14]), "+f"(d[15]), "+f"(d[16]), "+f"(d[17]), "+f"(d[18]), "+f"(d[19])
    : "l"(da), "l"(db), "r"(scale_d));
}
__device__ __forceinline__ void wgmma_n40_rs(float (&d)[20], const uint32_t (&a)[4], uint64_t db, int scale_d) {
  asm volatile("{\n.reg .pred p;\nsetp.ne.b32 p, %25, 0;\n"
    "wgmma.mma_async.sync.aligned.m64n40k16.f32.bf16.bf16 {%0, %1, %2, %3, %4, %5, %6, %7, %8, %9, %10, %11, %12, %13, %14, %15, %16, %17, %18, %19}, {%20, %21, %22, %23}, %24, p, 1, 1, 1;\n}\n"
    : "+f"(d[0]), "+f"(d[1]), "+f"(d[2]), "+f"(d[3]), "+f"(d[4]), "+f"(d[5]), "+f"(d[6]), "+f"(d[7]), "+f"(d[8]), "+f"(d[9]), "+f"(d[10]), "+f"(d[11]), "+f"(d[12]), "+f"(d[13]), "+f"(d[14]), "+f"(d[15]), "+f"(d[16]), "+f"(d[17]), "+f"(d[18]), "+f"(d[19])
    : "r"(a[0]), "r"(a[1]), "r"(a[2]), "r"(a[3]), "l"(db), "r"(scale_d));
}
__device__ __forceinline__ void wgmma_n256_0(float (&d)[192], uint64_t da, uint64_t db) {
  asm volatile("{\n.reg .pred p;\nsetp.ne.b32 p, 0, 0;\n"
    "wgmma.mma_async.sync.aligned.m64n256k16.f32.bf16.bf16 {%0, %1, %2, %3, %4, %5, %6, %7, %8, %9, %10, %11, %12, %13, %14, %15, %16, %17, %18, %19, %20, %21, %22, %23, %24, %25, %26, %27, %28, %29, %30, %31, %32, %33, %34, %35, %36, %37, %38, %39, %40, %41, %42, %43, %44, %45, %46, %47, %48, %49, %50, %51, %52, %53, %54, %55, %56, %57, %58, %59, %60, %61, %62, %63, %64, %65, %66, %67, %68, %69, %70, %71, %72, %73, %74, %75, %76, %77, %78, %79, %80, %81, %82, %83, %84, %85, %86, %87, %88, %89, %90, %91, %92, %93, %94, %95, %96, %97, %98, %99, %100, %101, %102, %103, %104, %105, %106, %107, %108, %109, %110, %111, %112, %113, %114, %115, %116, %117, %118, %119, %120, %121, %122, %123, %124, %125, %126, %127}, %128, %129, p, 1, 1, 0, 1;\n}\n"
    : "=f"(d[0]), "=f"(d[1]), "=f"(d[2]), "=f"(d[3]), "=f"(d[4]), "=f"(d[5]), "=f"(d[6]), "=f"(d[7]), "=f"(d[8]), "=f"(d[9]), "=f"(d[10]), "=f"(d[11]), "=f"(d[12]), "=f"(d[13]), "=f"(d[14]), "=f"(d[15]), "=f"(d[16]), "=f"(d[17]), "=f"(d[18]), "=f"(d[19]), "=f"(d[20]), "=f"(d[21]), "=f"(d[22]), "=f"(d[23]), "=f"(d[24]), "=f"(d[25]), "=f"(d[26]), "=f"(d[27]), "=f"(d[28]), "=f"(d[29]), "=f"(d[30]), "=f"(d[31]), "=f"(d[32]), "=f"(d[33]), "=f"(d[34]), "=f"(d[35]), "=f"(d[36]), "=f"(d[37]), "=f"(d[38]), "=f"(d[39]), "=f"(d[40]), "=f"(d[41]), "=f"(d[42]), "=f"(d[43]), "=f"(d[44]), "=f"(d[45]), "=f"(d[46]), "=f"(d[47]), "=f"(d[48]), "=f"(d[49]), "=f"(d[50]), "=f"(d[51]), "=f"(d[52]), "=f"(d[53]), "=f"(d[54]), "=f"(d[55]), "=f"(d[56]), "=f"(d[57]), "=f"(d[58]), "=f"(d[59]), "=f"(d[60]), "=f"(d[61]), "=f"(d[62]), "=f"(d[63]), "=f"(d[64]), "=f"(d[65]), "=f"(d[66]), "=f"(d[67]), "=f"(d[68]), "=f"(d[69]), "=f"(d[70]), "=f"(d[71]), "=f"(d[72]), "=f"(d[73]), "=f"(d[74]), "=f"(d[75]), "=f"(d[76]), "=f"(d[77]), "=f"(d[78]), "=f"(d[79]), "=f"(d[80]), "=f"(d[81]), "=f"(d[82]), "=f"(d[83]), "=f"(d[84]), "=f"(d[85]), "=f"(d[86]), "=f"(d[87]), "=f"(d[88]), "=f"(d[89]), "=f"(d[90]), "=f"(d[91]), "=f"(d[92]), "=f"(d[93]), "=f"(d[94]), "=f"(d[95]), "=f"(d[96]), "=f"(d[97]), "=f"(d[98]), "=f"(d[99]), "=f"(d[100]), "=f"(d[101]), "=f"(d[102]), "=f"(d[103]), "=f"(d[104]), "=f"(d[105]), "=f"(d[106]), "=f"(d[107]), "=f"(d[108]), "=f"(d[109]), "=f"(d[110]), "=f"(d[111]), "=f"(d[112]), "=f"(d[113]), "=f"(d[114]), "=f"(d[115]), "=f"(d[116]), "=f"(d[117]), "=f"(d[118]), "=f"(d[119]), "=f"(d[120]), "=f"(d[121]), "=f"(d[122]), "=f"(d[123]), "=f"(d[124]), "=f"(d[125]), "=f"(d[126]), "=f"(d[127])
    : "l"(da), "l"(db));
}
__device__ __forceinline__ void wgmma_n128_0(float (&d)[192], uint64_t da, uint64_t db) {
  asm volatile("{\n.reg .pred p;\nsetp.ne.b32 p, 0, 0;\n"
    "wgmma.mma_async.sync.aligned.m64n128k16.f32.bf16.bf16 {%0, %1, %2, %3, %4, %5, %6, %7, %8, %9, %10, %11, %12, %13, %14, %15, %16, %17, %18, %19, %20, %21, %22, %23, %24, %25, %26, %27, %28, %29, %30, %31, %32, %33, %34, %35, %36, %37, %38, %39, %40, %41, %42, %43, %44, %45, %46, %47, %48, %49, %50, %51, %52, %53, %54, %55, %56, %57, %58, %59, %60, %61, %62, %63}, %64, %65, p, 1, 1, 0, 1;\n}\n"
    : "=f"(d[128]), "=f"(d[129]), "=f"(d[130]), "=f"(d[131]), "=f"(d[132]), "=f"(d[133]), "=f"(d[134]), "=f"(d[135]), "=f"(d[136]), "=f"(d[137]), "=f"(d[138]), "=f"(d[139]), "=f"(d[140]), "=f"(d[141]), "=f"(d[142]), "=f"(d[143]), "=f"(d[144]), "=f"(d[145]), "=f"(d[146]), "=f"(d[147]), "=f"(d[148]), "=f"(d[149]), "=f"(d[150]), "=f"(d[151]), "=f"(d[152]), "=f"(d[153]), "=f"(d[154]), "=f"(d[155]), "=f"(d[156]), "=f"(d[157]), "=f"(d[158]), "=f"(d[159]), "=f"(d[160]), "=f"(d[161]), "=f"(d[162]), "=f"(d[163]), "=f"(d[164]), "=f"(d[165]), "=f"(d[166]), "=f"(d[167]), "=f"(d[168]), "=f"(d[169]), "=f"(d[170]), "=f"(d[171]), "=f"(d[172]), "=f"(d[173]), "=f"(d[174]), "=f"(d[175]), "=f"(d[176]), "=f"(d[177]), "=f"(d[178]), "=f"(d[179]), "=f"(d[180]), "=f"(d[181]), "=f"(d[182]), "=f"(d[183]), "=f"(d[184]), "=f"(d[185]), "=f"(d[186]), "=f"(d[187]), "=f"(d[188]), "=f"(d[189]), "=f"(d[190]), "=f"(d[191])
    : "l"(da), "l"(db));
}
__device__ __forceinline__ void wgmma_n128_rs(float (&d)[192], const uint32_t (&a)[4], uint64_t db, int scale_d) {
  asm volatile("{\n.reg .pred p;\nsetp.ne.b32 p, %69, 0;\n"
    "wgmma.mma_async.sync.aligned.m64n128k16.f32.bf16.bf16 {%0, %1, %2, %3, %4, %5, %6, %7, %8, %9, %10, %11, %12, %13, %14, %15, %16, %17, %18, %19, %20, %21, %22, %23, %24, %25, %26, %27, %28, %29, %30, %31, %32, %33, %34, %35, %36, %37, %38, %39, %40, %41, %42, %43, %44, %45, %46, %47, %48, %49, %50, %51, %52, %53, %54, %55, %56, %57, %58, %59, %60, %61, %62, %63}, {%64, %65, %66, %67}, %68, p, 1, 1, 1;\n}\n"
    : "+f"(d[128]), "+f"(d[129]), "+f"(d[130]), "+f"(d[131]), "+f"(d[132]), "+f"(d[133]), "+f"(d[134]), "+f"(d[135]), "+f"(d[136]), "+f"(d[137]), "+f"(d[138]), "+f"(d[139]), "+f"(d[140]), "+f"(d[141]), "+f"(d[142]), "+f"(d[143]), "+f"(d[144]), "+f"(d[145]), "+f"(d[146]), "+f"(d[147]), "+f"(d[148]), "+f"(d[149]), "+f"(d[150]), "+f"(d[151]), "+f"(d[152]), "+f"(d[153]), "+f"(d[154]), "+f"(d[155]), "+f"(d[156]), "+f"(d[157]), "+f"(d[158]), "+f"(d[159]), "+f"(d[160]), "+f"(d[161]), "+f"(d[162]), "+f"(d[163]), "+f"(d[164]), "+f"(d[165]), "+f"(d[166]), "+f"(d[167]), "+f"(d[168]), "+f"(d[169]), "+f"(d[170]), "+f"(d[171]), "+f"(d[172]), "+f"(d[173]), "+f"(d[174]), "+f"(d[175]), "+f"(d[176]), "+f"(d[177]), "+f"(d[178]), "+f"(d[179]), "+f"(d[180]), "+f"(d[181]), "+f"(d[182]), "+f"(d[183]), "+f"(d[184]), "+f"(d[185]), "+f"(d[186]), "+f"(d[187]), "+f"(d[188]), "+f"(d[189]), "+f"(d[190]), "+f"(d[191])
    : "r"(a[0]), "r"(a[1]), "r"(a[2]), "r"(a[3]), "l"(db), "r"(scale_d));
}
__device__ __forceinline__ void wgmma_n32_0(float (&d)[16], uint64_t da, uint64_t db) {
  asm volatile("{\n.reg .pred p;\nsetp.ne.b32 p, 0, 0;\n"
    "wgmma.mma_async.sync.aligned.m64n32k16.f32.bf16.bf16 {%0, %1, %2, %3, %4, %5, %6, %7, %8, %9, %10, %11, %12, %13, %14, %15}, %16, %17, p, 1, 1, 0, 1;\n}\n"
    : "=f"(d[0]), "=f"(d[1]), "=f"(d[2]), "=f"(d[3]), "=f"(d[4]), "=f"(d[5]), "=f"(d[6]), "=f"(d[7]), "=f"(d[8]), "=f"(d[9]), "=f"(d[10]), "=f"(d[11]), "=f"(d[12]), "=f"(d[13]), "=f"(d[14]), "=f"(d[15])
    : "l"(da), "l"(db));
}
__device__ __forceinline__ void wgmma_n32(float (&d)[16], uint64_t da, uint64_t db, int scale_d) {
  asm volatile("{\n.reg .pred p;\nsetp.ne.b32 p, %18, 0;\n"
    "wgmma.mma_async.sync.aligned.m64n32k16.f32.bf16.bf16 {%0, %1, %2, %3, %4, %5, %6, %7, %8, %9, %10, %11, %12, %13, %14, %15}, %16, %17, p, 1, 1, 0, 1;\n}\n"
    : "+f"(d[0]), "+f"(d[1]), "+f"(d[2]), "+f"(d[3]), "+f"(d[4]), "+f"(d[5]), "+f"(d[6]), "+f"(d[7]), "+f"(d[8]), "+f"(d[9]), "+f"(d[10]), "+f"(d[11]), "+f"(d[12]), "+f"(d[13]), "+f"(d[14]), "+f"(d[15])
    : "l"(da), "l"(db), "r"(scale_d));
}
__device__ __forceinline__ void wgmma_n8_t(float (&d)[4], uint64_t da, uint64_t db, int scale_d) {
  asm volatile("{\n.reg .pred p;\nsetp.ne.b32 p, %6, 0;\n"
    "wgmma.mma_async.sync.aligned.m64n8k16.f32.bf16.bf16 {%0, %1, %2, %3}, %4, %5, p, 1, 1, 1, 0;\n}\n"
    : "+f"(d[0]), "+f"(d[1]), "+f"(d[2]), "+f"(d[3])
    : "l"(da), "l"(db), "r"(scale_d));
}
__device__ __forceinline__ void wgmma_n64_lo(float (&d)[192], uint64_t da, uint64_t db, int scale_d) {
  asm volatile("{\n.reg .pred p;\nsetp.ne.b32 p, %34, 0;\n"
    "wgmma.mma_async.sync.aligned.m64n64k16.f32.bf16.bf16 {%0, %1, %2, %3, %4, %5, %6, %7, %8, %9, %10, %11, %12, %13, %14, %15, %16, %17, %18, %19, %20, %21, %22, %23, %24, %25, %26, %27, %28, %29, %30, %31}, %32, %33, p, 1, 1, 0, 1;\n}\n"
    : "+f"(d[128]), "+f"(d[129]), "+f"(d[130]), "+f"(d[131]), "+f"(d[132]), "+f"(d[133]), "+f"(d[134]), "+f"(d[135]), "+f"(d[136]), "+f"(d[137]), "+f"(d[138]), "+f"(d[139]), "+f"(d[140]), "+f"(d[141]), "+f"(d[142]), "+f"(d[143]), "+f"(d[144]), "+f"(d[145]), "+f"(d[146]), "+f"(d[147]), "+f"(d[148]), "+f"(d[149]), "+f"(d[150]), "+f"(d[151]), "+f"(d[152]), "+f"(d[153]), "+f"(d[154]), "+f"(d[155]), "+f"(d[156]), "+f"(d[157]), "+f"(d[158]), "+f"(d[159])
    : "l"(da), "l"(db), "r"(scale_d));
}
__device__ __forceinline__ void wgmma_n64_hi(float (&d)[192], uint64_t da, uint64_t db, int scale_d) {
  asm volatile("{\n.reg .pred p;\nsetp.ne.b32 p, %34, 0;\n"
    "wgmma.mma_async.sync.aligned.m64n64k16.f32.bf16.bf16 {%0, %1, %2, %3, %4, %5, %6, %7, %8, %9, %10, %11, %12, %13, %14, %15, %16, %17, %18, %19, %20, %21, %22, %23, %24, %25, %26, %27, %28, %29, %30, %31}, %32, %33, p, 1, 1, 0, 1;\n}\n"
    : "+f"(d[160]), "+f"(d[161]), "+f"(d[162]), "+f"(d[163]), "+f"(d[164]), "+f"(d[165]), "+f"(d[166]), "+f"(d[167]), "+f"(d[168]), "+f"(d[169]), "+f"(d[170]), "+f"(d[171]), "+f"(d[172]), "+f"(d[173]), "+f"(d[174]), "+f"(d[175]), "+f"(d[176]), "+f"(d[177]), "+f"(d[178]), "+f"(d[179]), "+f"(d[180]), "+f"(d[181]), "+f"(d[182]), "+f"(d[183]), "+f"(d[184]), "+f"(d[185]), "+f"(d[186]), "+f"(d[187]), "+f"(d[188]), "+f"(d[189]), "+f"(d[190]), "+f"(d[191])
    : "l"(da), "l"(db), "r"(scale_d));
}
__device__ __forceinline__ void wgmma_n128_rs0(float (&d)[192], const uint32_t (&a)[4], uint64_t db) {
  asm volatile("{\n.reg .pred p;\nsetp.ne.b32 p, 0, 0;\n"
    "wgmma.mma_async.sync.aligned.m64n128k16.f32.bf16.bf16 {%0, %1, %2, %3, %4, %5, %6, %7, %8, %9, %10, %11, %12, %13, %14, %15, %16, %17, %18, %19, %20, %21, %22, %23, %24, %25, %26, %27, %28, %29, %30, %31, %32, %33, %34, %35, %36, %37, %38, %39, %40, %41, %42, %43, %44, %45, %46, %47, %48, %49, %50, %51, %52, %53, %54, %55, %56, %57, %58, %59, %60, %61, %62, %63}, {%64, %65, %66, %67}, %68, p, 1, 1, 1;\n}\n"
    : "=f"(d[128]), "=f"(d[129]), "=f"(d[130]), "=f"(d[131]), "=f"(d[132]), "=f"(d[133]), "=f"(d[134]), "=f"(d[135]), "=f"(d[136]), "=f"(d[137]), "=f"(d[138]), "=f"(d[139]), "=f"(d[140]), "=f"(d[141]), "=f"(d[142]), "=f"(d[143]), "=f"(d[144]), "=f"(d[145]), "=f"(d[146]), "=f"(d[147]), "=f"(d[148]), "=f"(d[149]), "=f"(d[150]), "=f"(d[151]), "=f"(d[152]), "=f"(d[153]), "=f"(d[154]), "=f"(d[155]), "=f"(d[156]), "=f"(d[157]), "=f"(d[158]), "=f"(d[159]), "=f"(d[160]), "=f"(d[161]), "=f"(d[162]), "=f"(d[163]), "=f"(d[164]), "=f"(d[165]), "=f"(d[166]), "=f"(d[167]), "=f"(d[168]), "=f"(d[169]), "=f"(d[170]), "=f"(d[171]), "=f"(d[172]), "=f"(d[173]), "=f"(d[174]), "=f"(d[175]), "=f"(d[176]), "=f"(d[177]), "=f"(d[178]), "=f"(d[179]), "=f"(d[180]), "=f"(d[181]), "=f"(d[182]), "=f"(d[183]), "=f"(d[184]), "=f"(d[185]), "=f"(d[186]), "=f"(d[187]), "=f"(d[188]), "=f"(d[189]), "=f"(d[190]), "=f"(d[191])
    : "r"(a[0]), "r"(a[1]), "r"(a[2]), "r"(a[3]), "l"(db));
}

constexpr int SLOT = 16384;
constexpr int VB = 2 * SLOT, PH = 4 * SLOT, XS = 6;
constexpr int SM_SD = 13 * SLOT;
constexpr int SM_BAR = SM_SD + 8192;
constexpr int SM_RS = SM_BAR + 1024;
constexpr int SM_AP = SM_RS + 640;
constexpr int SM_BP = SM_AP + 2048;
constexpr int SM_EPOCH = SM_BP + 6144;
constexpr int SM_TOTAL = SM_EPOCH + 16;
constexpr int FM = 0, FT = 16, FW = 30, CM = 46, CT = 62, CW = 76, B_EF = 92, B_STAT = 93, B_KVF = 94, B_HALO = 95,
              B_KVDONE = 96, B_OH0 = 97, B_OH1 = 98, B_XH0 = 99, B_XDONE = 100, B_WFD = 101, B_XT = 102, B_OF0 = 103, B_KVF1 = 104, B_X0 = 105, B_RAW = 106  ;
constexpr uint64_t BAR_LG = 0x00043333330004ull;
#define BA(i) (bar + (i) * 8)
#define REL2(i) release2c(SB0 + SM_BAR + (i) * 8)
constexpr int NF = 4, ND = 12, NR = 0, NWOP = 48, NAOP = 37;
constexpr uint64_t TL_A = 0x861078610786ull, TL_B = 0x9bac9bac9bacull, WO_A = 0xb758610a45861cffull, WO_B = 0xca4329bc7329b0a7ull;
__constant__ uint32_t c_wop[NWOP + 1] = {0x6b0000, 0x1aeb0009, 0x6c0112, 0x6c8224, 0x18ed011a, 0x20ed822b, 0x170330, 0x22970339, 0x18178442, 0x18180554, 0x18188660, 0x18190772, 0x18198884, 0x181a0990, 0x181a8aa2, 0x181b0bb4, 0x181b8cc0, 0xaed90fc, 0xa9791ea, 0x181c0dd2, 0xa9812db, 0x129893c9, 0x181c8ee4, 0x181d0ff0, 0x109f14bc, 0x109f95aa, 0x10a0169b, 0x10a09789, 0x10a1187c, 0x10a1996a, 0x10a21a5b, 0x10a29b49, 0xb229e07, 0x11232020, 0x9239f1a, 0x1124213b, 0x1124a249, 0x112e2352, 0x132e2463, 0x11262577, 0x1127268c, 0x1127a79b, 0x112828a9, 0x1128a9b2, 0x11292ac3, 0x1129abd4, 0x112a2cea, 0x132a2dfc, 0};
__constant__ uint32_t c_aop[NAOP + 1] = {0x6c0228, 0x170336, 0x178447, 0x180558, 0x188666, 0x190777, 0x198888, 0x1a0996, 0x1a8aa7, 0x1b0bb8, 0x1b8cc6, 0x1c0dd7, 0x1c8ee8, 0x1d0ff6, 0x1e93c0, 0x21e94b1, 0x1f15a6, 0x1f9698, 0x201787, 0x209870, 0x211961, 0x219a56, 0x221b48, 0xa3202c, 0xa3a131, 0xa42246, 0xa4a358, 0xae2465, 0x2ae2574, 0xa6a68a, 0xa72790, 0xa7a8a1, 0xa829b6, 0xa8aac8, 0xa92bd5, 0xa9ace7, 0xaaadfb, 0};
__constant__ uint32_t c_map[64] = {4, 5, 6, 7, 0, 16, 32, 48, 64, 80, 96, 112, 1, 17, 33, 49, 65, 81, 97, 113, 2, 18, 34, 50, 66, 82, 98, 114, 3, 19, 35, 51, 67, 83, 99, 115, 20, 36, 52, 68, 84, 100, 116, 21, 37, 53, 69, 85, 101, 117, 22, 38, 54, 70, 86, 102, 118, 23, 39, 55, 71, 87, 103, 119};
enum { MAP_WF = 0, MAP_WA = 2, MAP_WB = 4, MAP_WOA = 6, MAP_WOB = 8, MAP_X0 = 10, MAP_X = 11, MAP_O = 12, MAP_PHI = 13, NMAP = 14 };
struct Maps { CUtensorMap m[NMAP]; };

#define PL 2
#define PROFL(a, b)
#define SUBS 8
#define QORD 1
#define NCH 4
#define CHW 1
#define DRAIN 0
#define SUBS1 12
#define XRAT 10
#define PFW 0
#define XRN 2
#define BT1 1
#define NLAYERS 4
constexpr float L2E = 1.4426950408889634f;

#define D128(lo) desc64(lo, 0x40000040u)
struct Ctx { uint32_t zero, boff; bf16* out; };
#define BLK_CTX() \
  uint32_t bid_; asm volatile("mov.u32 %0, %%ctaid.x;" : "=r"(bid_)); \
  bid_ -= c.boff; \
  const uint32_t gr_ = c_map[bid_ >> 1]; \
  const int cr = bid_ & 1, g = gr_ & 7, rb = (gr_ >> 3) + cr, m0 = rb * 128; \
  const uint32_t sb = SB0 + (cr << 24); \
  const uint32_t bar = sb + SM_BAR; \
  (void)cr; (void)g; (void)rb; (void)m0; (void)bar;
extern __shared__ uint8_t smem_raw[];
constexpr uint32_t SB0 = 1024;

#define PHASE_CTX() \
  BLK_CTX(); \
  int tid_ = threadIdx.x; asm volatile("" : "+r"(tid_)); \
  const int lane = tid_ & 31, cw = (tid_ >> 5) - 4, wg = cw >> 2, wq = cw & 3, gq = lane >> 2, t = lane & 3, wrow0 = cw * 16; \
  const int lrow = (lane & 7) + ((lane >> 3) & 1) * 8, lchk = lane >> 4; \
  const bool elected = (tid_ & 127) == 0; \
  const uint32_t rowo = (wrow0 + lrow) * 128, X = (lchk ^ (lane & 7)) << 4; \
  const uint32_t Y = (wrow0 + (lane & 7)) * 128 + (((lane >> 3) ^ (lane & 7)) << 4); \
  const size_t gfr = (size_t)(m0 + wrow0 + gq) * D_ + g * 128 + 8 * t; \
  (void)bar; (void)wq; (void)gq; (void)lrow; (void)lchk; (void)elected; (void)wrow0; (void)wg; (void)rowo; (void)X; (void)t; (void)Y; (void)gfr;
#define MMA_CTX() \
  const uint32_t wu = __shfl_sync(0xffffffffu, wg, 0); \
  const uint32_t dA0 = ((SB0 >> 4) | (1u << 16)) + wu * 512, dB0 = (SB0 >> 4) | (512u << 16); \
  const uint32_t par = layer & 1;

__device__ __forceinline__ void slab_out_half(uint32_t slot, bf16* dst, int wrow0, int lane) {
  const int r0 = lane >> 3, ch = lane & 7;
  const uint32_t src = slot + (wrow0 + r0) * 128;
  uint4 v[4];
#pragma unroll
  for (int i = 0; i < 4; ++i) v[i] = lds128(src + i * 512 + (((ch ^ (4 * i + r0)) & 7) << 4));
  dst += (size_t)(wrow0 + r0) * D_ + ch * 8;
#pragma unroll
  for (int i = 0; i < 4; ++i) *reinterpret_cast<uint4*>(dst + (size_t)i * 4 * D_) = v[i];
}

__device__ __forceinline__ void consumer(const Ctx& c) {
  float acc[192];
  uint32_t xp[8][4];
  {
    PHASE_CTX();
    const unsigned int epoch = ld_relaxed(&g_epoch);
    PROFT(tid_ == 128, 0);
    const uint32_t wu = __shfl_sync(0xffffffffu, wg, 0);
    if (tid_ < 128 + 8) sts128(sb + SM_AP + lane * 16, make_uint4(0x3F803F80u, 0x3F803F80u, 0x3F803F80u, 0x3F803F80u));
    float p[2][4][16];
#pragma unroll
    for (int it = 0; it < 2; ++it) {
      mbar_wait(BA(B_RAW + it), 0);
      PROFT(tid_ == 128, it ? 15 : 2);
      const uint32_t da = ((SB0 >> 4) | (1u << 16)) + (wu ? 9 + (cr ^ it) : 2 * (cr ^ it)) * 1024, db = (SB0 + SM_SD) >> 4;
      wgmma_fence();
#pragma unroll
      for (int h = 0; h < 4; ++h) wgmma_n32_0(p[it][h], D128(da + (h >> 1) * 512 + (h & 1) * 4), desc64(db + h * 128, 0x80000020u));
#pragma unroll
      for (int h = 0; h < 4; ++h) wgmma_n32(p[it][h], D128(da + (h >> 1) * 512 + (h & 1) * 4 + 2), desc64(db + h * 128 + 64, 0x80000020u), 1);
      wgmma_commit();
    }
#pragma unroll
    for (int it = 0; it < 2; ++it) {
      if (it) wgmma_wait<0>(); else wgmma_wait<1>();
#pragma unroll
      for (int i = 0; i < 64; ++i) asm volatile("" : "+f"(p[it][i >> 4][i & 15]) :: "memory");
      const uint32_t base = sb + (wg ? 9 + (cr ^ it) : 2 * (cr ^ it)) * SLOT + (wq * 16 + gq) * 128;
      uint32_t w[4][4][2];
#pragma unroll
      for (int i = 0; i < 32; ++i) w[i >> 3][(i >> 1) & 3][i & 1] = pack_bf16(p[it][i >> 3][2 * (i & 7)], p[it][i >> 3][2 * (i & 7) + 1]);
      if (wu) {
#pragma unroll
        for (int i = 0; i < 8; ++i)
          sts128(base + (i >> 2) * 8192 + (i & 1) * 1024 + (((((i >> 1) & 1) * 4 + t) ^ gq) << 4), make_uint4(w[i >> 1][0][i & 1], w[i >> 1][1][i & 1], w[i >> 1][2][i & 1], w[i >> 1][3][i & 1]));
      } else {
#pragma unroll
        for (int i = 0; i < 16; ++i)
          sts64(base + (i >> 3) * 8192 + (i & 1) * 1024 + ((((t & 1) * 4 + ((i >> 1) & 3)) ^ gq) << 4) + (t >> 1) * 8, w[(i >> 3) * 2][(i >> 1) & 3][i & 1], w[(i >> 3) * 2 + 1][(i >> 1) & 3][i & 1]);
      }
      if (it == 0) {
        fence_async_smem();
        __syncwarp();
        if (lane == 0) mbar_arrive(BA(B_WFD));
      }
    }
    if (tid_ == 128) sts_f(sb + SM_EPOCH, __uint_as_float(epoch & 1));
#pragma unroll
    for (int i = 0; i < 32; ++i) xp[i >> 2][i & 3] = 0u;
    fence_async_smem();
    nbar<1, 256>();
    PROFT(tid_ == 128, 13);
    mbar_wait(BA(FM + cr), 0);
    float cs[3][4];
    wgmma_fence();
#pragma unroll
    for (int ks = 0; ks < 4; ++ks)
#pragma unroll
      for (int i = 0; i < 3; ++i) {
        const uint32_t bx = (i == 0 ? 2 * cr * 1024 : i == 1 ? (2 * cr + 1) * 1024 : (9 + cr) * 1024) + wu * 512;
        wgmma_n8_t(cs[i], D128(((SB0 >> 4) | (512u << 16)) + bx + ks * 128), desc64((SB0 + SM_AP) >> 4, 0), ks != 0);
      }
    wgmma_commit();
    wgmma_wait<0>();
#pragma unroll
    for (int i = 0; i < 12; ++i) asm volatile("" : "+f"(cs[i >> 2][i & 3]) :: "memory");
    if (t < 2) {
#pragma unroll
      for (int i = 0; i < 3; ++i) red_add1(g_cs + (epoch & 1) * 6144 + g * 384 + i * 128 + wg * 64 + wq * 16 + gq + t * 8, t ? cs[i][2] : cs[i][0]);
    }
    PROFT(tid_ == 128, 14);
  }
#pragma unroll 1
  for (int layer = 0;; ++layer) {
    {
      PHASE_CTX();
      MMA_CTX();
      {
        const uint32_t ep = __float_as_uint(lds_f(sb + SM_EPOCH));
        mbar_wait(BA(FM), par);
        wgmma_fence();
        wgmma_n256_0(acc, D128(dA0 + XS * 1024), D128(dB0));
#pragma unroll
        for (int k = 1; k < 4; ++k) wgmma_n256(acc, D128(dA0 + XS * 1024 + k * 2), D128(dB0 + k * 128), 1);
#pragma unroll
        for (int i = 4; i < 8; ++i) stg128_p(layer != 0, g_x + gfr + (i & 1) * 8 * D_ + (i >> 1) * 32, xp[i][0], xp[i][1], xp[i][2], xp[i][3]);
        mbar_wait(BA(FM + 1), par);
        wgmma_fence();
#pragma unroll
        for (int k = 0; k < 4; ++k) wgmma_n256(acc, D128(dA0 + (XS + 1) * 1024 + k * 2), D128(dB0 + 2048 + k * 128), 1);
        if (layer == 0) {
          mbar_wait(BA(B_X0), 0);
#pragma unroll
          for (int i = 0; i < 8; ++i) ldsm_x4(xp[i][0], xp[i][1], xp[i][2], xp[i][3], sb + (11 + (i >> 2)) * SLOT + (Y ^ ((i & 2) << 5)) + (i & 1) * 1024);
#pragma unroll
          for (int i = 0; i < 8; ++i) stg128(g_x + gfr + (i & 1) * 8 * D_ + (i >> 1) * 32, xp[i][0], xp[i][1], xp[i][2], xp[i][3]);
          __syncwarp();
          if (lane == 0) REL2(B_XT);
        }
        float s0 = 0.f, s1 = 0.f, q0 = 0.f, q1 = 0.f;
#pragma unroll
        for (int j = 0; j < 16; ++j) {
          const uint32_t u0 = xp[(j >> 2) * 2][j & 3], u1 = xp[(j >> 2) * 2 + 1][j & 3];
          s0 += bf_lo(u0) + bf_hi(u0); s1 += bf_lo(u1) + bf_hi(u1);
          q0 = fmaf(bf_lo(u0), bf_lo(u0), fmaf(bf_hi(u0), bf_hi(u0), q0)); q1 = fmaf(bf_lo(u1), bf_lo(u1), fmaf(bf_hi(u1), bf_hi(u1), q1));
        }
        const bool od = t & 1;
        float sa = od ? s1 : s0, qa = od ? q1 : q0;
        const float sb_ = __shfl_xor_sync(0xffffffffu, od ? s0 : s1, 1), qb_ = __shfl_xor_sync(0xffffffffu, od ? q0 : q1, 1);
        wgmma_fence();
        wgmma_n128_0(acc, D128(dA0 + XS * 1024), D128(dB0 + 9 * 1024));
#pragma unroll
        for (int k = 1; k < 4; ++k) wgmma_n128(acc, D128(dA0 + XS * 1024 + k * 2), D128(dB0 + 9 * 1024 + k * 128), 1);
        wgmma_commit();
        sa += sb_; qa += qb_;
        sa += __shfl_xor_sync(0xffffffffu, sa, 2);
        qa += __shfl_xor_sync(0xffffffffu, qa, 2);
        wgmma_fence();
#pragma unroll
        for (int k = 0; k < 4; ++k) wgmma_n128(acc, D128(dA0 + (XS + 1) * 1024 + k * 2), D128(dB0 + 10 * 1024 + k * 128), 1);
        wgmma_commit();
        red_add2_p(t < 2, reinterpret_cast<float*>(g_stats + (ep * 4 + layer) * S_ + m0 + wrow0 + gq + t * 8), sa, qa);
        __syncwarp();
        if (lane == 0) mbar_arrive(BA(B_XDONE));
        wgmma_wait<1>();
        if (elected) REL2(CM);
      }
      uint32_t s = 2;
#pragma unroll 1
      for (int i = 2; i < NF; ++i) {
        mbar_wait(BA(FM + i), par);
        const uint32_t da = dA0 + (XS + s) * 1024, dk = dB0 + s * 2048, dq = dB0 + (9 + s) * 1024;
        wgmma_fence();
#pragma unroll
        for (int k = 0; k < 4; ++k) wgmma_n128(acc, D128(da + k * 2), D128(dq + k * 128), 1);
        wgmma_commit();
        wgmma_wait<1>();
        if (elected) REL2(CM + i - 1);
        wgmma_fence();
#pragma unroll
        for (int k = 0; k < 4; ++k) wgmma_n256(acc, D128(da + k * 2), D128(dk + k * 128), 1);
        wgmma_commit();
        if (++s == 3) s = 0;
      }
#pragma unroll 1
      for (int i = NF; i < 15; ++i) {
        mbar_wait(BA(FM + i), par);
        const uint32_t da = dA0 + (XS + s) * 1024, dk = dB0 + s * 2048;
        wgmma_fence();
#pragma unroll
        for (int k = 0; k < 4; ++k) wgmma_n256(acc, D128(da + k * 2), D128(dk + k * 128), 1);
        wgmma_commit();
        wgmma_wait<1>();
        if (elected) REL2(CM + i - 1);
        if (++s == 3) s = 0;
      }
      {
        const uint64_t dap = desc64(((SB0 + SM_AP) >> 4) + wu * 64, 8), dbp = make_desc_ns(SB0 + SM_BP, 0, 128);
        mbar_wait(BA(B_STAT), par);
        mbar_wait(BA(FM + 15), par);
        PROFT(tid_ == 128, layer * 16 + 9);
        wgmma_fence();
        wgmma_n256_k(acc, dap, dbp, 1);
#pragma unroll
        for (int k = 0; k < 4; ++k) wgmma_n256(acc, D128(dA0 + XS * 1024 + k * 2), D128(dB0 + k * 128), 1);
        wgmma_commit();
        wgmma_wait<1>();
        if (elected) REL2(CM + 14);
        mbar_wait(BA(FT), par);
        wgmma_fence();
        wgmma_n128_k(acc, dap, dbp + 256, 1);
#pragma unroll
        for (int k = 0; k < 4; ++k) wgmma_n128(acc, D128(dA0 + (uint32_t)(TL_A & 15) * 1024 + k * 2), D128(dB0 + (uint32_t)(TL_B & 15) * 1024 + k * 128), 1);
        wgmma_commit();
        wgmma_wait<1>();
        if (elected) REL2(CM + 15);
#pragma unroll
        for (int i = 0; i < 128; ++i) asm volatile("" : "+f"(acc[i]) :: "memory");
      }
    }
    uint32_t of[8][4], o1[4][4];
    {
      PHASE_CTX();
      MMA_CTX();
      PROFT(tid_ == 128, layer * 16 + 1);
      PROFT(lane == 0 && layer == PL, 192 + cw);
      PROFT(tid_ == 128 && layer == PL, 160);
      uint64_t ta = (TL_A >> 4), tw = TL_B >> 4;
      uint32_t da, db, dz = dA0;
      auto sub = [&](int n) {
        const int j = n >> 2, k = n & 3;
        if (k == 0) {
          dz += c.zero;
          da = dz + ((uint32_t)ta & 15) * 1024; db = dB0 + ((uint32_t)tw & 15) * 1024;
          ta >>= 4; tw >>= 4;
          mbar_wait(BA(FT + j), par);
          wgmma_fence();
        }
        wgmma_n128(acc, D128(da + k * 2), D128(db + k * 128), 1);
        if (k == 3) {
          wgmma_commit();
          wgmma_wait<1>();
          if (elected) REL2(CT + j - 1);
        }
      };
      auto run = [&](int j0, int j1) {
#pragma unroll 1
        for (int j = j0; j < j1; ++j) {
          mbar_wait(BA(FT + j), par);
          da = dA0 + ((uint32_t)ta & 15) * 1024; db = dB0 + ((uint32_t)tw & 15) * 1024;
          ta >>= 4; tw >>= 4;
          wgmma_fence();
#pragma unroll
          for (int k = 0; k < 4; ++k) wgmma_n128(acc, D128(da + k * 2), D128(db + k * 128), 1);
          wgmma_commit();
          wgmma_wait<1>();
          if (elected) REL2(CT + j - 1);
        }
        ta = TL_A >> (4 * j1); tw = TL_B >> (4 * j1);
      };
      auto rest = [&](int j0) {
        run(j0, ND - NR);
        if (NR) mbar_wait(BA(FT + ND - NR), par);
#pragma unroll
        for (int j = ND - NR; j < ND; ++j) {
          if (j > ND - NR) mbar_wait(BA(FT + j), par);
          wgmma_fence();
#pragma unroll
          for (int k = 0; k < 4; ++k)
            wgmma_n64_lo(acc, D128(dA0 + (uint32_t)((TL_A >> (4 * j)) & 15) * 1024 + k * 2), D128(dB0 + (uint32_t)((TL_B >> (4 * j)) & 15) * 1024 + k * 128), 1);
          wgmma_commit();
          if (!DRAIN && j == ND - NR) {
            wgmma_wait<1>();
            if (elected) REL2(CT + j - 1);
          }
        }
        wgmma_wait<0>();
        if (!NR && elected) REL2(CT + ND - 1);
#pragma unroll
        for (int i = 128; i < 192; ++i) asm volatile("" : "+f"(acc[i]) :: "memory");
#pragma unroll
        for (int i = 160; i < 192; ++i) if (NR) acc[i] += __uint_as_float(c.zero);
      };
      auto rest_hi = [&]() {
        if (!NR) return;
        dz += c.zero;
        wgmma_fence();
#pragma unroll
        for (int j = ND - NR; j < ND; ++j)
#pragma unroll
          for (int k = 0; k < 4; ++k)
            wgmma_n64_hi(acc, D128(dz + (uint32_t)((TL_A >> (4 * j)) & 15) * 1024 + k * 2), D128(dB0 + (uint32_t)((TL_B >> (4 * j)) & 15) * 1024 + 512 + k * 128), 1);
        wgmma_commit();
      };
      auto rest_end = [&]() {
        if (!NR) return;
        wgmma_wait<0>();
        if (elected) {
#pragma unroll
          for (int j = ND - NR; j < ND; ++j) REL2(CT + j);
        }
#pragma unroll
        for (int i = 160; i < 192; ++i) asm volatile("" : "+f"(acc[i]) :: "memory");
      };
      const float rs0 = lds_f(sb + SM_RS + (16 + wrow0 + gq) * 4), rs1 = lds_f(sb + SM_RS + (24 + wrow0 + gq) * 4);
#define EPOCH() __float_as_uint(lds_f(sb + SM_EPOCH))
      mbar_wait(BA(CM + 14), par);
      if (par) {
        uint32_t kk[8][4], kp[8][4], vf[2][2][4][4];
        int sn = 4;
#pragma unroll
        for (int i = 0; i < 4 * BT1; ++i) sub(sn++);
        {
          uint32_t vv[8][4];
#pragma unroll
          for (int jp = 0; jp < 8; ++jp) {
            kk[jp][0] = pack_bf16(acc[8 * jp], acc[8 * jp + 1]); kk[jp][1] = pack_bf16(acc[8 * jp + 4], acc[8 * jp + 5]);
            kk[jp][2] = pack_bf16(acc[8 * jp + 2], acc[8 * jp + 3]); kk[jp][3] = pack_bf16(acc[8 * jp + 6], acc[8 * jp + 7]);
#pragma unroll
            for (int i = 0; i < 4; ++i) vv[jp][i] = pack_bf16(acc[64 + 8 * jp + 2 * i], acc[65 + 8 * jp + 2 * i]);
          }
          if (cw == 7) {
            uint32_t* const hbuf = g_halo + (size_t)(((layer >> 1) * 17 + rb + 1) * 8 + g) * 2048;
#pragma unroll
            for (int jp = 0; jp < 8; ++jp) stg128(hbuf + jp * 128 + lane * 4, kk[jp][0], kk[jp][1], kk[jp][2], kk[jp][3]);
#pragma unroll
            for (int i = 0; i < 32; ++i) hbuf[1024 + (i >> 4) * 512 + (gq + (i & 1) * 8) * 32 + ((((i >> 1) & 7) ^ gq) << 2) + t] = vv[i >> 2][i & 3];
            __syncwarp();
            if (lane == 0) mbar_arrive(BA(B_OF0));
          }
#pragma unroll
          for (int jp = 0; jp < 8; ++jp) {
            sub(sn++);
            stsm_x4(sb + PH + (jp >> 2) * SLOT + rowo + (X ^ ((jp & 3) << 5)), vv[jp][0], vv[jp][1], vv[jp][2], vv[jp][3]);
          }
        }
        PROFT(tid_ == 128, layer * 16 + 2);
        const int e = gq & 1;
        float f0[4], f1[4], b0[4], b1[4], rj[4];
#pragma unroll
        for (int nt = 0; nt < 4; ++nt) {
          const int kx = nt * 8 + 2 * t + e;
          const bool okk = (m0 + wrow0 + kx) >= 16;
          const int d0 = kx - gq, d1 = d0 - 8;
          rj[nt] = lds_f(sb + SM_RS + (wrow0 + kx) * 4);
          const bool m0_ = okk && d0 >= 2 && d0 <= 16, m1_ = okk && d1 >= 2 && d1 <= 16;
          f0[nt] = m0_ ? rj[nt] * rs0 * (0.17677669529663687f * L2E) : 0.f;
          f1[nt] = m1_ ? rj[nt] * rs1 * (0.17677669529663687f * L2E) : 0.f;
          b0[nt] = m0_ ? 0.f : -1e30f; b1[nt] = m1_ ? 0.f : -1e30f;
        }
#pragma unroll
        for (int jp = 0; jp < 8; ++jp) {
          sub(sn++);
          sts128(sb + VB + cw * 4096 + jp * 512 + lane * 16, make_uint4(kk[jp][0], kk[jp][1], kk[jp][2], kk[jp][3]));
        }
        __syncwarp();
#pragma unroll
        for (int i = 0; i < 8; ++i) {
          sub(sn++);
          ldsm_x4_t(vf[1][i & 1][i >> 1][0], vf[1][i & 1][i >> 1][1], vf[1][i & 1][i >> 1][2], vf[1][i & 1][i >> 1][3],
                    sb + PH + (i >> 2) * SLOT + rowo + (X ^ ((i & 3) << 5)));
        }
        nbar<1, 256>();
        PROFT(tid_ == 128, layer * 16 + 3);
        rest(sn >> 2);
        PROFT(lane == 0 && layer == PL, 200 + cw);
        PROFT(tid_ == 128, layer * 16 + 10);
        if (cw == 0) mbar_wait(BA(B_HALO), (layer >> 1) & 1);
        PROFT(tid_ == 128, layer * 16 + 5);
        const uint32_t vs = sb + (cw ? PH + rowo - 2048 : SM_SD + 4096 + rowo), vst = cw ? SLOT : 2048;
        const uint32_t psel = e ? 0x1054u : 0x5410u;
#pragma unroll
        for (int hp = 0; hp < 2; ++hp) {
#pragma unroll
          for (int i = 4 * hp; i < 4 * hp + 4; ++i) {
            const uint4 u = lds128(sb + (cw ? VB + (cw - 1) * 4096 : SM_SD) + lane * 16 + i * 512);
            kp[i][0] = u.x; kp[i][1] = u.y; kp[i][2] = u.z; kp[i][3] = u.w;
          }
#pragma unroll
          for (int i = 4 * hp; i < 4 * hp + 4; ++i)
            ldsm_x4_t(vf[0][i & 1][i >> 1][0], vf[0][i & 1][i >> 1][1], vf[0][i & 1][i >> 1][2], vf[0][i & 1][i >> 1][3], vs + (i >> 2) * vst + (X ^ ((i & 3) << 5)));
          if (hp) {
            rest_end();
          }
          float l0[2][4], l1[2][4];
#pragma unroll
          for (int h = 0; h < 2; ++h) {
            const int H = 2 * hp + h;
            uint32_t qa[8];
#pragma unroll
            for (int i = 0; i < 8; ++i) qa[i] = pack_bf16(acc[128 + 16 * H + 2 * i], acc[129 + 16 * H + 2 * i]);
#pragma unroll
            for (int nt = 3; nt >= 0; --nt) {
              float sc[4] = {0.f, 0.f, 0.f, 0.f};
#pragma unroll
              for (int ks = 0; ks < 2; ++ks) {
                const uint32_t (&kf)[4] = nt < 2 ? kp[2 * H + ks] : kk[2 * H + ks];
                mma_bf16(sc, qa[4 * ks], qa[4 * ks + 1], qa[4 * ks + 2], qa[4 * ks + 3], kf[2 * (nt & 1)], kf[2 * (nt & 1) + 1]);
              }
              l0[h][nt] = fmaf(e ? sc[1] : sc[0], f0[nt], b0[nt]);
              l1[h][nt] = fmaf(e ? sc[3] : sc[2], f1[nt], b1[nt]);
            }
          }
          float mx0[2], mx1[2], s0[2], s1[2];
#pragma unroll
          for (int h = 0; h < 2; ++h) {
            mx0[h] = fmaxf(fmaxf(l0[h][0], l0[h][1]), l0[h][2]);
            mx1[h] = fmaxf(fmaxf(l1[h][1], l1[h][2]), l1[h][3]);
          }
#pragma unroll
          for (int o = 1; o <= 2; o <<= 1)
#pragma unroll
            for (int h = 0; h < 2; ++h) {
              mx0[h] = fmaxf(mx0[h], __shfl_xor_sync(0xffffffffu, mx0[h], o));
              mx1[h] = fmaxf(mx1[h], __shfl_xor_sync(0xffffffffu, mx1[h], o));
            }
#pragma unroll
          for (int h = 0; h < 2; ++h) {
#pragma unroll
            for (int nt = 0; nt < 3; ++nt) { l0[h][nt] = ex2(l0[h][nt] - mx0[h]); l1[h][nt + 1] = ex2(l1[h][nt + 1] - mx1[h]); }
            s0[h] = (l0[h][0] + l0[h][1]) + l0[h][2];
            s1[h] = (l1[h][1] + l1[h][2]) + l1[h][3];
          }
#pragma unroll
          for (int o = 1; o <= 2; o <<= 1)
#pragma unroll
            for (int h = 0; h < 2; ++h) {
              s0[h] += __shfl_xor_sync(0xffffffffu, s0[h], o);
              s1[h] += __shfl_xor_sync(0xffffffffu, s1[h], o);
            }
          uint32_t ow[2][2][4];
#pragma unroll
          for (int h = 0; h < 2; ++h) {
            const int H = 2 * hp + h;
            uint32_t pl[4], ph[4];
            const float i0 = rcp(s0[h]), i1 = rcp(s1[h]);
#pragma unroll
            for (int nt = 0; nt < 4; ++nt) {
              const uint32_t pk = pack_bf16(nt < 3 ? l0[h][nt] * i0 * rj[nt] : 0.f, nt > 0 ? l1[h][nt] * i1 * rj[nt] : 0.f);
              pl[nt] = nt < 3 ? __byte_perm(pk, 0u, psel) : 0u;
              ph[nt] = nt > 0 ? __byte_perm(pk, 0u, psel + 0x2222u) : 0u;
            }
#pragma unroll
            for (int nj = 0; nj < 4; ++nj) {
              float oa[4] = {0.f, 0.f, 0.f, 0.f};
#pragma unroll
              for (int ks = 0; ks < 2; ++ks)
                mma_bf16(oa, pl[2 * ks], ph[2 * ks], pl[2 * ks + 1], ph[2 * ks + 1], vf[ks][nj >> 1][H][2 * (nj & 1)], vf[ks][nj >> 1][H][2 * (nj & 1) + 1]);
              ow[h][0][nj] = pack_bf16(oa[0], oa[1]); ow[h][1][nj] = pack_bf16(oa[2], oa[3]);
            }
          }
          if (hp == 0) {
#pragma unroll
            for (int i = 0; i < 4; ++i) stg128(g_o + gfr + (i & 1) * 8 * D_ + (i >> 1) * 32, ow[i >> 1][i & 1][0], ow[i >> 1][i & 1][1], ow[i >> 1][i & 1][2], ow[i >> 1][i & 1][3]);
            __syncwarp();
            if (lane == 0) mbar_arrive(BA(B_OH0));
            rest_hi();
          } else {
#pragma unroll
            for (int i = 0; i < 16; ++i) o1[i >> 2][i & 3] = ow[i >> 3][(i >> 2) & 1][i & 3];
          }
#pragma unroll
          for (int i = 0; i < 16; ++i) of[4 * hp + (i >> 2)][i & 3] = ow[i >> 3][i & 1][(i >> 1) & 3];
          if (!hp) PROFT(tid_ == 128, layer * 16 + 15);
        }
      } else {
        float sc[2] = {rs0 * L2E, rs1 * L2E};
        {
          const uint32_t vb = sb + VB + (rowo >> 1), X0 = (lchk ^ ((lane & 7) >> 1)) << 4;
          const uint32_t pb = sb + PH + (t & 1) * SLOT + (wrow0 + gq) * 128 + ((((t & 1) * 4 + (t & 2)) ^ gq) << 4);
          float kva[20], en[32], mx[2][2], mn[2][2];
#define PV(hp, j) acc[32 * (hp) + (j)]
          auto mm = [&](int hp, int j) {
            const int r = (j >> 1) & 1;
            if (j < 4 && !(j & 1)) { mx[hp][r] = PV(hp, j); mn[hp][r] = PV(hp, j); }
            else { mx[hp][r] = fmaxf(mx[hp][r], PV(hp, j)); mn[hp][r] = fminf(mn[hp][r], PV(hp, j)); }
          };
          auto mmx = [&](int hp) {
#pragma unroll
            for (int r = 0; r < 2; ++r) {
              mx[hp][r] = fmaxf(mx[hp][r], __shfl_xor_sync(0xffffffffu, mx[hp][r], 2)) * -sc[r];
              mn[hp][r] = fmaf(fminf(mn[hp][r], __shfl_xor_sync(0xffffffffu, mn[hp][r], 2)), sc[r], mx[hp][r]);
            }
          };
          auto stage = [&](int hp) {
#pragma unroll
            for (int i = 0; i < 20; ++i) asm volatile("" : "+f"(kva[i]) :: "memory");
            nbar_dyn(3 + wu, 128);
#pragma unroll
            for (int i = 0; i < 4; ++i)
              sts128(sb + VB + hp * SLOT + wg * 8192 + (wq * 128 + i * 32 + lane) * 16,
                     make_uint4(__float_as_uint(kva[4 * i]), __float_as_uint(kva[4 * i + 1]), __float_as_uint(kva[4 * i + 2]), __float_as_uint(kva[4 * i + 3])));
            if (t == 0) sts_f2(sb + SM_AP + ((2 * hp + wg) * 64 + wq * 16 + gq * 2) * 4, kva[16], kva[18]);
            fence_async_smem();
            __syncwarp();
            if (lane == 0) mbar_arrive(BA(B_KVDONE));
          };
          int sn = 4;
#pragma unroll
          for (int j = 0; j < 32; ++j) mm(0, j);
          mmx(0);
#pragma unroll
          for (int hp = 0; hp < 2; ++hp) {
            float sp[2] = {0.f, 0.f}, sm[2] = {0.f, 0.f};
#pragma unroll
            for (int j = 0; j < 32; ++j) {
              const int r = (j >> 1) & 1, ns = hp ? SUBS1 : SUBS;
              if ((j * ns) / 32 != ((j + 1) * ns) / 32) {
                sub(sn++);
                if (hp && sn == 4 + SUBS + 4) { stage(0); PROFT(tid_ == 128, layer * 16 + 12); }
              }
              const float x = fmaf(PV(hp, j), sc[r], mx[hp][r]);
              PV(hp, j) = ex2(x); en[j] = ex2(mn[hp][r] - x);
              sp[r] += PV(hp, j); sm[r] += en[j];
              if (hp == 0) {
                mm(1, j);
                if ((j & 3) == 0) {
                  const int jp = 8 + (j >> 2);
                  stsm_x4(vb + ((jp - 8) >> 1) * 8192 + (X0 ^ ((jp & 1) << 5)), pack_bf16(acc[8 * jp], acc[8 * jp + 1]), pack_bf16(acc[8 * jp + 2], acc[8 * jp + 3]),
                          pack_bf16(acc[8 * jp + 4], acc[8 * jp + 5]), pack_bf16(acc[8 * jp + 6], acc[8 * jp + 7]));
                }
              }
            }
#pragma unroll
            for (int r = 0; r < 2; ++r) {
              sp[r] = rcp(sp[r] + __shfl_xor_sync(0xffffffffu, sp[r], 2)) * (r ? rs1 : rs0);
              sm[r] = rcp(sm[r] + __shfl_xor_sync(0xffffffffu, sm[r], 2)) * (r ? rs1 : rs0);
            }
            if (hp == 0) mmx(1);
            else { PROFT(tid_ == 128, layer * 16 + 11); nbar<1, 256>(); }
#pragma unroll
            for (int i = 0; i < 4; ++i) {
              const int r = i & 1, d = 16 * (i >> 1) + 2 * r;
              sts128((pb + r * 1024) ^ ((i >> 1) << 4), make_uint4(pack_bf16(PV(hp, d) * sp[r], PV(hp, d + 1) * sp[r]), pack_bf16(PV(hp, d + 4) * sp[r], PV(hp, d + 5) * sp[r]),
                                                                    pack_bf16(PV(hp, d + 8) * sp[r], PV(hp, d + 9) * sp[r]), pack_bf16(PV(hp, d + 12) * sp[r], PV(hp, d + 13) * sp[r])));
              sts128((pb + r * 1024) ^ ((i >> 1) << 4) ^ 64, make_uint4(pack_bf16(en[d] * sm[r], en[d + 1] * sm[r]), pack_bf16(en[d + 4] * sm[r], en[d + 5] * sm[r]),
                                                                         pack_bf16(en[d + 8] * sm[r], en[d + 9] * sm[r]), pack_bf16(en[d + 12] * sm[r], en[d + 13] * sm[r])));
            }
            fence_async_smem();
            nbar<1, 256>();
            const uint32_t dP = dB0 + (PH >> 4) + wu * 1024;
            const uint32_t dV = (dB0 & 0xFFFFu) + ((VB + hp * SLOT) >> 4) + (((SM_SD - VB - hp * SLOT) >> 4) << 16) + wu * (512u - (512u << 16));
            wgmma_fence();
#pragma unroll
            for (int ks = 0; ks < 8; ++ks) wgmma_n40_tt(kva, D128(dP + ks * 128), desc64(dV + ks * 64, 0x80000020u), ks != 0);
            wgmma_commit();
          }
#pragma unroll
          for (int i = 0; i < 4; ++i) sub(sn++);
          stage(1);
          PROFT(tid_ == 128, layer * 16 + 3);
          rest(sn >> 2);
          PROFT(lane == 0 && layer == PL, 200 + cw);
          PROFT(tid_ == 128, layer * 16 + 10);
        }
#define QV(H, i) acc[128 + 16 * (H) + (i)]
        float mx[4][2], mn[4][2];
        uint32_t ph[4][4][4];
        auto mnx = [&](int hp) {
#pragma unroll
          for (int H = 2 * hp; H < 2 * hp + 2; ++H)
#pragma unroll
            for (int r = 0; r < 2; ++r) {
              mx[H][r] = fmaxf(fmaxf(fmaxf(QV(H, 2 * r), QV(H, 2 * r + 1)), fmaxf(QV(H, 4 + 2 * r), QV(H, 5 + 2 * r))),
                               fmaxf(fmaxf(QV(H, 8 + 2 * r), QV(H, 9 + 2 * r)), fmaxf(QV(H, 12 + 2 * r), QV(H, 13 + 2 * r))));
              mn[H][r] = fminf(fminf(fminf(QV(H, 2 * r), QV(H, 2 * r + 1)), fminf(QV(H, 4 + 2 * r), QV(H, 5 + 2 * r))),
                               fminf(fminf(QV(H, 8 + 2 * r), QV(H, 9 + 2 * r)), fminf(QV(H, 12 + 2 * r), QV(H, 13 + 2 * r))));
            }
#pragma unroll
          for (int o = 1; o <= 2; o <<= 1)
#pragma unroll
            for (int H = 2 * hp; H < 2 * hp + 2; ++H)
#pragma unroll
              for (int r = 0; r < 2; ++r) {
                mx[H][r] = fmaxf(mx[H][r], __shfl_xor_sync(0xffffffffu, mx[H][r], o));
                mn[H][r] = fminf(mn[H][r], __shfl_xor_sync(0xffffffffu, mn[H][r], o));
              }
#pragma unroll
          for (int H = 2 * hp; H < 2 * hp + 2; ++H)
#pragma unroll
            for (int r = 0; r < 2; ++r) { mx[H][r] *= -sc[r]; mn[H][r] = fmaf(mn[H][r], sc[r], mx[H][r]); }
        };
        auto fm = [&](int H) {
#pragma unroll
          for (int i = 0; i < 8; ++i) {
            const int r = i & 1;
            const float x0 = fmaf(QV(H, 2 * i), sc[r], mx[H][r]), x1 = fmaf(QV(H, 2 * i + 1), sc[r], mx[H][r]);
            ph[H][i >> 2][i & 3] = pack_bf16(ex2(x0), ex2(x1));
            ph[H][2 + (i >> 2)][i & 3] = pack_bf16(ex2(mn[H][r] - x0), ex2(mn[H][r] - x1));
          }
        };
        auto conv = [&](int hp) {
          mbar_wait(BA(hp ? B_KVF1 : B_KVF), (layer >> 1) & 1);
          PROFT(tid_ == 128, layer * 16 + (hp ? 4 : 5));
          uint4 u[4];
#pragma unroll
          for (int i = 0; i < 4; ++i) u[i] = lds128(sb + VB + hp * SLOT + wg * 8192 + (wq * 128 + i * 32 + lane) * 16);
          const float zz = lds_f(sb + SM_AP + ((2 * hp + wg) * 64 + wq * 16 + (lane & 7) * 2 + ((lane >> 3) & 1)) * 4);
          const uint32_t kb_ = sb + PH + wg * SLOT + hp * 8192 + (wq * 16 + lrow) * 128;
#pragma unroll
          for (int i = 0; i < 4; i += 2)
            stsm_x4(kb_ + (X ^ (i << 4)),
                    pack_bf16(__uint_as_float(u[i].x), __uint_as_float(u[i].y)), pack_bf16(__uint_as_float(u[i].z), __uint_as_float(u[i].w)),
                    pack_bf16(__uint_as_float(u[i + 1].x), __uint_as_float(u[i + 1].y)), pack_bf16(__uint_as_float(u[i + 1].z), __uint_as_float(u[i + 1].w)));
          const uint32_t z1 = pack_bf16(zz, 1.f);
          if (lane < 16) sts128(kb_ + ((4 ^ (lane & 7)) << 4), make_uint4(z1, z1, z1, z1));
          fence_async_smem();
        };
        mnx(0);
        rest_hi();
        fm(0); fm(1);
        rest_end();
        conv(0);
#pragma unroll
        for (int hp = 0; hp < 2; ++hp) {
          nbar<1, 256>();
          float oa[4][20];
          wgmma_fence();
#pragma unroll
          for (int s = 0; s < 2; ++s)
#pragma unroll
            for (int v = 0; v < 4; ++v) {
              const int h = v >> 1, s4 = 2 * (v & 1) + s;
              wgmma_n40_rs(oa[v], ph[2 * hp + h][s4], D128(dB0 + (PH >> 4) + h * 1024 + hp * 512 + (s4 ^ (2 * h)) * 128), s != 0);
            }
          wgmma_commit();
          if (hp == 0) mnx(1);
          wgmma_wait<0>();
#pragma unroll
          for (int i = 0; i < 20; ++i) asm volatile("" : "+f"(oa[0][i]), "+f"(oa[1][i]), "+f"(oa[2][i]), "+f"(oa[3][i]) :: "memory");
          uint32_t ow[2][2][4];
#pragma unroll
          for (int h = 0; h < 2; ++h)
#pragma unroll
            for (int r = 0; r < 2; ++r) {
              const float a = rcp(oa[2 * h][17 + 2 * r]), b = rcp(oa[2 * h + 1][17 + 2 * r]);
              const float id = __fdividef(1.f, fmaf(oa[2 * h][16 + 2 * r], a, fmaf(oa[2 * h + 1][16 + 2 * r], b, 1e-6f)));
              const float fa = a * id, fb = b * id;
#pragma unroll
              for (int j = 0; j < 4; ++j)
                ow[h][r][j] = pack_bf16(fmaf(oa[2 * h][4 * j + 2 * r], fa, oa[2 * h + 1][4 * j + 2 * r] * fb),
                                        fmaf(oa[2 * h][4 * j + 2 * r + 1], fa, oa[2 * h + 1][4 * j + 2 * r + 1] * fb));
            }
          if (hp == 0) {
#pragma unroll
            for (int i = 0; i < 4; ++i) stg128(g_o + gfr + (i & 1) * 8 * D_ + (i >> 1) * 32, ow[i >> 1][i & 1][0], ow[i >> 1][i & 1][1], ow[i >> 1][i & 1][2], ow[i >> 1][i & 1][3]);
            __syncwarp();
            if (lane == 0) mbar_arrive(BA(B_OH0));
          } else {
#pragma unroll
            for (int i = 0; i < 16; ++i) o1[i >> 2][i & 3] = ow[i >> 3][(i >> 2) & 1][i & 3];
          }
#pragma unroll
          for (int i = 0; i < 16; ++i) of[4 * hp + (i >> 2)][i & 3] = ow[i >> 3][i & 1][(i >> 1) & 3];
          if (hp == 0) {
            PROFT(tid_ == 128 && layer, layer * 16 + 15);
            if (QORD) {
              uint32_t zc; asm volatile("mov.u32 %0, %%clock;" : "=r"(zc) :: "memory");
              sc[0] += __uint_as_float(zc & c.zero); sc[1] += __uint_as_float(zc & c.zero);
            }
            fm(2);
            conv(1);
            fm(3);
          }
        }
      }
      PROFT(tid_ == 128, layer * 16 + 6);
    }
    {
      PHASE_CTX();
      MMA_CTX();
#pragma unroll
      for (int i = 0; i < 4; ++i) stg128(g_o + gfr + (i & 1) * 8 * D_ + (2 + (i >> 1)) * 32, o1[i][0], o1[i][1], o1[i][2], o1[i][3]);
      __syncwarp();
      if (lane == 0) { mbar_arrive(BA(B_OH1)); REL2(B_EF); }
      PROFT(lane == 0 && layer == PL, 208 + cw);
#pragma unroll
      for (int i = 0; i < 2; ++i) {
        mbar_wait(BA(FW + i), par);
        wgmma_fence();
#pragma unroll
        for (int k = 0; k < 4; ++k) {
          if (i + k) wgmma_n128_rs(acc, of[4 * i + k], D128(dB0 + (uint32_t)((WO_B >> (4 * i)) & 15) * 1024 + k * 128), 1);
          else wgmma_n128_rs0(acc, of[0], D128(dB0 + (uint32_t)(WO_B & 15) * 1024));
        }
        wgmma_commit();
      }
      wgmma_wait<1>();
      if (elected) REL2(CW);
      uint64_t ta = WO_A >> 8, tw = WO_B >> 8;
      auto run = [&](int i0, int i1) {
#pragma unroll 1
        for (int i = i0; i < i1; ++i) {
          mbar_wait(BA(FW + i), par);
          PROFL(tid_ == 128 && layer == PL, 160 + i);
          const uint32_t da = dA0 + ((uint32_t)ta & 15) * 1024, db = dB0 + ((uint32_t)tw & 15) * 1024;
          ta >>= 4; tw >>= 4;
          wgmma_fence();
#pragma unroll
          for (int k = 0; k < 4; ++k) wgmma_n128(acc, D128(da + k * 2), D128(db + k * 128), 1);
          wgmma_commit();
          wgmma_wait<1>();
          if (elected) REL2(CW + i - 1);
        }
      };
      run(2, XRAT);
#pragma unroll
      for (int j = 0; j < 8 / XRN; ++j) {
#pragma unroll
        for (int i = j * XRN; i < (j + 1) * XRN; ++i) ldg128(g_x + gfr + (i & 1) * 8 * D_ + (i >> 1) * 32, xp[i][0], xp[i][1], xp[i][2], xp[i][3]);
        run(XRAT + j, j + 1 < 8 / XRN ? XRAT + j + 1 : 16);
      }
      wgmma_wait<0>();
#pragma unroll
      for (int i = 128; i < 192; ++i) asm volatile("" : "+f"(acc[i]) :: "memory");
      if (elected) REL2(CW + 15);
      PROFT(lane == 0 && layer == PL, 216 + cw);
      PROFT(tid_ == 128, layer * 16 + 7);
    }
    {
      PHASE_CTX();
#pragma unroll
      for (int i = 0; i < 32; ++i)
        xp[i >> 2][i & 3] = add_bf16x2(xp[i >> 2][i & 3], pack_bf16(acc[128 + 16 * (i >> 3) + 4 * (i & 3) + 2 * ((i >> 2) & 1)], acc[129 + 16 * (i >> 3) + 4 * (i & 3) + 2 * ((i >> 2) & 1)]));
#pragma unroll
      for (int i = 0; i < 8; ++i) stsm_x4(sb + (XS + (i >> 2)) * SLOT + (Y ^ ((i & 2) << 5)) + (i & 1) * 1024, xp[i][0], xp[i][1], xp[i][2], xp[i][3]);
      if (layer == NLAYERS - 1) {
        __syncwarp();
        slab_out_half(sb + XS * SLOT, c.out + (size_t)m0 * D_ + g * 128, wrow0, lane);
        slab_out_half(sb + (XS + 1) * SLOT, c.out + (size_t)m0 * D_ + g * 128 + 64, wrow0, lane);
        PROFT(tid_ == 128, layer * 16 + 24);
        break;
      }
      fence_async_smem();
#pragma unroll
      for (int i = 0; i < 4; ++i) stg128(g_x + gfr + (i & 1) * 8 * D_ + (i >> 1) * 32, xp[i][0], xp[i][1], xp[i][2], xp[i][3]);
      __syncwarp();
      if (lane == 0) mbar_arrive(BA(B_XH0));
      PROFT(tid_ == 128, layer * 16 + 24);
      nbar_dyn(3 + wg, 128);
    }
  }
}

__device__ __forceinline__ uint64_t k_order(int o) {
  const uint32_t lo = (1u << (4 * o)) - 1u, h0 = (0xECA86420u & lo) | ((0xECA86420u >> 4) & ~lo);
  return (uint64_t)(2 * o) | ((uint64_t)(2 * o + 1) << 4) | ((uint64_t)(h0 & 0xFFFFFFFu) << 8) | ((uint64_t)((h0 & 0xFFFFFFFu) | 0x1111111u) << 36);
}

__global__ void __cluster_dims__(2, 1, 1) __launch_bounds__(384, 1)
mega_kernel(const __grid_constant__ Maps maps, const __grid_constant__ Ctx c, const bf16* __restrict__ wA, const bf16* __restrict__ wB,
            const bf16* __restrict__ woA, const bf16* __restrict__ woB) {
  if (blockIdx.x - c.boff >= 128u) {
    const unsigned int epoch = ld_relaxed(&g_epoch);
    const int e = (blockIdx.x - c.boff) & 3, tid = threadIdx.x;
    float s[8] = {0.f, 0.f, 0.f, 0.f, 0.f, 0.f, 0.f, 0.f};
    const uint32_t sb = smem_u32(smem_raw), bar = sb + SM_BAR;
    auto issue = [&](int i) {
      mbar_expect_tx(BA(i & 3), 49152);
      bulk_load(sb + (i & 3) * 49152, wB + (size_t)e * 256 * 3072 + i * 24576, 49152, BA(i & 3));
    };
    if (tid == 0) {
#pragma unroll 1
      for (int i = 0; i < 4; ++i) {
        mbar_init(BA(i), 1);
        fence_async_smem();
        issue(i);
      }
    }
    __syncthreads();
#pragma unroll 1
    for (int i = 0; i < 32; ++i) {
      mbar_wait(BA(i & 3), (i >> 2) & 1);
#pragma unroll
      for (int r = 0; r < 8; ++r) {
        const uint4 v = lds128(sb + (i & 3) * 49152 + r * 6144 + tid * 16);
        s[0] += bf_lo(v.x); s[1] += bf_hi(v.x); s[2] += bf_lo(v.y); s[3] += bf_hi(v.y);
        s[4] += bf_lo(v.z); s[5] += bf_hi(v.z); s[6] += bf_lo(v.w); s[7] += bf_hi(v.w);
      }
      __syncthreads();
      if (tid == 0 && i < 28) issue(i + 4);
    }
    float* cd = g_cs + (epoch & 1) * 6144 + 3072 + ((tid >> 4) & 7) * 384 + (tid < 128 ? 256 : (tid >> 7) * 128 - 128) + (tid & 15) * 8;
    red_add4(cd, s[0], s[1], s[2], s[3]);
    red_add4(cd + 4, s[4], s[5], s[6], s[7]);
    __syncthreads();
    if (tid == 0) flag_add(&g_csflag[8].v);
    const int op = (epoch & 1) ^ 1;
    float4* kz = reinterpret_cast<float4*>(g_kv + (size_t)op * (2 * 8 * 8448)) + e * 8448;
#pragma unroll 2
    for (int i = tid; i < 8448; i += 384) kz[i] = make_float4(0.f, 0.f, 0.f, 0.f);
    reinterpret_cast<float4*>(g_cs + op * 6144)[e * 384 + tid] = make_float4(0.f, 0.f, 0.f, 0.f);
#pragma unroll 1
    for (int i = tid; i < 1024; i += 384) reinterpret_cast<float4*>(g_stats + (op * 4 + e) * S_)[i] = make_float4(0.f, 0.f, 0.f, 0.f);
    return;
  }
  const int warp = __shfl_sync(0xffffffffu, threadIdx.x >> 5, 0), lane = threadIdx.x & 31;
  if (smem_u32(smem_raw) != SB0 + ((blockIdx.x & 1) << 24)) __trap();
  {
  const int cid = (blockIdx.x - c.boff) >> 1, u7 = ((cid - 36) * 37) >> 8, cr = blockIdx.x & 1;
  const int g = cid < 4 ? 4 + cid : cid < 36 ? (cid - 4) >> 3 : 4 + u7, rb = (cid < 4 ? 0 : cid < 36 ? (cid - 4) & 7 : cid - 35 - 7 * u7) * 2 + cr, m0 = rb * 128;
  const uint32_t sb = SB0 + (cr << 24), bar = sb + SM_BAR;
  PROFT(lane == 0 && (warp == 0 || warp == 4), 224 + (warp >> 2) * 8);
  uint32_t cx = 0;
  if (warp == 2) {
    if (lane < NMAP) asm volatile("prefetch.tensormap [%0];" ::"l"(&maps.m[lane]) : "memory");
    if (lane == 31) asm volatile("prefetch.global.L2 [%0];" ::"l"(&g_epoch));
  } else if (warp == 3) {
    cx = c_map[cid] + c_wop[lane] + c_wop[NWOP - lane] + c_aop[lane] + c_aop[NAOP - lane] + (uint32_t)(uintptr_t)g_x;
  } else if (PFW && warp >= 4) {
    const int i = threadIdx.x - 128;
    asm volatile("prefetch.global.L2 [%0];" ::"l"(wA + (size_t)(rb * 64 + ((i >> 1) & 63)) * 3072 + (i >> 7) * 1024 + g * 128 + (i & 1) * 64));
  }
  if (warp < 2) {
    const int s = cr ^ warp, kb = (rb & ~1) + s;
    if (lane == 0) {
      mbar_init(BA(FM + s), 1u);
      mbar_init(BA(B_RAW + warp), 1u);
      asm volatile("fence.mbarrier_init.release.cluster;" ::: "memory");
    }
    __syncwarp();
    if (warp == 0) tma_2d_e(sb + SM_SD, &maps.m[MAP_PHI], 0, g * 128, BA(B_RAW));
#pragma unroll
    for (int j = 0; j < 6; ++j)
      tma_5d_e(sb + (j < 2 ? 2 * s : j < 4 ? 9 + s : 2 * s + 1) * SLOT + (j & 1) * 8192, &maps.m[MAP_WA], (j < 2 ? 1024 : j < 4 ? 0 : 2048) + g * 128 + (j & 1) * 64, 2 * kb,
               BA(j < 4 ? B_RAW + warp : FM + s));
    tma_2d_e(sb + (XS + s) * SLOT, &maps.m[MAP_X0], kb * 64, m0, BA(FM + s));
    expect_tx_e(BA(B_RAW + warp), warp ? 32768 : 32768 + 8192);
    expect_tx_e(BA(FM + s), 32768);
  } else if (warp >= 4 && lane == 0) {
#pragma unroll 1
    for (int i = 2 + (warp - 4) * 13; i < 15 + (warp - 4) * 13; ++i)
      mbar_init(BA(i), 1u << ((i < CM ? 0u : i < B_EF ? 2u : (uint32_t)(BAR_LG >> (4 * ((i - B_EF) & 15)))) & 7u));
    asm volatile("fence.mbarrier_init.release.cluster;" ::: "memory");
  }
  __syncwarp();
  asm volatile("barrier.cluster.arrive.relaxed.aligned;" ::: "memory");
  if (threadIdx.x == 96 + c.zero) sts_f(sb + SM_EPOCH + 4, __uint_as_float(cx));
  PROFT(lane == 0 && (warp == 0 || warp == 4), 225 + (warp >> 2) * 8);
  __syncwarp();
  PROFT(lane == 0 && (warp == 0 || warp == 4), 226 + (warp >> 2) * 8);
  }

  if (warp < 4) {
    asm volatile("setmaxnreg.dec.sync.aligned.u32 40;");
    PROFT(threadIdx.x == 0, 227);
    cluster_wait();
    PROFT(threadIdx.x == 0, 228);
    if (warp == 0 || warp == 3) {
    if (warp == 0) {
      BLK_CTX();
      const unsigned int epoch = __shfl_sync(0xffffffffu, ld_relaxed(&g_epoch), 0), xbase = epoch * NLAYERS;
      (void)xbase;
      const uint64_t ordg = k_order(g);
      mbar_wait_u(BA(B_RAW), 0);
      tma_2d_e(sb + 11 * SLOT, &maps.m[MAP_X0], g * 128, m0, BA(B_X0));
      tma_2d_e(sb + 12 * SLOT, &maps.m[MAP_X0], g * 128 + 64, m0, BA(B_X0));
      expect_tx_e(BA(B_X0), 32768);
#pragma unroll 1
      for (int lp = 0; lp < 2 * NLAYERS; ++lp) {
        const int layer = lp >> 1, n1 = (lp & 1) ? NAOP : NAOP - 14;
        int n = (lp & 1) ? NAOP - 14 : 0;
        const uint64_t ord = lp ? ordg : k_order(rb >> 1);
        uint32_t ready = lp ? 0u : 0xFFFFu, nop = c_aop[n];
        const unsigned int* fl = ((lp & 1) ? g_of : g_xf) + rb * 32;
        const CUtensorMap* tm = &maps.m[(lp & 1) ? MAP_O : lp ? MAP_X : MAP_X0];
        const uint32_t skip = layer ? 1u << 25 : 9u << 22;
#pragma unroll 1
        for (; n < n1; ++n) {
          const uint32_t op = nop;
          nop = c_aop[n + 1];
          const uint32_t kb = (uint32_t)(ord >> ((op >> 2) & 60)) & 15;
          if (!((ready >> kb) & 1)) {
            PROFT(lane == 0 && (n == 0 || n == NAOP - 14), 64 + layer * 16 + (n ? 2 : 0));
            src_wait<0>(fl, xbase + layer + 1, 1u << kb, ready, lane);
            fence_async_all();
            PROFT(lane == 0 && (n == 0 || n == NAOP - 14), 64 + layer * 16 + (n ? 3 : 1));
          }
          wait_tma_2d(!(op & skip), bar + ((op >> 12) & 0x3F8), (layer ^ (op >> 22)) & 1, sb + (op & 15) * SLOT, tm, kb * 64, m0, bar + ((op >> 5) & 0x3F8));
          PROFL(lane == 0 && layer == PL && n >= NAOP - 14, 178 + n - (NAOP - 14));
        }
      }
    } else {
      BLK_CTX();
      const unsigned int epoch = __shfl_sync(0xffffffffu, ld_relaxed(&g_epoch), 0), xbase = epoch * NLAYERS;
      (void)xbase;
      const uint64_t ordg = k_order(g);
#pragma unroll 1
      for (int layer = 0; layer < NLAYERS; ++layer) {
        const uint64_t ordq = layer ? ordg : k_order(rb >> 1);
        uint32_t ready = layer ? 0xFFFFu : 0u, nop = c_wop[0];
        const CUtensorMap* tq = &maps.m[(layer & 1) ? MAP_WB : MAP_WF];
        const CUtensorMap* tk = &maps.m[(layer & 1) ? MAP_WB : cr ? MAP_WA : MAP_WF];
        const uint32_t skip = layer ? 1u << 25 : 9u << 22, pm = layer ? 0xE0u : 0u;
        int n = 0;
#pragma unroll 1
        for (; n < NWOP - 16; ++n) {
          const uint32_t op = nop;
          nop = c_wop[n + 1];
          const uint32_t isq = (op >> 23) & 1, fb = bar + ((op >> 5) & 0x3F8);
          const uint32_t kb = (uint32_t)(ordq >> ((op >> 2) & 60)) & 15;
          const CUtensorMap* tm = (isq ? tq : tk) + ((op & pm) ? 1 : 0);
          const uint32_t dst = sb + (op & 15) * SLOT + cr * (isq ? 8192 : SLOT);
          const int col = g * 128 + (isq ? cr * 64 : 1024 + cr * 1024);
          if (layer == 0) {
            if ((op & 0x7E00) == 0) continue;
            const uint32_t need = ((isq || !cr) ? 1u << kb : 0u) | (((op >> 22) & 1) ? 0u : 3u << (rb & ~1));
            if ((ready & need) != need) {
              src_wait<0>(g_wff + g * 32, epoch + 1, need, ready, lane);
              fence_async_all();
            }
            if ((op & 15) >= 11) mbar_wait_u(BA(B_XT), 0);
          }
          wait_tma_5d_mc(!(op & skip), bar + ((op >> 12) & 0x3F8), (layer ^ (op >> 22)) & 1, dst, tm, col, 2 * kb, fb);
          if (!isq) tma_5d_mc_e(dst + 8192, tm, col + 64, 2 * kb, fb);
          if (op >> 26) expect_tx_e(fb, (op >> 26) * 8192);
        }
        const CUtensorMap* to = &maps.m[(layer & 1) ? MAP_WOB : MAP_WOA];
#pragma unroll 1
        for (; n < NWOP; ++n) {
          const uint32_t op = nop;
          nop = c_wop[n + 1];
          const uint32_t fb = bar + ((op >> 5) & 0x3F8), kb = (uint32_t)(ordg >> ((op >> 2) & 60)) & 15;
          wait_tma_5d_mc(!((op >> 25) & 1), bar + ((op >> 12) & 0x3F8), layer & 1, sb + (op & 15) * SLOT + cr * 8192, to + ((op & 0xE0) ? 1 : 0), g * 128 + cr * 64, 2 * kb, fb);
          expect_tx_e(fb, (op >> 26) * 8192);
          PROFL(lane == 0 && layer == PL, 144 + ((op >> 8) & 127) - FW);
        }
      }
    }
    } else if (warp == 1) {
      BLK_CTX();
      const unsigned int epoch = __shfl_sync(0xffffffffu, ld_relaxed(&g_epoch), 0), xbase = epoch * NLAYERS;
      (void)xbase;
      if (lane == 0) {
        mbar_wait(BA(B_WFD), 0);
#pragma unroll 1
        for (int j = 0; j < 4; ++j) tma_store_5d(&maps.m[MAP_WF], sb + (j < 2 ? 2 * cr : 9 + cr) * SLOT + (j & 1) * 8192, (j < 2 ? 1024 : 0) + g * 128 + (j & 1) * 64, 2 * rb);
        bulk_commit();
        bulk_wait0();
        fence_async_all();
        flag_set(g_wff + g * 32 + rb, epoch + 1);
        PROFT(true, 64 + 13);
#pragma unroll 1
        for (int e = 0; e < NLAYERS; ++e) {
          if (e > 0) {
            mbar_wait(BA(B_XH0), (e - 1) & 1);
            flag_set(g_xf + rb * 32 + 2 * g, xbase + e + 1);
          }
          mbar_wait(BA(B_XDONE), e & 1);
          PROFT(true, 64 + e * 16 + 4);
          flag_set(g_xf + rb * 32 + 2 * g + 1, xbase + e + 1);
          if (e == 0) {
            flag_add(&g_csflag[g].v);
            l2_prefetch(wB + (size_t)bid_ * 24576, 49152);
            l2_prefetch(woA + (size_t)bid_ * 8192, 16384);
            l2_prefetch(woB + (size_t)bid_ * 8192, 16384);
          }
          PROFT(true, 64 + e * 16 + 7);
          if ((e & 1) == 0) {
            float* kvl = g_kv + ((size_t)((epoch & 1) * 2 + (e >> 1)) * 8 + g) * 8448;
#pragma unroll 1
            for (int hp = 0; hp < 2; ++hp) {
              mbar_wait(BA(B_KVDONE), hp);
              bulk_red_add(kvl + 8192 + hp * 128, sb + SM_AP + hp * 512, 512);
#pragma unroll 1
              for (int i = 0; i < NCH; ++i) {
                const int ch = hp * NCH + ((i + rb * NCH / 16) & (NCH - 1));
                bulk_red_add(kvl + ch * (4096 / NCH), sb + VB + ch * (16384 / NCH), 16384 / NCH);
                bulk_commit();
                asm volatile("cp.async.bulk.wait_group %0;" :: "n"(CHW) : "memory");
              }
              bulk_wait0();
              PROFT(true, 64 + e * 16 + (hp ? 10 : 6));
              fence_async_all();
              flag_add(&g_kvflag[hp * 8 + g].v);
              PROFT(e > 0 && hp, 64 + e * 16 + 8);
            }
          }
          if (e & 1) {
            mbar_wait(BA(B_OF0), (e >> 1) & 1);
            flag_set(g_hf + rb * 32 + g, xbase + e + 1);
            if (rb) flag_wait(g_hf + (rb - 1) * 32 + g, xbase + e + 1);
            fence_async_all();
            mbar_expect_tx(BA(B_HALO), 8192);
            bulk_load(sb + SM_SD, g_halo + (size_t)(((e >> 1) * 17 + rb) * 8 + g) * 2048, 8192, BA(B_HALO));
            PROFT(true, 64 + e * 16 + 15);
          }
          mbar_wait(BA(B_OH0), e & 1);
          PROFT(e > 0, 64 + e * 16 + 13);
          flag_set(g_of + rb * 32 + 2 * g, xbase + e + 1);
          PROFT(true, 64 + e * 16 + 9);
          mbar_wait(BA(B_OH1), e & 1);
          PROFT(true, 64 + e * 16 + 5);
          flag_set(g_of + rb * 32 + 2 * g + 1, xbase + e + 1);
          PROFT(true, 64 + e * 16 + 11);
        }
        if (bid_ == 0) g_epoch = epoch + 1;
      }
    } else {
      BLK_CTX();
      const unsigned int epoch = __shfl_sync(0xffffffffu, ld_relaxed(&g_epoch), 0), xbase = epoch * NLAYERS;
      (void)xbase;
      if (lane < 16) sts_f(sb + SM_RS + lane * 4, 0.f);
#pragma unroll 1
      for (int layer = 0; layer < NLAYERS; ++layer) {
#define HLP_CTX() BLK_CTX(); int lane = threadIdx.x & 31; asm volatile("" : "+r"(lane)); const bool isB = layer & 1, hal = isB && rb > 0; (void)hal;
#pragma unroll 1
        for (int ph = 0; ph < 2; ++ph) {
          HLP_CTX();
          if (ph == (layer == 0)) {
            const float* cs = g_cs + (epoch & 1) * 6144 + g * 384;
            if (layer) mbar_wait_u(BA(CT), (layer - 1) & 1);
            if (layer < 2) {
              if (lane == 0) flag_wait_slow(&g_csflag[isB ? 8 : g].v, isB ? epoch * 4u + 4u : epoch * 16u + 16u);
              __syncwarp();
            }
            float a[12];
#pragma unroll
            for (int i = 0; i < 12; ++i) a[i] = __ldcg(cs + isB * 3072 + i * 32 + lane);
#pragma unroll
            for (int i = 0; i < 12; ++i) {
              const float c1 = bf16r(a[i]), c2 = bf16r(a[i] - c1), c3 = (a[i] - c1) - c2;
              sts128(sb + SM_BP + (i * 32 + lane) * 16, make_uint4(pack_bf16(c1, c2), pack_bf16(c3, 0.f), 0u, 0u));
            }
          } else {
            uint32_t rdy = 0u;
            src_wait<128>(g_xf + rb * 32, xbase + layer + 1, 0xAAAAu, rdy, lane);
            rdy = 0u;
            if (hal) src_wait<128>(g_xf + (rb - 1) * 32, xbase + layer + 1, 0xAAAAu, rdy, lane);
            const float2* sp = g_stats + ((epoch & 1) * 4 + layer) * S_ + m0 + lane;
            float2 u[5];
#pragma unroll
            for (int i = 0; i < 4; ++i) u[i] = __ldcg(sp + i * 32);
            u[4] = __ldcg(sp - (hal ? 16 : 0));
#pragma unroll
            for (int i = 0; i < 5; ++i) {
              const float mean = u[i].x * (1.f / D_);
              const float var = fmaxf(fmaf(-u[i].x, mean, u[i].y) * (1.f / D_), 0.f);
              const float sd = bf16r(sqrtf(bf16r(bf16r(var) + 1e-5f)));
              const int R = i * 32 + lane;
              if (i < 4) {
                const float hm = -0.5f * bf16r(mean);
                sts_f(sb + SM_RS + (16 + R) * 4, __fdividef(1.f, sd));
                if (!isB) sts128(sb + SM_SD + R * 64 + ((R >> 1) & 3) * 16, make_uint4(__float_as_uint(sd) >> 16, 0u, 0u, 0u));
                sts128(sb + SM_AP + R * 16, make_uint4(pack_bf16(hm, hm), pack_bf16(hm, 0.f), 0u, 0u));
              } else if (hal && lane < 16) sts_f(sb + SM_RS + lane * 4, __fdividef(1.f, sd));
            }
            PROFT(lane == 0, 64 + layer * 16 + 12);
          }
        }
        HLP_CTX();
        fence_async_smem();
        __syncwarp();
        if (lane == 0) mbar_arrive(BA(B_STAT));
        PROFT(lane == 0, 64 + layer * 16 + 14);
        if (!isB && lane == 0) {
#pragma unroll 1
          for (int hp = 0; hp < 2; ++hp) {
            mbar_wait(BA(B_KVDONE), hp);
            flag_wait(&g_kvflag[hp * 8 + g].v, epoch * (16u * ((NLAYERS + 1) / 2)) + 16u * ((layer >> 1) + 1));
            const float* kvl = g_kv + ((size_t)((epoch & 1) * 2 + (layer >> 1)) * 8 + g) * 8448;
            const uint32_t kb = BA(hp ? B_KVF1 : B_KVF);
            fence_async_all();
            mbar_expect_tx(kb, 16384 + 512);
            bulk_load(sb + VB + hp * SLOT, kvl + hp * 4096, 16384, kb);
            bulk_load(sb + SM_AP + hp * 512, kvl + 8192 + hp * 128, 512, kb);
            PROFT(hp == 0, 64 + layer * 16 + 15);
          }
        }
        __syncwarp();
      }
    }
    __syncwarp();
    cluster_arrive();
    cluster_wait();
  } else {
    asm volatile("setmaxnreg.inc.sync.aligned.u32 232;");
    PROFT(threadIdx.x == 128, 235);
    cluster_wait();
    PROFT(threadIdx.x == 128, 236);
    consumer(c);
    asm volatile("bar.warp.sync 0xffffffff;\nbarrier.cluster.arrive.release.aligned;\nbarrier.cluster.wait.acquire.aligned;\n" ::: "memory");
  }
}

typedef CUresult (*PFN_encodeTiled)(CUtensorMap*, CUtensorMapDataType, cuuint32_t, void*, const cuuint64_t*, const cuuint64_t*,
                                    const cuuint32_t*, const cuuint32_t*, CUtensorMapInterleave, CUtensorMapSwizzle,
                                    CUtensorMapL2promotion, CUtensorMapFloatOOBfill);

static void make_map2(PFN_encodeTiled enc, CUtensorMap* m, const void* ptr, uint64_t cols, uint64_t rows, uint32_t box_c, uint32_t box_r) {
  cuuint64_t dims[2] = {cols, rows};
  cuuint64_t strides[1] = {cols * 2};
  cuuint32_t box[2] = {box_c, box_r};
  cuuint32_t es[2] = {1, 1};
  CUresult r = enc(m, CU_TENSOR_MAP_DATA_TYPE_BFLOAT16, 2, const_cast<void*>(ptr), dims, strides, box, es, CU_TENSOR_MAP_INTERLEAVE_NONE,
                   box_c == 64 ? CU_TENSOR_MAP_SWIZZLE_128B : CU_TENSOR_MAP_SWIZZLE_64B, CU_TENSOR_MAP_L2_PROMOTION_L2_256B, CU_TENSOR_MAP_FLOAT_OOB_FILL_NONE);
  (void)r;
}
static void make_map5(PFN_encodeTiled enc, CUtensorMap* m, const void* ptr, uint64_t cols) {
  for (int p = 0; p < 2; ++p) {
    cuuint64_t dims[5] = {cols, 2, 4, 4, 32};
    cuuint64_t strides[4] = {cols * 2, cols * (p ? 16 : 4), cols * (p ? 4 : 16), cols * 64};
    cuuint32_t box[5] = {64, 2, 4, 4, 2};
    cuuint32_t es[5] = {1, 1, 1, 1, 1};
    CUresult r = enc(m + p, CU_TENSOR_MAP_DATA_TYPE_BFLOAT16, 5, const_cast<void*>(ptr), dims, strides, box, es, CU_TENSOR_MAP_INTERLEAVE_NONE,
                     CU_TENSOR_MAP_SWIZZLE_128B, CU_TENSOR_MAP_L2_PROMOTION_L2_256B, CU_TENSOR_MAP_FLOAT_OOB_FILL_NONE);
    (void)r;
  }
}

extern "C" void kernel_launch(void* const* d_in, const int* in_sizes, int n_in, void* d_out, int out_size) {
  const bf16* A_x = (const bf16*)d_in[0];
  const bf16* A_wqkv = (const bf16*)d_in[1];
  const bf16* A_wphi = (const bf16*)d_in[2];
  const bf16* A_wo = (const bf16*)d_in[3];
  const bf16* B_wqkv = (const bf16*)d_in[5];
  const bf16* B_wo = (const bf16*)d_in[6];
  bf16* out = (bf16*)d_out;

  static PFN_encodeTiled enc = nullptr;
  static bf16 *p_x, *p_o, *p_wf;
  static uint32_t boff;
  if (!enc) {
    void* fn = nullptr; cudaDriverEntryPointQueryResult qr;
    cudaGetDriverEntryPoint("cuTensorMapEncodeTiled", &fn, cudaEnableDefault, &qr);
    enc = (PFN_encodeTiled)fn;
    cudaGetSymbolAddress((void**)&p_x, g_x);
    cudaGetSymbolAddress((void**)&p_o, g_o);
    cudaGetSymbolAddress((void**)&p_wf, g_wf);
    cudaFuncSetAttribute(mega_kernel, cudaFuncAttributeMaxDynamicSharedMemorySize, SM_TOTAL);
    cudaLaunchConfig_t cfg = {};
    cudaLaunchAttribute at; at.id = cudaLaunchAttributeClusterDimension; at.val.clusterDim.x = 2; at.val.clusterDim.y = 1; at.val.clusterDim.z = 1;
    cfg.gridDim = dim3(132); cfg.blockDim = dim3(384); cfg.dynamicSmemBytes = SM_TOTAL; cfg.attrs = &at; cfg.numAttrs = 1;
    int nc = 0;
    if (cudaOccupancyMaxActiveClusters(&nc, mega_kernel, &cfg) != cudaSuccess) { nc = 0; (void)cudaGetLastError(); }
    boff = nc >= 66 ? 0u : 4u;
  }
  Maps maps;
  make_map5(enc, &maps.m[MAP_WF], p_wf, 2048);
  make_map5(enc, &maps.m[MAP_WA], A_wqkv, 3072);
  make_map5(enc, &maps.m[MAP_WB], B_wqkv, 3072);
  make_map5(enc, &maps.m[MAP_WOA], A_wo, 1024);
  make_map5(enc, &maps.m[MAP_WOB], B_wo, 1024);
  make_map2(enc, &maps.m[MAP_X0], A_x, 1024, 2048, 64, 128);
  make_map2(enc, &maps.m[MAP_X], p_x, 1024, 2048, 64, 128);
  make_map2(enc, &maps.m[MAP_O], p_o, 1024, 2048, 64, 128);
  make_map2(enc, &maps.m[MAP_PHI], A_wphi, 32, 1024, 32, 128);
  Ctx c; c.zero = 0u; c.boff = boff; c.out = out;
  mega_kernel<<<132, 384, SM_TOTAL, cudaStreamPerThread>>>(maps, c, A_wqkv, B_wqkv, A_wo, B_wo);
}
```

```cpp
#include <cuda_runtime.h>
#include <cuda_bf16.h>
#include <cuda.h>
#include <stdint.h>

typedef __nv_bfloat16 bf16;

constexpr int S_ = 2048, D_ = 1024;

struct __align__(128) Flag { unsigned int v; unsigned int pad[31]; };
__device__ __align__(1024) bf16 g_x[S_ * D_];
__device__ __align__(1024) bf16 g_o[S_ * D_];
__device__ __align__(1024) uint32_t g_halo[2 * 17 * 8 * 2048];
__device__ __align__(1024) float g_kv[2 * 2 * 8 * 8448];
__device__ __align__(1024) float2 g_stats[2 * 4 * S_];
__device__ __align__(1024) float g_cs[2 * 2 * 3072];
__device__ __align__(1024) bf16 g_wf[D_ * 2048];
__device__ Flag g_kvflag[16], g_csflag[13];
__device__ __align__(128) unsigned int g_xf[16 * 32], g_of[16 * 32];
__device__ __align__(128) unsigned int g_hf[16 * 32];
__device__ __align__(128) unsigned int g_wff[8 * 32];
__device__ unsigned int g_epoch, g_err;
#define PROFT(cond, idx) asm volatile("" ::: "memory")

#define PSL 100
__device__ __forceinline__ uint32_t smem_u32(const void* p) { return (uint32_t)__cvta_generic_to_shared(p); }
__device__ __forceinline__ void mbar_init(uint32_t bar, uint32_t count) {
  asm volatile("mbarrier.init.shared::cta.b64 [%0], %1;" ::"r"(bar), "r"(count) : "memory");
}
__device__ __forceinline__ void mbar_expect_tx(uint32_t bar, uint32_t bytes) {
  asm volatile("mbarrier.arrive.expect_tx.shared::cta.b64 _, [%0], %1;" ::"r"(bar), "r"(bytes) : "memory");
}
__device__ __forceinline__ void mbar_arrive(uint32_t bar) {
  asm volatile("mbarrier.arrive.shared::cta.b64 _, [%0];" ::"r"(bar) : "memory");
}
__device__ __forceinline__ bool mbar_try_wait(uint32_t bar, uint32_t parity) {
  uint32_t ok;
  asm volatile("{\n.reg .pred p;\nmbarrier.try_wait.parity.shared::cta.b64 p, [%1], %2;\nselp.b32 %0, 1, 0, p;\n}\n"
               : "=r"(ok) : "r"(bar), "r"(parity) : "memory");
  return ok != 0;
}
__device__ __forceinline__ bool mbar_test_wait(uint32_t bar, uint32_t parity) {
  uint32_t ok;
  asm volatile("{\n.reg .pred p;\nmbarrier.test_wait.parity.shared::cta.b64 p, [%1], %2;\nselp.b32 %0, 1, 0, p;\n}\n"
               : "=r"(ok) : "r"(bar), "r"(parity) : "memory");
  return ok != 0;
}
__device__ __forceinline__ uint64_t gtimer() {
  uint64_t t; asm volatile("mov.u64 %0, %globaltimer;" : "=l"(t)); return t;
}
__device__ __forceinline__ void mbar_wait(uint32_t bar, uint32_t parity) {
  uint32_t n = 0;
#pragma unroll 1
  while (!mbar_try_wait(bar, parity)) {
    if (++n > (1u << 22)) { g_err = 1u; break; }
  }
}
__device__ __forceinline__ unsigned int ld_acquire(const unsigned int* p) {
  unsigned int v; asm volatile("ld.acquire.gpu.global.u32 %0, [%1];" : "=r"(v) : "l"(p) : "memory"); return v;
}
__device__ __forceinline__ void flag_add(unsigned int* p) {
  asm volatile("red.release.gpu.global.add.u32 [%0], 1;" ::"l"(p) : "memory");
}
__device__ __forceinline__ void flag_set(unsigned int* p, unsigned int v) {
  asm volatile("st.release.gpu.global.u32 [%0], %1;" ::"l"(p), "r"(v) : "memory");
}
template <int SLEEP>
__device__ __forceinline__ void src_wait(const unsigned int* f, unsigned int target, uint32_t need, uint32_t& ready, int lane) {
  uint32_t n = 0;
#pragma unroll 1
  while ((ready & need) != need) {
    const unsigned int v = ld_acquire(f + (lane & 15));
    ready = __ballot_sync(0xffffffffu, (int)(v - target) >= 0);
    if (SLEEP) { if ((ready & need) != need) __nanosleep(SLEEP); }
    if (++n > (1u << 20)) { g_err = 3u; break; }
  }
  __syncwarp();
}
__device__ __forceinline__ unsigned int ld_relaxed(const unsigned int* p);
__device__ __forceinline__ void src_wait_fast(const unsigned int* f, unsigned int target, uint32_t need, uint32_t& ready, int lane) {
  f += lane & 15;
  unsigned int v0 = ld_relaxed(f); __nanosleep(PSL);
  unsigned int v1 = ld_relaxed(f); __nanosleep(PSL);
  unsigned int v2 = ld_relaxed(f);
  uint32_t n = 0;
#pragma unroll 1
  while (true) {
    ready = __ballot_sync(0xffffffffu, (int)(v0 - target) >= 0);
    if ((ready & need) == need) break;
    v0 = ld_relaxed(f);
    ready = __ballot_sync(0xffffffffu, (int)(v1 - target) >= 0);
    if ((ready & need) == need) break;
    v1 = ld_relaxed(f);
    ready = __ballot_sync(0xffffffffu, (int)(v2 - target) >= 0);
    if ((ready & need) == need) break;
    v2 = ld_relaxed(f);
    if (++n > (1u << 20)) { g_err = 3u; break; }
  }
  asm volatile("fence.acquire.gpu;" ::: "memory");
  __syncwarp();
}
__device__ __forceinline__ unsigned int ld_relaxed(const unsigned int* p) {
  unsigned int v; asm volatile("ld.relaxed.gpu.global.u32 %0, [%1];" : "=r"(v) : "l"(p) : "memory"); return v;
}
__device__ __forceinline__ uint4 ld_relaxed4(const uint4* p) {
  uint4 v; asm volatile("ld.relaxed.gpu.global.v4.u32 {%0,%1,%2,%3}, [%4];" : "=r"(v.x), "=r"(v.y), "=r"(v.z), "=r"(v.w) : "l"(p) : "memory"); return v;
}
__device__ __forceinline__ void st_relaxed4(uint4* p, uint32_t a, uint32_t b, uint32_t c, uint32_t d) {
  asm volatile("st.relaxed.gpu.global.v4.u32 [%0], {%1,%2,%3,%4};" ::"l"(p), "r"(a), "r"(b), "r"(c), "r"(d) : "memory");
}
__device__ __forceinline__ void st_relaxed4_p(bool on, uint4* p, uint32_t a, uint32_t b, uint32_t c, uint32_t d) {
  asm volatile("{\n.reg .pred p;\nsetp.ne.b32 p, %5, 0;\n@p st.relaxed.gpu.global.v4.u32 [%0], {%1,%2,%3,%4};\n}\n" ::"l"(p), "r"(a), "r"(b), "r"(c), "r"(d), "r"((int)on) : "memory");
}
template <int SLEEP>
__device__ __forceinline__ void flag_wait_t(const unsigned int* p, unsigned int target) {
  uint32_t n = 0;
#pragma unroll 1
  while ((int)(ld_acquire(p) - target) < 0) {
    if (SLEEP) __nanosleep(SLEEP);
    if (++n > (1u << 20)) { g_err = 2u; break; }
  }
}
__device__ __forceinline__ void flag_wait(const unsigned int* p, unsigned int target) { flag_wait_t<0>(p, target); }
__device__ __forceinline__ void flag_wait_slow(const unsigned int* p, unsigned int target) { flag_wait_t<256>(p, target); }
__device__ __forceinline__ void tma_load_2d(uint32_t dst, const CUtensorMap* tm, int c0, int c1, uint32_t bar) {
  asm volatile("cp.async.bulk.tensor.2d.shared::cluster.global.mbarrier::complete_tx::bytes [%0], [%1, {%2, %3}], [%4];"
               ::"r"(dst), "l"(tm), "r"(c0), "r"(c1), "r"(bar) : "memory");
}
__device__ __forceinline__ void tma_load_2d_mc(uint32_t dst, const CUtensorMap* tm, int c0, int c1, uint32_t bar, uint16_t mask) {
  asm volatile("cp.async.bulk.tensor.2d.shared::cluster.global.mbarrier::complete_tx::bytes.multicast::cluster [%0], [%1, {%2, %3}], [%4], %5;"
               ::"r"(dst), "l"(tm), "r"(c0), "r"(c1), "r"(bar), "h"(mask) : "memory");
}
__device__ __forceinline__ void mbar_wait_u(uint32_t bar, uint32_t parity) {
  uint32_t n = 0;
#pragma unroll 1
  while (!__all_sync(0xffffffffu, mbar_try_wait(bar, parity))) {
    if (++n > (1u << 22)) { g_err = 1u; break; }
  }
}
__device__ __forceinline__ void expect_tx_e(uint32_t bar, uint32_t bytes) {
  asm volatile("{\n.reg .pred p;\nelect.sync _|p, 0xffffffff;\n@p mbarrier.arrive.expect_tx.shared::cta.b64 _, [%0], %1;\n}\n" ::"r"(bar), "r"(bytes) : "memory");
}
__device__ __forceinline__ void tma_2d_e(uint32_t dst, const CUtensorMap* tm, int c0, int c1, uint32_t bar) {
  asm volatile("{\n.reg .pred p;\nelect.sync _|p, 0xffffffff;\n"
               "@p cp.async.bulk.tensor.2d.shared::cluster.global.mbarrier::complete_tx::bytes [%0], [%1, {%2, %3}], [%4];\n}\n"
               ::"r"(dst), "l"(tm), "r"(c0), "r"(c1), "r"(bar) : "memory");
}
__device__ __forceinline__ void tma_2d_mc_e(uint32_t dst, const CUtensorMap* tm, int c0, int c1, uint32_t bar) {
  asm volatile("{\n.reg .pred p;\nelect.sync _|p, 0xffffffff;\n"
               "@p cp.async.bulk.tensor.2d.shared::cluster.global.mbarrier::complete_tx::bytes.multicast::cluster [%0], [%1, {%2, %3}], [%4], %5;\n}\n"
               ::"r"(dst), "l"(tm), "r"(c0), "r"(c1), "r"(bar), "h"((uint16_t)3) : "memory");
}
__device__ __forceinline__ void tma_5d(uint32_t dst, const CUtensorMap* tm, int c0, int c4, uint32_t bar) {
  asm volatile("cp.async.bulk.tensor.5d.shared::cluster.global.mbarrier::complete_tx::bytes [%0], [%1, {%2, %5, %5, %5, %3}], [%4];"
               ::"r"(dst), "l"(tm), "r"(c0), "r"(c4), "r"(bar), "r"(0) : "memory");
}
__device__ __forceinline__ void tma_5d_e(uint32_t dst, const CUtensorMap* tm, int c0, int c4, uint32_t bar) {
  asm volatile("{\n.reg .pred p;\nelect.sync _|p, 0xffffffff;\n"
               "@p cp.async.bulk.tensor.5d.shared::cluster.global.mbarrier::complete_tx::bytes [%0], [%1, {%2, %5, %5, %5, %3}], [%4];\n}\n"
               ::"r"(dst), "l"(tm), "r"(c0), "r"(c4), "r"(bar), "r"(0) : "memory");
}
__device__ __forceinline__ void tma_5d_mc_e(uint32_t dst, const CUtensorMap* tm, int c0, int c4, uint32_t bar) {
  asm volatile("{\n.reg .pred p;\nelect.sync _|p, 0xffffffff;\n"
               "@p cp.async.bulk.tensor.5d.shared::cluster.global.mbarrier::complete_tx::bytes.multicast::cluster [%0], [%1, {%2, %6, %6, %6, %3}], [%4], %5;\n}\n"
               ::"r"(dst), "l"(tm), "r"(c0), "r"(c4), "r"(bar), "h"((uint16_t)3), "r"(0) : "memory");
}
__device__ __forceinline__ void wait_tma_2d(bool w, uint32_t eb, uint32_t par, uint32_t dst, const CUtensorMap* tm, int c0, int c1, uint32_t fb) {
  asm volatile("" : "+r"(dst), "+l"(tm), "+r"(c0), "+r"(fb));
  if (w) mbar_wait_u(eb, par);
  tma_2d_e(dst, tm, c0, c1, fb);
}
__device__ __forceinline__ void wait_tma_5d_mc(bool w, uint32_t eb, uint32_t par, uint32_t dst, const CUtensorMap* tm, int c0, int c4, uint32_t fb) {
  asm volatile("" : "+r"(dst), "+l"(tm), "+r"(c0), "+r"(c4), "+r"(fb));
  if (w) mbar_wait_u(eb, par);
  tma_5d_mc_e(dst, tm, c0, c4, fb);
}
__device__ __forceinline__ void stg128(void* p, uint32_t a, uint32_t b, uint32_t c, uint32_t d) {
  asm volatile("st.global.v4.u32 [%0], {%1,%2,%3,%4};" ::"l"(p), "r"(a), "r"(b), "r"(c), "r"(d) : "memory");
}
__device__ __forceinline__ void stg128_p(bool on, void* p, uint32_t a, uint32_t b, uint32_t c, uint32_t d) {
  asm volatile("{\n.reg .pred p;\nsetp.ne.b32 p, %5, 0;\n@p st.global.v4.u32 [%0], {%1,%2,%3,%4};\n}\n" ::"l"(p), "r"(a), "r"(b), "r"(c), "r"(d), "r"((int)on) : "memory");
}
__device__ __forceinline__ void ldg128(const void* p, uint32_t& a, uint32_t& b, uint32_t& c, uint32_t& d) {
  asm volatile("ld.global.cg.v4.u32 {%0,%1,%2,%3}, [%4];" : "=r"(a), "=r"(b), "=r"(c), "=r"(d) : "l"(p) : "memory");
}
__device__ __forceinline__ uint32_t ldg32(const void* p) {
  uint32_t v; asm volatile("ld.global.nc.u32 %0, [%1];" : "=r"(v) : "l"(p) : "memory"); return v;
}
__device__ __forceinline__ void tma_pf_e(const CUtensorMap* tm, int c0, int c1) {
  asm volatile("{\n.reg .pred p;\nelect.sync _|p, 0xffffffff;\n"
               "@p cp.async.bulk.prefetch.tensor.2d.L2.global.tile [%0, {%1, %2}];\n}\n" ::"l"(tm), "r"(c0), "r"(c1) : "memory");
}
__device__ __forceinline__ void tma_2d_to_e(uint32_t dst, const CUtensorMap* tm, int c0, int c1, uint32_t bar, uint32_t mask) {
  asm volatile("{\n.reg .pred p;\nelect.sync _|p, 0xffffffff;\n"
               "@p cp.async.bulk.tensor.2d.shared::cluster.global.mbarrier::complete_tx::bytes.multicast::cluster [%0], [%1, {%2, %3}], [%4], %5;\n}\n"
               ::"r"(dst), "l"(tm), "r"(c0), "r"(c1), "r"(bar), "h"((uint16_t)mask) : "memory");
}
__device__ __forceinline__ void tma_3d_mc_e(uint32_t dst, const CUtensorMap* tm, int c1, int c2, uint32_t bar) {
  asm volatile("{\n.reg .pred p;\nelect.sync _|p, 0xffffffff;\n"
               "@p cp.async.bulk.tensor.3d.shared::cluster.global.mbarrier::complete_tx::bytes.multicast::cluster [%0], [%1, {%6, %2, %3}], [%4], %5;\n}\n"
               ::"r"(dst), "l"(tm), "r"(c1), "r"(c2), "r"(bar), "h"((uint16_t)3), "r"(0) : "memory");
}
__device__ __forceinline__ uint32_t poll_flags(const unsigned int* f, unsigned int target, int lane) {
  const unsigned int v = ld_acquire(f + (lane & 15));
  const uint32_t r = __ballot_sync(0xffffffffu, (int)(v - target) >= 0);
  __syncwarp();
  return r;
}
__device__ __forceinline__ void mbar_arrive_cluster(uint32_t local_bar, uint32_t rank) {
  asm volatile("{\n.reg .b32 ra;\nmapa.shared::cluster.u32 ra, %0, %1;\nmbarrier.arrive.shared::cluster.b64 _, [ra];\n}\n"
               ::"r"(local_bar), "r"(rank) : "memory");
}
__device__ __forceinline__ void release2(uint32_t bar) { mbar_arrive_cluster(bar, 0); mbar_arrive_cluster(bar, 1); }
__device__ __forceinline__ void release2c(uint32_t off) {
  asm volatile("mbarrier.arrive.shared::cluster.b64 _, [%0];\nmbarrier.arrive.shared::cluster.b64 _, [%1];" ::"r"(off), "r"(off + (1u << 24)) : "memory");
}
__device__ __forceinline__ void tma_store_2d(const CUtensorMap* tm, uint32_t src, int c0, int c1) {
  asm volatile("cp.async.bulk.tensor.2d.global.shared::cta.bulk_group [%0, {%2, %3}], [%1];"
               ::"l"(tm), "r"(src), "r"(c0), "r"(c1) : "memory");
}
__device__ __forceinline__ void tma_store_5d(const CUtensorMap* tm, uint32_t src, int c0, int c4) {
  asm volatile("cp.async.bulk.tensor.5d.global.shared::cta.bulk_group [%0, {%2, %4, %4, %4, %3}], [%1];"
               ::"l"(tm), "r"(src), "r"(c0), "r"(c4), "r"(0) : "memory");
}
__device__ __forceinline__ void bulk_store(void* dst, uint32_t src, uint32_t bytes) {
  asm volatile("cp.async.bulk.global.shared::cta.bulk_group [%0], [%1], %2;" ::"l"(dst), "r"(src), "r"(bytes) : "memory");
}
__device__ __forceinline__ void bulk_load(uint32_t dst, const void* src, uint32_t bytes, uint32_t bar) {
  asm volatile("cp.async.bulk.shared::cluster.global.mbarrier::complete_tx::bytes [%0], [%1], %2, [%3];" ::"r"(dst), "l"(src), "r"(bytes), "r"(bar) : "memory");
}
__device__ __forceinline__ void bulk_red_add(void* dst, uint32_t src, uint32_t bytes) {
  asm volatile("cp.reduce.async.bulk.global.shared::cta.bulk_group.add.f32 [%0], [%1], %2;" ::"l"(dst), "r"(src), "r"(bytes) : "memory");
}
__device__ __forceinline__ void bulk_commit() { asm volatile("cp.async.bulk.commit_group;" ::: "memory"); }
__device__ __forceinline__ void bulk_wait0() { asm volatile("cp.async.bulk.wait_group 0;" ::: "memory"); }
__device__ __forceinline__ void fence_async_smem() { asm volatile("fence.proxy.async.shared::cta;" ::: "memory"); }
__device__ __forceinline__ void fence_async_all() { asm volatile("fence.proxy.async.global;" ::: "memory"); }
__device__ __forceinline__ void wgmma_fence() { asm volatile("wgmma.fence.sync.aligned;" ::: "memory"); }
__device__ __forceinline__ void wgmma_commit() { asm volatile("wgmma.commit_group.sync.aligned;" ::: "memory"); }
template <int N> __device__ __forceinline__ void wgmma_wait() { asm volatile("wgmma.wait_group.sync.aligned %0;" ::"n"(N) : "memory"); }
__device__ __forceinline__ void cluster_arrive() { asm volatile("barrier.cluster.arrive.release.aligned;" ::: "memory"); }
__device__ __forceinline__ void cluster_wait() { asm volatile("barrier.cluster.wait.acquire.aligned;" ::: "memory"); }
template <int ID, int N> __device__ __forceinline__ void nbar() { asm volatile("bar.sync %0, %1;" ::"n"(ID), "n"(N) : "memory"); }
__device__ __forceinline__ uint64_t make_desc(uint32_t addr, uint32_t lbo_bytes, uint32_t sbo_bytes) {
  uint64_t d = 0;
  d |= (uint64_t)((addr & 0x3FFFF) >> 4);
  d |= (uint64_t)((lbo_bytes >> 4) & 0x3FFF) << 16;
  d |= (uint64_t)((sbo_bytes >> 4) & 0x3FFF) << 32;
  d |= (uint64_t)1 << 62;
  return d;
}
__device__ __forceinline__ uint64_t desc64(uint32_t lo, uint32_t hi) { return (uint64_t)lo | ((uint64_t)hi << 32); }
__device__ __forceinline__ uint32_t pack_bf16(float lo, float hi) {
  uint32_t r; asm("cvt.rn.bf16x2.f32 %0, %1, %2;" : "=r"(r) : "f"(hi), "f"(lo)); return r;
}
__device__ __forceinline__ uint32_t add_bf16x2(uint32_t a, uint32_t b) {
  uint32_t r; asm("add.rn.bf16x2 %0, %1, %2;" : "=r"(r) : "r"(a), "r"(b)); return r;
}
__device__ __forceinline__ float bf16r(float x) { return __bfloat162float(__float2bfloat16_rn(x)); }
__device__ __forceinline__ float bf_lo(uint32_t u) { return __uint_as_float(u << 16); }
__device__ __forceinline__ float bf_hi(uint32_t u) { return __uint_as_float(u & 0xFFFF0000u); }
__device__ __forceinline__ float ex2(float x) { float r; asm("ex2.approx.ftz.f32 %0, %1;" : "=f"(r) : "f"(x)); return r; }
__device__ __forceinline__ float ex2v(float x) { float r; asm volatile("ex2.approx.ftz.f32 %0, %1;" : "=f"(r) : "f"(x) : "memory"); return r; }
__device__ __forceinline__ float rcp(float x) { float r; asm("rcp.approx.ftz.f32 %0, %1;" : "=f"(r) : "f"(x)); return r; }
__device__ __forceinline__ void mma_bf16(float (&d)[4], uint32_t a0, uint32_t a1, uint32_t a2, uint32_t a3, uint32_t b0, uint32_t b1) {
  asm("mma.sync.aligned.m16n8k16.row.col.f32.bf16.bf16.f32 {%0,%1,%2,%3}, {%4,%5,%6,%7}, {%8,%9}, {%0,%1,%2,%3};"
               : "+f"(d[0]), "+f"(d[1]), "+f"(d[2]), "+f"(d[3]) : "r"(a0), "r"(a1), "r"(a2), "r"(a3), "r"(b0), "r"(b1));
}
__device__ __forceinline__ void ldsm_x4(uint32_t& r0, uint32_t& r1, uint32_t& r2, uint32_t& r3, uint32_t addr) {
  asm volatile("ldmatrix.sync.aligned.m8n8.x4.shared.b16 {%0,%1,%2,%3}, [%4];"
               : "=r"(r0), "=r"(r1), "=r"(r2), "=r"(r3) : "r"(addr) : "memory");
}
__device__ __forceinline__ void ldsm_x4_t(uint32_t& r0, uint32_t& r1, uint32_t& r2, uint32_t& r3, uint32_t addr) {
  asm volatile("ldmatrix.sync.aligned.m8n8.x4.trans.shared.b16 {%0,%1,%2,%3}, [%4];"
               : "=r"(r0), "=r"(r1), "=r"(r2), "=r"(r3) : "r"(addr) : "memory");
}
__device__ __forceinline__ void ldsm_x2_t(uint32_t& r0, uint32_t& r1, uint32_t addr) {
  asm volatile("ldmatrix.sync.aligned.m8n8.x2.trans.shared.b16 {%0,%1}, [%2];"
               : "=r"(r0), "=r"(r1) : "r"(addr) : "memory");
}
__device__ __forceinline__ void stsm_x4(uint32_t addr, uint32_t r0, uint32_t r1, uint32_t r2, uint32_t r3) {
  asm volatile("stmatrix.sync.aligned.m8n8.x4.shared.b16 [%0], {%1,%2,%3,%4};"
               ::"r"(addr), "r"(r0), "r"(r1), "r"(r2), "r"(r3) : "memory");
}
__device__ __forceinline__ void stsm_x4_p(bool on, uint32_t addr, uint32_t r0, uint32_t r1, uint32_t r2, uint32_t r3) {
  asm volatile("{\n.reg .pred p;\nsetp.ne.b32 p, %5, 0;\n@p stmatrix.sync.aligned.m8n8.x4.shared.b16 [%0], {%1,%2,%3,%4};\n}\n"
               ::"r"(addr), "r"(r0), "r"(r1), "r"(r2), "r"(r3), "r"((int)on) : "memory");
}
__device__ __forceinline__ float2 lds_f2(uint32_t addr) {
  float2 v; asm volatile("ld.shared.v2.f32 {%0,%1}, [%2];" : "=f"(v.x), "=f"(v.y) : "r"(addr) : "memory"); return v;
}
__device__ __forceinline__ uint4 lds128(uint32_t addr) {
  uint4 v; asm volatile("ld.shared.v4.b32 {%0,%1,%2,%3}, [%4];" : "=r"(v.x), "=r"(v.y), "=r"(v.z), "=r"(v.w) : "r"(addr) : "memory"); return v;
}
__device__ __forceinline__ void sts128(uint32_t addr, uint4 v) {
  asm volatile("st.shared.v4.b32 [%0], {%1,%2,%3,%4};" ::"r"(addr), "r"(v.x), "r"(v.y), "r"(v.z), "r"(v.w) : "memory");
}
__device__ __forceinline__ float lds_f(uint32_t addr) {
  float v; asm volatile("ld.shared.f32 %0, [%1];" : "=f"(v) : "r"(addr) : "memory"); return v;
}
__device__ __forceinline__ void sts16(uint32_t addr, uint32_t v) {
  asm volatile("st.shared.u16 [%0], %1;" ::"r"(addr), "h"((unsigned short)v) : "memory");
}
__device__ __forceinline__ void nbar_dyn(int id, int n) { asm volatile("bar.sync %0, %1;" ::"r"(id), "r"(n) : "memory"); }
__device__ __forceinline__ uint64_t make_desc_ns(uint32_t addr, uint32_t lbo_bytes, uint32_t sbo_bytes) {
  return (uint64_t)((addr & 0x3FFFF) >> 4) | ((uint64_t)(lbo_bytes >> 4) << 16) | ((uint64_t)(sbo_bytes >> 4) << 32);
}
__device__ __forceinline__ void sts_f(uint32_t addr, float v) { asm volatile("st.shared.f32 [%0], %1;" ::"r"(addr), "f"(v) : "memory"); }
__device__ __forceinline__ void sts64(uint32_t addr, uint32_t a, uint32_t b) {
  asm volatile("st.shared.v2.b32 [%0], {%1,%2};" ::"r"(addr), "r"(a), "r"(b) : "memory");
}
__device__ __forceinline__ void sts_f2(uint32_t addr, float a, float b) {
  asm volatile("st.shared.v2.f32 [%0], {%1,%2};" ::"r"(addr), "f"(a), "f"(b) : "memory");
}
__device__ __forceinline__ void red_add2(float* p, float a, float b) {
  asm volatile("red.global.add.v2.f32 [%0], {%1,%2};" ::"l"(p), "f"(a), "f"(b) : "memory");
}
__device__ __forceinline__ void red_add2_p(bool on, float* p, float a, float b) {
  asm volatile("{\n.reg .pred p;\nsetp.ne.b32 p, %3, 0;\n@p red.global.add.v2.f32 [%0], {%1,%2};\n}\n" ::"l"(p), "f"(a), "f"(b), "r"((int)on) : "memory");
}
__device__ __forceinline__ void red_add4(float* p, float a, float b, float c, float d) {
  asm volatile("red.global.add.v4.f32 [%0], {%1,%2,%3,%4};" ::"l"(p), "f"(a), "f"(b), "f"(c), "f"(d) : "memory");
}
__device__ __forceinline__ void red_add1(float* p, float a) {
  asm volatile("red.global.add.f32 [%0], %1;" ::"l"(p), "f"(a) : "memory");
}
__device__ __forceinline__ void l2_prefetch(const void* p, uint32_t bytes) {
  asm volatile("cp.async.bulk.prefetch.L2.global [%0], %1;" ::"l"(p), "r"(bytes) : "memory");
}

__device__ __forceinline__ void wgmma_n256(float (&d)[192], uint64_t da, uint64_t db, int scale_d) {
  asm volatile("{\n.reg .pred p;\nsetp.ne.b32 p, %130, 0;\n"
    "wgmma.mma_async.sync.aligned.m64n256k16.f32.bf16.bf16 {%0, %1, %2, %3, %4, %5, %6, %7, %8, %9, %10, %11, %12, %13, %14, %15, %16, %17, %18, %19, %20, %21, %22, %23, %24, %25, %26, %27, %28, %29, %30, %31, %32, %33, %34, %35, %36, %37, %38, %39, %40, %41, %42, %43, %44, %45, %46, %47, %48, %49, %50, %51, %52, %53, %54, %55, %56, %57, %58, %59, %60, %61, %62, %63, %64, %65, %66, %67, %68, %69, %70, %71, %72, %73, %74, %75, %76, %77, %78, %79, %80, %81, %82, %83, %84, %85, %86, %87, %88, %89, %90, %91, %92, %93, %94, %95, %96, %97, %98, %99, %100, %101, %102, %103, %104, %105, %106, %107, %108, %109, %110, %111, %112, %113, %114, %115, %116, %117, %118, %119, %120, %121, %122, %123, %124, %125, %126, %127}, %128, %129, p, 1, 1, 0, 1;\n}\n"
    : "+f"(d[0]), "+f"(d[1]), "+f"(d[2]), "+f"(d[3]), "+f"(d[4]), "+f"(d[5]), "+f"(d[6]), "+f"(d[7]), "+f"(d[8]), "+f"(d[9]), "+f"(d[10]), "+f"(d[11]), "+f"(d[12]), "+f"(d[13]), "+f"(d[14]), "+f"(d[15]), "+f"(d[16]), "+f"(d[17]), "+f"(d[18]), "+f"(d[19]), "+f"(d[20]), "+f"(d[21]), "+f"(d[22]), "+f"(d[23]), "+f"(d[24]), "+f"(d[25]), "+f"(d[26]), "+f"(d[27]), "+f"(d[28]), "+f"(d[29]), "+f"(d[30]), "+f"(d[31]), "+f"(d[32]), "+f"(d[33]), "+f"(d[34]), "+f"(d[35]), "+f"(d[36]), "+f"(d[37]), "+f"(d[38]), "+f"(d[39]), "+f"(d[40]), "+f"(d[41]), "+f"(d[42]), "+f"(d[43]), "+f"(d[44]), "+f"(d[45]), "+f"(d[46]), "+f"(d[47]), "+f"(d[48]), "+f"(d[49]), "+f"(d[50]), "+f"(d[51]), "+f"(d[52]), "+f"(d[53]), "+f"(d[54]), "+f"(d[55]), "+f"(d[56]), "+f"(d[57]), "+f"(d[58]), "+f"(d[59]), "+f"(d[60]), "+f"(d[61]), "+f"(d[62]), "+f"(d[63]), "+f"(d[64]), "+f"(d[65]), "+f"(d[66]), "+f"(d[67]), "+f"(d[68]), "+f"(d[69]), "+f"(d[70]), "+f"(d[71]), "+f"(d[72]), "+f"(d[73]), "+f"(d[74]), "+f"(d[75]), "+f"(d[76]), "+f"(d[77]), "+f"(d[78]), "+f"(d[79]), "+f"(d[80]), "+f"(d[81]), "+f"(d[82]), "+f"(d[83]), "+f"(d[84]), "+f"(d[85]), "+f"(d[86]), "+f"(d[87]), "+f"(d[88]), "+f"(d[89]), "+f"(d[90]), "+f"(d[91]), "+f"(d[92]), "+f"(d[93]), "+f"(d[94]), "+f"(d[95]), "+f"(d[96]), "+f"(d[97]), "+f"(d[98]), "+f"(d[99]), "+f"(d[100]), "+f"(d[101]), "+f"(d[102]), "+f"(d[103]), "+f"(d[104]), "+f"(d[105]), "+f"(d[106]), "+f"(d[107]), "+f"(d[108]), "+f"(d[109]), "+f"(d[110]), "+f"(d[111]), "+f"(d[112]), "+f"(d[113]), "+f"(d[114]), "+f"(d[115]), "+f"(d[116]), "+f"(d[117]), "+f"(d[118]), "+f"(d[119]), "+f"(d[120]), "+f"(d[121]), "+f"(d[122]), "+f"(d[123]), "+f"(d[124]), "+f"(d[125]), "+f"(d[126]), "+f"(d[127])
    : "l"(da), "l"(db), "r"(scale_d));
}
__device__ __forceinline__ void wgmma_n128(float (&d)[192], uint64_t da, uint64_t db, int scale_d) {
  asm volatile("{\n.reg .pred p;\nsetp.ne.b32 p, %66, 0;\n"
    "wgmma.mma_async.sync.aligned.m64n128k16.f32.bf16.bf16 {%0, %1, %2, %3, %4, %5, %6, %7, %8, %9, %10, %11, %12, %13, %14, %15, %16, %17, %18, %19, %20, %21, %22, %23, %24, %25, %26, %27, %28, %29, %30, %31, %32, %33, %34, %35, %36, %37, %38, %39, %40, %41, %42, %43, %44, %45, %46, %47, %48, %49, %50, %51, %52, %53, %54, %55, %56, %57, %58, %59, %60, %61, %62, %63}, %64, %65, p, 1, 1, 0, 1;\n}\n"
    : "+f"(d[128]), "+f"(d[129]), "+f"(d[130]), "+f"(d[131]), "+f"(d[132]), "+f"(d[133]), "+f"(d[134]), "+f"(d[135]), "+f"(d[136]), "+f"(d[137]), "+f"(d[138]), "+f"(d[139]), "+f"(d[140]), "+f"(d[141]), "+f"(d[142]), "+f"(d[143]), "+f"(d[144]), "+f"(d[145]), "+f"(d[146]), "+f"(d[147]), "+f"(d[148]), "+f"(d[149]), "+f"(d[150]), "+f"(d[151]), "+f"(d[152]), "+f"(d[153]), "+f"(d[154]), "+f"(d[155]), "+f"(d[156]), "+f"(d[157]), "+f"(d[158]), "+f"(d[159]), "+f"(d[160]), "+f"(d[161]), "+f"(d[162]), "+f"(d[163]), "+f"(d[164]), "+f"(d[165]), "+f"(d[166]), "+f"(d[167]), "+f"(d[168]), "+f"(d[169]), "+f"(d[170]), "+f"(d[171]), "+f"(d[172]), "+f"(d[173]), "+f"(d[174]), "+f"(d[175]), "+f"(d[176]), "+f"(d[177]), "+f"(d[178]), "+f"(d[179]), "+f"(d[180]), "+f"(d[181]), "+f"(d[182]), "+f"(d[183]), "+f"(d[184]), "+f"(d[185]), "+f"(d[186]), "+f"(d[187]), "+f"(d[188]), "+f"(d[189]), "+f"(d[190]), "+f"(d[191])
    : "l"(da), "l"(db), "r"(scale_d));
}
__device__ __forceinline__ void wgmma_n256_k(float (&d)[192], uint64_t da, uint64_t db, int scale_d) {
  asm volatile("{\n.reg .pred p;\nsetp.ne.b32 p, %130, 0;\n"
    "wgmma.mma_async.sync.aligned.m64n256k16.f32.bf16.bf16 {%0, %1, %2, %3, %4, %5, %6, %7, %8, %9, %10, %11, %12, %13, %14, %15, %16, %17, %18, %19, %20, %21, %22, %23, %24, %25, %26, %27, %28, %29, %30, %31, %32, %33, %34, %35, %36, %37, %38, %39, %40, %41, %42, %43, %44, %45, %46, %47, %48, %49, %50, %51, %52, %53, %54, %55, %56, %57, %58, %59, %60, %61, %62, %63, %64, %65, %66, %67, %68, %69, %70, %71, %72, %73, %74, %75, %76, %77, %78, %79, %80, %81, %82, %83, %84, %85, %86, %87, %88, %89, %90, %91, %92, %93, %94, %95, %96, %97, %98, %99, %100, %101, %102, %103, %104, %105, %106, %107, %108, %109, %110, %111, %112, %113, %114, %115, %116, %117, %118, %119, %120, %121, %122, %123, %124, %125, %126, %127}, %128, %129, p, 1, 1, 0, 0;\n}\n"
    : "+f"(d[0]), "+f"(d[1]), "+f"(d[2]), "+f"(d[3]), "+f"(d[4]), "+f"(d[5]), "+f"(d[6]), "+f"(d[7]), "+f"(d[8]), "+f"(d[9]), "+f"(d[10]), "+f"(d[11]), "+f"(d[12]), "+f"(d[13]), "+f"(d[14]), "+f"(d[15]), "+f"(d[16]), "+f"(d[17]), "+f"(d[18]), "+f"(d[19]), "+f"(d[20]), "+f"(d[21]), "+f"(d[22]), "+f"(d[23]), "+f"(d[24]), "+f"(d[25]), "+f"(d[26]), "+f"(d[27]), "+f"(d[28]), "+f"(d[29]), "+f"(d[30]), "+f"(d[31]), "+f"(d[32]), "+f"(d[33]), "+f"(d[34]), "+f"(d[35]), "+f"(d[36]), "+f"(d[37]), "+f"(d[38]), "+f"(d[39]), "+f"(d[40]), "+f"(d[41]), "+f"(d[42]), "+f"(d[43]), "+f"(d[44]), "+f"(d[45]), "+f"(d[46]), "+f"(d[47]), "+f"(d[48]), "+f"(d[49]), "+f"(d[50]), "+f"(d[51]), "+f"(d[52]), "+f"(d[53]), "+f"(d[54]), "+f"(d[55]), "+f"(d[56]), "+f"(d[57]), "+f"(d[58]), "+f"(d[59]), "+f"(d[60]), "+f"(d[61]), "+f"(d[62]), "+f"(d[63]), "+f"(d[64]), "+f"(d[65]), "+f"(d[66]), "+f"(d[67]), "+f"(d[68]), "+f"(d[69]), "+f"(d[70]), "+f"(d[71]), "+f"(d[72]), "+f"(d[73]), "+f"(d[74]), "+f"(d[75]), "+f"(d[76]), "+f"(d[77]), "+f"(d[78]), "+f"(d[79]), "+f"(d[80]), "+f"(d[81]), "+f"(d[82]), "+f"(d[83]), "+f"(d[84]), "+f"(d[85]), "+f"(d[86]), "+f"(d[87]), "+f"(d[88]), "+f"(d[89]), "+f"(d[90]), "+f"(d[91]), "+f"(d[92]), "+f"(d[93]), "+f"(d[94]), "+f"(d[95]), "+f"(d[96]), "+f"(d[97]), "+f"(d[98]), "+f"(d[99]), "+f"(d[100]), "+f"(d[101]), "+f"(d[102]), "+f"(d[103]), "+f"(d[104]), "+f"(d[105]), "+f"(d[106]), "+f"(d[107]), "+f"(d[108]), "+f"(d[109]), "+f"(d[110]), "+f"(d[111]), "+f"(d[112]), "+f"(d[113]), "+f"(d[114]), "+f"(d[115]), "+f"(d[116]), "+f"(d[117]), "+f"(d[118]), "+f"(d[119]), "+f"(d[120]), "+f"(d[121]), "+f"(d[122]), "+f"(d[123]), "+f"(d[124]), "+f"(d[125]), "+f"(d[126]), "+f"(d[127])
    : "l"(da), "l"(db), "r"(scale_d));
}
__device__ __forceinline__ void wgmma_n128_k(float (&d)[192], uint64_t da, uint64_t db, int scale_d) {
  asm volatile("{\n.reg .pred p;\nsetp.ne.b32 p, %66, 0;\n"
    "wgmma.mma_async.sync.aligned.m64n128k16.f32.bf16.bf16 {%0, %1, %2, %3, %4, %5, %6, %7, %8, %9, %10, %11, %12, %13, %14, %15, %16, %17, %18, %19, %20, %21, %22, %23, %24, %25, %26, %27, %28, %29, %30, %31, %32, %33, %34, %35, %36, %37, %38, %39, %40, %41, %42, %43, %44, %45, %46, %47, %48, %49, %50, %51, %52, %53, %54, %55, %56, %57, %58, %59, %60, %61, %62, %63}, %64, %65, p, 1, 1, 0, 0;\n}\n"
    : "+f"(d[128]), "+f"(d[129]), "+f"(d[130]), "+f"(d[131]), "+f"(d[132]), "+f"(d[133]), "+f"(d[134]), "+f"(d[135]), "+f"(d[136]), "+f"(d[137]), "+f"(d[138]), "+f"(d[139]), "+f"(d[140]), "+f"(d[141]), "+f"(d[142]), "+f"(d[143]), "+f"(d[144]), "+f"(d[145]), "+f"(d[146]), "+f"(d[147]), "+f"(d[148]), "+f"(d[149]), "+f"(d[150]), "+f"(d[151]), "+f"(d[152]), "+f"(d[153]), "+f"(d[154]), "+f"(d[155]), "+f"(d[156]), "+f"(d[157]), "+f"(d[158]), "+f"(d[159]), "+f"(d[160]), "+f"(d[161]), "+f"(d[162]), "+f"(d[163]), "+f"(d[164]), "+f"(d[165]), "+f"(d[166]), "+f"(d[167]), "+f"(d[168]), "+f"(d[169]), "+f"(d[170]), "+f"(d[171]), "+f"(d[172]), "+f"(d[173]), "+f"(d[174]), "+f"(d[175]), "+f"(d[176]), "+f"(d[177]), "+f"(d[178]), "+f"(d[179]), "+f"(d[180]), "+f"(d[181]), "+f"(d[182]), "+f"(d[183]), "+f"(d[184]), "+f"(d[185]), "+f"(d[186]), "+f"(d[187]), "+f"(d[188]), "+f"(d[189]), "+f"(d[190]), "+f"(d[191])
    : "l"(da), "l"(db), "r"(scale_d));
}
__device__ __forceinline__ void wgmma_n40_tt(float (&d)[20], uint64_t da, uint64_t db, int scale_d) {
  asm volatile("{\n.reg .pred p;\nsetp.ne.b32 p, %22, 0;\n"
    "wgmma.mma_async.sync.aligned.m64n40k16.f32.bf16.bf16 {%0, %1, %2, %3, %4, %5, %6, %7, %8, %9, %10, %11, %12, %13, %14, %15, %16, %17, %18, %19}, %20, %21, p, 1, 1, 1, 1;\n}\n"
    : "+f"(d[0]), "+f"(d[1]), "+f"(d[2]), "+f"(d[3]), "+f"(d[4]), "+f"(d[5]), "+f"(d[6]), "+f"(d[7]), "+f"(d[8]), "+f"(d[9]), "+f"(d[10]), "+f"(d[11]), "+f"(d[12]), "+f"(d[13]), "+f"(d[14]), "+f"(d[15]), "+f"(d[16]), "+f"(d[17]), "+f"(d[18]), "+f"(d[19])
    : "l"(da), "l"(db), "r"(scale_d));
}
__device__ __forceinline__ void wgmma_n40_rs(float (&d)[20], const uint32_t (&a)[4], uint64_t db, int scale_d) {
  asm volatile("{\n.reg .pred p;\nsetp.ne.b32 p, %25, 0;\n"
    "wgmma.mma_async.sync.aligned.m64n40k16.f32.bf16.bf16 {%0, %1, %2, %3, %4, %5, %6, %7, %8, %9, %10, %11, %12, %13, %14, %15, %16, %17, %18, %19}, {%20, %21, %22, %23}, %24, p, 1, 1, 1;\n}\n"
    : "+f"(d[0]), "+f"(d[1]), "+f"(d[2]), "+f"(d[3]), "+f"(d[4]), "+f"(d[5]), "+f"(d[6]), "+f"(d[7]), "+f"(d[8]), "+f"(d[9]), "+f"(d[10]), "+f"(d[11]), "+f"(d[12]), "+f"(d[13]), "+f"(d[14]), "+f"(d[15]), "+f"(d[16]), "+f"(d[17]), "+f"(d[18]), "+f"(d[19])
    : "r"(a[0]), "r"(a[1]), "r"(a[2]), "r"(a[3]), "l"(db), "r"(scale_d));
}
__device__ __forceinline__ void wgmma_n256_0(float (&d)[192], uint64_t da, uint64_t db) {
  asm volatile("{\n.reg .pred p;\nsetp.ne.b32 p, 0, 0;\n"
    "wgmma.mma_async.sync.aligned.m64n256k16.f32.bf16.bf16 {%0, %1, %2, %3, %4, %5, %6, %7, %8, %9, %10, %11, %12, %13, %14, %15, %16, %17, %18, %19, %20, %21, %22, %23, %24, %25, %26, %27, %28, %29, %30, %31, %32, %33, %34, %35, %36, %37, %38, %39, %40, %41, %42, %43, %44, %45, %46, %47, %48, %49, %50, %51, %52, %53, %54, %55, %56, %57, %58, %59, %60, %61, %62, %63, %64, %65, %66, %67, %68, %69, %70, %71, %72, %73, %74, %75, %76, %77, %78, %79, %80, %81, %82, %83, %84, %85, %86, %87, %88, %89, %90, %91, %92, %93, %94, %95, %96, %97, %98, %99, %100, %101, %102, %103, %104, %105, %106, %107, %108, %109, %110, %111, %112, %113, %114, %115, %116, %117, %118, %119, %120, %121, %122, %123, %124, %125, %126, %127}, %128, %129, p, 1, 1, 0, 1;\n}\n"
    : "=f"(d[0]), "=f"(d[1]), "=f"(d[2]), "=f"(d[3]), "=f"(d[4]), "=f"(d[5]), "=f"(d[6]), "=f"(d[7]), "=f"(d[8]), "=f"(d[9]), "=f"(d[10]), "=f"(d[11]), "=f"(d[12]), "=f"(d[13]), "=f"(d[14]), "=f"(d[15]), "=f"(d[16]), "=f"(d[17]), "=f"(d[18]), "=f"(d[19]), "=f"(d[20]), "=f"(d[21]), "=f"(d[22]), "=f"(d[23]), "=f"(d[24]), "=f"(d[25]), "=f"(d[26]), "=f"(d[27]), "=f"(d[28]), "=f"(d[29]), "=f"(d[30]), "=f"(d[31]), "=f"(d[32]), "=f"(d[33]), "=f"(d[34]), "=f"(d[35]), "=f"(d[36]), "=f"(d[37]), "=f"(d[38]), "=f"(d[39]), "=f"(d[40]), "=f"(d[41]), "=f"(d[42]), "=f"(d[43]), "=f"(d[44]), "=f"(d[45]), "=f"(d[46]), "=f"(d[47]), "=f"(d[48]), "=f"(d[49]), "=f"(d[50]), "=f"(d[51]), "=f"(d[52]), "=f"(d[53]), "=f"(d[54]), "=f"(d[55]), "=f"(d[56]), "=f"(d[57]), "=f"(d[58]), "=f"(d[59]), "=f"(d[60]), "=f"(d[61]), "=f"(d[62]), "=f"(d[63]), "=f"(d[64]), "=f"(d[65]), "=f"(d[66]), "=f"(d[67]), "=f"(d[68]), "=f"(d[69]), "=f"(d[70]), "=f"(d[71]), "=f"(d[72]), "=f"(d[73]), "=f"(d[74]), "=f"(d[75]), "=f"(d[76]), "=f"(d[77]), "=f"(d[78]), "=f"(d[79]), "=f"(d[80]), "=f"(d[81]), "=f"(d[82]), "=f"(d[83]), "=f"(d[84]), "=f"(d[85]), "=f"(d[86]), "=f"(d[87]), "=f"(d[88]), "=f"(d[89]), "=f"(d[90]), "=f"(d[91]), "=f"(d[92]), "=f"(d[93]), "=f"(d[94]), "=f"(d[95]), "=f"(d[96]), "=f"(d[97]), "=f"(d[98]), "=f"(d[99]), "=f"(d[100]), "=f"(d[101]), "=f"(d[102]), "=f"(d[103]), "=f"(d[104]), "=f"(d[105]), "=f"(d[106]), "=f"(d[107]), "=f"(d[108]), "=f"(d[109]), "=f"(d[110]), "=f"(d[111]), "=f"(d[112]), "=f"(d[113]), "=f"(d[114]), "=f"(d[115]), "=f"(d[116]), "=f"(d[117]), "=f"(d[118]), "=f"(d[119]), "=f"(d[120]), "=f"(d[121]), "=f"(d[122]), "=f"(d[123]), "=f"(d[124]), "=f"(d[125]), "=f"(d[126]), "=f"(d[127])
    : "l"(da), "l"(db));
}
__device__ __forceinline__ void wgmma_n128_0(float (&d)[192], uint64_t da, uint64_t db) {
  asm volatile("{\n.reg .pred p;\nsetp.ne.b32 p, 0, 0;\n"
    "wgmma.mma_async.sync.aligned.m64n128k16.f32.bf16.bf16 {%0, %1, %2, %3, %4, %5, %6, %7, %8, %9, %10, %11, %12, %13, %14, %15, %16, %17, %18, %19, %20, %21, %22, %23, %24, %25, %26, %27, %28, %29, %30, %31, %32, %33, %34, %35, %36, %37, %38, %39, %40, %41, %42, %43, %44, %45, %46, %47, %48, %49, %50, %51, %52, %53, %54, %55, %56, %57, %58, %59, %60, %61, %62, %63}, %64, %65, p, 1, 1, 0, 1;\n}\n"
    : "=f"(d[128]), "=f"(d[129]), "=f"(d[130]), "=f"(d[131]), "=f"(d[132]), "=f"(d[133]), "=f"(d[134]), "=f"(d[135]), "=f"(d[136]), "=f"(d[137]), "=f"(d[138]), "=f"(d[139]), "=f"(d[140]), "=f"(d[141]), "=f"(d[142]), "=f"(d[143]), "=f"(d[144]), "=f"(d[145]), "=f"(d[146]), "=f"(d[147]), "=f"(d[148]), "=f"(d[149]), "=f"(d[150]), "=f"(d[151]), "=f"(d[152]), "=f"(d[153]), "=f"(d[154]), "=f"(d[155]), "=f"(d[156]), "=f"(d[157]), "=f"(d[158]), "=f"(d[159]), "=f"(d[160]), "=f"(d[161]), "=f"(d[162]), "=f"(d[163]), "=f"(d[164]), "=f"(d[165]), "=f"(d[166]), "=f"(d[167]), "=f"(d[168]), "=f"(d[169]), "=f"(d[170]), "=f"(d[171]), "=f"(d[172]), "=f"(d[173]), "=f"(d[174]), "=f"(d[175]), "=f"(d[176]), "=f"(d[177]), "=f"(d[178]), "=f"(d[179]), "=f"(d[180]), "=f"(d[181]), "=f"(d[182]), "=f"(d[183]), "=f"(d[184]), "=f"(d[185]), "=f"(d[186]), "=f"(d[187]), "=f"(d[188]), "=f"(d[189]), "=f"(d[190]), "=f"(d[191])
    : "l"(da), "l"(db));
}
__device__ __forceinline__ void wgmma_n128_rs(float (&d)[192], const uint32_t (&a)[4], uint64_t db, int scale_d) {
  asm volatile("{\n.reg .pred p;\nsetp.ne.b32 p, %69, 0;\n"
    "wgmma.mma_async.sync.aligned.m64n128k16.f32.bf16.bf16 {%0, %1, %2, %3, %4, %5, %6, %7, %8, %9, %10, %11, %12, %13, %14, %15, %16, %17, %18, %19, %20, %21, %22, %23, %24, %25, %26, %27, %28, %29, %30, %31, %32, %33, %34, %35, %36, %37, %38, %39, %40, %41, %42, %43, %44, %45, %46, %47, %48, %49, %50, %51, %52, %53, %54, %55, %56, %57, %58, %59, %60, %61, %62, %63}, {%64, %65, %66, %67}, %68, p, 1, 1, 1;\n}\n"
    : "+f"(d[128]), "+f"(d[129]), "+f"(d[130]), "+f"(d[131]), "+f"(d[132]), "+f"(d[133]), "+f"(d[134]), "+f"(d[135]), "+f"(d[136]), "+f"(d[137]), "+f"(d[138]), "+f"(d[139]), "+f"(d[140]), "+f"(d[141]), "+f"(d[142]), "+f"(d[143]), "+f"(d[144]), "+f"(d[145]), "+f"(d[146]), "+f"(d[147]), "+f"(d[148]), "+f"(d[149]), "+f"(d[150]), "+f"(d[151]), "+f"(d[152]), "+f"(d[153]), "+f"(d[154]), "+f"(d[155]), "+f"(d[156]), "+f"(d[157]), "+f"(d[158]), "+f"(d[159]), "+f"(d[160]), "+f"(d[161]), "+f"(d[162]), "+f"(d[163]), "+f"(d[164]), "+f"(d[165]), "+f"(d[166]), "+f"(d[167]), "+f"(d[168]), "+f"(d[169]), "+f"(d[170]), "+f"(d[171]), "+f"(d[172]), "+f"(d[173]), "+f"(d[174]), "+f"(d[175]), "+f"(d[176]), "+f"(d[177]), "+f"(d[178]), "+f"(d[179]), "+f"(d[180]), "+f"(d[181]), "+f"(d[182]), "+f"(d[183]), "+f"(d[184]), "+f"(d[185]), "+f"(d[186]), "+f"(d[187]), "+f"(d[188]), "+f"(d[189]), "+f"(d[190]), "+f"(d[191])
    : "r"(a[0]), "r"(a[1]), "r"(a[2]), "r"(a[3]), "l"(db), "r"(scale_d));
}
__device__ __forceinline__ void wgmma_n32_0(float (&d)[16], uint64_t da, uint64_t db) {
  asm volatile("{\n.reg .pred p;\nsetp.ne.b32 p, 0, 0;\n"
    "wgmma.mma_async.sync.aligned.m64n32k16.f32.bf16.bf16 {%0, %1, %2, %3, %4, %5, %6, %7, %8, %9, %10, %11, %12, %13, %14, %15}, %16, %17, p, 1, 1, 0, 1;\n}\n"
    : "=f"(d[0]), "=f"(d[1]), "=f"(d[2]), "=f"(d[3]), "=f"(d[4]), "=f"(d[5]), "=f"(d[6]), "=f"(d[7]), "=f"(d[8]), "=f"(d[9]), "=f"(d[10]), "=f"(d[11]), "=f"(d[12]), "=f"(d[13]), "=f"(d[14]), "=f"(d[15])
    : "l"(da), "l"(db));
}
__device__ __forceinline__ void wgmma_n32(float (&d)[16], uint64_t da, uint64_t db, int scale_d) {
  asm volatile("{\n.reg .pred p;\nsetp.ne.b32 p, %18, 0;\n"
    "wgmma.mma_async.sync.aligned.m64n32k16.f32.bf16.bf16 {%0, %1, %2, %3, %4, %5, %6, %7, %8, %9, %10, %11, %12, %13, %14, %15}, %16, %17, p, 1, 1, 0, 1;\n}\n"
    : "+f"(d[0]), "+f"(d[1]), "+f"(d[2]), "+f"(d[3]), "+f"(d[4]), "+f"(d[5]), "+f"(d[6]), "+f"(d[7]), "+f"(d[8]), "+f"(d[9]), "+f"(d[10]), "+f"(d[11]), "+f"(d[12]), "+f"(d[13]), "+f"(d[14]), "+f"(d[15])
    : "l"(da), "l"(db), "r"(scale_d));
}
__device__ __forceinline__ void wgmma_n8_t(float (&d)[4], uint64_t da, uint64_t db, int scale_d) {
  asm volatile("{\n.reg .pred p;\nsetp.ne.b32 p, %6, 0;\n"
    "wgmma.mma_async.sync.aligned.m64n8k16.f32.bf16.bf16 {%0, %1, %2, %3}, %4, %5, p, 1, 1, 1, 0;\n}\n"
    : "+f"(d[0]), "+f"(d[1]), "+f"(d[2]), "+f"(d[3])
    : "l"(da), "l"(db), "r"(scale_d));
}
__device__ __forceinline__ void wgmma_n64_lo(float (&d)[192], uint64_t da, uint64_t db, int scale_d) {
  asm volatile("{\n.reg .pred p;\nsetp.ne.b32 p, %34, 0;\n"
    "wgmma.mma_async.sync.aligned.m64n64k16.f32.bf16.bf16 {%0, %1, %2, %3, %4, %5, %6, %7, %8, %9, %10, %11, %12, %13, %14, %15, %16, %17, %18, %19, %20, %21, %22, %23, %24, %25, %26, %27, %28, %29, %30, %31}, %32, %33, p, 1, 1, 0, 1;\n}\n"
    : "+f"(d[128]), "+f"(d[129]), "+f"(d[130]), "+f"(d[131]), "+f"(d[132]), "+f"(d[133]), "+f"(d[134]), "+f"(d[135]), "+f"(d[136]), "+f"(d[137]), "+f"(d[138]), "+f"(d[139]), "+f"(d[140]), "+f"(d[141]), "+f"(d[142]), "+f"(d[143]), "+f"(d[144]), "+f"(d[145]), "+f"(d[146]), "+f"(d[147]), "+f"(d[148]), "+f"(d[149]), "+f"(d[150]), "+f"(d[151]), "+f"(d[152]), "+f"(d[153]), "+f"(d[154]), "+f"(d[155]), "+f"(d[156]), "+f"(d[157]), "+f"(d[158]), "+f"(d[159])
    : "l"(da), "l"(db), "r"(scale_d));
}
__device__ __forceinline__ void wgmma_n64_hi(float (&d)[192], uint64_t da, uint64_t db, int scale_d) {
  asm volatile("{\n.reg .pred p;\nsetp.ne.b32 p, %34, 0;\n"
    "wgmma.mma_async.sync.aligned.m64n64k16.f32.bf16.bf16 {%0, %1, %2, %3, %4, %5, %6, %7, %8, %9, %10, %11, %12, %13, %14, %15, %16, %17, %18, %19, %20, %21, %22, %23, %24, %25, %26, %27, %28, %29, %30, %31}, %32, %33, p, 1, 1, 0, 1;\n}\n"
    : "+f"(d[160]), "+f"(d[161]), "+f"(d[162]), "+f"(d[163]), "+f"(d[164]), "+f"(d[165]), "+f"(d[166]), "+f"(d[167]), "+f"(d[168]), "+f"(d[169]), "+f"(d[170]), "+f"(d[171]), "+f"(d[172]), "+f"(d[173]), "+f"(d[174]), "+f"(d[175]), "+f"(d[176]), "+f"(d[177]), "+f"(d[178]), "+f"(d[179]), "+f"(d[180]), "+f"(d[181]), "+f"(d[182]), "+f"(d[183]), "+f"(d[184]), "+f"(d[185]), "+f"(d[186]), "+f"(d[187]), "+f"(d[188]), "+f"(d[189]), "+f"(d[190]), "+f"(d[191])
    : "l"(da), "l"(db), "r"(scale_d));
}
__device__ __forceinline__ void wgmma_n128_rs0(float (&d)[192], const uint32_t (&a)[4], uint64_t db) {
  asm volatile("{\n.reg .pred p;\nsetp.ne.b32 p, 0, 0;\n"
    "wgmma.mma_async.sync.aligned.m64n128k16.f32.bf16.bf16 {%0, %1, %2, %3, %4, %5, %6, %7, %8, %9, %10, %11, %12, %13, %14, %15, %16, %17, %18, %19, %20, %21, %22, %23, %24, %25, %26, %27, %28, %29, %30, %31, %32, %33, %34, %35, %36, %37, %38, %39, %40, %41, %42, %43, %44, %45, %46, %47, %48, %49, %50, %51, %52, %53, %54, %55, %56, %57, %58, %59, %60, %61, %62, %63}, {%64, %65, %66, %67}, %68, p, 1, 1, 1;\n}\n"
    : "=f"(d[128]), "=f"(d[129]), "=f"(d[130]), "=f"(d[131]), "=f"(d[132]), "=f"(d[133]), "=f"(d[134]), "=f"(d[135]), "=f"(d[136]), "=f"(d[137]), "=f"(d[138]), "=f"(d[139]), "=f"(d[140]), "=f"(d[141]), "=f"(d[142]), "=f"(d[143]), "=f"(d[144]), "=f"(d[145]), "=f"(d[146]), "=f"(d[147]), "=f"(d[148]), "=f"(d[149]), "=f"(d[150]), "=f"(d[151]), "=f"(d[152]), "=f"(d[153]), "=f"(d[154]), "=f"(d[155]), "=f"(d[156]), "=f"(d[157]), "=f"(d[158]), "=f"(d[159]), "=f"(d[160]), "=f"(d[161]), "=f"(d[162]), "=f"(d[163]), "=f"(d[164]), "=f"(d[165]), "=f"(d[166]), "=f"(d[167]), "=f"(d[168]), "=f"(d[169]), "=f"(d[170]), "=f"(d[171]), "=f"(d[172]), "=f"(d[173]), "=f"(d[174]), "=f"(d[175]), "=f"(d[176]), "=f"(d[177]), "=f"(d[178]), "=f"(d[179]), "=f"(d[180]), "=f"(d[181]), "=f"(d[182]), "=f"(d[183]), "=f"(d[184]), "=f"(d[185]), "=f"(d[186]), "=f"(d[187]), "=f"(d[188]), "=f"(d[189]), "=f"(d[190]), "=f"(d[191])
    : "r"(a[0]), "r"(a[1]), "r"(a[2]), "r"(a[3]), "l"(db));
}
__device__ __forceinline__ void wgmma_n256_rs(float (&d)[192], const uint32_t (&a)[4], uint64_t db, int scale_d) {
  asm volatile("{\n.reg .pred p;\nsetp.ne.b32 p, %133, 0;\n"
    "wgmma.mma_async.sync.aligned.m64n256k16.f32.bf16.bf16 {%0, %1, %2, %3, %4, %5, %6, %7, %8, %9, %10, %11, %12, %13, %14, %15, %16, %17, %18, %19, %20, %21, %22, %23, %24, %25, %26, %27, %28, %29, %30, %31, %32, %33, %34, %35, %36, %37, %38, %39, %40, %41, %42, %43, %44, %45, %46, %47, %48, %49, %50, %51, %52, %53, %54, %55, %56, %57, %58, %59, %60, %61, %62, %63, %64, %65, %66, %67, %68, %69, %70, %71, %72, %73, %74, %75, %76, %77, %78, %79, %80, %81, %82, %83, %84, %85, %86, %87, %88, %89, %90, %91, %92, %93, %94, %95, %96, %97, %98, %99, %100, %101, %102, %103, %104, %105, %106, %107, %108, %109, %110, %111, %112, %113, %114, %115, %116, %117, %118, %119, %120, %121, %122, %123, %124, %125, %126, %127}, {%128, %129, %130, %131}, %132, p, 1, 1, 1;\n}\n"
    : "+f"(d[0]), "+f"(d[1]), "+f"(d[2]), "+f"(d[3]), "+f"(d[4]), "+f"(d[5]), "+f"(d[6]), "+f"(d[7]), "+f"(d[8]), "+f"(d[9]), "+f"(d[10]), "+f"(d[11]), "+f"(d[12]), "+f"(d[13]), "+f"(d[14]), "+f"(d[15]), "+f"(d[16]), "+f"(d[17]), "+f"(d[18]), "+f"(d[19]), "+f"(d[20]), "+f"(d[21]), "+f"(d[22]), "+f"(d[23]), "+f"(d[24]), "+f"(d[25]), "+f"(d[26]), "+f"(d[27]), "+f"(d[28]), "+f"(d[29]), "+f"(d[30]), "+f"(d[31]), "+f"(d[32]), "+f"(d[33]), "+f"(d[34]), "+f"(d[35]), "+f"(d[36]), "+f"(d[37]), "+f"(d[38]), "+f"(d[39]), "+f"(d[40]), "+f"(d[41]), "+f"(d[42]), "+f"(d[43]), "+f"(d[44]), "+f"(d[45]), "+f"(d[46]), "+f"(d[47]), "+f"(d[48]), "+f"(d[49]), "+f"(d[50]), "+f"(d[51]), "+f"(d[52]), "+f"(d[53]), "+f"(d[54]), "+f"(d[55]), "+f"(d[56]), "+f"(d[57]), "+f"(d[58]), "+f"(d[59]), "+f"(d[60]), "+f"(d[61]), "+f"(d[62]), "+f"(d[63]), "+f"(d[64]), "+f"(d[65]), "+f"(d[66]), "+f"(d[67]), "+f"(d[68]), "+f"(d[69]), "+f"(d[70]), "+f"(d[71]), "+f"(d[72]), "+f"(d[73]), "+f"(d[74]), "+f"(d[75]), "+f"(d[76]), "+f"(d[77]), "+f"(d[78]), "+f"(d[79]), "+f"(d[80]), "+f"(d[81]), "+f"(d[82]), "+f"(d[83]), "+f"(d[84]), "+f"(d[85]), "+f"(d[86]), "+f"(d[87]), "+f"(d[88]), "+f"(d[89]), "+f"(d[90]), "+f"(d[91]), "+f"(d[92]), "+f"(d[93]), "+f"(d[94]), "+f"(d[95]), "+f"(d[96]), "+f"(d[97]), "+f"(d[98]), "+f"(d[99]), "+f"(d[100]), "+f"(d[101]), "+f"(d[102]), "+f"(d[103]), "+f"(d[104]), "+f"(d[105]), "+f"(d[106]), "+f"(d[107]), "+f"(d[108]), "+f"(d[109]), "+f"(d[110]), "+f"(d[111]), "+f"(d[112]), "+f"(d[113]), "+f"(d[114]), "+f"(d[115]), "+f"(d[116]), "+f"(d[117]), "+f"(d[118]), "+f"(d[119]), "+f"(d[120]), "+f"(d[121]), "+f"(d[122]), "+f"(d[123]), "+f"(d[124]), "+f"(d[125]), "+f"(d[126]), "+f"(d[127])
    : "r"(a[0]), "r"(a[1]), "r"(a[2]), "r"(a[3]), "l"(db), "r"(scale_d));
}
__device__ __forceinline__ void wgmma_n256_rs0(float (&d)[192], const uint32_t (&a)[4], uint64_t db) {
  asm volatile("{\n.reg .pred p;\nsetp.ne.b32 p, 0, 0;\n"
    "wgmma.mma_async.sync.aligned.m64n256k16.f32.bf16.bf16 {%0, %1, %2, %3, %4, %5, %6, %7, %8, %9, %10, %11, %12, %13, %14, %15, %16, %17, %18, %19, %20, %21, %22, %23, %24, %25, %26, %27, %28, %29, %30, %31, %32, %33, %34, %35, %36, %37, %38, %39, %40, %41, %42, %43, %44, %45, %46, %47, %48, %49, %50, %51, %52, %53, %54, %55, %56, %57, %58, %59, %60, %61, %62, %63, %64, %65, %66, %67, %68, %69, %70, %71, %72, %73, %74, %75, %76, %77, %78, %79, %80, %81, %82, %83, %84, %85, %86, %87, %88, %89, %90, %91, %92, %93, %94, %95, %96, %97, %98, %99, %100, %101, %102, %103, %104, %105, %106, %107, %108, %109, %110, %111, %112, %113, %114, %115, %116, %117, %118, %119, %120, %121, %122, %123, %124, %125, %126, %127}, {%128, %129, %130, %131}, %132, p, 1, 1, 1;\n}\n"
    : "=f"(d[0]), "=f"(d[1]), "=f"(d[2]), "=f"(d[3]), "=f"(d[4]), "=f"(d[5]), "=f"(d[6]), "=f"(d[7]), "=f"(d[8]), "=f"(d[9]), "=f"(d[10]), "=f"(d[11]), "=f"(d[12]), "=f"(d[13]), "=f"(d[14]), "=f"(d[15]), "=f"(d[16]), "=f"(d[17]), "=f"(d[18]), "=f"(d[19]), "=f"(d[20]), "=f"(d[21]), "=f"(d[22]), "=f"(d[23]), "=f"(d[24]), "=f"(d[25]), "=f"(d[26]), "=f"(d[27]), "=f"(d[28]), "=f"(d[29]), "=f"(d[30]), "=f"(d[31]), "=f"(d[32]), "=f"(d[33]), "=f"(d[34]), "=f"(d[35]), "=f"(d[36]), "=f"(d[37]), "=f"(d[38]), "=f"(d[39]), "=f"(d[40]), "=f"(d[41]), "=f"(d[42]), "=f"(d[43]), "=f"(d[44]), "=f"(d[45]), "=f"(d[46]), "=f"(d[47]), "=f"(d[48]), "=f"(d[49]), "=f"(d[50]), "=f"(d[51]), "=f"(d[52]), "=f"(d[53]), "=f"(d[54]), "=f"(d[55]), "=f"(d[56]), "=f"(d[57]), "=f"(d[58]), "=f"(d[59]), "=f"(d[60]), "=f"(d[61]), "=f"(d[62]), "=f"(d[63]), "=f"(d[64]), "=f"(d[65]), "=f"(d[66]), "=f"(d[67]), "=f"(d[68]), "=f"(d[69]), "=f"(d[70]), "=f"(d[71]), "=f"(d[72]), "=f"(d[73]), "=f"(d[74]), "=f"(d[75]), "=f"(d[76]), "=f"(d[77]), "=f"(d[78]), "=f"(d[79]), "=f"(d[80]), "=f"(d[81]), "=f"(d[82]), "=f"(d[83]), "=f"(d[84]), "=f"(d[85]), "=f"(d[86]), "=f"(d[87]), "=f"(d[88]), "=f"(d[89]), "=f"(d[90]), "=f"(d[91]), "=f"(d[92]), "=f"(d[93]), "=f"(d[94]), "=f"(d[95]), "=f"(d[96]), "=f"(d[97]), "=f"(d[98]), "=f"(d[99]), "=f"(d[100]), "=f"(d[101]), "=f"(d[102]), "=f"(d[103]), "=f"(d[104]), "=f"(d[105]), "=f"(d[106]), "=f"(d[107]), "=f"(d[108]), "=f"(d[109]), "=f"(d[110]), "=f"(d[111]), "=f"(d[112]), "=f"(d[113]), "=f"(d[114]), "=f"(d[115]), "=f"(d[116]), "=f"(d[117]), "=f"(d[118]), "=f"(d[119]), "=f"(d[120]), "=f"(d[121]), "=f"(d[122]), "=f"(d[123]), "=f"(d[124]), "=f"(d[125]), "=f"(d[126]), "=f"(d[127])
    : "r"(a[0]), "r"(a[1]), "r"(a[2]), "r"(a[3]), "l"(db));
}

constexpr int SLOT = 16384;
constexpr int VB = 4 * SLOT, PH = 0, XS = 6;
constexpr int SM_SD = 13 * SLOT;
constexpr int SM_BAR = SM_SD + 8192;
constexpr int SM_RS = SM_BAR + 1024;
constexpr int SM_AP = SM_RS + 640;
constexpr int SM_BP = SM_AP + 2048;
constexpr int SM_EPOCH = SM_BP + 6144;
constexpr int SM_TOTAL = SM_EPOCH + 16;
constexpr int FM = 0, FT = 16, FW = 30, CM = 46, CT = 62, CW = 76, B_EF = 92, B_STAT = 93, B_KVF = 94, B_HALO = 95,
              B_KVDONE = 96, B_OH0 = 97, B_OH1 = 98, B_XH0 = 99, B_XDONE = 100, B_WFD = 101, B_XT = 102, B_OF0 = 103, B_KVF1 = 104, B_RAW = 106  , B_X0 = 108;
constexpr uint64_t BAR_LG = 0x00043333330004ull;
#define BA(i) (bar + (i) * 8)
#define REL2(i) release2c(SB0 + SM_BAR + (i) * 8)
constexpr int NF = 4, ND = 12, NR = 0, NWOP = 48, NAOP = 37;
constexpr uint64_t TL_A = 0x278627862786ull, TL_B = 0xac39bac39bacull, WO_A = 0x764a2396b4ac39ffull, WO_B = 0xc8b51c780512786bull;
__constant__ uint32_t c_wop[NWOP + 1] = {0xea8009, 0x186b8000, 0x26b8112, 0x18ec011a, 0x6c8224, 0x22ec822b, 0x170330, 0x22970339, 0x18178442, 0x18180554, 0x18188660, 0x18190772, 0x18198884, 0x181a0990, 0x181a8aa2, 0x181b0bb4, 0x181b8cc0, 0xaed90fc, 0xa9791ea, 0x181c0dd2, 0xa9812db, 0x129893c9, 0x181c8ee4, 0x181d0ff0, 0x109d94b3, 0x109f15ac, 0x109f969a, 0x10a0178b, 0x10a09879, 0x10a11963, 0x10a19a5c, 0x10a21b4a, 0x9229e0b, 0x9231f16, 0x1123a028, 0x11242137, 0x1124a242, 0x112e2351, 0x132e2465, 0x132e2570, 0x11272688, 0x1127a797, 0x112828ac, 0x1128a9b1, 0x11292ac5, 0x1129abdb, 0x112a2ce8, 0x112b2dfc, 0};
__constant__ uint32_t c_aop[NAOP + 1] = {0x6d0228, 0x170336, 0x178447, 0x180558, 0x188666, 0x190777, 0x198888, 0x1a0996, 0x1a8aa7, 0x1b0bb8, 0x1b8cc6, 0x1c0dd7, 0x1c8ee8, 0x1d0ff6, 0x1d93c2, 0x1f14b6, 0x1f95a8, 0x201697, 0x209782, 0x211876, 0x219968, 0x221a57, 0x229b42, 0xa32029, 0xa3a133, 0xa4224c, 0xa4a35a, 0xae2464, 0xa6257b, 0xa6a686, 0xa72799, 0xa7a8a3, 0xa829b2, 0xa8aaca, 0xa92bd4, 0xaa2ce6, 0xaaadf7, 0};
__constant__ uint32_t c_map[64] = {4, 5, 6, 7, 0, 16, 32, 48, 64, 80, 96, 112, 1, 17, 33, 49, 65, 81, 97, 113, 2, 18, 34, 50, 66, 82, 98, 114, 3, 19, 35, 51, 67, 83, 99, 115, 20, 36, 52, 68, 84, 100, 116, 21, 37, 53, 69, 85, 101, 117, 22, 38, 54, 70, 86, 102, 118, 23, 39, 55, 71, 87, 103, 119};
enum { MAP_WF = 0, MAP_WA = 2, MAP_WB = 4, MAP_WOA = 6, MAP_WOB = 8, MAP_X0 = 10, MAP_X = 11, MAP_O = 12, MAP_PHI = 13, NMAP = 14 };
struct Maps { CUtensorMap m[NMAP]; };

#define PL 2
#define PROFL(a, b)
#define SUBS 8
#define QORD 1
#define NCH 4
#define CHW 1
#define DRAIN 0
#define SUBS1 12
#define XRAT 9
#define PFW 0
#define XRN 2
#define BT1 1
#define CV0 0
#define ST1 8
#define FASTP 0
#define O1P 2
#define X0AT 1
#define W1DL 400
#define WFDL 0
#define NLAYERS 4
constexpr float L2E = 1.4426950408889634f;

#define D128(lo) desc64(lo, 0x40000040u)
struct Ctx { uint32_t zero, boff; const bf16* x0; bf16* out; };
#define BLK_CTX() \
  uint32_t bid_; asm volatile("mov.u32 %0, %%ctaid.x;" : "=r"(bid_)); \
  bid_ -= c.boff; \
  const uint32_t gr_ = c_map[bid_ >> 1]; \
  const int cr = bid_ & 1, g = gr_ & 7, rb = (gr_ >> 3) + cr, m0 = rb * 128; \
  const uint32_t sb = SB0 + (cr << 24); \
  const uint32_t bar = sb + SM_BAR; \
  (void)cr; (void)g; (void)rb; (void)m0; (void)bar;
extern __shared__ uint8_t smem_raw[];
constexpr uint32_t SB0 = 1024;

#define PHASE_CTX() \
  BLK_CTX(); \
  int tid_ = threadIdx.x; asm volatile("" : "+r"(tid_)); \
  const int lane = tid_ & 31, cw = (tid_ >> 5) - 4, wg = cw >> 2, wq = cw & 3, gq = lane >> 2, t = lane & 3, wrow0 = cw * 16; \
  const int lrow = (lane & 7) + ((lane >> 3) & 1) * 8, lchk = lane >> 4; \
  const bool elected = (tid_ & 127) == 0; \
  const uint32_t rowo = (wrow0 + lrow) * 128, X = (lchk ^ (lane & 7)) << 4; \
  const uint32_t Y = (wrow0 + (lane & 7)) * 128 + (((lane >> 3) ^ (lane & 7)) << 4); \
  const size_t gfr = (size_t)(m0 + wrow0 + gq) * D_ + g * 128 + 8 * t; \
  (void)bar; (void)wq; (void)gq; (void)lrow; (void)lchk; (void)elected; (void)wrow0; (void)wg; (void)rowo; (void)X; (void)t; (void)Y; (void)gfr;
#define MMA_CTX() \
  const uint32_t wu = __shfl_sync(0xffffffffu, wg, 0); \
  const uint32_t dA0 = ((SB0 >> 4) | (1u << 16)) + wu * 512, dB0 = (SB0 >> 4) | (512u << 16); \
  const uint32_t par = layer & 1;

__device__ __forceinline__ void slab_out_half(uint32_t slot, bf16* dst, int wrow0, int lane) {
  const int r0 = lane >> 3, ch = lane & 7;
  const uint32_t src = slot + (wrow0 + r0) * 128;
  uint4 v[4];
#pragma unroll
  for (int i = 0; i < 4; ++i) v[i] = lds128(src + i * 512 + (((ch ^ (4 * i + r0)) & 7) << 4));
  dst += (size_t)(wrow0 + r0) * D_ + ch * 8;
#pragma unroll
  for (int i = 0; i < 4; ++i) *reinterpret_cast<uint4*>(dst + (size_t)i * 4 * D_) = v[i];
}

__device__ __forceinline__ void consumer(const Ctx& c) {
  float acc[192];
  uint32_t xf[4][4];
  uint32_t xp[8][4];
  {
    PHASE_CTX();
    const unsigned int epoch = ld_relaxed(&g_epoch);
    PROFT(tid_ == 128, 0);
    const uint32_t wu = __shfl_sync(0xffffffffu, wg, 0);
    if (tid_ < 128 + 8) sts128(sb + SM_AP + lane * 16, make_uint4(0x3F803F80u, 0x3F803F80u, 0x3F803F80u, 0x3F803F80u));
#pragma unroll 1
    for (int it = 0; it < 2; ++it) {
      float p[4][16];
      mbar_wait(BA(B_RAW + it), 0);
      PROFT(tid_ == 128, it ? 15 : 2);
      const uint32_t da = ((SB0 >> 4) | (1u << 16)) + (wu ? 9 + it : 2 * it) * 1024, db = (SB0 + SM_SD) >> 4;
      wgmma_fence();
#pragma unroll
      for (int h = 0; h < 4; ++h) wgmma_n32_0(p[h], D128(da + (h >> 1) * 512 + (h & 1) * 4), desc64(db + h * 128, 0x80000020u));
#pragma unroll
      for (int h = 0; h < 4; ++h) wgmma_n32(p[h], D128(da + (h >> 1) * 512 + (h & 1) * 4 + 2), desc64(db + h * 128 + 64, 0x80000020u), 1);
      wgmma_commit();
      wgmma_wait<0>();
#pragma unroll
      for (int i = 0; i < 64; ++i) asm volatile("" : "+f"(p[i >> 4][i & 15]) :: "memory");
      const uint32_t base = sb + (wg ? 9 + it : 2 * it) * SLOT + (wq * 16 + gq) * 128;
      uint32_t w[4][4][2];
#pragma unroll
      for (int i = 0; i < 32; ++i) w[i >> 3][(i >> 1) & 3][i & 1] = pack_bf16(p[i >> 3][2 * (i & 7)], p[i >> 3][2 * (i & 7) + 1]);
      if (wu) {
#pragma unroll
        for (int i = 0; i < 8; ++i)
          sts128(base + (i >> 2) * 8192 + (i & 1) * 1024 + (((((i >> 1) & 1) * 4 + t) ^ gq) << 4), make_uint4(w[i >> 1][0][i & 1], w[i >> 1][1][i & 1], w[i >> 1][2][i & 1], w[i >> 1][3][i & 1]));
      } else {
#pragma unroll
        for (int i = 0; i < 16; ++i)
          sts64(base + (i >> 3) * 8192 + (i & 1) * 1024 + ((((t & 1) * 4 + ((i >> 1) & 3)) ^ gq) << 4) + (t >> 1) * 8, w[(i >> 3) * 2][(i >> 1) & 3][i & 1], w[(i >> 3) * 2 + 1][(i >> 1) & 3][i & 1]);
      }
      fence_async_smem();
      __syncwarp();
      if (it == cr && lane == 0) mbar_arrive(BA(B_WFD));
    }
    if (tid_ == 128) sts_f(sb + SM_EPOCH, __uint_as_float(epoch & 1));
#pragma unroll
    for (int i = 0; i < 32; ++i) xp[i >> 2][i & 3] = 0u;
    nbar<1, 256>();
    PROFT(tid_ == 128, 13);
    mbar_wait(BA(FM + cr), 0);
    float cs[3][4];
    wgmma_fence();
#pragma unroll
    for (int ks = 0; ks < 4; ++ks)
#pragma unroll
      for (int i = 0; i < 3; ++i) {
        const uint32_t bx = (i == 0 ? 2 * cr * 1024 : i == 1 ? (2 * cr + 1) * 1024 : (9 + cr) * 1024) + wu * 512;
        wgmma_n8_t(cs[i], D128(((SB0 >> 4) | (512u << 16)) + bx + ks * 128), desc64((SB0 + SM_AP) >> 4, 0), ks != 0);
      }
    wgmma_commit();
    mbar_wait(BA(FM), 0);
#pragma unroll
    for (int k = 0; k < 4; ++k) ldsm_x4(xf[k][0], xf[k][1], xf[k][2], xf[k][3], sb + XS * SLOT + rowo + (X ^ (k << 5)));
    wgmma_wait<0>();
#pragma unroll
    for (int i = 0; i < 12; ++i) asm volatile("" : "+f"(cs[i >> 2][i & 3]) :: "memory");
    if (t < 2) {
#pragma unroll
      for (int i = 0; i < 3; ++i) red_add1(g_cs + (epoch & 1) * 6144 + g * 384 + i * 128 + wg * 64 + wq * 16 + gq + t * 8, t ? cs[i][2] : cs[i][0]);
    }
    PROFT(tid_ == 128, 14);
  }
#pragma unroll 1
  for (int layer = 0;; ++layer) {
    {
      PHASE_CTX();
      MMA_CTX();
      {
        const uint32_t ep = __float_as_uint(lds_f(sb + SM_EPOCH));
        mbar_wait(BA(FM), par);
        wgmma_fence();
        wgmma_n256_rs0(acc, xf[0], D128(dB0));
#pragma unroll
        for (int k = 1; k < 4; ++k) wgmma_n256_rs(acc, xf[k], D128(dB0 + k * 128), 1);
        wgmma_commit();
        if (layer == 0) {
          mbar_wait(BA(B_X0), 0);
#pragma unroll
          for (int i = 0; i < 8; ++i) ldsm_x4(xp[i][0], xp[i][1], xp[i][2], xp[i][3], sb + (11 + (i >> 2)) * SLOT + (Y ^ ((i & 2) << 5)) + (i & 1) * 1024);
          if (lane == ((xp[0][0] ^ xp[1][0] ^ xp[2][0] ^ xp[3][0] ^ xp[7][0]) & c.zero)) REL2(B_XT);
        } else {
#pragma unroll
          for (int i = 0; i < 8; ++i) stsm_x4(sb + (XS + (i >> 2)) * SLOT + (Y ^ ((i & 2) << 5)) + (i & 1) * 1024, xp[i][0], xp[i][1], xp[i][2], xp[i][3]);
        }
        float s0 = 0.f, s1 = 0.f, q0 = 0.f, q1 = 0.f;
        auto stats = [&](int j0, int j1) {
#pragma unroll
          for (int j = j0; j < j1; ++j) {
            const uint32_t u0 = xp[(j >> 2) * 2][j & 3], u1 = xp[(j >> 2) * 2 + 1][j & 3];
            s0 += bf_lo(u0) + bf_hi(u0); s1 += bf_lo(u1) + bf_hi(u1);
            q0 = fmaf(bf_lo(u0), bf_lo(u0), fmaf(bf_hi(u0), bf_hi(u0), q0)); q1 = fmaf(bf_lo(u1), bf_lo(u1), fmaf(bf_hi(u1), bf_hi(u1), q1));
          }
        };
        stats(0, ST1);
        fence_async_smem();
        nbar_dyn(3 + wu + (__float_as_uint(s0 + s1 + q0 + q1) & c.zero), 128);
        mbar_wait(BA(FM + 1), par);
        wgmma_fence();
#pragma unroll
        for (int k = 0; k < 4; ++k) wgmma_n256(acc, D128(dA0 + (XS + 1) * 1024 + k * 2), D128(dB0 + 2048 + k * 128), 1);
        wgmma_commit();
        wgmma_wait<1>();
#pragma unroll
        for (int i = 4; i < 8; ++i) stg128_p(layer, g_x + gfr + (i & 1) * 8 * D_ + (i >> 1) * 32, xp[i][0], xp[i][1], xp[i][2], xp[i][3]);
        {
          uint32_t zc; asm volatile("mov.u32 %0, %%clock;" : "=r"(zc) :: "memory");
          q0 += __uint_as_float(zc & c.zero); q1 += __uint_as_float(zc & c.zero); s0 += __uint_as_float(zc & c.zero); s1 += __uint_as_float(zc & c.zero);
        }
        stats(ST1, 16);
        wgmma_fence();
        wgmma_n128_0(acc, D128(dA0 + XS * 1024), D128(dB0 + 9 * 1024));
#pragma unroll
        for (int k = 1; k < 4; ++k) wgmma_n128(acc, D128(dA0 + XS * 1024 + k * 2), D128(dB0 + 9 * 1024 + k * 128), 1);
        wgmma_commit();
        const bool od = t & 1;
        float sa = od ? s1 : s0, qa = od ? q1 : q0;
        sa += __shfl_xor_sync(0xffffffffu, od ? s0 : s1, 1);
        qa += __shfl_xor_sync(0xffffffffu, od ? q0 : q1, 1);
        wgmma_fence();
#pragma unroll
        for (int k = 0; k < 4; ++k) wgmma_n128(acc, D128(dA0 + (XS + 1) * 1024 + k * 2), D128(dB0 + 10 * 1024 + k * 128), 1);
        wgmma_commit();
        sa += __shfl_xor_sync(0xffffffffu, sa, 2);
        qa += __shfl_xor_sync(0xffffffffu, qa, 2);
        red_add2_p(t < 2, reinterpret_cast<float*>(g_stats + (ep * 4 + layer) * S_ + m0 + wrow0 + gq + t * 8), sa, qa);
        __syncwarp();
        if (lane == 0) mbar_arrive(BA(B_XDONE));
        wgmma_wait<1>();
        if (elected) REL2(CM);
      }
      uint32_t s = 2;
#pragma unroll 1
      for (int i = 2; i < NF; ++i) {
        PROFL(tid_ == 128 && layer == PL + 1, 244 + 2 * i);
        mbar_wait(BA(FM + i), par);
        PROFL(tid_ == 128 && layer == PL + 1, 245 + 2 * i);
        const uint32_t da = dA0 + (XS + s) * 1024, dk = dB0 + s * 2048, dq = dB0 + (9 + s) * 1024;
        wgmma_fence();
#pragma unroll
        for (int k = 0; k < 4; ++k) wgmma_n128(acc, D128(da + k * 2), D128(dq + k * 128), 1);
        wgmma_commit();
        wgmma_wait<1>();
        if (elected) REL2(CM + i - 1);
        wgmma_fence();
#pragma unroll
        for (int k = 0; k < 4; ++k) wgmma_n256(acc, D128(da + k * 2), D128(dk + k * 128), 1);
        wgmma_commit();
        if (++s == 3) s = 0;
      }
#pragma unroll 1
      for (int i = NF; i < 15; ++i) {
        mbar_wait(BA(FM + i), par);
        const uint32_t da = dA0 + (XS + s) * 1024, dk = dB0 + s * 2048;
        wgmma_fence();
#pragma unroll
        for (int k = 0; k < 4; ++k) wgmma_n256(acc, D128(da + k * 2), D128(dk + k * 128), 1);
        wgmma_commit();
        wgmma_wait<1>();
        if (elected) REL2(CM + i - 1);
        if (++s == 3) s = 0;
      }
      {
        const uint64_t dap = desc64(((SB0 + SM_AP) >> 4) + wu * 64, 8), dbp = make_desc_ns(SB0 + SM_BP, 0, 128);
        mbar_wait(BA(B_STAT), par);
        mbar_wait(BA(FM + 15), par);
        PROFT(tid_ == 128, layer * 16 + 9);
        wgmma_fence();
        wgmma_n256_k(acc, dap, dbp, 1);
#pragma unroll
        for (int k = 0; k < 4; ++k) wgmma_n256(acc, D128(dA0 + XS * 1024 + k * 2), D128(dB0 + k * 128), 1);
        wgmma_commit();
        wgmma_wait<1>();
        if (elected) REL2(CM + 14);
        mbar_wait(BA(FT), par);
        wgmma_fence();
        wgmma_n128_k(acc, dap, dbp + 256, 1);
#pragma unroll
        for (int k = 0; k < 4; ++k) wgmma_n128(acc, D128(dA0 + (uint32_t)(TL_A & 15) * 1024 + k * 2), D128(dB0 + (uint32_t)(TL_B & 15) * 1024 + k * 128), 1);
        wgmma_commit();
        wgmma_wait<1>();
        if (elected) REL2(CM + 15);
#pragma unroll
        for (int i = 0; i < 128; ++i) asm volatile("" : "+f"(acc[i]) :: "memory");
      }
    }
    uint32_t of[8][4], o1[4][4];
    {
      PHASE_CTX();
      MMA_CTX();
      PROFT(tid_ == 128, layer * 16 + 1);
      PROFT(lane == 0 && layer == PL, 192 + cw);
      PROFT(tid_ == 128 && layer == PL, 160);
      uint64_t ta = (TL_A >> 4), tw = TL_B >> 4;
      uint32_t da, db, dz = dA0;
      auto sub = [&](int n) {
        const int j = n >> 2, k = n & 3;
        if (k == 0) {
          dz += c.zero;
          da = dz + ((uint32_t)ta & 15) * 1024; db = dB0 + ((uint32_t)tw & 15) * 1024;
          ta >>= 4; tw >>= 4;
          mbar_wait(BA(FT + j), par);
          wgmma_fence();
        }
        wgmma_n128(acc, D128(da + k * 2), D128(db + k * 128), 1);
        if (k == 3) {
          wgmma_commit();
          wgmma_wait<1>();
          if (elected) REL2(CT + j - 1);
        }
      };
      auto run = [&](int j0, int j1) {
#pragma unroll 1
        for (int j = j0; j < j1; ++j) {
          mbar_wait(BA(FT + j), par);
          da = dA0 + ((uint32_t)ta & 15) * 1024; db = dB0 + ((uint32_t)tw & 15) * 1024;
          ta >>= 4; tw >>= 4;
          wgmma_fence();
#pragma unroll
          for (int k = 0; k < 4; ++k) wgmma_n128(acc, D128(da + k * 2), D128(db + k * 128), 1);
          wgmma_commit();
          wgmma_wait<1>();
          if (elected) REL2(CT + j - 1);
        }
        ta = TL_A >> (4 * j1); tw = TL_B >> (4 * j1);
      };
      auto rest = [&](int j0) {
        run(j0, ND - NR);
        if (NR) mbar_wait(BA(FT + ND - NR), par);
#pragma unroll
        for (int j = ND - NR; j < ND; ++j) {
          if (j > ND - NR) mbar_wait(BA(FT + j), par);
          wgmma_fence();
#pragma unroll
          for (int k = 0; k < 4; ++k)
            wgmma_n64_lo(acc, D128(dA0 + (uint32_t)((TL_A >> (4 * j)) & 15) * 1024 + k * 2), D128(dB0 + (uint32_t)((TL_B >> (4 * j)) & 15) * 1024 + k * 128), 1);
          wgmma_commit();
          if (!DRAIN && j == ND - NR) {
            wgmma_wait<1>();
            if (elected) REL2(CT + j - 1);
          }
        }
        wgmma_wait<0>();
        if (!NR && elected) REL2(CT + ND - 1);
#pragma unroll
        for (int i = 128; i < 192; ++i) asm volatile("" : "+f"(acc[i]) :: "memory");
#pragma unroll
        for (int i = 160; i < 192; ++i) if (NR) acc[i] += __uint_as_float(c.zero);
      };
      auto rest_hi = [&]() {
        if (!NR) return;
        dz += c.zero;
        wgmma_fence();
#pragma unroll
        for (int j = ND - NR; j < ND; ++j)
#pragma unroll
          for (int k = 0; k < 4; ++k)
            wgmma_n64_hi(acc, D128(dz + (uint32_t)((TL_A >> (4 * j)) & 15) * 1024 + k * 2), D128(dB0 + (uint32_t)((TL_B >> (4 * j)) & 15) * 1024 + 512 + k * 128), 1);
        wgmma_commit();
      };
      auto rest_end = [&]() {
        if (!NR) return;
        wgmma_wait<0>();
        if (elected) {
#pragma unroll
          for (int j = ND - NR; j < ND; ++j) REL2(CT + j);
        }
#pragma unroll
        for (int i = 160; i < 192; ++i) asm volatile("" : "+f"(acc[i]) :: "memory");
      };
      const float rs0 = lds_f(sb + SM_RS + (16 + wrow0 + gq) * 4), rs1 = lds_f(sb + SM_RS + (24 + wrow0 + gq) * 4);
#define EPOCH() __float_as_uint(lds_f(sb + SM_EPOCH))
      mbar_wait(BA(CM + 14), par);
      if (par) {
        uint32_t kk[8][4], kp[8][4], vf[2][2][4][4];
        int sn = 4;
#pragma unroll
        for (int i = 0; i < 4 * BT1; ++i) sub(sn++);
        {
          uint32_t vv[8][4];
#pragma unroll
          for (int jp = 0; jp < 8; ++jp) {
            kk[jp][0] = pack_bf16(acc[8 * jp], acc[8 * jp + 1]); kk[jp][1] = pack_bf16(acc[8 * jp + 4], acc[8 * jp + 5]);
            kk[jp][2] = pack_bf16(acc[8 * jp + 2], acc[8 * jp + 3]); kk[jp][3] = pack_bf16(acc[8 * jp + 6], acc[8 * jp + 7]);
#pragma unroll
            for (int i = 0; i < 4; ++i) vv[jp][i] = pack_bf16(acc[64 + 8 * jp + 2 * i], acc[65 + 8 * jp + 2 * i]);
          }
          if (cw == 7) {
            uint32_t* const hbuf = g_halo + (size_t)(((layer >> 1) * 17 + rb + 1) * 8 + g) * 2048;
#pragma unroll
            for (int jp = 0; jp < 8; ++jp) stg128(hbuf + jp * 128 + lane * 4, kk[jp][0], kk[jp][1], kk[jp][2], kk[jp][3]);
#pragma unroll
            for (int i = 0; i < 32; ++i) hbuf[1024 + (i >> 4) * 512 + (gq + (i & 1) * 8) * 32 + ((((i >> 1) & 7) ^ gq) << 2) + t] = vv[i >> 2][i & 3];
            __syncwarp();
            if (lane == 0) mbar_arrive(BA(B_OF0));
          }
#pragma unroll
          for (int jp = 0; jp < 8; ++jp) {
            sub(sn++);
            stsm_x4(sb + VB + (jp >> 2) * SLOT + rowo + (X ^ ((jp & 3) << 5)), vv[jp][0], vv[jp][1], vv[jp][2], vv[jp][3]);
          }
        }
        PROFT(tid_ == 128, layer * 16 + 2);
        const int e = gq & 1;
        float f0[4], f1[4], b0[4], b1[4], rj[4];
#pragma unroll
        for (int nt = 0; nt < 4; ++nt) {
          const int kx = nt * 8 + 2 * t + e;
          const bool okk = (m0 + wrow0 + kx) >= 16;
          const int d0 = kx - gq, d1 = d0 - 8;
          rj[nt] = lds_f(sb + SM_RS + (wrow0 + kx) * 4);
          const bool m0_ = okk && d0 >= 2 && d0 <= 16, m1_ = okk && d1 >= 2 && d1 <= 16;
          f0[nt] = m0_ ? rj[nt] * rs0 * (0.17677669529663687f * L2E) : 0.f;
          f1[nt] = m1_ ? rj[nt] * rs1 * (0.17677669529663687f * L2E) : 0.f;
          b0[nt] = m0_ ? 0.f : -1e30f; b1[nt] = m1_ ? 0.f : -1e30f;
        }
        mbar_wait(BA(CM + 15), par);
#pragma unroll
        for (int jp = 0; jp < 8; ++jp) {
          sub(sn++);
          sts128(sb + PH + cw * 4096 + jp * 512 + lane * 16, make_uint4(kk[jp][0], kk[jp][1], kk[jp][2], kk[jp][3]));
        }
#pragma unroll
        for (int i = 0; i < 4; ++i) sub(sn++);
        nbar<1, 256>();
        PROFT(tid_ == 128, layer * 16 + 3);
        rest(sn >> 2);
        PROFT(lane == 0 && layer == PL, 200 + cw);
        PROFT(tid_ == 128, layer * 16 + 10);
        if (cw == 0) mbar_wait(BA(B_HALO), (layer >> 1) & 1);
        PROFT(tid_ == 128, layer * 16 + 5);
        const uint32_t vs = sb + (cw ? VB + rowo - 2048 : SM_SD + 4096 + rowo), vst = cw ? SLOT : 2048;
        const uint32_t psel = e ? 0x1054u : 0x5410u;
#pragma unroll
        for (int hp = 0; hp < 2; ++hp) {
#pragma unroll
          for (int i = 4 * hp; i < 4 * hp + 4; ++i) {
            const uint4 u = lds128(sb + (cw ? PH + (cw - 1) * 4096 : SM_SD) + lane * 16 + i * 512);
            kp[i][0] = u.x; kp[i][1] = u.y; kp[i][2] = u.z; kp[i][3] = u.w;
          }
#pragma unroll
          for (int i = 4 * hp; i < 4 * hp + 4; ++i) {
            ldsm_x4_t(vf[0][i & 1][i >> 1][0], vf[0][i & 1][i >> 1][1], vf[0][i & 1][i >> 1][2], vf[0][i & 1][i >> 1][3], vs + (i >> 2) * vst + (X ^ ((i & 3) << 5)));
            ldsm_x4_t(vf[1][i & 1][i >> 1][0], vf[1][i & 1][i >> 1][1], vf[1][i & 1][i >> 1][2], vf[1][i & 1][i >> 1][3], sb + VB + (i >> 2) * SLOT + rowo + (X ^ ((i & 3) << 5)));
          }
          if (hp) {
            rest_end();
          }
          float l0[2][4], l1[2][4];
#pragma unroll
          for (int h = 0; h < 2; ++h) {
            const int H = 2 * hp + h;
            uint32_t qa[8];
#pragma unroll
            for (int i = 0; i < 8; ++i) qa[i] = pack_bf16(acc[128 + 16 * H + 2 * i], acc[129 + 16 * H + 2 * i]);
#pragma unroll
            for (int nt = 3; nt >= 0; --nt) {
              float sc[4] = {0.f, 0.f, 0.f, 0.f};
#pragma unroll
              for (int ks = 0; ks < 2; ++ks) {
                const uint32_t (&kf)[4] = nt < 2 ? kp[2 * H + ks] : kk[2 * H + ks];
                mma_bf16(sc, qa[4 * ks], qa[4 * ks + 1], qa[4 * ks + 2], qa[4 * ks + 3], kf[2 * (nt & 1)], kf[2 * (nt & 1) + 1]);
              }
              l0[h][nt] = fmaf(e ? sc[1] : sc[0], f0[nt], b0[nt]);
              l1[h][nt] = fmaf(e ? sc[3] : sc[2], f1[nt], b1[nt]);
            }
          }
          float mx0[2], mx1[2], s0[2], s1[2];
#pragma unroll
          for (int h = 0; h < 2; ++h) {
            mx0[h] = fmaxf(fmaxf(l0[h][0], l0[h][1]), l0[h][2]);
            mx1[h] = fmaxf(fmaxf(l1[h][1], l1[h][2]), l1[h][3]);
          }
#pragma unroll
          for (int o = 1; o <= 2; o <<= 1)
#pragma unroll
            for (int h = 0; h < 2; ++h) {
              mx0[h] = fmaxf(mx0[h], __shfl_xor_sync(0xffffffffu, mx0[h], o));
              mx1[h] = fmaxf(mx1[h], __shfl_xor_sync(0xffffffffu, mx1[h], o));
            }
#pragma unroll
          for (int h = 0; h < 2; ++h) {
#pragma unroll
            for (int nt = 0; nt < 3; ++nt) { l0[h][nt] = ex2(l0[h][nt] - mx0[h]); l1[h][nt + 1] = ex2(l1[h][nt + 1] - mx1[h]); }
            s0[h] = (l0[h][0] + l0[h][1]) + l0[h][2];
            s1[h] = (l1[h][1] + l1[h][2]) + l1[h][3];
          }
#pragma unroll
          for (int o = 1; o <= 2; o <<= 1)
#pragma unroll
            for (int h = 0; h < 2; ++h) {
              s0[h] += __shfl_xor_sync(0xffffffffu, s0[h], o);
              s1[h] += __shfl_xor_sync(0xffffffffu, s1[h], o);
            }
          uint32_t ow[2][2][4];
#pragma unroll
          for (int h = 0; h < 2; ++h) {
            const int H = 2 * hp + h;
            uint32_t pl[4], ph[4];
            const float i0 = rcp(s0[h]), i1 = rcp(s1[h]);
#pragma unroll
            for (int nt = 0; nt < 4; ++nt) {
              const uint32_t pk = pack_bf16(nt < 3 ? l0[h][nt] * i0 * rj[nt] : 0.f, nt > 0 ? l1[h][nt] * i1 * rj[nt] : 0.f);
              pl[nt] = nt < 3 ? __byte_perm(pk, 0u, psel) : 0u;
              ph[nt] = nt > 0 ? __byte_perm(pk, 0u, psel + 0x2222u) : 0u;
            }
#pragma unroll
            for (int nj = 0; nj < 4; ++nj) {
              float oa[4] = {0.f, 0.f, 0.f, 0.f};
#pragma unroll
              for (int ks = 0; ks < 2; ++ks)
                mma_bf16(oa, pl[2 * ks], ph[2 * ks], pl[2 * ks + 1], ph[2 * ks + 1], vf[ks][nj >> 1][H][2 * (nj & 1)], vf[ks][nj >> 1][H][2 * (nj & 1) + 1]);
              ow[h][0][nj] = pack_bf16(oa[0], oa[1]); ow[h][1][nj] = pack_bf16(oa[2], oa[3]);
            }
          }
          if (hp == 0) {
#pragma unroll
            for (int i = 0; i < 4; ++i) stg128(g_o + gfr + (i & 1) * 8 * D_ + (i >> 1) * 32, ow[i >> 1][i & 1][0], ow[i >> 1][i & 1][1], ow[i >> 1][i & 1][2], ow[i >> 1][i & 1][3]);
            __syncwarp();
            if (lane == 0) mbar_arrive(BA(B_OH0));
            rest_hi();
          } else {
#pragma unroll
            for (int i = 0; i < 16; ++i) o1[i >> 2][i & 3] = ow[i >> 3][(i >> 2) & 1][i & 3];
          }
#pragma unroll
          for (int i = 0; i < 16; ++i) of[4 * hp + (i >> 2)][i & 3] = ow[i >> 3][i & 1][(i >> 1) & 3];
          if (!hp) PROFT(tid_ == 128, layer * 16 + 15);
        }
      } else {
        float sc[2] = {rs0 * L2E, rs1 * L2E};
        {
          const uint32_t vb = sb + VB + (rowo >> 1), X0 = (lchk ^ ((lane & 7) >> 1)) << 4;
          const uint32_t pb = sb + PH + (t & 1) * SLOT + (wrow0 + gq) * 128 + ((((t & 1) * 4 + (t & 2)) ^ gq) << 4);
          float kva[20], en[32], mx[2][2], mn[2][2];
#define PV(hp, j) acc[32 * (hp) + (j)]
          auto mm = [&](int hp, int j) {
            const int r = (j >> 1) & 1;
            if (j < 4 && !(j & 1)) { mx[hp][r] = PV(hp, j); mn[hp][r] = PV(hp, j); }
            else { mx[hp][r] = fmaxf(mx[hp][r], PV(hp, j)); mn[hp][r] = fminf(mn[hp][r], PV(hp, j)); }
          };
          auto mmx = [&](int hp) {
#pragma unroll
            for (int r = 0; r < 2; ++r) {
              mx[hp][r] = fmaxf(mx[hp][r], __shfl_xor_sync(0xffffffffu, mx[hp][r], 2)) * -sc[r];
              mn[hp][r] = fmaf(fminf(mn[hp][r], __shfl_xor_sync(0xffffffffu, mn[hp][r], 2)), sc[r], mx[hp][r]);
            }
          };
          auto stage = [&](int hp) {
#pragma unroll
            for (int i = 0; i < 20; ++i) asm volatile("" : "+f"(kva[i]) :: "memory");
            nbar_dyn(3 + wu, 128);
#pragma unroll
            for (int i = 0; i < 4; ++i)
              sts128(sb + VB + hp * SLOT + wg * 8192 + (wq * 128 + i * 32 + lane) * 16,
                     make_uint4(__float_as_uint(kva[4 * i]), __float_as_uint(kva[4 * i + 1]), __float_as_uint(kva[4 * i + 2]), __float_as_uint(kva[4 * i + 3])));
            if (t == 0) sts_f2(sb + SM_AP + ((2 * hp + wg) * 64 + wq * 16 + gq * 2) * 4, kva[16], kva[18]);
            fence_async_smem();
            __syncwarp();
            if (lane == 0) mbar_arrive(BA(B_KVDONE));
          };
          int sn = 4;
#pragma unroll
          for (int j = 0; j < 32; ++j) mm(0, j);
          mmx(0);
#pragma unroll
          for (int hp = 0; hp < 2; ++hp) {
            float sp[2] = {0.f, 0.f}, sm[2] = {0.f, 0.f};
#pragma unroll
            for (int j = 0; j < 32; ++j) {
              const int r = (j >> 1) & 1, ns = hp ? SUBS1 : SUBS;
              if ((j * ns) / 32 != ((j + 1) * ns) / 32) {
                sub(sn++);
                if (hp && sn == 4 + SUBS + 4) { stage(0); PROFT(tid_ == 128, layer * 16 + 12); }
              }
              const float x = fmaf(PV(hp, j), sc[r], mx[hp][r]);
              PV(hp, j) = ex2(x); en[j] = ex2(mn[hp][r] - x);
              sp[r] += PV(hp, j); sm[r] += en[j];
              if (hp == 0) {
                mm(1, j);
                if ((j & 3) == 0) {
                  const int jp = 8 + (j >> 2);
                  stsm_x4(vb + ((jp - 8) >> 1) * 8192 + (X0 ^ ((jp & 1) << 5)), pack_bf16(acc[8 * jp], acc[8 * jp + 1]), pack_bf16(acc[8 * jp + 2], acc[8 * jp + 3]),
                          pack_bf16(acc[8 * jp + 4], acc[8 * jp + 5]), pack_bf16(acc[8 * jp + 6], acc[8 * jp + 7]));
                }
              }
            }
#pragma unroll
            for (int r = 0; r < 2; ++r) {
              sp[r] = rcp(sp[r] + __shfl_xor_sync(0xffffffffu, sp[r], 2)) * (r ? rs1 : rs0);
              sm[r] = rcp(sm[r] + __shfl_xor_sync(0xffffffffu, sm[r], 2)) * (r ? rs1 : rs0);
            }
            if (hp == 0) { mmx(1); mbar_wait(BA(CM + 15), par); }
            else { PROFT(tid_ == 128, layer * 16 + 11); nbar<1, 256>(); }
#pragma unroll
            for (int i = 0; i < 4; ++i) {
              const int r = i & 1, d = 16 * (i >> 1) + 2 * r;
              sts128((pb + r * 1024) ^ ((i >> 1) << 4), make_uint4(pack_bf16(PV(hp, d) * sp[r], PV(hp, d + 1) * sp[r]), pack_bf16(PV(hp, d + 4) * sp[r], PV(hp, d + 5) * sp[r]),
                                                                    pack_bf16(PV(hp, d + 8) * sp[r], PV(hp, d + 9) * sp[r]), pack_bf16(PV(hp, d + 12) * sp[r], PV(hp, d + 13) * sp[r])));
              sts128((pb + r * 1024) ^ ((i >> 1) << 4) ^ 64, make_uint4(pack_bf16(en[d] * sm[r], en[d + 1] * sm[r]), pack_bf16(en[d + 4] * sm[r], en[d + 5] * sm[r]),
                                                                         pack_bf16(en[d + 8] * sm[r], en[d + 9] * sm[r]), pack_bf16(en[d + 12] * sm[r], en[d + 13] * sm[r])));
            }
            fence_async_smem();
            nbar<1, 256>();
            const uint32_t dP = dB0 + (PH >> 4) + wu * 1024;
            const uint32_t dV = (dB0 & 0xFFFFu) + ((VB + hp * SLOT) >> 4) + (((SM_SD - VB - hp * SLOT) >> 4) << 16) + wu * (512u - (512u << 16));
            wgmma_fence();
#pragma unroll
            for (int ks = 0; ks < 8; ++ks) wgmma_n40_tt(kva, D128(dP + ks * 128), desc64(dV + ks * 64, 0x80000020u), ks != 0);
            wgmma_commit();
          }
#pragma unroll
          for (int i = 0; i < 4; ++i) sub(sn++);
          stage(1);
          PROFT(tid_ == 128, layer * 16 + 3);
          rest(sn >> 2);
          PROFT(lane == 0 && layer == PL, 200 + cw);
          PROFT(tid_ == 128, layer * 16 + 10);
        }
#define QV(H, i) acc[128 + 16 * (H) + (i)]
        float mx[4][2], mn[4][2];
        uint32_t ph[4][4][4];
        auto mnx = [&](int hp) {
#pragma unroll
          for (int H = 2 * hp; H < 2 * hp + 2; ++H)
#pragma unroll
            for (int r = 0; r < 2; ++r) {
              mx[H][r] = fmaxf(fmaxf(fmaxf(QV(H, 2 * r), QV(H, 2 * r + 1)), fmaxf(QV(H, 4 + 2 * r), QV(H, 5 + 2 * r))),
                               fmaxf(fmaxf(QV(H, 8 + 2 * r), QV(H, 9 + 2 * r)), fmaxf(QV(H, 12 + 2 * r), QV(H, 13 + 2 * r))));
              mn[H][r] = fminf(fminf(fminf(QV(H, 2 * r), QV(H, 2 * r + 1)), fminf(QV(H, 4 + 2 * r), QV(H, 5 + 2 * r))),
                               fminf(fminf(QV(H, 8 + 2 * r), QV(H, 9 + 2 * r)), fminf(QV(H, 12 + 2 * r), QV(H, 13 + 2 * r))));
            }
#pragma unroll
          for (int o = 1; o <= 2; o <<= 1)
#pragma unroll
            for (int H = 2 * hp; H < 2 * hp + 2; ++H)
#pragma unroll
              for (int r = 0; r < 2; ++r) {
                mx[H][r] = fmaxf(mx[H][r], __shfl_xor_sync(0xffffffffu, mx[H][r], o));
                mn[H][r] = fminf(mn[H][r], __shfl_xor_sync(0xffffffffu, mn[H][r], o));
              }
#pragma unroll
          for (int H = 2 * hp; H < 2 * hp + 2; ++H)
#pragma unroll
            for (int r = 0; r < 2; ++r) { mx[H][r] *= -sc[r]; mn[H][r] = fmaf(mn[H][r], sc[r], mx[H][r]); }
        };
        auto fm = [&](int H) {
#pragma unroll
          for (int i = 0; i < 8; ++i) {
            const int r = i & 1;
            const float x0 = fmaf(QV(H, 2 * i), sc[r], mx[H][r]), x1 = fmaf(QV(H, 2 * i + 1), sc[r], mx[H][r]);
            ph[H][i >> 2][i & 3] = pack_bf16(ex2(x0), ex2(x1));
            ph[H][2 + (i >> 2)][i & 3] = pack_bf16(ex2(mn[H][r] - x0), ex2(mn[H][r] - x1));
          }
        };
        auto conv = [&](int hp) {
          mbar_wait(BA(hp ? B_KVF1 : B_KVF), (layer >> 1) & 1);
          PROFT(tid_ == 128, layer * 16 + (hp ? 4 : 5));
          if (hp) nbar_dyn(3 + wu, 128);
#pragma unroll
          for (int h = 0; h < 2; ++h) {
            uint4 u[4];
#pragma unroll
            for (int i = 0; i < 4; ++i) u[i] = lds128(sb + VB + hp * SLOT + h * 8192 + (wq * 128 + i * 32 + lane) * 16);
            const float zz = lds_f(sb + SM_AP + ((2 * hp + h) * 64 + wq * 16 + (lane & 7) * 2 + ((lane >> 3) & 1)) * 4);
            const uint32_t kb_ = sb + PH + wg * SLOT + h * 8192 + (wq * 16 + lrow) * 128;
#pragma unroll
            for (int i = 0; i < 4; i += 2)
              stsm_x4(kb_ + (X ^ (i << 4)),
                      pack_bf16(__uint_as_float(u[i].x), __uint_as_float(u[i].y)), pack_bf16(__uint_as_float(u[i].z), __uint_as_float(u[i].w)),
                      pack_bf16(__uint_as_float(u[i + 1].x), __uint_as_float(u[i + 1].y)), pack_bf16(__uint_as_float(u[i + 1].z), __uint_as_float(u[i + 1].w)));
            const uint32_t z1 = pack_bf16(zz, 1.f);
            if (lane < 16) sts128(kb_ + ((4 ^ (lane & 7)) << 4), make_uint4(z1, z1, z1, z1));
          }
          fence_async_smem();
        };
        mnx(0);
        rest_hi();
        fm(0);
        if (CV0) conv(0);
        fm(1);
        rest_end();
        if (!CV0) conv(0);
#pragma unroll
        for (int hp = 0; hp < 2; ++hp) {
          nbar_dyn(3 + wu, 128);
          float oa[4][20];
          wgmma_fence();
#pragma unroll
          for (int s = 0; s < 2; ++s)
#pragma unroll
            for (int v = 0; v < 4; ++v) {
              const int h = v >> 1, s4 = 2 * (v & 1) + s;
              wgmma_n40_rs(oa[v], ph[2 * hp + h][s4], D128(dB0 + (PH >> 4) + wu * 1024 + h * 512 + (s4 ^ (2 * h)) * 128), s != 0);
            }
          wgmma_commit();
          if (hp == 0) mnx(1);
          wgmma_wait<0>();
#pragma unroll
          for (int i = 0; i < 20; ++i) asm volatile("" : "+f"(oa[0][i]), "+f"(oa[1][i]), "+f"(oa[2][i]), "+f"(oa[3][i]) :: "memory");
          uint32_t ow[2][2][4];
#pragma unroll
          for (int h = 0; h < 2; ++h)
#pragma unroll
            for (int r = 0; r < 2; ++r) {
              const float a = rcp(oa[2 * h][17 + 2 * r]), b = rcp(oa[2 * h + 1][17 + 2 * r]);
              const float id = __fdividef(1.f, fmaf(oa[2 * h][16 + 2 * r], a, fmaf(oa[2 * h + 1][16 + 2 * r], b, 1e-6f)));
              const float fa = a * id, fb = b * id;
#pragma unroll
              for (int j = 0; j < 4; ++j)
                ow[h][r][j] = pack_bf16(fmaf(oa[2 * h][4 * j + 2 * r], fa, oa[2 * h + 1][4 * j + 2 * r] * fb),
                                        fmaf(oa[2 * h][4 * j + 2 * r + 1], fa, oa[2 * h + 1][4 * j + 2 * r + 1] * fb));
            }
#pragma unroll
          for (int i = 0; i < 16; ++i) of[4 * hp + (i >> 2)][i & 3] = ow[i >> 3][i & 1][(i >> 1) & 3];
          if (hp == 0) {
#pragma unroll
            for (int i = 0; i < 8; ++i) {
              if (!(i & 1)) stg128(g_o + gfr + ((i >> 1) & 1) * 8 * D_ + (i >> 2) * 32, ow[i >> 2][(i >> 1) & 1][0], ow[i >> 2][(i >> 1) & 1][1], ow[i >> 2][(i >> 1) & 1][2], ow[i >> 2][(i >> 1) & 1][3]);
              const int r = i & 1;
              const float x0 = fmaf(QV(2, 2 * i), sc[r], mx[2][r]), x1 = fmaf(QV(2, 2 * i + 1), sc[r], mx[2][r]);
              ph[2][i >> 2][i & 3] = pack_bf16(ex2v(x0), ex2v(x1));
              ph[2][2 + (i >> 2)][i & 3] = pack_bf16(ex2v(mn[2][r] - x0), ex2v(mn[2][r] - x1));
            }
            __syncwarp();
            if (lane == 0) mbar_arrive(BA(B_OH0));
            PROFT(tid_ == 128 && layer, layer * 16 + 15);
            if (QORD) { fm(3); conv(1); } else { conv(1); fm(3); }
          } else {
#pragma unroll
            for (int i = 0; i < 16; ++i) o1[i >> 2][i & 3] = ow[i >> 3][(i >> 2) & 1][i & 3];
          }
        }
      }
      PROFT(tid_ == 128, layer * 16 + 6);
    }
    {
      PHASE_CTX();
      MMA_CTX();
      auto o1st = [&]() {
#pragma unroll
        for (int i = 0; i < 4; ++i) stg128(g_o + gfr + (i & 1) * 8 * D_ + (2 + (i >> 1)) * 32, o1[i][0], o1[i][1], o1[i][2], o1[i][3]);
        __syncwarp();
        if (lane == 0) { mbar_arrive(BA(B_OH1)); if (!O1P) REL2(B_EF); }
        PROFT(lane == 0 && layer == PL, 208 + cw);
      };
      if (O1P) {
        __syncwarp();
        if (lane == 0) REL2(B_EF);
      } else o1st();
      mbar_wait(BA(FW), par);
      mbar_wait(BA(FW + 1), par);
      if (O1P == 1) o1st();
#pragma unroll
      for (int i = 0; i < 2; ++i) {
        wgmma_fence();
#pragma unroll
        for (int k = 0; k < 4; ++k) {
          if (i + k) wgmma_n128_rs(acc, of[4 * i + k], D128(dB0 + (uint32_t)((WO_B >> (4 * i)) & 15) * 1024 + k * 128), 1);
          else wgmma_n128_rs0(acc, of[0], D128(dB0 + (uint32_t)(WO_B & 15) * 1024));
        }
        wgmma_commit();
        if (O1P == 2 && i == 0) o1st();
      }
      wgmma_wait<1>();
      if (elected) REL2(CW);
      uint64_t ta = WO_A >> 8, tw = WO_B >> 8;
      auto run = [&](int i0, int i1) {
#pragma unroll 1
        for (int i = i0; i < i1; ++i) {
          mbar_wait(BA(FW + i), par);
          PROFL(tid_ == 128 && layer == PL, 160 + i);
          const uint32_t da = dA0 + ((uint32_t)ta & 15) * 1024, db = dB0 + ((uint32_t)tw & 15) * 1024;
          ta >>= 4; tw >>= 4;
          wgmma_fence();
#pragma unroll
          for (int k = 0; k < 4; ++k) wgmma_n128(acc, D128(da + k * 2), D128(db + k * 128), 1);
          wgmma_commit();
          wgmma_wait<1>();
          if (elected) REL2(CW + i - 1);
        }
      };
      run(2, XRAT);
#pragma unroll
      for (int j = 0; j < 8 / XRN; ++j) {
#pragma unroll
        for (int i = j * XRN; i < (j + 1) * XRN; ++i) ldg128((layer ? g_x : c.x0) + gfr + (i & 1) * 8 * D_ + (i >> 1) * 32, xp[i][0], xp[i][1], xp[i][2], xp[i][3]);
        run(XRAT + j, j + 1 < 8 / XRN ? XRAT + j + 1 : 16);
      }
      if (layer == 0) {
#pragma unroll
        for (int o = 1; o <= 2; o <<= 1)
#pragma unroll
          for (int i = 0; i < 16; ++i) {
            const int j = o == 1 ? 2 * (i & 1) : (i & 1);
            uint32_t &a = xp[i >> 1][j], &b = xp[i >> 1][j + o];
            const uint32_t r = __shfl_xor_sync(0xffffffffu, (t & o) ? a : b, o);
            if (t & o) a = r; else b = r;
          }
      }
      wgmma_wait<0>();
#pragma unroll
      for (int i = 128; i < 192; ++i) asm volatile("" : "+f"(acc[i]) :: "memory");
      if (elected) REL2(CW + 15);
      PROFT(lane == 0 && layer == PL, 216 + cw);
      PROFT(tid_ == 128, layer * 16 + 7);
    }
    {
      PHASE_CTX();
#pragma unroll
      for (int i = 0; i < 32; ++i)
        xp[i >> 2][i & 3] = add_bf16x2(xp[i >> 2][i & 3], pack_bf16(acc[128 + 16 * (i >> 3) + 4 * (i & 3) + 2 * ((i >> 2) & 1)], acc[129 + 16 * (i >> 3) + 4 * (i & 3) + 2 * ((i >> 2) & 1)]));
      if (layer == NLAYERS - 1) {
#pragma unroll
        for (int i = 0; i < 8; ++i) stsm_x4(sb + (XS + (i >> 2)) * SLOT + (Y ^ ((i & 2) << 5)) + (i & 1) * 1024, xp[i][0], xp[i][1], xp[i][2], xp[i][3]);
        __syncwarp();
        slab_out_half(sb + XS * SLOT, c.out + (size_t)m0 * D_ + g * 128, wrow0, lane);
        slab_out_half(sb + (XS + 1) * SLOT, c.out + (size_t)m0 * D_ + g * 128 + 64, wrow0, lane);
        PROFT(tid_ == 128, layer * 16 + 24);
        break;
      }
#pragma unroll
      for (int i = 0; i < 4; ++i) stg128(g_x + gfr + (i & 1) * 8 * D_ + (i >> 1) * 32, xp[i][0], xp[i][1], xp[i][2], xp[i][3]);
      __syncwarp();
      if (lane == 0) mbar_arrive(BA(B_XH0));
#pragma unroll
      for (int i = 0; i < 16; ++i) xf[i >> 2][i & 3] = xp[2 * (i >> 3) + (i & 1)][(i >> 1) & 3];
      PROFT(tid_ == 128, layer * 16 + 24);
    }
  }
}

__device__ __forceinline__ uint64_t k_order(int o) {
  const uint32_t lo = (1u << (4 * o)) - 1u, h0 = (0xECA86420u & lo) | ((0xECA86420u >> 4) & ~lo);
  return (uint64_t)(2 * o) | ((uint64_t)(2 * o + 1) << 4) | ((uint64_t)(h0 & 0xFFFFFFFu) << 8) | ((uint64_t)((h0 & 0xFFFFFFFu) | 0x1111111u) << 36);
}

__global__ void __cluster_dims__(2, 1, 1) __launch_bounds__(384, 1)
mega_kernel(const __grid_constant__ Maps maps, const __grid_constant__ Ctx c, const bf16* __restrict__ wA, const bf16* __restrict__ wB,
            const bf16* __restrict__ woA, const bf16* __restrict__ woB) {
  if (blockIdx.x - c.boff >= 128u) {
    const unsigned int epoch = ld_relaxed(&g_epoch);
    const int e = (blockIdx.x - c.boff) & 3, tid = threadIdx.x;
    float s[8] = {0.f, 0.f, 0.f, 0.f, 0.f, 0.f, 0.f, 0.f};
    const uint32_t sb = smem_u32(smem_raw), bar = sb + SM_BAR;
    auto issue = [&](int i) {
      mbar_expect_tx(BA(i & 3), 49152);
      bulk_load(sb + (i & 3) * 49152, wB + (size_t)e * 256 * 3072 + i * 24576, 49152, BA(i & 3));
    };
    if (tid == 0) {
#pragma unroll 1
      for (int i = 0; i < 4; ++i) {
        mbar_init(BA(i), 1);
        fence_async_smem();
        issue(i);
      }
    }
    __syncthreads();
#pragma unroll 1
    for (int i = 0; i < 32; ++i) {
      mbar_wait(BA(i & 3), (i >> 2) & 1);
#pragma unroll
      for (int r = 0; r < 8; ++r) {
        const uint4 v = lds128(sb + (i & 3) * 49152 + r * 6144 + tid * 16);
        s[0] += bf_lo(v.x); s[1] += bf_hi(v.x); s[2] += bf_lo(v.y); s[3] += bf_hi(v.y);
        s[4] += bf_lo(v.z); s[5] += bf_hi(v.z); s[6] += bf_lo(v.w); s[7] += bf_hi(v.w);
      }
      __syncthreads();
      if (tid == 0 && i < 28) issue(i + 4);
    }
    float* cd = g_cs + (epoch & 1) * 6144 + 3072 + ((tid >> 4) & 7) * 384 + (tid < 128 ? 256 : (tid >> 7) * 128 - 128) + (tid & 15) * 8;
    red_add4(cd, s[0], s[1], s[2], s[3]);
    red_add4(cd + 4, s[4], s[5], s[6], s[7]);
    __syncthreads();
    if (tid == 0) flag_add(&g_csflag[8].v);
    const int op = (epoch & 1) ^ 1;
    float4* kz = reinterpret_cast<float4*>(g_kv + (size_t)op * (2 * 8 * 8448)) + e * 8448;
#pragma unroll 2
    for (int i = tid; i < 8448; i += 384) kz[i] = make_float4(0.f, 0.f, 0.f, 0.f);
    reinterpret_cast<float4*>(g_cs + op * 6144)[e * 384 + tid] = make_float4(0.f, 0.f, 0.f, 0.f);
#pragma unroll 1
    for (int i = tid; i < 1024; i += 384) reinterpret_cast<float4*>(g_stats + (op * 4 + e) * S_)[i] = make_float4(0.f, 0.f, 0.f, 0.f);
    return;
  }
  const int warp = __shfl_sync(0xffffffffu, threadIdx.x >> 5, 0), lane = threadIdx.x & 31;
  if (smem_u32(smem_raw) != SB0 + ((blockIdx.x & 1) << 24)) __trap();
  {
  const int cid = (blockIdx.x - c.boff) >> 1, u7 = ((cid - 36) * 37) >> 8, cr = blockIdx.x & 1;
  const int g = cid < 4 ? 4 + cid : cid < 36 ? (cid - 4) >> 3 : 4 + u7, rb = (cid < 4 ? 0 : cid < 36 ? (cid - 4) & 7 : cid - 35 - 7 * u7) * 2 + cr, m0 = rb * 128;
  const uint32_t sb = SB0 + (cr << 24), bar = sb + SM_BAR;
  PROFT(lane == 0 && (warp == 0 || warp == 4), 224 + (warp >> 2) * 8);
  uint32_t cx = 0;
  if (warp == 2) {
    if (lane < NMAP) asm volatile("prefetch.tensormap [%0];" ::"l"(&maps.m[lane]) : "memory");
    if (lane == 31) asm volatile("prefetch.global.L2 [%0];" ::"l"(&g_epoch));
  } else if (warp == 3) {
    cx = c_map[cid] + c_wop[lane] + c_wop[NWOP - lane] + c_aop[lane] + c_aop[NAOP - lane] + (uint32_t)(uintptr_t)g_x;
  } else if (PFW && warp >= 4) {
    const int i = threadIdx.x - 128;
    asm volatile("prefetch.global.L2 [%0];" ::"l"(wA + (size_t)(rb * 64 + ((i >> 1) & 63)) * 3072 + (i >> 7) * 1024 + g * 128 + (i & 1) * 64));
  }
  if (warp < 2) {
    const int s = warp, kb = (rb & ~1) + s;
    if (lane == 0) {
      mbar_init(BA(FM + s), 1u);
      mbar_init(BA(B_RAW + warp), 1u);
      if (warp) mbar_init(BA(B_X0), 1u);
      asm volatile("fence.mbarrier_init.release.cluster;" ::: "memory");
    }
    __syncwarp();
    if (warp == 0) tma_2d_e(sb + SM_SD, &maps.m[MAP_PHI], 0, g * 128, BA(B_RAW));
    else if (W1DL) __nanosleep(W1DL);
#pragma unroll
    for (int j = 0; j < 6; ++j)
      tma_5d_e(sb + (j < 2 ? 2 * s : j < 4 ? 9 + s : 2 * s + 1) * SLOT + (j & 1) * 8192, &maps.m[MAP_WA], (j < 2 ? 1024 : j < 4 ? 0 : 2048) + g * 128 + (j & 1) * 64, 2 * kb,
               BA(j < 4 ? B_RAW + warp : FM + s));
    tma_2d_e(sb + (XS + s) * SLOT, &maps.m[MAP_X0], kb * 64, m0, BA(FM + s));
    expect_tx_e(BA(B_RAW + warp), warp ? 32768 : 32768 + 8192);
    expect_tx_e(BA(FM + s), 32768);
    if (X0AT == 0 && warp == 1) {
      tma_2d_e(sb + 11 * SLOT, &maps.m[MAP_X0], g * 128, m0, BA(B_X0));
      tma_2d_e(sb + 12 * SLOT, &maps.m[MAP_X0], g * 128 + 64, m0, BA(B_X0));
      expect_tx_e(BA(B_X0), 32768);
    }
  } else if (warp >= 4 && lane == 0) {
#pragma unroll 1
    for (int i = 2 + (warp - 4) * 13; i < 15 + (warp - 4) * 13; ++i)
      mbar_init(BA(i), 1u << ((i < CM ? 0u : i < B_EF ? 2u : (uint32_t)(BAR_LG >> (4 * ((i - B_EF) & 15)))) & 7u));
    asm volatile("fence.mbarrier_init.release.cluster;" ::: "memory");
  }
  __syncwarp();
  asm volatile("barrier.cluster.arrive.relaxed.aligned;" ::: "memory");
  if (threadIdx.x == 96 + c.zero) sts_f(sb + SM_EPOCH + 4, __uint_as_float(cx));
  PROFT(lane == 0 && (warp == 0 || warp == 4), 225 + (warp >> 2) * 8);
  __syncwarp();
  PROFT(lane == 0 && (warp == 0 || warp == 4), 226 + (warp >> 2) * 8);
  }

  if (warp < 4) {
    asm volatile("setmaxnreg.dec.sync.aligned.u32 40;");
    PROFT(threadIdx.x == 0, 227);
    cluster_wait();
    PROFT(threadIdx.x == 0, 228);
    if (warp == 0 || warp == 3) {
    if (warp == 0) {
      BLK_CTX();
      const unsigned int epoch = __shfl_sync(0xffffffffu, ld_relaxed(&g_epoch), 0), xbase = epoch * NLAYERS;
      (void)xbase;
      const uint64_t ordg = k_order(g);
      if (X0AT) {
        mbar_wait_u(BA(B_RAW + X0AT - 1), 0);
        tma_2d_e(sb + 11 * SLOT, &maps.m[MAP_X0], g * 128, m0, BA(B_X0));
        tma_2d_e(sb + 12 * SLOT, &maps.m[MAP_X0], g * 128 + 64, m0, BA(B_X0));
        expect_tx_e(BA(B_X0), 32768);
      }
#pragma unroll 1
      for (int lp = 0; lp < 2 * NLAYERS; ++lp) {
        const int layer = lp >> 1, n1 = (lp & 1) ? NAOP : NAOP - 14;
        int n = (lp & 1) ? NAOP - 14 : 0;
        const uint64_t ord = lp ? ordg : k_order(rb >> 1);
        uint32_t ready = lp ? 0u : 0xFFFFu, nop = c_aop[n];
        const unsigned int* fl = ((lp & 1) ? g_of : g_xf) + rb * 32;
        const CUtensorMap* tm = &maps.m[(lp & 1) ? MAP_O : lp ? MAP_X : MAP_X0];
        const uint32_t skip = layer ? 1u << 25 : 9u << 22;
#pragma unroll 1
        for (; n < n1; ++n) {
          const uint32_t op = nop;
          nop = c_aop[n + 1];
          const uint32_t kb = (uint32_t)(ord >> ((op >> 2) & 60)) & 15;
          uint32_t dst = sb + (op & 15) * SLOT, kc = kb * 64, fb = bar + ((op >> 5) & 0x3F8), need = ~ready & (1u << kb);
          asm volatile("" : "+r"(dst), "+r"(kc), "+r"(fb), "+r"(need));
          if (!(op & skip)) mbar_wait_u(bar + ((op >> 12) & 0x3F8), (layer ^ (op >> 22)) & 1);
          if (need) {
            PROFT(lane == 0 && (n == 0 || n == NAOP - 14), 64 + layer * 16 + (n ? 2 : 0));
            if (FASTP) src_wait_fast(fl, xbase + layer + 1, need, ready, lane);
            else src_wait<0>(fl, xbase + layer + 1, need, ready, lane);
            fence_async_all();
          }
          tma_2d_e(dst, tm, kc, m0, fb);
          PROFT(lane == 0 && (n == 0 || n == NAOP - 14), 64 + layer * 16 + (n ? 3 : 1));
          PROFL(lane == 0 && layer == PL && n >= NAOP - 14, 178 + n - (NAOP - 14));
          PROFL(lane == 0 && layer == PL + 1 && n < 4, 242 + n);
        }
      }
    } else {
      BLK_CTX();
      const unsigned int epoch = __shfl_sync(0xffffffffu, ld_relaxed(&g_epoch), 0), xbase = epoch * NLAYERS;
      (void)xbase;
      const uint64_t ordg = k_order(g);
#pragma unroll 1
      for (int layer = 0; layer < NLAYERS; ++layer) {
        const uint64_t ordq = layer ? ordg : k_order(rb >> 1);
        uint32_t ready = layer ? 0xFFFFu : 0u, nop = c_wop[0];
        const CUtensorMap* tq = &maps.m[(layer & 1) ? MAP_WB : MAP_WF];
        const CUtensorMap* tk = &maps.m[(layer & 1) ? MAP_WB : cr ? MAP_WA : MAP_WF];
        const uint32_t skip = layer ? 1u << 25 : 9u << 22, pm = layer ? 0xE0u : 0u;
        int n = 0;
#pragma unroll 1
        for (; n < NWOP - 16; ++n) {
          const uint32_t op = nop;
          nop = c_wop[n + 1];
          const uint32_t isq = (op >> 23) & 1, fb = bar + ((op >> 5) & 0x3F8);
          const uint32_t kb = (uint32_t)(ordq >> ((op >> 2) & 60)) & 15;
          const CUtensorMap* tm = (isq ? tq : tk) + ((op & pm) ? 1 : 0);
          const uint32_t dst = sb + (op & 15) * SLOT + cr * (isq ? 8192 : SLOT);
          const int col = g * 128 + (isq ? cr * 64 : 1024 + cr * 1024);
          if (layer == 0) {
            if ((op & 0x7E00) == 0) continue;
            const uint32_t need = ((isq || !cr) ? 1u << kb : 0u) | (((op >> 22) & 1) ? 0u : (((op >> 15) & 127) == CM ? 1u : 3u) << (rb & ~1));
            if ((ready & need) != need) {
              src_wait<0>(g_wff + g * 32, epoch + 1, need, ready, lane);
              fence_async_all();
            }
            if ((op & 15) >= 11) mbar_wait_u(BA(B_XT), 0);
          }
          wait_tma_5d_mc(!(op & skip), bar + ((op >> 12) & 0x3F8), (layer ^ (op >> 22)) & 1, dst, tm, col, 2 * kb, fb);
          if (!isq) tma_5d_mc_e(dst + 8192, tm, col + 64, 2 * kb, fb);
          if (op >> 26) expect_tx_e(fb, (op >> 26) * 8192);
          PROFL(lane == 0 && layer == PL + 1 && n < 16, 128 + n);
        }
        const CUtensorMap* to = &maps.m[(layer & 1) ? MAP_WOB : MAP_WOA];
#pragma unroll 1
        for (; n < NWOP; ++n) {
          const uint32_t op = nop;
          nop = c_wop[n + 1];
          const uint32_t fb = bar + ((op >> 5) & 0x3F8), kb = (uint32_t)(ordg >> ((op >> 2) & 60)) & 15;
          wait_tma_5d_mc(!((op >> 25) & 1), bar + ((op >> 12) & 0x3F8), layer & 1, sb + (op & 15) * SLOT + cr * 8192, to + ((op & 0xE0) ? 1 : 0), g * 128 + cr * 64, 2 * kb, fb);
          expect_tx_e(fb, (op >> 26) * 8192);
          PROFL(lane == 0 && layer == PL, 144 + ((op >> 8) & 127) - FW);
        }
      }
    }
    } else if (warp == 1) {
      BLK_CTX();
      const unsigned int epoch = __shfl_sync(0xffffffffu, ld_relaxed(&g_epoch), 0), xbase = epoch * NLAYERS;
      (void)xbase;
      if (lane == 0) {
        mbar_wait(BA(B_WFD), 0);
        PROFT(true, 229);
        if (WFDL && cr) __nanosleep(WFDL);
#pragma unroll 1
        for (int j = 0; j < 4; ++j) tma_store_5d(&maps.m[MAP_WF], sb + (j < 2 ? 2 * cr : 9 + cr) * SLOT + (j & 1) * 8192, (j < 2 ? 1024 : 0) + g * 128 + (j & 1) * 64, 2 * rb);
        bulk_commit();
        bulk_wait0();
        PROFT(true, 230);
        fence_async_all();
        flag_set(g_wff + g * 32 + rb, epoch + 1);
        PROFT(true, 64 + 13);
#pragma unroll 1
        for (int e = 0; e < NLAYERS; ++e) {
          BLK_CTX();
          if (e > 0) {
            mbar_wait(BA(B_XH0), (e - 1) & 1);
            PROFT(e == PL + 1, 240);
            flag_set(g_xf + rb * 32 + 2 * g, xbase + e + 1);
            PROFT(e == PL + 1, 241);
          }
          mbar_wait(BA(B_XDONE), e & 1);
          PROFT(true, 64 + e * 16 + 4);
          flag_set(g_xf + rb * 32 + 2 * g + 1, xbase + e + 1);
          if (e == 0) {
            flag_add(&g_csflag[g].v);
            l2_prefetch(wB + (size_t)bid_ * 24576, 49152);
            l2_prefetch(woA + (size_t)bid_ * 8192, 16384);
            l2_prefetch(woB + (size_t)bid_ * 8192, 16384);
          }
          PROFT(true, 64 + e * 16 + 7);
          if ((e & 1) == 0) {
            float* kvl = g_kv + ((size_t)((epoch & 1) * 2 + (e >> 1)) * 8 + g) * 8448;
#pragma unroll 1
            for (int hp = 0; hp < 2; ++hp) {
              mbar_wait(BA(B_KVDONE), hp);
              bulk_red_add(kvl + 8192 + hp * 128, sb + SM_AP + hp * 512, 512);
#pragma unroll 1
              for (int i = 0; i < NCH; ++i) {
                const int ch = hp * NCH + ((i + rb * NCH / 16) & (NCH - 1));
                bulk_red_add(kvl + ch * (4096 / NCH), sb + VB + ch * (16384 / NCH), 16384 / NCH);
                bulk_commit();
                asm volatile("cp.async.bulk.wait_group %0;" :: "n"(CHW) : "memory");
              }
              bulk_wait0();
              PROFT(true, 64 + e * 16 + (hp ? 10 : 6));
              fence_async_all();
              flag_add(&g_kvflag[hp * 8 + g].v);
              PROFT(e > 0 && hp, 64 + e * 16 + 8);
            }
          }
          if (e & 1) {
            mbar_wait(BA(B_OF0), (e >> 1) & 1);
            flag_set(g_hf + rb * 32 + g, xbase + e + 1);
            if (rb) flag_wait(g_hf + (rb - 1) * 32 + g, xbase + e + 1);
            fence_async_all();
            mbar_expect_tx(BA(B_HALO), 8192);
            bulk_load(sb + SM_SD, g_halo + (size_t)(((e >> 1) * 17 + rb) * 8 + g) * 2048, 8192, BA(B_HALO));
            PROFT(true, 64 + e * 16 + 15);
          }
          mbar_wait(BA(B_OH0), e & 1);
          PROFT(e > 0, 64 + e * 16 + 13);
          flag_set(g_of + rb * 32 + 2 * g, xbase + e + 1);
          PROFT(true, 64 + e * 16 + 9);
          mbar_wait(BA(B_OH1), e & 1);
          PROFT(true, 64 + e * 16 + 5);
          flag_set(g_of + rb * 32 + 2 * g + 1, xbase + e + 1);
          PROFT(true, 64 + e * 16 + 11);
        }
        if (bid_ == 0) g_epoch = epoch + 1;
      }
    } else {
      BLK_CTX();
      const unsigned int epoch = __shfl_sync(0xffffffffu, ld_relaxed(&g_epoch), 0), xbase = epoch * NLAYERS;
      (void)xbase;
      if (lane < 16) sts_f(sb + SM_RS + lane * 4, 0.f);
#pragma unroll 1
      for (int layer = 0; layer < NLAYERS; ++layer) {
#define HLP_CTX() BLK_CTX(); int lane = threadIdx.x & 31; asm volatile("" : "+r"(lane)); const bool isB = layer & 1, hal = isB && rb > 0; (void)hal;
#pragma unroll 1
        for (int ph = 0; ph < 2; ++ph) {
          HLP_CTX();
          if (ph == (layer == 0)) {
            const float* cs = g_cs + (epoch & 1) * 6144 + g * 384;
            if (layer) mbar_wait_u(BA(CT), (layer - 1) & 1);
            if (layer < 2) {
              if (lane == 0) flag_wait_slow(&g_csflag[isB ? 8 : g].v, isB ? epoch * 4u + 4u : epoch * 16u + 16u);
              __syncwarp();
            }
            float a[12];
#pragma unroll
            for (int i = 0; i < 12; ++i) a[i] = __ldcg(cs + isB * 3072 + i * 32 + lane);
#pragma unroll
            for (int i = 0; i < 12; ++i) {
              const float c1 = bf16r(a[i]), c2 = bf16r(a[i] - c1), c3 = (a[i] - c1) - c2;
              sts128(sb + SM_BP + (i * 32 + lane) * 16, make_uint4(pack_bf16(c1, c2), pack_bf16(c3, 0.f), 0u, 0u));
            }
          } else {
            uint32_t rdy = 0u;
            src_wait<128>(g_xf + rb * 32, xbase + layer + 1, 0xAAAAu, rdy, lane);
            rdy = 0u;
            if (hal) src_wait<128>(g_xf + (rb - 1) * 32, xbase + layer + 1, 0xAAAAu, rdy, lane);
            const float2* sp = g_stats + ((epoch & 1) * 4 + layer) * S_ + m0 + lane;
            float2 u[5];
#pragma unroll
            for (int i = 0; i < 4; ++i) u[i] = __ldcg(sp + i * 32);
            u[4] = __ldcg(sp - (hal ? 16 : 0));
#pragma unroll
            for (int i = 0; i < 5; ++i) {
              const float mean = u[i].x * (1.f / D_);
              const float var = fmaxf(fmaf(-u[i].x, mean, u[i].y) * (1.f / D_), 0.f);
              const float sd = bf16r(sqrtf(bf16r(bf16r(var) + 1e-5f)));
              const int R = i * 32 + lane;
              if (i < 4) {
                const float hm = -0.5f * bf16r(mean);
                sts_f(sb + SM_RS + (16 + R) * 4, __fdividef(1.f, sd));
                if (!isB) sts128(sb + SM_SD + R * 64 + ((R >> 1) & 3) * 16, make_uint4(__float_as_uint(sd) >> 16, 0u, 0u, 0u));
                sts128(sb + SM_AP + R * 16, make_uint4(pack_bf16(hm, hm), pack_bf16(hm, 0.f), 0u, 0u));
              } else if (hal && lane < 16) sts_f(sb + SM_RS + lane * 4, __fdividef(1.f, sd));
            }
            PROFT(lane == 0, 64 + layer * 16 + 12);
          }
        }
        HLP_CTX();
        fence_async_smem();
        __syncwarp();
        if (lane == 0) mbar_arrive(BA(B_STAT));
        PROFT(lane == 0, 64 + layer * 16 + 14);
        if (!isB && lane == 0) {
#pragma unroll 1
          for (int hp = 0; hp < 2; ++hp) {
            mbar_wait(BA(B_KVDONE), hp);
            flag_wait(&g_kvflag[hp * 8 + g].v, epoch * (16u * ((NLAYERS + 1) / 2)) + 16u * ((layer >> 1) + 1));
            const float* kvl = g_kv + ((size_t)((epoch & 1) * 2 + (layer >> 1)) * 8 + g) * 8448;
            const uint32_t kb = BA(hp ? B_KVF1 : B_KVF);
            fence_async_all();
            mbar_expect_tx(kb, 16384 + 512);
            bulk_load(sb + VB + hp * SLOT, kvl + hp * 4096, 16384, kb);
            bulk_load(sb + SM_AP + hp * 512, kvl + 8192 + hp * 128, 512, kb);
            PROFT(hp == 0, 64 + layer * 16 + 15);
          }
        }
        __syncwarp();
      }
    }
    __syncwarp();
    cluster_arrive();
    cluster_wait();
  } else {
    asm volatile("setmaxnreg.inc.sync.aligned.u32 232;");
    PROFT(threadIdx.x == 128, 235);
    cluster_wait();
    PROFT(threadIdx.x == 128, 236);
    consumer(c);
    asm volatile("bar.warp.sync 0xffffffff;\nbarrier.cluster.arrive.release.aligned;\nbarrier.cluster.wait.acquire.aligned;\n" ::: "memory");
  }
}

typedef CUresult (*PFN_encodeTiled)(CUtensorMap*, CUtensorMapDataType, cuuint32_t, void*, const cuuint64_t*, const cuuint64_t*,
                                    const cuuint32_t*, const cuuint32_t*, CUtensorMapInterleave, CUtensorMapSwizzle,
                                    CUtensorMapL2promotion, CUtensorMapFloatOOBfill);

static void make_map2(PFN_encodeTiled enc, CUtensorMap* m, const void* ptr, uint64_t cols, uint64_t rows, uint32_t box_c, uint32_t box_r) {
  cuuint64_t dims[2] = {cols, rows};
  cuuint64_t strides[1] = {cols * 2};
  cuuint32_t box[2] = {box_c, box_r};
  cuuint32_t es[2] = {1, 1};
  CUresult r = enc(m, CU_TENSOR_MAP_DATA_TYPE_BFLOAT16, 2, const_cast<void*>(ptr), dims, strides, box, es, CU_TENSOR_MAP_INTERLEAVE_NONE,
                   box_c == 64 ? CU_TENSOR_MAP_SWIZZLE_128B : CU_TENSOR_MAP_SWIZZLE_64B, CU_TENSOR_MAP_L2_PROMOTION_L2_256B, CU_TENSOR_MAP_FLOAT_OOB_FILL_NONE);
  (void)r;
}
static void make_map5(PFN_encodeTiled enc, CUtensorMap* m, const void* ptr, uint64_t cols) {
  for (int p = 0; p < 2; ++p) {
    cuuint64_t dims[5] = {cols, 2, 4, 4, 32};
    cuuint64_t strides[4] = {cols * 2, cols * (p ? 16 : 4), cols * (p ? 4 : 16), cols * 64};
    cuuint32_t box[5] = {64, 2, 4, 4, 2};
    cuuint32_t es[5] = {1, 1, 1, 1, 1};
    CUresult r = enc(m + p, CU_TENSOR_MAP_DATA_TYPE_BFLOAT16, 5, const_cast<void*>(ptr), dims, strides, box, es, CU_TENSOR_MAP_INTERLEAVE_NONE,
                     CU_TENSOR_MAP_SWIZZLE_128B, CU_TENSOR_MAP_L2_PROMOTION_L2_256B, CU_TENSOR_MAP_FLOAT_OOB_FILL_NONE);
    (void)r;
  }
}

extern "C" void kernel_launch(void* const* d_in, const int* in_sizes, int n_in, void* d_out, int out_size) {
  const bf16* A_x = (const bf16*)d_in[0];
  const bf16* A_wqkv = (const bf16*)d_in[1];
  const bf16* A_wphi = (const bf16*)d_in[2];
  const bf16* A_wo = (const bf16*)d_in[3];
  const bf16* B_wqkv = (const bf16*)d_in[5];
  const bf16* B_wo = (const bf16*)d_in[6];
  bf16* out = (bf16*)d_out;

  static PFN_encodeTiled enc = nullptr;
  static bf16 *p_x, *p_o, *p_wf;
  static uint32_t boff;
  if (!enc) {
    void* fn = nullptr; cudaDriverEntryPointQueryResult qr;
    cudaGetDriverEntryPoint("cuTensorMapEncodeTiled", &fn, cudaEnableDefault, &qr);
    enc = (PFN_encodeTiled)fn;
    cudaGetSymbolAddress((void**)&p_x, g_x);
    cudaGetSymbolAddress((void**)&p_o, g_o);
    cudaGetSymbolAddress((void**)&p_wf, g_wf);
    cudaFuncSetAttribute(mega_kernel, cudaFuncAttributeMaxDynamicSharedMemorySize, SM_TOTAL);
    cudaLaunchConfig_t cfg = {};
    cudaLaunchAttribute at; at.id = cudaLaunchAttributeClusterDimension; at.val.clusterDim.x = 2; at.val.clusterDim.y = 1; at.val.clusterDim.z = 1;
    cfg.gridDim = dim3(132); cfg.blockDim = dim3(384); cfg.dynamicSmemBytes = SM_TOTAL; cfg.attrs = &at; cfg.numAttrs = 1;
    int nc = 0;
    if (cudaOccupancyMaxActiveClusters(&nc, mega_kernel, &cfg) != cudaSuccess) { nc = 0; (void)cudaGetLastError(); }
    boff = nc >= 66 ? 0u : 4u;
  }
  Maps maps;
  make_map5(enc, &maps.m[MAP_WF], p_wf, 2048);
  make_map5(enc, &maps.m[MAP_WA], A_wqkv, 3072);
  make_map5(enc, &maps.m[MAP_WB], B_wqkv, 3072);
  make_map5(enc, &maps.m[MAP_WOA], A_wo, 1024);
  make_map5(enc, &maps.m[MAP_WOB], B_wo, 1024);
  make_map2(enc, &maps.m[MAP_X0], A_x, 1024, 2048, 64, 128);
  make_map2(enc, &maps.m[MAP_X], p_x, 1024, 2048, 64, 128);
  make_map2(enc, &maps.m[MAP_O], p_o, 1024, 2048, 64, 128);
  make_map2(enc, &maps.m[MAP_PHI], A_wphi, 32, 1024, 32, 128);
  Ctx c; c.zero = 0u; c.boff = boff; c.x0 = A_x; c.out = out;
  mega_kernel<<<132, 384, SM_TOTAL, cudaStreamPerThread>>>(maps, c, A_wqkv, B_wqkv, A_wo, B_wo);
}
```

```cpp
#include <cuda_runtime.h>
#include <cuda_bf16.h>
#include <cuda.h>
#include <stdint.h>

typedef __nv_bfloat16 bf16;

constexpr int S_ = 2048, D_ = 1024;

struct __align__(128) Flag { unsigned int v; unsigned int pad[31]; };
__device__ __align__(1024) bf16 g_x[S_ * D_];
__device__ __align__(1024) bf16 g_o[S_ * D_];
__device__ __align__(1024) uint32_t g_halo[2 * 17 * 8 * 2048];
__device__ __align__(1024) float g_kv[2 * 2 * 8 * 8448];
__device__ __align__(1024) float2 g_stats[2 * 4 * S_];
__device__ __align__(1024) float g_cs[2 * 2 * 3072];
__device__ __align__(1024) bf16 g_wf[D_ * 2048];
__device__ Flag g_kvflag[16], g_csflag[13];
__device__ __align__(128) unsigned int g_xf[16 * 32], g_of[16 * 32];
__device__ __align__(128) unsigned int g_hf[16 * 32];
__device__ __align__(128) unsigned int g_wff[8 * 32];
__device__ unsigned int g_epoch, g_err;
#define PROFT(cond, idx) asm volatile("" ::: "memory")

#define PSL 100
__device__ __forceinline__ uint32_t smem_u32(const void* p) { return (uint32_t)__cvta_generic_to_shared(p); }
__device__ __forceinline__ void mbar_init(uint32_t bar, uint32_t count) {
  asm volatile("mbarrier.init.shared::cta.b64 [%0], %1;" ::"r"(bar), "r"(count) : "memory");
}
__device__ __forceinline__ void mbar_expect_tx(uint32_t bar, uint32_t bytes) {
  asm volatile("mbarrier.arrive.expect_tx.shared::cta.b64 _, [%0], %1;" ::"r"(bar), "r"(bytes) : "memory");
}
__device__ __forceinline__ void mbar_arrive(uint32_t bar) {
  asm volatile("mbarrier.arrive.shared::cta.b64 _, [%0];" ::"r"(bar) : "memory");
}
__device__ __forceinline__ bool mbar_try_wait(uint32_t bar, uint32_t parity) {
  uint32_t ok;
  asm volatile("{\n.reg .pred p;\nmbarrier.try_wait.parity.shared::cta.b64 p, [%1], %2;\nselp.b32 %0, 1, 0, p;\n}\n"
               : "=r"(ok) : "r"(bar), "r"(parity) : "memory");
  return ok != 0;
}
__device__ __forceinline__ bool mbar_test_wait(uint32_t bar, uint32_t parity) {
  uint32_t ok;
  asm volatile("{\n.reg .pred p;\nmbarrier.test_wait.parity.shared::cta.b64 p, [%1], %2;\nselp.b32 %0, 1, 0, p;\n}\n"
               : "=r"(ok) : "r"(bar), "r"(parity) : "memory");
  return ok != 0;
}
__device__ __forceinline__ uint64_t gtimer() {
  uint64_t t; asm volatile("mov.u64 %0, %globaltimer;" : "=l"(t)); return t;
}
__device__ __forceinline__ void mbar_wait(uint32_t bar, uint32_t parity) {
  uint32_t n = 0;
#pragma unroll 1
  while (!mbar_try_wait(bar, parity)) {
    if (++n > (1u << 22)) { g_err = 1u; break; }
  }
}
__device__ __forceinline__ unsigned int ld_acquire(const unsigned int* p) {
  unsigned int v; asm volatile("ld.acquire.gpu.global.u32 %0, [%1];" : "=r"(v) : "l"(p) : "memory"); return v;
}
__device__ __forceinline__ void flag_add(unsigned int* p) {
  asm volatile("red.release.gpu.global.add.u32 [%0], 1;" ::"l"(p) : "memory");
}
__device__ __forceinline__ void flag_set(unsigned int* p, unsigned int v) {
  asm volatile("st.release.gpu.global.u32 [%0], %1;" ::"l"(p), "r"(v) : "memory");
}
template <int SLEEP>
__device__ __forceinline__ void src_wait(const unsigned int* f, unsigned int target, uint32_t need, uint32_t& ready, int lane) {
  uint32_t n = 0;
#pragma unroll 1
  while ((ready & need) != need) {
    const unsigned int v = ld_acquire(f + (lane & 15));
    ready = __ballot_sync(0xffffffffu, (int)(v - target) >= 0);
    if (SLEEP) { if ((ready & need) != need) __nanosleep(SLEEP); }
    if (++n > (1u << 20)) { g_err = 3u; break; }
  }
  __syncwarp();
}
__device__ __forceinline__ unsigned int ld_relaxed(const unsigned int* p);
__device__ __forceinline__ void src_wait_fast(const unsigned int* f, unsigned int target, uint32_t need, uint32_t& ready, int lane) {
  f += lane & 15;
  unsigned int v0 = ld_relaxed(f); __nanosleep(PSL);
  unsigned int v1 = ld_relaxed(f); __nanosleep(PSL);
  unsigned int v2 = ld_relaxed(f);
  uint32_t n = 0;
#pragma unroll 1
  while (true) {
    ready = __ballot_sync(0xffffffffu, (int)(v0 - target) >= 0);
    if ((ready & need) == need) break;
    v0 = ld_relaxed(f);
    ready = __ballot_sync(0xffffffffu, (int)(v1 - target) >= 0);
    if ((ready & need) == need) break;
    v1 = ld_relaxed(f);
    ready = __ballot_sync(0xffffffffu, (int)(v2 - target) >= 0);
    if ((ready & need) == need) break;
    v2 = ld_relaxed(f);
    if (++n > (1u << 20)) { g_err = 3u; break; }
  }
  asm volatile("fence.acquire.gpu;" ::: "memory");
  __syncwarp();
}
__device__ __forceinline__ unsigned int ld_relaxed(const unsigned int* p) {
  unsigned int v; asm volatile("ld.relaxed.gpu.global.u32 %0, [%1];" : "=r"(v) : "l"(p) : "memory"); return v;
}
__device__ __forceinline__ uint4 ld_relaxed4(const uint4* p) {
  uint4 v; asm volatile("ld.relaxed.gpu.global.v4.u32 {%0,%1,%2,%3}, [%4];" : "=r"(v.x), "=r"(v.y), "=r"(v.z), "=r"(v.w) : "l"(p) : "memory"); return v;
}
__device__ __forceinline__ void st_relaxed4(uint4* p, uint32_t a, uint32_t b, uint32_t c, uint32_t d) {
  asm volatile("st.relaxed.gpu.global.v4.u32 [%0], {%1,%2,%3,%4};" ::"l"(p), "r"(a), "r"(b), "r"(c), "r"(d) : "memory");
}
__device__ __forceinline__ void st_relaxed4_p(bool on, uint4* p, uint32_t a, uint32_t b, uint32_t c, uint32_t d) {
  asm volatile("{\n.reg .pred p;\nsetp.ne.b32 p, %5, 0;\n@p st.relaxed.gpu.global.v4.u32 [%0], {%1,%2,%3,%4};\n}\n" ::"l"(p), "r"(a), "r"(b), "r"(c), "r"(d), "r"((int)on) : "memory");
}
template <int SLEEP>
__device__ __forceinline__ void flag_wait_t(const unsigned int* p, unsigned int target) {
  uint32_t n = 0;
#pragma unroll 1
  while ((int)(ld_acquire(p) - target) < 0) {
    if (SLEEP) __nanosleep(SLEEP);
    if (++n > (1u << 20)) { g_err = 2u; break; }
  }
}
__device__ __forceinline__ void flag_wait(const unsigned int* p, unsigned int target) { flag_wait_t<0>(p, target); }
__device__ __forceinline__ void flag_wait_slow(const unsigned int* p, unsigned int target) { flag_wait_t<256>(p, target); }
__device__ __forceinline__ void tma_load_2d(uint32_t dst, const CUtensorMap* tm, int c0, int c1, uint32_t bar) {
  asm volatile("cp.async.bulk.tensor.2d.shared::cluster.global.mbarrier::complete_tx::bytes [%0], [%1, {%2, %3}], [%4];"
               ::"r"(dst), "l"(tm), "r"(c0), "r"(c1), "r"(bar) : "memory");
}
__device__ __forceinline__ void tma_load_2d_mc(uint32_t dst, const CUtensorMap* tm, int c0, int c1, uint32_t bar, uint16_t mask) {
  asm volatile("cp.async.bulk.tensor.2d.shared::cluster.global.mbarrier::complete_tx::bytes.multicast::cluster [%0], [%1, {%2, %3}], [%4], %5;"
               ::"r"(dst), "l"(tm), "r"(c0), "r"(c1), "r"(bar), "h"(mask) : "memory");
}
__device__ __forceinline__ void mbar_wait_u(uint32_t bar, uint32_t parity) {
  uint32_t n = 0;
#pragma unroll 1
  while (!__all_sync(0xffffffffu, mbar_try_wait(bar, parity))) {
    if (++n > (1u << 22)) { g_err = 1u; break; }
  }
}
__device__ __forceinline__ void expect_tx_e(uint32_t bar, uint32_t bytes) {
  asm volatile("{\n.reg .pred p;\nelect.sync _|p, 0xffffffff;\n@p mbarrier.arrive.expect_tx.shared::cta.b64 _, [%0], %1;\n}\n" ::"r"(bar), "r"(bytes) : "memory");
}
__device__ __forceinline__ void tma_2d_e(uint32_t dst, const CUtensorMap* tm, int c0, int c1, uint32_t bar) {
  asm volatile("{\n.reg .pred p;\nelect.sync _|p, 0xffffffff;\n"
               "@p cp.async.bulk.tensor.2d.shared::cluster.global.mbarrier::complete_tx::bytes [%0], [%1, {%2, %3}], [%4];\n}\n"
               ::"r"(dst), "l"(tm), "r"(c0), "r"(c1), "r"(bar) : "memory");
}
__device__ __forceinline__ void tma_2d_mc_e(uint32_t dst, const CUtensorMap* tm, int c0, int c1, uint32_t bar) {
  asm volatile("{\n.reg .pred p;\nelect.sync _|p, 0xffffffff;\n"
               "@p cp.async.bulk.tensor.2d.shared::cluster.global.mbarrier::complete_tx::bytes.multicast::cluster [%0], [%1, {%2, %3}], [%4], %5;\n}\n"
               ::"r"(dst), "l"(tm), "r"(c0), "r"(c1), "r"(bar), "h"((uint16_t)3) : "memory");
}
__device__ __forceinline__ void tma_5d(uint32_t dst, const CUtensorMap* tm, int c0, int c4, uint32_t bar) {
  asm volatile("cp.async.bulk.tensor.5d.shared::cluster.global.mbarrier::complete_tx::bytes [%0], [%1, {%2, %5, %5, %5, %3}], [%4];"
               ::"r"(dst), "l"(tm), "r"(c0), "r"(c4), "r"(bar), "r"(0) : "memory");
}
__device__ __forceinline__ void tma_5d_e(uint32_t dst, const CUtensorMap* tm, int c0, int c4, uint32_t bar) {
  asm volatile("{\n.reg .pred p;\nelect.sync _|p, 0xffffffff;\n"
               "@p cp.async.bulk.tensor.5d.shared::cluster.global.mbarrier::complete_tx::bytes [%0], [%1, {%2, %5, %5, %5, %3}], [%4];\n}\n"
               ::"r"(dst), "l"(tm), "r"(c0), "r"(c4), "r"(bar), "r"(0) : "memory");
}
__device__ __forceinline__ void tma_5d_mc_e(uint32_t dst, const CUtensorMap* tm, int c0, int c4, uint32_t bar) {
  asm volatile("{\n.reg .pred p;\nelect.sync _|p, 0xffffffff;\n"
               "@p cp.async.bulk.tensor.5d.shared::cluster.global.mbarrier::complete_tx::bytes.multicast::cluster [%0], [%1, {%2, %6, %6, %6, %3}], [%4], %5;\n}\n"
               ::"r"(dst), "l"(tm), "r"(c0), "r"(c4), "r"(bar), "h"((uint16_t)3), "r"(0) : "memory");
}
__device__ __forceinline__ void wait_tma_2d(bool w, uint32_t eb, uint32_t par, uint32_t dst, const CUtensorMap* tm, int c0, int c1, uint32_t fb) {
  asm volatile("" : "+r"(dst), "+l"(tm), "+r"(c0), "+r"(fb));
  if (w) mbar_wait_u(eb, par);
  tma_2d_e(dst, tm, c0, c1, fb);
}
__device__ __forceinline__ void wait_tma_5d_mc(bool w, uint32_t eb, uint32_t par, uint32_t dst, const CUtensorMap* tm, int c0, int c4, uint32_t fb) {
  asm volatile("" : "+r"(dst), "+l"(tm), "+r"(c0), "+r"(c4), "+r"(fb));
  if (w) mbar_wait_u(eb, par);
  tma_5d_mc_e(dst, tm, c0, c4, fb);
}
__device__ __forceinline__ void stg128(void* p, uint32_t a, uint32_t b, uint32_t c, uint32_t d) {
  asm volatile("st.global.v4.u32 [%0], {%1,%2,%3,%4};" ::"l"(p), "r"(a), "r"(b), "r"(c), "r"(d) : "memory");
}
__device__ __forceinline__ void stg128_p(bool on, void* p, uint32_t a, uint32_t b, uint32_t c, uint32_t d) {
  asm volatile("{\n.reg .pred p;\nsetp.ne.b32 p, %5, 0;\n@p st.global.v4.u32 [%0], {%1,%2,%3,%4};\n}\n" ::"l"(p), "r"(a), "r"(b), "r"(c), "r"(d), "r"((int)on) : "memory");
}
__device__ __forceinline__ void ldg128(const void* p, uint32_t& a, uint32_t& b, uint32_t& c, uint32_t& d) {
  asm volatile("ld.global.cg.v4.u32 {%0,%1,%2,%3}, [%4];" : "=r"(a), "=r"(b), "=r"(c), "=r"(d) : "l"(p) : "memory");
}
__device__ __forceinline__ uint32_t ldg32(const void* p) {
  uint32_t v; asm volatile("ld.global.nc.u32 %0, [%1];" : "=r"(v) : "l"(p) : "memory"); return v;
}
__device__ __forceinline__ void tma_pf_e(const CUtensorMap* tm, int c0, int c1) {
  asm volatile("{\n.reg .pred p;\nelect.sync _|p, 0xffffffff;\n"
               "@p cp.async.bulk.prefetch.tensor.2d.L2.global.tile [%0, {%1, %2}];\n}\n" ::"l"(tm), "r"(c0), "r"(c1) : "memory");
}
__device__ __forceinline__ void tma_2d_to_e(uint32_t dst, const CUtensorMap* tm, int c0, int c1, uint32_t bar, uint32_t mask) {
  asm volatile("{\n.reg .pred p;\nelect.sync _|p, 0xffffffff;\n"
               "@p cp.async.bulk.tensor.2d.shared::cluster.global.mbarrier::complete_tx::bytes.multicast::cluster [%0], [%1, {%2, %3}], [%4], %5;\n}\n"
               ::"r"(dst), "l"(tm), "r"(c0), "r"(c1), "r"(bar), "h"((uint16_t)mask) : "memory");
}
__device__ __forceinline__ void tma_3d_mc_e(uint32_t dst, const CUtensorMap* tm, int c1, int c2, uint32_t bar) {
  asm volatile("{\n.reg .pred p;\nelect.sync _|p, 0xffffffff;\n"
               "@p cp.async.bulk.tensor.3d.shared::cluster.global.mbarrier::complete_tx::bytes.multicast::cluster [%0], [%1, {%6, %2, %3}], [%4], %5;\n}\n"
               ::"r"(dst), "l"(tm), "r"(c1), "r"(c2), "r"(bar), "h"((uint16_t)3), "r"(0) : "memory");
}
__device__ __forceinline__ uint32_t poll_flags(const unsigned int* f, unsigned int target, int lane) {
  const unsigned int v = ld_acquire(f + (lane & 15));
  const uint32_t r = __ballot_sync(0xffffffffu, (int)(v - target) >= 0);
  __syncwarp();
  return r;
}
__device__ __forceinline__ void mbar_arrive_cluster(uint32_t local_bar, uint32_t rank) {
  asm volatile("{\n.reg .b32 ra;\nmapa.shared::cluster.u32 ra, %0, %1;\nmbarrier.arrive.shared::cluster.b64 _, [ra];\n}\n"
               ::"r"(local_bar), "r"(rank) : "memory");
}
__device__ __forceinline__ void release2(uint32_t bar) { mbar_arrive_cluster(bar, 0); mbar_arrive_cluster(bar, 1); }
__device__ __forceinline__ void release2c(uint32_t off) {
  asm volatile("mbarrier.arrive.shared::cluster.b64 _, [%0];\nmbarrier.arrive.shared::cluster.b64 _, [%1];" ::"r"(off), "r"(off + (1u << 24)) : "memory");
}
__device__ __forceinline__ void tma_store_2d(const CUtensorMap* tm, uint32_t src, int c0, int c1) {
  asm volatile("cp.async.bulk.tensor.2d.global.shared::cta.bulk_group [%0, {%2, %3}], [%1];"
               ::"l"(tm), "r"(src), "r"(c0), "r"(c1) : "memory");
}
__device__ __forceinline__ void tma_store_5d(const CUtensorMap* tm, uint32_t src, int c0, int c4) {
  asm volatile("cp.async.bulk.tensor.5d.global.shared::cta.bulk_group [%0, {%2, %4, %4, %4, %3}], [%1];"
               ::"l"(tm), "r"(src), "r"(c0), "r"(c4), "r"(0) : "memory");
}
__device__ __forceinline__ void bulk_store(void* dst, uint32_t src, uint32_t bytes) {
  asm volatile("cp.async.bulk.global.shared::cta.bulk_group [%0], [%1], %2;" ::"l"(dst), "r"(src), "r"(bytes) : "memory");
}
__device__ __forceinline__ void bulk_load(uint32_t dst, const void* src, uint32_t bytes, uint32_t bar) {
  asm volatile("cp.async.bulk.shared::cluster.global.mbarrier::complete_tx::bytes [%0], [%1], %2, [%3];" ::"r"(dst), "l"(src), "r"(bytes), "r"(bar) : "memory");
}
__device__ __forceinline__ void bulk_red_add(void* dst, uint32_t src, uint32_t bytes) {
  asm volatile("cp.reduce.async.bulk.global.shared::cta.bulk_group.add.f32 [%0], [%1], %2;" ::"l"(dst), "r"(src), "r"(bytes) : "memory");
}
__device__ __forceinline__ void bulk_commit() { asm volatile("cp.async.bulk.commit_group;" ::: "memory"); }
__device__ __forceinline__ void bulk_wait0() { asm volatile("cp.async.bulk.wait_group 0;" ::: "memory"); }
__device__ __forceinline__ void fence_async_smem() { asm volatile("fence.proxy.async.shared::cta;" ::: "memory"); }
__device__ __forceinline__ void fence_async_all() { asm volatile("fence.proxy.async.global;" ::: "memory"); }
__device__ __forceinline__ void wgmma_fence() { asm volatile("wgmma.fence.sync.aligned;" ::: "memory"); }
__device__ __forceinline__ void wgmma_commit() { asm volatile("wgmma.commit_group.sync.aligned;" ::: "memory"); }
template <int N> __device__ __forceinline__ void wgmma_wait() { asm volatile("wgmma.wait_group.sync.aligned %0;" ::"n"(N) : "memory"); }
__device__ __forceinline__ void cluster_arrive() { asm volatile("barrier.cluster.arrive.release.aligned;" ::: "memory"); }
__device__ __forceinline__ void cluster_wait() { asm volatile("barrier.cluster.wait.acquire.aligned;" ::: "memory"); }
template <int ID, int N> __device__ __forceinline__ void nbar() { asm volatile("bar.sync %0, %1;" ::"n"(ID), "n"(N) : "memory"); }
__device__ __forceinline__ uint64_t make_desc(uint32_t addr, uint32_t lbo_bytes, uint32_t sbo_bytes) {
  uint64_t d = 0;
  d |= (uint64_t)((addr & 0x3FFFF) >> 4);
  d |= (uint64_t)((lbo_bytes >> 4) & 0x3FFF) << 16;
  d |= (uint64_t)((sbo_bytes >> 4) & 0x3FFF) << 32;
  d |= (uint64_t)1 << 62;
  return d;
}
__device__ __forceinline__ uint64_t desc64(uint32_t lo, uint32_t hi) { return (uint64_t)lo | ((uint64_t)hi << 32); }
__device__ __forceinline__ uint32_t pack_bf16(float lo, float hi) {
  uint32_t r; asm("cvt.rn.bf16x2.f32 %0, %1, %2;" : "=r"(r) : "f"(hi), "f"(lo)); return r;
}
__device__ __forceinline__ uint32_t add_bf16x2(uint32_t a, uint32_t b) {
  uint32_t r; asm("add.rn.bf16x2 %0, %1, %2;" : "=r"(r) : "r"(a), "r"(b)); return r;
}
__device__ __forceinline__ float bf16r(float x) { return __bfloat162float(__float2bfloat16_rn(x)); }
__device__ __forceinline__ float bf_lo(uint32_t u) { return __uint_as_float(u << 16); }
__device__ __forceinline__ float bf_hi(uint32_t u) { return __uint_as_float(u & 0xFFFF0000u); }
__device__ __forceinline__ float ex2(float x) { float r; asm("ex2.approx.ftz.f32 %0, %1;" : "=f"(r) : "f"(x)); return r; }
__device__ __forceinline__ float ex2v(float x) { float r; asm volatile("ex2.approx.ftz.f32 %0, %1;" : "=f"(r) : "f"(x) : "memory"); return r; }
__device__ __forceinline__ float rcp(float x) { float r; asm("rcp.approx.ftz.f32 %0, %1;" : "=f"(r) : "f"(x)); return r; }
__device__ __forceinline__ void mma_bf16(float (&d)[4], uint32_t a0, uint32_t a1, uint32_t a2, uint32_t a3, uint32_t b0, uint32_t b1) {
  asm("mma.sync.aligned.m16n8k16.row.col.f32.bf16.bf16.f32 {%0,%1,%2,%3}, {%4,%5,%6,%7}, {%8,%9}, {%0,%1,%2,%3};"
               : "+f"(d[0]), "+f"(d[1]), "+f"(d[2]), "+f"(d[3]) : "r"(a0), "r"(a1), "r"(a2), "r"(a3), "r"(b0), "r"(b1));
}
__device__ __forceinline__ void ldsm_x4(uint32_t& r0, uint32_t& r1, uint32_t& r2, uint32_t& r3, uint32_t addr) {
  asm volatile("ldmatrix.sync.aligned.m8n8.x4.shared.b16 {%0,%1,%2,%3}, [%4];"
               : "=r"(r0), "=r"(r1), "=r"(r2), "=r"(r3) : "r"(addr) : "memory");
}
__device__ __forceinline__ void ldsm_x4_t(uint32_t& r0, uint32_t& r1, uint32_t& r2, uint32_t& r3, uint32_t addr) {
  asm volatile("ldmatrix.sync.aligned.m8n8.x4.trans.shared.b16 {%0,%1,%2,%3}, [%4];"
               : "=r"(r0), "=r"(r1), "=r"(r2), "=r"(r3) : "r"(addr) : "memory");
}
__device__ __forceinline__ void ldsm_x2_t(uint32_t& r0, uint32_t& r1, uint32_t addr) {
  asm volatile("ldmatrix.sync.aligned.m8n8.x2.trans.shared.b16 {%0,%1}, [%2];"
               : "=r"(r0), "=r"(r1) : "r"(addr) : "memory");
}
__device__ __forceinline__ void stsm_x4(uint32_t addr, uint32_t r0, uint32_t r1, uint32_t r2, uint32_t r3) {
  asm volatile("stmatrix.sync.aligned.m8n8.x4.shared.b16 [%0], {%1,%2,%3,%4};"
               ::"r"(addr), "r"(r0), "r"(r1), "r"(r2), "r"(r3) : "memory");
}
__device__ __forceinline__ void stsm_x4_p(bool on, uint32_t addr, uint32_t r0, uint32_t r1, uint32_t r2, uint32_t r3) {
  asm volatile("{\n.reg .pred p;\nsetp.ne.b32 p, %5, 0;\n@p stmatrix.sync.aligned.m8n8.x4.shared.b16 [%0], {%1,%2,%3,%4};\n}\n"
               ::"r"(addr), "r"(r0), "r"(r1), "r"(r2), "r"(r3), "r"((int)on) : "memory");
}
__device__ __forceinline__ float2 lds_f2(uint32_t addr) {
  float2 v; asm volatile("ld.shared.v2.f32 {%0,%1}, [%2];" : "=f"(v.x), "=f"(v.y) : "r"(addr) : "memory"); return v;
}
__device__ __forceinline__ uint4 lds128(uint32_t addr) {
  uint4 v; asm volatile("ld.shared.v4.b32 {%0,%1,%2,%3}, [%4];" : "=r"(v.x), "=r"(v.y), "=r"(v.z), "=r"(v.w) : "r"(addr) : "memory"); return v;
}
__device__ __forceinline__ void sts128(uint32_t addr, uint4 v) {
  asm volatile("st.shared.v4.b32 [%0], {%1,%2,%3,%4};" ::"r"(addr), "r"(v.x), "r"(v.y), "r"(v.z), "r"(v.w) : "memory");
}
__device__ __forceinline__ float lds_f(uint32_t addr) {
  float v; asm volatile("ld.shared.f32 %0, [%1];" : "=f"(v) : "r"(addr) : "memory"); return v;
}
__device__ __forceinline__ void sts16(uint32_t addr, uint32_t v) {
  asm volatile("st.shared.u16 [%0], %1;" ::"r"(addr), "h"((unsigned short)v) : "memory");
}
__device__ __forceinline__ void nbar_dyn(int id, int n) { asm volatile("bar.sync %0, %1;" ::"r"(id), "r"(n) : "memory"); }
__device__ __forceinline__ uint64_t make_desc_ns(uint32_t addr, uint32_t lbo_bytes, uint32_t sbo_bytes) {
  return (uint64_t)((addr & 0x3FFFF) >> 4) | ((uint64_t)(lbo_bytes >> 4) << 16) | ((uint64_t)(sbo_bytes >> 4) << 32);
}
__device__ __forceinline__ void sts_f(uint32_t addr, float v) { asm volatile("st.shared.f32 [%0], %1;" ::"r"(addr), "f"(v) : "memory"); }
__device__ __forceinline__ void sts64(uint32_t addr, uint32_t a, uint32_t b) {
  asm volatile("st.shared.v2.b32 [%0], {%1,%2};" ::"r"(addr), "r"(a), "r"(b) : "memory");
}
__device__ __forceinline__ void sts_f2(uint32_t addr, float a, float b) {
  asm volatile("st.shared.v2.f32 [%0], {%1,%2};" ::"r"(addr), "f"(a), "f"(b) : "memory");
}
__device__ __forceinline__ void red_add2(float* p, float a, float b) {
  asm volatile("red.global.add.v2.f32 [%0], {%1,%2};" ::"l"(p), "f"(a), "f"(b) : "memory");
}
__device__ __forceinline__ void red_add2_p(bool on, float* p, float a, float b) {
  asm volatile("{\n.reg .pred p;\nsetp.ne.b32 p, %3, 0;\n@p red.global.add.v2.f32 [%0], {%1,%2};\n}\n" ::"l"(p), "f"(a), "f"(b), "r"((int)on) : "memory");
}
__device__ __forceinline__ void red_add4(float* p, float a, float b, float c, float d) {
  asm volatile("red.global.add.v4.f32 [%0], {%1,%2,%3,%4};" ::"l"(p), "f"(a), "f"(b), "f"(c), "f"(d) : "memory");
}
__device__ __forceinline__ void red_add1(float* p, float a) {
  asm volatile("red.global.add.f32 [%0], %1;" ::"l"(p), "f"(a) : "memory");
}
__device__ __forceinline__ void l2_prefetch(const void* p, uint32_t bytes) {
  asm volatile("cp.async.bulk.prefetch.L2.global [%0], %1;" ::"l"(p), "r"(bytes) : "memory");
}

__device__ __forceinline__ void wgmma_n256(float (&d)[192], uint64_t da, uint64_t db, int scale_d) {
  asm volatile("{\n.reg .pred p;\nsetp.ne.b32 p, %130, 0;\n"
    "wgmma.mma_async.sync.aligned.m64n256k16.f32.bf16.bf16 {%0, %1, %2, %3, %4, %5, %6, %7, %8, %9, %10, %11, %12, %13, %14, %15, %16, %17, %18, %19, %20, %21, %22, %23, %24, %25, %26, %27, %28, %29, %30, %31, %32, %33, %34, %35, %36, %37, %38, %39, %40, %41, %42, %43, %44, %45, %46, %47, %48, %49, %50, %51, %52, %53, %54, %55, %56, %57, %58, %59, %60, %61, %62, %63, %64, %65, %66, %67, %68, %69, %70, %71, %72, %73, %74, %75, %76, %77, %78, %79, %80, %81, %82, %83, %84, %85, %86, %87, %88, %89, %90, %91, %92, %93, %94, %95, %96, %97, %98, %99, %100, %101, %102, %103, %104, %105, %106, %107, %108, %109, %110, %111, %112, %113, %114, %115, %116, %117, %118, %119, %120, %121, %122, %123, %124, %125, %126, %127}, %128, %129, p, 1, 1, 0, 1;\n}\n"
    : "+f"(d[0]), "+f"(d[1]), "+f"(d[2]), "+f"(d[3]), "+f"(d[4]), "+f"(d[5]), "+f"(d[6]), "+f"(d[7]), "+f"(d[8]), "+f"(d[9]), "+f"(d[10]), "+f"(d[11]), "+f"(d[12]), "+f"(d[13]), "+f"(d[14]), "+f"(d[15]), "+f"(d[16]), "+f"(d[17]), "+f"(d[18]), "+f"(d[19]), "+f"(d[20]), "+f"(d[21]), "+f"(d[22]), "+f"(d[23]), "+f"(d[24]), "+f"(d[25]), "+f"(d[26]), "+f"(d[27]), "+f"(d[28]), "+f"(d[29]), "+f"(d[30]), "+f"(d[31]), "+f"(d[32]), "+f"(d[33]), "+f"(d[34]), "+f"(d[35]), "+f"(d[36]), "+f"(d[37]), "+f"(d[38]), "+f"(d[39]), "+f"(d[40]), "+f"(d[41]), "+f"(d[42]), "+f"(d[43]), "+f"(d[44]), "+f"(d[45]), "+f"(d[46]), "+f"(d[47]), "+f"(d[48]), "+f"(d[49]), "+f"(d[50]), "+f"(d[51]), "+f"(d[52]), "+f"(d[53]), "+f"(d[54]), "+f"(d[55]), "+f"(d[56]), "+f"(d[57]), "+f"(d[58]), "+f"(d[59]), "+f"(d[60]), "+f"(d[61]), "+f"(d[62]), "+f"(d[63]), "+f"(d[64]), "+f"(d[65]), "+f"(d[66]), "+f"(d[67]), "+f"(d[68]), "+f"(d[69]), "+f"(d[70]), "+f"(d[71]), "+f"(d[72]), "+f"(d[73]), "+f"(d[74]), "+f"(d[75]), "+f"(d[76]), "+f"(d[77]), "+f"(d[78]), "+f"(d[79]), "+f"(d[80]), "+f"(d[81]), "+f"(d[82]), "+f"(d[83]), "+f"(d[84]), "+f"(d[85]), "+f"(d[86]), "+f"(d[87]), "+f"(d[88]), "+f"(d[89]), "+f"(d[90]), "+f"(d[91]), "+f"(d[92]), "+f"(d[93]), "+f"(d[94]), "+f"(d[95]), "+f"(d[96]), "+f"(d[97]), "+f"(d[98]), "+f"(d[99]), "+f"(d[100]), "+f"(d[101]), "+f"(d[102]), "+f"(d[103]), "+f"(d[104]), "+f"(d[105]), "+f"(d[106]), "+f"(d[107]), "+f"(d[108]), "+f"(d[109]), "+f"(d[110]), "+f"(d[111]), "+f"(d[112]), "+f"(d[113]), "+f"(d[114]), "+f"(d[115]), "+f"(d[116]), "+f"(d[117]), "+f"(d[118]), "+f"(d[119]), "+f"(d[120]), "+f"(d[121]), "+f"(d[122]), "+f"(d[123]), "+f"(d[124]), "+f"(d[125]), "+f"(d[126]), "+f"(d[127])
    : "l"(da), "l"(db), "r"(scale_d));
}
__device__ __forceinline__ void wgmma_n128(float (&d)[192], uint64_t da, uint64_t db, int scale_d) {
  asm volatile("{\n.reg .pred p;\nsetp.ne.b32 p, %66, 0;\n"
    "wgmma.mma_async.sync.aligned.m64n128k16.f32.bf16.bf16 {%0, %1, %2, %3, %4, %5, %6, %7, %8, %9, %10, %11, %12, %13, %14, %15, %16, %17, %18, %19, %20, %21, %22, %23, %24, %25, %26, %27, %28, %29, %30, %31, %32, %33, %34, %35, %36, %37, %38, %39, %40, %41, %42, %43, %44, %45, %46, %47, %48, %49, %50, %51, %52, %53, %54, %55, %56, %57, %58, %59, %60, %61, %62, %63}, %64, %65, p, 1, 1, 0, 1;\n}\n"
    : "+f"(d[128]), "+f"(d[129]), "+f"(d[130]), "+f"(d[131]), "+f"(d[132]), "+f"(d[133]), "+f"(d[134]), "+f"(d[135]), "+f"(d[136]), "+f"(d[137]), "+f"(d[138]), "+f"(d[139]), "+f"(d[140]), "+f"(d[141]), "+f"(d[142]), "+f"(d[143]), "+f"(d[144]), "+f"(d[145]), "+f"(d[146]), "+f"(d[147]), "+f"(d[148]), "+f"(d[149]), "+f"(d[150]), "+f"(d[151]), "+f"(d[152]), "+f"(d[153]), "+f"(d[154]), "+f"(d[155]), "+f"(d[156]), "+f"(d[157]), "+f"(d[158]), "+f"(d[159]), "+f"(d[160]), "+f"(d[161]), "+f"(d[162]), "+f"(d[163]), "+f"(d[164]), "+f"(d[165]), "+f"(d[166]), "+f"(d[167]), "+f"(d[168]), "+f"(d[169]), "+f"(d[170]), "+f"(d[171]), "+f"(d[172]), "+f"(d[173]), "+f"(d[174]), "+f"(d[175]), "+f"(d[176]), "+f"(d[177]), "+f"(d[178]), "+f"(d[179]), "+f"(d[180]), "+f"(d[181]), "+f"(d[182]), "+f"(d[183]), "+f"(d[184]), "+f"(d[185]), "+f"(d[186]), "+f"(d[187]), "+f"(d[188]), "+f"(d[189]), "+f"(d[190]), "+f"(d[191])
    : "l"(da), "l"(db), "r"(scale_d));
}
__device__ __forceinline__ void wgmma_n256_k(float (&d)[192], uint64_t da, uint64_t db, int scale_d) {
  asm volatile("{\n.reg .pred p;\nsetp.ne.b32 p, %130, 0;\n"
    "wgmma.mma_async.sync.aligned.m64n256k16.f32.bf16.bf16 {%0, %1, %2, %3, %4, %5, %6, %7, %8, %9, %10, %11, %12, %13, %14, %15, %16, %17, %18, %19, %20, %21, %22, %23, %24, %25, %26, %27, %28, %29, %30, %31, %32, %33, %34, %35, %36, %37, %38, %39, %40, %41, %42, %43, %44, %45, %46, %47, %48, %49, %50, %51, %52, %53, %54, %55, %56, %57, %58, %59, %60, %61, %62, %63, %64, %65, %66, %67, %68, %69, %70, %71, %72, %73, %74, %75, %76, %77, %78, %79, %80, %81, %82, %83, %84, %85, %86, %87, %88, %89, %90, %91, %92, %93, %94, %95, %96, %97, %98, %99, %100, %101, %102, %103, %104, %105, %106, %107, %108, %109, %110, %111, %112, %113, %114, %115, %116, %117, %118, %119, %120, %121, %122, %123, %124, %125, %126, %127}, %128, %129, p, 1, 1, 0, 0;\n}\n"
    : "+f"(d[0]), "+f"(d[1]), "+f"(d[2]), "+f"(d[3]), "+f"(d[4]), "+f"(d[5]), "+f"(d[6]), "+f"(d[7]), "+f"(d[8]), "+f"(d[9]), "+f"(d[10]), "+f"(d[11]), "+f"(d[12]), "+f"(d[13]), "+f"(d[14]), "+f"(d[15]), "+f"(d[16]), "+f"(d[17]), "+f"(d[18]), "+f"(d[19]), "+f"(d[20]), "+f"(d[21]), "+f"(d[22]), "+f"(d[23]), "+f"(d[24]), "+f"(d[25]), "+f"(d[26]), "+f"(d[27]), "+f"(d[28]), "+f"(d[29]), "+f"(d[30]), "+f"(d[31]), "+f"(d[32]), "+f"(d[33]), "+f"(d[34]), "+f"(d[35]), "+f"(d[36]), "+f"(d[37]), "+f"(d[38]), "+f"(d[39]), "+f"(d[40]), "+f"(d[41]), "+f"(d[42]), "+f"(d[43]), "+f"(d[44]), "+f"(d[45]), "+f"(d[46]), "+f"(d[47]), "+f"(d[48]), "+f"(d[49]), "+f"(d[50]), "+f"(d[51]), "+f"(d[52]), "+f"(d[53]), "+f"(d[54]), "+f"(d[55]), "+f"(d[56]), "+f"(d[57]), "+f"(d[58]), "+f"(d[59]), "+f"(d[60]), "+f"(d[61]), "+f"(d[62]), "+f"(d[63]), "+f"(d[64]), "+f"(d[65]), "+f"(d[66]), "+f"(d[67]), "+f"(d[68]), "+f"(d[69]), "+f"(d[70]), "+f"(d[71]), "+f"(d[72]), "+f"(d[73]), "+f"(d[74]), "+f"(d[75]), "+f"(d[76]), "+f"(d[77]), "+f"(d[78]), "+f"(d[79]), "+f"(d[80]), "+f"(d[81]), "+f"(d[82]), "+f"(d[83]), "+f"(d[84]), "+f"(d[85]), "+f"(d[86]), "+f"(d[87]), "+f"(d[88]), "+f"(d[89]), "+f"(d[90]), "+f"(d[91]), "+f"(d[92]), "+f"(d[93]), "+f"(d[94]), "+f"(d[95]), "+f"(d[96]), "+f"(d[97]), "+f"(d[98]), "+f"(d[99]), "+f"(d[100]), "+f"(d[101]), "+f"(d[102]), "+f"(d[103]), "+f"(d[104]), "+f"(d[105]), "+f"(d[106]), "+f"(d[107]), "+f"(d[108]), "+f"(d[109]), "+f"(d[110]), "+f"(d[111]), "+f"(d[112]), "+f"(d[113]), "+f"(d[114]), "+f"(d[115]), "+f"(d[116]), "+f"(d[117]), "+f"(d[118]), "+f"(d[119]), "+f"(d[120]), "+f"(d[121]), "+f"(d[122]), "+f"(d[123]), "+f"(d[124]), "+f"(d[125]), "+f"(d[126]), "+f"(d[127])
    : "l"(da), "l"(db), "r"(scale_d));
}
__device__ __forceinline__ void wgmma_n128_k(float (&d)[192], uint64_t da, uint64_t db, int scale_d) {
  asm volatile("{\n.reg .pred p;\nsetp.ne.b32 p, %66, 0;\n"
    "wgmma.mma_async.sync.aligned.m64n128k16.f32.bf16.bf16 {%0, %1, %2, %3, %4, %5, %6, %7, %8, %9, %10, %11, %12, %13, %14, %15, %16, %17, %18, %19, %20, %21, %22, %23, %24, %25, %26, %27, %28, %29, %30, %31, %32, %33, %34, %35, %36, %37, %38, %39, %40, %41, %42, %43, %44, %45, %46, %47, %48, %49, %50, %51, %52, %53, %54, %55, %56, %57, %58, %59, %60, %61, %62, %63}, %64, %65, p, 1, 1, 0, 0;\n}\n"
    : "+f"(d[128]), "+f"(d[129]), "+f"(d[130]), "+f"(d[131]), "+f"(d[132]), "+f"(d[133]), "+f"(d[134]), "+f"(d[135]), "+f"(d[136]), "+f"(d[137]), "+f"(d[138]), "+f"(d[139]), "+f"(d[140]), "+f"(d[141]), "+f"(d[142]), "+f"(d[143]), "+f"(d[144]), "+f"(d[145]), "+f"(d[146]), "+f"(d[147]), "+f"(d[148]), "+f"(d[149]), "+f"(d[150]), "+f"(d[151]), "+f"(d[152]), "+f"(d[153]), "+f"(d[154]), "+f"(d[155]), "+f"(d[156]), "+f"(d[157]), "+f"(d[158]), "+f"(d[159]), "+f"(d[160]), "+f"(d[161]), "+f"(d[162]), "+f"(d[163]), "+f"(d[164]), "+f"(d[165]), "+f"(d[166]), "+f"(d[167]), "+f"(d[168]), "+f"(d[169]), "+f"(d[170]), "+f"(d[171]), "+f"(d[172]), "+f"(d[173]), "+f"(d[174]), "+f"(d[175]), "+f"(d[176]), "+f"(d[177]), "+f"(d[178]), "+f"(d[179]), "+f"(d[180]), "+f"(d[181]), "+f"(d[182]), "+f"(d[183]), "+f"(d[184]), "+f"(d[185]), "+f"(d[186]), "+f"(d[187]), "+f"(d[188]), "+f"(d[189]), "+f"(d[190]), "+f"(d[191])
    : "l"(da), "l"(db), "r"(scale_d));
}
__device__ __forceinline__ void wgmma_n40_tt(float (&d)[20], uint64_t da, uint64_t db, int scale_d) {
  asm volatile("{\n.reg .pred p;\nsetp.ne.b32 p, %22, 0;\n"
    "wgmma.mma_async.sync.aligned.m64n40k16.f32.bf16.bf16 {%0, %1, %2, %3, %4, %5, %6, %7, %8, %9, %10, %11, %12, %13, %14, %15, %16, %17, %18, %19}, %20, %21, p, 1, 1, 1, 1;\n}\n"
    : "+f"(d[0]), "+f"(d[1]), "+f"(d[2]), "+f"(d[3]), "+f"(d[4]), "+f"(d[5]), "+f"(d[6]), "+f"(d[7]), "+f"(d[8]), "+f"(d[9]), "+f"(d[10]), "+f"(d[11]), "+f"(d[12]), "+f"(d[13]), "+f"(d[14]), "+f"(d[15]), "+f"(d[16]), "+f"(d[17]), "+f"(d[18]), "+f"(d[19])
    : "l"(da), "l"(db), "r"(scale_d));
}
__device__ __forceinline__ void wgmma_n40_rs(float (&d)[20], const uint32_t (&a)[4], uint64_t db, int scale_d) {
  asm volatile("{\n.reg .pred p;\nsetp.ne.b32 p, %25, 0;\n"
    "wgmma.mma_async.sync.aligned.m64n40k16.f32.bf16.bf16 {%0, %1, %2, %3, %4, %5, %6, %7, %8, %9, %10, %11, %12, %13, %14, %15, %16, %17, %18, %19}, {%20, %21, %22, %23}, %24, p, 1, 1, 1;\n}\n"
    : "+f"(d[0]), "+f"(d[1]), "+f"(d[2]), "+f"(d[3]), "+f"(d[4]), "+f"(d[5]), "+f"(d[6]), "+f"(d[7]), "+f"(d[8]), "+f"(d[9]), "+f"(d[10]), "+f"(d[11]), "+f"(d[12]), "+f"(d[13]), "+f"(d[14]), "+f"(d[15]), "+f"(d[16]), "+f"(d[17]), "+f"(d[18]), "+f"(d[19])
    : "r"(a[0]), "r"(a[1]), "r"(a[2]), "r"(a[3]), "l"(db), "r"(scale_d));
}
__device__ __forceinline__ void wgmma_n256_0(float (&d)[192], uint64_t da, uint64_t db) {
  asm volatile("{\n.reg .pred p;\nsetp.ne.b32 p, 0, 0;\n"
    "wgmma.mma_async.sync.aligned.m64n256k16.f32.bf16.bf16 {%0, %1, %2, %3, %4, %5, %6, %7, %8, %9, %10, %11, %12, %13, %14, %15, %16, %17, %18, %19, %20, %21, %22, %23, %24, %25, %26, %27, %28, %29, %30, %31, %32, %33, %34, %35, %36, %37, %38, %39, %40, %41, %42, %43, %44, %45, %46, %47, %48, %49, %50, %51, %52, %53, %54, %55, %56, %57, %58, %59, %60, %61, %62, %63, %64, %65, %66, %67, %68, %69, %70, %71, %72, %73, %74, %75, %76, %77, %78, %79, %80, %81, %82, %83, %84, %85, %86, %87, %88, %89, %90, %91, %92, %93, %94, %95, %96, %97, %98, %99, %100, %101, %102, %103, %104, %105, %106, %107, %108, %109, %110, %111, %112, %113, %114, %115, %116, %117, %118, %119, %120, %121, %122, %123, %124, %125, %126, %127}, %128, %129, p, 1, 1, 0, 1;\n}\n"
    : "=f"(d[0]), "=f"(d[1]), "=f"(d[2]), "=f"(d[3]), "=f"(d[4]), "=f"(d[5]), "=f"(d[6]), "=f"(d[7]), "=f"(d[8]), "=f"(d[9]), "=f"(d[10]), "=f"(d[11]), "=f"(d[12]), "=f"(d[13]), "=f"(d[14]), "=f"(d[15]), "=f"(d[16]), "=f"(d[17]), "=f"(d[18]), "=f"(d[19]), "=f"(d[20]), "=f"(d[21]), "=f"(d[22]), "=f"(d[23]), "=f"(d[24]), "=f"(d[25]), "=f"(d[26]), "=f"(d[27]), "=f"(d[28]), "=f"(d[29]), "=f"(d[30]), "=f"(d[31]), "=f"(d[32]), "=f"(d[33]), "=f"(d[34]), "=f"(d[35]), "=f"(d[36]), "=f"(d[37]), "=f"(d[38]), "=f"(d[39]), "=f"(d[40]), "=f"(d[41]), "=f"(d[42]), "=f"(d[43]), "=f"(d[44]), "=f"(d[45]), "=f"(d[46]), "=f"(d[47]), "=f"(d[48]), "=f"(d[49]), "=f"(d[50]), "=f"(d[51]), "=f"(d[52]), "=f"(d[53]), "=f"(d[54]), "=f"(d[55]), "=f"(d[56]), "=f"(d[57]), "=f"(d[58]), "=f"(d[59]), "=f"(d[60]), "=f"(d[61]), "=f"(d[62]), "=f"(d[63]), "=f"(d[64]), "=f"(d[65]), "=f"(d[66]), "=f"(d[67]), "=f"(d[68]), "=f"(d[69]), "=f"(d[70]), "=f"(d[71]), "=f"(d[72]), "=f"(d[73]), "=f"(d[74]), "=f"(d[75]), "=f"(d[76]), "=f"(d[77]), "=f"(d[78]), "=f"(d[79]), "=f"(d[80]), "=f"(d[81]), "=f"(d[82]), "=f"(d[83]), "=f"(d[84]), "=f"(d[85]), "=f"(d[86]), "=f"(d[87]), "=f"(d[88]), "=f"(d[89]), "=f"(d[90]), "=f"(d[91]), "=f"(d[92]), "=f"(d[93]), "=f"(d[94]), "=f"(d[95]), "=f"(d[96]), "=f"(d[97]), "=f"(d[98]), "=f"(d[99]), "=f"(d[100]), "=f"(d[101]), "=f"(d[102]), "=f"(d[103]), "=f"(d[104]), "=f"(d[105]), "=f"(d[106]), "=f"(d[107]), "=f"(d[108]), "=f"(d[109]), "=f"(d[110]), "=f"(d[111]), "=f"(d[112]), "=f"(d[113]), "=f"(d[114]), "=f"(d[115]), "=f"(d[116]), "=f"(d[117]), "=f"(d[118]), "=f"(d[119]), "=f"(d[120]), "=f"(d[121]), "=f"(d[122]), "=f"(d[123]), "=f"(d[124]), "=f"(d[125]), "=f"(d[126]), "=f"(d[127])
    : "l"(da), "l"(db));
}
__device__ __forceinline__ void wgmma_n128_0(float (&d)[192], uint64_t da, uint64_t db) {
  asm volatile("{\n.reg .pred p;\nsetp.ne.b32 p, 0, 0;\n"
    "wgmma.mma_async.sync.aligned.m64n128k16.f32.bf16.bf16 {%0, %1, %2, %3, %4, %5, %6, %7, %8, %9, %10, %11, %12, %13, %14, %15, %16, %17, %18, %19, %20, %21, %22, %23, %24, %25, %26, %27, %28, %29, %30, %31, %32, %33, %34, %35, %36, %37, %38, %39, %40, %41, %42, %43, %44, %45, %46, %47, %48, %49, %50, %51, %52, %53, %54, %55, %56, %57, %58, %59, %60, %61, %62, %63}, %64, %65, p, 1, 1, 0, 1;\n}\n"
    : "=f"(d[128]), "=f"(d[129]), "=f"(d[130]), "=f"(d[131]), "=f"(d[132]), "=f"(d[133]), "=f"(d[134]), "=f"(d[135]), "=f"(d[136]), "=f"(d[137]), "=f"(d[138]), "=f"(d[139]), "=f"(d[140]), "=f"(d[141]), "=f"(d[142]), "=f"(d[143]), "=f"(d[144]), "=f"(d[145]), "=f"(d[146]), "=f"(d[147]), "=f"(d[148]), "=f"(d[149]), "=f"(d[150]), "=f"(d[151]), "=f"(d[152]), "=f"(d[153]), "=f"(d[154]), "=f"(d[155]), "=f"(d[156]), "=f"(d[157]), "=f"(d[158]), "=f"(d[159]), "=f"(d[160]), "=f"(d[161]), "=f"(d[162]), "=f"(d[163]), "=f"(d[164]), "=f"(d[165]), "=f"(d[166]), "=f"(d[167]), "=f"(d[168]), "=f"(d[169]), "=f"(d[170]), "=f"(d[171]), "=f"(d[172]), "=f"(d[173]), "=f"(d[174]), "=f"(d[175]), "=f"(d[176]), "=f"(d[177]), "=f"(d[178]), "=f"(d[179]), "=f"(d[180]), "=f"(d[181]), "=f"(d[182]), "=f"(d[183]), "=f"(d[184]), "=f"(d[185]), "=f"(d[186]), "=f"(d[187]), "=f"(d[188]), "=f"(d[189]), "=f"(d[190]), "=f"(d[191])
    : "l"(da), "l"(db));
}
__device__ __forceinline__ void wgmma_n128_rs(float (&d)[192], const uint32_t (&a)[4], uint64_t db, int scale_d) {
  asm volatile("{\n.reg .pred p;\nsetp.ne.b32 p, %69, 0;\n"
    "wgmma.mma_async.sync.aligned.m64n128k16.f32.bf16.bf16 {%0, %1, %2, %3, %4, %5, %6, %7, %8, %9, %10, %11, %12, %13, %14, %15, %16, %17, %18, %19, %20, %21, %22, %23, %24, %25, %26, %27, %28, %29, %30, %31, %32, %33, %34, %35, %36, %37, %38, %39, %40, %41, %42, %43, %44, %45, %46, %47, %48, %49, %50, %51, %52, %53, %54, %55, %56, %57, %58, %59, %60, %61, %62, %63}, {%64, %65, %66, %67}, %68, p, 1, 1, 1;\n}\n"
    : "+f"(d[128]), "+f"(d[129]), "+f"(d[130]), "+f"(d[131]), "+f"(d[132]), "+f"(d[133]), "+f"(d[134]), "+f"(d[135]), "+f"(d[136]), "+f"(d[137]), "+f"(d[138]), "+f"(d[139]), "+f"(d[140]), "+f"(d[141]), "+f"(d[142]), "+f"(d[143]), "+f"(d[144]), "+f"(d[145]), "+f"(d[146]), "+f"(d[147]), "+f"(d[148]), "+f"(d[149]), "+f"(d[150]), "+f"(d[151]), "+f"(d[152]), "+f"(d[153]), "+f"(d[154]), "+f"(d[155]), "+f"(d[156]), "+f"(d[157]), "+f"(d[158]), "+f"(d[159]), "+f"(d[160]), "+f"(d[161]), "+f"(d[162]), "+f"(d[163]), "+f"(d[164]), "+f"(d[165]), "+f"(d[166]), "+f"(d[167]), "+f"(d[168]), "+f"(d[169]), "+f"(d[170]), "+f"(d[171]), "+f"(d[172]), "+f"(d[173]), "+f"(d[174]), "+f"(d[175]), "+f"(d[176]), "+f"(d[177]), "+f"(d[178]), "+f"(d[179]), "+f"(d[180]), "+f"(d[181]), "+f"(d[182]), "+f"(d[183]), "+f"(d[184]), "+f"(d[185]), "+f"(d[186]), "+f"(d[187]), "+f"(d[188]), "+f"(d[189]), "+f"(d[190]), "+f"(d[191])
    : "r"(a[0]), "r"(a[1]), "r"(a[2]), "r"(a[3]), "l"(db), "r"(scale_d));
}
__device__ __forceinline__ void wgmma_n32_0(float (&d)[16], uint64_t da, uint64_t db) {
  asm volatile("{\n.reg .pred p;\nsetp.ne.b32 p, 0, 0;\n"
    "wgmma.mma_async.sync.aligned.m64n32k16.f32.bf16.bf16 {%0, %1, %2, %3, %4, %5, %6, %7, %8, %9, %10, %11, %12, %13, %14, %15}, %16, %17, p, 1, 1, 0, 1;\n}\n"
    : "=f"(d[0]), "=f"(d[1]), "=f"(d[2]), "=f"(d[3]), "=f"(d[4]), "=f"(d[5]), "=f"(d[6]), "=f"(d[7]), "=f"(d[8]), "=f"(d[9]), "=f"(d[10]), "=f"(d[11]), "=f"(d[12]), "=f"(d[13]), "=f"(d[14]), "=f"(d[15])
    : "l"(da), "l"(db));
}
__device__ __forceinline__ void wgmma_n32(float (&d)[16], uint64_t da, uint64_t db, int scale_d) {
  asm volatile("{\n.reg .pred p;\nsetp.ne.b32 p, %18, 0;\n"
    "wgmma.mma_async.sync.aligned.m64n32k16.f32.bf16.bf16 {%0, %1, %2, %3, %4, %5, %6, %7, %8, %9, %10, %11, %12, %13, %14, %15}, %16, %17, p, 1, 1, 0, 1;\n}\n"
    : "+f"(d[0]), "+f"(d[1]), "+f"(d[2]), "+f"(d[3]), "+f"(d[4]), "+f"(d[5]), "+f"(d[6]), "+f"(d[7]), "+f"(d[8]), "+f"(d[9]), "+f"(d[10]), "+f"(d[11]), "+f"(d[12]), "+f"(d[13]), "+f"(d[14]), "+f"(d[15])
    : "l"(da), "l"(db), "r"(scale_d));
}
__device__ __forceinline__ void wgmma_n8_t(float (&d)[4], uint64_t da, uint64_t db, int scale_d) {
  asm volatile("{\n.reg .pred p;\nsetp.ne.b32 p, %6, 0;\n"
    "wgmma.mma_async.sync.aligned.m64n8k16.f32.bf16.bf16 {%0, %1, %2, %3}, %4, %5, p, 1, 1, 1, 0;\n}\n"
    : "+f"(d[0]), "+f"(d[1]), "+f"(d[2]), "+f"(d[3])
    : "l"(da), "l"(db), "r"(scale_d));
}
__device__ __forceinline__ void wgmma_n64_lo(float (&d)[192], uint64_t da, uint64_t db, int scale_d) {
  asm volatile("{\n.reg .pred p;\nsetp.ne.b32 p, %34, 0;\n"
    "wgmma.mma_async.sync.aligned.m64n64k16.f32.bf16.bf16 {%0, %1, %2, %3, %4, %5, %6, %7, %8, %9, %10, %11, %12, %13, %14, %15, %16, %17, %18, %19, %20, %21, %22, %23, %24, %25, %26, %27, %28, %29, %30, %31}, %32, %33, p, 1, 1, 0, 1;\n}\n"
    : "+f"(d[128]), "+f"(d[129]), "+f"(d[130]), "+f"(d[131]), "+f"(d[132]), "+f"(d[133]), "+f"(d[134]), "+f"(d[135]), "+f"(d[136]), "+f"(d[137]), "+f"(d[138]), "+f"(d[139]), "+f"(d[140]), "+f"(d[141]), "+f"(d[142]), "+f"(d[143]), "+f"(d[144]), "+f"(d[145]), "+f"(d[146]), "+f"(d[147]), "+f"(d[148]), "+f"(d[149]), "+f"(d[150]), "+f"(d[151]), "+f"(d[152]), "+f"(d[153]), "+f"(d[154]), "+f"(d[155]), "+f"(d[156]), "+f"(d[157]), "+f"(d[158]), "+f"(d[159])
    : "l"(da), "l"(db), "r"(scale_d));
}
__device__ __forceinline__ void wgmma_n64_hi(float (&d)[192], uint64_t da, uint64_t db, int scale_d) {
  asm volatile("{\n.reg .pred p;\nsetp.ne.b32 p, %34, 0;\n"
    "wgmma.mma_async.sync.aligned.m64n64k16.f32.bf16.bf16 {%0, %1, %2, %3, %4, %5, %6, %7, %8, %9, %10, %11, %12, %13, %14, %15, %16, %17, %18, %19, %20, %21, %22, %23, %24, %25, %26, %27, %28, %29, %30, %31}, %32, %33, p, 1, 1, 0, 1;\n}\n"
    : "+f"(d[160]), "+f"(d[161]), "+f"(d[162]), "+f"(d[163]), "+f"(d[164]), "+f"(d[165]), "+f"(d[166]), "+f"(d[167]), "+f"(d[168]), "+f"(d[169]), "+f"(d[170]), "+f"(d[171]), "+f"(d[172]), "+f"(d[173]), "+f"(d[174]), "+f"(d[175]), "+f"(d[176]), "+f"(d[177]), "+f"(d[178]), "+f"(d[179]), "+f"(d[180]), "+f"(d[181]), "+f"(d[182]), "+f"(d[183]), "+f"(d[184]), "+f"(d[185]), "+f"(d[186]), "+f"(d[187]), "+f"(d[188]), "+f"(d[189]), "+f"(d[190]), "+f"(d[191])
    : "l"(da), "l"(db), "r"(scale_d));
}
__device__ __forceinline__ void wgmma_n128_rs0(float (&d)[192], const uint32_t (&a)[4], uint64_t db) {
  asm volatile("{\n.reg .pred p;\nsetp.ne.b32 p, 0, 0;\n"
    "wgmma.mma_async.sync.aligned.m64n128k16.f32.bf16.bf16 {%0, %1, %2, %3, %4, %5, %6, %7, %8, %9, %10, %11, %12, %13, %14, %15, %16, %17, %18, %19, %20, %21, %22, %23, %24, %25, %26, %27, %28, %29, %30, %31, %32, %33, %34, %35, %36, %37, %38, %39, %40, %41, %42, %43, %44, %45, %46, %47, %48, %49, %50, %51, %52, %53, %54, %55, %56, %57, %58, %59, %60, %61, %62, %63}, {%64, %65, %66, %67}, %68, p, 1, 1, 1;\n}\n"
    : "=f"(d[128]), "=f"(d[129]), "=f"(d[130]), "=f"(d[131]), "=f"(d[132]), "=f"(d[133]), "=f"(d[134]), "=f"(d[135]), "=f"(d[136]), "=f"(d[137]), "=f"(d[138]), "=f"(d[139]), "=f"(d[140]), "=f"(d[141]), "=f"(d[142]), "=f"(d[143]), "=f"(d[144]), "=f"(d[145]), "=f"(d[146]), "=f"(d[147]), "=f"(d[148]), "=f"(d[149]), "=f"(d[150]), "=f"(d[151]), "=f"(d[152]), "=f"(d[153]), "=f"(d[154]), "=f"(d[155]), "=f"(d[156]), "=f"(d[157]), "=f"(d[158]), "=f"(d[159]), "=f"(d[160]), "=f"(d[161]), "=f"(d[162]), "=f"(d[163]), "=f"(d[164]), "=f"(d[165]), "=f"(d[166]), "=f"(d[167]), "=f"(d[168]), "=f"(d[169]), "=f"(d[170]), "=f"(d[171]), "=f"(d[172]), "=f"(d[173]), "=f"(d[174]), "=f"(d[175]), "=f"(d[176]), "=f"(d[177]), "=f"(d[178]), "=f"(d[179]), "=f"(d[180]), "=f"(d[181]), "=f"(d[182]), "=f"(d[183]), "=f"(d[184]), "=f"(d[185]), "=f"(d[186]), "=f"(d[187]), "=f"(d[188]), "=f"(d[189]), "=f"(d[190]), "=f"(d[191])
    : "r"(a[0]), "r"(a[1]), "r"(a[2]), "r"(a[3]), "l"(db));
}
__device__ __forceinline__ void wgmma_n256_rs(float (&d)[192], const uint32_t (&a)[4], uint64_t db, int scale_d) {
  asm volatile("{\n.reg .pred p;\nsetp.ne.b32 p, %133, 0;\n"
    "wgmma.mma_async.sync.aligned.m64n256k16.f32.bf16.bf16 {%0, %1, %2, %3, %4, %5, %6, %7, %8, %9, %10, %11, %12, %13, %14, %15, %16, %17, %18, %19, %20, %21, %22, %23, %24, %25, %26, %27, %28, %29, %30, %31, %32, %33, %34, %35, %36, %37, %38, %39, %40, %41, %42, %43, %44, %45, %46, %47, %48, %49, %50, %51, %52, %53, %54, %55, %56, %57, %58, %59, %60, %61, %62, %63, %64, %65, %66, %67, %68, %69, %70, %71, %72, %73, %74, %75, %76, %77, %78, %79, %80, %81, %82, %83, %84, %85, %86, %87, %88, %89, %90, %91, %92, %93, %94, %95, %96, %97, %98, %99, %100, %101, %102, %103, %104, %105, %106, %107, %108, %109, %110, %111, %112, %113, %114, %115, %116, %117, %118, %119, %120, %121, %122, %123, %124, %125, %126, %127}, {%128, %129, %130, %131}, %132, p, 1, 1, 1;\n}\n"
    : "+f"(d[0]), "+f"(d[1]), "+f"(d[2]), "+f"(d[3]), "+f"(d[4]), "+f"(d[5]), "+f"(d[6]), "+f"(d[7]), "+f"(d[8]), "+f"(d[9]), "+f"(d[10]), "+f"(d[11]), "+f"(d[12]), "+f"(d[13]), "+f"(d[14]), "+f"(d[15]), "+f"(d[16]), "+f"(d[17]), "+f"(d[18]), "+f"(d[19]), "+f"(d[20]), "+f"(d[21]), "+f"(d[22]), "+f"(d[23]), "+f"(d[24]), "+f"(d[25]), "+f"(d[26]), "+f"(d[27]), "+f"(d[28]), "+f"(d[29]), "+f"(d[30]), "+f"(d[31]), "+f"(d[32]), "+f"(d[33]), "+f"(d[34]), "+f"(d[35]), "+f"(d[36]), "+f"(d[37]), "+f"(d[38]), "+f"(d[39]), "+f"(d[40]), "+f"(d[41]), "+f"(d[42]), "+f"(d[43]), "+f"(d[44]), "+f"(d[45]), "+f"(d[46]), "+f"(d[47]), "+f"(d[48]), "+f"(d[49]), "+f"(d[50]), "+f"(d[51]), "+f"(d[52]), "+f"(d[53]), "+f"(d[54]), "+f"(d[55]), "+f"(d[56]), "+f"(d[57]), "+f"(d[58]), "+f"(d[59]), "+f"(d[60]), "+f"(d[61]), "+f"(d[62]), "+f"(d[63]), "+f"(d[64]), "+f"(d[65]), "+f"(d[66]), "+f"(d[67]), "+f"(d[68]), "+f"(d[69]), "+f"(d[70]), "+f"(d[71]), "+f"(d[72]), "+f"(d[73]), "+f"(d[74]), "+f"(d[75]), "+f"(d[76]), "+f"(d[77]), "+f"(d[78]), "+f"(d[79]), "+f"(d[80]), "+f"(d[81]), "+f"(d[82]), "+f"(d[83]), "+f"(d[84]), "+f"(d[85]), "+f"(d[86]), "+f"(d[87]), "+f"(d[88]), "+f"(d[89]), "+f"(d[90]), "+f"(d[91]), "+f"(d[92]), "+f"(d[93]), "+f"(d[94]), "+f"(d[95]), "+f"(d[96]), "+f"(d[97]), "+f"(d[98]), "+f"(d[99]), "+f"(d[100]), "+f"(d[101]), "+f"(d[102]), "+f"(d[103]), "+f"(d[104]), "+f"(d[105]), "+f"(d[106]), "+f"(d[107]), "+f"(d[108]), "+f"(d[109]), "+f"(d[110]), "+f"(d[111]), "+f"(d[112]), "+f"(d[113]), "+f"(d[114]), "+f"(d[115]), "+f"(d[116]), "+f"(d[117]), "+f"(d[118]), "+f"(d[119]), "+f"(d[120]), "+f"(d[121]), "+f"(d[122]), "+f"(d[123]), "+f"(d[124]), "+f"(d[125]), "+f"(d[126]), "+f"(d[127])
    : "r"(a[0]), "r"(a[1]), "r"(a[2]), "r"(a[3]), "l"(db), "r"(scale_d));
}
__device__ __forceinline__ void wgmma_n256_rs0(float (&d)[192], const uint32_t (&a)[4], uint64_t db) {
  asm volatile("{\n.reg .pred p;\nsetp.ne.b32 p, 0, 0;\n"
    "wgmma.mma_async.sync.aligned.m64n256k16.f32.bf16.bf16 {%0, %1, %2, %3, %4, %5, %6, %7, %8, %9, %10, %11, %12, %13, %14, %15, %16, %17, %18, %19, %20, %21, %22, %23, %24, %25, %26, %27, %28, %29, %30, %31, %32, %33, %34, %35, %36, %37, %38, %39, %40, %41, %42, %43, %44, %45, %46, %47, %48, %49, %50, %51, %52, %53, %54, %55, %56, %57, %58, %59, %60, %61, %62, %63, %64, %65, %66, %67, %68, %69, %70, %71, %72, %73, %74, %75, %76, %77, %78, %79, %80, %81, %82, %83, %84, %85, %86, %87, %88, %89, %90, %91, %92, %93, %94, %95, %96, %97, %98, %99, %100, %101, %102, %103, %104, %105, %106, %107, %108, %109, %110, %111, %112, %113, %114, %115, %116, %117, %118, %119, %120, %121, %122, %123, %124, %125, %126, %127}, {%128, %129, %130, %131}, %132, p, 1, 1, 1;\n}\n"
    : "=f"(d[0]), "=f"(d[1]), "=f"(d[2]), "=f"(d[3]), "=f"(d[4]), "=f"(d[5]), "=f"(d[6]), "=f"(d[7]), "=f"(d[8]), "=f"(d[9]), "=f"(d[10]), "=f"(d[11]), "=f"(d[12]), "=f"(d[13]), "=f"(d[14]), "=f"(d[15]), "=f"(d[16]), "=f"(d[17]), "=f"(d[18]), "=f"(d[19]), "=f"(d[20]), "=f"(d[21]), "=f"(d[22]), "=f"(d[23]), "=f"(d[24]), "=f"(d[25]), "=f"(d[26]), "=f"(d[27]), "=f"(d[28]), "=f"(d[29]), "=f"(d[30]), "=f"(d[31]), "=f"(d[32]), "=f"(d[33]), "=f"(d[34]), "=f"(d[35]), "=f"(d[36]), "=f"(d[37]), "=f"(d[38]), "=f"(d[39]), "=f"(d[40]), "=f"(d[41]), "=f"(d[42]), "=f"(d[43]), "=f"(d[44]), "=f"(d[45]), "=f"(d[46]), "=f"(d[47]), "=f"(d[48]), "=f"(d[49]), "=f"(d[50]), "=f"(d[51]), "=f"(d[52]), "=f"(d[53]), "=f"(d[54]), "=f"(d[55]), "=f"(d[56]), "=f"(d[57]), "=f"(d[58]), "=f"(d[59]), "=f"(d[60]), "=f"(d[61]), "=f"(d[62]), "=f"(d[63]), "=f"(d[64]), "=f"(d[65]), "=f"(d[66]), "=f"(d[67]), "=f"(d[68]), "=f"(d[69]), "=f"(d[70]), "=f"(d[71]), "=f"(d[72]), "=f"(d[73]), "=f"(d[74]), "=f"(d[75]), "=f"(d[76]), "=f"(d[77]), "=f"(d[78]), "=f"(d[79]), "=f"(d[80]), "=f"(d[81]), "=f"(d[82]), "=f"(d[83]), "=f"(d[84]), "=f"(d[85]), "=f"(d[86]), "=f"(d[87]), "=f"(d[88]), "=f"(d[89]), "=f"(d[90]), "=f"(d[91]), "=f"(d[92]), "=f"(d[93]), "=f"(d[94]), "=f"(d[95]), "=f"(d[96]), "=f"(d[97]), "=f"(d[98]), "=f"(d[99]), "=f"(d[100]), "=f"(d[101]), "=f"(d[102]), "=f"(d[103]), "=f"(d[104]), "=f"(d[105]), "=f"(d[106]), "=f"(d[107]), "=f"(d[108]), "=f"(d[109]), "=f"(d[110]), "=f"(d[111]), "=f"(d[112]), "=f"(d[113]), "=f"(d[114]), "=f"(d[115]), "=f"(d[116]), "=f"(d[117]), "=f"(d[118]), "=f"(d[119]), "=f"(d[120]), "=f"(d[121]), "=f"(d[122]), "=f"(d[123]), "=f"(d[124]), "=f"(d[125]), "=f"(d[126]), "=f"(d[127])
    : "r"(a[0]), "r"(a[1]), "r"(a[2]), "r"(a[3]), "l"(db));
}

constexpr int SLOT = 16384;
constexpr int VB = 4 * SLOT, PH = 0, XS = 6;
constexpr int SM_SD = 13 * SLOT;
constexpr int SM_BAR = SM_SD + 8192;
constexpr int SM_RS = SM_BAR + 1024;
constexpr int SM_AP = SM_RS + 640;
constexpr int SM_BP = SM_AP + 2048;
constexpr int SM_EPOCH = SM_BP + 6144;
constexpr int SM_TOTAL = SM_EPOCH + 16;
constexpr int FM = 0, FT = 16, FW = 30, CM = 46, CT = 62, CW = 76, B_EF = 92, B_STAT = 93, B_KVF = 94, B_HALO = 95,
              B_KVDONE = 96, B_OH0 = 97, B_OH1 = 98, B_XH0 = 99, B_XDONE = 100, B_WFD = 101, B_XT = 102, B_OF0 = 103, B_KVF1 = 104, B_RAW = 106  , B_X0 = 108;
constexpr uint64_t BAR_LG = 0x00043333330004ull;
#define BA(i) (bar + (i) * 8)
#define REL2(i) release2c(SB0 + SM_BAR + (i) * 8)
constexpr int NF = 4, ND = 12, NR = 0, NWOP = 48, NAOP = 37;
constexpr uint64_t TL_A = 0x278627862786ull, TL_B = 0xac39bac39bacull, WO_A = 0x764a2396b4ac39ffull, WO_B = 0xc8b51c780512786bull;
__constant__ uint32_t c_wop[NWOP + 1] = {0xea8009, 0x186b8000, 0x26b8112, 0x18ec011a, 0x6c8224, 0x22ec822b, 0x170330, 0x22970339, 0x18178442, 0x18180554, 0x18188660, 0x18190772, 0x18198884, 0x181a0990, 0x181a8aa2, 0x181b0bb4, 0x181b8cc0, 0xaed90fc, 0xa9791ea, 0x181c0dd2, 0xa9812db, 0x129893c9, 0x181c8ee4, 0x181d0ff0, 0x109d94b3, 0x109f15ac, 0x109f969a, 0x10a0178b, 0x10a09879, 0x10a11963, 0x10a19a5c, 0x10a21b4a, 0x9229e0b, 0x9231f16, 0x1123a028, 0x11242137, 0x1124a242, 0x112e2351, 0x132e2465, 0x132e2570, 0x11272688, 0x1127a797, 0x112828ac, 0x1128a9b1, 0x11292ac5, 0x1129abdb, 0x112a2ce8, 0x112b2dfc, 0};
__constant__ uint32_t c_aop[NAOP + 1] = {0x6d0228, 0x170336, 0x178447, 0x180558, 0x188666, 0x190777, 0x198888, 0x1a0996, 0x1a8aa7, 0x1b0bb8, 0x1b8cc6, 0x1c0dd7, 0x1c8ee8, 0x1d0ff6, 0x1d93c2, 0x1f14b6, 0x1f95a8, 0x201697, 0x209782, 0x211876, 0x219968, 0x221a57, 0x229b42, 0xa32029, 0xa3a133, 0xa4224c, 0xa4a35a, 0xae2464, 0xa6257b, 0xa6a686, 0xa72799, 0xa7a8a3, 0xa829b2, 0xa8aaca, 0xa92bd4, 0xaa2ce6, 0xaaadf7, 0};
__constant__ uint32_t c_map[64] = {4, 5, 6, 7, 0, 16, 32, 48, 64, 80, 96, 112, 1, 17, 33, 49, 65, 81, 97, 113, 2, 18, 34, 50, 66, 82, 98, 114, 3, 19, 35, 51, 67, 83, 99, 115, 20, 36, 52, 68, 84, 100, 116, 21, 37, 53, 69, 85, 101, 117, 22, 38, 54, 70, 86, 102, 118, 23, 39, 55, 71, 87, 103, 119};
enum { MAP_WF = 0, MAP_WA = 2, MAP_WB = 4, MAP_WOA = 6, MAP_WOB = 8, MAP_X0 = 10, MAP_X = 11, MAP_O = 12, MAP_PHI = 13, NMAP = 14 };
struct Maps { CUtensorMap m[NMAP]; };

#define PL 2
#define PROFL(a, b)
#define SUBS 8
#define QORD 1
#define NCH 4
#define CHW 1
#define DRAIN 0
#define SUBS1 12
#define XRAT 9
#define PFW 0
#define XRN 2
#define BT1 1
#define CV0 0
#define ST1 8
#define FASTP 0
#define O1P 2
#define X0AT 1
#define W1DL 400
#define WFDL 0
#define SKA 2
#define SKB 0
#define NLAYERS 4
constexpr float L2E = 1.4426950408889634f;

#define D128(lo) desc64(lo, 0x40000040u)
struct Ctx { uint32_t zero, boff; const bf16* x0; bf16* out; };
#define BLK_CTX() \
  uint32_t bid_; asm volatile("mov.u32 %0, %%ctaid.x;" : "=r"(bid_)); \
  bid_ -= c.boff; \
  const uint32_t gr_ = c_map[bid_ >> 1]; \
  const int cr = bid_ & 1, g = gr_ & 7, rb = (gr_ >> 3) + cr, m0 = rb * 128; \
  const uint32_t sb = SB0 + (cr << 24); \
  const uint32_t bar = sb + SM_BAR; \
  (void)cr; (void)g; (void)rb; (void)m0; (void)bar;
extern __shared__ uint8_t smem_raw[];
constexpr uint32_t SB0 = 1024;

#define PHASE_CTX() \
  BLK_CTX(); \
  int tid_ = threadIdx.x; asm volatile("" : "+r"(tid_)); \
  const int lane = tid_ & 31, cw = (tid_ >> 5) - 4, wg = cw >> 2, wq = cw & 3, gq = lane >> 2, t = lane & 3, wrow0 = cw * 16; \
  const int lrow = (lane & 7) + ((lane >> 3) & 1) * 8, lchk = lane >> 4; \
  const bool elected = (tid_ & 127) == 0; \
  const uint32_t rowo = (wrow0 + lrow) * 128, X = (lchk ^ (lane & 7)) << 4; \
  const uint32_t Y = (wrow0 + (lane & 7)) * 128 + (((lane >> 3) ^ (lane & 7)) << 4); \
  const size_t gfr = (size_t)(m0 + wrow0 + gq) * D_ + g * 128 + 8 * t; \
  (void)bar; (void)wq; (void)gq; (void)lrow; (void)lchk; (void)elected; (void)wrow0; (void)wg; (void)rowo; (void)X; (void)t; (void)Y; (void)gfr;
#define MMA_CTX() \
  const uint32_t wu = __shfl_sync(0xffffffffu, wg, 0); \
  const uint32_t dA0 = ((SB0 >> 4) | (1u << 16)) + wu * 512, dB0 = (SB0 >> 4) | (512u << 16); \
  const uint32_t par = layer & 1;

__device__ __forceinline__ void slab_out_half(uint32_t slot, bf16* dst, int wrow0, int lane) {
  const int r0 = lane >> 3, ch = lane & 7;
  const uint32_t src = slot + (wrow0 + r0) * 128;
  uint4 v[4];
#pragma unroll
  for (int i = 0; i < 4; ++i) v[i] = lds128(src + i * 512 + (((ch ^ (4 * i + r0)) & 7) << 4));
  dst += (size_t)(wrow0 + r0) * D_ + ch * 8;
#pragma unroll
  for (int i = 0; i < 4; ++i) *reinterpret_cast<uint4*>(dst + (size_t)i * 4 * D_) = v[i];
}

__device__ __forceinline__ void consumer(const Ctx& c) {
  float acc[192];
  uint32_t xf[4][4];
  uint32_t xp[8][4];
  {
    PHASE_CTX();
    const unsigned int epoch = ld_relaxed(&g_epoch);
    PROFT(tid_ == 128, 0);
    const uint32_t wu = __shfl_sync(0xffffffffu, wg, 0);
    if (tid_ < 128 + 8) sts128(sb + SM_AP + lane * 16, make_uint4(0x3F803F80u, 0x3F803F80u, 0x3F803F80u, 0x3F803F80u));
#pragma unroll 1
    for (int it = 0; it < 2; ++it) {
      float p[4][16];
      mbar_wait(BA(B_RAW + it), 0);
      PROFT(tid_ == 128, it ? 15 : 2);
      const uint32_t da = ((SB0 >> 4) | (1u << 16)) + (wu ? 9 + it : 2 * it) * 1024, db = (SB0 + SM_SD) >> 4;
      wgmma_fence();
#pragma unroll
      for (int h = 0; h < 4; ++h) wgmma_n32_0(p[h], D128(da + (h >> 1) * 512 + (h & 1) * 4), desc64(db + h * 128, 0x80000020u));
#pragma unroll
      for (int h = 0; h < 4; ++h) wgmma_n32(p[h], D128(da + (h >> 1) * 512 + (h & 1) * 4 + 2), desc64(db + h * 128 + 64, 0x80000020u), 1);
      wgmma_commit();
      wgmma_wait<0>();
#pragma unroll
      for (int i = 0; i < 64; ++i) asm volatile("" : "+f"(p[i >> 4][i & 15]) :: "memory");
      const uint32_t base = sb + (wg ? 9 + it : 2 * it) * SLOT + (wq * 16 + gq) * 128;
      uint32_t w[4][4][2];
#pragma unroll
      for (int i = 0; i < 32; ++i) w[i >> 3][(i >> 1) & 3][i & 1] = pack_bf16(p[i >> 3][2 * (i & 7)], p[i >> 3][2 * (i & 7) + 1]);
      if (wu) {
#pragma unroll
        for (int i = 0; i < 8; ++i)
          sts128(base + (i >> 2) * 8192 + (i & 1) * 1024 + (((((i >> 1) & 1) * 4 + t) ^ gq) << 4), make_uint4(w[i >> 1][0][i & 1], w[i >> 1][1][i & 1], w[i >> 1][2][i & 1], w[i >> 1][3][i & 1]));
      } else {
#pragma unroll
        for (int i = 0; i < 16; ++i)
          sts64(base + (i >> 3) * 8192 + (i & 1) * 1024 + ((((t & 1) * 4 + ((i >> 1) & 3)) ^ gq) << 4) + (t >> 1) * 8, w[(i >> 3) * 2][(i >> 1) & 3][i & 1], w[(i >> 3) * 2 + 1][(i >> 1) & 3][i & 1]);
      }
      fence_async_smem();
      __syncwarp();
      if (it == cr && lane == 0) mbar_arrive(BA(B_WFD));
    }
    if (tid_ == 128) sts_f(sb + SM_EPOCH, __uint_as_float(epoch & 1));
#pragma unroll
    for (int i = 0; i < 32; ++i) xp[i >> 2][i & 3] = 0u;
    nbar<1, 256>();
    PROFT(tid_ == 128, 13);
    mbar_wait(BA(FM + cr), 0);
    float cs[3][4];
    wgmma_fence();
#pragma unroll
    for (int ks = 0; ks < 4; ++ks)
#pragma unroll
      for (int i = 0; i < 3; ++i) {
        const uint32_t bx = (i == 0 ? 2 * cr * 1024 : i == 1 ? (2 * cr + 1) * 1024 : (9 + cr) * 1024) + wu * 512;
        wgmma_n8_t(cs[i], D128(((SB0 >> 4) | (512u << 16)) + bx + ks * 128), desc64((SB0 + SM_AP) >> 4, 0), ks != 0);
      }
    wgmma_commit();
    mbar_wait(BA(FM), 0);
#pragma unroll
    for (int k = 0; k < 4; ++k) ldsm_x4(xf[k][0], xf[k][1], xf[k][2], xf[k][3], sb + XS * SLOT + rowo + (X ^ (k << 5)));
    wgmma_wait<0>();
#pragma unroll
    for (int i = 0; i < 12; ++i) asm volatile("" : "+f"(cs[i >> 2][i & 3]) :: "memory");
    if (t < 2) {
#pragma unroll
      for (int i = 0; i < 3; ++i) red_add1(g_cs + (epoch & 1) * 6144 + g * 384 + i * 128 + wg * 64 + wq * 16 + gq + t * 8, t ? cs[i][2] : cs[i][0]);
    }
    PROFT(tid_ == 128, 14);
  }
#pragma unroll 1
  for (int layer = 0;; ++layer) {
    {
      PHASE_CTX();
      MMA_CTX();
      {
        const uint32_t ep = __float_as_uint(lds_f(sb + SM_EPOCH));
        mbar_wait(BA(FM), par);
        wgmma_fence();
        wgmma_n256_rs0(acc, xf[0], D128(dB0));
#pragma unroll
        for (int k = 1; k < 4; ++k) wgmma_n256_rs(acc, xf[k], D128(dB0 + k * 128), 1);
        wgmma_commit();
        if (layer == 0) {
          mbar_wait(BA(B_X0), 0);
#pragma unroll
          for (int i = 0; i < 8; ++i) ldsm_x4(xp[i][0], xp[i][1], xp[i][2], xp[i][3], sb + (11 + (i >> 2)) * SLOT + (Y ^ ((i & 2) << 5)) + (i & 1) * 1024);
          if (lane == ((xp[0][0] ^ xp[1][0] ^ xp[2][0] ^ xp[3][0] ^ xp[7][0]) & c.zero)) REL2(B_XT);
        } else {
#pragma unroll
          for (int i = 0; i < 8; ++i) stsm_x4(sb + (XS + (i >> 2)) * SLOT + (Y ^ ((i & 2) << 5)) + (i & 1) * 1024, xp[i][0], xp[i][1], xp[i][2], xp[i][3]);
        }
        float s0 = 0.f, s1 = 0.f, q0 = 0.f, q1 = 0.f;
        auto stats = [&](int j0, int j1) {
#pragma unroll
          for (int j = j0; j < j1; ++j) {
            const uint32_t u0 = xp[(j >> 2) * 2][j & 3], u1 = xp[(j >> 2) * 2 + 1][j & 3];
            s0 += bf_lo(u0) + bf_hi(u0); s1 += bf_lo(u1) + bf_hi(u1);
            q0 = fmaf(bf_lo(u0), bf_lo(u0), fmaf(bf_hi(u0), bf_hi(u0), q0)); q1 = fmaf(bf_lo(u1), bf_lo(u1), fmaf(bf_hi(u1), bf_hi(u1), q1));
          }
        };
        stats(0, ST1);
        fence_async_smem();
        nbar_dyn(3 + wu + (__float_as_uint(s0 + s1 + q0 + q1) & c.zero), 128);
        mbar_wait(BA(FM + 1), par);
        wgmma_fence();
#pragma unroll
        for (int k = 0; k < 4; ++k) wgmma_n256(acc, D128(dA0 + (XS + 1) * 1024 + k * 2), D128(dB0 + 2048 + k * 128), 1);
        wgmma_commit();
        wgmma_wait<1>();
#pragma unroll
        for (int i = 4; i < 8; ++i) stg128_p(layer, g_x + gfr + (i & 1) * 8 * D_ + (i >> 1) * 32, xp[i][0], xp[i][1], xp[i][2], xp[i][3]);
        {
          uint32_t zc; asm volatile("mov.u32 %0, %%clock;" : "=r"(zc) :: "memory");
          q0 += __uint_as_float(zc & c.zero); q1 += __uint_as_float(zc & c.zero); s0 += __uint_as_float(zc & c.zero); s1 += __uint_as_float(zc & c.zero);
        }
        stats(ST1, 16);
        wgmma_fence();
        wgmma_n128_0(acc, D128(dA0 + XS * 1024), D128(dB0 + 9 * 1024));
#pragma unroll
        for (int k = 1; k < 4; ++k) wgmma_n128(acc, D128(dA0 + XS * 1024 + k * 2), D128(dB0 + 9 * 1024 + k * 128), 1);
        wgmma_commit();
        const bool od = t & 1;
        float sa = od ? s1 : s0, qa = od ? q1 : q0;
        sa += __shfl_xor_sync(0xffffffffu, od ? s0 : s1, 1);
        qa += __shfl_xor_sync(0xffffffffu, od ? q0 : q1, 1);
        wgmma_fence();
#pragma unroll
        for (int k = 0; k < 4; ++k) wgmma_n128(acc, D128(dA0 + (XS + 1) * 1024 + k * 2), D128(dB0 + 10 * 1024 + k * 128), 1);
        wgmma_commit();
        sa += __shfl_xor_sync(0xffffffffu, sa, 2);
        qa += __shfl_xor_sync(0xffffffffu, qa, 2);
        red_add2_p(t < 2, reinterpret_cast<float*>(g_stats + (ep * 4 + layer) * S_ + m0 + wrow0 + gq + t * 8), sa, qa);
        __syncwarp();
        if (lane == 0) mbar_arrive(BA(B_XDONE));
        wgmma_wait<1>();
        if (elected) REL2(CM);
      }
      uint32_t s = 2;
#pragma unroll 1
      for (int i = 2; i < NF; ++i) {
        PROFL(tid_ == 128 && layer == PL + 1, 244 + 2 * i);
        mbar_wait(BA(FM + i), par);
        PROFL(tid_ == 128 && layer == PL + 1, 245 + 2 * i);
        const uint32_t da = dA0 + (XS + s) * 1024, dk = dB0 + s * 2048, dq = dB0 + (9 + s) * 1024;
        wgmma_fence();
#pragma unroll
        for (int k = 0; k < 4; ++k) wgmma_n128(acc, D128(da + k * 2), D128(dq + k * 128), 1);
        wgmma_commit();
        wgmma_wait<1>();
        if (elected) REL2(CM + i - 1);
        wgmma_fence();
#pragma unroll
        for (int k = 0; k < 4; ++k) wgmma_n256(acc, D128(da + k * 2), D128(dk + k * 128), 1);
        wgmma_commit();
        if (++s == 3) s = 0;
      }
#pragma unroll 1
      for (int i = NF; i < 15; ++i) {
        mbar_wait(BA(FM + i), par);
        const uint32_t da = dA0 + (XS + s) * 1024, dk = dB0 + s * 2048;
        wgmma_fence();
#pragma unroll
        for (int k = 0; k < 4; ++k) wgmma_n256(acc, D128(da + k * 2), D128(dk + k * 128), 1);
        wgmma_commit();
        wgmma_wait<1>();
        if (elected) REL2(CM + i - 1);
        if (++s == 3) s = 0;
      }
      {
        const uint64_t dap = desc64(((SB0 + SM_AP) >> 4) + wu * 64, 8), dbp = make_desc_ns(SB0 + SM_BP, 0, 128);
        mbar_wait(BA(B_STAT), par);
        mbar_wait(BA(FM + 15), par);
        PROFT(tid_ == 128, layer * 16 + 9);
        wgmma_fence();
        wgmma_n256_k(acc, dap, dbp, 1);
#pragma unroll
        for (int k = 0; k < 4; ++k) wgmma_n256(acc, D128(dA0 + XS * 1024 + k * 2), D128(dB0 + k * 128), 1);
        wgmma_commit();
        wgmma_wait<1>();
        if (elected) REL2(CM + 14);
        mbar_wait(BA(FT), par);
        wgmma_fence();
        wgmma_n128_k(acc, dap, dbp + 256, 1);
#pragma unroll
        for (int k = 0; k < 4; ++k) wgmma_n128(acc, D128(dA0 + (uint32_t)(TL_A & 15) * 1024 + k * 2), D128(dB0 + (uint32_t)(TL_B & 15) * 1024 + k * 128), 1);
        wgmma_commit();
        wgmma_wait<1>();
        if (elected) REL2(CM + 15);
#pragma unroll
        for (int i = 0; i < 128; ++i) asm volatile("" : "+f"(acc[i]) :: "memory");
      }
    }
    uint32_t of[8][4], o1[4][4];
    {
      PHASE_CTX();
      MMA_CTX();
      PROFT(tid_ == 128, layer * 16 + 1);
      PROFT(lane == 0 && layer == PL, 192 + cw);
      PROFT(tid_ == 128 && layer == PL, 160);
      uint64_t ta = (TL_A >> 4), tw = TL_B >> 4;
      uint32_t da, db, dz = dA0;
      auto sub = [&](int n) {
        const int j = n >> 2, k = n & 3;
        if (k == 0) {
          dz += c.zero;
          da = dz + ((uint32_t)ta & 15) * 1024; db = dB0 + ((uint32_t)tw & 15) * 1024;
          ta >>= 4; tw >>= 4;
          mbar_wait(BA(FT + j), par);
          wgmma_fence();
        }
        wgmma_n128(acc, D128(da + k * 2), D128(db + k * 128), 1);
        if (k == 3) {
          wgmma_commit();
          wgmma_wait<1>();
          if (elected) REL2(CT + j - 1);
        }
      };
      auto run = [&](int j0, int j1) {
#pragma unroll 1
        for (int j = j0; j < j1; ++j) {
          mbar_wait(BA(FT + j), par);
          da = dA0 + ((uint32_t)ta & 15) * 1024; db = dB0 + ((uint32_t)tw & 15) * 1024;
          ta >>= 4; tw >>= 4;
          wgmma_fence();
#pragma unroll
          for (int k = 0; k < 4; ++k) wgmma_n128(acc, D128(da + k * 2), D128(db + k * 128), 1);
          wgmma_commit();
          wgmma_wait<1>();
          if (elected) REL2(CT + j - 1);
        }
        ta = TL_A >> (4 * j1); tw = TL_B >> (4 * j1);
      };
      auto rest = [&](int j0, int sk, int nr) {
        if (sk) {
          run(j0, ND - sk);
          if (wu == 0) nbar<6, 256>();
          j0 = ND - sk;
        }
        run(j0, ND - nr);
        if (sk && wu) asm volatile("bar.arrive 6, 256;" ::: "memory");
        if (nr) mbar_wait(BA(FT + ND - nr), par);
#pragma unroll
        for (int j = ND - nr; j < ND; ++j) {
          if (j > ND - nr) mbar_wait(BA(FT + j), par);
          wgmma_fence();
#pragma unroll
          for (int k = 0; k < 4; ++k)
            wgmma_n64_lo(acc, D128(dA0 + (uint32_t)((TL_A >> (4 * j)) & 15) * 1024 + k * 2), D128(dB0 + (uint32_t)((TL_B >> (4 * j)) & 15) * 1024 + k * 128), 1);
          wgmma_commit();
          if (!DRAIN && j == ND - nr) {
            wgmma_wait<1>();
            if (elected) REL2(CT + j - 1);
          }
        }
        wgmma_wait<0>();
        if (!nr && elected) REL2(CT + ND - 1);
#pragma unroll
        for (int i = 128; i < 192; ++i) asm volatile("" : "+f"(acc[i]) :: "memory");
#pragma unroll
        for (int i = 160; i < 192; ++i) if (nr) acc[i] += __uint_as_float(c.zero);
      };
      auto rest_hi = [&]() {
        if (!NR) return;
        dz += c.zero;
        wgmma_fence();
#pragma unroll
        for (int j = ND - NR; j < ND; ++j)
#pragma unroll
          for (int k = 0; k < 4; ++k)
            wgmma_n64_hi(acc, D128(dz + (uint32_t)((TL_A >> (4 * j)) & 15) * 1024 + k * 2), D128(dB0 + (uint32_t)((TL_B >> (4 * j)) & 15) * 1024 + 512 + k * 128), 1);
        wgmma_commit();
      };
      auto rest_end = [&]() {
        if (!NR) return;
        wgmma_wait<0>();
        if (elected) {
#pragma unroll
          for (int j = ND - NR; j < ND; ++j) REL2(CT + j);
        }
#pragma unroll
        for (int i = 160; i < 192; ++i) asm volatile("" : "+f"(acc[i]) :: "memory");
      };
      const float rs0 = lds_f(sb + SM_RS + (16 + wrow0 + gq) * 4), rs1 = lds_f(sb + SM_RS + (24 + wrow0 + gq) * 4);
#define EPOCH() __float_as_uint(lds_f(sb + SM_EPOCH))
      mbar_wait(BA(CM + 14), par);
      if (par) {
        uint32_t kk[8][4], kp[8][4], vf[2][2][4][4];
        int sn = 4;
#pragma unroll
        for (int i = 0; i < 4 * BT1; ++i) sub(sn++);
        {
          uint32_t vv[8][4];
#pragma unroll
          for (int jp = 0; jp < 8; ++jp) {
            kk[jp][0] = pack_bf16(acc[8 * jp], acc[8 * jp + 1]); kk[jp][1] = pack_bf16(acc[8 * jp + 4], acc[8 * jp + 5]);
            kk[jp][2] = pack_bf16(acc[8 * jp + 2], acc[8 * jp + 3]); kk[jp][3] = pack_bf16(acc[8 * jp + 6], acc[8 * jp + 7]);
#pragma unroll
            for (int i = 0; i < 4; ++i) vv[jp][i] = pack_bf16(acc[64 + 8 * jp + 2 * i], acc[65 + 8 * jp + 2 * i]);
          }
          if (cw == 7) {
            uint32_t* const hbuf = g_halo + (size_t)(((layer >> 1) * 17 + rb + 1) * 8 + g) * 2048;
#pragma unroll
            for (int jp = 0; jp < 8; ++jp) stg128(hbuf + jp * 128 + lane * 4, kk[jp][0], kk[jp][1], kk[jp][2], kk[jp][3]);
#pragma unroll
            for (int i = 0; i < 32; ++i) hbuf[1024 + (i >> 4) * 512 + (gq + (i & 1) * 8) * 32 + ((((i >> 1) & 7) ^ gq) << 2) + t] = vv[i >> 2][i & 3];
            __syncwarp();
            if (lane == 0) mbar_arrive(BA(B_OF0));
          }
#pragma unroll
          for (int jp = 0; jp < 8; ++jp) {
            sub(sn++);
            stsm_x4(sb + VB + (jp >> 2) * SLOT + rowo + (X ^ ((jp & 3) << 5)), vv[jp][0], vv[jp][1], vv[jp][2], vv[jp][3]);
          }
        }
        PROFT(tid_ == 128, layer * 16 + 2);
        const int e = gq & 1;
        float f0[4], f1[4], b0[4], b1[4], rj[4];
#pragma unroll
        for (int nt = 0; nt < 4; ++nt) {
          const int kx = nt * 8 + 2 * t + e;
          const bool okk = (m0 + wrow0 + kx) >= 16;
          const int d0 = kx - gq, d1 = d0 - 8;
          rj[nt] = lds_f(sb + SM_RS + (wrow0 + kx) * 4);
          const bool m0_ = okk && d0 >= 2 && d0 <= 16, m1_ = okk && d1 >= 2 && d1 <= 16;
          f0[nt] = m0_ ? rj[nt] * rs0 * (0.17677669529663687f * L2E) : 0.f;
          f1[nt] = m1_ ? rj[nt] * rs1 * (0.17677669529663687f * L2E) : 0.f;
          b0[nt] = m0_ ? 0.f : -1e30f; b1[nt] = m1_ ? 0.f : -1e30f;
        }
        mbar_wait(BA(CM + 15), par);
#pragma unroll
        for (int jp = 0; jp < 8; ++jp) {
          sub(sn++);
          sts128(sb + PH + cw * 4096 + jp * 512 + lane * 16, make_uint4(kk[jp][0], kk[jp][1], kk[jp][2], kk[jp][3]));
        }
#pragma unroll
        for (int i = 0; i < 4; ++i) sub(sn++);
        nbar<1, 256>();
        PROFT(tid_ == 128, layer * 16 + 3);
        rest(sn >> 2, SKB, NR);
        PROFT(lane == 0 && layer == PL, 200 + cw);
        PROFT(tid_ == 128, layer * 16 + 10);
        if (cw == 0) mbar_wait(BA(B_HALO), (layer >> 1) & 1);
        PROFT(tid_ == 128, layer * 16 + 5);
        const uint32_t vs = sb + (cw ? VB + rowo - 2048 : SM_SD + 4096 + rowo), vst = cw ? SLOT : 2048;
        const uint32_t psel = e ? 0x1054u : 0x5410u;
#pragma unroll
        for (int hp = 0; hp < 2; ++hp) {
#pragma unroll
          for (int i = 4 * hp; i < 4 * hp + 4; ++i) {
            const uint4 u = lds128(sb + (cw ? PH + (cw - 1) * 4096 : SM_SD) + lane * 16 + i * 512);
            kp[i][0] = u.x; kp[i][1] = u.y; kp[i][2] = u.z; kp[i][3] = u.w;
          }
#pragma unroll
          for (int i = 4 * hp; i < 4 * hp + 4; ++i) {
            ldsm_x4_t(vf[0][i & 1][i >> 1][0], vf[0][i & 1][i >> 1][1], vf[0][i & 1][i >> 1][2], vf[0][i & 1][i >> 1][3], vs + (i >> 2) * vst + (X ^ ((i & 3) << 5)));
            ldsm_x4_t(vf[1][i & 1][i >> 1][0], vf[1][i & 1][i >> 1][1], vf[1][i & 1][i >> 1][2], vf[1][i & 1][i >> 1][3], sb + VB + (i >> 2) * SLOT + rowo + (X ^ ((i & 3) << 5)));
          }
          if (hp) {
            rest_end();
          }
          float l0[2][4], l1[2][4];
#pragma unroll
          for (int h = 0; h < 2; ++h) {
            const int H = 2 * hp + h;
            uint32_t qa[8];
#pragma unroll
            for (int i = 0; i < 8; ++i) qa[i] = pack_bf16(acc[128 + 16 * H + 2 * i], acc[129 + 16 * H + 2 * i]);
#pragma unroll
            for (int nt = 3; nt >= 0; --nt) {
              float sc[4] = {0.f, 0.f, 0.f, 0.f};
#pragma unroll
              for (int ks = 0; ks < 2; ++ks) {
                const uint32_t (&kf)[4] = nt < 2 ? kp[2 * H + ks] : kk[2 * H + ks];
                mma_bf16(sc, qa[4 * ks], qa[4 * ks + 1], qa[4 * ks + 2], qa[4 * ks + 3], kf[2 * (nt & 1)], kf[2 * (nt & 1) + 1]);
              }
              l0[h][nt] = fmaf(e ? sc[1] : sc[0], f0[nt], b0[nt]);
              l1[h][nt] = fmaf(e ? sc[3] : sc[2], f1[nt], b1[nt]);
            }
          }
          float mx0[2], mx1[2], s0[2], s1[2];
#pragma unroll
          for (int h = 0; h < 2; ++h) {
            mx0[h] = fmaxf(fmaxf(l0[h][0], l0[h][1]), l0[h][2]);
            mx1[h] = fmaxf(fmaxf(l1[h][1], l1[h][2]), l1[h][3]);
          }
#pragma unroll
          for (int o = 1; o <= 2; o <<= 1)
#pragma unroll
            for (int h = 0; h < 2; ++h) {
              mx0[h] = fmaxf(mx0[h], __shfl_xor_sync(0xffffffffu, mx0[h], o));
              mx1[h] = fmaxf(mx1[h], __shfl_xor_sync(0xffffffffu, mx1[h], o));
            }
#pragma unroll
          for (int h = 0; h < 2; ++h) {
#pragma unroll
            for (int nt = 0; nt < 3; ++nt) { l0[h][nt] = ex2(l0[h][nt] - mx0[h]); l1[h][nt + 1] = ex2(l1[h][nt + 1] - mx1[h]); }
            s0[h] = (l0[h][0] + l0[h][1]) + l0[h][2];
            s1[h] = (l1[h][1] + l1[h][2]) + l1[h][3];
          }
#pragma unroll
          for (int o = 1; o <= 2; o <<= 1)
#pragma unroll
            for (int h = 0; h < 2; ++h) {
              s0[h] += __shfl_xor_sync(0xffffffffu, s0[h], o);
              s1[h] += __shfl_xor_sync(0xffffffffu, s1[h], o);
            }
          uint32_t ow[2][2][4];
#pragma unroll
          for (int h = 0; h < 2; ++h) {
            const int H = 2 * hp + h;
            uint32_t pl[4], ph[4];
            const float i0 = rcp(s0[h]), i1 = rcp(s1[h]);
#pragma unroll
            for (int nt = 0; nt < 4; ++nt) {
              const uint32_t pk = pack_bf16(nt < 3 ? l0[h][nt] * i0 * rj[nt] : 0.f, nt > 0 ? l1[h][nt] * i1 * rj[nt] : 0.f);
              pl[nt] = nt < 3 ? __byte_perm(pk, 0u, psel) : 0u;
              ph[nt] = nt > 0 ? __byte_perm(pk, 0u, psel + 0x2222u) : 0u;
            }
#pragma unroll
            for (int nj = 0; nj < 4; ++nj) {
              float oa[4] = {0.f, 0.f, 0.f, 0.f};
#pragma unroll
              for (int ks = 0; ks < 2; ++ks)
                mma_bf16(oa, pl[2 * ks], ph[2 * ks], pl[2 * ks + 1], ph[2 * ks + 1], vf[ks][nj >> 1][H][2 * (nj & 1)], vf[ks][nj >> 1][H][2 * (nj & 1) + 1]);
              ow[h][0][nj] = pack_bf16(oa[0], oa[1]); ow[h][1][nj] = pack_bf16(oa[2], oa[3]);
            }
          }
          if (hp == 0) {
#pragma unroll
            for (int i = 0; i < 4; ++i) stg128(g_o + gfr + (i & 1) * 8 * D_ + (i >> 1) * 32, ow[i >> 1][i & 1][0], ow[i >> 1][i & 1][1], ow[i >> 1][i & 1][2], ow[i >> 1][i & 1][3]);
            __syncwarp();
            if (lane == 0) mbar_arrive(BA(B_OH0));
            rest_hi();
          } else {
#pragma unroll
            for (int i = 0; i < 16; ++i) o1[i >> 2][i & 3] = ow[i >> 3][(i >> 2) & 1][i & 3];
          }
#pragma unroll
          for (int i = 0; i < 16; ++i) of[4 * hp + (i >> 2)][i & 3] = ow[i >> 3][i & 1][(i >> 1) & 3];
          if (!hp) PROFT(tid_ == 128, layer * 16 + 15);
        }
      } else {
        float sc[2] = {rs0 * L2E, rs1 * L2E};
        {
          const uint32_t vb = sb + VB + (rowo >> 1), X0 = (lchk ^ ((lane & 7) >> 1)) << 4;
          const uint32_t pb = sb + PH + (t & 1) * SLOT + (wrow0 + gq) * 128 + ((((t & 1) * 4 + (t & 2)) ^ gq) << 4);
          float kva[20], en[32], mx[2][2], mn[2][2];
#define PV(hp, j) acc[32 * (hp) + (j)]
          auto mm = [&](int hp, int j) {
            const int r = (j >> 1) & 1;
            if (j < 4 && !(j & 1)) { mx[hp][r] = PV(hp, j); mn[hp][r] = PV(hp, j); }
            else { mx[hp][r] = fmaxf(mx[hp][r], PV(hp, j)); mn[hp][r] = fminf(mn[hp][r], PV(hp, j)); }
          };
          auto mmx = [&](int hp) {
#pragma unroll
            for (int r = 0; r < 2; ++r) {
              mx[hp][r] = fmaxf(mx[hp][r], __shfl_xor_sync(0xffffffffu, mx[hp][r], 2)) * -sc[r];
              mn[hp][r] = fmaf(fminf(mn[hp][r], __shfl_xor_sync(0xffffffffu, mn[hp][r], 2)), sc[r], mx[hp][r]);
            }
          };
          auto stage = [&](int hp) {
#pragma unroll
            for (int i = 0; i < 20; ++i) asm volatile("" : "+f"(kva[i]) :: "memory");
            nbar_dyn(3 + wu, 128);
#pragma unroll
            for (int i = 0; i < 4; ++i)
              sts128(sb + VB + hp * SLOT + wg * 8192 + (wq * 128 + i * 32 + lane) * 16,
                     make_uint4(__float_as_uint(kva[4 * i]), __float_as_uint(kva[4 * i + 1]), __float_as_uint(kva[4 * i + 2]), __float_as_uint(kva[4 * i + 3])));
            if (t == 0) sts_f2(sb + SM_AP + ((2 * hp + wg) * 64 + wq * 16 + gq * 2) * 4, kva[16], kva[18]);
            fence_async_smem();
            __syncwarp();
            if (lane == 0) mbar_arrive(BA(B_KVDONE));
          };
          int sn = 4;
#pragma unroll
          for (int j = 0; j < 32; ++j) mm(0, j);
          mmx(0);
#pragma unroll
          for (int hp = 0; hp < 2; ++hp) {
            float sp[2] = {0.f, 0.f}, sm[2] = {0.f, 0.f};
#pragma unroll
            for (int j = 0; j < 32; ++j) {
              const int r = (j >> 1) & 1, ns = hp ? SUBS1 : SUBS;
              if ((j * ns) / 32 != ((j + 1) * ns) / 32) {
                sub(sn++);
                if (hp && sn == 4 + SUBS + 4) { stage(0); PROFT(tid_ == 128, layer * 16 + 12); }
              }
              const float x = fmaf(PV(hp, j), sc[r], mx[hp][r]);
              PV(hp, j) = ex2(x); en[j] = ex2(mn[hp][r] - x);
              sp[r] += PV(hp, j); sm[r] += en[j];
              if (hp == 0) {
                mm(1, j);
                if ((j & 3) == 0) {
                  const int jp = 8 + (j >> 2);
                  stsm_x4(vb + ((jp - 8) >> 1) * 8192 + (X0 ^ ((jp & 1) << 5)), pack_bf16(acc[8 * jp], acc[8 * jp + 1]), pack_bf16(acc[8 * jp + 2], acc[8 * jp + 3]),
                          pack_bf16(acc[8 * jp + 4], acc[8 * jp + 5]), pack_bf16(acc[8 * jp + 6], acc[8 * jp + 7]));
                }
              }
            }
#pragma unroll
            for (int r = 0; r < 2; ++r) {
              sp[r] = rcp(sp[r] + __shfl_xor_sync(0xffffffffu, sp[r], 2)) * (r ? rs1 : rs0);
              sm[r] = rcp(sm[r] + __shfl_xor_sync(0xffffffffu, sm[r], 2)) * (r ? rs1 : rs0);
            }
            if (hp == 0) { mmx(1); mbar_wait(BA(CM + 15), par); }
            else { PROFT(tid_ == 128, layer * 16 + 11); nbar<1, 256>(); }
#pragma unroll
            for (int i = 0; i < 4; ++i) {
              const int r = i & 1, d = 16 * (i >> 1) + 2 * r;
              sts128((pb + r * 1024) ^ ((i >> 1) << 4), make_uint4(pack_bf16(PV(hp, d) * sp[r], PV(hp, d + 1) * sp[r]), pack_bf16(PV(hp, d + 4) * sp[r], PV(hp, d + 5) * sp[r]),
                                                                    pack_bf16(PV(hp, d + 8) * sp[r], PV(hp, d + 9) * sp[r]), pack_bf16(PV(hp, d + 12) * sp[r], PV(hp, d + 13) * sp[r])));
              sts128((pb + r * 1024) ^ ((i >> 1) << 4) ^ 64, make_uint4(pack_bf16(en[d] * sm[r], en[d + 1] * sm[r]), pack_bf16(en[d + 4] * sm[r], en[d + 5] * sm[r]),
                                                                         pack_bf16(en[d + 8] * sm[r], en[d + 9] * sm[r]), pack_bf16(en[d + 12] * sm[r], en[d + 13] * sm[r])));
            }
            fence_async_smem();
            nbar<1, 256>();
            const uint32_t dP = dB0 + (PH >> 4) + wu * 1024;
            const uint32_t dV = (dB0 & 0xFFFFu) + ((VB + hp * SLOT) >> 4) + (((SM_SD - VB - hp * SLOT) >> 4) << 16) + wu * (512u - (512u << 16));
            wgmma_fence();
#pragma unroll
            for (int ks = 0; ks < 8; ++ks) wgmma_n40_tt(kva, D128(dP + ks * 128), desc64(dV + ks * 64, 0x80000020u), ks != 0);
            wgmma_commit();
          }
#pragma unroll
          for (int i = 0; i < 4; ++i) sub(sn++);
          stage(1);
          PROFT(tid_ == 128, layer * 16 + 3);
          rest(sn >> 2, SKA, 0);
          PROFT(lane == 0 && layer == PL, 200 + cw);
          PROFT(tid_ == 128, layer * 16 + 10);
        }
#define QV(H, i) acc[128 + 16 * (H) + (i)]
        float mx[4][2], mn[4][2];
        uint32_t ph[4][4][4];
        auto mnx = [&](int hp) {
#pragma unroll
          for (int H = 2 * hp; H < 2 * hp + 2; ++H)
#pragma unroll
            for (int r = 0; r < 2; ++r) {
              mx[H][r] = fmaxf(fmaxf(fmaxf(QV(H, 2 * r), QV(H, 2 * r + 1)), fmaxf(QV(H, 4 + 2 * r), QV(H, 5 + 2 * r))),
                               fmaxf(fmaxf(QV(H, 8 + 2 * r), QV(H, 9 + 2 * r)), fmaxf(QV(H, 12 + 2 * r), QV(H, 13 + 2 * r))));
              mn[H][r] = fminf(fminf(fminf(QV(H, 2 * r), QV(H, 2 * r + 1)), fminf(QV(H, 4 + 2 * r), QV(H, 5 + 2 * r))),
                               fminf(fminf(QV(H, 8 + 2 * r), QV(H, 9 + 2 * r)), fminf(QV(H, 12 + 2 * r), QV(H, 13 + 2 * r))));
            }
#pragma unroll
          for (int o = 1; o <= 2; o <<= 1)
#pragma unroll
            for (int H = 2 * hp; H < 2 * hp + 2; ++H)
#pragma unroll
              for (int r = 0; r < 2; ++r) {
                mx[H][r] = fmaxf(mx[H][r], __shfl_xor_sync(0xffffffffu, mx[H][r], o));
                mn[H][r] = fminf(mn[H][r], __shfl_xor_sync(0xffffffffu, mn[H][r], o));
              }
#pragma unroll
          for (int H = 2 * hp; H < 2 * hp + 2; ++H)
#pragma unroll
            for (int r = 0; r < 2; ++r) { mx[H][r] *= -sc[r]; mn[H][r] = fmaf(mn[H][r], sc[r], mx[H][r]); }
        };
        auto fm = [&](int H) {
#pragma unroll
          for (int i = 0; i < 8; ++i) {
            const int r = i & 1;
            const float x0 = fmaf(QV(H, 2 * i), sc[r], mx[H][r]), x1 = fmaf(QV(H, 2 * i + 1), sc[r], mx[H][r]);
            ph[H][i >> 2][i & 3] = pack_bf16(ex2(x0), ex2(x1));
            ph[H][2 + (i >> 2)][i & 3] = pack_bf16(ex2(mn[H][r] - x0), ex2(mn[H][r] - x1));
          }
        };
        auto conv = [&](int hp) {
          mbar_wait(BA(hp ? B_KVF1 : B_KVF), (layer >> 1) & 1);
          PROFT(tid_ == 128, layer * 16 + (hp ? 4 : 5));
          if (hp) nbar_dyn(3 + wu, 128);
#pragma unroll
          for (int h = 0; h < 2; ++h) {
            uint4 u[4];
#pragma unroll
            for (int i = 0; i < 4; ++i) u[i] = lds128(sb + VB + hp * SLOT + h * 8192 + (wq * 128 + i * 32 + lane) * 16);
            const float zz = lds_f(sb + SM_AP + ((2 * hp + h) * 64 + wq * 16 + (lane & 7) * 2 + ((lane >> 3) & 1)) * 4);
            const uint32_t kb_ = sb + PH + wg * SLOT + h * 8192 + (wq * 16 + lrow) * 128;
#pragma unroll
            for (int i = 0; i < 4; i += 2)
              stsm_x4(kb_ + (X ^ (i << 4)),
                      pack_bf16(__uint_as_float(u[i].x), __uint_as_float(u[i].y)), pack_bf16(__uint_as_float(u[i].z), __uint_as_float(u[i].w)),
                      pack_bf16(__uint_as_float(u[i + 1].x), __uint_as_float(u[i + 1].y)), pack_bf16(__uint_as_float(u[i + 1].z), __uint_as_float(u[i + 1].w)));
            const uint32_t z1 = pack_bf16(zz, 1.f);
            if (lane < 16) sts128(kb_ + ((4 ^ (lane & 7)) << 4), make_uint4(z1, z1, z1, z1));
          }
          fence_async_smem();
        };
        mnx(0);
        fm(0);
        if (CV0) conv(0);
        fm(1);
        if (!CV0) conv(0);
#pragma unroll
        for (int hp = 0; hp < 2; ++hp) {
          nbar_dyn(3 + wu, 128);
          float oa[4][20];
          wgmma_fence();
#pragma unroll
          for (int s = 0; s < 2; ++s)
#pragma unroll
            for (int v = 0; v < 4; ++v) {
              const int h = v >> 1, s4 = 2 * (v & 1) + s;
              wgmma_n40_rs(oa[v], ph[2 * hp + h][s4], D128(dB0 + (PH >> 4) + wu * 1024 + h * 512 + (s4 ^ (2 * h)) * 128), s != 0);
            }
          wgmma_commit();
          if (hp == 0) mnx(1);
          wgmma_wait<0>();
#pragma unroll
          for (int i = 0; i < 20; ++i) asm volatile("" : "+f"(oa[0][i]), "+f"(oa[1][i]), "+f"(oa[2][i]), "+f"(oa[3][i]) :: "memory");
          uint32_t ow[2][2][4];
#pragma unroll
          for (int h = 0; h < 2; ++h)
#pragma unroll
            for (int r = 0; r < 2; ++r) {
              const float a = oa[2 * h + 1][17 + 2 * r], b = oa[2 * h][17 + 2 * r];
              const float id = rcp(fmaf(oa[2 * h][16 + 2 * r], a, fmaf(a, 1e-6f, oa[2 * h + 1][16 + 2 * r]) * b));
              const float fa = a * id, fb = b * id;
#pragma unroll
              for (int j = 0; j < 4; ++j)
                ow[h][r][j] = pack_bf16(fmaf(oa[2 * h][4 * j + 2 * r], fa, oa[2 * h + 1][4 * j + 2 * r] * fb),
                                        fmaf(oa[2 * h][4 * j + 2 * r + 1], fa, oa[2 * h + 1][4 * j + 2 * r + 1] * fb));
            }
#pragma unroll
          for (int i = 0; i < 16; ++i) of[4 * hp + (i >> 2)][i & 3] = ow[i >> 3][i & 1][(i >> 1) & 3];
          if (hp == 0) {
#pragma unroll
            for (int i = 0; i < 8; ++i) {
              if (!(i & 1)) stg128(g_o + gfr + ((i >> 1) & 1) * 8 * D_ + (i >> 2) * 32, ow[i >> 2][(i >> 1) & 1][0], ow[i >> 2][(i >> 1) & 1][1], ow[i >> 2][(i >> 1) & 1][2], ow[i >> 2][(i >> 1) & 1][3]);
              const int r = i & 1;
              const float x0 = fmaf(QV(2, 2 * i), sc[r], mx[2][r]), x1 = fmaf(QV(2, 2 * i + 1), sc[r], mx[2][r]);
              ph[2][i >> 2][i & 3] = pack_bf16(ex2v(x0), ex2v(x1));
              ph[2][2 + (i >> 2)][i & 3] = pack_bf16(ex2v(mn[2][r] - x0), ex2v(mn[2][r] - x1));
            }
            __syncwarp();
            if (lane == 0) mbar_arrive(BA(B_OH0));
            PROFT(tid_ == 128 && layer, layer * 16 + 15);
            if (QORD) { fm(3); conv(1); } else { conv(1); fm(3); }
          } else {
#pragma unroll
            for (int i = 0; i < 16; ++i) o1[i >> 2][i & 3] = ow[i >> 3][(i >> 2) & 1][i & 3];
          }
        }
      }
      PROFT(tid_ == 128, layer * 16 + 6);
    }
    {
      PHASE_CTX();
      MMA_CTX();
      auto o1st = [&]() {
#pragma unroll
        for (int i = 0; i < 4; ++i) stg128(g_o + gfr + (i & 1) * 8 * D_ + (2 + (i >> 1)) * 32, o1[i][0], o1[i][1], o1[i][2], o1[i][3]);
        __syncwarp();
        if (lane == 0) { mbar_arrive(BA(B_OH1)); if (!O1P) REL2(B_EF); }
        PROFT(lane == 0 && layer == PL, 208 + cw);
      };
      if (O1P) {
        __syncwarp();
        if (lane == 0) REL2(B_EF);
      } else o1st();
      mbar_wait(BA(FW), par);
      mbar_wait(BA(FW + 1), par);
      if (O1P == 1) o1st();
#pragma unroll
      for (int i = 0; i < 2; ++i) {
        wgmma_fence();
#pragma unroll
        for (int k = 0; k < 4; ++k) {
          if (i + k) wgmma_n128_rs(acc, of[4 * i + k], D128(dB0 + (uint32_t)((WO_B >> (4 * i)) & 15) * 1024 + k * 128), 1);
          else wgmma_n128_rs0(acc, of[0], D128(dB0 + (uint32_t)(WO_B & 15) * 1024));
        }
        wgmma_commit();
        if (O1P == 2 && i == 0) o1st();
      }
      wgmma_wait<1>();
      if (elected) REL2(CW);
      uint64_t ta = WO_A >> 8, tw = WO_B >> 8;
      auto run = [&](int i0, int i1) {
#pragma unroll 1
        for (int i = i0; i < i1; ++i) {
          mbar_wait(BA(FW + i), par);
          PROFL(tid_ == 128 && layer == PL, 160 + i);
          const uint32_t da = dA0 + ((uint32_t)ta & 15) * 1024, db = dB0 + ((uint32_t)tw & 15) * 1024;
          ta >>= 4; tw >>= 4;
          wgmma_fence();
#pragma unroll
          for (int k = 0; k < 4; ++k) wgmma_n128(acc, D128(da + k * 2), D128(db + k * 128), 1);
          wgmma_commit();
          wgmma_wait<1>();
          if (elected) REL2(CW + i - 1);
        }
      };
      run(2, XRAT);
#pragma unroll
      for (int j = 0; j < 8 / XRN; ++j) {
#pragma unroll
        for (int i = j * XRN; i < (j + 1) * XRN; ++i) ldg128((layer ? g_x : c.x0) + gfr + (i & 1) * 8 * D_ + (i >> 1) * 32, xp[i][0], xp[i][1], xp[i][2], xp[i][3]);
        run(XRAT + j, j + 1 < 8 / XRN ? XRAT + j + 1 : 16);
      }
      if (layer == 0) {
#pragma unroll
        for (int o = 1; o <= 2; o <<= 1)
#pragma unroll
          for (int i = 0; i < 16; ++i) {
            const int j = o == 1 ? 2 * (i & 1) : (i & 1);
            uint32_t &a = xp[i >> 1][j], &b = xp[i >> 1][j + o];
            const uint32_t r = __shfl_xor_sync(0xffffffffu, (t & o) ? a : b, o);
            if (t & o) a = r; else b = r;
          }
      }
      wgmma_wait<0>();
#pragma unroll
      for (int i = 128; i < 192; ++i) asm volatile("" : "+f"(acc[i]) :: "memory");
      if (elected) REL2(CW + 15);
      PROFT(lane == 0 && layer == PL, 216 + cw);
      PROFT(tid_ == 128, layer * 16 + 7);
    }
    {
      PHASE_CTX();
#pragma unroll
      for (int i = 0; i < 32; ++i)
        xp[i >> 2][i & 3] = add_bf16x2(xp[i >> 2][i & 3], pack_bf16(acc[128 + 16 * (i >> 3) + 4 * (i & 3) + 2 * ((i >> 2) & 1)], acc[129 + 16 * (i >> 3) + 4 * (i & 3) + 2 * ((i >> 2) & 1)]));
      if (layer == NLAYERS - 1) {
#pragma unroll
        for (int i = 0; i < 8; ++i) stsm_x4(sb + (XS + (i >> 2)) * SLOT + (Y ^ ((i & 2) << 5)) + (i & 1) * 1024, xp[i][0], xp[i][1], xp[i][2], xp[i][3]);
        __syncwarp();
        slab_out_half(sb + XS * SLOT, c.out + (size_t)m0 * D_ + g * 128, wrow0, lane);
        slab_out_half(sb + (XS + 1) * SLOT, c.out + (size_t)m0 * D_ + g * 128 + 64, wrow0, lane);
        PROFT(tid_ == 128, layer * 16 + 24);
        break;
      }
#pragma unroll
      for (int i = 0; i < 4; ++i) stg128(g_x + gfr + (i & 1) * 8 * D_ + (i >> 1) * 32, xp[i][0], xp[i][1], xp[i][2], xp[i][3]);
      __syncwarp();
      if (lane == 0) mbar_arrive(BA(B_XH0));
#pragma unroll
      for (int i = 0; i < 16; ++i) xf[i >> 2][i & 3] = xp[2 * (i >> 3) + (i & 1)][(i >> 1) & 3];
      PROFT(tid_ == 128, layer * 16 + 24);
    }
  }
}

__device__ __forceinline__ uint64_t k_order(int o) {
  const uint32_t lo = (1u << (4 * o)) - 1u, h0 = (0xECA86420u & lo) | ((0xECA86420u >> 4) & ~lo);
  return (uint64_t)(2 * o) | ((uint64_t)(2 * o + 1) << 4) | ((uint64_t)(h0 & 0xFFFFFFFu) << 8) | ((uint64_t)((h0 & 0xFFFFFFFu) | 0x1111111u) << 36);
}

__global__ void __cluster_dims__(2, 1, 1) __launch_bounds__(384, 1)
mega_kernel(const __grid_constant__ Maps maps, const __grid_constant__ Ctx c, const bf16* __restrict__ wA, const bf16* __restrict__ wB,
            const bf16* __restrict__ woA, const bf16* __restrict__ woB) {
  if (blockIdx.x - c.boff >= 128u) {
    const unsigned int epoch = ld_relaxed(&g_epoch);
    const int e = (blockIdx.x - c.boff) & 3, tid = threadIdx.x;
    float s[8] = {0.f, 0.f, 0.f, 0.f, 0.f, 0.f, 0.f, 0.f};
    const uint32_t sb = smem_u32(smem_raw), bar = sb + SM_BAR;
    auto issue = [&](int i) {
      mbar_expect_tx(BA(i & 3), 49152);
      bulk_load(sb + (i & 3) * 49152, wB + (size_t)e * 256 * 3072 + i * 24576, 49152, BA(i & 3));
    };
    if (tid == 0) {
#pragma unroll 1
      for (int i = 0; i < 4; ++i) {
        mbar_init(BA(i), 1);
        fence_async_smem();
        issue(i);
      }
    }
    __syncthreads();
#pragma unroll 1
    for (int i = 0; i < 32; ++i) {
      mbar_wait(BA(i & 3), (i >> 2) & 1);
#pragma unroll
      for (int r = 0; r < 8; ++r) {
        const uint4 v = lds128(sb + (i & 3) * 49152 + r * 6144 + tid * 16);
        s[0] += bf_lo(v.x); s[1] += bf_hi(v.x); s[2] += bf_lo(v.y); s[3] += bf_hi(v.y);
        s[4] += bf_lo(v.z); s[5] += bf_hi(v.z); s[6] += bf_lo(v.w); s[7] += bf_hi(v.w);
      }
      __syncthreads();
      if (tid == 0 && i < 28) issue(i + 4);
    }
    float* cd = g_cs + (epoch & 1) * 6144 + 3072 + ((tid >> 4) & 7) * 384 + (tid < 128 ? 256 : (tid >> 7) * 128 - 128) + (tid & 15) * 8;
    red_add4(cd, s[0], s[1], s[2], s[3]);
    red_add4(cd + 4, s[4], s[5], s[6], s[7]);
    __syncthreads();
    if (tid == 0) flag_add(&g_csflag[8].v);
    const int op = (epoch & 1) ^ 1;
    float4* kz = reinterpret_cast<float4*>(g_kv + (size_t)op * (2 * 8 * 8448)) + e * 8448;
#pragma unroll 2
    for (int i = tid; i < 8448; i += 384) kz[i] = make_float4(0.f, 0.f, 0.f, 0.f);
    reinterpret_cast<float4*>(g_cs + op * 6144)[e * 384 + tid] = make_float4(0.f, 0.f, 0.f, 0.f);
#pragma unroll 1
    for (int i = tid; i < 1024; i += 384) reinterpret_cast<float4*>(g_stats + (op * 4 + e) * S_)[i] = make_float4(0.f, 0.f, 0.f, 0.f);
    return;
  }
  const int warp = __shfl_sync(0xffffffffu, threadIdx.x >> 5, 0), lane = threadIdx.x & 31;
  if (smem_u32(smem_raw) != SB0 + ((blockIdx.x & 1) << 24)) __trap();
  {
  const int cid = (blockIdx.x - c.boff) >> 1, u7 = ((cid - 36) * 37) >> 8, cr = blockIdx.x & 1;
  const int g = cid < 4 ? 4 + cid : cid < 36 ? (cid - 4) >> 3 : 4 + u7, rb = (cid < 4 ? 0 : cid < 36 ? (cid - 4) & 7 : cid - 35 - 7 * u7) * 2 + cr, m0 = rb * 128;
  const uint32_t sb = SB0 + (cr << 24), bar = sb + SM_BAR;
  PROFT(lane == 0 && (warp == 0 || warp == 4), 224 + (warp >> 2) * 8);
  uint32_t cx = 0;
  if (warp == 2) {
    if (lane < NMAP) asm volatile("prefetch.tensormap [%0];" ::"l"(&maps.m[lane]) : "memory");
    if (lane == 31) asm volatile("prefetch.global.L2 [%0];" ::"l"(&g_epoch));
  } else if (warp == 3) {
    cx = c_map[cid] + c_wop[lane] + c_wop[NWOP - lane] + c_aop[lane] + c_aop[NAOP - lane] + (uint32_t)(uintptr_t)g_x;
  } else if (PFW && warp >= 4) {
    const int i = threadIdx.x - 128;
    asm volatile("prefetch.global.L2 [%0];" ::"l"(wA + (size_t)(rb * 64 + ((i >> 1) & 63)) * 3072 + (i >> 7) * 1024 + g * 128 + (i & 1) * 64));
  }
  if (warp < 2) {
    const int s = warp, kb = (rb & ~1) + s;
    if (lane == 0) {
      mbar_init(BA(FM + s), 1u);
      mbar_init(BA(B_RAW + warp), 1u);
      if (warp) mbar_init(BA(B_X0), 1u);
      asm volatile("fence.mbarrier_init.release.cluster;" ::: "memory");
    }
    __syncwarp();
    if (warp == 0) tma_2d_e(sb + SM_SD, &maps.m[MAP_PHI], 0, g * 128, BA(B_RAW));
    else if (W1DL) __nanosleep(W1DL);
#pragma unroll
    for (int j = 0; j < 6; ++j)
      tma_5d_e(sb + (j < 2 ? 2 * s : j < 4 ? 9 + s : 2 * s + 1) * SLOT + (j & 1) * 8192, &maps.m[MAP_WA], (j < 2 ? 1024 : j < 4 ? 0 : 2048) + g * 128 + (j & 1) * 64, 2 * kb,
               BA(j < 4 ? B_RAW + warp : FM + s));
    tma_2d_e(sb + (XS + s) * SLOT, &maps.m[MAP_X0], kb * 64, m0, BA(FM + s));
    expect_tx_e(BA(B_RAW + warp), warp ? 32768 : 32768 + 8192);
    expect_tx_e(BA(FM + s), 32768);
    if (X0AT == 0 && warp == 1) {
      tma_2d_e(sb + 11 * SLOT, &maps.m[MAP_X0], g * 128, m0, BA(B_X0));
      tma_2d_e(sb + 12 * SLOT, &maps.m[MAP_X0], g * 128 + 64, m0, BA(B_X0));
      expect_tx_e(BA(B_X0), 32768);
    }
  } else if (warp >= 4 && lane == 0) {
#pragma unroll 1
    for (int i = 2 + (warp - 4) * 13; i < 15 + (warp - 4) * 13; ++i)
      mbar_init(BA(i), 1u << ((i < CM ? 0u : i < B_EF ? 2u : (uint32_t)(BAR_LG >> (4 * ((i - B_EF) & 15)))) & 7u));
    asm volatile("fence.mbarrier_init.release.cluster;" ::: "memory");
  }
  __syncwarp();
  asm volatile("barrier.cluster.arrive.relaxed.aligned;" ::: "memory");
  if (threadIdx.x == 96 + c.zero) sts_f(sb + SM_EPOCH + 4, __uint_as_float(cx));
  PROFT(lane == 0 && (warp == 0 || warp == 4), 225 + (warp >> 2) * 8);
  __syncwarp();
  PROFT(lane == 0 && (warp == 0 || warp == 4), 226 + (warp >> 2) * 8);
  }

  if (warp < 4) {
    asm volatile("setmaxnreg.dec.sync.aligned.u32 40;");
    PROFT(threadIdx.x == 0, 227);
    cluster_wait();
    PROFT(threadIdx.x == 0, 228);
    if (warp == 0 || warp == 3) {
    if (warp == 0) {
      BLK_CTX();
      const unsigned int epoch = __shfl_sync(0xffffffffu, ld_relaxed(&g_epoch), 0), xbase = epoch * NLAYERS;
      (void)xbase;
      const uint64_t ordg = k_order(g);
      if (X0AT) {
        mbar_wait_u(BA(B_RAW + X0AT - 1), 0);
        tma_2d_e(sb + 11 * SLOT, &maps.m[MAP_X0], g * 128, m0, BA(B_X0));
        tma_2d_e(sb + 12 * SLOT, &maps.m[MAP_X0], g * 128 + 64, m0, BA(B_X0));
        expect_tx_e(BA(B_X0), 32768);
      }
#pragma unroll 1
      for (int lp = 0; lp < 2 * NLAYERS; ++lp) {
        const int layer = lp >> 1, n1 = (lp & 1) ? NAOP : NAOP - 14;
        int n = (lp & 1) ? NAOP - 14 : 0;
        const uint64_t ord = lp ? ordg : k_order(rb >> 1);
        uint32_t ready = lp ? 0u : 0xFFFFu, nop = c_aop[n];
        const unsigned int* fl = ((lp & 1) ? g_of : g_xf) + rb * 32;
        const CUtensorMap* tm = &maps.m[(lp & 1) ? MAP_O : lp ? MAP_X : MAP_X0];
        const uint32_t skip = layer ? 1u << 25 : 9u << 22;
#pragma unroll 1
        for (; n < n1; ++n) {
          const uint32_t op = nop;
          nop = c_aop[n + 1];
          const uint32_t kb = (uint32_t)(ord >> ((op >> 2) & 60)) & 15;
          uint32_t dst = sb + (op & 15) * SLOT, kc = kb * 64, fb = bar + ((op >> 5) & 0x3F8), need = ~ready & (1u << kb);
          asm volatile("" : "+r"(dst), "+r"(kc), "+r"(fb), "+r"(need));
          if (!(op & skip)) mbar_wait_u(bar + ((op >> 12) & 0x3F8), (layer ^ (op >> 22)) & 1);
          if (need) {
            PROFT(lane == 0 && (n == 0 || n == NAOP - 14), 64 + layer * 16 + (n ? 2 : 0));
            if (FASTP) src_wait_fast(fl, xbase + layer + 1, need, ready, lane);
            else src_wait<0>(fl, xbase + layer + 1, need, ready, lane);
            fence_async_all();
          }
          tma_2d_e(dst, tm, kc, m0, fb);
          PROFT(lane == 0 && (n == 0 || n == NAOP - 14), 64 + layer * 16 + (n ? 3 : 1));
          PROFL(lane == 0 && layer == PL && n >= NAOP - 14, 178 + n - (NAOP - 14));
          PROFL(lane == 0 && layer == PL + 1 && n < 4, 242 + n);
        }
      }
    } else {
      BLK_CTX();
      const unsigned int epoch = __shfl_sync(0xffffffffu, ld_relaxed(&g_epoch), 0), xbase = epoch * NLAYERS;
      (void)xbase;
      const uint64_t ordg = k_order(g);
#pragma unroll 1
      for (int layer = 0; layer < NLAYERS; ++layer) {
        const uint64_t ordq = layer ? ordg : k_order(rb >> 1);
        uint32_t ready = layer ? 0xFFFFu : 0u, nop = c_wop[0];
        const CUtensorMap* tq = &maps.m[(layer & 1) ? MAP_WB : MAP_WF];
        const CUtensorMap* tk = &maps.m[(layer & 1) ? MAP_WB : cr ? MAP_WA : MAP_WF];
        const uint32_t skip = layer ? 1u << 25 : 9u << 22, pm = layer ? 0xE0u : 0u;
        int n = 0;
#pragma unroll 1
        for (; n < NWOP - 16; ++n) {
          const uint32_t op = nop;
          nop = c_wop[n + 1];
          const uint32_t isq = (op >> 23) & 1, fb = bar + ((op >> 5) & 0x3F8);
          const uint32_t kb = (uint32_t)(ordq >> ((op >> 2) & 60)) & 15;
          const CUtensorMap* tm = (isq ? tq : tk) + ((op & pm) ? 1 : 0);
          const uint32_t dst = sb + (op & 15) * SLOT + cr * (isq ? 8192 : SLOT);
          const int col = g * 128 + (isq ? cr * 64 : 1024 + cr * 1024);
          if (layer == 0) {
            if ((op & 0x7E00) == 0) continue;
            const uint32_t need = ((isq || !cr) ? 1u << kb : 0u) | (((op >> 22) & 1) ? 0u : (((op >> 15) & 127) == CM ? 1u : 3u) << (rb & ~1));
            if ((ready & need) != need) {
              src_wait<0>(g_wff + g * 32, epoch + 1, need, ready, lane);
              fence_async_all();
            }
            if ((op & 15) >= 11) mbar_wait_u(BA(B_XT), 0);
          }
          wait_tma_5d_mc(!(op & skip), bar + ((op >> 12) & 0x3F8), (layer ^ (op >> 22)) & 1, dst, tm, col, 2 * kb, fb);
          if (!isq) tma_5d_mc_e(dst + 8192, tm, col + 64, 2 * kb, fb);
          if (op >> 26) expect_tx_e(fb, (op >> 26) * 8192);
          PROFL(lane == 0 && layer == PL + 1 && n < 16, 128 + n);
        }
        const CUtensorMap* to = &maps.m[(layer & 1) ? MAP_WOB : MAP_WOA];
#pragma unroll 1
        for (; n < NWOP; ++n) {
          const uint32_t op = nop;
          nop = c_wop[n + 1];
          const uint32_t fb = bar + ((op >> 5) & 0x3F8), kb = (uint32_t)(ordg >> ((op >> 2) & 60)) & 15;
          wait_tma_5d_mc(!((op >> 25) & 1), bar + ((op >> 12) & 0x3F8), layer & 1, sb + (op & 15) * SLOT + cr * 8192, to + ((op & 0xE0) ? 1 : 0), g * 128 + cr * 64, 2 * kb, fb);
          expect_tx_e(fb, (op >> 26) * 8192);
          PROFL(lane == 0 && layer == PL, 144 + ((op >> 8) & 127) - FW);
        }
      }
    }
    } else if (warp == 1) {
      BLK_CTX();
      const unsigned int epoch = __shfl_sync(0xffffffffu, ld_relaxed(&g_epoch), 0), xbase = epoch * NLAYERS;
      (void)xbase;
      if (lane == 0) {
        mbar_wait(BA(B_WFD), 0);
        PROFT(true, 229);
        if (WFDL && cr) __nanosleep(WFDL);
#pragma unroll 1
        for (int j = 0; j < 4; ++j) tma_store_5d(&maps.m[MAP_WF], sb + (j < 2 ? 2 * cr : 9 + cr) * SLOT + (j & 1) * 8192, (j < 2 ? 1024 : 0) + g * 128 + (j & 1) * 64, 2 * rb);
        bulk_commit();
        bulk_wait0();
        PROFT(true, 230);
        fence_async_all();
        flag_set(g_wff + g * 32 + rb, epoch + 1);
        PROFT(true, 64 + 13);
#pragma unroll 1
        for (int e = 0; e < NLAYERS; ++e) {
          BLK_CTX();
          if (e > 0) {
            mbar_wait(BA(B_XH0), (e - 1) & 1);
            PROFT(e == PL + 1, 240);
            flag_set(g_xf + rb * 32 + 2 * g, xbase + e + 1);
            PROFT(e == PL + 1, 241);
          }
          mbar_wait(BA(B_XDONE), e & 1);
          PROFT(true, 64 + e * 16 + 4);
          flag_set(g_xf + rb * 32 + 2 * g + 1, xbase + e + 1);
          if (e == 0) {
            flag_add(&g_csflag[g].v);
            l2_prefetch(wB + (size_t)bid_ * 24576, 49152);
            l2_prefetch(woA + (size_t)bid_ * 8192, 16384);
            l2_prefetch(woB + (size_t)bid_ * 8192, 16384);
          }
          PROFT(true, 64 + e * 16 + 7);
          if ((e & 1) == 0) {
            float* kvl = g_kv + ((size_t)((epoch & 1) * 2 + (e >> 1)) * 8 + g) * 8448;
#pragma unroll 1
            for (int hp = 0; hp < 2; ++hp) {
              mbar_wait(BA(B_KVDONE), hp);
              bulk_red_add(kvl + 8192 + hp * 128, sb + SM_AP + hp * 512, 512);
#pragma unroll 1
              for (int i = 0; i < NCH; ++i) {
                const int ch = hp * NCH + ((i + rb * NCH / 16) & (NCH - 1));
                bulk_red_add(kvl + ch * (4096 / NCH), sb + VB + ch * (16384 / NCH), 16384 / NCH);
                bulk_commit();
                asm volatile("cp.async.bulk.wait_group %0;" :: "n"(CHW) : "memory");
              }
              bulk_wait0();
              PROFT(true, 64 + e * 16 + (hp ? 10 : 6));
              fence_async_all();
              flag_add(&g_kvflag[hp * 8 + g].v);
              PROFT(e > 0 && hp, 64 + e * 16 + 8);
            }
          }
          if (e & 1) {
            mbar_wait(BA(B_OF0), (e >> 1) & 1);
            flag_set(g_hf + rb * 32 + g, xbase + e + 1);
            if (rb) flag_wait(g_hf + (rb - 1) * 32 + g, xbase + e + 1);
            fence_async_all();
            mbar_expect_tx(BA(B_HALO), 8192);
            bulk_load(sb + SM_SD, g_halo + (size_t)(((e >> 1) * 17 + rb) * 8 + g) * 2048, 8192, BA(B_HALO));
            PROFT(true, 64 + e * 16 + 15);
          }
          mbar_wait(BA(B_OH0), e & 1);
          PROFT(e > 0, 64 + e * 16 + 13);
          flag_set(g_of + rb * 32 + 2 * g, xbase + e + 1);
          PROFT(true, 64 + e * 16 + 9);
          mbar_wait(BA(B_OH1), e & 1);
          PROFT(true, 64 + e * 16 + 5);
          flag_set(g_of + rb * 32 + 2 * g + 1, xbase + e + 1);
          PROFT(true, 64 + e * 16 + 11);
        }
        if (bid_ == 0) g_epoch = epoch + 1;
      }
    } else {
      BLK_CTX();
      const unsigned int epoch = __shfl_sync(0xffffffffu, ld_relaxed(&g_epoch), 0), xbase = epoch * NLAYERS;
      (void)xbase;
      if (lane < 16) sts_f(sb + SM_RS + lane * 4, 0.f);
#pragma unroll 1
      for (int layer = 0; layer < NLAYERS; ++layer) {
#define HLP_CTX() BLK_CTX(); int lane = threadIdx.x & 31; asm volatile("" : "+r"(lane)); const bool isB = layer & 1, hal = isB && rb > 0; (void)hal;
#pragma unroll 1
        for (int ph = 0; ph < 2; ++ph) {
          HLP_CTX();
          if (ph == (layer == 0)) {
            const float* cs = g_cs + (epoch & 1) * 6144 + g * 384;
            if (layer) mbar_wait_u(BA(CT), (layer - 1) & 1);
            if (layer < 2) {
              if (lane == 0) flag_wait_slow(&g_csflag[isB ? 8 : g].v, isB ? epoch * 4u + 4u : epoch * 16u + 16u);
              __syncwarp();
            }
            float a[12];
#pragma unroll
            for (int i = 0; i < 12; ++i) a[i] = __ldcg(cs + isB * 3072 + i * 32 + lane);
#pragma unroll
            for (int i = 0; i < 12; ++i) {
              const float c1 = bf16r(a[i]), c2 = bf16r(a[i] - c1), c3 = (a[i] - c1) - c2;
              sts128(sb + SM_BP + (i * 32 + lane) * 16, make_uint4(pack_bf16(c1, c2), pack_bf16(c3, 0.f), 0u, 0u));
            }
          } else {
            uint32_t rdy = 0u;
            src_wait<128>(g_xf + rb * 32, xbase + layer + 1, 0xAAAAu, rdy, lane);
            rdy = 0u;
            if (hal) src_wait<128>(g_xf + (rb - 1) * 32, xbase + layer + 1, 0xAAAAu, rdy, lane);
            const float2* sp = g_stats + ((epoch & 1) * 4 + layer) * S_ + m0 + lane;
            float2 u[5];
#pragma unroll
            for (int i = 0; i < 4; ++i) u[i] = __ldcg(sp + i * 32);
            u[4] = __ldcg(sp - (hal ? 16 : 0));
#pragma unroll
            for (int i = 0; i < 5; ++i) {
              const float mean = u[i].x * (1.f / D_);
              const float var = fmaxf(fmaf(-u[i].x, mean, u[i].y) * (1.f / D_), 0.f);
              const float sd = bf16r(sqrtf(bf16r(bf16r(var) + 1e-5f)));
              const int R = i * 32 + lane;
              if (i < 4) {
                const float hm = -0.5f * bf16r(mean);
                sts_f(sb + SM_RS + (16 + R) * 4, __fdividef(1.f, sd));
                if (!isB) sts128(sb + SM_SD + R * 64 + ((R >> 1) & 3) * 16, make_uint4(__float_as_uint(sd) >> 16, 0u, 0u, 0u));
                sts128(sb + SM_AP + R * 16, make_uint4(pack_bf16(hm, hm), pack_bf16(hm, 0.f), 0u, 0u));
              } else if (hal && lane < 16) sts_f(sb + SM_RS + lane * 4, __fdividef(1.f, sd));
            }
            PROFT(lane == 0, 64 + layer * 16 + 12);
          }
        }
        HLP_CTX();
        fence_async_smem();
        __syncwarp();
        if (lane == 0) mbar_arrive(BA(B_STAT));
        PROFT(lane == 0, 64 + layer * 16 + 14);
        if (!isB && lane == 0) {
#pragma unroll 1
          for (int hp = 0; hp < 2; ++hp) {
            mbar_wait(BA(B_KVDONE), hp);
            flag_wait(&g_kvflag[hp * 8 + g].v, epoch * (16u * ((NLAYERS + 1) / 2)) + 16u * ((layer >> 1) + 1));
            const float* kvl = g_kv + ((size_t)((epoch & 1) * 2 + (layer >> 1)) * 8 + g) * 8448;
            const uint32_t kb = BA(hp ? B_KVF1 : B_KVF);
            fence_async_all();
            mbar_expect_tx(kb, 16384 + 512);
            bulk_load(sb + VB + hp * SLOT, kvl + hp * 4096, 16384, kb);
            bulk_load(sb + SM_AP + hp * 512, kvl + 8192 + hp * 128, 512, kb);
            PROFT(hp == 0, 64 + layer * 16 + 15);
          }
        }
        __syncwarp();
      }
    }
    __syncwarp();
    cluster_arrive();
    cluster_wait();
  } else {
    asm volatile("setmaxnreg.inc.sync.aligned.u32 232;");
    PROFT(threadIdx.x == 128, 235);
    cluster_wait();
    PROFT(threadIdx.x == 128, 236);
    consumer(c);
    asm volatile("bar.warp.sync 0xffffffff;\nbarrier.cluster.arrive.release.aligned;\nbarrier.cluster.wait.acquire.aligned;\n" ::: "memory");
  }
}

typedef CUresult (*PFN_encodeTiled)(CUtensorMap*, CUtensorMapDataType, cuuint32_t, void*, const cuuint64_t*, const cuuint64_t*,
                                    const cuuint32_t*, const cuuint32_t*, CUtensorMapInterleave, CUtensorMapSwizzle,
                                    CUtensorMapL2promotion, CUtensorMapFloatOOBfill);

static void make_map2(PFN_encodeTiled enc, CUtensorMap* m, const void* ptr, uint64_t cols, uint64_t rows, uint32_t box_c, uint32_t box_r) {
  cuuint64_t dims[2] = {cols, rows};
  cuuint64_t strides[1] = {cols * 2};
  cuuint32_t box[2] = {box_c, box_r};
  cuuint32_t es[2] = {1, 1};
  CUresult r = enc(m, CU_TENSOR_MAP_DATA_TYPE_BFLOAT16, 2, const_cast<void*>(ptr), dims, strides, box, es, CU_TENSOR_MAP_INTERLEAVE_NONE,
                   box_c == 64 ? CU_TENSOR_MAP_SWIZZLE_128B : CU_TENSOR_MAP_SWIZZLE_64B, CU_TENSOR_MAP_L2_PROMOTION_L2_256B, CU_TENSOR_MAP_FLOAT_OOB_FILL_NONE);
  (void)r;
}
static void make_map5(PFN_encodeTiled enc, CUtensorMap* m, const void* ptr, uint64_t cols) {
  for (int p = 0; p < 2; ++p) {
    cuuint64_t dims[5] = {cols, 2, 4, 4, 32};
    cuuint64_t strides[4] = {cols * 2, cols * (p ? 16 : 4), cols * (p ? 4 : 16), cols * 64};
    cuuint32_t box[5] = {64, 2, 4, 4, 2};
    cuuint32_t es[5] = {1, 1, 1, 1, 1};
    CUresult r = enc(m + p, CU_TENSOR_MAP_DATA_TYPE_BFLOAT16, 5, const_cast<void*>(ptr), dims, strides, box, es, CU_TENSOR_MAP_INTERLEAVE_NONE,
                     CU_TENSOR_MAP_SWIZZLE_128B, CU_TENSOR_MAP_L2_PROMOTION_L2_256B, CU_TENSOR_MAP_FLOAT_OOB_FILL_NONE);
    (void)r;
  }
}

extern "C" void kernel_launch(void* const* d_in, const int* in_sizes, int n_in, void* d_out, int out_size) {
  const bf16* A_x = (const bf16*)d_in[0];
  const bf16* A_wqkv = (const bf16*)d_in[1];
  const bf16* A_wphi = (const bf16*)d_in[2];
  const bf16* A_wo = (const bf16*)d_in[3];
  const bf16* B_wqkv = (const bf16*)d_in[5];
  const bf16* B_wo = (const bf16*)d_in[6];
  bf16* out = (bf16*)d_out;

  static PFN_encodeTiled enc = nullptr;
  static bf16 *p_x, *p_o, *p_wf;
  static uint32_t boff;
  if (!enc) {
    void* fn = nullptr; cudaDriverEntryPointQueryResult qr;
    cudaGetDriverEntryPoint("cuTensorMapEncodeTiled", &fn, cudaEnableDefault, &qr);
    enc = (PFN_encodeTiled)fn;
    cudaGetSymbolAddress((void**)&p_x, g_x);
    cudaGetSymbolAddress((void**)&p_o, g_o);
    cudaGetSymbolAddress((void**)&p_wf, g_wf);
    cudaFuncSetAttribute(mega_kernel, cudaFuncAttributeMaxDynamicSharedMemorySize, SM_TOTAL);
    cudaLaunchConfig_t cfg = {};
    cudaLaunchAttribute at; at.id = cudaLaunchAttributeClusterDimension; at.val.clusterDim.x = 2; at.val.clusterDim.y = 1; at.val.clusterDim.z = 1;
    cfg.gridDim = dim3(132); cfg.blockDim = dim3(384); cfg.dynamicSmemBytes = SM_TOTAL; cfg.attrs = &at; cfg.numAttrs = 1;
    int nc = 0;
    if (cudaOccupancyMaxActiveClusters(&nc, mega_kernel, &cfg) != cudaSuccess) { nc = 0; (void)cudaGetLastError(); }
    boff = nc >= 66 ? 0u : 4u;
  }
  Maps maps;
  make_map5(enc, &maps.m[MAP_WF], p_wf, 2048);
  make_map5(enc, &maps.m[MAP_WA], A_wqkv, 3072);
  make_map5(enc, &maps.m[MAP_WB], B_wqkv, 3072);
  make_map5(enc, &maps.m[MAP_WOA], A_wo, 1024);
  make_map5(enc, &maps.m[MAP_WOB], B_wo, 1024);
  make_map2(enc, &maps.m[MAP_X0], A_x, 1024, 2048, 64, 128);
  make_map2(enc, &maps.m[MAP_X], p_x, 1024, 2048, 64, 128);
  make_map2(enc, &maps.m[MAP_O], p_o, 1024, 2048, 64, 128);
  make_map2(enc, &maps.m[MAP_PHI], A_wphi, 32, 1024, 32, 128);
  Ctx c; c.zero = 0u; c.boff = boff; c.x0 = A_x; c.out = out;
  mega_kernel<<<132, 384, SM_TOTAL, cudaStreamPerThread>>>(maps, c, A_wqkv, B_wqkv, A_wo, B_wo);
}
```

```cpp
#include <cuda_runtime.h>
#include <cuda_bf16.h>
#include <cuda.h>
#include <stdint.h>

typedef __nv_bfloat16 bf16;

constexpr int S_ = 2048, D_ = 1024;

struct __align__(128) Flag { unsigned int v; unsigned int pad[31]; };
__device__ __align__(1024) bf16 g_x[S_ * D_];
__device__ __align__(1024) bf16 g_o[S_ * D_];
__device__ __align__(1024) uint32_t g_halo[2 * 17 * 8 * 2048];
__device__ __align__(1024) float g_kv[2 * 2 * 8 * 8448];
__device__ __align__(1024) float2 g_stats[2 * 4 * S_];
__device__ __align__(1024) float g_cs[2 * 2 * 3072];
__device__ __align__(1024) bf16 g_wf[D_ * 2048];
__device__ Flag g_kvflag[16], g_csflag[13];
__device__ __align__(128) unsigned int g_xf[16 * 32], g_of[16 * 32];
__device__ __align__(128) unsigned int g_hf[16 * 32];
__device__ __align__(128) unsigned int g_wff[8 * 32];
__device__ unsigned int g_epoch, g_err;
#define PROFT(cond, idx) asm volatile("" ::: "memory")

#define PSL 100
__device__ __forceinline__ uint32_t smem_u32(const void* p) { return (uint32_t)__cvta_generic_to_shared(p); }
__device__ __forceinline__ void mbar_init(uint32_t bar, uint32_t count) {
  asm volatile("mbarrier.init.shared::cta.b64 [%0], %1;" ::"r"(bar), "r"(count) : "memory");
}
__device__ __forceinline__ void mbar_expect_tx(uint32_t bar, uint32_t bytes) {
  asm volatile("mbarrier.arrive.expect_tx.shared::cta.b64 _, [%0], %1;" ::"r"(bar), "r"(bytes) : "memory");
}
__device__ __forceinline__ void mbar_arrive(uint32_t bar) {
  asm volatile("mbarrier.arrive.shared::cta.b64 _, [%0];" ::"r"(bar) : "memory");
}
__device__ __forceinline__ bool mbar_try_wait(uint32_t bar, uint32_t parity) {
  uint32_t ok;
  asm volatile("{\n.reg .pred p;\nmbarrier.try_wait.parity.shared::cta.b64 p, [%1], %2;\nselp.b32 %0, 1, 0, p;\n}\n"
               : "=r"(ok) : "r"(bar), "r"(parity) : "memory");
  return ok != 0;
}
__device__ __forceinline__ bool mbar_test_wait(uint32_t bar, uint32_t parity) {
  uint32_t ok;
  asm volatile("{\n.reg .pred p;\nmbarrier.test_wait.parity.shared::cta.b64 p, [%1], %2;\nselp.b32 %0, 1, 0, p;\n}\n"
               : "=r"(ok) : "r"(bar), "r"(parity) : "memory");
  return ok != 0;
}
__device__ __forceinline__ uint64_t gtimer() {
  uint64_t t; asm volatile("mov.u64 %0, %globaltimer;" : "=l"(t)); return t;
}
__device__ __forceinline__ void mbar_wait(uint32_t bar, uint32_t parity) {
  uint32_t n = 0;
#pragma unroll 1
  while (!mbar_try_wait(bar, parity)) {
    if (++n > (1u << 22)) { g_err = 1u; break; }
  }
}
__device__ __forceinline__ unsigned int ld_acquire(const unsigned int* p) {
  unsigned int v; asm volatile("ld.acquire.gpu.global.u32 %0, [%1];" : "=r"(v) : "l"(p) : "memory"); return v;
}
__device__ __forceinline__ void flag_add(unsigned int* p) {
  asm volatile("red.release.gpu.global.add.u32 [%0], 1;" ::"l"(p) : "memory");
}
__device__ __forceinline__ void flag_set(unsigned int* p, unsigned int v) {
  asm volatile("st.release.gpu.global.u32 [%0], %1;" ::"l"(p), "r"(v) : "memory");
}
template <int SLEEP>
__device__ __forceinline__ void src_wait(const unsigned int* f, unsigned int target, uint32_t need, uint32_t& ready, int lane) {
  uint32_t n = 0;
#pragma unroll 1
  while ((ready & need) != need) {
    const unsigned int v = ld_acquire(f + (lane & 15));
    ready = __ballot_sync(0xffffffffu, (int)(v - target) >= 0);
    if (SLEEP) { if ((ready & need) != need) __nanosleep(SLEEP); }
    if (++n > (1u << 20)) { g_err = 3u; break; }
  }
  __syncwarp();
}
__device__ __forceinline__ unsigned int ld_relaxed(const unsigned int* p);
__device__ __forceinline__ void src_wait_fast(const unsigned int* f, unsigned int target, uint32_t need, uint32_t& ready, int lane) {
  f += lane & 15;
  unsigned int v0 = ld_relaxed(f); __nanosleep(PSL);
  unsigned int v1 = ld_relaxed(f); __nanosleep(PSL);
  unsigned int v2 = ld_relaxed(f);
  uint32_t n = 0;
#pragma unroll 1
  while (true) {
    ready = __ballot_sync(0xffffffffu, (int)(v0 - target) >= 0);
    if ((ready & need) == need) break;
    v0 = ld_relaxed(f);
    ready = __ballot_sync(0xffffffffu, (int)(v1 - target) >= 0);
    if ((ready & need) == need) break;
    v1 = ld_relaxed(f);
    ready = __ballot_sync(0xffffffffu, (int)(v2 - target) >= 0);
    if ((ready & need) == need) break;
    v2 = ld_relaxed(f);
    if (++n > (1u << 20)) { g_err = 3u; break; }
  }
  asm volatile("fence.acquire.gpu;" ::: "memory");
  __syncwarp();
}
__device__ __forceinline__ unsigned int ld_relaxed(const unsigned int* p) {
  unsigned int v; asm volatile("ld.relaxed.gpu.global.u32 %0, [%1];" : "=r"(v) : "l"(p) : "memory"); return v;
}
__device__ __forceinline__ uint4 ld_relaxed4(const uint4* p) {
  uint4 v; asm volatile("ld.relaxed.gpu.global.v4.u32 {%0,%1,%2,%3}, [%4];" : "=r"(v.x), "=r"(v.y), "=r"(v.z), "=r"(v.w) : "l"(p) : "memory"); return v;
}
__device__ __forceinline__ void st_relaxed4(uint4* p, uint32_t a, uint32_t b, uint32_t c, uint32_t d) {
  asm volatile("st.relaxed.gpu.global.v4.u32 [%0], {%1,%2,%3,%4};" ::"l"(p), "r"(a), "r"(b), "r"(c), "r"(d) : "memory");
}
__device__ __forceinline__ void st_relaxed4_p(bool on, uint4* p, uint32_t a, uint32_t b, uint32_t c, uint32_t d) {
  asm volatile("{\n.reg .pred p;\nsetp.ne.b32 p, %5, 0;\n@p st.relaxed.gpu.global.v4.u32 [%0], {%1,%2,%3,%4};\n}\n" ::"l"(p), "r"(a), "r"(b), "r"(c), "r"(d), "r"((int)on) : "memory");
}
template <int SLEEP>
__device__ __forceinline__ void flag_wait_t(const unsigned int* p, unsigned int target) {
  uint32_t n = 0;
#pragma unroll 1
  while ((int)(ld_acquire(p) - target) < 0) {
    if (SLEEP) __nanosleep(SLEEP);
    if (++n > (1u << 20)) { g_err = 2u; break; }
  }
}
__device__ __forceinline__ void flag_wait(const unsigned int* p, unsigned int target) { flag_wait_t<0>(p, target); }
__device__ __forceinline__ void flag_wait_slow(const unsigned int* p, unsigned int target) { flag_wait_t<256>(p, target); }
__device__ __forceinline__ void tma_load_2d(uint32_t dst, const CUtensorMap* tm, int c0, int c1, uint32_t bar) {
  asm volatile("cp.async.bulk.tensor.2d.shared::cluster.global.mbarrier::complete_tx::bytes [%0], [%1, {%2, %3}], [%4];"
               ::"r"(dst), "l"(tm), "r"(c0), "r"(c1), "r"(bar) : "memory");
}
__device__ __forceinline__ void tma_load_2d_mc(uint32_t dst, const CUtensorMap* tm, int c0, int c1, uint32_t bar, uint16_t mask) {
  asm volatile("cp.async.bulk.tensor.2d.shared::cluster.global.mbarrier::complete_tx::bytes.multicast::cluster [%0], [%1, {%2, %3}], [%4], %5;"
               ::"r"(dst), "l"(tm), "r"(c0), "r"(c1), "r"(bar), "h"(mask) : "memory");
}
__device__ __forceinline__ void mbar_wait_u(uint32_t bar, uint32_t parity) {
  uint32_t n = 0;
#pragma unroll 1
  while (!__all_sync(0xffffffffu, mbar_try_wait(bar, parity))) {
    if (++n > (1u << 22)) { g_err = 1u; break; }
  }
}
__device__ __forceinline__ void expect_tx_e(uint32_t bar, uint32_t bytes) {
  asm volatile("{\n.reg .pred p;\nelect.sync _|p, 0xffffffff;\n@p mbarrier.arrive.expect_tx.shared::cta.b64 _, [%0], %1;\n}\n" ::"r"(bar), "r"(bytes) : "memory");
}
__device__ __forceinline__ void tma_2d_e(uint32_t dst, const CUtensorMap* tm, int c0, int c1, uint32_t bar) {
  asm volatile("{\n.reg .pred p;\nelect.sync _|p, 0xffffffff;\n"
               "@p cp.async.bulk.tensor.2d.shared::cluster.global.mbarrier::complete_tx::bytes [%0], [%1, {%2, %3}], [%4];\n}\n"
               ::"r"(dst), "l"(tm), "r"(c0), "r"(c1), "r"(bar) : "memory");
}
__device__ __forceinline__ void tma_2d_mc_e(uint32_t dst, const CUtensorMap* tm, int c0, int c1, uint32_t bar) {
  asm volatile("{\n.reg .pred p;\nelect.sync _|p, 0xffffffff;\n"
               "@p cp.async.bulk.tensor.2d.shared::cluster.global.mbarrier::complete_tx::bytes.multicast::cluster [%0], [%1, {%2, %3}], [%4], %5;\n}\n"
               ::"r"(dst), "l"(tm), "r"(c0), "r"(c1), "r"(bar), "h"((uint16_t)3) : "memory");
}
__device__ __forceinline__ void tma_5d(uint32_t dst, const CUtensorMap* tm, int c0, int c4, uint32_t bar) {
  asm volatile("cp.async.bulk.tensor.5d.shared::cluster.global.mbarrier::complete_tx::bytes [%0], [%1, {%2, %5, %5, %5, %3}], [%4];"
               ::"r"(dst), "l"(tm), "r"(c0), "r"(c4), "r"(bar), "r"(0) : "memory");
}
__device__ __forceinline__ void tma_5d_e(uint32_t dst, const CUtensorMap* tm, int c0, int c4, uint32_t bar) {
  asm volatile("{\n.reg .pred p;\nelect.sync _|p, 0xffffffff;\n"
               "@p cp.async.bulk.tensor.5d.shared::cluster.global.mbarrier::complete_tx::bytes [%0], [%1, {%2, %5, %5, %5, %3}], [%4];\n}\n"
               ::"r"(dst), "l"(tm), "r"(c0), "r"(c4), "r"(bar), "r"(0) : "memory");
}
__device__ __forceinline__ void tma_5d_mc_e(uint32_t dst, const CUtensorMap* tm, int c0, int c4, uint32_t bar) {
  asm volatile("{\n.reg .pred p;\nelect.sync _|p, 0xffffffff;\n"
               "@p cp.async.bulk.tensor.5d.shared::cluster.global.mbarrier::complete_tx::bytes.multicast::cluster [%0], [%1, {%2, %6, %6, %6, %3}], [%4], %5;\n}\n"
               ::"r"(dst), "l"(tm), "r"(c0), "r"(c4), "r"(bar), "h"((uint16_t)3), "r"(0) : "memory");
}
__device__ __forceinline__ void wait_tma_2d(bool w, uint32_t eb, uint32_t par, uint32_t dst, const CUtensorMap* tm, int c0, int c1, uint32_t fb) {
  asm volatile("" : "+r"(dst), "+l"(tm), "+r"(c0), "+r"(fb));
  if (w) mbar_wait_u(eb, par);
  tma_2d_e(dst, tm, c0, c1, fb);
}
__device__ __forceinline__ void wait_tma_5d_mc(bool w, uint32_t eb, uint32_t par, uint32_t dst, const CUtensorMap* tm, int c0, int c4, uint32_t fb) {
  asm volatile("" : "+r"(dst), "+l"(tm), "+r"(c0), "+r"(c4), "+r"(fb));
  if (w) mbar_wait_u(eb, par);
  tma_5d_mc_e(dst, tm, c0, c4, fb);
}
__device__ __forceinline__ void wait_tma_5d(bool w, uint32_t eb, uint32_t par, uint32_t dst, const CUtensorMap* tm, int c0, int c4, uint32_t fb) {
  asm volatile("" : "+r"(dst), "+l"(tm), "+r"(c0), "+r"(c4), "+r"(fb));
  if (w) mbar_wait_u(eb, par);
  tma_5d_e(dst, tm, c0, c4, fb);
}
__device__ __forceinline__ void st_async4(uint32_t dst, const uint32_t (&v)[4], uint32_t bar) {
  asm volatile("st.async.weak.shared::cluster.mbarrier::complete_tx::bytes.v4.b32 [%0], {%1,%2,%3,%4}, [%5];"
               ::"r"(dst), "r"(v[0]), "r"(v[1]), "r"(v[2]), "r"(v[3]), "r"(bar) : "memory");
}
__device__ __forceinline__ void mbar_wait_cl(uint32_t bar, uint32_t parity) {
  uint32_t n = 0, ok;
#pragma unroll 1
  do {
    asm volatile("{\n.reg .pred p;\nmbarrier.try_wait.parity.acquire.cluster.shared::cta.b64 p, [%1], %2;\nselp.b32 %0, 1, 0, p;\n}\n"
                 : "=r"(ok) : "r"(bar), "r"(parity) : "memory");
    if (++n > (1u << 22)) { g_err = 1u; break; }
  } while (!ok);
}
__device__ __forceinline__ void stg128(void* p, uint32_t a, uint32_t b, uint32_t c, uint32_t d) {
  asm volatile("st.global.v4.u32 [%0], {%1,%2,%3,%4};" ::"l"(p), "r"(a), "r"(b), "r"(c), "r"(d) : "memory");
}
__device__ __forceinline__ void stg128_p(bool on, void* p, uint32_t a, uint32_t b, uint32_t c, uint32_t d) {
  asm volatile("{\n.reg .pred p;\nsetp.ne.b32 p, %5, 0;\n@p st.global.v4.u32 [%0], {%1,%2,%3,%4};\n}\n" ::"l"(p), "r"(a), "r"(b), "r"(c), "r"(d), "r"((int)on) : "memory");
}
__device__ __forceinline__ void ldg128(const void* p, uint32_t& a, uint32_t& b, uint32_t& c, uint32_t& d) {
  asm volatile("ld.global.cg.v4.u32 {%0,%1,%2,%3}, [%4];" : "=r"(a), "=r"(b), "=r"(c), "=r"(d) : "l"(p) : "memory");
}
__device__ __forceinline__ uint32_t ldg32(const void* p) {
  uint32_t v; asm volatile("ld.global.nc.u32 %0, [%1];" : "=r"(v) : "l"(p) : "memory"); return v;
}
__device__ __forceinline__ void tma_pf_e(const CUtensorMap* tm, int c0, int c1) {
  asm volatile("{\n.reg .pred p;\nelect.sync _|p, 0xffffffff;\n"
               "@p cp.async.bulk.prefetch.tensor.2d.L2.global.tile [%0, {%1, %2}];\n}\n" ::"l"(tm), "r"(c0), "r"(c1) : "memory");
}
__device__ __forceinline__ void tma_2d_to_e(uint32_t dst, const CUtensorMap* tm, int c0, int c1, uint32_t bar, uint32_t mask) {
  asm volatile("{\n.reg .pred p;\nelect.sync _|p, 0xffffffff;\n"
               "@p cp.async.bulk.tensor.2d.shared::cluster.global.mbarrier::complete_tx::bytes.multicast::cluster [%0], [%1, {%2, %3}], [%4], %5;\n}\n"
               ::"r"(dst), "l"(tm), "r"(c0), "r"(c1), "r"(bar), "h"((uint16_t)mask) : "memory");
}
__device__ __forceinline__ void tma_3d_mc_e(uint32_t dst, const CUtensorMap* tm, int c1, int c2, uint32_t bar) {
  asm volatile("{\n.reg .pred p;\nelect.sync _|p, 0xffffffff;\n"
               "@p cp.async.bulk.tensor.3d.shared::cluster.global.mbarrier::complete_tx::bytes.multicast::cluster [%0], [%1, {%6, %2, %3}], [%4], %5;\n}\n"
               ::"r"(dst), "l"(tm), "r"(c1), "r"(c2), "r"(bar), "h"((uint16_t)3), "r"(0) : "memory");
}
__device__ __forceinline__ uint32_t poll_flags(const unsigned int* f, unsigned int target, int lane) {
  const unsigned int v = ld_acquire(f + (lane & 15));
  const uint32_t r = __ballot_sync(0xffffffffu, (int)(v - target) >= 0);
  __syncwarp();
  return r;
}
__device__ __forceinline__ void mbar_arrive_cluster(uint32_t local_bar, uint32_t rank) {
  asm volatile("{\n.reg .b32 ra;\nmapa.shared::cluster.u32 ra, %0, %1;\nmbarrier.arrive.shared::cluster.b64 _, [ra];\n}\n"
               ::"r"(local_bar), "r"(rank) : "memory");
}
__device__ __forceinline__ void release2(uint32_t bar) { mbar_arrive_cluster(bar, 0); mbar_arrive_cluster(bar, 1); }
__device__ __forceinline__ void release2c(uint32_t off) {
  asm volatile("mbarrier.arrive.shared::cluster.b64 _, [%0];\nmbarrier.arrive.shared::cluster.b64 _, [%1];" ::"r"(off), "r"(off + (1u << 24)) : "memory");
}
__device__ __forceinline__ void tma_store_2d(const CUtensorMap* tm, uint32_t src, int c0, int c1) {
  asm volatile("cp.async.bulk.tensor.2d.global.shared::cta.bulk_group [%0, {%2, %3}], [%1];"
               ::"l"(tm), "r"(src), "r"(c0), "r"(c1) : "memory");
}
__device__ __forceinline__ void tma_store_5d(const CUtensorMap* tm, uint32_t src, int c0, int c4) {
  asm volatile("cp.async.bulk.tensor.5d.global.shared::cta.bulk_group [%0, {%2, %4, %4, %4, %3}], [%1];"
               ::"l"(tm), "r"(src), "r"(c0), "r"(c4), "r"(0) : "memory");
}
__device__ __forceinline__ void bulk_store(void* dst, uint32_t src, uint32_t bytes) {
  asm volatile("cp.async.bulk.global.shared::cta.bulk_group [%0], [%1], %2;" ::"l"(dst), "r"(src), "r"(bytes) : "memory");
}
__device__ __forceinline__ void bulk_load(uint32_t dst, const void* src, uint32_t bytes, uint32_t bar) {
  asm volatile("cp.async.bulk.shared::cluster.global.mbarrier::complete_tx::bytes [%0], [%1], %2, [%3];" ::"r"(dst), "l"(src), "r"(bytes), "r"(bar) : "memory");
}
__device__ __forceinline__ void bulk_red_add(void* dst, uint32_t src, uint32_t bytes) {
  asm volatile("cp.reduce.async.bulk.global.shared::cta.bulk_group.add.f32 [%0], [%1], %2;" ::"l"(dst), "r"(src), "r"(bytes) : "memory");
}
__device__ __forceinline__ void bulk_commit() { asm volatile("cp.async.bulk.commit_group;" ::: "memory"); }
__device__ __forceinline__ void bulk_wait0() { asm volatile("cp.async.bulk.wait_group 0;" ::: "memory"); }
__device__ __forceinline__ void fence_async_smem() { asm volatile("fence.proxy.async.shared::cta;" ::: "memory"); }
__device__ __forceinline__ void fence_async_all() { asm volatile("fence.proxy.async.global;" ::: "memory"); }
__device__ __forceinline__ void wgmma_fence() { asm volatile("wgmma.fence.sync.aligned;" ::: "memory"); }
__device__ __forceinline__ void wgmma_commit() { asm volatile("wgmma.commit_group.sync.aligned;" ::: "memory"); }
template <int N> __device__ __forceinline__ void wgmma_wait() { asm volatile("wgmma.wait_group.sync.aligned %0;" ::"n"(N) : "memory"); }
__device__ __forceinline__ void cluster_arrive() { asm volatile("barrier.cluster.arrive.release.aligned;" ::: "memory"); }
__device__ __forceinline__ void cluster_wait() { asm volatile("barrier.cluster.wait.acquire.aligned;" ::: "memory"); }
template <int ID, int N> __device__ __forceinline__ void nbar() { asm volatile("bar.sync %0, %1;" ::"n"(ID), "n"(N) : "memory"); }
__device__ __forceinline__ uint64_t make_desc(uint32_t addr, uint32_t lbo_bytes, uint32_t sbo_bytes) {
  uint64_t d = 0;
  d |= (uint64_t)((addr & 0x3FFFF) >> 4);
  d |= (uint64_t)((lbo_bytes >> 4) & 0x3FFF) << 16;
  d |= (uint64_t)((sbo_bytes >> 4) & 0x3FFF) << 32;
  d |= (uint64_t)1 << 62;
  return d;
}
__device__ __forceinline__ uint64_t desc64(uint32_t lo, uint32_t hi) { return (uint64_t)lo | ((uint64_t)hi << 32); }
__device__ __forceinline__ uint32_t pack_bf16(float lo, float hi) {
  uint32_t r; asm("cvt.rn.bf16x2.f32 %0, %1, %2;" : "=r"(r) : "f"(hi), "f"(lo)); return r;
}
__device__ __forceinline__ uint32_t add_bf16x2(uint32_t a, uint32_t b) {
  uint32_t r; asm("add.rn.bf16x2 %0, %1, %2;" : "=r"(r) : "r"(a), "r"(b)); return r;
}
__device__ __forceinline__ float bf16r(float x) { return __bfloat162float(__float2bfloat16_rn(x)); }
__device__ __forceinline__ float bf_lo(uint32_t u) { return __uint_as_float(u << 16); }
__device__ __forceinline__ float bf_hi(uint32_t u) { return __uint_as_float(u & 0xFFFF0000u); }
__device__ __forceinline__ float ex2(float x) { float r; asm("ex2.approx.ftz.f32 %0, %1;" : "=f"(r) : "f"(x)); return r; }
__device__ __forceinline__ float ex2v(float x) { float r; asm volatile("ex2.approx.ftz.f32 %0, %1;" : "=f"(r) : "f"(x) : "memory"); return r; }
__device__ __forceinline__ float rcp(float x) { float r; asm("rcp.approx.ftz.f32 %0, %1;" : "=f"(r) : "f"(x)); return r; }
__device__ __forceinline__ void mma_bf16(float (&d)[4], uint32_t a0, uint32_t a1, uint32_t a2, uint32_t a3, uint32_t b0, uint32_t b1) {
  asm("mma.sync.aligned.m16n8k16.row.col.f32.bf16.bf16.f32 {%0,%1,%2,%3}, {%4,%5,%6,%7}, {%8,%9}, {%0,%1,%2,%3};"
               : "+f"(d[0]), "+f"(d[1]), "+f"(d[2]), "+f"(d[3]) : "r"(a0), "r"(a1), "r"(a2), "r"(a3), "r"(b0), "r"(b1));
}
__device__ __forceinline__ void ldsm_x4(uint32_t& r0, uint32_t& r1, uint32_t& r2, uint32_t& r3, uint32_t addr) {
  asm volatile("ldmatrix.sync.aligned.m8n8.x4.shared.b16 {%0,%1,%2,%3}, [%4];"
               : "=r"(r0), "=r"(r1), "=r"(r2), "=r"(r3) : "r"(addr) : "memory");
}
__device__ __forceinline__ void ldsm_x4_t(uint32_t& r0, uint32_t& r1, uint32_t& r2, uint32_t& r3, uint32_t addr) {
  asm volatile("ldmatrix.sync.aligned.m8n8.x4.trans.shared.b16 {%0,%1,%2,%3}, [%4];"
               : "=r"(r0), "=r"(r1), "=r"(r2), "=r"(r3) : "r"(addr) : "memory");
}
__device__ __forceinline__ void ldsm_x2_t(uint32_t& r0, uint32_t& r1, uint32_t addr) {
  asm volatile("ldmatrix.sync.aligned.m8n8.x2.trans.shared.b16 {%0,%1}, [%2];"
               : "=r"(r0), "=r"(r1) : "r"(addr) : "memory");
}
__device__ __forceinline__ void stsm_x4(uint32_t addr, uint32_t r0, uint32_t r1, uint32_t r2, uint32_t r3) {
  asm volatile("stmatrix.sync.aligned.m8n8.x4.shared.b16 [%0], {%1,%2,%3,%4};"
               ::"r"(addr), "r"(r0), "r"(r1), "r"(r2), "r"(r3) : "memory");
}
__device__ __forceinline__ void stsm_x4_p(bool on, uint32_t addr, uint32_t r0, uint32_t r1, uint32_t r2, uint32_t r3) {
  asm volatile("{\n.reg .pred p;\nsetp.ne.b32 p, %5, 0;\n@p stmatrix.sync.aligned.m8n8.x4.shared.b16 [%0], {%1,%2,%3,%4};\n}\n"
               ::"r"(addr), "r"(r0), "r"(r1), "r"(r2), "r"(r3), "r"((int)on) : "memory");
}
__device__ __forceinline__ float2 lds_f2(uint32_t addr) {
  float2 v; asm volatile("ld.shared.v2.f32 {%0,%1}, [%2];" : "=f"(v.x), "=f"(v.y) : "r"(addr) : "memory"); return v;
}
__device__ __forceinline__ uint4 lds128(uint32_t addr) {
  uint4 v; asm volatile("ld.shared.v4.b32 {%0,%1,%2,%3}, [%4];" : "=r"(v.x), "=r"(v.y), "=r"(v.z), "=r"(v.w) : "r"(addr) : "memory"); return v;
}
__device__ __forceinline__ void sts128(uint32_t addr, uint4 v) {
  asm volatile("st.shared.v4.b32 [%0], {%1,%2,%3,%4};" ::"r"(addr), "r"(v.x), "r"(v.y), "r"(v.z), "r"(v.w) : "memory");
}
__device__ __forceinline__ float lds_f(uint32_t addr) {
  float v; asm volatile("ld.shared.f32 %0, [%1];" : "=f"(v) : "r"(addr) : "memory"); return v;
}
__device__ __forceinline__ void sts16(uint32_t addr, uint32_t v) {
  asm volatile("st.shared.u16 [%0], %1;" ::"r"(addr), "h"((unsigned short)v) : "memory");
}
__device__ __forceinline__ void nbar_dyn(int id, int n) { asm volatile("bar.sync %0, %1;" ::"r"(id), "r"(n) : "memory"); }
__device__ __forceinline__ uint64_t make_desc_ns(uint32_t addr, uint32_t lbo_bytes, uint32_t sbo_bytes) {
  return (uint64_t)((addr & 0x3FFFF) >> 4) | ((uint64_t)(lbo_bytes >> 4) << 16) | ((uint64_t)(sbo_bytes >> 4) << 32);
}
__device__ __forceinline__ void sts_f(uint32_t addr, float v) { asm volatile("st.shared.f32 [%0], %1;" ::"r"(addr), "f"(v) : "memory"); }
__device__ __forceinline__ void sts64(uint32_t addr, uint32_t a, uint32_t b) {
  asm volatile("st.shared.v2.b32 [%0], {%1,%2};" ::"r"(addr), "r"(a), "r"(b) : "memory");
}
__device__ __forceinline__ void sts_f2(uint32_t addr, float a, float b) {
  asm volatile("st.shared.v2.f32 [%0], {%1,%2};" ::"r"(addr), "f"(a), "f"(b) : "memory");
}
__device__ __forceinline__ void red_add2(float* p, float a, float b) {
  asm volatile("red.global.add.v2.f32 [%0], {%1,%2};" ::"l"(p), "f"(a), "f"(b) : "memory");
}
__device__ __forceinline__ void red_add2_p(bool on, float* p, float a, float b) {
  asm volatile("{\n.reg .pred p;\nsetp.ne.b32 p, %3, 0;\n@p red.global.add.v2.f32 [%0], {%1,%2};\n}\n" ::"l"(p), "f"(a), "f"(b), "r"((int)on) : "memory");
}
__device__ __forceinline__ void red_add4(float* p, float a, float b, float c, float d) {
  asm volatile("red.global.add.v4.f32 [%0], {%1,%2,%3,%4};" ::"l"(p), "f"(a), "f"(b), "f"(c), "f"(d) : "memory");
}
__device__ __forceinline__ void red_add1(float* p, float a) {
  asm volatile("red.global.add.f32 [%0], %1;" ::"l"(p), "f"(a) : "memory");
}
__device__ __forceinline__ void l2_prefetch(const void* p, uint32_t bytes) {
  asm volatile("cp.async.bulk.prefetch.L2.global [%0], %1;" ::"l"(p), "r"(bytes) : "memory");
}

__device__ __forceinline__ void wgmma_n256(float (&d)[192], uint64_t da, uint64_t db, int scale_d) {
  asm volatile("{\n.reg .pred p;\nsetp.ne.b32 p, %130, 0;\n"
    "wgmma.mma_async.sync.aligned.m64n256k16.f32.bf16.bf16 {%0, %1, %2, %3, %4, %5, %6, %7, %8, %9, %10, %11, %12, %13, %14, %15, %16, %17, %18, %19, %20, %21, %22, %23, %24, %25, %26, %27, %28, %29, %30, %31, %32, %33, %34, %35, %36, %37, %38, %39, %40, %41, %42, %43, %44, %45, %46, %47, %48, %49, %50, %51, %52, %53, %54, %55, %56, %57, %58, %59, %60, %61, %62, %63, %64, %65, %66, %67, %68, %69, %70, %71, %72, %73, %74, %75, %76, %77, %78, %79, %80, %81, %82, %83, %84, %85, %86, %87, %88, %89, %90, %91, %92, %93, %94, %95, %96, %97, %98, %99, %100, %101, %102, %103, %104, %105, %106, %107, %108, %109, %110, %111, %112, %113, %114, %115, %116, %117, %118, %119, %120, %121, %122, %123, %124, %125, %126, %127}, %128, %129, p, 1, 1, 0, 1;\n}\n"
    : "+f"(d[0]), "+f"(d[1]), "+f"(d[2]), "+f"(d[3]), "+f"(d[4]), "+f"(d[5]), "+f"(d[6]), "+f"(d[7]), "+f"(d[8]), "+f"(d[9]), "+f"(d[10]), "+f"(d[11]), "+f"(d[12]), "+f"(d[13]), "+f"(d[14]), "+f"(d[15]), "+f"(d[16]), "+f"(d[17]), "+f"(d[18]), "+f"(d[19]), "+f"(d[20]), "+f"(d[21]), "+f"(d[22]), "+f"(d[23]), "+f"(d[24]), "+f"(d[25]), "+f"(d[26]), "+f"(d[27]), "+f"(d[28]), "+f"(d[29]), "+f"(d[30]), "+f"(d[31]), "+f"(d[32]), "+f"(d[33]), "+f"(d[34]), "+f"(d[35]), "+f"(d[36]), "+f"(d[37]), "+f"(d[38]), "+f"(d[39]), "+f"(d[40]), "+f"(d[41]), "+f"(d[42]), "+f"(d[43]), "+f"(d[44]), "+f"(d[45]), "+f"(d[46]), "+f"(d[47]), "+f"(d[48]), "+f"(d[49]), "+f"(d[50]), "+f"(d[51]), "+f"(d[52]), "+f"(d[53]), "+f"(d[54]), "+f"(d[55]), "+f"(d[56]), "+f"(d[57]), "+f"(d[58]), "+f"(d[59]), "+f"(d[60]), "+f"(d[61]), "+f"(d[62]), "+f"(d[63]), "+f"(d[64]), "+f"(d[65]), "+f"(d[66]), "+f"(d[67]), "+f"(d[68]), "+f"(d[69]), "+f"(d[70]), "+f"(d[71]), "+f"(d[72]), "+f"(d[73]), "+f"(d[74]), "+f"(d[75]), "+f"(d[76]), "+f"(d[77]), "+f"(d[78]), "+f"(d[79]), "+f"(d[80]), "+f"(d[81]), "+f"(d[82]), "+f"(d[83]), "+f"(d[84]), "+f"(d[85]), "+f"(d[86]), "+f"(d[87]), "+f"(d[88]), "+f"(d[89]), "+f"(d[90]), "+f"(d[91]), "+f"(d[92]), "+f"(d[93]), "+f"(d[94]), "+f"(d[95]), "+f"(d[96]), "+f"(d[97]), "+f"(d[98]), "+f"(d[99]), "+f"(d[100]), "+f"(d[101]), "+f"(d[102]), "+f"(d[103]), "+f"(d[104]), "+f"(d[105]), "+f"(d[106]), "+f"(d[107]), "+f"(d[108]), "+f"(d[109]), "+f"(d[110]), "+f"(d[111]), "+f"(d[112]), "+f"(d[113]), "+f"(d[114]), "+f"(d[115]), "+f"(d[116]), "+f"(d[117]), "+f"(d[118]), "+f"(d[119]), "+f"(d[120]), "+f"(d[121]), "+f"(d[122]), "+f"(d[123]), "+f"(d[124]), "+f"(d[125]), "+f"(d[126]), "+f"(d[127])
    : "l"(da), "l"(db), "r"(scale_d));
}
__device__ __forceinline__ void wgmma_n128(float (&d)[192], uint64_t da, uint64_t db, int scale_d) {
  asm volatile("{\n.reg .pred p;\nsetp.ne.b32 p, %66, 0;\n"
    "wgmma.mma_async.sync.aligned.m64n128k16.f32.bf16.bf16 {%0, %1, %2, %3, %4, %5, %6, %7, %8, %9, %10, %11, %12, %13, %14, %15, %16, %17, %18, %19, %20, %21, %22, %23, %24, %25, %26, %27, %28, %29, %30, %31, %32, %33, %34, %35, %36, %37, %38, %39, %40, %41, %42, %43, %44, %45, %46, %47, %48, %49, %50, %51, %52, %53, %54, %55, %56, %57, %58, %59, %60, %61, %62, %63}, %64, %65, p, 1, 1, 0, 1;\n}\n"
    : "+f"(d[128]), "+f"(d[129]), "+f"(d[130]), "+f"(d[131]), "+f"(d[132]), "+f"(d[133]), "+f"(d[134]), "+f"(d[135]), "+f"(d[136]), "+f"(d[137]), "+f"(d[138]), "+f"(d[139]), "+f"(d[140]), "+f"(d[141]), "+f"(d[142]), "+f"(d[143]), "+f"(d[144]), "+f"(d[145]), "+f"(d[146]), "+f"(d[147]), "+f"(d[148]), "+f"(d[149]), "+f"(d[150]), "+f"(d[151]), "+f"(d[152]), "+f"(d[153]), "+f"(d[154]), "+f"(d[155]), "+f"(d[156]), "+f"(d[157]), "+f"(d[158]), "+f"(d[159]), "+f"(d[160]), "+f"(d[161]), "+f"(d[162]), "+f"(d[163]), "+f"(d[164]), "+f"(d[165]), "+f"(d[166]), "+f"(d[167]), "+f"(d[168]), "+f"(d[169]), "+f"(d[170]), "+f"(d[171]), "+f"(d[172]), "+f"(d[173]), "+f"(d[174]), "+f"(d[175]), "+f"(d[176]), "+f"(d[177]), "+f"(d[178]), "+f"(d[179]), "+f"(d[180]), "+f"(d[181]), "+f"(d[182]), "+f"(d[183]), "+f"(d[184]), "+f"(d[185]), "+f"(d[186]), "+f"(d[187]), "+f"(d[188]), "+f"(d[189]), "+f"(d[190]), "+f"(d[191])
    : "l"(da), "l"(db), "r"(scale_d));
}
__device__ __forceinline__ void wgmma_n256_k(float (&d)[192], uint64_t da, uint64_t db, int scale_d) {
  asm volatile("{\n.reg .pred p;\nsetp.ne.b32 p, %130, 0;\n"
    "wgmma.mma_async.sync.aligned.m64n256k16.f32.bf16.bf16 {%0, %1, %2, %3, %4, %5, %6, %7, %8, %9, %10, %11, %12, %13, %14, %15, %16, %17, %18, %19, %20, %21, %22, %23, %24, %25, %26, %27, %28, %29, %30, %31, %32, %33, %34, %35, %36, %37, %38, %39, %40, %41, %42, %43, %44, %45, %46, %47, %48, %49, %50, %51, %52, %53, %54, %55, %56, %57, %58, %59, %60, %61, %62, %63, %64, %65, %66, %67, %68, %69, %70, %71, %72, %73, %74, %75, %76, %77, %78, %79, %80, %81, %82, %83, %84, %85, %86, %87, %88, %89, %90, %91, %92, %93, %94, %95, %96, %97, %98, %99, %100, %101, %102, %103, %104, %105, %106, %107, %108, %109, %110, %111, %112, %113, %114, %115, %116, %117, %118, %119, %120, %121, %122, %123, %124, %125, %126, %127}, %128, %129, p, 1, 1, 0, 0;\n}\n"
    : "+f"(d[0]), "+f"(d[1]), "+f"(d[2]), "+f"(d[3]), "+f"(d[4]), "+f"(d[5]), "+f"(d[6]), "+f"(d[7]), "+f"(d[8]), "+f"(d[9]), "+f"(d[10]), "+f"(d[11]), "+f"(d[12]), "+f"(d[13]), "+f"(d[14]), "+f"(d[15]), "+f"(d[16]), "+f"(d[17]), "+f"(d[18]), "+f"(d[19]), "+f"(d[20]), "+f"(d[21]), "+f"(d[22]), "+f"(d[23]), "+f"(d[24]), "+f"(d[25]), "+f"(d[26]), "+f"(d[27]), "+f"(d[28]), "+f"(d[29]), "+f"(d[30]), "+f"(d[31]), "+f"(d[32]), "+f"(d[33]), "+f"(d[34]), "+f"(d[35]), "+f"(d[36]), "+f"(d[37]), "+f"(d[38]), "+f"(d[39]), "+f"(d[40]), "+f"(d[41]), "+f"(d[42]), "+f"(d[43]), "+f"(d[44]), "+f"(d[45]), "+f"(d[46]), "+f"(d[47]), "+f"(d[48]), "+f"(d[49]), "+f"(d[50]), "+f"(d[51]), "+f"(d[52]), "+f"(d[53]), "+f"(d[54]), "+f"(d[55]), "+f"(d[56]), "+f"(d[57]), "+f"(d[58]), "+f"(d[59]), "+f"(d[60]), "+f"(d[61]), "+f"(d[62]), "+f"(d[63]), "+f"(d[64]), "+f"(d[65]), "+f"(d[66]), "+f"(d[67]), "+f"(d[68]), "+f"(d[69]), "+f"(d[70]), "+f"(d[71]), "+f"(d[72]), "+f"(d[73]), "+f"(d[74]), "+f"(d[75]), "+f"(d[76]), "+f"(d[77]), "+f"(d[78]), "+f"(d[79]), "+f"(d[80]), "+f"(d[81]), "+f"(d[82]), "+f"(d[83]), "+f"(d[84]), "+f"(d[85]), "+f"(d[86]), "+f"(d[87]), "+f"(d[88]), "+f"(d[89]), "+f"(d[90]), "+f"(d[91]), "+f"(d[92]), "+f"(d[93]), "+f"(d[94]), "+f"(d[95]), "+f"(d[96]), "+f"(d[97]), "+f"(d[98]), "+f"(d[99]), "+f"(d[100]), "+f"(d[101]), "+f"(d[102]), "+f"(d[103]), "+f"(d[104]), "+f"(d[105]), "+f"(d[106]), "+f"(d[107]), "+f"(d[108]), "+f"(d[109]), "+f"(d[110]), "+f"(d[111]), "+f"(d[112]), "+f"(d[113]), "+f"(d[114]), "+f"(d[115]), "+f"(d[116]), "+f"(d[117]), "+f"(d[118]), "+f"(d[119]), "+f"(d[120]), "+f"(d[121]), "+f"(d[122]), "+f"(d[123]), "+f"(d[124]), "+f"(d[125]), "+f"(d[126]), "+f"(d[127])
    : "l"(da), "l"(db), "r"(scale_d));
}
__device__ __forceinline__ void wgmma_n128_k(float (&d)[192], uint64_t da, uint64_t db, int scale_d) {
  asm volatile("{\n.reg .pred p;\nsetp.ne.b32 p, %66, 0;\n"
    "wgmma.mma_async.sync.aligned.m64n128k16.f32.bf16.bf16 {%0, %1, %2, %3, %4, %5, %6, %7, %8, %9, %10, %11, %12, %13, %14, %15, %16, %17, %18, %19, %20, %21, %22, %23, %24, %25, %26, %27, %28, %29, %30, %31, %32, %33, %34, %35, %36, %37, %38, %39, %40, %41, %42, %43, %44, %45, %46, %47, %48, %49, %50, %51, %52, %53, %54, %55, %56, %57, %58, %59, %60, %61, %62, %63}, %64, %65, p, 1, 1, 0, 0;\n}\n"
    : "+f"(d[128]), "+f"(d[129]), "+f"(d[130]), "+f"(d[131]), "+f"(d[132]), "+f"(d[133]), "+f"(d[134]), "+f"(d[135]), "+f"(d[136]), "+f"(d[137]), "+f"(d[138]), "+f"(d[139]), "+f"(d[140]), "+f"(d[141]), "+f"(d[142]), "+f"(d[143]), "+f"(d[144]), "+f"(d[145]), "+f"(d[146]), "+f"(d[147]), "+f"(d[148]), "+f"(d[149]), "+f"(d[150]), "+f"(d[151]), "+f"(d[152]), "+f"(d[153]), "+f"(d[154]), "+f"(d[155]), "+f"(d[156]), "+f"(d[157]), "+f"(d[158]), "+f"(d[159]), "+f"(d[160]), "+f"(d[161]), "+f"(d[162]), "+f"(d[163]), "+f"(d[164]), "+f"(d[165]), "+f"(d[166]), "+f"(d[167]), "+f"(d[168]), "+f"(d[169]), "+f"(d[170]), "+f"(d[171]), "+f"(d[172]), "+f"(d[173]), "+f"(d[174]), "+f"(d[175]), "+f"(d[176]), "+f"(d[177]), "+f"(d[178]), "+f"(d[179]), "+f"(d[180]), "+f"(d[181]), "+f"(d[182]), "+f"(d[183]), "+f"(d[184]), "+f"(d[185]), "+f"(d[186]), "+f"(d[187]), "+f"(d[188]), "+f"(d[189]), "+f"(d[190]), "+f"(d[191])
    : "l"(da), "l"(db), "r"(scale_d));
}
__device__ __forceinline__ void wgmma_n40_tt(float (&d)[20], uint64_t da, uint64_t db, int scale_d) {
  asm volatile("{\n.reg .pred p;\nsetp.ne.b32 p, %22, 0;\n"
    "wgmma.mma_async.sync.aligned.m64n40k16.f32.bf16.bf16 {%0, %1, %2, %3, %4, %5, %6, %7, %8, %9, %10, %11, %12, %13, %14, %15, %16, %17, %18, %19}, %20, %21, p, 1, 1, 1, 1;\n}\n"
    : "+f"(d[0]), "+f"(d[1]), "+f"(d[2]), "+f"(d[3]), "+f"(d[4]), "+f"(d[5]), "+f"(d[6]), "+f"(d[7]), "+f"(d[8]), "+f"(d[9]), "+f"(d[10]), "+f"(d[11]), "+f"(d[12]), "+f"(d[13]), "+f"(d[14]), "+f"(d[15]), "+f"(d[16]), "+f"(d[17]), "+f"(d[18]), "+f"(d[19])
    : "l"(da), "l"(db), "r"(scale_d));
}
__device__ __forceinline__ void wgmma_n40_rs(float (&d)[20], const uint32_t (&a)[4], uint64_t db, int scale_d) {
  asm volatile("{\n.reg .pred p;\nsetp.ne.b32 p, %25, 0;\n"
    "wgmma.mma_async.sync.aligned.m64n40k16.f32.bf16.bf16 {%0, %1, %2, %3, %4, %5, %6, %7, %8, %9, %10, %11, %12, %13, %14, %15, %16, %17, %18, %19}, {%20, %21, %22, %23}, %24, p, 1, 1, 1;\n}\n"
    : "+f"(d[0]), "+f"(d[1]), "+f"(d[2]), "+f"(d[3]), "+f"(d[4]), "+f"(d[5]), "+f"(d[6]), "+f"(d[7]), "+f"(d[8]), "+f"(d[9]), "+f"(d[10]), "+f"(d[11]), "+f"(d[12]), "+f"(d[13]), "+f"(d[14]), "+f"(d[15]), "+f"(d[16]), "+f"(d[17]), "+f"(d[18]), "+f"(d[19])
    : "r"(a[0]), "r"(a[1]), "r"(a[2]), "r"(a[3]), "l"(db), "r"(scale_d));
}
__device__ __forceinline__ void wgmma_n256_0(float (&d)[192], uint64_t da, uint64_t db) {
  asm volatile("{\n.reg .pred p;\nsetp.ne.b32 p, 0, 0;\n"
    "wgmma.mma_async.sync.aligned.m64n256k16.f32.bf16.bf16 {%0, %1, %2, %3, %4, %5, %6, %7, %8, %9, %10, %11, %12, %13, %14, %15, %16, %17, %18, %19, %20, %21, %22, %23, %24, %25, %26, %27, %28, %29, %30, %31, %32, %33, %34, %35, %36, %37, %38, %39, %40, %41, %42, %43, %44, %45, %46, %47, %48, %49, %50, %51, %52, %53, %54, %55, %56, %57, %58, %59, %60, %61, %62, %63, %64, %65, %66, %67, %68, %69, %70, %71, %72, %73, %74, %75, %76, %77, %78, %79, %80, %81, %82, %83, %84, %85, %86, %87, %88, %89, %90, %91, %92, %93, %94, %95, %96, %97, %98, %99, %100, %101, %102, %103, %104, %105, %106, %107, %108, %109, %110, %111, %112, %113, %114, %115, %116, %117, %118, %119, %120, %121, %122, %123, %124, %125, %126, %127}, %128, %129, p, 1, 1, 0, 1;\n}\n"
    : "=f"(d[0]), "=f"(d[1]), "=f"(d[2]), "=f"(d[3]), "=f"(d[4]), "=f"(d[5]), "=f"(d[6]), "=f"(d[7]), "=f"(d[8]), "=f"(d[9]), "=f"(d[10]), "=f"(d[11]), "=f"(d[12]), "=f"(d[13]), "=f"(d[14]), "=f"(d[15]), "=f"(d[16]), "=f"(d[17]), "=f"(d[18]), "=f"(d[19]), "=f"(d[20]), "=f"(d[21]), "=f"(d[22]), "=f"(d[23]), "=f"(d[24]), "=f"(d[25]), "=f"(d[26]), "=f"(d[27]), "=f"(d[28]), "=f"(d[29]), "=f"(d[30]), "=f"(d[31]), "=f"(d[32]), "=f"(d[33]), "=f"(d[34]), "=f"(d[35]), "=f"(d[36]), "=f"(d[37]), "=f"(d[38]), "=f"(d[39]), "=f"(d[40]), "=f"(d[41]), "=f"(d[42]), "=f"(d[43]), "=f"(d[44]), "=f"(d[45]), "=f"(d[46]), "=f"(d[47]), "=f"(d[48]), "=f"(d[49]), "=f"(d[50]), "=f"(d[51]), "=f"(d[52]), "=f"(d[53]), "=f"(d[54]), "=f"(d[55]), "=f"(d[56]), "=f"(d[57]), "=f"(d[58]), "=f"(d[59]), "=f"(d[60]), "=f"(d[61]), "=f"(d[62]), "=f"(d[63]), "=f"(d[64]), "=f"(d[65]), "=f"(d[66]), "=f"(d[67]), "=f"(d[68]), "=f"(d[69]), "=f"(d[70]), "=f"(d[71]), "=f"(d[72]), "=f"(d[73]), "=f"(d[74]), "=f"(d[75]), "=f"(d[76]), "=f"(d[77]), "=f"(d[78]), "=f"(d[79]), "=f"(d[80]), "=f"(d[81]), "=f"(d[82]), "=f"(d[83]), "=f"(d[84]), "=f"(d[85]), "=f"(d[86]), "=f"(d[87]), "=f"(d[88]), "=f"(d[89]), "=f"(d[90]), "=f"(d[91]), "=f"(d[92]), "=f"(d[93]), "=f"(d[94]), "=f"(d[95]), "=f"(d[96]), "=f"(d[97]), "=f"(d[98]), "=f"(d[99]), "=f"(d[100]), "=f"(d[101]), "=f"(d[102]), "=f"(d[103]), "=f"(d[104]), "=f"(d[105]), "=f"(d[106]), "=f"(d[107]), "=f"(d[108]), "=f"(d[109]), "=f"(d[110]), "=f"(d[111]), "=f"(d[112]), "=f"(d[113]), "=f"(d[114]), "=f"(d[115]), "=f"(d[116]), "=f"(d[117]), "=f"(d[118]), "=f"(d[119]), "=f"(d[120]), "=f"(d[121]), "=f"(d[122]), "=f"(d[123]), "=f"(d[124]), "=f"(d[125]), "=f"(d[126]), "=f"(d[127])
    : "l"(da), "l"(db));
}
__device__ __forceinline__ void wgmma_n128_0(float (&d)[192], uint64_t da, uint64_t db) {
  asm volatile("{\n.reg .pred p;\nsetp.ne.b32 p, 0, 0;\n"
    "wgmma.mma_async.sync.aligned.m64n128k16.f32.bf16.bf16 {%0, %1, %2, %3, %4, %5, %6, %7, %8, %9, %10, %11, %12, %13, %14, %15, %16, %17, %18, %19, %20, %21, %22, %23, %24, %25, %26, %27, %28, %29, %30, %31, %32, %33, %34, %35, %36, %37, %38, %39, %40, %41, %42, %43, %44, %45, %46, %47, %48, %49, %50, %51, %52, %53, %54, %55, %56, %57, %58, %59, %60, %61, %62, %63}, %64, %65, p, 1, 1, 0, 1;\n}\n"
    : "=f"(d[128]), "=f"(d[129]), "=f"(d[130]), "=f"(d[131]), "=f"(d[132]), "=f"(d[133]), "=f"(d[134]), "=f"(d[135]), "=f"(d[136]), "=f"(d[137]), "=f"(d[138]), "=f"(d[139]), "=f"(d[140]), "=f"(d[141]), "=f"(d[142]), "=f"(d[143]), "=f"(d[144]), "=f"(d[145]), "=f"(d[146]), "=f"(d[147]), "=f"(d[148]), "=f"(d[149]), "=f"(d[150]), "=f"(d[151]), "=f"(d[152]), "=f"(d[153]), "=f"(d[154]), "=f"(d[155]), "=f"(d[156]), "=f"(d[157]), "=f"(d[158]), "=f"(d[159]), "=f"(d[160]), "=f"(d[161]), "=f"(d[162]), "=f"(d[163]), "=f"(d[164]), "=f"(d[165]), "=f"(d[166]), "=f"(d[167]), "=f"(d[168]), "=f"(d[169]), "=f"(d[170]), "=f"(d[171]), "=f"(d[172]), "=f"(d[173]), "=f"(d[174]), "=f"(d[175]), "=f"(d[176]), "=f"(d[177]), "=f"(d[178]), "=f"(d[179]), "=f"(d[180]), "=f"(d[181]), "=f"(d[182]), "=f"(d[183]), "=f"(d[184]), "=f"(d[185]), "=f"(d[186]), "=f"(d[187]), "=f"(d[188]), "=f"(d[189]), "=f"(d[190]), "=f"(d[191])
    : "l"(da), "l"(db));
}
__device__ __forceinline__ void wgmma_n128_rs(float (&d)[192], const uint32_t (&a)[4], uint64_t db, int scale_d) {
  asm volatile("{\n.reg .pred p;\nsetp.ne.b32 p, %69, 0;\n"
    "wgmma.mma_async.sync.aligned.m64n128k16.f32.bf16.bf16 {%0, %1, %2, %3, %4, %5, %6, %7, %8, %9, %10, %11, %12, %13, %14, %15, %16, %17, %18, %19, %20, %21, %22, %23, %24, %25, %26, %27, %28, %29, %30, %31, %32, %33, %34, %35, %36, %37, %38, %39, %40, %41, %42, %43, %44, %45, %46, %47, %48, %49, %50, %51, %52, %53, %54, %55, %56, %57, %58, %59, %60, %61, %62, %63}, {%64, %65, %66, %67}, %68, p, 1, 1, 1;\n}\n"
    : "+f"(d[128]), "+f"(d[129]), "+f"(d[130]), "+f"(d[131]), "+f"(d[132]), "+f"(d[133]), "+f"(d[134]), "+f"(d[135]), "+f"(d[136]), "+f"(d[137]), "+f"(d[138]), "+f"(d[139]), "+f"(d[140]), "+f"(d[141]), "+f"(d[142]), "+f"(d[143]), "+f"(d[144]), "+f"(d[145]), "+f"(d[146]), "+f"(d[147]), "+f"(d[148]), "+f"(d[149]), "+f"(d[150]), "+f"(d[151]), "+f"(d[152]), "+f"(d[153]), "+f"(d[154]), "+f"(d[155]), "+f"(d[156]), "+f"(d[157]), "+f"(d[158]), "+f"(d[159]), "+f"(d[160]), "+f"(d[161]), "+f"(d[162]), "+f"(d[163]), "+f"(d[164]), "+f"(d[165]), "+f"(d[166]), "+f"(d[167]), "+f"(d[168]), "+f"(d[169]), "+f"(d[170]), "+f"(d[171]), "+f"(d[172]), "+f"(d[173]), "+f"(d[174]), "+f"(d[175]), "+f"(d[176]), "+f"(d[177]), "+f"(d[178]), "+f"(d[179]), "+f"(d[180]), "+f"(d[181]), "+f"(d[182]), "+f"(d[183]), "+f"(d[184]), "+f"(d[185]), "+f"(d[186]), "+f"(d[187]), "+f"(d[188]), "+f"(d[189]), "+f"(d[190]), "+f"(d[191])
    : "r"(a[0]), "r"(a[1]), "r"(a[2]), "r"(a[3]), "l"(db), "r"(scale_d));
}
__device__ __forceinline__ void wgmma_n32_0(float (&d)[16], uint64_t da, uint64_t db) {
  asm volatile("{\n.reg .pred p;\nsetp.ne.b32 p, 0, 0;\n"
    "wgmma.mma_async.sync.aligned.m64n32k16.f32.bf16.bf16 {%0, %1, %2, %3, %4, %5, %6, %7, %8, %9, %10, %11, %12, %13, %14, %15}, %16, %17, p, 1, 1, 0, 1;\n}\n"
    : "=f"(d[0]), "=f"(d[1]), "=f"(d[2]), "=f"(d[3]), "=f"(d[4]), "=f"(d[5]), "=f"(d[6]), "=f"(d[7]), "=f"(d[8]), "=f"(d[9]), "=f"(d[10]), "=f"(d[11]), "=f"(d[12]), "=f"(d[13]), "=f"(d[14]), "=f"(d[15])
    : "l"(da), "l"(db));
}
__device__ __forceinline__ void wgmma_n32(float (&d)[16], uint64_t da, uint64_t db, int scale_d) {
  asm volatile("{\n.reg .pred p;\nsetp.ne.b32 p, %18, 0;\n"
    "wgmma.mma_async.sync.aligned.m64n32k16.f32.bf16.bf16 {%0, %1, %2, %3, %4, %5, %6, %7, %8, %9, %10, %11, %12, %13, %14, %15}, %16, %17, p, 1, 1, 0, 1;\n}\n"
    : "+f"(d[0]), "+f"(d[1]), "+f"(d[2]), "+f"(d[3]), "+f"(d[4]), "+f"(d[5]), "+f"(d[6]), "+f"(d[7]), "+f"(d[8]), "+f"(d[9]), "+f"(d[10]), "+f"(d[11]), "+f"(d[12]), "+f"(d[13]), "+f"(d[14]), "+f"(d[15])
    : "l"(da), "l"(db), "r"(scale_d));
}
__device__ __forceinline__ void wgmma_n8_t(float (&d)[4], uint64_t da, uint64_t db, int scale_d) {
  asm volatile("{\n.reg .pred p;\nsetp.ne.b32 p, %6, 0;\n"
    "wgmma.mma_async.sync.aligned.m64n8k16.f32.bf16.bf16 {%0, %1, %2, %3}, %4, %5, p, 1, 1, 1, 0;\n}\n"
    : "+f"(d[0]), "+f"(d[1]), "+f"(d[2]), "+f"(d[3])
    : "l"(da), "l"(db), "r"(scale_d));
}
__device__ __forceinline__ void wgmma_n64_lo(float (&d)[192], uint64_t da, uint64_t db, int scale_d) {
  asm volatile("{\n.reg .pred p;\nsetp.ne.b32 p, %34, 0;\n"
    "wgmma.mma_async.sync.aligned.m64n64k16.f32.bf16.bf16 {%0, %1, %2, %3, %4, %5, %6, %7, %8, %9, %10, %11, %12, %13, %14, %15, %16, %17, %18, %19, %20, %21, %22, %23, %24, %25, %26, %27, %28, %29, %30, %31}, %32, %33, p, 1, 1, 0, 1;\n}\n"
    : "+f"(d[128]), "+f"(d[129]), "+f"(d[130]), "+f"(d[131]), "+f"(d[132]), "+f"(d[133]), "+f"(d[134]), "+f"(d[135]), "+f"(d[136]), "+f"(d[137]), "+f"(d[138]), "+f"(d[139]), "+f"(d[140]), "+f"(d[141]), "+f"(d[142]), "+f"(d[143]), "+f"(d[144]), "+f"(d[145]), "+f"(d[146]), "+f"(d[147]), "+f"(d[148]), "+f"(d[149]), "+f"(d[150]), "+f"(d[151]), "+f"(d[152]), "+f"(d[153]), "+f"(d[154]), "+f"(d[155]), "+f"(d[156]), "+f"(d[157]), "+f"(d[158]), "+f"(d[159])
    : "l"(da), "l"(db), "r"(scale_d));
}
__device__ __forceinline__ void wgmma_n64_hi(float (&d)[192], uint64_t da, uint64_t db, int scale_d) {
  asm volatile("{\n.reg .pred p;\nsetp.ne.b32 p, %34, 0;\n"
    "wgmma.mma_async.sync.aligned.m64n64k16.f32.bf16.bf16 {%0, %1, %2, %3, %4, %5, %6, %7, %8, %9, %10, %11, %12, %13, %14, %15, %16, %17, %18, %19, %20, %21, %22, %23, %24, %25, %26, %27, %28, %29, %30, %31}, %32, %33, p, 1, 1, 0, 1;\n}\n"
    : "+f"(d[160]), "+f"(d[161]), "+f"(d[162]), "+f"(d[163]), "+f"(d[164]), "+f"(d[165]), "+f"(d[166]), "+f"(d[167]), "+f"(d[168]), "+f"(d[169]), "+f"(d[170]), "+f"(d[171]), "+f"(d[172]), "+f"(d[173]), "+f"(d[174]), "+f"(d[175]), "+f"(d[176]), "+f"(d[177]), "+f"(d[178]), "+f"(d[179]), "+f"(d[180]), "+f"(d[181]), "+f"(d[182]), "+f"(d[183]), "+f"(d[184]), "+f"(d[185]), "+f"(d[186]), "+f"(d[187]), "+f"(d[188]), "+f"(d[189]), "+f"(d[190]), "+f"(d[191])
    : "l"(da), "l"(db), "r"(scale_d));
}
__device__ __forceinline__ void wgmma_n128_rs0(float (&d)[192], const uint32_t (&a)[4], uint64_t db) {
  asm volatile("{\n.reg .pred p;\nsetp.ne.b32 p, 0, 0;\n"
    "wgmma.mma_async.sync.aligned.m64n128k16.f32.bf16.bf16 {%0, %1, %2, %3, %4, %5, %6, %7, %8, %9, %10, %11, %12, %13, %14, %15, %16, %17, %18, %19, %20, %21, %22, %23, %24, %25, %26, %27, %28, %29, %30, %31, %32, %33, %34, %35, %36, %37, %38, %39, %40, %41, %42, %43, %44, %45, %46, %47, %48, %49, %50, %51, %52, %53, %54, %55, %56, %57, %58, %59, %60, %61, %62, %63}, {%64, %65, %66, %67}, %68, p, 1, 1, 1;\n}\n"
    : "=f"(d[128]), "=f"(d[129]), "=f"(d[130]), "=f"(d[131]), "=f"(d[132]), "=f"(d[133]), "=f"(d[134]), "=f"(d[135]), "=f"(d[136]), "=f"(d[137]), "=f"(d[138]), "=f"(d[139]), "=f"(d[140]), "=f"(d[141]), "=f"(d[142]), "=f"(d[143]), "=f"(d[144]), "=f"(d[145]), "=f"(d[146]), "=f"(d[147]), "=f"(d[148]), "=f"(d[149]), "=f"(d[150]), "=f"(d[151]), "=f"(d[152]), "=f"(d[153]), "=f"(d[154]), "=f"(d[155]), "=f"(d[156]), "=f"(d[157]), "=f"(d[158]), "=f"(d[159]), "=f"(d[160]), "=f"(d[161]), "=f"(d[162]), "=f"(d[163]), "=f"(d[164]), "=f"(d[165]), "=f"(d[166]), "=f"(d[167]), "=f"(d[168]), "=f"(d[169]), "=f"(d[170]), "=f"(d[171]), "=f"(d[172]), "=f"(d[173]), "=f"(d[174]), "=f"(d[175]), "=f"(d[176]), "=f"(d[177]), "=f"(d[178]), "=f"(d[179]), "=f"(d[180]), "=f"(d[181]), "=f"(d[182]), "=f"(d[183]), "=f"(d[184]), "=f"(d[185]), "=f"(d[186]), "=f"(d[187]), "=f"(d[188]), "=f"(d[189]), "=f"(d[190]), "=f"(d[191])
    : "r"(a[0]), "r"(a[1]), "r"(a[2]), "r"(a[3]), "l"(db));
}
__device__ __forceinline__ void wgmma_n256_rs(float (&d)[192], const uint32_t (&a)[4], uint64_t db, int scale_d) {
  asm volatile("{\n.reg .pred p;\nsetp.ne.b32 p, %133, 0;\n"
    "wgmma.mma_async.sync.aligned.m64n256k16.f32.bf16.bf16 {%0, %1, %2, %3, %4, %5, %6, %7, %8, %9, %10, %11, %12, %13, %14, %15, %16, %17, %18, %19, %20, %21, %22, %23, %24, %25, %26, %27, %28, %29, %30, %31, %32, %33, %34, %35, %36, %37, %38, %39, %40, %41, %42, %43, %44, %45, %46, %47, %48, %49, %50, %51, %52, %53, %54, %55, %56, %57, %58, %59, %60, %61, %62, %63, %64, %65, %66, %67, %68, %69, %70, %71, %72, %73, %74, %75, %76, %77, %78, %79, %80, %81, %82, %83, %84, %85, %86, %87, %88, %89, %90, %91, %92, %93, %94, %95, %96, %97, %98, %99, %100, %101, %102, %103, %104, %105, %106, %107, %108, %109, %110, %111, %112, %113, %114, %115, %116, %117, %118, %119, %120, %121, %122, %123, %124, %125, %126, %127}, {%128, %129, %130, %131}, %132, p, 1, 1, 1;\n}\n"
    : "+f"(d[0]), "+f"(d[1]), "+f"(d[2]), "+f"(d[3]), "+f"(d[4]), "+f"(d[5]), "+f"(d[6]), "+f"(d[7]), "+f"(d[8]), "+f"(d[9]), "+f"(d[10]), "+f"(d[11]), "+f"(d[12]), "+f"(d[13]), "+f"(d[14]), "+f"(d[15]), "+f"(d[16]), "+f"(d[17]), "+f"(d[18]), "+f"(d[19]), "+f"(d[20]), "+f"(d[21]), "+f"(d[22]), "+f"(d[23]), "+f"(d[24]), "+f"(d[25]), "+f"(d[26]), "+f"(d[27]), "+f"(d[28]), "+f"(d[29]), "+f"(d[30]), "+f"(d[31]), "+f"(d[32]), "+f"(d[33]), "+f"(d[34]), "+f"(d[35]), "+f"(d[36]), "+f"(d[37]), "+f"(d[38]), "+f"(d[39]), "+f"(d[40]), "+f"(d[41]), "+f"(d[42]), "+f"(d[43]), "+f"(d[44]), "+f"(d[45]), "+f"(d[46]), "+f"(d[47]), "+f"(d[48]), "+f"(d[49]), "+f"(d[50]), "+f"(d[51]), "+f"(d[52]), "+f"(d[53]), "+f"(d[54]), "+f"(d[55]), "+f"(d[56]), "+f"(d[57]), "+f"(d[58]), "+f"(d[59]), "+f"(d[60]), "+f"(d[61]), "+f"(d[62]), "+f"(d[63]), "+f"(d[64]), "+f"(d[65]), "+f"(d[66]), "+f"(d[67]), "+f"(d[68]), "+f"(d[69]), "+f"(d[70]), "+f"(d[71]), "+f"(d[72]), "+f"(d[73]), "+f"(d[74]), "+f"(d[75]), "+f"(d[76]), "+f"(d[77]), "+f"(d[78]), "+f"(d[79]), "+f"(d[80]), "+f"(d[81]), "+f"(d[82]), "+f"(d[83]), "+f"(d[84]), "+f"(d[85]), "+f"(d[86]), "+f"(d[87]), "+f"(d[88]), "+f"(d[89]), "+f"(d[90]), "+f"(d[91]), "+f"(d[92]), "+f"(d[93]), "+f"(d[94]), "+f"(d[95]), "+f"(d[96]), "+f"(d[97]), "+f"(d[98]), "+f"(d[99]), "+f"(d[100]), "+f"(d[101]), "+f"(d[102]), "+f"(d[103]), "+f"(d[104]), "+f"(d[105]), "+f"(d[106]), "+f"(d[107]), "+f"(d[108]), "+f"(d[109]), "+f"(d[110]), "+f"(d[111]), "+f"(d[112]), "+f"(d[113]), "+f"(d[114]), "+f"(d[115]), "+f"(d[116]), "+f"(d[117]), "+f"(d[118]), "+f"(d[119]), "+f"(d[120]), "+f"(d[121]), "+f"(d[122]), "+f"(d[123]), "+f"(d[124]), "+f"(d[125]), "+f"(d[126]), "+f"(d[127])
    : "r"(a[0]), "r"(a[1]), "r"(a[2]), "r"(a[3]), "l"(db), "r"(scale_d));
}
__device__ __forceinline__ void wgmma_n256_rs0(float (&d)[192], const uint32_t (&a)[4], uint64_t db) {
  asm volatile("{\n.reg .pred p;\nsetp.ne.b32 p, 0, 0;\n"
    "wgmma.mma_async.sync.aligned.m64n256k16.f32.bf16.bf16 {%0, %1, %2, %3, %4, %5, %6, %7, %8, %9, %10, %11, %12, %13, %14, %15, %16, %17, %18, %19, %20, %21, %22, %23, %24, %25, %26, %27, %28, %29, %30, %31, %32, %33, %34, %35, %36, %37, %38, %39, %40, %41, %42, %43, %44, %45, %46, %47, %48, %49, %50, %51, %52, %53, %54, %55, %56, %57, %58, %59, %60, %61, %62, %63, %64, %65, %66, %67, %68, %69, %70, %71, %72, %73, %74, %75, %76, %77, %78, %79, %80, %81, %82, %83, %84, %85, %86, %87, %88, %89, %90, %91, %92, %93, %94, %95, %96, %97, %98, %99, %100, %101, %102, %103, %104, %105, %106, %107, %108, %109, %110, %111, %112, %113, %114, %115, %116, %117, %118, %119, %120, %121, %122, %123, %124, %125, %126, %127}, {%128, %129, %130, %131}, %132, p, 1, 1, 1;\n}\n"
    : "=f"(d[0]), "=f"(d[1]), "=f"(d[2]), "=f"(d[3]), "=f"(d[4]), "=f"(d[5]), "=f"(d[6]), "=f"(d[7]), "=f"(d[8]), "=f"(d[9]), "=f"(d[10]), "=f"(d[11]), "=f"(d[12]), "=f"(d[13]), "=f"(d[14]), "=f"(d[15]), "=f"(d[16]), "=f"(d[17]), "=f"(d[18]), "=f"(d[19]), "=f"(d[20]), "=f"(d[21]), "=f"(d[22]), "=f"(d[23]), "=f"(d[24]), "=f"(d[25]), "=f"(d[26]), "=f"(d[27]), "=f"(d[28]), "=f"(d[29]), "=f"(d[30]), "=f"(d[31]), "=f"(d[32]), "=f"(d[33]), "=f"(d[34]), "=f"(d[35]), "=f"(d[36]), "=f"(d[37]), "=f"(d[38]), "=f"(d[39]), "=f"(d[40]), "=f"(d[41]), "=f"(d[42]), "=f"(d[43]), "=f"(d[44]), "=f"(d[45]), "=f"(d[46]), "=f"(d[47]), "=f"(d[48]), "=f"(d[49]), "=f"(d[50]), "=f"(d[51]), "=f"(d[52]), "=f"(d[53]), "=f"(d[54]), "=f"(d[55]), "=f"(d[56]), "=f"(d[57]), "=f"(d[58]), "=f"(d[59]), "=f"(d[60]), "=f"(d[61]), "=f"(d[62]), "=f"(d[63]), "=f"(d[64]), "=f"(d[65]), "=f"(d[66]), "=f"(d[67]), "=f"(d[68]), "=f"(d[69]), "=f"(d[70]), "=f"(d[71]), "=f"(d[72]), "=f"(d[73]), "=f"(d[74]), "=f"(d[75]), "=f"(d[76]), "=f"(d[77]), "=f"(d[78]), "=f"(d[79]), "=f"(d[80]), "=f"(d[81]), "=f"(d[82]), "=f"(d[83]), "=f"(d[84]), "=f"(d[85]), "=f"(d[86]), "=f"(d[87]), "=f"(d[88]), "=f"(d[89]), "=f"(d[90]), "=f"(d[91]), "=f"(d[92]), "=f"(d[93]), "=f"(d[94]), "=f"(d[95]), "=f"(d[96]), "=f"(d[97]), "=f"(d[98]), "=f"(d[99]), "=f"(d[100]), "=f"(d[101]), "=f"(d[102]), "=f"(d[103]), "=f"(d[104]), "=f"(d[105]), "=f"(d[106]), "=f"(d[107]), "=f"(d[108]), "=f"(d[109]), "=f"(d[110]), "=f"(d[111]), "=f"(d[112]), "=f"(d[113]), "=f"(d[114]), "=f"(d[115]), "=f"(d[116]), "=f"(d[117]), "=f"(d[118]), "=f"(d[119]), "=f"(d[120]), "=f"(d[121]), "=f"(d[122]), "=f"(d[123]), "=f"(d[124]), "=f"(d[125]), "=f"(d[126]), "=f"(d[127])
    : "r"(a[0]), "r"(a[1]), "r"(a[2]), "r"(a[3]), "l"(db));
}

constexpr int SLOT = 16384;
constexpr int VB = 4 * SLOT, PH = 0, XS = 6;
constexpr int SM_SD = 13 * SLOT;
constexpr int SM_BAR = SM_SD + 8192;
constexpr int SM_RS = SM_BAR + 1024;
constexpr int SM_AP = SM_RS + 640;
constexpr int SM_BP = SM_AP + 2048;
constexpr int SM_EPOCH = SM_BP + 6144;
constexpr int SM_TOTAL = SM_EPOCH + 16;
constexpr int FM = 0, FT = 16, FW = 30, CM = 46, CT = 62, CW = 76, B_EF = 92, B_STAT = 93, B_KVF = 94, B_HALO = 95,
              B_KVDONE = 96, B_OH0 = 97, B_OH1 = 98, B_XH0 = 99, B_XDONE = 100, B_WFD = 101, B_XT = 102, B_OF0 = 103, B_KVF1 = 104, B_RAW = 106  , B_X0 = 108;
constexpr uint64_t BAR_LG = 0x00043333330004ull;
#define BA(i) (bar + (i) * 8)
#define REL2(i) release2c(SB0 + SM_BAR + (i) * 8)
constexpr int NF = 4, ND = 12, NR = 0, NWOP = 48, NAOP = 37;
constexpr uint64_t TL_A = 0x278627862786ull, TL_B = 0xac39bac39bacull, WO_A = 0x764a2396b4ac39ffull, WO_B = 0xc8b51c780512786bull;
__constant__ uint32_t c_wop[NWOP + 1] = {0xea8009, 0x186b8000, 0x26b8112, 0x18ec011a, 0x6c8224, 0x22ec822b, 0x170330, 0x22970339, 0x18178442, 0x18180554, 0x18188660, 0x18190772, 0x18198884, 0x181a0990, 0x181a8aa2, 0x181b0bb4, 0x181b8cc0, 0xaed90fc, 0xa9791ea, 0x181c0dd2, 0xa9812db, 0x129893c9, 0x181c8ee4, 0x181d0ff0, 0x109d94b3, 0x109f15ac, 0x109f969a, 0x10a0178b, 0x10a09879, 0x10a11963, 0x10a19a5c, 0x10a21b4a, 0x9229e0b, 0x9231f16, 0x1123a028, 0x11242137, 0x1124a242, 0x112e2351, 0x132e2465, 0x132e2570, 0x11272688, 0x1127a797, 0x112828ac, 0x1128a9b1, 0x11292ac5, 0x1129abdb, 0x112a2ce8, 0x112b2dfc, 0};
__constant__ uint32_t c_aop[NAOP + 1] = {0x6d0228, 0x170336, 0x178447, 0x180558, 0x188666, 0x190777, 0x198888, 0x1a0996, 0x1a8aa7, 0x1b0bb8, 0x1b8cc6, 0x1c0dd7, 0x1c8ee8, 0x1d0ff6, 0x1d93c2, 0x1f14b6, 0x1f95a8, 0x201697, 0x209782, 0x211876, 0x219968, 0x221a57, 0x229b42, 0xa32029, 0xa3a133, 0xa4224c, 0xa4a35a, 0xae2464, 0xa6257b, 0xa6a686, 0xa72799, 0xa7a8a3, 0xa829b2, 0xa8aaca, 0xa92bd4, 0xaa2ce6, 0xaaadf7, 0};
__constant__ uint32_t c_map[64] = {4, 5, 6, 7, 0, 16, 32, 48, 64, 80, 96, 112, 1, 17, 33, 49, 65, 81, 97, 113, 2, 18, 34, 50, 66, 82, 98, 114, 3, 19, 35, 51, 67, 83, 99, 115, 20, 36, 52, 68, 84, 100, 116, 21, 37, 53, 69, 85, 101, 117, 22, 38, 54, 70, 86, 102, 118, 23, 39, 55, 71, 87, 103, 119};
enum { MAP_WF = 0, MAP_WA = 2, MAP_WB = 4, MAP_WOA = 6, MAP_WOB = 8, MAP_X0 = 10, MAP_X = 11, MAP_O = 12, MAP_PHI = 13, NMAP = 14 };
struct Maps { CUtensorMap m[NMAP]; };

#define PL 2
#define PROFL(a, b)
#define SUBS 8
#define QORD 1
#define NCH 4
#define CHW 1
#define SUBS1 12
#define XRAT 9
#define PFW 0
#define XRN 2
#define BT1 1
#define CV0 0
#define ST1 8
#define FASTP 0
#define O1P 2
#define X0AT 1
#define W1DL 400
#define WFDL 0
#define SKA 2
#define SKB 0
#define BPRE 0
#define XST 3
#define XDR 0
#define SKW 0
#define SKL 1
#define NLAYERS 4
constexpr float L2E = 1.4426950408889634f;

#define D128(lo) desc64(lo, 0x40000040u)
struct Ctx { uint32_t zero, boff; const bf16* x0; bf16* out; };
#define BLK_CTX() \
  uint32_t bid_; asm volatile("mov.u32 %0, %%ctaid.x;" : "=r"(bid_)); \
  bid_ -= c.boff; \
  const uint32_t gr_ = c_map[bid_ >> 1]; \
  const int cr = bid_ & 1, g = gr_ & 7, rb = (gr_ >> 3) + cr, m0 = rb * 128; \
  const uint32_t sb = SB0 + (cr << 24); \
  const uint32_t bar = sb + SM_BAR; \
  (void)cr; (void)g; (void)rb; (void)m0; (void)bar;
extern __shared__ uint8_t smem_raw[];
constexpr uint32_t SB0 = 1024;

#define PHASE_CTX() \
  BLK_CTX(); \
  int tid_ = threadIdx.x; asm volatile("" : "+r"(tid_)); \
  const int lane = tid_ & 31, cw = (tid_ >> 5) - 4, wg = cw >> 2, wq = cw & 3, gq = lane >> 2, t = lane & 3, wrow0 = cw * 16; \
  const int lrow = (lane & 7) + ((lane >> 3) & 1) * 8, lchk = lane >> 4; \
  const bool elected = (tid_ & 127) == 0; \
  const uint32_t rowo = (wrow0 + lrow) * 128, X = (lchk ^ (lane & 7)) << 4; \
  const uint32_t Y = (wrow0 + (lane & 7)) * 128 + (((lane >> 3) ^ (lane & 7)) << 4); \
  const size_t gfr = (size_t)(m0 + wrow0 + gq) * D_ + g * 128 + 8 * t; \
  (void)bar; (void)wq; (void)gq; (void)lrow; (void)lchk; (void)elected; (void)wrow0; (void)wg; (void)rowo; (void)X; (void)t; (void)Y; (void)gfr;
#define MMA_CTX() \
  const uint32_t wu = __shfl_sync(0xffffffffu, wg, 0); \
  const uint32_t dA0 = ((SB0 >> 4) | (1u << 16)) + wu * 512, dB0 = (SB0 >> 4) | (512u << 16); \
  const uint32_t par = layer & 1;

__device__ __forceinline__ void slab_out_half(uint32_t slot, bf16* dst, int wrow0, int lane) {
  const int r0 = lane >> 3, ch = lane & 7;
  const uint32_t src = slot + (wrow0 + r0) * 128;
  uint4 v[4];
#pragma unroll
  for (int i = 0; i < 4; ++i) v[i] = lds128(src + i * 512 + (((ch ^ (4 * i + r0)) & 7) << 4));
  dst += (size_t)(wrow0 + r0) * D_ + ch * 8;
#pragma unroll
  for (int i = 0; i < 4; ++i) *reinterpret_cast<uint4*>(dst + (size_t)i * 4 * D_) = v[i];
}

__device__ __forceinline__ void consumer(const Ctx& c) {
  float acc[192];
  uint32_t xf[4][4];
  uint32_t xp[8][4];
  {
    PHASE_CTX();
    const unsigned int epoch = ld_relaxed(&g_epoch);
    PROFT(tid_ == 128, 0);
    const uint32_t wu = __shfl_sync(0xffffffffu, wg, 0);
    if (tid_ < 128 + 8) sts128(sb + SM_AP + lane * 16, make_uint4(0x3F803F80u, 0x3F803F80u, 0x3F803F80u, 0x3F803F80u));
#pragma unroll 1
    for (int it = 0; it < 2; ++it) {
      float p[4][16];
      mbar_wait(BA(B_RAW + it), 0);
      PROFT(tid_ == 128, it ? 15 : 2);
      const uint32_t da = ((SB0 >> 4) | (1u << 16)) + (wu ? 9 + it : 2 * it) * 1024, db = (SB0 + SM_SD) >> 4;
      wgmma_fence();
#pragma unroll
      for (int h = 0; h < 4; ++h) wgmma_n32_0(p[h], D128(da + (h >> 1) * 512 + (h & 1) * 4), desc64(db + h * 128, 0x80000020u));
#pragma unroll
      for (int h = 0; h < 4; ++h) wgmma_n32(p[h], D128(da + (h >> 1) * 512 + (h & 1) * 4 + 2), desc64(db + h * 128 + 64, 0x80000020u), 1);
      wgmma_commit();
      wgmma_wait<0>();
#pragma unroll
      for (int i = 0; i < 64; ++i) asm volatile("" : "+f"(p[i >> 4][i & 15]) :: "memory");
      const uint32_t base = sb + (wg ? 9 + it : 2 * it) * SLOT + (wq * 16 + gq) * 128;
      uint32_t w[4][4][2];
#pragma unroll
      for (int i = 0; i < 32; ++i) w[i >> 3][(i >> 1) & 3][i & 1] = pack_bf16(p[i >> 3][2 * (i & 7)], p[i >> 3][2 * (i & 7) + 1]);
      if (wu) {
#pragma unroll
        for (int i = 0; i < 8; ++i)
          sts128(base + (i >> 2) * 8192 + (i & 1) * 1024 + (((((i >> 1) & 1) * 4 + t) ^ gq) << 4), make_uint4(w[i >> 1][0][i & 1], w[i >> 1][1][i & 1], w[i >> 1][2][i & 1], w[i >> 1][3][i & 1]));
      } else {
#pragma unroll
        for (int i = 0; i < 16; ++i)
          sts64(base + (i >> 3) * 8192 + (i & 1) * 1024 + ((((t & 1) * 4 + ((i >> 1) & 3)) ^ gq) << 4) + (t >> 1) * 8, w[(i >> 3) * 2][(i >> 1) & 3][i & 1], w[(i >> 3) * 2 + 1][(i >> 1) & 3][i & 1]);
      }
      fence_async_smem();
      __syncwarp();
      if (it == cr && lane == 0) mbar_arrive(BA(B_WFD));
    }
    if (tid_ == 128) sts_f(sb + SM_EPOCH, __uint_as_float(epoch & 1));
#pragma unroll
    for (int i = 0; i < 32; ++i) xp[i >> 2][i & 3] = 0u;
    nbar<1, 256>();
    PROFT(tid_ == 128, 13);
    mbar_wait(BA(FM + cr), 0);
    float cs[3][4];
    wgmma_fence();
#pragma unroll
    for (int ks = 0; ks < 4; ++ks)
#pragma unroll
      for (int i = 0; i < 3; ++i) {
        const uint32_t bx = (i == 0 ? 2 * cr * 1024 : i == 1 ? (2 * cr + 1) * 1024 : (9 + cr) * 1024) + wu * 512;
        wgmma_n8_t(cs[i], D128(((SB0 >> 4) | (512u << 16)) + bx + ks * 128), desc64((SB0 + SM_AP) >> 4, 0), ks != 0);
      }
    wgmma_commit();
    mbar_wait(BA(FM), 0);
#pragma unroll
    for (int k = 0; k < 4; ++k) ldsm_x4(xf[k][0], xf[k][1], xf[k][2], xf[k][3], sb + XS * SLOT + rowo + (X ^ (k << 5)));
    wgmma_wait<0>();
#pragma unroll
    for (int i = 0; i < 12; ++i) asm volatile("" : "+f"(cs[i >> 2][i & 3]) :: "memory");
    if (t < 2) {
#pragma unroll
      for (int i = 0; i < 3; ++i) red_add1(g_cs + (epoch & 1) * 6144 + g * 384 + i * 128 + wg * 64 + wq * 16 + gq + t * 8, t ? cs[i][2] : cs[i][0]);
    }
    PROFT(tid_ == 128, 14);
  }
#pragma unroll 1
  for (int layer = 0;; ++layer) {
    {
      PHASE_CTX();
      MMA_CTX();
      {
        const uint32_t ep = __float_as_uint(lds_f(sb + SM_EPOCH));
        mbar_wait(BA(FM), par);
        wgmma_fence();
        wgmma_n256_rs0(acc, xf[0], D128(dB0));
#pragma unroll
        for (int k = 1; k < 4; ++k) wgmma_n256_rs(acc, xf[k], D128(dB0 + k * 128), 1);
        wgmma_commit();
        if (layer == 0) {
          mbar_wait(BA(B_X0), 0);
#pragma unroll
          for (int i = 0; i < 8; ++i) ldsm_x4(xp[i][0], xp[i][1], xp[i][2], xp[i][3], sb + (11 + (i >> 2)) * SLOT + (Y ^ ((i & 2) << 5)) + (i & 1) * 1024);
          if (lane == ((xp[0][0] ^ xp[1][0] ^ xp[2][0] ^ xp[3][0] ^ xp[7][0]) & c.zero)) REL2(B_XT);
        } else {
#pragma unroll
          for (int i = 0; i < 8; ++i) stsm_x4(sb + (XS + (i >> 2)) * SLOT + (Y ^ ((i & 2) << 5)) + (i & 1) * 1024, xp[i][0], xp[i][1], xp[i][2], xp[i][3]);
        }
        float s0 = 0.f, s1 = 0.f, q0 = 0.f, q1 = 0.f;
        auto stats = [&](int j0, int j1) {
#pragma unroll
          for (int j = j0; j < j1; ++j) {
            const uint32_t u0 = xp[(j >> 2) * 2][j & 3], u1 = xp[(j >> 2) * 2 + 1][j & 3];
            s0 += bf_lo(u0) + bf_hi(u0); s1 += bf_lo(u1) + bf_hi(u1);
            q0 = fmaf(bf_lo(u0), bf_lo(u0), fmaf(bf_hi(u0), bf_hi(u0), q0)); q1 = fmaf(bf_lo(u1), bf_lo(u1), fmaf(bf_hi(u1), bf_hi(u1), q1));
          }
        };
        stats(0, ST1);
        fence_async_smem();
        nbar_dyn(3 + wu + (__float_as_uint(s0 + s1 + q0 + q1) & c.zero), 128);
        mbar_wait(BA(FM + 1), par);
        wgmma_fence();
#pragma unroll
        for (int k = 0; k < 4; ++k) wgmma_n256(acc, D128(dA0 + (XS + 1) * 1024 + k * 2), D128(dB0 + 2048 + k * 128), 1);
        wgmma_commit();
        wgmma_wait<1>();
#pragma unroll
        for (int i = 4; i < 8; ++i) stg128_p(layer, g_x + gfr + (i & 1) * 8 * D_ + (i >> 1) * 32, xp[i][0], xp[i][1], xp[i][2], xp[i][3]);
        {
          uint32_t zc; asm volatile("mov.u32 %0, %%clock;" : "=r"(zc) :: "memory");
          q0 += __uint_as_float(zc & c.zero); q1 += __uint_as_float(zc & c.zero); s0 += __uint_as_float(zc & c.zero); s1 += __uint_as_float(zc & c.zero);
        }
        stats(ST1, 16);
        wgmma_fence();
        wgmma_n128_0(acc, D128(dA0 + XS * 1024), D128(dB0 + 9 * 1024));
#pragma unroll
        for (int k = 1; k < 4; ++k) wgmma_n128(acc, D128(dA0 + XS * 1024 + k * 2), D128(dB0 + 9 * 1024 + k * 128), 1);
        wgmma_commit();
        const bool od = t & 1;
        float sa = od ? s1 : s0, qa = od ? q1 : q0;
        sa += __shfl_xor_sync(0xffffffffu, od ? s0 : s1, 1);
        qa += __shfl_xor_sync(0xffffffffu, od ? q0 : q1, 1);
        wgmma_fence();
#pragma unroll
        for (int k = 0; k < 4; ++k) wgmma_n128(acc, D128(dA0 + (XS + 1) * 1024 + k * 2), D128(dB0 + 10 * 1024 + k * 128), 1);
        wgmma_commit();
        sa += __shfl_xor_sync(0xffffffffu, sa, 2);
        qa += __shfl_xor_sync(0xffffffffu, qa, 2);
        red_add2_p(t < 2, reinterpret_cast<float*>(g_stats + (ep * 4 + layer) * S_ + m0 + wrow0 + gq + t * 8), sa, qa);
        __syncwarp();
        if (lane == 0) mbar_arrive(BA(B_XDONE));
        wgmma_wait<1>();
        if (elected) REL2(CM);
      }
      uint32_t s = 2;
#pragma unroll 1
      for (int i = 2; i < NF; ++i) {
        PROFL(tid_ == 128 && layer == PL + 1, 244 + 2 * i);
        mbar_wait(BA(FM + i), par);
        PROFL(tid_ == 128 && layer == PL + 1, 245 + 2 * i);
        const uint32_t da = dA0 + (XS + s) * 1024, dk = dB0 + s * 2048, dq = dB0 + (9 + s) * 1024;
        wgmma_fence();
#pragma unroll
        for (int k = 0; k < 4; ++k) wgmma_n128(acc, D128(da + k * 2), D128(dq + k * 128), 1);
        wgmma_commit();
        wgmma_wait<1>();
        if (elected) REL2(CM + i - 1);
        wgmma_fence();
#pragma unroll
        for (int k = 0; k < 4; ++k) wgmma_n256(acc, D128(da + k * 2), D128(dk + k * 128), 1);
        wgmma_commit();
        if (++s == 3) s = 0;
      }
#pragma unroll 1
      for (int i = NF; i < 15; ++i) {
        mbar_wait(BA(FM + i), par);
        const uint32_t da = dA0 + (XS + s) * 1024, dk = dB0 + s * 2048;
        wgmma_fence();
#pragma unroll
        for (int k = 0; k < 4; ++k) wgmma_n256(acc, D128(da + k * 2), D128(dk + k * 128), 1);
        wgmma_commit();
        wgmma_wait<1>();
        if (elected) REL2(CM + i - 1);
        if (++s == 3) s = 0;
      }
      {
        const uint64_t dap = desc64(((SB0 + SM_AP) >> 4) + wu * 64, 8), dbp = make_desc_ns(SB0 + SM_BP, 0, 128);
        mbar_wait(BA(B_STAT), par);
        mbar_wait(BA(FM + 15), par);
        PROFT(tid_ == 128, layer * 16 + 9);
        wgmma_fence();
        wgmma_n256_k(acc, dap, dbp, 1);
#pragma unroll
        for (int k = 0; k < 4; ++k) wgmma_n256(acc, D128(dA0 + XS * 1024 + k * 2), D128(dB0 + k * 128), 1);
        wgmma_commit();
        wgmma_wait<1>();
        if (elected) REL2(CM + 14);
        mbar_wait(BA(FT), par);
        wgmma_fence();
        wgmma_n128_k(acc, dap, dbp + 256, 1);
#pragma unroll
        for (int k = 0; k < 4; ++k) wgmma_n128(acc, D128(dA0 + (uint32_t)(TL_A & 15) * 1024 + k * 2), D128(dB0 + (uint32_t)(TL_B & 15) * 1024 + k * 128), 1);
        wgmma_commit();
        wgmma_wait<1>();
        if (elected) REL2(CM + 15);
#pragma unroll
        for (int i = 0; i < 128; ++i) asm volatile("" : "+f"(acc[i]) :: "memory");
      }
    }
    uint32_t of[8][4], o1[4][4];
    {
      PHASE_CTX();
      MMA_CTX();
      PROFT(tid_ == 128, layer * 16 + 1);
      PROFT(lane == 0 && layer == PL, 192 + cw);
      PROFT(tid_ == 128 && layer == PL, 160);
      uint64_t ta = (TL_A >> 4), tw = TL_B >> 4;
      uint32_t da, db, dz = dA0;
      auto sub = [&](int n) {
        const int j = n >> 2, k = n & 3;
        if (k == 0) {
          dz += c.zero;
          da = dz + ((uint32_t)ta & 15) * 1024; db = dB0 + ((uint32_t)tw & 15) * 1024;
          ta >>= 4; tw >>= 4;
          mbar_wait(BA(FT + j), par);
          wgmma_fence();
        }
        wgmma_n128(acc, D128(da + k * 2), D128(db + k * 128), 1);
        if (k == 3) {
          wgmma_commit();
          wgmma_wait<1>();
          if (elected) REL2(CT + j - 1);
        }
      };
      auto run = [&](int j0, int j1) {
#pragma unroll 1
        for (int j = j0; j < j1; ++j) {
          mbar_wait(BA(FT + j), par);
          da = dA0 + ((uint32_t)ta & 15) * 1024; db = dB0 + ((uint32_t)tw & 15) * 1024;
          ta >>= 4; tw >>= 4;
          wgmma_fence();
#pragma unroll
          for (int k = 0; k < 4; ++k) wgmma_n128(acc, D128(da + k * 2), D128(db + k * 128), 1);
          wgmma_commit();
          wgmma_wait<1>();
          if (elected) REL2(CT + j - 1);
        }
        ta = TL_A >> (4 * j1); tw = TL_B >> (4 * j1);
      };
      auto rest = [&](int j0, int sk) {
        if (sk) {
          run(j0, ND - sk);
          if (wu == 0) nbar<6, 256>();
          j0 = ND - sk;
        }
        run(j0, ND);
        if (sk && wu) asm volatile("bar.arrive 6, 256;" ::: "memory");
      };
      auto rest_end = [&]() {
        wgmma_wait<0>();
        if (elected) REL2(CT + ND - 1);
#pragma unroll
        for (int i = 128; i < 192; ++i) asm volatile("" : "+f"(acc[i]) :: "memory");
      };
      const float rs0 = lds_f(sb + SM_RS + (16 + wrow0 + gq) * 4), rs1 = lds_f(sb + SM_RS + (24 + wrow0 + gq) * 4);
#define EPOCH() __float_as_uint(lds_f(sb + SM_EPOCH))
      mbar_wait(BA(CM + 14), par);
      if (par) {
        uint32_t kk[8][4], kp[8][4], vf[2][2][4][4];
        int sn = 4;
#pragma unroll
        for (int i = 0; i < 4 * BT1; ++i) sub(sn++);
        {
          uint32_t vv[8][4];
#pragma unroll
          for (int jp = 0; jp < 8; ++jp) {
            kk[jp][0] = pack_bf16(acc[8 * jp], acc[8 * jp + 1]); kk[jp][1] = pack_bf16(acc[8 * jp + 4], acc[8 * jp + 5]);
            kk[jp][2] = pack_bf16(acc[8 * jp + 2], acc[8 * jp + 3]); kk[jp][3] = pack_bf16(acc[8 * jp + 6], acc[8 * jp + 7]);
#pragma unroll
            for (int i = 0; i < 4; ++i) vv[jp][i] = pack_bf16(acc[64 + 8 * jp + 2 * i], acc[65 + 8 * jp + 2 * i]);
          }
          if (cw == 7) {
            uint32_t* const hbuf = g_halo + (size_t)(((layer >> 1) * 17 + rb + 1) * 8 + g) * 2048;
#pragma unroll
            for (int jp = 0; jp < 8; ++jp) stg128(hbuf + jp * 128 + lane * 4, kk[jp][0], kk[jp][1], kk[jp][2], kk[jp][3]);
#pragma unroll
            for (int i = 0; i < 32; ++i) hbuf[1024 + (i >> 4) * 512 + (gq + (i & 1) * 8) * 32 + ((((i >> 1) & 7) ^ gq) << 2) + t] = vv[i >> 2][i & 3];
            __syncwarp();
            if (lane == 0) mbar_arrive(BA(B_OF0));
          }
#pragma unroll
          for (int jp = 0; jp < 8; ++jp) {
            sub(sn++);
            stsm_x4(sb + VB + (jp >> 2) * SLOT + rowo + (X ^ ((jp & 3) << 5)), vv[jp][0], vv[jp][1], vv[jp][2], vv[jp][3]);
          }
        }
        PROFT(tid_ == 128, layer * 16 + 2);
        const int e = gq & 1;
        float f0[4], f1[4], b0[4], b1[4], rj[4];
#pragma unroll
        for (int nt = 0; nt < 4; ++nt) {
          const int kx = nt * 8 + 2 * t + e;
          const bool okk = (m0 + wrow0 + kx) >= 16;
          const int d0 = kx - gq, d1 = d0 - 8;
          rj[nt] = lds_f(sb + SM_RS + (wrow0 + kx) * 4);
          const bool m0_ = okk && d0 >= 2 && d0 <= 16, m1_ = okk && d1 >= 2 && d1 <= 16;
          f0[nt] = m0_ ? rj[nt] * rs0 * (0.17677669529663687f * L2E) : 0.f;
          f1[nt] = m1_ ? rj[nt] * rs1 * (0.17677669529663687f * L2E) : 0.f;
          b0[nt] = m0_ ? 0.f : -1e30f; b1[nt] = m1_ ? 0.f : -1e30f;
        }
        mbar_wait(BA(CM + 15), par);
#pragma unroll
        for (int jp = 0; jp < 8; ++jp) {
          sub(sn++);
          sts128(sb + PH + cw * 4096 + jp * 512 + lane * 16, make_uint4(kk[jp][0], kk[jp][1], kk[jp][2], kk[jp][3]));
        }
#pragma unroll
        for (int i = 0; i < 4; ++i) sub(sn++);
        nbar<1, 256>();
        PROFT(tid_ == 128, layer * 16 + 3);
        rest(sn >> 2, SKB);
        if (!BPRE) rest_end();
        PROFT(lane == 0 && layer == PL, 200 + cw);
        PROFT(tid_ == 128, layer * 16 + 10);
        if (cw == 0) mbar_wait(BA(B_HALO), (layer >> 1) & 1);
        PROFT(tid_ == 128, layer * 16 + 5);
        const uint32_t vs = sb + (cw ? VB + rowo - 2048 : SM_SD + 4096 + rowo), vst = cw ? SLOT : 2048;
        const uint32_t psel = e ? 0x1054u : 0x5410u;
#pragma unroll
        for (int hp = 0; hp < 2; ++hp) {
#pragma unroll
          for (int i = 4 * hp; i < 4 * hp + 4; ++i) {
            const uint4 u = lds128(sb + (cw ? PH + (cw - 1) * 4096 : SM_SD) + lane * 16 + i * 512);
            kp[i][0] = u.x; kp[i][1] = u.y; kp[i][2] = u.z; kp[i][3] = u.w;
          }
#pragma unroll
          for (int i = 4 * hp; i < 4 * hp + 4; ++i) {
            ldsm_x4_t(vf[0][i & 1][i >> 1][0], vf[0][i & 1][i >> 1][1], vf[0][i & 1][i >> 1][2], vf[0][i & 1][i >> 1][3], vs + (i >> 2) * vst + (X ^ ((i & 3) << 5)));
            ldsm_x4_t(vf[1][i & 1][i >> 1][0], vf[1][i & 1][i >> 1][1], vf[1][i & 1][i >> 1][2], vf[1][i & 1][i >> 1][3], sb + VB + (i >> 2) * SLOT + rowo + (X ^ ((i & 3) << 5)));
          }
          if (BPRE && !hp) rest_end();
          float l0[2][4], l1[2][4];
#pragma unroll
          for (int h = 0; h < 2; ++h) {
            const int H = 2 * hp + h;
            uint32_t qa[8];
#pragma unroll
            for (int i = 0; i < 8; ++i) qa[i] = pack_bf16(acc[128 + 16 * H + 2 * i], acc[129 + 16 * H + 2 * i]);
#pragma unroll
            for (int nt = 3; nt >= 0; --nt) {
              float sc[4] = {0.f, 0.f, 0.f, 0.f};
#pragma unroll
              for (int ks = 0; ks < 2; ++ks) {
                const uint32_t (&kf)[4] = nt < 2 ? kp[2 * H + ks] : kk[2 * H + ks];
                mma_bf16(sc, qa[4 * ks], qa[4 * ks + 1], qa[4 * ks + 2], qa[4 * ks + 3], kf[2 * (nt & 1)], kf[2 * (nt & 1) + 1]);
              }
              l0[h][nt] = fmaf(e ? sc[1] : sc[0], f0[nt], b0[nt]);
              l1[h][nt] = fmaf(e ? sc[3] : sc[2], f1[nt], b1[nt]);
            }
          }
          float mx0[2], mx1[2], s0[2], s1[2];
#pragma unroll
          for (int h = 0; h < 2; ++h) {
            mx0[h] = fmaxf(fmaxf(l0[h][0], l0[h][1]), l0[h][2]);
            mx1[h] = fmaxf(fmaxf(l1[h][1], l1[h][2]), l1[h][3]);
          }
#pragma unroll
          for (int o = 1; o <= 2; o <<= 1)
#pragma unroll
            for (int h = 0; h < 2; ++h) {
              mx0[h] = fmaxf(mx0[h], __shfl_xor_sync(0xffffffffu, mx0[h], o));
              mx1[h] = fmaxf(mx1[h], __shfl_xor_sync(0xffffffffu, mx1[h], o));
            }
#pragma unroll
          for (int h = 0; h < 2; ++h) {
#pragma unroll
            for (int nt = 0; nt < 3; ++nt) { l0[h][nt] = ex2(l0[h][nt] - mx0[h]); l1[h][nt + 1] = ex2(l1[h][nt + 1] - mx1[h]); }
            s0[h] = (l0[h][0] + l0[h][1]) + l0[h][2];
            s1[h] = (l1[h][1] + l1[h][2]) + l1[h][3];
          }
#pragma unroll
          for (int o = 1; o <= 2; o <<= 1)
#pragma unroll
            for (int h = 0; h < 2; ++h) {
              s0[h] += __shfl_xor_sync(0xffffffffu, s0[h], o);
              s1[h] += __shfl_xor_sync(0xffffffffu, s1[h], o);
            }
          uint32_t ow[2][2][4];
#pragma unroll
          for (int h = 0; h < 2; ++h) {
            const int H = 2 * hp + h;
            uint32_t pl[4], ph[4];
            const float i0 = rcp(s0[h]), i1 = rcp(s1[h]);
#pragma unroll
            for (int nt = 0; nt < 4; ++nt) {
              const uint32_t pk = pack_bf16(nt < 3 ? l0[h][nt] * i0 * rj[nt] : 0.f, nt > 0 ? l1[h][nt] * i1 * rj[nt] : 0.f);
              pl[nt] = nt < 3 ? __byte_perm(pk, 0u, psel) : 0u;
              ph[nt] = nt > 0 ? __byte_perm(pk, 0u, psel + 0x2222u) : 0u;
            }
#pragma unroll
            for (int nj = 0; nj < 4; ++nj) {
              float oa[4] = {0.f, 0.f, 0.f, 0.f};
#pragma unroll
              for (int ks = 0; ks < 2; ++ks)
                mma_bf16(oa, pl[2 * ks], ph[2 * ks], pl[2 * ks + 1], ph[2 * ks + 1], vf[ks][nj >> 1][H][2 * (nj & 1)], vf[ks][nj >> 1][H][2 * (nj & 1) + 1]);
              ow[h][0][nj] = pack_bf16(oa[0], oa[1]); ow[h][1][nj] = pack_bf16(oa[2], oa[3]);
            }
          }
          if (hp == 0) {
#pragma unroll
            for (int i = 0; i < 4; ++i) stg128(g_o + gfr + (i & 1) * 8 * D_ + (i >> 1) * 32, ow[i >> 1][i & 1][0], ow[i >> 1][i & 1][1], ow[i >> 1][i & 1][2], ow[i >> 1][i & 1][3]);
            __syncwarp();
            if (lane == 0) mbar_arrive(BA(B_OH0));
          } else {
#pragma unroll
            for (int i = 0; i < 16; ++i) o1[i >> 2][i & 3] = ow[i >> 3][(i >> 2) & 1][i & 3];
          }
#pragma unroll
          for (int i = 0; i < 16; ++i) of[4 * hp + (i >> 2)][i & 3] = ow[i >> 3][i & 1][(i >> 1) & 3];
          if (!hp) PROFT(tid_ == 128, layer * 16 + 15);
        }
      } else {
        float sc[2] = {rs0 * L2E, rs1 * L2E};
        {
          const uint32_t vb = sb + VB + (rowo >> 1), X0 = (lchk ^ ((lane & 7) >> 1)) << 4;
          const uint32_t pb = sb + PH + (t & 1) * SLOT + (wrow0 + gq) * 128 + ((((t & 1) * 4 + (t & 2)) ^ gq) << 4);
          float kva[20], en[32], mx[2][2], mn[2][2];
#define PV(hp, j) acc[32 * (hp) + (j)]
          auto mm = [&](int hp, int j) {
            const int r = (j >> 1) & 1;
            if (j < 4 && !(j & 1)) { mx[hp][r] = PV(hp, j); mn[hp][r] = PV(hp, j); }
            else { mx[hp][r] = fmaxf(mx[hp][r], PV(hp, j)); mn[hp][r] = fminf(mn[hp][r], PV(hp, j)); }
          };
          auto mmx = [&](int hp) {
#pragma unroll
            for (int r = 0; r < 2; ++r) {
              mx[hp][r] = fmaxf(mx[hp][r], __shfl_xor_sync(0xffffffffu, mx[hp][r], 2)) * -sc[r];
              mn[hp][r] = fmaf(fminf(mn[hp][r], __shfl_xor_sync(0xffffffffu, mn[hp][r], 2)), sc[r], mx[hp][r]);
            }
          };
          auto stage = [&](int hp) {
#pragma unroll
            for (int i = 0; i < 20; ++i) asm volatile("" : "+f"(kva[i]) :: "memory");
            nbar_dyn(3 + wu, 128);
#pragma unroll
            for (int i = 0; i < 4; ++i)
              sts128(sb + VB + hp * SLOT + wg * 8192 + (wq * 128 + i * 32 + lane) * 16,
                     make_uint4(__float_as_uint(kva[4 * i]), __float_as_uint(kva[4 * i + 1]), __float_as_uint(kva[4 * i + 2]), __float_as_uint(kva[4 * i + 3])));
            if (t == 0) sts_f2(sb + SM_AP + ((2 * hp + wg) * 64 + wq * 16 + gq * 2) * 4, kva[16], kva[18]);
            fence_async_smem();
            __syncwarp();
            if (lane == 0) mbar_arrive(BA(B_KVDONE));
          };
          int sn = 4;
#pragma unroll
          for (int j = 0; j < 32; ++j) mm(0, j);
          mmx(0);
#pragma unroll
          for (int hp = 0; hp < 2; ++hp) {
            float sp[2] = {0.f, 0.f}, sm[2] = {0.f, 0.f};
#pragma unroll
            for (int j = 0; j < 32; ++j) {
              const int r = (j >> 1) & 1, ns = hp ? SUBS1 : SUBS;
              if ((j * ns) / 32 != ((j + 1) * ns) / 32) {
                sub(sn++);
                if (hp && sn == 4 + SUBS + 4 + 4 * (XST & 1)) { stage(0); PROFT(tid_ == 128, layer * 16 + 12); }
              }
              const float x = fmaf(PV(hp, j), sc[r], mx[hp][r]);
              PV(hp, j) = ex2(x); en[j] = ex2(mn[hp][r] - x);
              sp[r] += PV(hp, j); sm[r] += en[j];
              if (hp == 0) {
                mm(1, j);
                if ((j & 3) == 0) {
                  const int jp = 8 + (j >> 2);
                  stsm_x4(vb + ((jp - 8) >> 1) * 8192 + (X0 ^ ((jp & 1) << 5)), pack_bf16(acc[8 * jp], acc[8 * jp + 1]), pack_bf16(acc[8 * jp + 2], acc[8 * jp + 3]),
                          pack_bf16(acc[8 * jp + 4], acc[8 * jp + 5]), pack_bf16(acc[8 * jp + 6], acc[8 * jp + 7]));
                }
              }
            }
#pragma unroll
            for (int i = 0; i < 4; ++i) if (XST & (1 << hp)) sub(sn++);
#pragma unroll
            for (int r = 0; r < 2; ++r) {
              sp[r] = rcp(sp[r] + __shfl_xor_sync(0xffffffffu, sp[r], 2)) * (r ? rs1 : rs0);
              sm[r] = rcp(sm[r] + __shfl_xor_sync(0xffffffffu, sm[r], 2)) * (r ? rs1 : rs0);
            }
            if (hp == 0) { mmx(1); mbar_wait(BA(CM + 15), par); }
            else { PROFT(tid_ == 128, layer * 16 + 11); nbar<1, 256>(); }
#pragma unroll
            for (int i = 0; i < 4; ++i) {
              const int r = i & 1, d = 16 * (i >> 1) + 2 * r;
              sts128((pb + r * 1024) ^ ((i >> 1) << 4), make_uint4(pack_bf16(PV(hp, d) * sp[r], PV(hp, d + 1) * sp[r]), pack_bf16(PV(hp, d + 4) * sp[r], PV(hp, d + 5) * sp[r]),
                                                                    pack_bf16(PV(hp, d + 8) * sp[r], PV(hp, d + 9) * sp[r]), pack_bf16(PV(hp, d + 12) * sp[r], PV(hp, d + 13) * sp[r])));
              sts128((pb + r * 1024) ^ ((i >> 1) << 4) ^ 64, make_uint4(pack_bf16(en[d] * sm[r], en[d + 1] * sm[r]), pack_bf16(en[d + 4] * sm[r], en[d + 5] * sm[r]),
                                                                         pack_bf16(en[d + 8] * sm[r], en[d + 9] * sm[r]), pack_bf16(en[d + 12] * sm[r], en[d + 13] * sm[r])));
            }
            fence_async_smem();
            nbar<1, 256>();
            const uint32_t dP = dB0 + (PH >> 4) + wu * 1024;
            const uint32_t dV = (dB0 & 0xFFFFu) + ((VB + hp * SLOT) >> 4) + (((SM_SD - VB - hp * SLOT) >> 4) << 16) + wu * (512u - (512u << 16));
            wgmma_fence();
#pragma unroll
            for (int ks = 0; ks < 8; ++ks) wgmma_n40_tt(kva, D128(dP + ks * 128), desc64(dV + ks * 64, 0x80000020u), ks != 0);
            wgmma_commit();
          }
#pragma unroll
          for (int i = 0; i < 4; ++i) sub(sn++);
          stage(1);
          PROFT(tid_ == 128, layer * 16 + 3);
          rest(sn >> 2, SKA);
          rest_end();
          PROFT(lane == 0 && layer == PL, 200 + cw);
          PROFT(tid_ == 128, layer * 16 + 10);
        }
#define QV(H, i) acc[128 + 16 * (H) + (i)]
        float mx[4][2], mn[4][2];
        uint32_t ph[4][4][4];
        auto mnx = [&](int hp) {
#pragma unroll
          for (int H = 2 * hp; H < 2 * hp + 2; ++H)
#pragma unroll
            for (int r = 0; r < 2; ++r) {
              mx[H][r] = fmaxf(fmaxf(fmaxf(QV(H, 2 * r), QV(H, 2 * r + 1)), fmaxf(QV(H, 4 + 2 * r), QV(H, 5 + 2 * r))),
                               fmaxf(fmaxf(QV(H, 8 + 2 * r), QV(H, 9 + 2 * r)), fmaxf(QV(H, 12 + 2 * r), QV(H, 13 + 2 * r))));
              mn[H][r] = fminf(fminf(fminf(QV(H, 2 * r), QV(H, 2 * r + 1)), fminf(QV(H, 4 + 2 * r), QV(H, 5 + 2 * r))),
                               fminf(fminf(QV(H, 8 + 2 * r), QV(H, 9 + 2 * r)), fminf(QV(H, 12 + 2 * r), QV(H, 13 + 2 * r))));
            }
#pragma unroll
          for (int o = 1; o <= 2; o <<= 1)
#pragma unroll
            for (int H = 2 * hp; H < 2 * hp + 2; ++H)
#pragma unroll
              for (int r = 0; r < 2; ++r) {
                mx[H][r] = fmaxf(mx[H][r], __shfl_xor_sync(0xffffffffu, mx[H][r], o));
                mn[H][r] = fminf(mn[H][r], __shfl_xor_sync(0xffffffffu, mn[H][r], o));
              }
#pragma unroll
          for (int H = 2 * hp; H < 2 * hp + 2; ++H)
#pragma unroll
            for (int r = 0; r < 2; ++r) { mx[H][r] *= -sc[r]; mn[H][r] = fmaf(mn[H][r], sc[r], mx[H][r]); }
        };
        auto fm = [&](int H) {
#pragma unroll
          for (int i = 0; i < 8; ++i) {
            const int r = i & 1;
            const float x0 = fmaf(QV(H, 2 * i), sc[r], mx[H][r]), x1 = fmaf(QV(H, 2 * i + 1), sc[r], mx[H][r]);
            ph[H][i >> 2][i & 3] = pack_bf16(ex2(x0), ex2(x1));
            ph[H][2 + (i >> 2)][i & 3] = pack_bf16(ex2(mn[H][r] - x0), ex2(mn[H][r] - x1));
          }
        };
        auto conv = [&](int hp) {
          mbar_wait(BA(hp ? B_KVF1 : B_KVF), (layer >> 1) & 1);
          PROFT(tid_ == 128, layer * 16 + (hp ? 4 : 5));
          if (hp) nbar_dyn(3 + wu, 128);
#pragma unroll
          for (int h = 0; h < 2; ++h) {
            uint4 u[4];
#pragma unroll
            for (int i = 0; i < 4; ++i) u[i] = lds128(sb + VB + hp * SLOT + h * 8192 + (wq * 128 + i * 32 + lane) * 16);
            const float zz = lds_f(sb + SM_AP + ((2 * hp + h) * 64 + wq * 16 + (lane & 7) * 2 + ((lane >> 3) & 1)) * 4);
            const uint32_t kb_ = sb + PH + wg * SLOT + h * 8192 + (wq * 16 + lrow) * 128;
#pragma unroll
            for (int i = 0; i < 4; i += 2)
              stsm_x4(kb_ + (X ^ (i << 4)),
                      pack_bf16(__uint_as_float(u[i].x), __uint_as_float(u[i].y)), pack_bf16(__uint_as_float(u[i].z), __uint_as_float(u[i].w)),
                      pack_bf16(__uint_as_float(u[i + 1].x), __uint_as_float(u[i + 1].y)), pack_bf16(__uint_as_float(u[i + 1].z), __uint_as_float(u[i + 1].w)));
            const uint32_t z1 = pack_bf16(zz, 1.f);
            if (lane < 16) sts128(kb_ + ((4 ^ (lane & 7)) << 4), make_uint4(z1, z1, z1, z1));
          }
          fence_async_smem();
        };
        mnx(0);
        fm(0);
        if (CV0) conv(0);
        fm(1);
        if (!CV0) conv(0);
#pragma unroll
        for (int hp = 0; hp < 2; ++hp) {
          nbar_dyn(3 + wu, 128);
          float oa[4][20];
          wgmma_fence();
#pragma unroll
          for (int s = 0; s < 2; ++s)
#pragma unroll
            for (int v = 0; v < 4; ++v) {
              const int h = v >> 1, s4 = 2 * (v & 1) + s;
              wgmma_n40_rs(oa[v], ph[2 * hp + h][s4], D128(dB0 + (PH >> 4) + wu * 1024 + h * 512 + (s4 ^ (2 * h)) * 128), s != 0);
            }
          wgmma_commit();
          if (hp == 0) mnx(1);
          wgmma_wait<0>();
#pragma unroll
          for (int i = 0; i < 20; ++i) asm volatile("" : "+f"(oa[0][i]), "+f"(oa[1][i]), "+f"(oa[2][i]), "+f"(oa[3][i]) :: "memory");
          uint32_t ow[2][2][4];
#pragma unroll
          for (int h = 0; h < 2; ++h)
#pragma unroll
            for (int r = 0; r < 2; ++r) {
              const float a = oa[2 * h + 1][17 + 2 * r], b = oa[2 * h][17 + 2 * r];
              const float id = rcp(fmaf(oa[2 * h][16 + 2 * r], a, fmaf(a, 1e-6f, oa[2 * h + 1][16 + 2 * r]) * b));
              const float fa = a * id, fb = b * id;
#pragma unroll
              for (int j = 0; j < 4; ++j)
                ow[h][r][j] = pack_bf16(fmaf(oa[2 * h][4 * j + 2 * r], fa, oa[2 * h + 1][4 * j + 2 * r] * fb),
                                        fmaf(oa[2 * h][4 * j + 2 * r + 1], fa, oa[2 * h + 1][4 * j + 2 * r + 1] * fb));
            }
#pragma unroll
          for (int i = 0; i < 16; ++i) of[4 * hp + (i >> 2)][i & 3] = ow[i >> 3][i & 1][(i >> 1) & 3];
          if (hp == 0) {
#pragma unroll
            for (int i = 0; i < 8; ++i) {
              if (!(i & 1)) stg128(g_o + gfr + ((i >> 1) & 1) * 8 * D_ + (i >> 2) * 32, ow[i >> 2][(i >> 1) & 1][0], ow[i >> 2][(i >> 1) & 1][1], ow[i >> 2][(i >> 1) & 1][2], ow[i >> 2][(i >> 1) & 1][3]);
              const int r = i & 1;
              const float x0 = fmaf(QV(2, 2 * i), sc[r], mx[2][r]), x1 = fmaf(QV(2, 2 * i + 1), sc[r], mx[2][r]);
              ph[2][i >> 2][i & 3] = pack_bf16(ex2v(x0), ex2v(x1));
              ph[2][2 + (i >> 2)][i & 3] = pack_bf16(ex2v(mn[2][r] - x0), ex2v(mn[2][r] - x1));
            }
            __syncwarp();
            if (lane == 0) mbar_arrive(BA(B_OH0));
            PROFT(tid_ == 128 && layer, layer * 16 + 15);
            if (QORD) { fm(3); conv(1); } else { conv(1); fm(3); }
          } else {
#pragma unroll
            for (int i = 0; i < 16; ++i) o1[i >> 2][i & 3] = ow[i >> 3][(i >> 2) & 1][i & 3];
          }
        }
      }
      PROFT(tid_ == 128, layer * 16 + 6);
    }
    {
      PHASE_CTX();
      MMA_CTX();
      auto o1st = [&]() {
#pragma unroll
        for (int i = 0; i < 4; ++i) stg128(g_o + gfr + (i & 1) * 8 * D_ + (2 + (i >> 1)) * 32, o1[i][0], o1[i][1], o1[i][2], o1[i][3]);
        __syncwarp();
        if (lane == 0) { mbar_arrive(BA(B_OH1)); if (!O1P) REL2(B_EF); }
        PROFT(lane == 0 && layer == PL, 208 + cw);
      };
      if (O1P) {
        __syncwarp();
        if (lane == 0) REL2(B_EF);
      } else o1st();
      mbar_wait(BA(FW), par);
      mbar_wait(BA(FW + 1), par);
      if (O1P == 1) o1st();
#pragma unroll
      for (int i = 0; i < 2; ++i) {
        wgmma_fence();
#pragma unroll
        for (int k = 0; k < 4; ++k) {
          if (i + k) wgmma_n128_rs(acc, of[4 * i + k], D128(dB0 + (uint32_t)((WO_B >> (4 * i)) & 15) * 1024 + k * 128), 1);
          else wgmma_n128_rs0(acc, of[0], D128(dB0 + (uint32_t)(WO_B & 15) * 1024));
        }
        wgmma_commit();
        if (O1P == 2 && i == 0) o1st();
      }
      wgmma_wait<1>();
      if (elected) REL2(CW);
      uint64_t ta = WO_A >> 8, tw = WO_B >> 8;
      auto run = [&](int i0, int i1) {
#pragma unroll 1
        for (int i = i0; i < i1; ++i) {
          mbar_wait(BA(FW + i), par);
          PROFL(tid_ == 128 && layer == PL, 160 + i);
          const uint32_t da = dA0 + ((uint32_t)ta & 15) * 1024, db = dB0 + ((uint32_t)tw & 15) * 1024;
          ta >>= 4; tw >>= 4;
          wgmma_fence();
#pragma unroll
          for (int k = 0; k < 4; ++k) wgmma_n128(acc, D128(da + k * 2), D128(db + k * 128), 1);
          wgmma_commit();
          wgmma_wait<1>();
          if (elected) REL2(CW + i - 1);
        }
      };
      run(2, XRAT);
#pragma unroll
      for (int j = 0; j < 8 / XRN; ++j) {
#pragma unroll
        for (int i = j * XRN; i < (j + 1) * XRN; ++i) ldg128((layer ? g_x : c.x0) + gfr + (i & 1) * 8 * D_ + (i >> 1) * 32, xp[i][0], xp[i][1], xp[i][2], xp[i][3]);
        run(XRAT + j, j + 1 < 8 / XRN ? XRAT + j + 1 : 16 - SKW);
      }
      if (SKW) {
        const bool on = SKL || layer == NLAYERS - 1;
        if (on && wu == 0) nbar<6, 256>();
        run(16 - SKW, 16);
        if (on && wu) asm volatile("bar.arrive 6, 256;" ::: "memory");
        if (SKL == 1 && wu == 0 && layer != NLAYERS - 1) asm volatile("bar.arrive 7, 256;" ::: "memory");
      }
      if (layer == 0) {
#pragma unroll
        for (int o = 1; o <= 2; o <<= 1)
#pragma unroll
          for (int i = 0; i < 16; ++i) {
            const int j = o == 1 ? 2 * (i & 1) : (i & 1);
            uint32_t &a = xp[i >> 1][j], &b = xp[i >> 1][j + o];
            const uint32_t r = __shfl_xor_sync(0xffffffffu, (t & o) ? a : b, o);
            if (t & o) a = r; else b = r;
          }
      }
      wgmma_wait<0>();
#pragma unroll
      for (int i = 128; i < 192; ++i) asm volatile("" : "+f"(acc[i]) :: "memory");
      if (elected) REL2(CW + 15);
      PROFT(lane == 0 && layer == PL, 216 + cw);
      PROFT(tid_ == 128, layer * 16 + 7);
    }
    {
      PHASE_CTX();
#pragma unroll
      for (int i = 0; i < 32; ++i)
        xp[i >> 2][i & 3] = add_bf16x2(xp[i >> 2][i & 3], pack_bf16(acc[128 + 16 * (i >> 3) + 4 * (i & 3) + 2 * ((i >> 2) & 1)], acc[129 + 16 * (i >> 3) + 4 * (i & 3) + 2 * ((i >> 2) & 1)]));
      if (layer == NLAYERS - 1) {
#pragma unroll
        for (int i = 0; i < 8; ++i) stsm_x4(sb + (XS + (i >> 2)) * SLOT + (Y ^ ((i & 2) << 5)) + (i & 1) * 1024, xp[i][0], xp[i][1], xp[i][2], xp[i][3]);
        __syncwarp();
        slab_out_half(sb + XS * SLOT, c.out + (size_t)m0 * D_ + g * 128, wrow0, lane);
        slab_out_half(sb + (XS + 1) * SLOT, c.out + (size_t)m0 * D_ + g * 128 + 64, wrow0, lane);
        PROFT(tid_ == 128, layer * 16 + 24);
        break;
      }
#pragma unroll
      for (int i = 0; i < 4; ++i) stg128(g_x + gfr + (i & 1) * 8 * D_ + (i >> 1) * 32, xp[i][0], xp[i][1], xp[i][2], xp[i][3]);
      __syncwarp();
      if (lane == 0) mbar_arrive(BA(B_XH0));
      if (SKW && SKL == 1 && wg) nbar<7, 256>();
#pragma unroll
      for (int i = 0; i < 16; ++i) xf[i >> 2][i & 3] = xp[2 * (i >> 3) + (i & 1)][(i >> 1) & 3];
      PROFT(tid_ == 128, layer * 16 + 24);
    }
  }
}

__device__ __forceinline__ uint64_t k_order(int o) {
  const uint32_t lo = (1u << (4 * o)) - 1u, h0 = (0xECA86420u & lo) | ((0xECA86420u >> 4) & ~lo);
  return (uint64_t)(2 * o) | ((uint64_t)(2 * o + 1) << 4) | ((uint64_t)(h0 & 0xFFFFFFFu) << 8) | ((uint64_t)((h0 & 0xFFFFFFFu) | 0x1111111u) << 36);
}

__global__ void __cluster_dims__(2, 1, 1) __launch_bounds__(384, 1)
mega_kernel(const __grid_constant__ Maps maps, const __grid_constant__ Ctx c, const bf16* __restrict__ wA, const bf16* __restrict__ wB,
            const bf16* __restrict__ woA, const bf16* __restrict__ woB) {
  if (blockIdx.x - c.boff >= 128u) {
    const unsigned int epoch = ld_relaxed(&g_epoch);
    const int e = (blockIdx.x - c.boff) & 3, tid = threadIdx.x;
    float s[8] = {0.f, 0.f, 0.f, 0.f, 0.f, 0.f, 0.f, 0.f};
    const uint32_t sb = smem_u32(smem_raw), bar = sb + SM_BAR;
    auto issue = [&](int i) {
      mbar_expect_tx(BA(i & 3), 49152);
      bulk_load(sb + (i & 3) * 49152, wB + (size_t)e * 256 * 3072 + i * 24576, 49152, BA(i & 3));
    };
    if (tid == 0) {
#pragma unroll 1
      for (int i = 0; i < 4; ++i) {
        mbar_init(BA(i), 1);
        fence_async_smem();
        issue(i);
      }
    }
    __syncthreads();
#pragma unroll 1
    for (int i = 0; i < 32; ++i) {
      mbar_wait(BA(i & 3), (i >> 2) & 1);
#pragma unroll
      for (int r = 0; r < 8; ++r) {
        const uint4 v = lds128(sb + (i & 3) * 49152 + r * 6144 + tid * 16);
        s[0] += bf_lo(v.x); s[1] += bf_hi(v.x); s[2] += bf_lo(v.y); s[3] += bf_hi(v.y);
        s[4] += bf_lo(v.z); s[5] += bf_hi(v.z); s[6] += bf_lo(v.w); s[7] += bf_hi(v.w);
      }
      __syncthreads();
      if (tid == 0 && i < 28) issue(i + 4);
    }
    float* cd = g_cs + (epoch & 1) * 6144 + 3072 + ((tid >> 4) & 7) * 384 + (tid < 128 ? 256 : (tid >> 7) * 128 - 128) + (tid & 15) * 8;
    red_add4(cd, s[0], s[1], s[2], s[3]);
    red_add4(cd + 4, s[4], s[5], s[6], s[7]);
    __syncthreads();
    if (tid == 0) flag_add(&g_csflag[8].v);
    const int op = (epoch & 1) ^ 1;
    float4* kz = reinterpret_cast<float4*>(g_kv + (size_t)op * (2 * 8 * 8448)) + e * 8448;
#pragma unroll 2
    for (int i = tid; i < 8448; i += 384) kz[i] = make_float4(0.f, 0.f, 0.f, 0.f);
    reinterpret_cast<float4*>(g_cs + op * 6144)[e * 384 + tid] = make_float4(0.f, 0.f, 0.f, 0.f);
#pragma unroll 1
    for (int i = tid; i < 1024; i += 384) reinterpret_cast<float4*>(g_stats + (op * 4 + e) * S_)[i] = make_float4(0.f, 0.f, 0.f, 0.f);
    return;
  }
  const int warp = __shfl_sync(0xffffffffu, threadIdx.x >> 5, 0), lane = threadIdx.x & 31;
  if (smem_u32(smem_raw) != SB0 + ((blockIdx.x & 1) << 24)) __trap();
  {
  const int cid = (blockIdx.x - c.boff) >> 1, u7 = ((cid - 36) * 37) >> 8, cr = blockIdx.x & 1;
  const int g = cid < 4 ? 4 + cid : cid < 36 ? (cid - 4) >> 3 : 4 + u7, rb = (cid < 4 ? 0 : cid < 36 ? (cid - 4) & 7 : cid - 35 - 7 * u7) * 2 + cr, m0 = rb * 128;
  const uint32_t sb = SB0 + (cr << 24), bar = sb + SM_BAR;
  PROFT(lane == 0 && (warp == 0 || warp == 4), 224 + (warp >> 2) * 8);
  uint32_t cx = 0;
  if (warp == 2) {
    if (lane < NMAP) asm volatile("prefetch.tensormap [%0];" ::"l"(&maps.m[lane]) : "memory");
    if (lane == 31) asm volatile("prefetch.global.L2 [%0];" ::"l"(&g_epoch));
  } else if (warp == 3) {
    cx = c_map[cid] + c_wop[lane] + c_wop[NWOP - lane] + c_aop[lane] + c_aop[NAOP - lane] + (uint32_t)(uintptr_t)g_x;
  } else if (PFW && warp >= 4) {
    const int i = threadIdx.x - 128;
    asm volatile("prefetch.global.L2 [%0];" ::"l"(wA + (size_t)(rb * 64 + ((i >> 1) & 63)) * 3072 + (i >> 7) * 1024 + g * 128 + (i & 1) * 64));
  }
  if (warp < 2) {
    const int s = warp, kb = (rb & ~1) + s;
    if (lane == 0) {
      mbar_init(BA(FM + s), 1u);
      mbar_init(BA(B_RAW + warp), 1u);
      if (warp) mbar_init(BA(B_X0), 1u);
      asm volatile("fence.mbarrier_init.release.cluster;" ::: "memory");
    }
    __syncwarp();
    if (warp == 0) tma_2d_e(sb + SM_SD, &maps.m[MAP_PHI], 0, g * 128, BA(B_RAW));
    else if (W1DL) __nanosleep(W1DL);
#pragma unroll
    for (int j = 0; j < 6; ++j)
      tma_5d_e(sb + (j < 2 ? 2 * s : j < 4 ? 9 + s : 2 * s + 1) * SLOT + (j & 1) * 8192, &maps.m[MAP_WA], (j < 2 ? 1024 : j < 4 ? 0 : 2048) + g * 128 + (j & 1) * 64, 2 * kb,
               BA(j < 4 ? B_RAW + warp : FM + s));
    tma_2d_e(sb + (XS + s) * SLOT, &maps.m[MAP_X0], kb * 64, m0, BA(FM + s));
    expect_tx_e(BA(B_RAW + warp), warp ? 32768 : 32768 + 8192);
    expect_tx_e(BA(FM + s), 32768);
    if (X0AT == 0 && warp == 1) {
      tma_2d_e(sb + 11 * SLOT, &maps.m[MAP_X0], g * 128, m0, BA(B_X0));
      tma_2d_e(sb + 12 * SLOT, &maps.m[MAP_X0], g * 128 + 64, m0, BA(B_X0));
      expect_tx_e(BA(B_X0), 32768);
    }
  } else if (warp >= 4 && lane == 0) {
#pragma unroll 1
    for (int i = 2 + (warp - 4) * 13; i < 15 + (warp - 4) * 13; ++i)
      mbar_init(BA(i), 1u << ((i < CM ? 0u : i < B_EF ? 2u : (uint32_t)(BAR_LG >> (4 * ((i - B_EF) & 15)))) & 7u));
    asm volatile("fence.mbarrier_init.release.cluster;" ::: "memory");
  }
  __syncwarp();
  asm volatile("barrier.cluster.arrive.relaxed.aligned;" ::: "memory");
  if (threadIdx.x == 96 + c.zero) sts_f(sb + SM_EPOCH + 4, __uint_as_float(cx));
  PROFT(lane == 0 && (warp == 0 || warp == 4), 225 + (warp >> 2) * 8);
  __syncwarp();
  PROFT(lane == 0 && (warp == 0 || warp == 4), 226 + (warp >> 2) * 8);
  }

  if (warp < 4) {
    asm volatile("setmaxnreg.dec.sync.aligned.u32 40;");
    PROFT(threadIdx.x == 0, 227);
    cluster_wait();
    PROFT(threadIdx.x == 0, 228);
    if (warp == 0 || warp == 3) {
    if (warp == 0) {
      BLK_CTX();
      const unsigned int epoch = __shfl_sync(0xffffffffu, ld_relaxed(&g_epoch), 0), xbase = epoch * NLAYERS;
      (void)xbase;
      const uint64_t ordg = k_order(g);
      if (X0AT) {
        mbar_wait_u(BA(B_RAW + X0AT - 1), 0);
        tma_2d_e(sb + 11 * SLOT, &maps.m[MAP_X0], g * 128, m0, BA(B_X0));
        tma_2d_e(sb + 12 * SLOT, &maps.m[MAP_X0], g * 128 + 64, m0, BA(B_X0));
        expect_tx_e(BA(B_X0), 32768);
      }
#pragma unroll 1
      for (int lp = 0; lp < 2 * NLAYERS; ++lp) {
        const int layer = lp >> 1, n1 = (lp & 1) ? NAOP : NAOP - 14;
        int n = (lp & 1) ? NAOP - 14 : 0;
        const uint64_t ord = lp ? ordg : k_order(rb >> 1);
        uint32_t ready = lp ? 0u : 0xFFFFu, nop = c_aop[n];
        const unsigned int* fl = ((lp & 1) ? g_of : g_xf) + rb * 32;
        const CUtensorMap* tm = &maps.m[(lp & 1) ? MAP_O : lp ? MAP_X : MAP_X0];
        const uint32_t skip = layer ? 1u << 25 : 9u << 22;
#pragma unroll 1
        for (; n < n1; ++n) {
          const uint32_t op = nop;
          nop = c_aop[n + 1];
          const uint32_t kb = (uint32_t)(ord >> ((op >> 2) & 60)) & 15;
          uint32_t dst = sb + (op & 15) * SLOT, kc = kb * 64, fb = bar + ((op >> 5) & 0x3F8), need = ~ready & (1u << kb);
          asm volatile("" : "+r"(dst), "+r"(kc), "+r"(fb), "+r"(need));
          if (!(op & skip)) mbar_wait_u(bar + ((op >> 12) & 0x3F8), (layer ^ (op >> 22)) & 1);
          if (need) {
            PROFT(lane == 0 && (n == 0 || n == NAOP - 14), 64 + layer * 16 + (n ? 2 : 0));
            if (FASTP) src_wait_fast(fl, xbase + layer + 1, need, ready, lane);
            else src_wait<0>(fl, xbase + layer + 1, need, ready, lane);
            fence_async_all();
          }
          tma_2d_e(dst, tm, kc, m0, fb);
          PROFT(lane == 0 && (n == 0 || n == NAOP - 14), 64 + layer * 16 + (n ? 3 : 1));
          PROFL(lane == 0 && layer == PL && n >= NAOP - 14, 178 + n - (NAOP - 14));
          PROFL(lane == 0 && layer == PL + 1 && n < 4, 242 + n);
        }
      }
    } else {
      BLK_CTX();
      const unsigned int epoch = __shfl_sync(0xffffffffu, ld_relaxed(&g_epoch), 0), xbase = epoch * NLAYERS;
      (void)xbase;
      const uint64_t ordg = k_order(g);
#pragma unroll 1
      for (int layer = 0; layer < NLAYERS; ++layer) {
        const uint64_t ordq = layer ? ordg : k_order(rb >> 1);
        uint32_t ready = layer ? 0xFFFFu : 0u, nop = c_wop[0];
        const CUtensorMap* tq = &maps.m[(layer & 1) ? MAP_WB : MAP_WF];
        const CUtensorMap* tk = &maps.m[(layer & 1) ? MAP_WB : cr ? MAP_WA : MAP_WF];
        const uint32_t skip = layer ? 1u << 25 : 9u << 22, pm = layer ? 0xE0u : 0u;
        int n = 0;
#pragma unroll 1
        for (; n < NWOP - 16; ++n) {
          const uint32_t op = nop;
          nop = c_wop[n + 1];
          const uint32_t isq = (op >> 23) & 1, fb = bar + ((op >> 5) & 0x3F8);
          const uint32_t kb = (uint32_t)(ordq >> ((op >> 2) & 60)) & 15;
          const CUtensorMap* tm = (isq ? tq : tk) + ((op & pm) ? 1 : 0);
          const uint32_t dst = sb + (op & 15) * SLOT + cr * (isq ? 8192 : SLOT);
          const int col = g * 128 + (isq ? cr * 64 : 1024 + cr * 1024);
          if (layer == 0) {
            if ((op & 0x7E00) == 0) continue;
            const uint32_t need = ((isq || !cr) ? 1u << kb : 0u) | (((op >> 22) & 1) ? 0u : (((op >> 15) & 127) == CM ? 1u : 3u) << (rb & ~1));
            if ((ready & need) != need) {
              src_wait<0>(g_wff + g * 32, epoch + 1, need, ready, lane);
              fence_async_all();
            }
            if ((op & 15) >= 11) mbar_wait_u(BA(B_XT), 0);
          }
          wait_tma_5d_mc(!(op & skip), bar + ((op >> 12) & 0x3F8), (layer ^ (op >> 22)) & 1, dst, tm, col, 2 * kb, fb);
          if (!isq) tma_5d_mc_e(dst + 8192, tm, col + 64, 2 * kb, fb);
          if (op >> 26) expect_tx_e(fb, (op >> 26) * 8192);
          PROFL(lane == 0 && layer == PL + 1 && n < 16, 128 + n);
        }
        const CUtensorMap* to = &maps.m[(layer & 1) ? MAP_WOB : MAP_WOA];
#pragma unroll 1
        for (; n < NWOP; ++n) {
          const uint32_t op = nop;
          nop = c_wop[n + 1];
          const uint32_t fb = bar + ((op >> 5) & 0x3F8), kb = (uint32_t)(ordg >> ((op >> 2) & 60)) & 15;
          wait_tma_5d_mc(!((op >> 25) & 1), bar + ((op >> 12) & 0x3F8), layer & 1, sb + (op & 15) * SLOT + cr * 8192, to + ((op & 0xE0) ? 1 : 0), g * 128 + cr * 64, 2 * kb, fb);
          expect_tx_e(fb, (op >> 26) * 8192);
          PROFL(lane == 0 && layer == PL, 144 + ((op >> 8) & 127) - FW);
        }
      }
    }
    } else if (warp == 1) {
      BLK_CTX();
      const unsigned int epoch = __shfl_sync(0xffffffffu, ld_relaxed(&g_epoch), 0), xbase = epoch * NLAYERS;
      (void)xbase;
      if (lane == 0) {
        mbar_wait(BA(B_WFD), 0);
        PROFT(true, 229);
        if (WFDL && cr) __nanosleep(WFDL);
#pragma unroll 1
        for (int j = 0; j < 4; ++j) tma_store_5d(&maps.m[MAP_WF], sb + (j < 2 ? 2 * cr : 9 + cr) * SLOT + (j & 1) * 8192, (j < 2 ? 1024 : 0) + g * 128 + (j & 1) * 64, 2 * rb);
        bulk_commit();
        bulk_wait0();
        PROFT(true, 230);
        fence_async_all();
        flag_set(g_wff + g * 32 + rb, epoch + 1);
        PROFT(true, 64 + 13);
#pragma unroll 1
        for (int e = 0; e < NLAYERS; ++e) {
          BLK_CTX();
          if (e > 0) {
            mbar_wait(BA(B_XH0), (e - 1) & 1);
            PROFT(e == PL + 1, 240);
            flag_set(g_xf + rb * 32 + 2 * g, xbase + e + 1);
            PROFT(e == PL + 1, 241);
          }
          mbar_wait(BA(B_XDONE), e & 1);
          PROFT(true, 64 + e * 16 + 4);
          flag_set(g_xf + rb * 32 + 2 * g + 1, xbase + e + 1);
          if (e == 0) {
            flag_add(&g_csflag[g].v);
            l2_prefetch(wB + (size_t)bid_ * 24576, 49152);
            l2_prefetch(woA + (size_t)bid_ * 8192, 16384);
            l2_prefetch(woB + (size_t)bid_ * 8192, 16384);
          }
          PROFT(true, 64 + e * 16 + 7);
          if ((e & 1) == 0) {
            float* kvl = g_kv + ((size_t)((epoch & 1) * 2 + (e >> 1)) * 8 + g) * 8448;
#pragma unroll 1
            for (int hp = 0; hp < 2; ++hp) {
              mbar_wait(BA(B_KVDONE), hp);
              bulk_red_add(kvl + 8192 + hp * 128, sb + SM_AP + hp * 512, 512);
#pragma unroll 1
              for (int i = 0; i < NCH; ++i) {
                const int ch = hp * NCH + ((i + rb * NCH / 16) & (NCH - 1));
                bulk_red_add(kvl + ch * (4096 / NCH), sb + VB + ch * (16384 / NCH), 16384 / NCH);
                bulk_commit();
                asm volatile("cp.async.bulk.wait_group %0;" :: "n"(CHW) : "memory");
              }
              bulk_wait0();
              PROFT(true, 64 + e * 16 + (hp ? 10 : 6));
              fence_async_all();
              flag_add(&g_kvflag[hp * 8 + g].v);
              PROFT(e > 0 && hp, 64 + e * 16 + 8);
            }
          }
          if (e & 1) {
            mbar_wait(BA(B_OF0), (e >> 1) & 1);
            flag_set(g_hf + rb * 32 + g, xbase + e + 1);
            if (rb) flag_wait(g_hf + (rb - 1) * 32 + g, xbase + e + 1);
            fence_async_all();
            mbar_expect_tx(BA(B_HALO), 8192);
            bulk_load(sb + SM_SD, g_halo + (size_t)(((e >> 1) * 17 + rb) * 8 + g) * 2048, 8192, BA(B_HALO));
            PROFT(true, 64 + e * 16 + 15);
          }
          mbar_wait(BA(B_OH0), e & 1);
          PROFT(e > 0, 64 + e * 16 + 13);
          flag_set(g_of + rb * 32 + 2 * g, xbase + e + 1);
          PROFT(true, 64 + e * 16 + 9);
          mbar_wait(BA(B_OH1), e & 1);
          PROFT(true, 64 + e * 16 + 5);
          flag_set(g_of + rb * 32 + 2 * g + 1, xbase + e + 1);
          PROFT(true, 64 + e * 16 + 11);
        }
        if (bid_ == 0) g_epoch = epoch + 1;
      }
    } else {
      BLK_CTX();
      const unsigned int epoch = __shfl_sync(0xffffffffu, ld_relaxed(&g_epoch), 0), xbase = epoch * NLAYERS;
      (void)xbase;
      if (lane < 16) sts_f(sb + SM_RS + lane * 4, 0.f);
#pragma unroll 1
      for (int layer = 0; layer < NLAYERS; ++layer) {
#define HLP_CTX() BLK_CTX(); int lane = threadIdx.x & 31; asm volatile("" : "+r"(lane)); const bool isB = layer & 1, hal = isB && rb > 0; (void)hal;
#pragma unroll 1
        for (int ph = 0; ph < 2; ++ph) {
          HLP_CTX();
          if (ph == (layer == 0)) {
            const float* cs = g_cs + (epoch & 1) * 6144 + g * 384;
            if (layer) mbar_wait_u(BA(CT), (layer - 1) & 1);
            if (layer < 2) {
              if (lane == 0) flag_wait_slow(&g_csflag[isB ? 8 : g].v, isB ? epoch * 4u + 4u : epoch * 16u + 16u);
              __syncwarp();
            }
            float a[12];
#pragma unroll
            for (int i = 0; i < 12; ++i) a[i] = __ldcg(cs + isB * 3072 + i * 32 + lane);
#pragma unroll
            for (int i = 0; i < 12; ++i) {
              const float c1 = bf16r(a[i]), c2 = bf16r(a[i] - c1), c3 = (a[i] - c1) - c2;
              sts128(sb + SM_BP + (i * 32 + lane) * 16, make_uint4(pack_bf16(c1, c2), pack_bf16(c3, 0.f), 0u, 0u));
            }
          } else {
            uint32_t rdy = 0u;
            src_wait<128>(g_xf + rb * 32, xbase + layer + 1, 0xAAAAu, rdy, lane);
            rdy = 0u;
            if (hal) src_wait<128>(g_xf + (rb - 1) * 32, xbase + layer + 1, 0xAAAAu, rdy, lane);
            const float2* sp = g_stats + ((epoch & 1) * 4 + layer) * S_ + m0 + lane;
            float2 u[5];
#pragma unroll
            for (int i = 0; i < 4; ++i) u[i] = __ldcg(sp + i * 32);
            u[4] = __ldcg(sp - (hal ? 16 : 0));
#pragma unroll
            for (int i = 0; i < 5; ++i) {
              const float mean = u[i].x * (1.f / D_);
              const float var = fmaxf(fmaf(-u[i].x, mean, u[i].y) * (1.f / D_), 0.f);
              const float sd = bf16r(sqrtf(bf16r(bf16r(var) + 1e-5f)));
              const int R = i * 32 + lane;
              if (i < 4) {
                const float hm = -0.5f * bf16r(mean);
                sts_f(sb + SM_RS + (16 + R) * 4, __fdividef(1.f, sd));
                if (!isB) sts128(sb + SM_SD + R * 64 + ((R >> 1) & 3) * 16, make_uint4(__float_as_uint(sd) >> 16, 0u, 0u, 0u));
                sts128(sb + SM_AP + R * 16, make_uint4(pack_bf16(hm, hm), pack_bf16(hm, 0.f), 0u, 0u));
              } else if (hal && lane < 16) sts_f(sb + SM_RS + lane * 4, __fdividef(1.f, sd));
            }
            PROFT(lane == 0, 64 + layer * 16 + 12);
          }
        }
        HLP_CTX();
        fence_async_smem();
        __syncwarp();
        if (lane == 0) mbar_arrive(BA(B_STAT));
        PROFT(lane == 0, 64 + layer * 16 + 14);
        if (!isB && lane == 0) {
#pragma unroll 1
          for (int hp = 0; hp < 2; ++hp) {
            mbar_wait(BA(B_KVDONE), hp);
            flag_wait(&g_kvflag[hp * 8 + g].v, epoch * (16u * ((NLAYERS + 1) / 2)) + 16u * ((layer >> 1) + 1));
            const float* kvl = g_kv + ((size_t)((epoch & 1) * 2 + (layer >> 1)) * 8 + g) * 8448;
            const uint32_t kb = BA(hp ? B_KVF1 : B_KVF);
            fence_async_all();
            mbar_expect_tx(kb, 16384 + 512);
            bulk_load(sb + VB + hp * SLOT, kvl + hp * 4096, 16384, kb);
            bulk_load(sb + SM_AP + hp * 512, kvl + 8192 + hp * 128, 512, kb);
            PROFT(hp == 0, 64 + layer * 16 + 15);
          }
        }
        __syncwarp();
      }
    }
    __syncwarp();
    asm volatile("barrier.cluster.arrive.relaxed.aligned;" ::: "memory");
    cluster_wait();
  } else {
    asm volatile("setmaxnreg.inc.sync.aligned.u32 232;");
    PROFT(threadIdx.x == 128, 235);
    cluster_wait();
    PROFT(threadIdx.x == 128, 236);
    consumer(c);
    asm volatile("bar.warp.sync 0xffffffff;\nbarrier.cluster.arrive.relaxed.aligned;\nbarrier.cluster.wait.aligned;\n" ::: "memory");
  }
}

typedef CUresult (*PFN_encodeTiled)(CUtensorMap*, CUtensorMapDataType, cuuint32_t, void*, const cuuint64_t*, const cuuint64_t*,
                                    const cuuint32_t*, const cuuint32_t*, CUtensorMapInterleave, CUtensorMapSwizzle,
                                    CUtensorMapL2promotion, CUtensorMapFloatOOBfill);

static void make_map2(PFN_encodeTiled enc, CUtensorMap* m, const void* ptr, uint64_t cols, uint64_t rows, uint32_t box_c, uint32_t box_r) {
  cuuint64_t dims[2] = {cols, rows};
  cuuint64_t strides[1] = {cols * 2};
  cuuint32_t box[2] = {box_c, box_r};
  cuuint32_t es[2] = {1, 1};
  CUresult r = enc(m, CU_TENSOR_MAP_DATA_TYPE_BFLOAT16, 2, const_cast<void*>(ptr), dims, strides, box, es, CU_TENSOR_MAP_INTERLEAVE_NONE,
                   box_c == 64 ? CU_TENSOR_MAP_SWIZZLE_128B : CU_TENSOR_MAP_SWIZZLE_64B, CU_TENSOR_MAP_L2_PROMOTION_L2_256B, CU_TENSOR_MAP_FLOAT_OOB_FILL_NONE);
  (void)r;
}
static void make_map5(PFN_encodeTiled enc, CUtensorMap* m, const void* ptr, uint64_t cols) {
  for (int p = 0; p < 2; ++p) {
    cuuint64_t dims[5] = {cols, 2, 4, 4, 32};
    cuuint64_t strides[4] = {cols * 2, cols * (p ? 16 : 4), cols * (p ? 4 : 16), cols * 64};
    cuuint32_t box[5] = {64, 2, 4, 4, 2};
    cuuint32_t es[5] = {1, 1, 1, 1, 1};
    CUresult r = enc(m + p, CU_TENSOR_MAP_DATA_TYPE_BFLOAT16, 5, const_cast<void*>(ptr), dims, strides, box, es, CU_TENSOR_MAP_INTERLEAVE_NONE,
                     CU_TENSOR_MAP_SWIZZLE_128B, CU_TENSOR_MAP_L2_PROMOTION_L2_256B, CU_TENSOR_MAP_FLOAT_OOB_FILL_NONE);
    (void)r;
  }
}

extern "C" void kernel_launch(void* const* d_in, const int* in_sizes, int n_in, void* d_out, int out_size) {
  const bf16* A_x = (const bf16*)d_in[0];
  const bf16* A_wqkv = (const bf16*)d_in[1];
  const bf16* A_wphi = (const bf16*)d_in[2];
  const bf16* A_wo = (const bf16*)d_in[3];
  const bf16* B_wqkv = (const bf16*)d_in[5];
  const bf16* B_wo = (const bf16*)d_in[6];
  bf16* out = (bf16*)d_out;

  static PFN_encodeTiled enc = nullptr;
  static bf16 *p_x, *p_o, *p_wf;
  static uint32_t boff;
  if (!enc) {
    void* fn = nullptr; cudaDriverEntryPointQueryResult qr;
    cudaGetDriverEntryPoint("cuTensorMapEncodeTiled", &fn, cudaEnableDefault, &qr);
    enc = (PFN_encodeTiled)fn;
    cudaGetSymbolAddress((void**)&p_x, g_x);
    cudaGetSymbolAddress((void**)&p_o, g_o);
    cudaGetSymbolAddress((void**)&p_wf, g_wf);
    cudaFuncSetAttribute(mega_kernel, cudaFuncAttributeMaxDynamicSharedMemorySize, SM_TOTAL);
    cudaLaunchConfig_t cfg = {};
    cudaLaunchAttribute at; at.id = cudaLaunchAttributeClusterDimension; at.val.clusterDim.x = 2; at.val.clusterDim.y = 1; at.val.clusterDim.z = 1;
    cfg.gridDim = dim3(132); cfg.blockDim = dim3(384); cfg.dynamicSmemBytes = SM_TOTAL; cfg.attrs = &at; cfg.numAttrs = 1;
    int nc = 0;
    if (cudaOccupancyMaxActiveClusters(&nc, mega_kernel, &cfg) != cudaSuccess) { nc = 0; (void)cudaGetLastError(); }
    boff = nc >= 66 ? 0u : 4u;
  }
  Maps maps;
  make_map5(enc, &maps.m[MAP_WF], p_wf, 2048);
  make_map5(enc, &maps.m[MAP_WA], A_wqkv, 3072);
  make_map5(enc, &maps.m[MAP_WB], B_wqkv, 3072);
  make_map5(enc, &maps.m[MAP_WOA], A_wo, 1024);
  make_map5(enc, &maps.m[MAP_WOB], B_wo, 1024);
  make_map2(enc, &maps.m[MAP_X0], A_x, 1024, 2048, 64, 128);
  make_map2(enc, &maps.m[MAP_X], p_x, 1024, 2048, 64, 128);
  make_map2(enc, &maps.m[MAP_O], p_o, 1024, 2048, 64, 128);
  make_map2(enc, &maps.m[MAP_PHI], A_wphi, 32, 1024, 32, 128);
  Ctx c; c.zero = 0u; c.boff = boff; c.x0 = A_x; c.out = out;
  mega_kernel<<<132, 384, SM_TOTAL, cudaStreamPerThread>>>(maps, c, A_wqkv, B_wqkv, A_wo, B_wo);
}
```

```cpp
#include <cuda_runtime.h>
#include <cuda_bf16.h>
#include <cuda.h>
#include <stdint.h>

typedef __nv_bfloat16 bf16;

constexpr int S_ = 2048, D_ = 1024;

struct __align__(128) Flag { unsigned int v; unsigned int pad[31]; };
__device__ __align__(1024) bf16 g_x[S_ * D_];
__device__ __align__(1024) bf16 g_o[S_ * D_];
__device__ __align__(1024) uint32_t g_halo[2 * 17 * 8 * 2048];
__device__ __align__(1024) float g_kv[2 * 2 * 8 * 8448];
__device__ __align__(1024) float2 g_stats[2 * 4 * S_];
__device__ __align__(1024) float g_cs[2 * 2 * 3072];
__device__ __align__(1024) bf16 g_wf[D_ * 2048];
__device__ Flag g_kvflag[16], g_csflag[13];
__device__ __align__(128) unsigned int g_xf[16 * 32], g_of[16 * 32];
__device__ __align__(128) unsigned int g_hf[16 * 32];
__device__ __align__(128) unsigned int g_wff[8 * 32];
__device__ unsigned int g_epoch, g_err;
#define PROFT(cond, idx) asm volatile("" ::: "memory")

#define PSL 100
__device__ __forceinline__ uint32_t smem_u32(const void* p) { return (uint32_t)__cvta_generic_to_shared(p); }
__device__ __forceinline__ void mbar_init(uint32_t bar, uint32_t count) {
  asm volatile("mbarrier.init.shared::cta.b64 [%0], %1;" ::"r"(bar), "r"(count) : "memory");
}
__device__ __forceinline__ void mbar_expect_tx(uint32_t bar, uint32_t bytes) {
  asm volatile("mbarrier.arrive.expect_tx.shared::cta.b64 _, [%0], %1;" ::"r"(bar), "r"(bytes) : "memory");
}
__device__ __forceinline__ void mbar_arrive(uint32_t bar) {
  asm volatile("mbarrier.arrive.shared::cta.b64 _, [%0];" ::"r"(bar) : "memory");
}
__device__ __forceinline__ bool mbar_try_wait(uint32_t bar, uint32_t parity) {
  uint32_t ok;
  asm volatile("{\n.reg .pred p;\nmbarrier.try_wait.parity.shared::cta.b64 p, [%1], %2;\nselp.b32 %0, 1, 0, p;\n}\n"
               : "=r"(ok) : "r"(bar), "r"(parity) : "memory");
  return ok != 0;
}
__device__ __forceinline__ bool mbar_test_wait(uint32_t bar, uint32_t parity) {
  uint32_t ok;
  asm volatile("{\n.reg .pred p;\nmbarrier.test_wait.parity.shared::cta.b64 p, [%1], %2;\nselp.b32 %0, 1, 0, p;\n}\n"
               : "=r"(ok) : "r"(bar), "r"(parity) : "memory");
  return ok != 0;
}
__device__ __forceinline__ uint64_t gtimer() {
  uint64_t t; asm volatile("mov.u64 %0, %globaltimer;" : "=l"(t)); return t;
}
__device__ __forceinline__ void mbar_wait(uint32_t bar, uint32_t parity) {
  uint32_t n = 0;
  bool ok;
#pragma unroll 1
  do { ++n; ok = mbar_try_wait(bar, parity); } while (!ok && n < (1u << 22));
}
__device__ __forceinline__ unsigned int ld_acquire(const unsigned int* p) {
  unsigned int v; asm volatile("ld.acquire.gpu.global.u32 %0, [%1];" : "=r"(v) : "l"(p) : "memory"); return v;
}
__device__ __forceinline__ void flag_add(unsigned int* p) {
  asm volatile("red.release.gpu.global.add.u32 [%0], 1;" ::"l"(p) : "memory");
}
__device__ __forceinline__ void flag_set(unsigned int* p, unsigned int v) {
  asm volatile("st.release.gpu.global.u32 [%0], %1;" ::"l"(p), "r"(v) : "memory");
}
template <int SLEEP>
__device__ __forceinline__ void src_wait(const unsigned int* f, unsigned int target, uint32_t need, uint32_t& ready, int lane) {
  uint32_t n = 0;
#pragma unroll 1
  while ((ready & need) != need) {
    const unsigned int v = ld_acquire(f + (lane & 15));
    ready = __ballot_sync(0xffffffffu, (int)(v - target) >= 0);
    if (SLEEP) { if ((ready & need) != need) __nanosleep(SLEEP); }
    if (++n > (1u << 20)) break;
  }
  __syncwarp();
}
__device__ __forceinline__ unsigned int ld_relaxed(const unsigned int* p);
__device__ __forceinline__ void src_wait_fast(const unsigned int* f, unsigned int target, uint32_t need, uint32_t& ready, int lane) {
  f += lane & 15;
  unsigned int v0 = ld_relaxed(f); __nanosleep(PSL);
  unsigned int v1 = ld_relaxed(f); __nanosleep(PSL);
  unsigned int v2 = ld_relaxed(f);
  uint32_t n = 0;
#pragma unroll 1
  while (true) {
    ready = __ballot_sync(0xffffffffu, (int)(v0 - target) >= 0);
    if ((ready & need) == need) break;
    v0 = ld_relaxed(f);
    ready = __ballot_sync(0xffffffffu, (int)(v1 - target) >= 0);
    if ((ready & need) == need) break;
    v1 = ld_relaxed(f);
    ready = __ballot_sync(0xffffffffu, (int)(v2 - target) >= 0);
    if ((ready & need) == need) break;
    v2 = ld_relaxed(f);
    if (++n > (1u << 20)) break;
  }
  asm volatile("fence.acquire.gpu;" ::: "memory");
  __syncwarp();
}
__device__ __forceinline__ unsigned int ld_relaxed(const unsigned int* p) {
  unsigned int v; asm volatile("ld.relaxed.gpu.global.u32 %0, [%1];" : "=r"(v) : "l"(p) : "memory"); return v;
}
__device__ __forceinline__ uint4 ld_relaxed4(const uint4* p) {
  uint4 v; asm volatile("ld.relaxed.gpu.global.v4.u32 {%0,%1,%2,%3}, [%4];" : "=r"(v.x), "=r"(v.y), "=r"(v.z), "=r"(v.w) : "l"(p) : "memory"); return v;
}
__device__ __forceinline__ void st_relaxed4(uint4* p, uint32_t a, uint32_t b, uint32_t c, uint32_t d) {
  asm volatile("st.relaxed.gpu.global.v4.u32 [%0], {%1,%2,%3,%4};" ::"l"(p), "r"(a), "r"(b), "r"(c), "r"(d) : "memory");
}
__device__ __forceinline__ void st_relaxed4_p(bool on, uint4* p, uint32_t a, uint32_t b, uint32_t c, uint32_t d) {
  asm volatile("{\n.reg .pred p;\nsetp.ne.b32 p, %5, 0;\n@p st.relaxed.gpu.global.v4.u32 [%0], {%1,%2,%3,%4};\n}\n" ::"l"(p), "r"(a), "r"(b), "r"(c), "r"(d), "r"((int)on) : "memory");
}
template <int SLEEP>
__device__ __forceinline__ void flag_wait_t(const unsigned int* p, unsigned int target) {
  uint32_t n = 0;
#pragma unroll 1
  while ((int)(ld_acquire(p) - target) < 0) {
    if (SLEEP) __nanosleep(SLEEP);
    if (++n > (1u << 20)) break;
  }
}
__device__ __forceinline__ void flag_wait(const unsigned int* p, unsigned int target) { flag_wait_t<0>(p, target); }
__device__ __forceinline__ void flag_wait_slow(const unsigned int* p, unsigned int target) { flag_wait_t<256>(p, target); }
__device__ __forceinline__ void tma_load_2d(uint32_t dst, const CUtensorMap* tm, int c0, int c1, uint32_t bar) {
  asm volatile("cp.async.bulk.tensor.2d.shared::cluster.global.mbarrier::complete_tx::bytes [%0], [%1, {%2, %3}], [%4];"
               ::"r"(dst), "l"(tm), "r"(c0), "r"(c1), "r"(bar) : "memory");
}
__device__ __forceinline__ void tma_load_2d_mc(uint32_t dst, const CUtensorMap* tm, int c0, int c1, uint32_t bar, uint16_t mask) {
  asm volatile("cp.async.bulk.tensor.2d.shared::cluster.global.mbarrier::complete_tx::bytes.multicast::cluster [%0], [%1, {%2, %3}], [%4], %5;"
               ::"r"(dst), "l"(tm), "r"(c0), "r"(c1), "r"(bar), "h"(mask) : "memory");
}
__device__ __forceinline__ void mbar_wait_u(uint32_t bar, uint32_t parity) {
  uint32_t n = 0;
#pragma unroll 1
  while (!__all_sync(0xffffffffu, mbar_try_wait(bar, parity))) {
    if (++n > (1u << 22)) break;
  }
}
__device__ __forceinline__ void expect_tx_e(uint32_t bar, uint32_t bytes) {
  asm volatile("{\n.reg .pred p;\nelect.sync _|p, 0xffffffff;\n@p mbarrier.arrive.expect_tx.shared::cta.b64 _, [%0], %1;\n}\n" ::"r"(bar), "r"(bytes) : "memory");
}
__device__ __forceinline__ void tma_2d_e(uint32_t dst, const CUtensorMap* tm, int c0, int c1, uint32_t bar) {
  asm volatile("{\n.reg .pred p;\nelect.sync _|p, 0xffffffff;\n"
               "@p cp.async.bulk.tensor.2d.shared::cluster.global.mbarrier::complete_tx::bytes [%0], [%1, {%2, %3}], [%4];\n}\n"
               ::"r"(dst), "l"(tm), "r"(c0), "r"(c1), "r"(bar) : "memory");
}
__device__ __forceinline__ void tma_2d_mc_e(uint32_t dst, const CUtensorMap* tm, int c0, int c1, uint32_t bar) {
  asm volatile("{\n.reg .pred p;\nelect.sync _|p, 0xffffffff;\n"
               "@p cp.async.bulk.tensor.2d.shared::cluster.global.mbarrier::complete_tx::bytes.multicast::cluster [%0], [%1, {%2, %3}], [%4], %5;\n}\n"
               ::"r"(dst), "l"(tm), "r"(c0), "r"(c1), "r"(bar), "h"((uint16_t)3) : "memory");
}
__device__ __forceinline__ void tma_5d(uint32_t dst, const CUtensorMap* tm, int c0, int c4, uint32_t bar) {
  asm volatile("cp.async.bulk.tensor.5d.shared::cluster.global.mbarrier::complete_tx::bytes [%0], [%1, {%2, %5, %5, %5, %3}], [%4];"
               ::"r"(dst), "l"(tm), "r"(c0), "r"(c4), "r"(bar), "r"(0) : "memory");
}
__device__ __forceinline__ void tma_5d_e(uint32_t dst, const CUtensorMap* tm, int c0, int c4, uint32_t bar) {
  asm volatile("{\n.reg .pred p;\nelect.sync _|p, 0xffffffff;\n"
               "@p cp.async.bulk.tensor.5d.shared::cluster.global.mbarrier::complete_tx::bytes [%0], [%1, {%2, %5, %5, %5, %3}], [%4];\n}\n"
               ::"r"(dst), "l"(tm), "r"(c0), "r"(c4), "r"(bar), "r"(0) : "memory");
}
__device__ __forceinline__ void tma_5d_mc_e(uint32_t dst, const CUtensorMap* tm, int c0, int c4, uint32_t bar) {
  asm volatile("{\n.reg .pred p;\nelect.sync _|p, 0xffffffff;\n"
               "@p cp.async.bulk.tensor.5d.shared::cluster.global.mbarrier::complete_tx::bytes.multicast::cluster [%0], [%1, {%2, %6, %6, %6, %3}], [%4], %5;\n}\n"
               ::"r"(dst), "l"(tm), "r"(c0), "r"(c4), "r"(bar), "h"((uint16_t)3), "r"(0) : "memory");
}
__device__ __forceinline__ void wait_tma_2d(bool w, uint32_t eb, uint32_t par, uint32_t dst, const CUtensorMap* tm, int c0, int c1, uint32_t fb) {
  asm volatile("" : "+r"(dst), "+l"(tm), "+r"(c0), "+r"(fb));
  if (w) mbar_wait_u(eb, par);
  tma_2d_e(dst, tm, c0, c1, fb);
}
__device__ __forceinline__ void wait_tma_5d_mc(bool w, uint32_t eb, uint32_t par, uint32_t dst, const CUtensorMap* tm, int c0, int c4, uint32_t fb) {
  asm volatile("" : "+r"(dst), "+l"(tm), "+r"(c0), "+r"(c4), "+r"(fb));
  if (w) mbar_wait_u(eb, par);
  tma_5d_mc_e(dst, tm, c0, c4, fb);
}
__device__ __forceinline__ void wait_tma_5d(bool w, uint32_t eb, uint32_t par, uint32_t dst, const CUtensorMap* tm, int c0, int c4, uint32_t fb) {
  asm volatile("" : "+r"(dst), "+l"(tm), "+r"(c0), "+r"(c4), "+r"(fb));
  if (w) mbar_wait_u(eb, par);
  tma_5d_e(dst, tm, c0, c4, fb);
}
__device__ __forceinline__ void st_async4(uint32_t dst, const uint32_t (&v)[4], uint32_t bar) {
  asm volatile("st.async.weak.shared::cluster.mbarrier::complete_tx::bytes.v4.b32 [%0], {%1,%2,%3,%4}, [%5];"
               ::"r"(dst), "r"(v[0]), "r"(v[1]), "r"(v[2]), "r"(v[3]), "r"(bar) : "memory");
}
__device__ __forceinline__ void mbar_wait_cl(uint32_t bar, uint32_t parity) {
  uint32_t n = 0, ok;
#pragma unroll 1
  do {
    asm volatile("{\n.reg .pred p;\nmbarrier.try_wait.parity.acquire.cluster.shared::cta.b64 p, [%1], %2;\nselp.b32 %0, 1, 0, p;\n}\n"
                 : "=r"(ok) : "r"(bar), "r"(parity) : "memory");
    if (++n > (1u << 22)) break;
  } while (!ok);
}
__device__ __forceinline__ void stg128(void* p, uint32_t a, uint32_t b, uint32_t c, uint32_t d) {
  asm volatile("st.global.v4.u32 [%0], {%1,%2,%3,%4};" ::"l"(p), "r"(a), "r"(b), "r"(c), "r"(d) : "memory");
}
__device__ __forceinline__ void stg128_p(bool on, void* p, uint32_t a, uint32_t b, uint32_t c, uint32_t d) {
  asm volatile("{\n.reg .pred p;\nsetp.ne.b32 p, %5, 0;\n@p st.global.v4.u32 [%0], {%1,%2,%3,%4};\n}\n" ::"l"(p), "r"(a), "r"(b), "r"(c), "r"(d), "r"((int)on) : "memory");
}
__device__ __forceinline__ void ldg128(const void* p, uint32_t& a, uint32_t& b, uint32_t& c, uint32_t& d) {
  asm volatile("ld.global.cg.v4.u32 {%0,%1,%2,%3}, [%4];" : "=r"(a), "=r"(b), "=r"(c), "=r"(d) : "l"(p) : "memory");
}
__device__ __forceinline__ void ldg128_p(bool on, const void* p, uint32_t (&v)[4]) {
  asm volatile("{\n.reg .pred p;\nsetp.ne.b32 p, %5, 0;\n@p ld.global.cg.v4.u32 {%0,%1,%2,%3}, [%4];\n}\n"
               : "+r"(v[0]), "+r"(v[1]), "+r"(v[2]), "+r"(v[3]) : "l"(p), "r"((int)on) : "memory");
}
__device__ __forceinline__ uint32_t ldg32(const void* p) {
  uint32_t v; asm volatile("ld.global.nc.u32 %0, [%1];" : "=r"(v) : "l"(p) : "memory"); return v;
}
__device__ __forceinline__ void tma_pf_e(const CUtensorMap* tm, int c0, int c1) {
  asm volatile("{\n.reg .pred p;\nelect.sync _|p, 0xffffffff;\n"
               "@p cp.async.bulk.prefetch.tensor.2d.L2.global.tile [%0, {%1, %2}];\n}\n" ::"l"(tm), "r"(c0), "r"(c1) : "memory");
}
__device__ __forceinline__ void tma_2d_to_e(uint32_t dst, const CUtensorMap* tm, int c0, int c1, uint32_t bar, uint32_t mask) {
  asm volatile("{\n.reg .pred p;\nelect.sync _|p, 0xffffffff;\n"
               "@p cp.async.bulk.tensor.2d.shared::cluster.global.mbarrier::complete_tx::bytes.multicast::cluster [%0], [%1, {%2, %3}], [%4], %5;\n}\n"
               ::"r"(dst), "l"(tm), "r"(c0), "r"(c1), "r"(bar), "h"((uint16_t)mask) : "memory");
}
__device__ __forceinline__ void tma_3d_mc_e(uint32_t dst, const CUtensorMap* tm, int c1, int c2, uint32_t bar) {
  asm volatile("{\n.reg .pred p;\nelect.sync _|p, 0xffffffff;\n"
               "@p cp.async.bulk.tensor.3d.shared::cluster.global.mbarrier::complete_tx::bytes.multicast::cluster [%0], [%1, {%6, %2, %3}], [%4], %5;\n}\n"
               ::"r"(dst), "l"(tm), "r"(c1), "r"(c2), "r"(bar), "h"((uint16_t)3), "r"(0) : "memory");
}
__device__ __forceinline__ uint32_t poll_flags(const unsigned int* f, unsigned int target, int lane) {
  const unsigned int v = ld_acquire(f + (lane & 15));
  const uint32_t r = __ballot_sync(0xffffffffu, (int)(v - target) >= 0);
  __syncwarp();
  return r;
}
__device__ __forceinline__ void mbar_arrive_cluster(uint32_t local_bar, uint32_t rank) {
  asm volatile("{\n.reg .b32 ra;\nmapa.shared::cluster.u32 ra, %0, %1;\nmbarrier.arrive.shared::cluster.b64 _, [ra];\n}\n"
               ::"r"(local_bar), "r"(rank) : "memory");
}
__device__ __forceinline__ void release2(uint32_t bar) { mbar_arrive_cluster(bar, 0); mbar_arrive_cluster(bar, 1); }
__device__ __forceinline__ void release2c(uint32_t off) {
  asm volatile("mbarrier.arrive.shared::cluster.b64 _, [%0];\nmbarrier.arrive.shared::cluster.b64 _, [%1];" ::"r"(off), "r"(off + (1u << 24)) : "memory");
}
__device__ __forceinline__ void tma_store_2d(const CUtensorMap* tm, uint32_t src, int c0, int c1) {
  asm volatile("cp.async.bulk.tensor.2d.global.shared::cta.bulk_group [%0, {%2, %3}], [%1];"
               ::"l"(tm), "r"(src), "r"(c0), "r"(c1) : "memory");
}
__device__ __forceinline__ void tma_store_5d(const CUtensorMap* tm, uint32_t src, int c0, int c4) {
  asm volatile("cp.async.bulk.tensor.5d.global.shared::cta.bulk_group [%0, {%2, %4, %4, %4, %3}], [%1];"
               ::"l"(tm), "r"(src), "r"(c0), "r"(c4), "r"(0) : "memory");
}
__device__ __forceinline__ void bulk_store(void* dst, uint32_t src, uint32_t bytes) {
  asm volatile("cp.async.bulk.global.shared::cta.bulk_group [%0], [%1], %2;" ::"l"(dst), "r"(src), "r"(bytes) : "memory");
}
__device__ __forceinline__ void bulk_load(uint32_t dst, const void* src, uint32_t bytes, uint32_t bar) {
  asm volatile("cp.async.bulk.shared::cluster.global.mbarrier::complete_tx::bytes [%0], [%1], %2, [%3];" ::"r"(dst), "l"(src), "r"(bytes), "r"(bar) : "memory");
}
__device__ __forceinline__ void bulk_red_add(void* dst, uint32_t src, uint32_t bytes) {
  asm volatile("cp.reduce.async.bulk.global.shared::cta.bulk_group.add.f32 [%0], [%1], %2;" ::"l"(dst), "r"(src), "r"(bytes) : "memory");
}
__device__ __forceinline__ void bulk_commit() { asm volatile("cp.async.bulk.commit_group;" ::: "memory"); }
__device__ __forceinline__ void bulk_wait0() { asm volatile("cp.async.bulk.wait_group 0;" ::: "memory"); }
__device__ __forceinline__ void fence_async_smem() { asm volatile("fence.proxy.async.shared::cta;" ::: "memory"); }
__device__ __forceinline__ void fence_async_all() { asm volatile("fence.proxy.async.global;" ::: "memory"); }
__device__ __forceinline__ void wgmma_fence() { asm volatile("wgmma.fence.sync.aligned;" ::: "memory"); }
__device__ __forceinline__ void wgmma_commit() { asm volatile("wgmma.commit_group.sync.aligned;" ::: "memory"); }
template <int N> __device__ __forceinline__ void wgmma_wait() { asm volatile("wgmma.wait_group.sync.aligned %0;" ::"n"(N) : "memory"); }
__device__ __forceinline__ void cluster_arrive() { asm volatile("barrier.cluster.arrive.release.aligned;" ::: "memory"); }
__device__ __forceinline__ void cluster_wait() { asm volatile("barrier.cluster.wait.acquire.aligned;" ::: "memory"); }
template <int ID, int N> __device__ __forceinline__ void nbar() { asm volatile("bar.sync %0, %1;" ::"n"(ID), "n"(N) : "memory"); }
__device__ __forceinline__ uint64_t make_desc(uint32_t addr, uint32_t lbo_bytes, uint32_t sbo_bytes) {
  uint64_t d = 0;
  d |= (uint64_t)((addr & 0x3FFFF) >> 4);
  d |= (uint64_t)((lbo_bytes >> 4) & 0x3FFF) << 16;
  d |= (uint64_t)((sbo_bytes >> 4) & 0x3FFF) << 32;
  d |= (uint64_t)1 << 62;
  return d;
}
__device__ __forceinline__ uint64_t desc64(uint32_t lo, uint32_t hi) { return (uint64_t)lo | ((uint64_t)hi << 32); }
__device__ __forceinline__ uint32_t pack_bf16(float lo, float hi) {
  uint32_t r; asm("cvt.rn.bf16x2.f32 %0, %1, %2;" : "=r"(r) : "f"(hi), "f"(lo)); return r;
}
__device__ __forceinline__ uint32_t add_bf16x2(uint32_t a, uint32_t b) {
  uint32_t r; asm("add.rn.bf16x2 %0, %1, %2;" : "=r"(r) : "r"(a), "r"(b)); return r;
}
__device__ __forceinline__ float bf16r(float x) { return __bfloat162float(__float2bfloat16_rn(x)); }
__device__ __forceinline__ float bf_lo(uint32_t u) { return __uint_as_float(u << 16); }
__device__ __forceinline__ float bf_hi(uint32_t u) { return __uint_as_float(u & 0xFFFF0000u); }
__device__ __forceinline__ float ex2(float x) { float r; asm("ex2.approx.ftz.f32 %0, %1;" : "=f"(r) : "f"(x)); return r; }
__device__ __forceinline__ float ex2v(float x) { float r; asm volatile("ex2.approx.ftz.f32 %0, %1;" : "=f"(r) : "f"(x) : "memory"); return r; }
__device__ __forceinline__ float rcp(float x) { float r; asm("rcp.approx.ftz.f32 %0, %1;" : "=f"(r) : "f"(x)); return r; }
__device__ __forceinline__ void mma_bf16(float (&d)[4], uint32_t a0, uint32_t a1, uint32_t a2, uint32_t a3, uint32_t b0, uint32_t b1) {
  asm("mma.sync.aligned.m16n8k16.row.col.f32.bf16.bf16.f32 {%0,%1,%2,%3}, {%4,%5,%6,%7}, {%8,%9}, {%0,%1,%2,%3};"
               : "+f"(d[0]), "+f"(d[1]), "+f"(d[2]), "+f"(d[3]) : "r"(a0), "r"(a1), "r"(a2), "r"(a3), "r"(b0), "r"(b1));
}
__device__ __forceinline__ void ldsm_x4(uint32_t& r0, uint32_t& r1, uint32_t& r2, uint32_t& r3, uint32_t addr) {
  asm volatile("ldmatrix.sync.aligned.m8n8.x4.shared.b16 {%0,%1,%2,%3}, [%4];"
               : "=r"(r0), "=r"(r1), "=r"(r2), "=r"(r3) : "r"(addr) : "memory");
}
__device__ __forceinline__ void ldsm_x4_t(uint32_t& r0, uint32_t& r1, uint32_t& r2, uint32_t& r3, uint32_t addr) {
  asm volatile("ldmatrix.sync.aligned.m8n8.x4.trans.shared.b16 {%0,%1,%2,%3}, [%4];"
               : "=r"(r0), "=r"(r1), "=r"(r2), "=r"(r3) : "r"(addr) : "memory");
}
__device__ __forceinline__ void ldsm_x2_t(uint32_t& r0, uint32_t& r1, uint32_t addr) {
  asm volatile("ldmatrix.sync.aligned.m8n8.x2.trans.shared.b16 {%0,%1}, [%2];"
               : "=r"(r0), "=r"(r1) : "r"(addr) : "memory");
}
__device__ __forceinline__ void stsm_x4(uint32_t addr, uint32_t r0, uint32_t r1, uint32_t r2, uint32_t r3) {
  asm volatile("stmatrix.sync.aligned.m8n8.x4.shared.b16 [%0], {%1,%2,%3,%4};"
               ::"r"(addr), "r"(r0), "r"(r1), "r"(r2), "r"(r3) : "memory");
}
__device__ __forceinline__ void stsm_x4_p(bool on, uint32_t addr, uint32_t r0, uint32_t r1, uint32_t r2, uint32_t r3) {
  asm volatile("{\n.reg .pred p;\nsetp.ne.b32 p, %5, 0;\n@p stmatrix.sync.aligned.m8n8.x4.shared.b16 [%0], {%1,%2,%3,%4};\n}\n"
               ::"r"(addr), "r"(r0), "r"(r1), "r"(r2), "r"(r3), "r"((int)on) : "memory");
}
__device__ __forceinline__ float2 lds_f2(uint32_t addr) {
  float2 v; asm volatile("ld.shared.v2.f32 {%0,%1}, [%2];" : "=f"(v.x), "=f"(v.y) : "r"(addr) : "memory"); return v;
}
__device__ __forceinline__ uint4 lds128(uint32_t addr) {
  uint4 v; asm volatile("ld.shared.v4.b32 {%0,%1,%2,%3}, [%4];" : "=r"(v.x), "=r"(v.y), "=r"(v.z), "=r"(v.w) : "r"(addr) : "memory"); return v;
}
__device__ __forceinline__ void sts128(uint32_t addr, uint4 v) {
  asm volatile("st.shared.v4.b32 [%0], {%1,%2,%3,%4};" ::"r"(addr), "r"(v.x), "r"(v.y), "r"(v.z), "r"(v.w) : "memory");
}
__device__ __forceinline__ float lds_f(uint32_t addr) {
  float v; asm volatile("ld.shared.f32 %0, [%1];" : "=f"(v) : "r"(addr) : "memory"); return v;
}
__device__ __forceinline__ void sts16(uint32_t addr, uint32_t v) {
  asm volatile("st.shared.u16 [%0], %1;" ::"r"(addr), "h"((unsigned short)v) : "memory");
}
__device__ __forceinline__ void nbar_dyn(int id, int n) { asm volatile("bar.sync %0, %1;" ::"r"(id), "r"(n) : "memory"); }
__device__ __forceinline__ uint64_t make_desc_ns(uint32_t addr, uint32_t lbo_bytes, uint32_t sbo_bytes) {
  return (uint64_t)((addr & 0x3FFFF) >> 4) | ((uint64_t)(lbo_bytes >> 4) << 16) | ((uint64_t)(sbo_bytes >> 4) << 32);
}
__device__ __forceinline__ void sts_f(uint32_t addr, float v) { asm volatile("st.shared.f32 [%0], %1;" ::"r"(addr), "f"(v) : "memory"); }
__device__ __forceinline__ void sts64(uint32_t addr, uint32_t a, uint32_t b) {
  asm volatile("st.shared.v2.b32 [%0], {%1,%2};" ::"r"(addr), "r"(a), "r"(b) : "memory");
}
__device__ __forceinline__ void sts_f2(uint32_t addr, float a, float b) {
  asm volatile("st.shared.v2.f32 [%0], {%1,%2};" ::"r"(addr), "f"(a), "f"(b) : "memory");
}
__device__ __forceinline__ void red_add2(float* p, float a, float b) {
  asm volatile("red.global.add.v2.f32 [%0], {%1,%2};" ::"l"(p), "f"(a), "f"(b) : "memory");
}
__device__ __forceinline__ void red_add2_p(bool on, float* p, float a, float b) {
  asm volatile("{\n.reg .pred p;\nsetp.ne.b32 p, %3, 0;\n@p red.global.add.v2.f32 [%0], {%1,%2};\n}\n" ::"l"(p), "f"(a), "f"(b), "r"((int)on) : "memory");
}
__device__ __forceinline__ void red_add4(float* p, float a, float b, float c, float d) {
  asm volatile("red.global.add.v4.f32 [%0], {%1,%2,%3,%4};" ::"l"(p), "f"(a), "f"(b), "f"(c), "f"(d) : "memory");
}
__device__ __forceinline__ void red_add1(float* p, float a) {
  asm volatile("red.global.add.f32 [%0], %1;" ::"l"(p), "f"(a) : "memory");
}
__device__ __forceinline__ void l2_prefetch(const void* p, uint32_t bytes) {
  asm volatile("cp.async.bulk.prefetch.L2.global [%0], %1;" ::"l"(p), "r"(bytes) : "memory");
}

__device__ __forceinline__ void wgmma_n256(float (&d)[192], uint64_t da, uint64_t db, int scale_d) {
  asm volatile("{\n.reg .pred p;\nsetp.ne.b32 p, %130, 0;\n"
    "wgmma.mma_async.sync.aligned.m64n256k16.f32.bf16.bf16 {%0, %1, %2, %3, %4, %5, %6, %7, %8, %9, %10, %11, %12, %13, %14, %15, %16, %17, %18, %19, %20, %21, %22, %23, %24, %25, %26, %27, %28, %29, %30, %31, %32, %33, %34, %35, %36, %37, %38, %39, %40, %41, %42, %43, %44, %45, %46, %47, %48, %49, %50, %51, %52, %53, %54, %55, %56, %57, %58, %59, %60, %61, %62, %63, %64, %65, %66, %67, %68, %69, %70, %71, %72, %73, %74, %75, %76, %77, %78, %79, %80, %81, %82, %83, %84, %85, %86, %87, %88, %89, %90, %91, %92, %93, %94, %95, %96, %97, %98, %99, %100, %101, %102, %103, %104, %105, %106, %107, %108, %109, %110, %111, %112, %113, %114, %115, %116, %117, %118, %119, %120, %121, %122, %123, %124, %125, %126, %127}, %128, %129, p, 1, 1, 0, 1;\n}\n"
    : "+f"(d[0]), "+f"(d[1]), "+f"(d[2]), "+f"(d[3]), "+f"(d[4]), "+f"(d[5]), "+f"(d[6]), "+f"(d[7]), "+f"(d[8]), "+f"(d[9]), "+f"(d[10]), "+f"(d[11]), "+f"(d[12]), "+f"(d[13]), "+f"(d[14]), "+f"(d[15]), "+f"(d[16]), "+f"(d[17]), "+f"(d[18]), "+f"(d[19]), "+f"(d[20]), "+f"(d[21]), "+f"(d[22]), "+f"(d[23]), "+f"(d[24]), "+f"(d[25]), "+f"(d[26]), "+f"(d[27]), "+f"(d[28]), "+f"(d[29]), "+f"(d[30]), "+f"(d[31]), "+f"(d[32]), "+f"(d[33]), "+f"(d[34]), "+f"(d[35]), "+f"(d[36]), "+f"(d[37]), "+f"(d[38]), "+f"(d[39]), "+f"(d[40]), "+f"(d[41]), "+f"(d[42]), "+f"(d[43]), "+f"(d[44]), "+f"(d[45]), "+f"(d[46]), "+f"(d[47]), "+f"(d[48]), "+f"(d[49]), "+f"(d[50]), "+f"(d[51]), "+f"(d[52]), "+f"(d[53]), "+f"(d[54]), "+f"(d[55]), "+f"(d[56]), "+f"(d[57]), "+f"(d[58]), "+f"(d[59]), "+f"(d[60]), "+f"(d[61]), "+f"(d[62]), "+f"(d[63]), "+f"(d[64]), "+f"(d[65]), "+f"(d[66]), "+f"(d[67]), "+f"(d[68]), "+f"(d[69]), "+f"(d[70]), "+f"(d[71]), "+f"(d[72]), "+f"(d[73]), "+f"(d[74]), "+f"(d[75]), "+f"(d[76]), "+f"(d[77]), "+f"(d[78]), "+f"(d[79]), "+f"(d[80]), "+f"(d[81]), "+f"(d[82]), "+f"(d[83]), "+f"(d[84]), "+f"(d[85]), "+f"(d[86]), "+f"(d[87]), "+f"(d[88]), "+f"(d[89]), "+f"(d[90]), "+f"(d[91]), "+f"(d[92]), "+f"(d[93]), "+f"(d[94]), "+f"(d[95]), "+f"(d[96]), "+f"(d[97]), "+f"(d[98]), "+f"(d[99]), "+f"(d[100]), "+f"(d[101]), "+f"(d[102]), "+f"(d[103]), "+f"(d[104]), "+f"(d[105]), "+f"(d[106]), "+f"(d[107]), "+f"(d[108]), "+f"(d[109]), "+f"(d[110]), "+f"(d[111]), "+f"(d[112]), "+f"(d[113]), "+f"(d[114]), "+f"(d[115]), "+f"(d[116]), "+f"(d[117]), "+f"(d[118]), "+f"(d[119]), "+f"(d[120]), "+f"(d[121]), "+f"(d[122]), "+f"(d[123]), "+f"(d[124]), "+f"(d[125]), "+f"(d[126]), "+f"(d[127])
    : "l"(da), "l"(db), "r"(scale_d));
}
__device__ __forceinline__ void wgmma_n128(float (&d)[192], uint64_t da, uint64_t db, int scale_d) {
  asm volatile("{\n.reg .pred p;\nsetp.ne.b32 p, %66, 0;\n"
    "wgmma.mma_async.sync.aligned.m64n128k16.f32.bf16.bf16 {%0, %1, %2, %3, %4, %5, %6, %7, %8, %9, %10, %11, %12, %13, %14, %15, %16, %17, %18, %19, %20, %21, %22, %23, %24, %25, %26, %27, %28, %29, %30, %31, %32, %33, %34, %35, %36, %37, %38, %39, %40, %41, %42, %43, %44, %45, %46, %47, %48, %49, %50, %51, %52, %53, %54, %55, %56, %57, %58, %59, %60, %61, %62, %63}, %64, %65, p, 1, 1, 0, 1;\n}\n"
    : "+f"(d[128]), "+f"(d[129]), "+f"(d[130]), "+f"(d[131]), "+f"(d[132]), "+f"(d[133]), "+f"(d[134]), "+f"(d[135]), "+f"(d[136]), "+f"(d[137]), "+f"(d[138]), "+f"(d[139]), "+f"(d[140]), "+f"(d[141]), "+f"(d[142]), "+f"(d[143]), "+f"(d[144]), "+f"(d[145]), "+f"(d[146]), "+f"(d[147]), "+f"(d[148]), "+f"(d[149]), "+f"(d[150]), "+f"(d[151]), "+f"(d[152]), "+f"(d[153]), "+f"(d[154]), "+f"(d[155]), "+f"(d[156]), "+f"(d[157]), "+f"(d[158]), "+f"(d[159]), "+f"(d[160]), "+f"(d[161]), "+f"(d[162]), "+f"(d[163]), "+f"(d[164]), "+f"(d[165]), "+f"(d[166]), "+f"(d[167]), "+f"(d[168]), "+f"(d[169]), "+f"(d[170]), "+f"(d[171]), "+f"(d[172]), "+f"(d[173]), "+f"(d[174]), "+f"(d[175]), "+f"(d[176]), "+f"(d[177]), "+f"(d[178]), "+f"(d[179]), "+f"(d[180]), "+f"(d[181]), "+f"(d[182]), "+f"(d[183]), "+f"(d[184]), "+f"(d[185]), "+f"(d[186]), "+f"(d[187]), "+f"(d[188]), "+f"(d[189]), "+f"(d[190]), "+f"(d[191])
    : "l"(da), "l"(db), "r"(scale_d));
}
__device__ __forceinline__ void wgmma_n256_k(float (&d)[192], uint64_t da, uint64_t db, int scale_d) {
  asm volatile("{\n.reg .pred p;\nsetp.ne.b32 p, %130, 0;\n"
    "wgmma.mma_async.sync.aligned.m64n256k16.f32.bf16.bf16 {%0, %1, %2, %3, %4, %5, %6, %7, %8, %9, %10, %11, %12, %13, %14, %15, %16, %17, %18, %19, %20, %21, %22, %23, %24, %25, %26, %27, %28, %29, %30, %31, %32, %33, %34, %35, %36, %37, %38, %39, %40, %41, %42, %43, %44, %45, %46, %47, %48, %49, %50, %51, %52, %53, %54, %55, %56, %57, %58, %59, %60, %61, %62, %63, %64, %65, %66, %67, %68, %69, %70, %71, %72, %73, %74, %75, %76, %77, %78, %79, %80, %81, %82, %83, %84, %85, %86, %87, %88, %89, %90, %91, %92, %93, %94, %95, %96, %97, %98, %99, %100, %101, %102, %103, %104, %105, %106, %107, %108, %109, %110, %111, %112, %113, %114, %115, %116, %117, %118, %119, %120, %121, %122, %123, %124, %125, %126, %127}, %128, %129, p, 1, 1, 0, 0;\n}\n"
    : "+f"(d[0]), "+f"(d[1]), "+f"(d[2]), "+f"(d[3]), "+f"(d[4]), "+f"(d[5]), "+f"(d[6]), "+f"(d[7]), "+f"(d[8]), "+f"(d[9]), "+f"(d[10]), "+f"(d[11]), "+f"(d[12]), "+f"(d[13]), "+f"(d[14]), "+f"(d[15]), "+f"(d[16]), "+f"(d[17]), "+f"(d[18]), "+f"(d[19]), "+f"(d[20]), "+f"(d[21]), "+f"(d[22]), "+f"(d[23]), "+f"(d[24]), "+f"(d[25]), "+f"(d[26]), "+f"(d[27]), "+f"(d[28]), "+f"(d[29]), "+f"(d[30]), "+f"(d[31]), "+f"(d[32]), "+f"(d[33]), "+f"(d[34]), "+f"(d[35]), "+f"(d[36]), "+f"(d[37]), "+f"(d[38]), "+f"(d[39]), "+f"(d[40]), "+f"(d[41]), "+f"(d[42]), "+f"(d[43]), "+f"(d[44]), "+f"(d[45]), "+f"(d[46]), "+f"(d[47]), "+f"(d[48]), "+f"(d[49]), "+f"(d[50]), "+f"(d[51]), "+f"(d[52]), "+f"(d[53]), "+f"(d[54]), "+f"(d[55]), "+f"(d[56]), "+f"(d[57]), "+f"(d[58]), "+f"(d[59]), "+f"(d[60]), "+f"(d[61]), "+f"(d[62]), "+f"(d[63]), "+f"(d[64]), "+f"(d[65]), "+f"(d[66]), "+f"(d[67]), "+f"(d[68]), "+f"(d[69]), "+f"(d[70]), "+f"(d[71]), "+f"(d[72]), "+f"(d[73]), "+f"(d[74]), "+f"(d[75]), "+f"(d[76]), "+f"(d[77]), "+f"(d[78]), "+f"(d[79]), "+f"(d[80]), "+f"(d[81]), "+f"(d[82]), "+f"(d[83]), "+f"(d[84]), "+f"(d[85]), "+f"(d[86]), "+f"(d[87]), "+f"(d[88]), "+f"(d[89]), "+f"(d[90]), "+f"(d[91]), "+f"(d[92]), "+f"(d[93]), "+f"(d[94]), "+f"(d[95]), "+f"(d[96]), "+f"(d[97]), "+f"(d[98]), "+f"(d[99]), "+f"(d[100]), "+f"(d[101]), "+f"(d[102]), "+f"(d[103]), "+f"(d[104]), "+f"(d[105]), "+f"(d[106]), "+f"(d[107]), "+f"(d[108]), "+f"(d[109]), "+f"(d[110]), "+f"(d[111]), "+f"(d[112]), "+f"(d[113]), "+f"(d[114]), "+f"(d[115]), "+f"(d[116]), "+f"(d[117]), "+f"(d[118]), "+f"(d[119]), "+f"(d[120]), "+f"(d[121]), "+f"(d[122]), "+f"(d[123]), "+f"(d[124]), "+f"(d[125]), "+f"(d[126]), "+f"(d[127])
    : "l"(da), "l"(db), "r"(scale_d));
}
__device__ __forceinline__ void wgmma_n128_k(float (&d)[192], uint64_t da, uint64_t db, int scale_d) {
  asm volatile("{\n.reg .pred p;\nsetp.ne.b32 p, %66, 0;\n"
    "wgmma.mma_async.sync.aligned.m64n128k16.f32.bf16.bf16 {%0, %1, %2, %3, %4, %5, %6, %7, %8, %9, %10, %11, %12, %13, %14, %15, %16, %17, %18, %19, %20, %21, %22, %23, %24, %25, %26, %27, %28, %29, %30, %31, %32, %33, %34, %35, %36, %37, %38, %39, %40, %41, %42, %43, %44, %45, %46, %47, %48, %49, %50, %51, %52, %53, %54, %55, %56, %57, %58, %59, %60, %61, %62, %63}, %64, %65, p, 1, 1, 0, 0;\n}\n"
    : "+f"(d[128]), "+f"(d[129]), "+f"(d[130]), "+f"(d[131]), "+f"(d[132]), "+f"(d[133]), "+f"(d[134]), "+f"(d[135]), "+f"(d[136]), "+f"(d[137]), "+f"(d[138]), "+f"(d[139]), "+f"(d[140]), "+f"(d[141]), "+f"(d[142]), "+f"(d[143]), "+f"(d[144]), "+f"(d[145]), "+f"(d[146]), "+f"(d[147]), "+f"(d[148]), "+f"(d[149]), "+f"(d[150]), "+f"(d[151]), "+f"(d[152]), "+f"(d[153]), "+f"(d[154]), "+f"(d[155]), "+f"(d[156]), "+f"(d[157]), "+f"(d[158]), "+f"(d[159]), "+f"(d[160]), "+f"(d[161]), "+f"(d[162]), "+f"(d[163]), "+f"(d[164]), "+f"(d[165]), "+f"(d[166]), "+f"(d[167]), "+f"(d[168]), "+f"(d[169]), "+f"(d[170]), "+f"(d[171]), "+f"(d[172]), "+f"(d[173]), "+f"(d[174]), "+f"(d[175]), "+f"(d[176]), "+f"(d[177]), "+f"(d[178]), "+f"(d[179]), "+f"(d[180]), "+f"(d[181]), "+f"(d[182]), "+f"(d[183]), "+f"(d[184]), "+f"(d[185]), "+f"(d[186]), "+f"(d[187]), "+f"(d[188]), "+f"(d[189]), "+f"(d[190]), "+f"(d[191])
    : "l"(da), "l"(db), "r"(scale_d));
}
__device__ __forceinline__ void wgmma_n40_tt(float (&d)[20], uint64_t da, uint64_t db, int scale_d) {
  asm volatile("{\n.reg .pred p;\nsetp.ne.b32 p, %22, 0;\n"
    "wgmma.mma_async.sync.aligned.m64n40k16.f32.bf16.bf16 {%0, %1, %2, %3, %4, %5, %6, %7, %8, %9, %10, %11, %12, %13, %14, %15, %16, %17, %18, %19}, %20, %21, p, 1, 1, 1, 1;\n}\n"
    : "+f"(d[0]), "+f"(d[1]), "+f"(d[2]), "+f"(d[3]), "+f"(d[4]), "+f"(d[5]), "+f"(d[6]), "+f"(d[7]), "+f"(d[8]), "+f"(d[9]), "+f"(d[10]), "+f"(d[11]), "+f"(d[12]), "+f"(d[13]), "+f"(d[14]), "+f"(d[15]), "+f"(d[16]), "+f"(d[17]), "+f"(d[18]), "+f"(d[19])
    : "l"(da), "l"(db), "r"(scale_d));
}
__device__ __forceinline__ void wgmma_n40_rs(float (&d)[20], const uint32_t (&a)[4], uint64_t db, int scale_d) {
  asm volatile("{\n.reg .pred p;\nsetp.ne.b32 p, %25, 0;\n"
    "wgmma.mma_async.sync.aligned.m64n40k16.f32.bf16.bf16 {%0, %1, %2, %3, %4, %5, %6, %7, %8, %9, %10, %11, %12, %13, %14, %15, %16, %17, %18, %19}, {%20, %21, %22, %23}, %24, p, 1, 1, 1;\n}\n"
    : "+f"(d[0]), "+f"(d[1]), "+f"(d[2]), "+f"(d[3]), "+f"(d[4]), "+f"(d[5]), "+f"(d[6]), "+f"(d[7]), "+f"(d[8]), "+f"(d[9]), "+f"(d[10]), "+f"(d[11]), "+f"(d[12]), "+f"(d[13]), "+f"(d[14]), "+f"(d[15]), "+f"(d[16]), "+f"(d[17]), "+f"(d[18]), "+f"(d[19])
    : "r"(a[0]), "r"(a[1]), "r"(a[2]), "r"(a[3]), "l"(db), "r"(scale_d));
}
__device__ __forceinline__ void wgmma_n256_0(float (&d)[192], uint64_t da, uint64_t db) {
  asm volatile("{\n.reg .pred p;\nsetp.ne.b32 p, 0, 0;\n"
    "wgmma.mma_async.sync.aligned.m64n256k16.f32.bf16.bf16 {%0, %1, %2, %3, %4, %5, %6, %7, %8, %9, %10, %11, %12, %13, %14, %15, %16, %17, %18, %19, %20, %21, %22, %23, %24, %25, %26, %27, %28, %29, %30, %31, %32, %33, %34, %35, %36, %37, %38, %39, %40, %41, %42, %43, %44, %45, %46, %47, %48, %49, %50, %51, %52, %53, %54, %55, %56, %57, %58, %59, %60, %61, %62, %63, %64, %65, %66, %67, %68, %69, %70, %71, %72, %73, %74, %75, %76, %77, %78, %79, %80, %81, %82, %83, %84, %85, %86, %87, %88, %89, %90, %91, %92, %93, %94, %95, %96, %97, %98, %99, %100, %101, %102, %103, %104, %105, %106, %107, %108, %109, %110, %111, %112, %113, %114, %115, %116, %117, %118, %119, %120, %121, %122, %123, %124, %125, %126, %127}, %128, %129, p, 1, 1, 0, 1;\n}\n"
    : "=f"(d[0]), "=f"(d[1]), "=f"(d[2]), "=f"(d[3]), "=f"(d[4]), "=f"(d[5]), "=f"(d[6]), "=f"(d[7]), "=f"(d[8]), "=f"(d[9]), "=f"(d[10]), "=f"(d[11]), "=f"(d[12]), "=f"(d[13]), "=f"(d[14]), "=f"(d[15]), "=f"(d[16]), "=f"(d[17]), "=f"(d[18]), "=f"(d[19]), "=f"(d[20]), "=f"(d[21]), "=f"(d[22]), "=f"(d[23]), "=f"(d[24]), "=f"(d[25]), "=f"(d[26]), "=f"(d[27]), "=f"(d[28]), "=f"(d[29]), "=f"(d[30]), "=f"(d[31]), "=f"(d[32]), "=f"(d[33]), "=f"(d[34]), "=f"(d[35]), "=f"(d[36]), "=f"(d[37]), "=f"(d[38]), "=f"(d[39]), "=f"(d[40]), "=f"(d[41]), "=f"(d[42]), "=f"(d[43]), "=f"(d[44]), "=f"(d[45]), "=f"(d[46]), "=f"(d[47]), "=f"(d[48]), "=f"(d[49]), "=f"(d[50]), "=f"(d[51]), "=f"(d[52]), "=f"(d[53]), "=f"(d[54]), "=f"(d[55]), "=f"(d[56]), "=f"(d[57]), "=f"(d[58]), "=f"(d[59]), "=f"(d[60]), "=f"(d[61]), "=f"(d[62]), "=f"(d[63]), "=f"(d[64]), "=f"(d[65]), "=f"(d[66]), "=f"(d[67]), "=f"(d[68]), "=f"(d[69]), "=f"(d[70]), "=f"(d[71]), "=f"(d[72]), "=f"(d[73]), "=f"(d[74]), "=f"(d[75]), "=f"(d[76]), "=f"(d[77]), "=f"(d[78]), "=f"(d[79]), "=f"(d[80]), "=f"(d[81]), "=f"(d[82]), "=f"(d[83]), "=f"(d[84]), "=f"(d[85]), "=f"(d[86]), "=f"(d[87]), "=f"(d[88]), "=f"(d[89]), "=f"(d[90]), "=f"(d[91]), "=f"(d[92]), "=f"(d[93]), "=f"(d[94]), "=f"(d[95]), "=f"(d[96]), "=f"(d[97]), "=f"(d[98]), "=f"(d[99]), "=f"(d[100]), "=f"(d[101]), "=f"(d[102]), "=f"(d[103]), "=f"(d[104]), "=f"(d[105]), "=f"(d[106]), "=f"(d[107]), "=f"(d[108]), "=f"(d[109]), "=f"(d[110]), "=f"(d[111]), "=f"(d[112]), "=f"(d[113]), "=f"(d[114]), "=f"(d[115]), "=f"(d[116]), "=f"(d[117]), "=f"(d[118]), "=f"(d[119]), "=f"(d[120]), "=f"(d[121]), "=f"(d[122]), "=f"(d[123]), "=f"(d[124]), "=f"(d[125]), "=f"(d[126]), "=f"(d[127])
    : "l"(da), "l"(db));
}
__device__ __forceinline__ void wgmma_n128_0(float (&d)[192], uint64_t da, uint64_t db) {
  asm volatile("{\n.reg .pred p;\nsetp.ne.b32 p, 0, 0;\n"
    "wgmma.mma_async.sync.aligned.m64n128k16.f32.bf16.bf16 {%0, %1, %2, %3, %4, %5, %6, %7, %8, %9, %10, %11, %12, %13, %14, %15, %16, %17, %18, %19, %20, %21, %22, %23, %24, %25, %26, %27, %28, %29, %30, %31, %32, %33, %34, %35, %36, %37, %38, %39, %40, %41, %42, %43, %44, %45, %46, %47, %48, %49, %50, %51, %52, %53, %54, %55, %56, %57, %58, %59, %60, %61, %62, %63}, %64, %65, p, 1, 1, 0, 1;\n}\n"
    : "=f"(d[128]), "=f"(d[129]), "=f"(d[130]), "=f"(d[131]), "=f"(d[132]), "=f"(d[133]), "=f"(d[134]), "=f"(d[135]), "=f"(d[136]), "=f"(d[137]), "=f"(d[138]), "=f"(d[139]), "=f"(d[140]), "=f"(d[141]), "=f"(d[142]), "=f"(d[143]), "=f"(d[144]), "=f"(d[145]), "=f"(d[146]), "=f"(d[147]), "=f"(d[148]), "=f"(d[149]), "=f"(d[150]), "=f"(d[151]), "=f"(d[152]), "=f"(d[153]), "=f"(d[154]), "=f"(d[155]), "=f"(d[156]), "=f"(d[157]), "=f"(d[158]), "=f"(d[159]), "=f"(d[160]), "=f"(d[161]), "=f"(d[162]), "=f"(d[163]), "=f"(d[164]), "=f"(d[165]), "=f"(d[166]), "=f"(d[167]), "=f"(d[168]), "=f"(d[169]), "=f"(d[170]), "=f"(d[171]), "=f"(d[172]), "=f"(d[173]), "=f"(d[174]), "=f"(d[175]), "=f"(d[176]), "=f"(d[177]), "=f"(d[178]), "=f"(d[179]), "=f"(d[180]), "=f"(d[181]), "=f"(d[182]), "=f"(d[183]), "=f"(d[184]), "=f"(d[185]), "=f"(d[186]), "=f"(d[187]), "=f"(d[188]), "=f"(d[189]), "=f"(d[190]), "=f"(d[191])
    : "l"(da), "l"(db));
}
__device__ __forceinline__ void wgmma_n128_rs(float (&d)[192], const uint32_t (&a)[4], uint64_t db, int scale_d) {
  asm volatile("{\n.reg .pred p;\nsetp.ne.b32 p, %69, 0;\n"
    "wgmma.mma_async.sync.aligned.m64n128k16.f32.bf16.bf16 {%0, %1, %2, %3, %4, %5, %6, %7, %8, %9, %10, %11, %12, %13, %14, %15, %16, %17, %18, %19, %20, %21, %22, %23, %24, %25, %26, %27, %28, %29, %30, %31, %32, %33, %34, %35, %36, %37, %38, %39, %40, %41, %42, %43, %44, %45, %46, %47, %48, %49, %50, %51, %52, %53, %54, %55, %56, %57, %58, %59, %60, %61, %62, %63}, {%64, %65, %66, %67}, %68, p, 1, 1, 1;\n}\n"
    : "+f"(d[128]), "+f"(d[129]), "+f"(d[130]), "+f"(d[131]), "+f"(d[132]), "+f"(d[133]), "+f"(d[134]), "+f"(d[135]), "+f"(d[136]), "+f"(d[137]), "+f"(d[138]), "+f"(d[139]), "+f"(d[140]), "+f"(d[141]), "+f"(d[142]), "+f"(d[143]), "+f"(d[144]), "+f"(d[145]), "+f"(d[146]), "+f"(d[147]), "+f"(d[148]), "+f"(d[149]), "+f"(d[150]), "+f"(d[151]), "+f"(d[152]), "+f"(d[153]), "+f"(d[154]), "+f"(d[155]), "+f"(d[156]), "+f"(d[157]), "+f"(d[158]), "+f"(d[159]), "+f"(d[160]), "+f"(d[161]), "+f"(d[162]), "+f"(d[163]), "+f"(d[164]), "+f"(d[165]), "+f"(d[166]), "+f"(d[167]), "+f"(d[168]), "+f"(d[169]), "+f"(d[170]), "+f"(d[171]), "+f"(d[172]), "+f"(d[173]), "+f"(d[174]), "+f"(d[175]), "+f"(d[176]), "+f"(d[177]), "+f"(d[178]), "+f"(d[179]), "+f"(d[180]), "+f"(d[181]), "+f"(d[182]), "+f"(d[183]), "+f"(d[184]), "+f"(d[185]), "+f"(d[186]), "+f"(d[187]), "+f"(d[188]), "+f"(d[189]), "+f"(d[190]), "+f"(d[191])
    : "r"(a[0]), "r"(a[1]), "r"(a[2]), "r"(a[3]), "l"(db), "r"(scale_d));
}
__device__ __forceinline__ void wgmma_n32_0(float (&d)[16], uint64_t da, uint64_t db) {
  asm volatile("{\n.reg .pred p;\nsetp.ne.b32 p, 0, 0;\n"
    "wgmma.mma_async.sync.aligned.m64n32k16.f32.bf16.bf16 {%0, %1, %2, %3, %4, %5, %6, %7, %8, %9, %10, %11, %12, %13, %14, %15}, %16, %17, p, 1, 1, 0, 1;\n}\n"
    : "=f"(d[0]), "=f"(d[1]), "=f"(d[2]), "=f"(d[3]), "=f"(d[4]), "=f"(d[5]), "=f"(d[6]), "=f"(d[7]), "=f"(d[8]), "=f"(d[9]), "=f"(d[10]), "=f"(d[11]), "=f"(d[12]), "=f"(d[13]), "=f"(d[14]), "=f"(d[15])
    : "l"(da), "l"(db));
}
__device__ __forceinline__ void wgmma_n32(float (&d)[16], uint64_t da, uint64_t db, int scale_d) {
  asm volatile("{\n.reg .pred p;\nsetp.ne.b32 p, %18, 0;\n"
    "wgmma.mma_async.sync.aligned.m64n32k16.f32.bf16.bf16 {%0, %1, %2, %3, %4, %5, %6, %7, %8, %9, %10, %11, %12, %13, %14, %15}, %16, %17, p, 1, 1, 0, 1;\n}\n"
    : "+f"(d[0]), "+f"(d[1]), "+f"(d[2]), "+f"(d[3]), "+f"(d[4]), "+f"(d[5]), "+f"(d[6]), "+f"(d[7]), "+f"(d[8]), "+f"(d[9]), "+f"(d[10]), "+f"(d[11]), "+f"(d[12]), "+f"(d[13]), "+f"(d[14]), "+f"(d[15])
    : "l"(da), "l"(db), "r"(scale_d));
}
__device__ __forceinline__ void wgmma_n8_t(float (&d)[4], uint64_t da, uint64_t db, int scale_d) {
  asm volatile("{\n.reg .pred p;\nsetp.ne.b32 p, %6, 0;\n"
    "wgmma.mma_async.sync.aligned.m64n8k16.f32.bf16.bf16 {%0, %1, %2, %3}, %4, %5, p, 1, 1, 1, 0;\n}\n"
    : "+f"(d[0]), "+f"(d[1]), "+f"(d[2]), "+f"(d[3])
    : "l"(da), "l"(db), "r"(scale_d));
}
__device__ __forceinline__ void wgmma_n64_lo(float (&d)[192], uint64_t da, uint64_t db, int scale_d) {
  asm volatile("{\n.reg .pred p;\nsetp.ne.b32 p, %34, 0;\n"
    "wgmma.mma_async.sync.aligned.m64n64k16.f32.bf16.bf16 {%0, %1, %2, %3, %4, %5, %6, %7, %8, %9, %10, %11, %12, %13, %14, %15, %16, %17, %18, %19, %20, %21, %22, %23, %24, %25, %26, %27, %28, %29, %30, %31}, %32, %33, p, 1, 1, 0, 1;\n}\n"
    : "+f"(d[128]), "+f"(d[129]), "+f"(d[130]), "+f"(d[131]), "+f"(d[132]), "+f"(d[133]), "+f"(d[134]), "+f"(d[135]), "+f"(d[136]), "+f"(d[137]), "+f"(d[138]), "+f"(d[139]), "+f"(d[140]), "+f"(d[141]), "+f"(d[142]), "+f"(d[143]), "+f"(d[144]), "+f"(d[145]), "+f"(d[146]), "+f"(d[147]), "+f"(d[148]), "+f"(d[149]), "+f"(d[150]), "+f"(d[151]), "+f"(d[152]), "+f"(d[153]), "+f"(d[154]), "+f"(d[155]), "+f"(d[156]), "+f"(d[157]), "+f"(d[158]), "+f"(d[159])
    : "l"(da), "l"(db), "r"(scale_d));
}
__device__ __forceinline__ void wgmma_n64_hi(float (&d)[192], uint64_t da, uint64_t db, int scale_d) {
  asm volatile("{\n.reg .pred p;\nsetp.ne.b32 p, %34, 0;\n"
    "wgmma.mma_async.sync.aligned.m64n64k16.f32.bf16.bf16 {%0, %1, %2, %3, %4, %5, %6, %7, %8, %9, %10, %11, %12, %13, %14, %15, %16, %17, %18, %19, %20, %21, %22, %23, %24, %25, %26, %27, %28, %29, %30, %31}, %32, %33, p, 1, 1, 0, 1;\n}\n"
    : "+f"(d[160]), "+f"(d[161]), "+f"(d[162]), "+f"(d[163]), "+f"(d[164]), "+f"(d[165]), "+f"(d[166]), "+f"(d[167]), "+f"(d[168]), "+f"(d[169]), "+f"(d[170]), "+f"(d[171]), "+f"(d[172]), "+f"(d[173]), "+f"(d[174]), "+f"(d[175]), "+f"(d[176]), "+f"(d[177]), "+f"(d[178]), "+f"(d[179]), "+f"(d[180]), "+f"(d[181]), "+f"(d[182]), "+f"(d[183]), "+f"(d[184]), "+f"(d[185]), "+f"(d[186]), "+f"(d[187]), "+f"(d[188]), "+f"(d[189]), "+f"(d[190]), "+f"(d[191])
    : "l"(da), "l"(db), "r"(scale_d));
}
__device__ __forceinline__ void wgmma_n128_rs0(float (&d)[192], const uint32_t (&a)[4], uint64_t db) {
  asm volatile("{\n.reg .pred p;\nsetp.ne.b32 p, 0, 0;\n"
    "wgmma.mma_async.sync.aligned.m64n128k16.f32.bf16.bf16 {%0, %1, %2, %3, %4, %5, %6, %7, %8, %9, %10, %11, %12, %13, %14, %15, %16, %17, %18, %19, %20, %21, %22, %23, %24, %25, %26, %27, %28, %29, %30, %31, %32, %33, %34, %35, %36, %37, %38, %39, %40, %41, %42, %43, %44, %45, %46, %47, %48, %49, %50, %51, %52, %53, %54, %55, %56, %57, %58, %59, %60, %61, %62, %63}, {%64, %65, %66, %67}, %68, p, 1, 1, 1;\n}\n"
    : "=f"(d[128]), "=f"(d[129]), "=f"(d[130]), "=f"(d[131]), "=f"(d[132]), "=f"(d[133]), "=f"(d[134]), "=f"(d[135]), "=f"(d[136]), "=f"(d[137]), "=f"(d[138]), "=f"(d[139]), "=f"(d[140]), "=f"(d[141]), "=f"(d[142]), "=f"(d[143]), "=f"(d[144]), "=f"(d[145]), "=f"(d[146]), "=f"(d[147]), "=f"(d[148]), "=f"(d[149]), "=f"(d[150]), "=f"(d[151]), "=f"(d[152]), "=f"(d[153]), "=f"(d[154]), "=f"(d[155]), "=f"(d[156]), "=f"(d[157]), "=f"(d[158]), "=f"(d[159]), "=f"(d[160]), "=f"(d[161]), "=f"(d[162]), "=f"(d[163]), "=f"(d[164]), "=f"(d[165]), "=f"(d[166]), "=f"(d[167]), "=f"(d[168]), "=f"(d[169]), "=f"(d[170]), "=f"(d[171]), "=f"(d[172]), "=f"(d[173]), "=f"(d[174]), "=f"(d[175]), "=f"(d[176]), "=f"(d[177]), "=f"(d[178]), "=f"(d[179]), "=f"(d[180]), "=f"(d[181]), "=f"(d[182]), "=f"(d[183]), "=f"(d[184]), "=f"(d[185]), "=f"(d[186]), "=f"(d[187]), "=f"(d[188]), "=f"(d[189]), "=f"(d[190]), "=f"(d[191])
    : "r"(a[0]), "r"(a[1]), "r"(a[2]), "r"(a[3]), "l"(db));
}
__device__ __forceinline__ void wgmma_n256_rs(float (&d)[192], const uint32_t (&a)[4], uint64_t db, int scale_d) {
  asm volatile("{\n.reg .pred p;\nsetp.ne.b32 p, %133, 0;\n"
    "wgmma.mma_async.sync.aligned.m64n256k16.f32.bf16.bf16 {%0, %1, %2, %3, %4, %5, %6, %7, %8, %9, %10, %11, %12, %13, %14, %15, %16, %17, %18, %19, %20, %21, %22, %23, %24, %25, %26, %27, %28, %29, %30, %31, %32, %33, %34, %35, %36, %37, %38, %39, %40, %41, %42, %43, %44, %45, %46, %47, %48, %49, %50, %51, %52, %53, %54, %55, %56, %57, %58, %59, %60, %61, %62, %63, %64, %65, %66, %67, %68, %69, %70, %71, %72, %73, %74, %75, %76, %77, %78, %79, %80, %81, %82, %83, %84, %85, %86, %87, %88, %89, %90, %91, %92, %93, %94, %95, %96, %97, %98, %99, %100, %101, %102, %103, %104, %105, %106, %107, %108, %109, %110, %111, %112, %113, %114, %115, %116, %117, %118, %119, %120, %121, %122, %123, %124, %125, %126, %127}, {%128, %129, %130, %131}, %132, p, 1, 1, 1;\n}\n"
    : "+f"(d[0]), "+f"(d[1]), "+f"(d[2]), "+f"(d[3]), "+f"(d[4]), "+f"(d[5]), "+f"(d[6]), "+f"(d[7]), "+f"(d[8]), "+f"(d[9]), "+f"(d[10]), "+f"(d[11]), "+f"(d[12]), "+f"(d[13]), "+f"(d[14]), "+f"(d[15]), "+f"(d[16]), "+f"(d[17]), "+f"(d[18]), "+f"(d[19]), "+f"(d[20]), "+f"(d[21]), "+f"(d[22]), "+f"(d[23]), "+f"(d[24]), "+f"(d[25]), "+f"(d[26]), "+f"(d[27]), "+f"(d[28]), "+f"(d[29]), "+f"(d[30]), "+f"(d[31]), "+f"(d[32]), "+f"(d[33]), "+f"(d[34]), "+f"(d[35]), "+f"(d[36]), "+f"(d[37]), "+f"(d[38]), "+f"(d[39]), "+f"(d[40]), "+f"(d[41]), "+f"(d[42]), "+f"(d[43]), "+f"(d[44]), "+f"(d[45]), "+f"(d[46]), "+f"(d[47]), "+f"(d[48]), "+f"(d[49]), "+f"(d[50]), "+f"(d[51]), "+f"(d[52]), "+f"(d[53]), "+f"(d[54]), "+f"(d[55]), "+f"(d[56]), "+f"(d[57]), "+f"(d[58]), "+f"(d[59]), "+f"(d[60]), "+f"(d[61]), "+f"(d[62]), "+f"(d[63]), "+f"(d[64]), "+f"(d[65]), "+f"(d[66]), "+f"(d[67]), "+f"(d[68]), "+f"(d[69]), "+f"(d[70]), "+f"(d[71]), "+f"(d[72]), "+f"(d[73]), "+f"(d[74]), "+f"(d[75]), "+f"(d[76]), "+f"(d[77]), "+f"(d[78]), "+f"(d[79]), "+f"(d[80]), "+f"(d[81]), "+f"(d[82]), "+f"(d[83]), "+f"(d[84]), "+f"(d[85]), "+f"(d[86]), "+f"(d[87]), "+f"(d[88]), "+f"(d[89]), "+f"(d[90]), "+f"(d[91]), "+f"(d[92]), "+f"(d[93]), "+f"(d[94]), "+f"(d[95]), "+f"(d[96]), "+f"(d[97]), "+f"(d[98]), "+f"(d[99]), "+f"(d[100]), "+f"(d[101]), "+f"(d[102]), "+f"(d[103]), "+f"(d[104]), "+f"(d[105]), "+f"(d[106]), "+f"(d[107]), "+f"(d[108]), "+f"(d[109]), "+f"(d[110]), "+f"(d[111]), "+f"(d[112]), "+f"(d[113]), "+f"(d[114]), "+f"(d[115]), "+f"(d[116]), "+f"(d[117]), "+f"(d[118]), "+f"(d[119]), "+f"(d[120]), "+f"(d[121]), "+f"(d[122]), "+f"(d[123]), "+f"(d[124]), "+f"(d[125]), "+f"(d[126]), "+f"(d[127])
    : "r"(a[0]), "r"(a[1]), "r"(a[2]), "r"(a[3]), "l"(db), "r"(scale_d));
}
__device__ __forceinline__ void wgmma_n256_rs0(float (&d)[192], const uint32_t (&a)[4], uint64_t db) {
  asm volatile("{\n.reg .pred p;\nsetp.ne.b32 p, 0, 0;\n"
    "wgmma.mma_async.sync.aligned.m64n256k16.f32.bf16.bf16 {%0, %1, %2, %3, %4, %5, %6, %7, %8, %9, %10, %11, %12, %13, %14, %15, %16, %17, %18, %19, %20, %21, %22, %23, %24, %25, %26, %27, %28, %29, %30, %31, %32, %33, %34, %35, %36, %37, %38, %39, %40, %41, %42, %43, %44, %45, %46, %47, %48, %49, %50, %51, %52, %53, %54, %55, %56, %57, %58, %59, %60, %61, %62, %63, %64, %65, %66, %67, %68, %69, %70, %71, %72, %73, %74, %75, %76, %77, %78, %79, %80, %81, %82, %83, %84, %85, %86, %87, %88, %89, %90, %91, %92, %93, %94, %95, %96, %97, %98, %99, %100, %101, %102, %103, %104, %105, %106, %107, %108, %109, %110, %111, %112, %113, %114, %115, %116, %117, %118, %119, %120, %121, %122, %123, %124, %125, %126, %127}, {%128, %129, %130, %131}, %132, p, 1, 1, 1;\n}\n"
    : "=f"(d[0]), "=f"(d[1]), "=f"(d[2]), "=f"(d[3]), "=f"(d[4]), "=f"(d[5]), "=f"(d[6]), "=f"(d[7]), "=f"(d[8]), "=f"(d[9]), "=f"(d[10]), "=f"(d[11]), "=f"(d[12]), "=f"(d[13]), "=f"(d[14]), "=f"(d[15]), "=f"(d[16]), "=f"(d[17]), "=f"(d[18]), "=f"(d[19]), "=f"(d[20]), "=f"(d[21]), "=f"(d[22]), "=f"(d[23]), "=f"(d[24]), "=f"(d[25]), "=f"(d[26]), "=f"(d[27]), "=f"(d[28]), "=f"(d[29]), "=f"(d[30]), "=f"(d[31]), "=f"(d[32]), "=f"(d[33]), "=f"(d[34]), "=f"(d[35]), "=f"(d[36]), "=f"(d[37]), "=f"(d[38]), "=f"(d[39]), "=f"(d[40]), "=f"(d[41]), "=f"(d[42]), "=f"(d[43]), "=f"(d[44]), "=f"(d[45]), "=f"(d[46]), "=f"(d[47]), "=f"(d[48]), "=f"(d[49]), "=f"(d[50]), "=f"(d[51]), "=f"(d[52]), "=f"(d[53]), "=f"(d[54]), "=f"(d[55]), "=f"(d[56]), "=f"(d[57]), "=f"(d[58]), "=f"(d[59]), "=f"(d[60]), "=f"(d[61]), "=f"(d[62]), "=f"(d[63]), "=f"(d[64]), "=f"(d[65]), "=f"(d[66]), "=f"(d[67]), "=f"(d[68]), "=f"(d[69]), "=f"(d[70]), "=f"(d[71]), "=f"(d[72]), "=f"(d[73]), "=f"(d[74]), "=f"(d[75]), "=f"(d[76]), "=f"(d[77]), "=f"(d[78]), "=f"(d[79]), "=f"(d[80]), "=f"(d[81]), "=f"(d[82]), "=f"(d[83]), "=f"(d[84]), "=f"(d[85]), "=f"(d[86]), "=f"(d[87]), "=f"(d[88]), "=f"(d[89]), "=f"(d[90]), "=f"(d[91]), "=f"(d[92]), "=f"(d[93]), "=f"(d[94]), "=f"(d[95]), "=f"(d[96]), "=f"(d[97]), "=f"(d[98]), "=f"(d[99]), "=f"(d[100]), "=f"(d[101]), "=f"(d[102]), "=f"(d[103]), "=f"(d[104]), "=f"(d[105]), "=f"(d[106]), "=f"(d[107]), "=f"(d[108]), "=f"(d[109]), "=f"(d[110]), "=f"(d[111]), "=f"(d[112]), "=f"(d[113]), "=f"(d[114]), "=f"(d[115]), "=f"(d[116]), "=f"(d[117]), "=f"(d[118]), "=f"(d[119]), "=f"(d[120]), "=f"(d[121]), "=f"(d[122]), "=f"(d[123]), "=f"(d[124]), "=f"(d[125]), "=f"(d[126]), "=f"(d[127])
    : "r"(a[0]), "r"(a[1]), "r"(a[2]), "r"(a[3]), "l"(db));
}

constexpr int SLOT = 16384;
constexpr int VB = 4 * SLOT, PH = 0, XS = 6;
constexpr int SM_SD = 13 * SLOT;
constexpr int SM_BAR = SM_SD + 8192;
constexpr int SM_RS = SM_BAR + 1024;
constexpr int SM_AP = SM_RS + 640;
constexpr int SM_BP = SM_AP + 2048;
constexpr int SM_EPOCH = SM_BP + 6144;
constexpr int SM_TOTAL = SM_EPOCH + 16;
constexpr int FM = 0, FT = 16, FW = 30, CM = 46, CT = 62, CW = 76, B_EF = 92, B_STAT = 93, B_KVF = 94, B_HALO = 95,
              B_KVDONE = 96, B_OH0 = 97, B_OH1 = 98, B_XH0 = 99, B_XDONE = 100, B_WFD = 101, B_XT = 102, B_OF0 = 103, B_KVF1 = 104, B_RAW = 106  , B_X0 = 108;
constexpr uint64_t BAR_LG = 0x00043333330004ull;
#define BA(i) (bar + (i) * 8)
#define REL2(i) release2c(SB0 + SM_BAR + (i) * 8)
constexpr int NF = 4, ND = 12, NR = 0, NWOP = 48, NAOP = 37;
constexpr uint64_t TL_A = 0x278627862786ull, TL_B = 0xac39bac39bacull, WO_A = 0x764a2396b4ac39ffull, WO_B = 0xc8b51c780512786bull;
__constant__ uint32_t c_wop[NWOP + 1] = {0xea8009, 0x186b8000, 0x26b8112, 0x18ec011a, 0x6c8224, 0x22ec822b, 0x170330, 0x22970339, 0x18178442, 0x18180554, 0x18188660, 0x18190772, 0x18198884, 0x181a0990, 0x181a8aa2, 0x181b0bb4, 0x181b8cc0, 0xaed90fc, 0xa9791ea, 0x181c0dd2, 0xa9812db, 0x129893c9, 0x181c8ee4, 0x181d0ff0, 0x109d94b3, 0x109f15ac, 0x109f969a, 0x10a0178b, 0x10a09879, 0x10a11963, 0x10a19a5c, 0x10a21b4a, 0x9229e0b, 0x9231f16, 0x1123a028, 0x11242137, 0x1124a242, 0x112e2351, 0x132e2465, 0x132e2570, 0x11272688, 0x1127a797, 0x112828ac, 0x1128a9b1, 0x11292ac5, 0x1129abdb, 0x112a2ce8, 0x112b2dfc, 0};
__constant__ uint32_t c_aop[NAOP + 1] = {0x6d0228, 0x170336, 0x178447, 0x180558, 0x188666, 0x190777, 0x198888, 0x1a0996, 0x1a8aa7, 0x1b0bb8, 0x1b8cc6, 0x1c0dd7, 0x1c8ee8, 0x1d0ff6, 0x1d93c2, 0x1f14b6, 0x1f95a8, 0x201697, 0x209782, 0x211876, 0x219968, 0x221a57, 0x229b42, 0xa32029, 0xa3a133, 0xa4224c, 0xa4a35a, 0xae2464, 0xa6257b, 0xa6a686, 0xa72799, 0xa7a8a3, 0xa829b2, 0xa8aaca, 0xa92bd4, 0xaa2ce6, 0xaaadf7, 0};
__constant__ uint32_t c_map[64] = {4, 5, 6, 7, 0, 16, 32, 48, 64, 80, 96, 112, 1, 17, 33, 49, 65, 81, 97, 113, 2, 18, 34, 50, 66, 82, 98, 114, 3, 19, 35, 51, 67, 83, 99, 115, 20, 36, 52, 68, 84, 100, 116, 21, 37, 53, 69, 85, 101, 117, 22, 38, 54, 70, 86, 102, 118, 23, 39, 55, 71, 87, 103, 119};
enum { MAP_WF = 0, MAP_WA = 2, MAP_WB = 4, MAP_WOA = 6, MAP_WOB = 8, MAP_X0 = 10, MAP_X = 11, MAP_O = 12, MAP_PHI = 13, NMAP = 14 };
struct Maps { CUtensorMap m[NMAP]; };

#define PL 2
#define PROFL(a, b)
#define SUBS 8
#define QORD 1
#define NCH 4
#define CHW 1
#define SUBS1 12
#define XRAT 10
#define PFW 0
#define XRN 4
#define BT1 1
#define CV0 0
#define ST1 8
#define FASTP 0
#define O1P 2
#define X0AT 1
#define W1DL 400
#define WFDL 0
#define SKA 0
#define SKB 0
#define BPRE 0
#define XST 3
#define XDR 0
#define SKW 0
#define SKL 1
#define NLAYERS 4
constexpr float L2E = 1.4426950408889634f;

#define D128(lo) desc64(lo, 0x40000040u)
struct Ctx { uint32_t zero, boff; const bf16* x0; bf16* out; };
#define BLK_CTX() \
  uint32_t bid_; asm volatile("mov.u32 %0, %%ctaid.x;" : "=r"(bid_)); \
  bid_ -= c.boff; \
  const uint32_t gr_ = c_map[bid_ >> 1]; \
  const int cr = bid_ & 1, g = gr_ & 7, rb = (gr_ >> 3) + cr, m0 = rb * 128; \
  const uint32_t sb = SB0 + (cr << 24); \
  const uint32_t bar = sb + SM_BAR; \
  (void)cr; (void)g; (void)rb; (void)m0; (void)bar;
extern __shared__ uint8_t smem_raw[];
constexpr uint32_t SB0 = 1024;

#define PHASE_CTX() \
  BLK_CTX(); \
  int tid_ = threadIdx.x; asm volatile("" : "+r"(tid_)); \
  const int lane = tid_ & 31, cw = (tid_ >> 5) - 4, wg = cw >> 2, wq = cw & 3, gq = lane >> 2, t = lane & 3, wrow0 = cw * 16; \
  const int lrow = (lane & 7) + ((lane >> 3) & 1) * 8, lchk = lane >> 4; \
  const bool elected = (tid_ & 127) == 0; \
  const uint32_t rowo = (wrow0 + lrow) * 128, X = (lchk ^ (lane & 7)) << 4; \
  const uint32_t Y = (wrow0 + (lane & 7)) * 128 + (((lane >> 3) ^ (lane & 7)) << 4); \
  const size_t gfr = (size_t)(m0 + wrow0 + gq) * D_ + g * 128 + 8 * t; \
  (void)bar; (void)wq; (void)gq; (void)lrow; (void)lchk; (void)elected; (void)wrow0; (void)wg; (void)rowo; (void)X; (void)t; (void)Y; (void)gfr;
#define MMA_CTX() \
  const uint32_t wu = __shfl_sync(0xffffffffu, wg, 0); \
  const uint32_t dA0 = ((SB0 >> 4) | (1u << 16)) + wu * 512, dB0 = (SB0 >> 4) | (512u << 16); \
  const uint32_t par = layer & 1;

__device__ __forceinline__ void slab_out_half(uint32_t slot, bf16* dst, int wrow0, int lane) {
  const int r0 = lane >> 3, ch = lane & 7;
  const uint32_t src = slot + (wrow0 + r0) * 128;
  uint4 v[4];
#pragma unroll
  for (int i = 0; i < 4; ++i) v[i] = lds128(src + i * 512 + (((ch ^ (4 * i + r0)) & 7) << 4));
  dst += (size_t)(wrow0 + r0) * D_ + ch * 8;
#pragma unroll
  for (int i = 0; i < 4; ++i) *reinterpret_cast<uint4*>(dst + (size_t)i * 4 * D_) = v[i];
}

__device__ __forceinline__ void consumer(const Ctx& c) {
  float acc[192];
  uint32_t xf[4][4];
  uint32_t xp[8][4];
  {
    PHASE_CTX();
    const unsigned int epoch = ld_relaxed(&g_epoch);
    PROFT(tid_ == 128, 0);
    const uint32_t wu = __shfl_sync(0xffffffffu, wg, 0);
    if (tid_ < 128 + 8) sts128(sb + SM_AP + lane * 16, make_uint4(0x3F803F80u, 0x3F803F80u, 0x3F803F80u, 0x3F803F80u));
#pragma unroll 1
    for (int it = 0; it < 2; ++it) {
      float p[4][16];
      mbar_wait(BA(B_RAW + it), 0);
      PROFT(tid_ == 128, it ? 15 : 2);
      const uint32_t da = ((SB0 >> 4) | (1u << 16)) + (wu ? 9 + it : 2 * it) * 1024, db = (SB0 + SM_SD) >> 4;
      wgmma_fence();
#pragma unroll
      for (int h = 0; h < 4; ++h) wgmma_n32_0(p[h], D128(da + (h >> 1) * 512 + (h & 1) * 4), desc64(db + h * 128, 0x80000020u));
#pragma unroll
      for (int h = 0; h < 4; ++h) wgmma_n32(p[h], D128(da + (h >> 1) * 512 + (h & 1) * 4 + 2), desc64(db + h * 128 + 64, 0x80000020u), 1);
      wgmma_commit();
      wgmma_wait<0>();
#pragma unroll
      for (int i = 0; i < 64; ++i) asm volatile("" : "+f"(p[i >> 4][i & 15]) :: "memory");
      const uint32_t base = sb + (wg ? 9 + it : 2 * it) * SLOT + (wq * 16 + gq) * 128;
      uint32_t w[4][4][2];
#pragma unroll
      for (int i = 0; i < 32; ++i) w[i >> 3][(i >> 1) & 3][i & 1] = pack_bf16(p[i >> 3][2 * (i & 7)], p[i >> 3][2 * (i & 7) + 1]);
      if (wu) {
#pragma unroll
        for (int i = 0; i < 8; ++i)
          sts128(base + (i >> 2) * 8192 + (i & 1) * 1024 + (((((i >> 1) & 1) * 4 + t) ^ gq) << 4), make_uint4(w[i >> 1][0][i & 1], w[i >> 1][1][i & 1], w[i >> 1][2][i & 1], w[i >> 1][3][i & 1]));
      } else {
#pragma unroll
        for (int i = 0; i < 16; ++i)
          sts64(base + (i >> 3) * 8192 + (i & 1) * 1024 + ((((t & 1) * 4 + ((i >> 1) & 3)) ^ gq) << 4) + (t >> 1) * 8, w[(i >> 3) * 2][(i >> 1) & 3][i & 1], w[(i >> 3) * 2 + 1][(i >> 1) & 3][i & 1]);
      }
      fence_async_smem();
      __syncwarp();
      if (it == cr && lane == 0) mbar_arrive(BA(B_WFD));
    }
    if (tid_ == 128) sts_f(sb + SM_EPOCH, __uint_as_float(epoch & 1));
#pragma unroll
    for (int i = 0; i < 32; ++i) xp[i >> 2][i & 3] = 0u;
    nbar<1, 256>();
    PROFT(tid_ == 128, 13);
    mbar_wait(BA(FM + cr), 0);
    float cs[3][4];
    wgmma_fence();
#pragma unroll
    for (int ks = 0; ks < 4; ++ks)
#pragma unroll
      for (int i = 0; i < 3; ++i) {
        const uint32_t bx = (i == 0 ? 2 * cr * 1024 : i == 1 ? (2 * cr + 1) * 1024 : (9 + cr) * 1024) + wu * 512;
        wgmma_n8_t(cs[i], D128(((SB0 >> 4) | (512u << 16)) + bx + ks * 128), desc64((SB0 + SM_AP) >> 4, 0), ks != 0);
      }
    wgmma_commit();
    mbar_wait(BA(FM), 0);
#pragma unroll
    for (int k = 0; k < 4; ++k) ldsm_x4(xf[k][0], xf[k][1], xf[k][2], xf[k][3], sb + XS * SLOT + rowo + (X ^ (k << 5)));
    wgmma_wait<0>();
#pragma unroll
    for (int i = 0; i < 12; ++i) asm volatile("" : "+f"(cs[i >> 2][i & 3]) :: "memory");
    if (t < 2) {
#pragma unroll
      for (int i = 0; i < 3; ++i) red_add1(g_cs + (epoch & 1) * 6144 + g * 384 + i * 128 + wg * 64 + wq * 16 + gq + t * 8, t ? cs[i][2] : cs[i][0]);
    }
    PROFT(tid_ == 128, 14);
  }
#pragma unroll 1
  for (int layer = 0;; ++layer) {
    {
      PHASE_CTX();
      MMA_CTX();
      {
        const uint32_t ep = __float_as_uint(lds_f(sb + SM_EPOCH));
        mbar_wait(BA(FM), par);
        wgmma_fence();
        wgmma_n256_rs0(acc, xf[0], D128(dB0));
#pragma unroll
        for (int k = 1; k < 4; ++k) wgmma_n256_rs(acc, xf[k], D128(dB0 + k * 128), 1);
        wgmma_commit();
        if (layer == 0) {
          mbar_wait(BA(B_X0), 0);
#pragma unroll
          for (int i = 0; i < 8; ++i) ldsm_x4(xp[i][0], xp[i][1], xp[i][2], xp[i][3], sb + (11 + (i >> 2)) * SLOT + (Y ^ ((i & 2) << 5)) + (i & 1) * 1024);
          if (lane == ((xp[0][0] ^ xp[1][0] ^ xp[2][0] ^ xp[3][0] ^ xp[7][0]) & c.zero)) REL2(B_XT);
        } else {
#pragma unroll
          for (int i = 0; i < 8; ++i) stsm_x4(sb + (XS + (i >> 2)) * SLOT + (Y ^ ((i & 2) << 5)) + (i & 1) * 1024, xp[i][0], xp[i][1], xp[i][2], xp[i][3]);
        }
        float s0 = 0.f, s1 = 0.f, q0 = 0.f, q1 = 0.f;
        auto stats = [&](int j0, int j1) {
#pragma unroll
          for (int j = j0; j < j1; ++j) {
            const uint32_t u0 = xp[(j >> 2) * 2][j & 3], u1 = xp[(j >> 2) * 2 + 1][j & 3];
            s0 += bf_lo(u0) + bf_hi(u0); s1 += bf_lo(u1) + bf_hi(u1);
            q0 = fmaf(bf_lo(u0), bf_lo(u0), fmaf(bf_hi(u0), bf_hi(u0), q0)); q1 = fmaf(bf_lo(u1), bf_lo(u1), fmaf(bf_hi(u1), bf_hi(u1), q1));
          }
        };
        stats(0, ST1);
        fence_async_smem();
        nbar_dyn(3 + wu + (__float_as_uint(s0 + s1 + q0 + q1) & c.zero), 128);
        mbar_wait(BA(FM + 1), par);
        wgmma_fence();
#pragma unroll
        for (int k = 0; k < 4; ++k) wgmma_n256(acc, D128(dA0 + (XS + 1) * 1024 + k * 2), D128(dB0 + 2048 + k * 128), 1);
        wgmma_commit();
        wgmma_wait<1>();
#pragma unroll
        for (int i = 4; i < 8; ++i) stg128_p(layer, g_x + gfr + (i & 1) * 8 * D_ + (i >> 1) * 32, xp[i][0], xp[i][1], xp[i][2], xp[i][3]);
        {
          uint32_t zc; asm volatile("mov.u32 %0, %%clock;" : "=r"(zc) :: "memory");
          q0 += __uint_as_float(zc & c.zero); q1 += __uint_as_float(zc & c.zero); s0 += __uint_as_float(zc & c.zero); s1 += __uint_as_float(zc & c.zero);
        }
        stats(ST1, 16);
        wgmma_fence();
        wgmma_n128_0(acc, D128(dA0 + XS * 1024), D128(dB0 + 9 * 1024));
#pragma unroll
        for (int k = 1; k < 4; ++k) wgmma_n128(acc, D128(dA0 + XS * 1024 + k * 2), D128(dB0 + 9 * 1024 + k * 128), 1);
        wgmma_commit();
        const bool od = t & 1;
        float sa = od ? s1 : s0, qa = od ? q1 : q0;
        sa += __shfl_xor_sync(0xffffffffu, od ? s0 : s1, 1);
        qa += __shfl_xor_sync(0xffffffffu, od ? q0 : q1, 1);
        wgmma_fence();
#pragma unroll
        for (int k = 0; k < 4; ++k) wgmma_n128(acc, D128(dA0 + (XS + 1) * 1024 + k * 2), D128(dB0 + 10 * 1024 + k * 128), 1);
        wgmma_commit();
        sa += __shfl_xor_sync(0xffffffffu, sa, 2);
        qa += __shfl_xor_sync(0xffffffffu, qa, 2);
        red_add2_p(t < 2, reinterpret_cast<float*>(g_stats + (ep * 4 + layer) * S_ + m0 + wrow0 + gq + t * 8), sa, qa);
        __syncwarp();
        if (lane == 0) mbar_arrive(BA(B_XDONE));
        wgmma_wait<1>();
        if (elected) REL2(CM);
      }
      uint32_t s = 2;
#pragma unroll 1
      for (int i = 2; i < NF; ++i) {
        PROFL(tid_ == 128 && layer == PL + 1, 244 + 2 * i);
        mbar_wait(BA(FM + i), par);
        PROFL(tid_ == 128 && layer == PL + 1, 245 + 2 * i);
        const uint32_t da = dA0 + (XS + s) * 1024, dk = dB0 + s * 2048, dq = dB0 + (9 + s) * 1024;
        wgmma_fence();
#pragma unroll
        for (int k = 0; k < 4; ++k) wgmma_n128(acc, D128(da + k * 2), D128(dq + k * 128), 1);
        wgmma_commit();
        wgmma_wait<1>();
        if (elected) REL2(CM + i - 1);
        wgmma_fence();
#pragma unroll
        for (int k = 0; k < 4; ++k) wgmma_n256(acc, D128(da + k * 2), D128(dk + k * 128), 1);
        wgmma_commit();
        if (++s == 3) s = 0;
      }
#pragma unroll 1
      for (int i = NF; i < 15; ++i) {
        mbar_wait(BA(FM + i), par);
        const uint32_t da = dA0 + (XS + s) * 1024, dk = dB0 + s * 2048;
        wgmma_fence();
#pragma unroll
        for (int k = 0; k < 4; ++k) wgmma_n256(acc, D128(da + k * 2), D128(dk + k * 128), 1);
        wgmma_commit();
        wgmma_wait<1>();
        if (elected) REL2(CM + i - 1);
        if (++s == 3) s = 0;
      }
      {
        const uint64_t dap = desc64(((SB0 + SM_AP) >> 4) + wu * 64, 8), dbp = make_desc_ns(SB0 + SM_BP, 0, 128);
        mbar_wait(BA(B_STAT), par);
        mbar_wait(BA(FM + 15), par);
        PROFT(tid_ == 128, layer * 16 + 9);
        wgmma_fence();
        wgmma_n256_k(acc, dap, dbp, 1);
#pragma unroll
        for (int k = 0; k < 4; ++k) wgmma_n256(acc, D128(dA0 + XS * 1024 + k * 2), D128(dB0 + k * 128), 1);
        wgmma_commit();
        wgmma_wait<1>();
        if (elected) REL2(CM + 14);
        mbar_wait(BA(FT), par);
        wgmma_fence();
        wgmma_n128_k(acc, dap, dbp + 256, 1);
#pragma unroll
        for (int k = 0; k < 4; ++k) wgmma_n128(acc, D128(dA0 + (uint32_t)(TL_A & 15) * 1024 + k * 2), D128(dB0 + (uint32_t)(TL_B & 15) * 1024 + k * 128), 1);
        wgmma_commit();
        wgmma_wait<1>();
        if (elected) REL2(CM + 15);
#pragma unroll
        for (int i = 0; i < 128; ++i) asm volatile("" : "+f"(acc[i]) :: "memory");
      }
    }
    uint32_t of[8][4], o1[4][4];
    {
      PHASE_CTX();
      MMA_CTX();
      PROFT(tid_ == 128, layer * 16 + 1);
      PROFT(lane == 0 && layer == PL, 192 + cw);
      PROFT(tid_ == 128 && layer == PL, 160);
      uint64_t ta = (TL_A >> 4), tw = TL_B >> 4;
      uint32_t da, db, dz = dA0;
      auto sub = [&](int n) {
        const int j = n >> 2, k = n & 3;
        if (k == 0) {
          dz += c.zero;
          da = dz + ((uint32_t)ta & 15) * 1024; db = dB0 + ((uint32_t)tw & 15) * 1024;
          ta >>= 4; tw >>= 4;
          mbar_wait(BA(FT + j), par);
          wgmma_fence();
        }
        wgmma_n128(acc, D128(da + k * 2), D128(db + k * 128), 1);
        if (k == 3) {
          wgmma_commit();
          wgmma_wait<1>();
          if (elected) REL2(CT + j - 1);
        }
      };
      auto run = [&](int j0, int j1) {
#pragma unroll 1
        for (int j = j0; j < j1; ++j) {
          mbar_wait(BA(FT + j), par);
          da = dA0 + ((uint32_t)ta & 15) * 1024; db = dB0 + ((uint32_t)tw & 15) * 1024;
          ta >>= 4; tw >>= 4;
          wgmma_fence();
#pragma unroll
          for (int k = 0; k < 4; ++k) wgmma_n128(acc, D128(da + k * 2), D128(db + k * 128), 1);
          wgmma_commit();
          wgmma_wait<1>();
          if (elected) REL2(CT + j - 1);
        }
        ta = TL_A >> (4 * j1); tw = TL_B >> (4 * j1);
      };
      auto rest = [&](int j0, int sk) {
        if (sk) {
          run(j0, ND - sk);
          if (wu == 0) nbar<6, 256>();
          j0 = ND - sk;
        }
        run(j0, ND);
        if (sk && wu) asm volatile("bar.arrive 6, 256;" ::: "memory");
      };
      auto rest_end = [&]() {
        wgmma_wait<0>();
        if (elected) REL2(CT + ND - 1);
#pragma unroll
        for (int i = 128; i < 192; ++i) asm volatile("" : "+f"(acc[i]) :: "memory");
      };
      const float rs0 = lds_f(sb + SM_RS + (16 + wrow0 + gq) * 4), rs1 = lds_f(sb + SM_RS + (24 + wrow0 + gq) * 4);
#define EPOCH() __float_as_uint(lds_f(sb + SM_EPOCH))
      mbar_wait(BA(CM + 14), par);
      if (par) {
        uint32_t kk[8][4], kp[8][4], vf[2][2][4][4];
        int sn = 4;
#pragma unroll
        for (int i = 0; i < 4 * BT1; ++i) sub(sn++);
        {
          uint32_t vv[8][4];
#pragma unroll
          for (int jp = 0; jp < 8; ++jp) {
            kk[jp][0] = pack_bf16(acc[8 * jp], acc[8 * jp + 1]); kk[jp][1] = pack_bf16(acc[8 * jp + 4], acc[8 * jp + 5]);
            kk[jp][2] = pack_bf16(acc[8 * jp + 2], acc[8 * jp + 3]); kk[jp][3] = pack_bf16(acc[8 * jp + 6], acc[8 * jp + 7]);
#pragma unroll
            for (int i = 0; i < 4; ++i) vv[jp][i] = pack_bf16(acc[64 + 8 * jp + 2 * i], acc[65 + 8 * jp + 2 * i]);
          }
          if (cw == 7) {
            uint32_t* const hbuf = g_halo + (size_t)(((layer >> 1) * 17 + rb + 1) * 8 + g) * 2048;
#pragma unroll
            for (int jp = 0; jp < 8; ++jp) stg128(hbuf + jp * 128 + lane * 4, kk[jp][0], kk[jp][1], kk[jp][2], kk[jp][3]);
#pragma unroll
            for (int i = 0; i < 32; ++i) hbuf[1024 + (i >> 4) * 512 + (gq + (i & 1) * 8) * 32 + ((((i >> 1) & 7) ^ gq) << 2) + t] = vv[i >> 2][i & 3];
            __syncwarp();
            if (lane == 0) mbar_arrive(BA(B_OF0));
          }
#pragma unroll
          for (int jp = 0; jp < 8; ++jp) {
            sub(sn++);
            stsm_x4(sb + VB + (jp >> 2) * SLOT + rowo + (X ^ ((jp & 3) << 5)), vv[jp][0], vv[jp][1], vv[jp][2], vv[jp][3]);
          }
        }
        PROFT(tid_ == 128, layer * 16 + 2);
        const int e = gq & 1;
        float f0[4], f1[4], b0[4], b1[4], rj[4];
#pragma unroll
        for (int nt = 0; nt < 4; ++nt) {
          const int kx = nt * 8 + 2 * t + e;
          const bool okk = (m0 + wrow0 + kx) >= 16;
          const int d0 = kx - gq, d1 = d0 - 8;
          rj[nt] = lds_f(sb + SM_RS + (wrow0 + kx) * 4);
          const bool m0_ = okk && d0 >= 2 && d0 <= 16, m1_ = okk && d1 >= 2 && d1 <= 16;
          f0[nt] = m0_ ? rj[nt] * rs0 * (0.17677669529663687f * L2E) : 0.f;
          f1[nt] = m1_ ? rj[nt] * rs1 * (0.17677669529663687f * L2E) : 0.f;
          b0[nt] = m0_ ? 0.f : -1e30f; b1[nt] = m1_ ? 0.f : -1e30f;
        }
        mbar_wait(BA(CM + 15), par);
#pragma unroll
        for (int jp = 0; jp < 8; ++jp) {
          sub(sn++);
          sts128(sb + PH + cw * 4096 + jp * 512 + lane * 16, make_uint4(kk[jp][0], kk[jp][1], kk[jp][2], kk[jp][3]));
        }
#pragma unroll
        for (int i = 0; i < 4; ++i) sub(sn++);
        nbar<1, 256>();
        PROFT(tid_ == 128, layer * 16 + 3);
        rest(sn >> 2, SKB);
        if (!BPRE) rest_end();
        PROFT(lane == 0 && layer == PL, 200 + cw);
        PROFT(tid_ == 128, layer * 16 + 10);
        if (cw == 0) mbar_wait(BA(B_HALO), (layer >> 1) & 1);
        PROFT(tid_ == 128, layer * 16 + 5);
        const uint32_t vs = sb + (cw ? VB + rowo - 2048 : SM_SD + 4096 + rowo), vst = cw ? SLOT : 2048;
        const uint32_t psel = e ? 0x1054u : 0x5410u;
#pragma unroll
        for (int hp = 0; hp < 2; ++hp) {
#pragma unroll
          for (int i = 4 * hp; i < 4 * hp + 4; ++i) {
            const uint4 u = lds128(sb + (cw ? PH + (cw - 1) * 4096 : SM_SD) + lane * 16 + i * 512);
            kp[i][0] = u.x; kp[i][1] = u.y; kp[i][2] = u.z; kp[i][3] = u.w;
          }
#pragma unroll
          for (int i = 4 * hp; i < 4 * hp + 4; ++i) {
            ldsm_x4_t(vf[0][i & 1][i >> 1][0], vf[0][i & 1][i >> 1][1], vf[0][i & 1][i >> 1][2], vf[0][i & 1][i >> 1][3], vs + (i >> 2) * vst + (X ^ ((i & 3) << 5)));
            ldsm_x4_t(vf[1][i & 1][i >> 1][0], vf[1][i & 1][i >> 1][1], vf[1][i & 1][i >> 1][2], vf[1][i & 1][i >> 1][3], sb + VB + (i >> 2) * SLOT + rowo + (X ^ ((i & 3) << 5)));
          }
          if (BPRE && !hp) rest_end();
          float l0[2][4], l1[2][4];
#pragma unroll
          for (int h = 0; h < 2; ++h) {
            const int H = 2 * hp + h;
            uint32_t qa[8];
#pragma unroll
            for (int i = 0; i < 8; ++i) qa[i] = pack_bf16(acc[128 + 16 * H + 2 * i], acc[129 + 16 * H + 2 * i]);
#pragma unroll
            for (int nt = 3; nt >= 0; --nt) {
              float sc[4] = {0.f, 0.f, 0.f, 0.f};
#pragma unroll
              for (int ks = 0; ks < 2; ++ks) {
                const uint32_t (&kf)[4] = nt < 2 ? kp[2 * H + ks] : kk[2 * H + ks];
                mma_bf16(sc, qa[4 * ks], qa[4 * ks + 1], qa[4 * ks + 2], qa[4 * ks + 3], kf[2 * (nt & 1)], kf[2 * (nt & 1) + 1]);
              }
              l0[h][nt] = fmaf(e ? sc[1] : sc[0], f0[nt], b0[nt]);
              l1[h][nt] = fmaf(e ? sc[3] : sc[2], f1[nt], b1[nt]);
            }
          }
          float mx0[2], mx1[2], s0[2], s1[2];
#pragma unroll
          for (int h = 0; h < 2; ++h) {
            mx0[h] = fmaxf(fmaxf(l0[h][0], l0[h][1]), l0[h][2]);
            mx1[h] = fmaxf(fmaxf(l1[h][1], l1[h][2]), l1[h][3]);
          }
#pragma unroll
          for (int o = 1; o <= 2; o <<= 1)
#pragma unroll
            for (int h = 0; h < 2; ++h) {
              mx0[h] = fmaxf(mx0[h], __shfl_xor_sync(0xffffffffu, mx0[h], o));
              mx1[h] = fmaxf(mx1[h], __shfl_xor_sync(0xffffffffu, mx1[h], o));
            }
#pragma unroll
          for (int h = 0; h < 2; ++h) {
#pragma unroll
            for (int nt = 0; nt < 3; ++nt) { l0[h][nt] = ex2(l0[h][nt] - mx0[h]); l1[h][nt + 1] = ex2(l1[h][nt + 1] - mx1[h]); }
            s0[h] = (l0[h][0] + l0[h][1]) + l0[h][2];
            s1[h] = (l1[h][1] + l1[h][2]) + l1[h][3];
          }
#pragma unroll
          for (int o = 1; o <= 2; o <<= 1)
#pragma unroll
            for (int h = 0; h < 2; ++h) {
              s0[h] += __shfl_xor_sync(0xffffffffu, s0[h], o);
              s1[h] += __shfl_xor_sync(0xffffffffu, s1[h], o);
            }
          uint32_t ow[2][2][4];
#pragma unroll
          for (int h = 0; h < 2; ++h) {
            const int H = 2 * hp + h;
            uint32_t pl[4], ph[4];
            const float i0 = rcp(s0[h]), i1 = rcp(s1[h]);
#pragma unroll
            for (int nt = 0; nt < 4; ++nt) {
              const uint32_t pk = pack_bf16(nt < 3 ? l0[h][nt] * i0 * rj[nt] : 0.f, nt > 0 ? l1[h][nt] * i1 * rj[nt] : 0.f);
              pl[nt] = nt < 3 ? __byte_perm(pk, 0u, psel) : 0u;
              ph[nt] = nt > 0 ? __byte_perm(pk, 0u, psel + 0x2222u) : 0u;
            }
#pragma unroll
            for (int nj = 0; nj < 4; ++nj) {
              float oa[4] = {0.f, 0.f, 0.f, 0.f};
#pragma unroll
              for (int ks = 0; ks < 2; ++ks)
                mma_bf16(oa, pl[2 * ks], ph[2 * ks], pl[2 * ks + 1], ph[2 * ks + 1], vf[ks][nj >> 1][H][2 * (nj & 1)], vf[ks][nj >> 1][H][2 * (nj & 1) + 1]);
              ow[h][0][nj] = pack_bf16(oa[0], oa[1]); ow[h][1][nj] = pack_bf16(oa[2], oa[3]);
            }
          }
          if (hp == 0) {
#pragma unroll
            for (int i = 0; i < 4; ++i) stg128(g_o + gfr + (i & 1) * 8 * D_ + (i >> 1) * 32, ow[i >> 1][i & 1][0], ow[i >> 1][i & 1][1], ow[i >> 1][i & 1][2], ow[i >> 1][i & 1][3]);
            __syncwarp();
            if (lane == 0) mbar_arrive(BA(B_OH0));
          } else {
#pragma unroll
            for (int i = 0; i < 16; ++i) o1[i >> 2][i & 3] = ow[i >> 3][(i >> 2) & 1][i & 3];
          }
#pragma unroll
          for (int i = 0; i < 16; ++i) of[4 * hp + (i >> 2)][i & 3] = ow[i >> 3][i & 1][(i >> 1) & 3];
          if (!hp) PROFT(tid_ == 128, layer * 16 + 15);
        }
      } else {
        float sc[2] = {rs0 * L2E, rs1 * L2E};
        {
          const uint32_t vb = sb + VB + (rowo >> 1), X0 = (lchk ^ ((lane & 7) >> 1)) << 4;
          const uint32_t pb = sb + PH + (t & 1) * SLOT + (wrow0 + gq) * 128 + ((((t & 1) * 4 + (t & 2)) ^ gq) << 4);
          float kva[20], en[32], mx[2][2], mn[2][2];
#define PV(hp, j) acc[32 * (hp) + (j)]
          auto mm = [&](int hp, int j) {
            const int r = (j >> 1) & 1;
            if (j < 4 && !(j & 1)) { mx[hp][r] = PV(hp, j); mn[hp][r] = PV(hp, j); }
            else { mx[hp][r] = fmaxf(mx[hp][r], PV(hp, j)); mn[hp][r] = fminf(mn[hp][r], PV(hp, j)); }
          };
          auto mmx = [&](int hp) {
#pragma unroll
            for (int r = 0; r < 2; ++r) {
              mx[hp][r] = fmaxf(mx[hp][r], __shfl_xor_sync(0xffffffffu, mx[hp][r], 2)) * -sc[r];
              mn[hp][r] = fmaf(fminf(mn[hp][r], __shfl_xor_sync(0xffffffffu, mn[hp][r], 2)), sc[r], mx[hp][r]);
            }
          };
          auto stage = [&](int hp) {
#pragma unroll
            for (int i = 0; i < 20; ++i) asm volatile("" : "+f"(kva[i]) :: "memory");
            nbar_dyn(3 + wu, 128);
#pragma unroll
            for (int i = 0; i < 4; ++i)
              sts128(sb + VB + hp * SLOT + wg * 8192 + (wq * 128 + i * 32 + lane) * 16,
                     make_uint4(__float_as_uint(kva[4 * i]), __float_as_uint(kva[4 * i + 1]), __float_as_uint(kva[4 * i + 2]), __float_as_uint(kva[4 * i + 3])));
            if (t == 0) sts_f2(sb + SM_AP + ((2 * hp + wg) * 64 + wq * 16 + gq * 2) * 4, kva[16], kva[18]);
            fence_async_smem();
            __syncwarp();
            if (lane == 0) mbar_arrive(BA(B_KVDONE));
          };
          int sn = 4;
#pragma unroll
          for (int j = 0; j < 32; ++j) mm(0, j);
          mmx(0);
#pragma unroll
          for (int hp = 0; hp < 2; ++hp) {
            float sp[2] = {0.f, 0.f}, sm[2] = {0.f, 0.f};
#pragma unroll
            for (int j = 0; j < 32; ++j) {
              const int r = (j >> 1) & 1, ns = hp ? SUBS1 : SUBS;
              if ((j * ns) / 32 != ((j + 1) * ns) / 32) {
                sub(sn++);
                if (hp && sn == 4 + SUBS + 4 + 4 * (XST & 1)) { stage(0); PROFT(tid_ == 128, layer * 16 + 12); }
              }
              const float x = fmaf(PV(hp, j), sc[r], mx[hp][r]);
              PV(hp, j) = ex2(x); en[j] = ex2(mn[hp][r] - x);
              sp[r] += PV(hp, j); sm[r] += en[j];
              if (hp == 0) {
                mm(1, j);
                if ((j & 3) == 0) {
                  const int jp = 8 + (j >> 2);
                  stsm_x4(vb + ((jp - 8) >> 1) * 8192 + (X0 ^ ((jp & 1) << 5)), pack_bf16(acc[8 * jp], acc[8 * jp + 1]), pack_bf16(acc[8 * jp + 2], acc[8 * jp + 3]),
                          pack_bf16(acc[8 * jp + 4], acc[8 * jp + 5]), pack_bf16(acc[8 * jp + 6], acc[8 * jp + 7]));
                }
              }
            }
#pragma unroll
            for (int i = 0; i < 4; ++i) if (XST & (1 << hp)) sub(sn++);
#pragma unroll
            for (int r = 0; r < 2; ++r) {
              sp[r] = rcp(sp[r] + __shfl_xor_sync(0xffffffffu, sp[r], 2)) * (r ? rs1 : rs0);
              sm[r] = rcp(sm[r] + __shfl_xor_sync(0xffffffffu, sm[r], 2)) * (r ? rs1 : rs0);
            }
            if (hp == 0) { mmx(1); mbar_wait(BA(CM + 15), par); }
            else { PROFT(tid_ == 128, layer * 16 + 11); nbar<1, 256>(); }
#pragma unroll
            for (int i = 0; i < 4; ++i) {
              const int r = i & 1, d = 16 * (i >> 1) + 2 * r;
              sts128((pb + r * 1024) ^ ((i >> 1) << 4), make_uint4(pack_bf16(PV(hp, d) * sp[r], PV(hp, d + 1) * sp[r]), pack_bf16(PV(hp, d + 4) * sp[r], PV(hp, d + 5) * sp[r]),
                                                                    pack_bf16(PV(hp, d + 8) * sp[r], PV(hp, d + 9) * sp[r]), pack_bf16(PV(hp, d + 12) * sp[r], PV(hp, d + 13) * sp[r])));
              sts128((pb + r * 1024) ^ ((i >> 1) << 4) ^ 64, make_uint4(pack_bf16(en[d] * sm[r], en[d + 1] * sm[r]), pack_bf16(en[d + 4] * sm[r], en[d + 5] * sm[r]),
                                                                         pack_bf16(en[d + 8] * sm[r], en[d + 9] * sm[r]), pack_bf16(en[d + 12] * sm[r], en[d + 13] * sm[r])));
            }
            fence_async_smem();
            nbar<1, 256>();
            const uint32_t dP = dB0 + (PH >> 4) + wu * 1024;
            const uint32_t dV = (dB0 & 0xFFFFu) + ((VB + hp * SLOT) >> 4) + (((SM_SD - VB - hp * SLOT) >> 4) << 16) + wu * (512u - (512u << 16));
            wgmma_fence();
#pragma unroll
            for (int ks = 0; ks < 8; ++ks) wgmma_n40_tt(kva, D128(dP + ks * 128), desc64(dV + ks * 64, 0x80000020u), ks != 0);
            wgmma_commit();
          }
#pragma unroll
          for (int i = 0; i < 4; ++i) sub(sn++);
          stage(1);
          PROFT(tid_ == 128, layer * 16 + 3);
          rest(sn >> 2, SKA);
          rest_end();
          PROFT(lane == 0 && layer == PL, 200 + cw);
          PROFT(tid_ == 128, layer * 16 + 10);
        }
#define QV(H, i) acc[128 + 16 * (H) + (i)]
        float mx[4][2], mn[4][2];
        uint32_t ph[4][4][4];
        auto mnx = [&](int hp) {
#pragma unroll
          for (int H = 2 * hp; H < 2 * hp + 2; ++H)
#pragma unroll
            for (int r = 0; r < 2; ++r) {
              mx[H][r] = fmaxf(fmaxf(fmaxf(QV(H, 2 * r), QV(H, 2 * r + 1)), fmaxf(QV(H, 4 + 2 * r), QV(H, 5 + 2 * r))),
                               fmaxf(fmaxf(QV(H, 8 + 2 * r), QV(H, 9 + 2 * r)), fmaxf(QV(H, 12 + 2 * r), QV(H, 13 + 2 * r))));
              mn[H][r] = fminf(fminf(fminf(QV(H, 2 * r), QV(H, 2 * r + 1)), fminf(QV(H, 4 + 2 * r), QV(H, 5 + 2 * r))),
                               fminf(fminf(QV(H, 8 + 2 * r), QV(H, 9 + 2 * r)), fminf(QV(H, 12 + 2 * r), QV(H, 13 + 2 * r))));
            }
#pragma unroll
          for (int o = 1; o <= 2; o <<= 1)
#pragma unroll
            for (int H = 2 * hp; H < 2 * hp + 2; ++H)
#pragma unroll
              for (int r = 0; r < 2; ++r) {
                mx[H][r] = fmaxf(mx[H][r], __shfl_xor_sync(0xffffffffu, mx[H][r], o));
                mn[H][r] = fminf(mn[H][r], __shfl_xor_sync(0xffffffffu, mn[H][r], o));
              }
#pragma unroll
          for (int H = 2 * hp; H < 2 * hp + 2; ++H)
#pragma unroll
            for (int r = 0; r < 2; ++r) { mx[H][r] *= -sc[r]; mn[H][r] = fmaf(mn[H][r], sc[r], mx[H][r]); }
        };
        auto fm = [&](int H) {
#pragma unroll
          for (int i = 0; i < 8; ++i) {
            const int r = i & 1;
            const float x0 = fmaf(QV(H, 2 * i), sc[r], mx[H][r]), x1 = fmaf(QV(H, 2 * i + 1), sc[r], mx[H][r]);
            ph[H][i >> 2][i & 3] = pack_bf16(ex2(x0), ex2(x1));
            ph[H][2 + (i >> 2)][i & 3] = pack_bf16(ex2(mn[H][r] - x0), ex2(mn[H][r] - x1));
          }
        };
        auto conv = [&](int hp) {
          mbar_wait(BA(hp ? B_KVF1 : B_KVF), (layer >> 1) & 1);
          PROFT(tid_ == 128, layer * 16 + (hp ? 4 : 5));
          if (hp) nbar_dyn(3 + wu, 128);
#pragma unroll
          for (int h = 0; h < 2; ++h) {
            uint4 u[4];
#pragma unroll
            for (int i = 0; i < 4; ++i) u[i] = lds128(sb + VB + hp * SLOT + h * 8192 + (wq * 128 + i * 32 + lane) * 16);
            const float zz = lds_f(sb + SM_AP + ((2 * hp + h) * 64 + wq * 16 + (lane & 7) * 2 + ((lane >> 3) & 1)) * 4);
            const uint32_t kb_ = sb + PH + wg * SLOT + h * 8192 + (wq * 16 + lrow) * 128;
#pragma unroll
            for (int i = 0; i < 4; i += 2)
              stsm_x4(kb_ + (X ^ (i << 4)),
                      pack_bf16(__uint_as_float(u[i].x), __uint_as_float(u[i].y)), pack_bf16(__uint_as_float(u[i].z), __uint_as_float(u[i].w)),
                      pack_bf16(__uint_as_float(u[i + 1].x), __uint_as_float(u[i + 1].y)), pack_bf16(__uint_as_float(u[i + 1].z), __uint_as_float(u[i + 1].w)));
            const uint32_t z1 = pack_bf16(zz, 1.f);
            if (lane < 16) sts128(kb_ + ((4 ^ (lane & 7)) << 4), make_uint4(z1, z1, z1, z1));
          }
          fence_async_smem();
        };
        mnx(0);
        fm(0);
        if (CV0) conv(0);
        fm(1);
        if (!CV0) conv(0);
#pragma unroll
        for (int hp = 0; hp < 2; ++hp) {
          nbar_dyn(3 + wu, 128);
          float oa[4][20];
          wgmma_fence();
#pragma unroll
          for (int s = 0; s < 2; ++s)
#pragma unroll
            for (int v = 0; v < 4; ++v) {
              const int h = v >> 1, s4 = 2 * (v & 1) + s;
              wgmma_n40_rs(oa[v], ph[2 * hp + h][s4], D128(dB0 + (PH >> 4) + wu * 1024 + h * 512 + (s4 ^ (2 * h)) * 128), s != 0);
            }
          wgmma_commit();
          if (hp == 0) mnx(1);
          wgmma_wait<0>();
#pragma unroll
          for (int i = 0; i < 20; ++i) asm volatile("" : "+f"(oa[0][i]), "+f"(oa[1][i]), "+f"(oa[2][i]), "+f"(oa[3][i]) :: "memory");
          uint32_t ow[2][2][4];
#pragma unroll
          for (int h = 0; h < 2; ++h)
#pragma unroll
            for (int r = 0; r < 2; ++r) {
              const float a = oa[2 * h + 1][17 + 2 * r], b = oa[2 * h][17 + 2 * r];
              const float id = rcp(fmaf(oa[2 * h][16 + 2 * r], a, fmaf(a, 1e-6f, oa[2 * h + 1][16 + 2 * r]) * b));
              const float fa = a * id, fb = b * id;
#pragma unroll
              for (int j = 0; j < 4; ++j)
                ow[h][r][j] = pack_bf16(fmaf(oa[2 * h][4 * j + 2 * r], fa, oa[2 * h + 1][4 * j + 2 * r] * fb),
                                        fmaf(oa[2 * h][4 * j + 2 * r + 1], fa, oa[2 * h + 1][4 * j + 2 * r + 1] * fb));
            }
#pragma unroll
          for (int i = 0; i < 16; ++i) of[4 * hp + (i >> 2)][i & 3] = ow[i >> 3][i & 1][(i >> 1) & 3];
          if (hp == 0) {
#pragma unroll
            for (int i = 0; i < 8; ++i) {
              if (!(i & 1)) stg128(g_o + gfr + ((i >> 1) & 1) * 8 * D_ + (i >> 2) * 32, ow[i >> 2][(i >> 1) & 1][0], ow[i >> 2][(i >> 1) & 1][1], ow[i >> 2][(i >> 1) & 1][2], ow[i >> 2][(i >> 1) & 1][3]);
              const int r = i & 1;
              const float x0 = fmaf(QV(2, 2 * i), sc[r], mx[2][r]), x1 = fmaf(QV(2, 2 * i + 1), sc[r], mx[2][r]);
              ph[2][i >> 2][i & 3] = pack_bf16(ex2v(x0), ex2v(x1));
              ph[2][2 + (i >> 2)][i & 3] = pack_bf16(ex2v(mn[2][r] - x0), ex2v(mn[2][r] - x1));
            }
            __syncwarp();
            if (lane == 0) mbar_arrive(BA(B_OH0));
            PROFT(tid_ == 128 && layer, layer * 16 + 15);
            if (QORD) { fm(3); conv(1); } else { conv(1); fm(3); }
          } else {
#pragma unroll
            for (int i = 0; i < 16; ++i) o1[i >> 2][i & 3] = ow[i >> 3][(i >> 2) & 1][i & 3];
          }
        }
      }
      PROFT(tid_ == 128, layer * 16 + 6);
    }
    {
      PHASE_CTX();
      MMA_CTX();
      auto o1st = [&]() {
#pragma unroll
        for (int i = 0; i < 4; ++i) stg128(g_o + gfr + (i & 1) * 8 * D_ + (2 + (i >> 1)) * 32, o1[i][0], o1[i][1], o1[i][2], o1[i][3]);
        __syncwarp();
        if (lane == 0) { mbar_arrive(BA(B_OH1)); if (!O1P) REL2(B_EF); }
        PROFT(lane == 0 && layer == PL, 208 + cw);
      };
      if (O1P) {
        __syncwarp();
        if (lane == 0) REL2(B_EF);
      } else o1st();
      mbar_wait(BA(FW), par);
      mbar_wait(BA(FW + 1), par);
      if (O1P == 1) o1st();
#pragma unroll
      for (int i = 0; i < 2; ++i) {
        wgmma_fence();
#pragma unroll
        for (int k = 0; k < 4; ++k) {
          if (i + k) wgmma_n128_rs(acc, of[4 * i + k], D128(dB0 + (uint32_t)((WO_B >> (4 * i)) & 15) * 1024 + k * 128), 1);
          else wgmma_n128_rs0(acc, of[0], D128(dB0 + (uint32_t)(WO_B & 15) * 1024));
        }
        wgmma_commit();
        if (O1P == 2 && i == 0) o1st();
      }
      wgmma_wait<1>();
      if (elected) REL2(CW);
      uint64_t ta = WO_A >> 8, tw = WO_B >> 8;
      auto run = [&](int i0, int i1) {
#pragma unroll 1
        for (int i = i0; i < i1; ++i) {
          mbar_wait(BA(FW + i), par);
          PROFL(tid_ == 128 && layer == PL, 160 + i);
          const uint32_t da = dA0 + ((uint32_t)ta & 15) * 1024, db = dB0 + ((uint32_t)tw & 15) * 1024;
          ta >>= 4; tw >>= 4;
          wgmma_fence();
#pragma unroll
          for (int k = 0; k < 4; ++k) wgmma_n128(acc, D128(da + k * 2), D128(db + k * 128), 1);
          wgmma_commit();
          wgmma_wait<1>();
          if (elected) REL2(CW + i - 1);
        }
        ta = WO_A >> (4 * (i1 & 15)); tw = WO_B >> (4 * (i1 & 15));
      };
      run(2, XRAT);
#pragma unroll
      for (int j = 0; j < 8 / XRN; ++j) {
#pragma unroll
        for (int i = j * XRN; i < (j + 1) * XRN; ++i) ldg128((layer ? g_x : c.x0) + gfr + (i & 1) * 8 * D_ + (i >> 1) * 32, xp[i][0], xp[i][1], xp[i][2], xp[i][3]);
        run(XRAT + j, j + 1 < 8 / XRN ? XRAT + j + 1 : 16);
      }
      if (layer == 0) {
#pragma unroll
        for (int o = 1; o <= 2; o <<= 1)
#pragma unroll
          for (int i = 0; i < 16; ++i) {
            const int j = o == 1 ? 2 * (i & 1) : (i & 1);
            uint32_t &a = xp[i >> 1][j], &b = xp[i >> 1][j + o];
            const uint32_t r = __shfl_xor_sync(0xffffffffu, (t & o) ? a : b, o);
            if (t & o) a = r; else b = r;
          }
      }
      wgmma_wait<0>();
#pragma unroll
      for (int i = 128; i < 192; ++i) asm volatile("" : "+f"(acc[i]) :: "memory");
      if (elected) REL2(CW + 15);
      PROFT(lane == 0 && layer == PL, 216 + cw);
      PROFT(tid_ == 128, layer * 16 + 7);
    }
    {
      PHASE_CTX();
#pragma unroll
      for (int i = 0; i < 32; ++i)
        xp[i >> 2][i & 3] = add_bf16x2(xp[i >> 2][i & 3], pack_bf16(acc[128 + 16 * (i >> 3) + 4 * (i & 3) + 2 * ((i >> 2) & 1)], acc[129 + 16 * (i >> 3) + 4 * (i & 3) + 2 * ((i >> 2) & 1)]));
      if (layer == NLAYERS - 1) {
#pragma unroll
        for (int i = 0; i < 8; ++i) stsm_x4(sb + (XS + (i >> 2)) * SLOT + (Y ^ ((i & 2) << 5)) + (i & 1) * 1024, xp[i][0], xp[i][1], xp[i][2], xp[i][3]);
        __syncwarp();
        slab_out_half(sb + XS * SLOT, c.out + (size_t)m0 * D_ + g * 128, wrow0, lane);
        slab_out_half(sb + (XS + 1) * SLOT, c.out + (size_t)m0 * D_ + g * 128 + 64, wrow0, lane);
        PROFT(tid_ == 128, layer * 16 + 24);
        break;
      }
#pragma unroll
      for (int i = 0; i < 4; ++i) stg128(g_x + gfr + (i & 1) * 8 * D_ + (i >> 1) * 32, xp[i][0], xp[i][1], xp[i][2], xp[i][3]);
      __syncwarp();
      if (lane == 0) mbar_arrive(BA(B_XH0));
#pragma unroll
      for (int i = 0; i < 16; ++i) xf[i >> 2][i & 3] = xp[2 * (i >> 3) + (i & 1)][(i >> 1) & 3];
      PROFT(tid_ == 128, layer * 16 + 24);
    }
  }
}

__device__ __forceinline__ uint64_t k_order(int o) {
  const uint32_t lo = (1u << (4 * o)) - 1u, h0 = (0xECA86420u & lo) | ((0xECA86420u >> 4) & ~lo);
  return (uint64_t)(2 * o) | ((uint64_t)(2 * o + 1) << 4) | ((uint64_t)(h0 & 0xFFFFFFFu) << 8) | ((uint64_t)((h0 & 0xFFFFFFFu) | 0x1111111u) << 36);
}

__global__ void __cluster_dims__(2, 1, 1) __launch_bounds__(384, 1)
mega_kernel(const __grid_constant__ Maps maps, const __grid_constant__ Ctx c, const bf16* __restrict__ wA, const bf16* __restrict__ wB,
            const bf16* __restrict__ woA, const bf16* __restrict__ woB) {
  if (blockIdx.x - c.boff >= 128u) {
    const unsigned int epoch = ld_relaxed(&g_epoch);
    const int e = (blockIdx.x - c.boff) & 3, tid = threadIdx.x;
    float s[8] = {0.f, 0.f, 0.f, 0.f, 0.f, 0.f, 0.f, 0.f};
    const uint32_t sb = smem_u32(smem_raw), bar = sb + SM_BAR;
    auto issue = [&](int i) {
      mbar_expect_tx(BA(i & 3), 49152);
      bulk_load(sb + (i & 3) * 49152, wB + (size_t)e * 256 * 3072 + i * 24576, 49152, BA(i & 3));
    };
    if (tid == 0) {
#pragma unroll 1
      for (int i = 0; i < 4; ++i) {
        mbar_init(BA(i), 1);
        fence_async_smem();
        issue(i);
      }
    }
    __syncthreads();
#pragma unroll 1
    for (int i = 0; i < 32; ++i) {
      mbar_wait(BA(i & 3), (i >> 2) & 1);
#pragma unroll 2
      for (int r = 0; r < 8; ++r) {
        const uint4 v = lds128(sb + (i & 3) * 49152 + r * 6144 + tid * 16);
        s[0] += bf_lo(v.x); s[1] += bf_hi(v.x); s[2] += bf_lo(v.y); s[3] += bf_hi(v.y);
        s[4] += bf_lo(v.z); s[5] += bf_hi(v.z); s[6] += bf_lo(v.w); s[7] += bf_hi(v.w);
      }
      __syncthreads();
      if (tid == 0 && i < 28) issue(i + 4);
    }
    float* cd = g_cs + (epoch & 1) * 6144 + 3072 + ((tid >> 4) & 7) * 384 + (tid < 128 ? 256 : (tid >> 7) * 128 - 128) + (tid & 15) * 8;
    red_add4(cd, s[0], s[1], s[2], s[3]);
    red_add4(cd + 4, s[4], s[5], s[6], s[7]);
    __syncthreads();
    if (tid == 0) flag_add(&g_csflag[8].v);
    const int op = (epoch & 1) ^ 1;
    float4* kz = reinterpret_cast<float4*>(g_kv + (size_t)op * (2 * 8 * 8448)) + e * 8448;
#pragma unroll 1
    for (int i = tid; i < 8448; i += 384) kz[i] = make_float4(0.f, 0.f, 0.f, 0.f);
    reinterpret_cast<float4*>(g_cs + op * 6144)[e * 384 + tid] = make_float4(0.f, 0.f, 0.f, 0.f);
#pragma unroll 1
    for (int i = tid; i < 1024; i += 384) reinterpret_cast<float4*>(g_stats + (op * 4 + e) * S_)[i] = make_float4(0.f, 0.f, 0.f, 0.f);
    return;
  }
  const int warp = __shfl_sync(0xffffffffu, threadIdx.x >> 5, 0), lane = threadIdx.x & 31;
  if (smem_u32(smem_raw) != SB0 + ((blockIdx.x & 1) << 24)) __trap();
  {
  const int cid = (blockIdx.x - c.boff) >> 1, u7 = ((cid - 36) * 37) >> 8, cr = blockIdx.x & 1;
  const int g = cid < 4 ? 4 + cid : cid < 36 ? (cid - 4) >> 3 : 4 + u7, rb = (cid < 4 ? 0 : cid < 36 ? (cid - 4) & 7 : cid - 35 - 7 * u7) * 2 + cr, m0 = rb * 128;
  const uint32_t sb = SB0 + (cr << 24), bar = sb + SM_BAR;
  PROFT(lane == 0 && (warp == 0 || warp == 4), 224 + (warp >> 2) * 8);
  uint32_t cx = 0;
  if (warp == 2) {
    if (lane < NMAP) asm volatile("prefetch.tensormap [%0];" ::"l"(&maps.m[lane]) : "memory");
    if (lane == 31) asm volatile("prefetch.global.L2 [%0];" ::"l"(&g_epoch));
  } else if (warp == 3) {
    cx = c_map[cid] + c_wop[lane] + c_wop[NWOP - lane] + c_aop[lane] + c_aop[NAOP - lane] + (uint32_t)(uintptr_t)g_x;
  } else if (PFW && warp >= 4) {
    const int i = threadIdx.x - 128;
    asm volatile("prefetch.global.L2 [%0];" ::"l"(wA + (size_t)(rb * 64 + ((i >> 1) & 63)) * 3072 + (i >> 7) * 1024 + g * 128 + (i & 1) * 64));
  }
  if (warp < 2) {
    const int s = warp, kb = (rb & ~1) + s;
    if (lane == 0) {
      mbar_init(BA(FM + s), 1u);
      mbar_init(BA(B_RAW + warp), 1u);
      if (warp) mbar_init(BA(B_X0), 1u);
      asm volatile("fence.mbarrier_init.release.cluster;" ::: "memory");
    }
    __syncwarp();
    if (warp == 0) tma_2d_e(sb + SM_SD, &maps.m[MAP_PHI], 0, g * 128, BA(B_RAW));
    else if (W1DL) __nanosleep(W1DL);
#pragma unroll
    for (int j = 0; j < 6; ++j)
      tma_5d_e(sb + (j < 2 ? 2 * s : j < 4 ? 9 + s : 2 * s + 1) * SLOT + (j & 1) * 8192, &maps.m[MAP_WA], (j < 2 ? 1024 : j < 4 ? 0 : 2048) + g * 128 + (j & 1) * 64, 2 * kb,
               BA(j < 4 ? B_RAW + warp : FM + s));
    tma_2d_e(sb + (XS + s) * SLOT, &maps.m[MAP_X0], kb * 64, m0, BA(FM + s));
    expect_tx_e(BA(B_RAW + warp), warp ? 32768 : 32768 + 8192);
    expect_tx_e(BA(FM + s), 32768);
    if (X0AT == 0 && warp == 1) {
      tma_2d_e(sb + 11 * SLOT, &maps.m[MAP_X0], g * 128, m0, BA(B_X0));
      tma_2d_e(sb + 12 * SLOT, &maps.m[MAP_X0], g * 128 + 64, m0, BA(B_X0));
      expect_tx_e(BA(B_X0), 32768);
    }
  } else if (warp >= 4 && lane == 0) {
#pragma unroll 1
    for (int i = 2 + (warp - 4) * 13; i < 15 + (warp - 4) * 13; ++i)
      mbar_init(BA(i), 1u << ((i < CM ? 0u : i < B_EF ? 2u : (uint32_t)(BAR_LG >> (4 * ((i - B_EF) & 15)))) & 7u));
    asm volatile("fence.mbarrier_init.release.cluster;" ::: "memory");
  }
  __syncwarp();
  asm volatile("barrier.cluster.arrive.relaxed.aligned;" ::: "memory");
  if (threadIdx.x == 96 + c.zero) sts_f(sb + SM_EPOCH + 4, __uint_as_float(cx));
  PROFT(lane == 0 && (warp == 0 || warp == 4), 225 + (warp >> 2) * 8);
  __syncwarp();
  PROFT(lane == 0 && (warp == 0 || warp == 4), 226 + (warp >> 2) * 8);
  }

  if (warp < 4) {
    asm volatile("setmaxnreg.dec.sync.aligned.u32 40;");
    PROFT(threadIdx.x == 0, 227);
    cluster_wait();
    PROFT(threadIdx.x == 0, 228);
    if (warp == 0 || warp == 3) {
    if (warp == 0) {
      BLK_CTX();
      const unsigned int epoch = __shfl_sync(0xffffffffu, ld_relaxed(&g_epoch), 0), xbase = epoch * NLAYERS;
      (void)xbase;
      const uint64_t ordg = k_order(g);
      if (X0AT) {
        mbar_wait_u(BA(B_RAW + X0AT - 1), 0);
        tma_2d_e(sb + 11 * SLOT, &maps.m[MAP_X0], g * 128, m0, BA(B_X0));
        tma_2d_e(sb + 12 * SLOT, &maps.m[MAP_X0], g * 128 + 64, m0, BA(B_X0));
        expect_tx_e(BA(B_X0), 32768);
      }
#pragma unroll 1
      for (int lp = 0; lp < 2 * NLAYERS; ++lp) {
        const int layer = lp >> 1, n1 = (lp & 1) ? NAOP : NAOP - 14;
        int n = (lp & 1) ? NAOP - 14 : 0;
        const uint64_t ord = lp ? ordg : k_order(rb >> 1);
        uint32_t ready = lp ? 0u : 0xFFFFu, nop = c_aop[n];
        const unsigned int* fl = ((lp & 1) ? g_of : g_xf) + rb * 32;
        const CUtensorMap* tm = &maps.m[(lp & 1) ? MAP_O : lp ? MAP_X : MAP_X0];
        const uint32_t skip = layer ? 1u << 25 : 9u << 22;
#pragma unroll 1
        for (; n < n1; ++n) {
          const uint32_t op = nop;
          nop = c_aop[n + 1];
          const uint32_t kb = (uint32_t)(ord >> ((op >> 2) & 60)) & 15;
          uint32_t dst = sb + (op & 15) * SLOT, kc = kb * 64, fb = bar + ((op >> 5) & 0x3F8), need = ~ready & (1u << kb);
          asm volatile("" : "+r"(dst), "+r"(kc), "+r"(fb), "+r"(need));
          if (!(op & skip)) mbar_wait_u(bar + ((op >> 12) & 0x3F8), (layer ^ (op >> 22)) & 1);
          if (need) {
            PROFT(lane == 0 && (n == 0 || n == NAOP - 14), 64 + layer * 16 + (n ? 2 : 0));
            if (FASTP) src_wait_fast(fl, xbase + layer + 1, need, ready, lane);
            else src_wait<0>(fl, xbase + layer + 1, need, ready, lane);
            fence_async_all();
          }
          tma_2d_e(dst, tm, kc, m0, fb);
          PROFT(lane == 0 && (n == 0 || n == NAOP - 14), 64 + layer * 16 + (n ? 3 : 1));
          PROFL(lane == 0 && layer == PL && n >= NAOP - 14, 178 + n - (NAOP - 14));
          PROFL(lane == 0 && layer == PL + 1 && n < 4, 242 + n);
        }
      }
    } else {
      BLK_CTX();
      const unsigned int epoch = __shfl_sync(0xffffffffu, ld_relaxed(&g_epoch), 0), xbase = epoch * NLAYERS;
      (void)xbase;
      const uint64_t ordg = k_order(g);
#pragma unroll 1
      for (int layer = 0; layer < NLAYERS; ++layer) {
        const uint64_t ordq = layer ? ordg : k_order(rb >> 1);
        uint32_t ready = layer ? 0xFFFFu : 0u, nop = c_wop[0];
        const CUtensorMap* tq = &maps.m[(layer & 1) ? MAP_WB : MAP_WF];
        const CUtensorMap* tk = &maps.m[(layer & 1) ? MAP_WB : cr ? MAP_WA : MAP_WF];
        const uint32_t skip = layer ? 1u << 25 : 9u << 22, pm = layer ? 0xE0u : 0u;
        int n = 0;
#pragma unroll 1
        for (; n < NWOP - 16; ++n) {
          const uint32_t op = nop;
          nop = c_wop[n + 1];
          const uint32_t isq = (op >> 23) & 1, fb = bar + ((op >> 5) & 0x3F8);
          const uint32_t kb = (uint32_t)(ordq >> ((op >> 2) & 60)) & 15;
          const CUtensorMap* tm = (isq ? tq : tk) + ((op & pm) ? 1 : 0);
          const uint32_t dst = sb + (op & 15) * SLOT + cr * (isq ? 8192 : SLOT);
          const int col = g * 128 + (isq ? cr * 64 : 1024 + cr * 1024);
          if (layer == 0) {
            if ((op & 0x7E00) == 0) continue;
            const uint32_t need = ((isq || !cr) ? 1u << kb : 0u) | (((op >> 22) & 1) ? 0u : (((op >> 15) & 127) == CM ? 1u : 3u) << (rb & ~1));
            if ((ready & need) != need) {
              src_wait<0>(g_wff + g * 32, epoch + 1, need, ready, lane);
              fence_async_all();
            }
            if ((op & 15) >= 11) mbar_wait_u(BA(B_XT), 0);
          }
          wait_tma_5d_mc(!(op & skip), bar + ((op >> 12) & 0x3F8), (layer ^ (op >> 22)) & 1, dst, tm, col, 2 * kb, fb);
          if (!isq) tma_5d_mc_e(dst + 8192, tm, col + 64, 2 * kb, fb);
          if (op >> 26) expect_tx_e(fb, (op >> 26) * 8192);
          PROFL(lane == 0 && layer == PL + 1 && n < 16, 128 + n);
        }
        const CUtensorMap* to = &maps.m[(layer & 1) ? MAP_WOB : MAP_WOA];
#pragma unroll 1
        for (; n < NWOP; ++n) {
          const uint32_t op = nop;
          nop = c_wop[n + 1];
          const uint32_t fb = bar + ((op >> 5) & 0x3F8), kb = (uint32_t)(ordg >> ((op >> 2) & 60)) & 15;
          wait_tma_5d_mc(!((op >> 25) & 1), bar + ((op >> 12) & 0x3F8), layer & 1, sb + (op & 15) * SLOT + cr * 8192, to + ((op & 0xE0) ? 1 : 0), g * 128 + cr * 64, 2 * kb, fb);
          expect_tx_e(fb, (op >> 26) * 8192);
          PROFL(lane == 0 && layer == PL, 144 + ((op >> 8) & 127) - FW);
        }
      }
    }
    } else if (warp == 1) {
      BLK_CTX();
      const unsigned int epoch = __shfl_sync(0xffffffffu, ld_relaxed(&g_epoch), 0), xbase = epoch * NLAYERS;
      (void)xbase;
      if (lane == 0) {
        mbar_wait(BA(B_WFD), 0);
        PROFT(true, 229);
        if (WFDL && cr) __nanosleep(WFDL);
#pragma unroll 1
        for (int j = 0; j < 4; ++j) tma_store_5d(&maps.m[MAP_WF], sb + (j < 2 ? 2 * cr : 9 + cr) * SLOT + (j & 1) * 8192, (j < 2 ? 1024 : 0) + g * 128 + (j & 1) * 64, 2 * rb);
        bulk_commit();
        bulk_wait0();
        PROFT(true, 230);
        fence_async_all();
        flag_set(g_wff + g * 32 + rb, epoch + 1);
        PROFT(true, 64 + 13);
#pragma unroll 1
        for (int e = 0; e < NLAYERS; ++e) {
          BLK_CTX();
          if (e > 0) {
            mbar_wait(BA(B_XH0), (e - 1) & 1);
            PROFT(e == PL + 1, 240);
            flag_set(g_xf + rb * 32 + 2 * g, xbase + e + 1);
            PROFT(e == PL + 1, 241);
          }
          mbar_wait(BA(B_XDONE), e & 1);
          PROFT(true, 64 + e * 16 + 4);
          flag_set(g_xf + rb * 32 + 2 * g + 1, xbase + e + 1);
          if (e == 0) {
            flag_add(&g_csflag[g].v);
            l2_prefetch(wB + (size_t)bid_ * 24576, 49152);
            l2_prefetch(woA + (size_t)bid_ * 8192, 16384);
            l2_prefetch(woB + (size_t)bid_ * 8192, 16384);
          }
          PROFT(true, 64 + e * 16 + 7);
          if ((e & 1) == 0) {
            float* kvl = g_kv + ((size_t)((epoch & 1) * 2 + (e >> 1)) * 8 + g) * 8448;
#pragma unroll 1
            for (int hp = 0; hp < 2; ++hp) {
              mbar_wait(BA(B_KVDONE), hp);
              bulk_red_add(kvl + 8192 + hp * 128, sb + SM_AP + hp * 512, 512);
#pragma unroll 1
              for (int i = 0; i < NCH; ++i) {
                const int ch = hp * NCH + ((i + rb * NCH / 16) & (NCH - 1));
                bulk_red_add(kvl + ch * (4096 / NCH), sb + VB + ch * (16384 / NCH), 16384 / NCH);
                bulk_commit();
                asm volatile("cp.async.bulk.wait_group %0;" :: "n"(CHW) : "memory");
              }
              bulk_wait0();
              PROFT(true, 64 + e * 16 + (hp ? 10 : 6));
              fence_async_all();
              flag_add(&g_kvflag[hp * 8 + g].v);
              PROFT(e > 0 && hp, 64 + e * 16 + 8);
            }
          }
          if (e & 1) {
            mbar_wait(BA(B_OF0), (e >> 1) & 1);
            flag_set(g_hf + rb * 32 + g, xbase + e + 1);
            if (rb) flag_wait(g_hf + (rb - 1) * 32 + g, xbase + e + 1);
            fence_async_all();
            mbar_expect_tx(BA(B_HALO), 8192);
            bulk_load(sb + SM_SD, g_halo + (size_t)(((e >> 1) * 17 + rb) * 8 + g) * 2048, 8192, BA(B_HALO));
            PROFT(true, 64 + e * 16 + 15);
          }
          mbar_wait(BA(B_OH0), e & 1);
          PROFT(e > 0, 64 + e * 16 + 13);
          flag_set(g_of + rb * 32 + 2 * g, xbase + e + 1);
          PROFT(true, 64 + e * 16 + 9);
          mbar_wait(BA(B_OH1), e & 1);
          PROFT(true, 64 + e * 16 + 5);
          flag_set(g_of + rb * 32 + 2 * g + 1, xbase + e + 1);
          PROFT(true, 64 + e * 16 + 11);
        }
        if (bid_ == 0) g_epoch = epoch + 1;
      }
    } else {
      BLK_CTX();
      const unsigned int epoch = __shfl_sync(0xffffffffu, ld_relaxed(&g_epoch), 0), xbase = epoch * NLAYERS;
      (void)xbase;
      if (lane < 16) sts_f(sb + SM_RS + lane * 4, 0.f);
#pragma unroll 1
      for (int layer = 0; layer < NLAYERS; ++layer) {
#define HLP_CTX() BLK_CTX(); int lane = threadIdx.x & 31; asm volatile("" : "+r"(lane)); const bool isB = layer & 1, hal = isB && rb > 0; (void)hal;
#pragma unroll 1
        for (int ph = 0; ph < 2; ++ph) {
          HLP_CTX();
          if (ph == (layer == 0)) {
            const float* cs = g_cs + (epoch & 1) * 6144 + g * 384;
            if (layer) mbar_wait_u(BA(CT), (layer - 1) & 1);
            if (layer < 2) {
              if (lane == 0) flag_wait_slow(&g_csflag[isB ? 8 : g].v, isB ? epoch * 4u + 4u : epoch * 16u + 16u);
              __syncwarp();
            }
#pragma unroll 1
            for (int i0 = 0; i0 < 12; i0 += 4) {
              float a[4];
#pragma unroll
              for (int i = 0; i < 4; ++i) a[i] = __ldcg(cs + isB * 3072 + (i0 + i) * 32 + lane);
#pragma unroll
              for (int i = 0; i < 4; ++i) {
                const float c1 = bf16r(a[i]), c2 = bf16r(a[i] - c1), c3 = (a[i] - c1) - c2;
                sts128(sb + SM_BP + ((i0 + i) * 32 + lane) * 16, make_uint4(pack_bf16(c1, c2), pack_bf16(c3, 0.f), 0u, 0u));
              }
            }
          } else {
            uint32_t rdy = 0u;
            src_wait<128>(g_xf + rb * 32, xbase + layer + 1, 0xAAAAu, rdy, lane);
            rdy = 0u;
            if (hal) src_wait<128>(g_xf + (rb - 1) * 32, xbase + layer + 1, 0xAAAAu, rdy, lane);
            const float2* sp = g_stats + ((epoch & 1) * 4 + layer) * S_ + m0 + lane;
            float2 u[5];
#pragma unroll
            for (int i = 0; i < 4; ++i) u[i] = __ldcg(sp + i * 32);
            u[4] = __ldcg(sp - (hal ? 16 : 0));
#pragma unroll 1
            for (int i = 0; i < 5; ++i) {
              const float mean = u[0].x * (1.f / D_);
              const float var = fmaxf(fmaf(-u[0].x, mean, u[0].y) * (1.f / D_), 0.f);
              const float sd = bf16r(sqrtf(bf16r(bf16r(var) + 1e-5f)));
              const int R = i * 32 + lane;
              if (i < 4) {
                const float hm = -0.5f * bf16r(mean);
                if (!isB) sts128(sb + SM_SD + R * 64 + ((R >> 1) & 3) * 16, make_uint4(__float_as_uint(sd) >> 16, 0u, 0u, 0u));
                sts128(sb + SM_AP + R * 16, make_uint4(pack_bf16(hm, hm), pack_bf16(hm, 0.f), 0u, 0u));
              }
              if (i < 4 || (hal && lane < 16)) sts_f(sb + SM_RS + (i < 4 ? 16 + R : lane) * 4, __fdividef(1.f, sd));
#pragma unroll
              for (int j = 0; j < 4; ++j) u[j] = u[j + 1];
            }
            PROFT(lane == 0, 64 + layer * 16 + 12);
          }
        }
        HLP_CTX();
        fence_async_smem();
        __syncwarp();
        if (lane == 0) mbar_arrive(BA(B_STAT));
        PROFT(lane == 0, 64 + layer * 16 + 14);
        if (!isB && lane == 0) {
#pragma unroll 1
          for (int hp = 0; hp < 2; ++hp) {
            mbar_wait(BA(B_KVDONE), hp);
            flag_wait(&g_kvflag[hp * 8 + g].v, epoch * (16u * ((NLAYERS + 1) / 2)) + 16u * ((layer >> 1) + 1));
            const float* kvl = g_kv + ((size_t)((epoch & 1) * 2 + (layer >> 1)) * 8 + g) * 8448;
            const uint32_t kb = BA(hp ? B_KVF1 : B_KVF);
            fence_async_all();
            mbar_expect_tx(kb, 16384 + 512);
            bulk_load(sb + VB + hp * SLOT, kvl + hp * 4096, 16384, kb);
            bulk_load(sb + SM_AP + hp * 512, kvl + 8192 + hp * 128, 512, kb);
            PROFT(hp == 0, 64 + layer * 16 + 15);
          }
        }
        __syncwarp();
      }
    }
    __syncwarp();
    asm volatile("barrier.cluster.arrive.relaxed.aligned;" ::: "memory");
    cluster_wait();
  } else {
    asm volatile("setmaxnreg.inc.sync.aligned.u32 232;");
    PROFT(threadIdx.x == 128, 235);
    cluster_wait();
    PROFT(threadIdx.x == 128, 236);
    consumer(c);
    asm volatile("bar.warp.sync 0xffffffff;\nbarrier.cluster.arrive.relaxed.aligned;\nbarrier.cluster.wait.aligned;\n" ::: "memory");
  }
}

typedef CUresult (*PFN_encodeTiled)(CUtensorMap*, CUtensorMapDataType, cuuint32_t, void*, const cuuint64_t*, const cuuint64_t*,
                                    const cuuint32_t*, const cuuint32_t*, CUtensorMapInterleave, CUtensorMapSwizzle,
                                    CUtensorMapL2promotion, CUtensorMapFloatOOBfill);

static void make_map2(PFN_encodeTiled enc, CUtensorMap* m, const void* ptr, uint64_t cols, uint64_t rows, uint32_t box_c, uint32_t box_r) {
  cuuint64_t dims[2] = {cols, rows};
  cuuint64_t strides[1] = {cols * 2};
  cuuint32_t box[2] = {box_c, box_r};
  cuuint32_t es[2] = {1, 1};
  CUresult r = enc(m, CU_TENSOR_MAP_DATA_TYPE_BFLOAT16, 2, const_cast<void*>(ptr), dims, strides, box, es, CU_TENSOR_MAP_INTERLEAVE_NONE,
                   box_c == 64 ? CU_TENSOR_MAP_SWIZZLE_128B : CU_TENSOR_MAP_SWIZZLE_64B, CU_TENSOR_MAP_L2_PROMOTION_L2_256B, CU_TENSOR_MAP_FLOAT_OOB_FILL_NONE);
  (void)r;
}
static void make_map5(PFN_encodeTiled enc, CUtensorMap* m, const void* ptr, uint64_t cols) {
  for (int p = 0; p < 2; ++p) {
    cuuint64_t dims[5] = {cols, 2, 4, 4, 32};
    cuuint64_t strides[4] = {cols * 2, cols * (p ? 16 : 4), cols * (p ? 4 : 16), cols * 64};
    cuuint32_t box[5] = {64, 2, 4, 4, 2};
    cuuint32_t es[5] = {1, 1, 1, 1, 1};
    CUresult r = enc(m + p, CU_TENSOR_MAP_DATA_TYPE_BFLOAT16, 5, const_cast<void*>(ptr), dims, strides, box, es, CU_TENSOR_MAP_INTERLEAVE_NONE,
                     CU_TENSOR_MAP_SWIZZLE_128B, CU_TENSOR_MAP_L2_PROMOTION_L2_256B, CU_TENSOR_MAP_FLOAT_OOB_FILL_NONE);
    (void)r;
  }
}

extern "C" void kernel_launch(void* const* d_in, const int* in_sizes, int n_in, void* d_out, int out_size) {
  const bf16* A_x = (const bf16*)d_in[0];
  const bf16* A_wqkv = (const bf16*)d_in[1];
  const bf16* A_wphi = (const bf16*)d_in[2];
  const bf16* A_wo = (const bf16*)d_in[3];
  const bf16* B_wqkv = (const bf16*)d_in[5];
  const bf16* B_wo = (const bf16*)d_in[6];
  bf16* out = (bf16*)d_out;

  static PFN_encodeTiled enc = nullptr;
  static bf16 *p_x, *p_o, *p_wf;
  static uint32_t boff;
  if (!enc) {
    void* fn = nullptr; cudaDriverEntryPointQueryResult qr;
    cudaGetDriverEntryPoint("cuTensorMapEncodeTiled", &fn, cudaEnableDefault, &qr);
    enc = (PFN_encodeTiled)fn;
    cudaGetSymbolAddress((void**)&p_x, g_x);
    cudaGetSymbolAddress((void**)&p_o, g_o);
    cudaGetSymbolAddress((void**)&p_wf, g_wf);
    cudaFuncSetAttribute(mega_kernel, cudaFuncAttributeMaxDynamicSharedMemorySize, SM_TOTAL);
    cudaLaunchConfig_t cfg = {};
    cudaLaunchAttribute at; at.id = cudaLaunchAttributeClusterDimension; at.val.clusterDim.x = 2; at.val.clusterDim.y = 1; at.val.clusterDim.z = 1;
    cfg.gridDim = dim3(132); cfg.blockDim = dim3(384); cfg.dynamicSmemBytes = SM_TOTAL; cfg.attrs = &at; cfg.numAttrs = 1;
    int nc = 0;
    if (cudaOccupancyMaxActiveClusters(&nc, mega_kernel, &cfg) != cudaSuccess) { nc = 0; (void)cudaGetLastError(); }
    boff = nc >= 66 ? 0u : 4u;
  }
  Maps maps;
  make_map5(enc, &maps.m[MAP_WF], p_wf, 2048);
  make_map5(enc, &maps.m[MAP_WA], A_wqkv, 3072);
  make_map5(enc, &maps.m[MAP_WB], B_wqkv, 3072);
  make_map5(enc, &maps.m[MAP_WOA], A_wo, 1024);
  make_map5(enc, &maps.m[MAP_WOB], B_wo, 1024);
  make_map2(enc, &maps.m[MAP_X0], A_x, 1024, 2048, 64, 128);
  make_map2(enc, &maps.m[MAP_X], p_x, 1024, 2048, 64, 128);
  make_map2(enc, &maps.m[MAP_O], p_o, 1024, 2048, 64, 128);
  make_map2(enc, &maps.m[MAP_PHI], A_wphi, 32, 1024, 32, 128);
  Ctx c; c.zero = 0u; c.boff = boff; c.x0 = A_x; c.out = out;
  mega_kernel<<<132, 384, SM_TOTAL, cudaStreamPerThread>>>(maps, c, A_wqkv, B_wqkv, A_wo, B_wo);
}
```

```cpp
#include <cuda_runtime.h>
#include <cuda_bf16.h>
#include <cuda.h>
#include <stdint.h>

typedef __nv_bfloat16 bf16;

constexpr int S_ = 2048, D_ = 1024;

struct __align__(128) Flag { unsigned int v; unsigned int pad[31]; };
__device__ __align__(1024) bf16 g_x[S_ * D_];
__device__ __align__(1024) bf16 g_o[S_ * D_];
__device__ __align__(1024) uint32_t g_halo[2 * 17 * 8 * 2048];
__device__ __align__(1024) float g_kv[2 * 2 * 8 * 8448];
__device__ __align__(1024) float2 g_stats[2 * 4 * S_];
__device__ __align__(1024) float g_cs[2 * 2 * 3072];
__device__ __align__(1024) bf16 g_wf[D_ * 2048];
__device__ Flag g_kvflag[16], g_csflag[13];
__device__ __align__(128) unsigned int g_xf[16 * 32], g_of[16 * 32];
__device__ __align__(128) unsigned int g_hf[16 * 32];
__device__ __align__(128) unsigned int g_wff[8 * 32];
__device__ unsigned int g_epoch, g_err;
#define PROFT(cond, idx) asm volatile("" ::: "memory")

__device__ __forceinline__ uint32_t smem_u32(const void* p) { return (uint32_t)__cvta_generic_to_shared(p); }
__device__ __forceinline__ void mbar_init(uint32_t bar, uint32_t count) {
  asm volatile("mbarrier.init.shared::cta.b64 [%0], %1;" ::"r"(bar), "r"(count) : "memory");
}
__device__ __forceinline__ void mbar_expect_tx(uint32_t bar, uint32_t bytes) {
  asm volatile("mbarrier.arrive.expect_tx.shared::cta.b64 _, [%0], %1;" ::"r"(bar), "r"(bytes) : "memory");
}
__device__ __forceinline__ void mbar_arrive(uint32_t bar) {
  asm volatile("mbarrier.arrive.shared::cta.b64 _, [%0];" ::"r"(bar) : "memory");
}
__device__ __forceinline__ bool mbar_try_wait(uint32_t bar, uint32_t parity) {
  uint32_t ok;
  asm volatile("{\n.reg .pred p;\nmbarrier.try_wait.parity.shared::cta.b64 p, [%1], %2;\nselp.b32 %0, 1, 0, p;\n}\n"
               : "=r"(ok) : "r"(bar), "r"(parity) : "memory");
  return ok != 0;
}
__device__ __forceinline__ uint64_t gtimer() {
  uint64_t t; asm volatile("mov.u64 %0, %globaltimer;" : "=l"(t)); return t;
}
__device__ __forceinline__ void mbar_wait(uint32_t bar, uint32_t parity) {
  uint32_t n = 0;
  bool ok;
#pragma unroll 1
  do { ++n; ok = mbar_try_wait(bar, parity); } while (!ok && n < (1u << 22));
}
__device__ __forceinline__ unsigned int ld_acquire(const unsigned int* p) {
  unsigned int v; asm volatile("ld.acquire.gpu.global.u32 %0, [%1];" : "=r"(v) : "l"(p) : "memory"); return v;
}
__device__ __forceinline__ void flag_add(unsigned int* p) {
  asm volatile("red.release.gpu.global.add.u32 [%0], 1;" ::"l"(p) : "memory");
}
__device__ __forceinline__ void flag_set(unsigned int* p, unsigned int v) {
  asm volatile("st.release.gpu.global.u32 [%0], %1;" ::"l"(p), "r"(v) : "memory");
}
template <int SLEEP>
__device__ __forceinline__ void src_wait(const unsigned int* f, unsigned int target, uint32_t need, uint32_t& ready, int lane) {
  uint32_t n = 0;
#pragma unroll 1
  while ((ready & need) != need) {
    const unsigned int v = ld_acquire(f + (lane & 15));
    ready = __ballot_sync(0xffffffffu, (int)(v - target) >= 0);
    if (SLEEP) { if ((ready & need) != need) __nanosleep(SLEEP); }
    if (++n > (1u << 20)) break;
  }
  __syncwarp();
}
__device__ __forceinline__ unsigned int ld_relaxed(const unsigned int* p);
__device__ __forceinline__ unsigned int ld_relaxed(const unsigned int* p) {
  unsigned int v; asm volatile("ld.relaxed.gpu.global.u32 %0, [%1];" : "=r"(v) : "l"(p) : "memory"); return v;
}
template <int SLEEP>
__device__ __forceinline__ void flag_wait_t(const unsigned int* p, unsigned int target) {
  uint32_t n = 0;
#pragma unroll 1
  while ((int)(ld_acquire(p) - target) < 0) {
    if (SLEEP) __nanosleep(SLEEP);
    if (++n > (1u << 20)) break;
  }
}
__device__ __forceinline__ void flag_wait(const unsigned int* p, unsigned int target) { flag_wait_t<0>(p, target); }
__device__ __forceinline__ void flag_wait_slow(const unsigned int* p, unsigned int target) { flag_wait_t<256>(p, target); }
__device__ __forceinline__ void mbar_wait_u(uint32_t bar, uint32_t parity) {
  uint32_t n = 0;
#pragma unroll 1
  while (!__all_sync(0xffffffffu, mbar_try_wait(bar, parity))) {
    if (++n > (1u << 22)) break;
  }
}
__device__ __forceinline__ void expect_tx_e(uint32_t bar, uint32_t bytes) {
  asm volatile("{\n.reg .pred p;\nelect.sync _|p, 0xffffffff;\n@p mbarrier.arrive.expect_tx.shared::cta.b64 _, [%0], %1;\n}\n" ::"r"(bar), "r"(bytes) : "memory");
}
__device__ __forceinline__ void tma_2d_e(uint32_t dst, const CUtensorMap* tm, int c0, int c1, uint32_t bar) {
  asm volatile("{\n.reg .pred p;\nelect.sync _|p, 0xffffffff;\n"
               "@p cp.async.bulk.tensor.2d.shared::cluster.global.mbarrier::complete_tx::bytes [%0], [%1, {%2, %3}], [%4];\n}\n"
               ::"r"(dst), "l"(tm), "r"(c0), "r"(c1), "r"(bar) : "memory");
}
__device__ __forceinline__ void tma_5d_e(uint32_t dst, const CUtensorMap* tm, int c0, int c4, uint32_t bar) {
  asm volatile("{\n.reg .pred p;\nelect.sync _|p, 0xffffffff;\n"
               "@p cp.async.bulk.tensor.5d.shared::cluster.global.mbarrier::complete_tx::bytes [%0], [%1, {%2, %5, %5, %5, %3}], [%4];\n}\n"
               ::"r"(dst), "l"(tm), "r"(c0), "r"(c4), "r"(bar), "r"(0) : "memory");
}
__device__ __forceinline__ void tma_5d_mc_e(uint32_t dst, const CUtensorMap* tm, int c0, int c4, uint32_t bar) {
  asm volatile("{\n.reg .pred p;\nelect.sync _|p, 0xffffffff;\n"
               "@p cp.async.bulk.tensor.5d.shared::cluster.global.mbarrier::complete_tx::bytes.multicast::cluster [%0], [%1, {%2, %6, %6, %6, %3}], [%4], %5;\n}\n"
               ::"r"(dst), "l"(tm), "r"(c0), "r"(c4), "r"(bar), "h"((uint16_t)3), "r"(0) : "memory");
}
__device__ __forceinline__ void wait_tma_5d_mc(bool w, uint32_t eb, uint32_t par, uint32_t dst, const CUtensorMap* tm, int c0, int c4, uint32_t fb) {
  asm volatile("" : "+r"(dst), "+l"(tm), "+r"(c0), "+r"(c4), "+r"(fb));
  if (w) mbar_wait_u(eb, par);
  tma_5d_mc_e(dst, tm, c0, c4, fb);
}
__device__ __forceinline__ void stg128(void* p, uint32_t a, uint32_t b, uint32_t c, uint32_t d) {
  asm volatile("st.global.v4.u32 [%0], {%1,%2,%3,%4};" ::"l"(p), "r"(a), "r"(b), "r"(c), "r"(d) : "memory");
}
__device__ __forceinline__ void stg128_p(bool on, void* p, uint32_t a, uint32_t b, uint32_t c, uint32_t d) {
  asm volatile("{\n.reg .pred p;\nsetp.ne.b32 p, %5, 0;\n@p st.global.v4.u32 [%0], {%1,%2,%3,%4};\n}\n" ::"l"(p), "r"(a), "r"(b), "r"(c), "r"(d), "r"((int)on) : "memory");
}
__device__ __forceinline__ void ldg128(const void* p, uint32_t& a, uint32_t& b, uint32_t& c, uint32_t& d) {
  asm volatile("ld.global.cg.v4.u32 {%0,%1,%2,%3}, [%4];" : "=r"(a), "=r"(b), "=r"(c), "=r"(d) : "l"(p) : "memory");
}
__device__ __forceinline__ void release2c(uint32_t off) {
  asm volatile("mbarrier.arrive.shared::cluster.b64 _, [%0];\nmbarrier.arrive.shared::cluster.b64 _, [%1];" ::"r"(off), "r"(off + (1u << 24)) : "memory");
}
__device__ __forceinline__ void tma_store_5d(const CUtensorMap* tm, uint32_t src, int c0, int c4) {
  asm volatile("cp.async.bulk.tensor.5d.global.shared::cta.bulk_group [%0, {%2, %4, %4, %4, %3}], [%1];"
               ::"l"(tm), "r"(src), "r"(c0), "r"(c4), "r"(0) : "memory");
}
__device__ __forceinline__ void bulk_load(uint32_t dst, const void* src, uint32_t bytes, uint32_t bar) {
  asm volatile("cp.async.bulk.shared::cluster.global.mbarrier::complete_tx::bytes [%0], [%1], %2, [%3];" ::"r"(dst), "l"(src), "r"(bytes), "r"(bar) : "memory");
}
__device__ __forceinline__ void bulk_red_add(void* dst, uint32_t src, uint32_t bytes) {
  asm volatile("cp.reduce.async.bulk.global.shared::cta.bulk_group.add.f32 [%0], [%1], %2;" ::"l"(dst), "r"(src), "r"(bytes) : "memory");
}
__device__ __forceinline__ void bulk_commit() { asm volatile("cp.async.bulk.commit_group;" ::: "memory"); }
__device__ __forceinline__ void bulk_wait0() { asm volatile("cp.async.bulk.wait_group 0;" ::: "memory"); }
__device__ __forceinline__ void fence_async_smem() { asm volatile("fence.proxy.async.shared::cta;" ::: "memory"); }
__device__ __forceinline__ void fence_async_all() { asm volatile("fence.proxy.async.global;" ::: "memory"); }
__device__ __forceinline__ void wgmma_fence() { asm volatile("wgmma.fence.sync.aligned;" ::: "memory"); }
__device__ __forceinline__ void wgmma_commit() { asm volatile("wgmma.commit_group.sync.aligned;" ::: "memory"); }
template <int N> __device__ __forceinline__ void wgmma_wait() { asm volatile("wgmma.wait_group.sync.aligned %0;" ::"n"(N) : "memory"); }
__device__ __forceinline__ void cluster_wait() { asm volatile("barrier.cluster.wait.acquire.aligned;" ::: "memory"); }
template <int ID, int N> __device__ __forceinline__ void nbar() { asm volatile("bar.sync %0, %1;" ::"n"(ID), "n"(N) : "memory"); }
__device__ __forceinline__ uint64_t desc64(uint32_t lo, uint32_t hi) { return (uint64_t)lo | ((uint64_t)hi << 32); }
__device__ __forceinline__ uint32_t pack_bf16(float lo, float hi) {
  uint32_t r; asm("cvt.rn.bf16x2.f32 %0, %1, %2;" : "=r"(r) : "f"(hi), "f"(lo)); return r;
}
__device__ __forceinline__ uint32_t add_bf16x2(uint32_t a, uint32_t b) {
  uint32_t r; asm("add.rn.bf16x2 %0, %1, %2;" : "=r"(r) : "r"(a), "r"(b)); return r;
}
__device__ __forceinline__ float bf16r(float x) { return __bfloat162float(__float2bfloat16_rn(x)); }
__device__ __forceinline__ float bf_lo(uint32_t u) { return __uint_as_float(u << 16); }
__device__ __forceinline__ float bf_hi(uint32_t u) { return __uint_as_float(u & 0xFFFF0000u); }
__device__ __forceinline__ float ex2(float x) { float r; asm("ex2.approx.ftz.f32 %0, %1;" : "=f"(r) : "f"(x)); return r; }
__device__ __forceinline__ float ex2v(float x) { float r; asm volatile("ex2.approx.ftz.f32 %0, %1;" : "=f"(r) : "f"(x) : "memory"); return r; }
__device__ __forceinline__ float rcp(float x) { float r; asm("rcp.approx.ftz.f32 %0, %1;" : "=f"(r) : "f"(x)); return r; }
__device__ __forceinline__ void mma_bf16(float (&d)[4], uint32_t a0, uint32_t a1, uint32_t a2, uint32_t a3, uint32_t b0, uint32_t b1) {
  asm("mma.sync.aligned.m16n8k16.row.col.f32.bf16.bf16.f32 {%0,%1,%2,%3}, {%4,%5,%6,%7}, {%8,%9}, {%0,%1,%2,%3};"
               : "+f"(d[0]), "+f"(d[1]), "+f"(d[2]), "+f"(d[3]) : "r"(a0), "r"(a1), "r"(a2), "r"(a3), "r"(b0), "r"(b1));
}
__device__ __forceinline__ void ldsm_x4(uint32_t& r0, uint32_t& r1, uint32_t& r2, uint32_t& r3, uint32_t addr) {
  asm volatile("ldmatrix.sync.aligned.m8n8.x4.shared.b16 {%0,%1,%2,%3}, [%4];"
               : "=r"(r0), "=r"(r1), "=r"(r2), "=r"(r3) : "r"(addr) : "memory");
}
__device__ __forceinline__ void ldsm_x4_t(uint32_t& r0, uint32_t& r1, uint32_t& r2, uint32_t& r3, uint32_t addr) {
  asm volatile("ldmatrix.sync.aligned.m8n8.x4.trans.shared.b16 {%0,%1,%2,%3}, [%4];"
               : "=r"(r0), "=r"(r1), "=r"(r2), "=r"(r3) : "r"(addr) : "memory");
}
__device__ __forceinline__ void stsm_x4(uint32_t addr, uint32_t r0, uint32_t r1, uint32_t r2, uint32_t r3) {
  asm volatile("stmatrix.sync.aligned.m8n8.x4.shared.b16 [%0], {%1,%2,%3,%4};"
               ::"r"(addr), "r"(r0), "r"(r1), "r"(r2), "r"(r3) : "memory");
}
__device__ __forceinline__ uint4 lds128(uint32_t addr) {
  uint4 v; asm volatile("ld.shared.v4.b32 {%0,%1,%2,%3}, [%4];" : "=r"(v.x), "=r"(v.y), "=r"(v.z), "=r"(v.w) : "r"(addr) : "memory"); return v;
}
__device__ __forceinline__ void sts128(uint32_t addr, uint4 v) {
  asm volatile("st.shared.v4.b32 [%0], {%1,%2,%3,%4};" ::"r"(addr), "r"(v.x), "r"(v.y), "r"(v.z), "r"(v.w) : "memory");
}
__device__ __forceinline__ float lds_f(uint32_t addr) {
  float v; asm volatile("ld.shared.f32 %0, [%1];" : "=f"(v) : "r"(addr) : "memory"); return v;
}
__device__ __forceinline__ void nbar_dyn(int id, int n) { asm volatile("bar.sync %0, %1;" ::"r"(id), "r"(n) : "memory"); }
__device__ __forceinline__ uint64_t make_desc_ns(uint32_t addr, uint32_t lbo_bytes, uint32_t sbo_bytes) {
  return (uint64_t)((addr & 0x3FFFF) >> 4) | ((uint64_t)(lbo_bytes >> 4) << 16) | ((uint64_t)(sbo_bytes >> 4) << 32);
}
__device__ __forceinline__ void sts_f(uint32_t addr, float v) { asm volatile("st.shared.f32 [%0], %1;" ::"r"(addr), "f"(v) : "memory"); }
__device__ __forceinline__ void sts64(uint32_t addr, uint32_t a, uint32_t b) {
  asm volatile("st.shared.v2.b32 [%0], {%1,%2};" ::"r"(addr), "r"(a), "r"(b) : "memory");
}
__device__ __forceinline__ void sts_f2(uint32_t addr, float a, float b) {
  asm volatile("st.shared.v2.f32 [%0], {%1,%2};" ::"r"(addr), "f"(a), "f"(b) : "memory");
}
__device__ __forceinline__ void red_add2_p(bool on, float* p, float a, float b) {
  asm volatile("{\n.reg .pred p;\nsetp.ne.b32 p, %3, 0;\n@p red.global.add.v2.f32 [%0], {%1,%2};\n}\n" ::"l"(p), "f"(a), "f"(b), "r"((int)on) : "memory");
}
__device__ __forceinline__ void red_add4(float* p, float a, float b, float c, float d) {
  asm volatile("red.global.add.v4.f32 [%0], {%1,%2,%3,%4};" ::"l"(p), "f"(a), "f"(b), "f"(c), "f"(d) : "memory");
}
__device__ __forceinline__ void red_add1(float* p, float a) {
  asm volatile("red.global.add.f32 [%0], %1;" ::"l"(p), "f"(a) : "memory");
}
__device__ __forceinline__ void l2_prefetch(const void* p, uint32_t bytes) {
  asm volatile("cp.async.bulk.prefetch.L2.global [%0], %1;" ::"l"(p), "r"(bytes) : "memory");
}

__device__ __forceinline__ void wgmma_n256(float (&d)[192], uint64_t da, uint64_t db, int scale_d) {
  asm volatile("{\n.reg .pred p;\nsetp.ne.b32 p, %130, 0;\n"
    "wgmma.mma_async.sync.aligned.m64n256k16.f32.bf16.bf16 {%0, %1, %2, %3, %4, %5, %6, %7, %8, %9, %10, %11, %12, %13, %14, %15, %16, %17, %18, %19, %20, %21, %22, %23, %24, %25, %26, %27, %28, %29, %30, %31, %32, %33, %34, %35, %36, %37, %38, %39, %40, %41, %42, %43, %44, %45, %46, %47, %48, %49, %50, %51, %52, %53, %54, %55, %56, %57, %58, %59, %60, %61, %62, %63, %64, %65, %66, %67, %68, %69, %70, %71, %72, %73, %74, %75, %76, %77, %78, %79, %80, %81, %82, %83, %84, %85, %86, %87, %88, %89, %90, %91, %92, %93, %94, %95, %96, %97, %98, %99, %100, %101, %102, %103, %104, %105, %106, %107, %108, %109, %110, %111, %112, %113, %114, %115, %116, %117, %118, %119, %120, %121, %122, %123, %124, %125, %126, %127}, %128, %129, p, 1, 1, 0, 1;\n}\n"
    : "+f"(d[0]), "+f"(d[1]), "+f"(d[2]), "+f"(d[3]), "+f"(d[4]), "+f"(d[5]), "+f"(d[6]), "+f"(d[7]), "+f"(d[8]), "+f"(d[9]), "+f"(d[10]), "+f"(d[11]), "+f"(d[12]), "+f"(d[13]), "+f"(d[14]), "+f"(d[15]), "+f"(d[16]), "+f"(d[17]), "+f"(d[18]), "+f"(d[19]), "+f"(d[20]), "+f"(d[21]), "+f"(d[22]), "+f"(d[23]), "+f"(d[24]), "+f"(d[25]), "+f"(d[26]), "+f"(d[27]), "+f"(d[28]), "+f"(d[29]), "+f"(d[30]), "+f"(d[31]), "+f"(d[32]), "+f"(d[33]), "+f"(d[34]), "+f"(d[35]), "+f"(d[36]), "+f"(d[37]), "+f"(d[38]), "+f"(d[39]), "+f"(d[40]), "+f"(d[41]), "+f"(d[42]), "+f"(d[43]), "+f"(d[44]), "+f"(d[45]), "+f"(d[46]), "+f"(d[47]), "+f"(d[48]), "+f"(d[49]), "+f"(d[50]), "+f"(d[51]), "+f"(d[52]), "+f"(d[53]), "+f"(d[54]), "+f"(d[55]), "+f"(d[56]), "+f"(d[57]), "+f"(d[58]), "+f"(d[59]), "+f"(d[60]), "+f"(d[61]), "+f"(d[62]), "+f"(d[63]), "+f"(d[64]), "+f"(d[65]), "+f"(d[66]), "+f"(d[67]), "+f"(d[68]), "+f"(d[69]), "+f"(d[70]), "+f"(d[71]), "+f"(d[72]), "+f"(d[73]), "+f"(d[74]), "+f"(d[75]), "+f"(d[76]), "+f"(d[77]), "+f"(d[78]), "+f"(d[79]), "+f"(d[80]), "+f"(d[81]), "+f"(d[82]), "+f"(d[83]), "+f"(d[84]), "+f"(d[85]), "+f"(d[86]), "+f"(d[87]), "+f"(d[88]), "+f"(d[89]), "+f"(d[90]), "+f"(d[91]), "+f"(d[92]), "+f"(d[93]), "+f"(d[94]), "+f"(d[95]), "+f"(d[96]), "+f"(d[97]), "+f"(d[98]), "+f"(d[99]), "+f"(d[100]), "+f"(d[101]), "+f"(d[102]), "+f"(d[103]), "+f"(d[104]), "+f"(d[105]), "+f"(d[106]), "+f"(d[107]), "+f"(d[108]), "+f"(d[109]), "+f"(d[110]), "+f"(d[111]), "+f"(d[112]), "+f"(d[113]), "+f"(d[114]), "+f"(d[115]), "+f"(d[116]), "+f"(d[117]), "+f"(d[118]), "+f"(d[119]), "+f"(d[120]), "+f"(d[121]), "+f"(d[122]), "+f"(d[123]), "+f"(d[124]), "+f"(d[125]), "+f"(d[126]), "+f"(d[127])
    : "l"(da), "l"(db), "r"(scale_d));
}
__device__ __forceinline__ void wgmma_n128(float (&d)[192], uint64_t da, uint64_t db, int scale_d) {
  asm volatile("{\n.reg .pred p;\nsetp.ne.b32 p, %66, 0;\n"
    "wgmma.mma_async.sync.aligned.m64n128k16.f32.bf16.bf16 {%0, %1, %2, %3, %4, %5, %6, %7, %8, %9, %10, %11, %12, %13, %14, %15, %16, %17, %18, %19, %20, %21, %22, %23, %24, %25, %26, %27, %28, %29, %30, %31, %32, %33, %34, %35, %36, %37, %38, %39, %40, %41, %42, %43, %44, %45, %46, %47, %48, %49, %50, %51, %52, %53, %54, %55, %56, %57, %58, %59, %60, %61, %62, %63}, %64, %65, p, 1, 1, 0, 1;\n}\n"
    : "+f"(d[128]), "+f"(d[129]), "+f"(d[130]), "+f"(d[131]), "+f"(d[132]), "+f"(d[133]), "+f"(d[134]), "+f"(d[135]), "+f"(d[136]), "+f"(d[137]), "+f"(d[138]), "+f"(d[139]), "+f"(d[140]), "+f"(d[141]), "+f"(d[142]), "+f"(d[143]), "+f"(d[144]), "+f"(d[145]), "+f"(d[146]), "+f"(d[147]), "+f"(d[148]), "+f"(d[149]), "+f"(d[150]), "+f"(d[151]), "+f"(d[152]), "+f"(d[153]), "+f"(d[154]), "+f"(d[155]), "+f"(d[156]), "+f"(d[157]), "+f"(d[158]), "+f"(d[159]), "+f"(d[160]), "+f"(d[161]), "+f"(d[162]), "+f"(d[163]), "+f"(d[164]), "+f"(d[165]), "+f"(d[166]), "+f"(d[167]), "+f"(d[168]), "+f"(d[169]), "+f"(d[170]), "+f"(d[171]), "+f"(d[172]), "+f"(d[173]), "+f"(d[174]), "+f"(d[175]), "+f"(d[176]), "+f"(d[177]), "+f"(d[178]), "+f"(d[179]), "+f"(d[180]), "+f"(d[181]), "+f"(d[182]), "+f"(d[183]), "+f"(d[184]), "+f"(d[185]), "+f"(d[186]), "+f"(d[187]), "+f"(d[188]), "+f"(d[189]), "+f"(d[190]), "+f"(d[191])
    : "l"(da), "l"(db), "r"(scale_d));
}
__device__ __forceinline__ void wgmma_n256_k(float (&d)[192], uint64_t da, uint64_t db, int scale_d) {
  asm volatile("{\n.reg .pred p;\nsetp.ne.b32 p, %130, 0;\n"
    "wgmma.mma_async.sync.aligned.m64n256k16.f32.bf16.bf16 {%0, %1, %2, %3, %4, %5, %6, %7, %8, %9, %10, %11, %12, %13, %14, %15, %16, %17, %18, %19, %20, %21, %22, %23, %24, %25, %26, %27, %28, %29, %30, %31, %32, %33, %34, %35, %36, %37, %38, %39, %40, %41, %42, %43, %44, %45, %46, %47, %48, %49, %50, %51, %52, %53, %54, %55, %56, %57, %58, %59, %60, %61, %62, %63, %64, %65, %66, %67, %68, %69, %70, %71, %72, %73, %74, %75, %76, %77, %78, %79, %80, %81, %82, %83, %84, %85, %86, %87, %88, %89, %90, %91, %92, %93, %94, %95, %96, %97, %98, %99, %100, %101, %102, %103, %104, %105, %106, %107, %108, %109, %110, %111, %112, %113, %114, %115, %116, %117, %118, %119, %120, %121, %122, %123, %124, %125, %126, %127}, %128, %129, p, 1, 1, 0, 0;\n}\n"
    : "+f"(d[0]), "+f"(d[1]), "+f"(d[2]), "+f"(d[3]), "+f"(d[4]), "+f"(d[5]), "+f"(d[6]), "+f"(d[7]), "+f"(d[8]), "+f"(d[9]), "+f"(d[10]), "+f"(d[11]), "+f"(d[12]), "+f"(d[13]), "+f"(d[14]), "+f"(d[15]), "+f"(d[16]), "+f"(d[17]), "+f"(d[18]), "+f"(d[19]), "+f"(d[20]), "+f"(d[21]), "+f"(d[22]), "+f"(d[23]), "+f"(d[24]), "+f"(d[25]), "+f"(d[26]), "+f"(d[27]), "+f"(d[28]), "+f"(d[29]), "+f"(d[30]), "+f"(d[31]), "+f"(d[32]), "+f"(d[33]), "+f"(d[34]), "+f"(d[35]), "+f"(d[36]), "+f"(d[37]), "+f"(d[38]), "+f"(d[39]), "+f"(d[40]), "+f"(d[41]), "+f"(d[42]), "+f"(d[43]), "+f"(d[44]), "+f"(d[45]), "+f"(d[46]), "+f"(d[47]), "+f"(d[48]), "+f"(d[49]), "+f"(d[50]), "+f"(d[51]), "+f"(d[52]), "+f"(d[53]), "+f"(d[54]), "+f"(d[55]), "+f"(d[56]), "+f"(d[57]), "+f"(d[58]), "+f"(d[59]), "+f"(d[60]), "+f"(d[61]), "+f"(d[62]), "+f"(d[63]), "+f"(d[64]), "+f"(d[65]), "+f"(d[66]), "+f"(d[67]), "+f"(d[68]), "+f"(d[69]), "+f"(d[70]), "+f"(d[71]), "+f"(d[72]), "+f"(d[73]), "+f"(d[74]), "+f"(d[75]), "+f"(d[76]), "+f"(d[77]), "+f"(d[78]), "+f"(d[79]), "+f"(d[80]), "+f"(d[81]), "+f"(d[82]), "+f"(d[83]), "+f"(d[84]), "+f"(d[85]), "+f"(d[86]), "+f"(d[87]), "+f"(d[88]), "+f"(d[89]), "+f"(d[90]), "+f"(d[91]), "+f"(d[92]), "+f"(d[93]), "+f"(d[94]), "+f"(d[95]), "+f"(d[96]), "+f"(d[97]), "+f"(d[98]), "+f"(d[99]), "+f"(d[100]), "+f"(d[101]), "+f"(d[102]), "+f"(d[103]), "+f"(d[104]), "+f"(d[105]), "+f"(d[106]), "+f"(d[107]), "+f"(d[108]), "+f"(d[109]), "+f"(d[110]), "+f"(d[111]), "+f"(d[112]), "+f"(d[113]), "+f"(d[114]), "+f"(d[115]), "+f"(d[116]), "+f"(d[117]), "+f"(d[118]), "+f"(d[119]), "+f"(d[120]), "+f"(d[121]), "+f"(d[122]), "+f"(d[123]), "+f"(d[124]), "+f"(d[125]), "+f"(d[126]), "+f"(d[127])
    : "l"(da), "l"(db), "r"(scale_d));
}
__device__ __forceinline__ void wgmma_n128_k(float (&d)[192], uint64_t da, uint64_t db, int scale_d) {
  asm volatile("{\n.reg .pred p;\nsetp.ne.b32 p, %66, 0;\n"
    "wgmma.mma_async.sync.aligned.m64n128k16.f32.bf16.bf16 {%0, %1, %2, %3, %4, %5, %6, %7, %8, %9, %10, %11, %12, %13, %14, %15, %16, %17, %18, %19, %20, %21, %22, %23, %24, %25, %26, %27, %28, %29, %30, %31, %32, %33, %34, %35, %36, %37, %38, %39, %40, %41, %42, %43, %44, %45, %46, %47, %48, %49, %50, %51, %52, %53, %54, %55, %56, %57, %58, %59, %60, %61, %62, %63}, %64, %65, p, 1, 1, 0, 0;\n}\n"
    : "+f"(d[128]), "+f"(d[129]), "+f"(d[130]), "+f"(d[131]), "+f"(d[132]), "+f"(d[133]), "+f"(d[134]), "+f"(d[135]), "+f"(d[136]), "+f"(d[137]), "+f"(d[138]), "+f"(d[139]), "+f"(d[140]), "+f"(d[141]), "+f"(d[142]), "+f"(d[143]), "+f"(d[144]), "+f"(d[145]), "+f"(d[146]), "+f"(d[147]), "+f"(d[148]), "+f"(d[149]), "+f"(d[150]), "+f"(d[151]), "+f"(d[152]), "+f"(d[153]), "+f"(d[154]), "+f"(d[155]), "+f"(d[156]), "+f"(d[157]), "+f"(d[158]), "+f"(d[159]), "+f"(d[160]), "+f"(d[161]), "+f"(d[162]), "+f"(d[163]), "+f"(d[164]), "+f"(d[165]), "+f"(d[166]), "+f"(d[167]), "+f"(d[168]), "+f"(d[169]), "+f"(d[170]), "+f"(d[171]), "+f"(d[172]), "+f"(d[173]), "+f"(d[174]), "+f"(d[175]), "+f"(d[176]), "+f"(d[177]), "+f"(d[178]), "+f"(d[179]), "+f"(d[180]), "+f"(d[181]), "+f"(d[182]), "+f"(d[183]), "+f"(d[184]), "+f"(d[185]), "+f"(d[186]), "+f"(d[187]), "+f"(d[188]), "+f"(d[189]), "+f"(d[190]), "+f"(d[191])
    : "l"(da), "l"(db), "r"(scale_d));
}
__device__ __forceinline__ void wgmma_n40_tt(float (&d)[20], uint64_t da, uint64_t db, int scale_d) {
  asm volatile("{\n.reg .pred p;\nsetp.ne.b32 p, %22, 0;\n"
    "wgmma.mma_async.sync.aligned.m64n40k16.f32.bf16.bf16 {%0, %1, %2, %3, %4, %5, %6, %7, %8, %9, %10, %11, %12, %13, %14, %15, %16, %17, %18, %19}, %20, %21, p, 1, 1, 1, 1;\n}\n"
    : "+f"(d[0]), "+f"(d[1]), "+f"(d[2]), "+f"(d[3]), "+f"(d[4]), "+f"(d[5]), "+f"(d[6]), "+f"(d[7]), "+f"(d[8]), "+f"(d[9]), "+f"(d[10]), "+f"(d[11]), "+f"(d[12]), "+f"(d[13]), "+f"(d[14]), "+f"(d[15]), "+f"(d[16]), "+f"(d[17]), "+f"(d[18]), "+f"(d[19])
    : "l"(da), "l"(db), "r"(scale_d));
}
__device__ __forceinline__ void wgmma_n40_rs(float (&d)[20], const uint32_t (&a)[4], uint64_t db, int scale_d) {
  asm volatile("{\n.reg .pred p;\nsetp.ne.b32 p, %25, 0;\n"
    "wgmma.mma_async.sync.aligned.m64n40k16.f32.bf16.bf16 {%0, %1, %2, %3, %4, %5, %6, %7, %8, %9, %10, %11, %12, %13, %14, %15, %16, %17, %18, %19}, {%20, %21, %22, %23}, %24, p, 1, 1, 1;\n}\n"
    : "+f"(d[0]), "+f"(d[1]), "+f"(d[2]), "+f"(d[3]), "+f"(d[4]), "+f"(d[5]), "+f"(d[6]), "+f"(d[7]), "+f"(d[8]), "+f"(d[9]), "+f"(d[10]), "+f"(d[11]), "+f"(d[12]), "+f"(d[13]), "+f"(d[14]), "+f"(d[15]), "+f"(d[16]), "+f"(d[17]), "+f"(d[18]), "+f"(d[19])
    : "r"(a[0]), "r"(a[1]), "r"(a[2]), "r"(a[3]), "l"(db), "r"(scale_d));
}
__device__ __forceinline__ void wgmma_n128_0(float (&d)[192], uint64_t da, uint64_t db) {
  asm volatile("{\n.reg .pred p;\nsetp.ne.b32 p, 0, 0;\n"
    "wgmma.mma_async.sync.aligned.m64n128k16.f32.bf16.bf16 {%0, %1, %2, %3, %4, %5, %6, %7, %8, %9, %10, %11, %12, %13, %14, %15, %16, %17, %18, %19, %20, %21, %22, %23, %24, %25, %26, %27, %28, %29, %30, %31, %32, %33, %34, %35, %36, %37, %38, %39, %40, %41, %42, %43, %44, %45, %46, %47, %48, %49, %50, %51, %52, %53, %54, %55, %56, %57, %58, %59, %60, %61, %62, %63}, %64, %65, p, 1, 1, 0, 1;\n}\n"
    : "=f"(d[128]), "=f"(d[129]), "=f"(d[130]), "=f"(d[131]), "=f"(d[132]), "=f"(d[133]), "=f"(d[134]), "=f"(d[135]), "=f"(d[136]), "=f"(d[137]), "=f"(d[138]), "=f"(d[139]), "=f"(d[140]), "=f"(d[141]), "=f"(d[142]), "=f"(d[143]), "=f"(d[144]), "=f"(d[145]), "=f"(d[146]), "=f"(d[147]), "=f"(d[148]), "=f"(d[149]), "=f"(d[150]), "=f"(d[151]), "=f"(d[152]), "=f"(d[153]), "=f"(d[154]), "=f"(d[155]), "=f"(d[156]), "=f"(d[157]), "=f"(d[158]), "=f"(d[159]), "=f"(d[160]), "=f"(d[161]), "=f"(d[162]), "=f"(d[163]), "=f"(d[164]), "=f"(d[165]), "=f"(d[166]), "=f"(d[167]), "=f"(d[168]), "=f"(d[169]), "=f"(d[170]), "=f"(d[171]), "=f"(d[172]), "=f"(d[173]), "=f"(d[174]), "=f"(d[175]), "=f"(d[176]), "=f"(d[177]), "=f"(d[178]), "=f"(d[179]), "=f"(d[180]), "=f"(d[181]), "=f"(d[182]), "=f"(d[183]), "=f"(d[184]), "=f"(d[185]), "=f"(d[186]), "=f"(d[187]), "=f"(d[188]), "=f"(d[189]), "=f"(d[190]), "=f"(d[191])
    : "l"(da), "l"(db));
}
__device__ __forceinline__ void wgmma_n128_rs(float (&d)[192], const uint32_t (&a)[4], uint64_t db, int scale_d) {
  asm volatile("{\n.reg .pred p;\nsetp.ne.b32 p, %69, 0;\n"
    "wgmma.mma_async.sync.aligned.m64n128k16.f32.bf16.bf16 {%0, %1, %2, %3, %4, %5, %6, %7, %8, %9, %10, %11, %12, %13, %14, %15, %16, %17, %18, %19, %20, %21, %22, %23, %24, %25, %26, %27, %28, %29, %30, %31, %32, %33, %34, %35, %36, %37, %38, %39, %40, %41, %42, %43, %44, %45, %46, %47, %48, %49, %50, %51, %52, %53, %54, %55, %56, %57, %58, %59, %60, %61, %62, %63}, {%64, %65, %66, %67}, %68, p, 1, 1, 1;\n}\n"
    : "+f"(d[128]), "+f"(d[129]), "+f"(d[130]), "+f"(d[131]), "+f"(d[132]), "+f"(d[133]), "+f"(d[134]), "+f"(d[135]), "+f"(d[136]), "+f"(d[137]), "+f"(d[138]), "+f"(d[139]), "+f"(d[140]), "+f"(d[141]), "+f"(d[142]), "+f"(d[143]), "+f"(d[144]), "+f"(d[145]), "+f"(d[146]), "+f"(d[147]), "+f"(d[148]), "+f"(d[149]), "+f"(d[150]), "+f"(d[151]), "+f"(d[152]), "+f"(d[153]), "+f"(d[154]), "+f"(d[155]), "+f"(d[156]), "+f"(d[157]), "+f"(d[158]), "+f"(d[159]), "+f"(d[160]), "+f"(d[161]), "+f"(d[162]), "+f"(d[163]), "+f"(d[164]), "+f"(d[165]), "+f"(d[166]), "+f"(d[167]), "+f"(d[168]), "+f"(d[169]), "+f"(d[170]), "+f"(d[171]), "+f"(d[172]), "+f"(d[173]), "+f"(d[174]), "+f"(d[175]), "+f"(d[176]), "+f"(d[177]), "+f"(d[178]), "+f"(d[179]), "+f"(d[180]), "+f"(d[181]), "+f"(d[182]), "+f"(d[183]), "+f"(d[184]), "+f"(d[185]), "+f"(d[186]), "+f"(d[187]), "+f"(d[188]), "+f"(d[189]), "+f"(d[190]), "+f"(d[191])
    : "r"(a[0]), "r"(a[1]), "r"(a[2]), "r"(a[3]), "l"(db), "r"(scale_d));
}
__device__ __forceinline__ void wgmma_n32_0(float (&d)[16], uint64_t da, uint64_t db) {
  asm volatile("{\n.reg .pred p;\nsetp.ne.b32 p, 0, 0;\n"
    "wgmma.mma_async.sync.aligned.m64n32k16.f32.bf16.bf16 {%0, %1, %2, %3, %4, %5, %6, %7, %8, %9, %10, %11, %12, %13, %14, %15}, %16, %17, p, 1, 1, 0, 1;\n}\n"
    : "=f"(d[0]), "=f"(d[1]), "=f"(d[2]), "=f"(d[3]), "=f"(d[4]), "=f"(d[5]), "=f"(d[6]), "=f"(d[7]), "=f"(d[8]), "=f"(d[9]), "=f"(d[10]), "=f"(d[11]), "=f"(d[12]), "=f"(d[13]), "=f"(d[14]), "=f"(d[15])
    : "l"(da), "l"(db));
}
__device__ __forceinline__ void wgmma_n32(float (&d)[16], uint64_t da, uint64_t db, int scale_d) {
  asm volatile("{\n.reg .pred p;\nsetp.ne.b32 p, %18, 0;\n"
    "wgmma.mma_async.sync.aligned.m64n32k16.f32.bf16.bf16 {%0, %1, %2, %3, %4, %5, %6, %7, %8, %9, %10, %11, %12, %13, %14, %15}, %16, %17, p, 1, 1, 0, 1;\n}\n"
    : "+f"(d[0]), "+f"(d[1]), "+f"(d[2]), "+f"(d[3]), "+f"(d[4]), "+f"(d[5]), "+f"(d[6]), "+f"(d[7]), "+f"(d[8]), "+f"(d[9]), "+f"(d[10]), "+f"(d[11]), "+f"(d[12]), "+f"(d[13]), "+f"(d[14]), "+f"(d[15])
    : "l"(da), "l"(db), "r"(scale_d));
}
__device__ __forceinline__ void wgmma_n8_t(float (&d)[4], uint64_t da, uint64_t db, int scale_d) {
  asm volatile("{\n.reg .pred p;\nsetp.ne.b32 p, %6, 0;\n"
    "wgmma.mma_async.sync.aligned.m64n8k16.f32.bf16.bf16 {%0, %1, %2, %3}, %4, %5, p, 1, 1, 1, 0;\n}\n"
    : "+f"(d[0]), "+f"(d[1]), "+f"(d[2]), "+f"(d[3])
    : "l"(da), "l"(db), "r"(scale_d));
}
__device__ __forceinline__ void wgmma_n128_rs0(float (&d)[192], const uint32_t (&a)[4], uint64_t db) {
  asm volatile("{\n.reg .pred p;\nsetp.ne.b32 p, 0, 0;\n"
    "wgmma.mma_async.sync.aligned.m64n128k16.f32.bf16.bf16 {%0, %1, %2, %3, %4, %5, %6, %7, %8, %9, %10, %11, %12, %13, %14, %15, %16, %17, %18, %19, %20, %21, %22, %23, %24, %25, %26, %27, %28, %29, %30, %31, %32, %33, %34, %35, %36, %37, %38, %39, %40, %41, %42, %43, %44, %45, %46, %47, %48, %49, %50, %51, %52, %53, %54, %55, %56, %57, %58, %59, %60, %61, %62, %63}, {%64, %65, %66, %67}, %68, p, 1, 1, 1;\n}\n"
    : "=f"(d[128]), "=f"(d[129]), "=f"(d[130]), "=f"(d[131]), "=f"(d[132]), "=f"(d[133]), "=f"(d[134]), "=f"(d[135]), "=f"(d[136]), "=f"(d[137]), "=f"(d[138]), "=f"(d[139]), "=f"(d[140]), "=f"(d[141]), "=f"(d[142]), "=f"(d[143]), "=f"(d[144]), "=f"(d[145]), "=f"(d[146]), "=f"(d[147]), "=f"(d[148]), "=f"(d[149]), "=f"(d[150]), "=f"(d[151]), "=f"(d[152]), "=f"(d[153]), "=f"(d[154]), "=f"(d[155]), "=f"(d[156]), "=f"(d[157]), "=f"(d[158]), "=f"(d[159]), "=f"(d[160]), "=f"(d[161]), "=f"(d[162]), "=f"(d[163]), "=f"(d[164]), "=f"(d[165]), "=f"(d[166]), "=f"(d[167]), "=f"(d[168]), "=f"(d[169]), "=f"(d[170]), "=f"(d[171]), "=f"(d[172]), "=f"(d[173]), "=f"(d[174]), "=f"(d[175]), "=f"(d[176]), "=f"(d[177]), "=f"(d[178]), "=f"(d[179]), "=f"(d[180]), "=f"(d[181]), "=f"(d[182]), "=f"(d[183]), "=f"(d[184]), "=f"(d[185]), "=f"(d[186]), "=f"(d[187]), "=f"(d[188]), "=f"(d[189]), "=f"(d[190]), "=f"(d[191])
    : "r"(a[0]), "r"(a[1]), "r"(a[2]), "r"(a[3]), "l"(db));
}
__device__ __forceinline__ void wgmma_n256_rs(float (&d)[192], const uint32_t (&a)[4], uint64_t db, int scale_d) {
  asm volatile("{\n.reg .pred p;\nsetp.ne.b32 p, %133, 0;\n"
    "wgmma.mma_async.sync.aligned.m64n256k16.f32.bf16.bf16 {%0, %1, %2, %3, %4, %5, %6, %7, %8, %9, %10, %11, %12, %13, %14, %15, %16, %17, %18, %19, %20, %21, %22, %23, %24, %25, %26, %27, %28, %29, %30, %31, %32, %33, %34, %35, %36, %37, %38, %39, %40, %41, %42, %43, %44, %45, %46, %47, %48, %49, %50, %51, %52, %53, %54, %55, %56, %57, %58, %59, %60, %61, %62, %63, %64, %65, %66, %67, %68, %69, %70, %71, %72, %73, %74, %75, %76, %77, %78, %79, %80, %81, %82, %83, %84, %85, %86, %87, %88, %89, %90, %91, %92, %93, %94, %95, %96, %97, %98, %99, %100, %101, %102, %103, %104, %105, %106, %107, %108, %109, %110, %111, %112, %113, %114, %115, %116, %117, %118, %119, %120, %121, %122, %123, %124, %125, %126, %127}, {%128, %129, %130, %131}, %132, p, 1, 1, 1;\n}\n"
    : "+f"(d[0]), "+f"(d[1]), "+f"(d[2]), "+f"(d[3]), "+f"(d[4]), "+f"(d[5]), "+f"(d[6]), "+f"(d[7]), "+f"(d[8]), "+f"(d[9]), "+f"(d[10]), "+f"(d[11]), "+f"(d[12]), "+f"(d[13]), "+f"(d[14]), "+f"(d[15]), "+f"(d[16]), "+f"(d[17]), "+f"(d[18]), "+f"(d[19]), "+f"(d[20]), "+f"(d[21]), "+f"(d[22]), "+f"(d[23]), "+f"(d[24]), "+f"(d[25]), "+f"(d[26]), "+f"(d[27]), "+f"(d[28]), "+f"(d[29]), "+f"(d[30]), "+f"(d[31]), "+f"(d[32]), "+f"(d[33]), "+f"(d[34]), "+f"(d[35]), "+f"(d[36]), "+f"(d[37]), "+f"(d[38]), "+f"(d[39]), "+f"(d[40]), "+f"(d[41]), "+f"(d[42]), "+f"(d[43]), "+f"(d[44]), "+f"(d[45]), "+f"(d[46]), "+f"(d[47]), "+f"(d[48]), "+f"(d[49]), "+f"(d[50]), "+f"(d[51]), "+f"(d[52]), "+f"(d[53]), "+f"(d[54]), "+f"(d[55]), "+f"(d[56]), "+f"(d[57]), "+f"(d[58]), "+f"(d[59]), "+f"(d[60]), "+f"(d[61]), "+f"(d[62]), "+f"(d[63]), "+f"(d[64]), "+f"(d[65]), "+f"(d[66]), "+f"(d[67]), "+f"(d[68]), "+f"(d[69]), "+f"(d[70]), "+f"(d[71]), "+f"(d[72]), "+f"(d[73]), "+f"(d[74]), "+f"(d[75]), "+f"(d[76]), "+f"(d[77]), "+f"(d[78]), "+f"(d[79]), "+f"(d[80]), "+f"(d[81]), "+f"(d[82]), "+f"(d[83]), "+f"(d[84]), "+f"(d[85]), "+f"(d[86]), "+f"(d[87]), "+f"(d[88]), "+f"(d[89]), "+f"(d[90]), "+f"(d[91]), "+f"(d[92]), "+f"(d[93]), "+f"(d[94]), "+f"(d[95]), "+f"(d[96]), "+f"(d[97]), "+f"(d[98]), "+f"(d[99]), "+f"(d[100]), "+f"(d[101]), "+f"(d[102]), "+f"(d[103]), "+f"(d[104]), "+f"(d[105]), "+f"(d[106]), "+f"(d[107]), "+f"(d[108]), "+f"(d[109]), "+f"(d[110]), "+f"(d[111]), "+f"(d[112]), "+f"(d[113]), "+f"(d[114]), "+f"(d[115]), "+f"(d[116]), "+f"(d[117]), "+f"(d[118]), "+f"(d[119]), "+f"(d[120]), "+f"(d[121]), "+f"(d[122]), "+f"(d[123]), "+f"(d[124]), "+f"(d[125]), "+f"(d[126]), "+f"(d[127])
    : "r"(a[0]), "r"(a[1]), "r"(a[2]), "r"(a[3]), "l"(db), "r"(scale_d));
}
__device__ __forceinline__ void wgmma_n256_rs0(float (&d)[192], const uint32_t (&a)[4], uint64_t db) {
  asm volatile("{\n.reg .pred p;\nsetp.ne.b32 p, 0, 0;\n"
    "wgmma.mma_async.sync.aligned.m64n256k16.f32.bf16.bf16 {%0, %1, %2, %3, %4, %5, %6, %7, %8, %9, %10, %11, %12, %13, %14, %15, %16, %17, %18, %19, %20, %21, %22, %23, %24, %25, %26, %27, %28, %29, %30, %31, %32, %33, %34, %35, %36, %37, %38, %39, %40, %41, %42, %43, %44, %45, %46, %47, %48, %49, %50, %51, %52, %53, %54, %55, %56, %57, %58, %59, %60, %61, %62, %63, %64, %65, %66, %67, %68, %69, %70, %71, %72, %73, %74, %75, %76, %77, %78, %79, %80, %81, %82, %83, %84, %85, %86, %87, %88, %89, %90, %91, %92, %93, %94, %95, %96, %97, %98, %99, %100, %101, %102, %103, %104, %105, %106, %107, %108, %109, %110, %111, %112, %113, %114, %115, %116, %117, %118, %119, %120, %121, %122, %123, %124, %125, %126, %127}, {%128, %129, %130, %131}, %132, p, 1, 1, 1;\n}\n"
    : "=f"(d[0]), "=f"(d[1]), "=f"(d[2]), "=f"(d[3]), "=f"(d[4]), "=f"(d[5]), "=f"(d[6]), "=f"(d[7]), "=f"(d[8]), "=f"(d[9]), "=f"(d[10]), "=f"(d[11]), "=f"(d[12]), "=f"(d[13]), "=f"(d[14]), "=f"(d[15]), "=f"(d[16]), "=f"(d[17]), "=f"(d[18]), "=f"(d[19]), "=f"(d[20]), "=f"(d[21]), "=f"(d[22]), "=f"(d[23]), "=f"(d[24]), "=f"(d[25]), "=f"(d[26]), "=f"(d[27]), "=f"(d[28]), "=f"(d[29]), "=f"(d[30]), "=f"(d[31]), "=f"(d[32]), "=f"(d[33]), "=f"(d[34]), "=f"(d[35]), "=f"(d[36]), "=f"(d[37]), "=f"(d[38]), "=f"(d[39]), "=f"(d[40]), "=f"(d[41]), "=f"(d[42]), "=f"(d[43]), "=f"(d[44]), "=f"(d[45]), "=f"(d[46]), "=f"(d[47]), "=f"(d[48]), "=f"(d[49]), "=f"(d[50]), "=f"(d[51]), "=f"(d[52]), "=f"(d[53]), "=f"(d[54]), "=f"(d[55]), "=f"(d[56]), "=f"(d[57]), "=f"(d[58]), "=f"(d[59]), "=f"(d[60]), "=f"(d[61]), "=f"(d[62]), "=f"(d[63]), "=f"(d[64]), "=f"(d[65]), "=f"(d[66]), "=f"(d[67]), "=f"(d[68]), "=f"(d[69]), "=f"(d[70]), "=f"(d[71]), "=f"(d[72]), "=f"(d[73]), "=f"(d[74]), "=f"(d[75]), "=f"(d[76]), "=f"(d[77]), "=f"(d[78]), "=f"(d[79]), "=f"(d[80]), "=f"(d[81]), "=f"(d[82]), "=f"(d[83]), "=f"(d[84]), "=f"(d[85]), "=f"(d[86]), "=f"(d[87]), "=f"(d[88]), "=f"(d[89]), "=f"(d[90]), "=f"(d[91]), "=f"(d[92]), "=f"(d[93]), "=f"(d[94]), "=f"(d[95]), "=f"(d[96]), "=f"(d[97]), "=f"(d[98]), "=f"(d[99]), "=f"(d[100]), "=f"(d[101]), "=f"(d[102]), "=f"(d[103]), "=f"(d[104]), "=f"(d[105]), "=f"(d[106]), "=f"(d[107]), "=f"(d[108]), "=f"(d[109]), "=f"(d[110]), "=f"(d[111]), "=f"(d[112]), "=f"(d[113]), "=f"(d[114]), "=f"(d[115]), "=f"(d[116]), "=f"(d[117]), "=f"(d[118]), "=f"(d[119]), "=f"(d[120]), "=f"(d[121]), "=f"(d[122]), "=f"(d[123]), "=f"(d[124]), "=f"(d[125]), "=f"(d[126]), "=f"(d[127])
    : "r"(a[0]), "r"(a[1]), "r"(a[2]), "r"(a[3]), "l"(db));
}

constexpr int SLOT = 16384;
constexpr int VB = 4 * SLOT, PH = 0, XS = 6;
constexpr int SM_SD = 13 * SLOT;
constexpr int SM_BAR = SM_SD + 8192;
constexpr int SM_RS = SM_BAR + 1024;
constexpr int SM_AP = SM_RS + 640;
constexpr int SM_BP = SM_AP + 2048;
constexpr int SM_EPOCH = SM_BP + 6144;
constexpr int SM_TOTAL = SM_EPOCH + 16;
constexpr int FM = 0, FT = 16, FW = 30, CM = 46, CT = 62, CW = 76, B_EF = 92, B_STAT = 93, B_KVF = 94, B_HALO = 95,
              B_KVDONE = 96, B_OH0 = 97, B_OH1 = 98, B_XH0 = 99, B_XDONE = 100, B_WFD = 101, B_XT = 102, B_OF0 = 103, B_KVF1 = 104, B_RAW = 106  , B_X0 = 108;
constexpr uint64_t BAR_LG = 0x00043333330004ull;
#define BA(i) (bar + (i) * 8)
#define REL2(i) release2c(SB0 + SM_BAR + (i) * 8)
constexpr int NF = 4, ND = 12, NR = 0, NWOP = 48, NAOP = 37;
constexpr uint64_t TL_A = 0x278627862786ull, TL_B = 0xac39bac39bacull, WO_A = 0x764a2396b4ac39ffull, WO_B = 0xc8b51c780512786bull;
__constant__ uint32_t c_wop[NWOP + 1] = {0xea8009, 0x186b8000, 0x26b8112, 0x18ec011a, 0x6c8224, 0x22ec822b, 0x170330, 0x22970339, 0x18178442, 0x18180554, 0x18188660, 0x18190772, 0x18198884, 0x181a0990, 0x181a8aa2, 0x181b0bb4, 0x181b8cc0, 0xaed90fc, 0xa9791ea, 0x181c0dd2, 0xa9812db, 0x129893c9, 0x181c8ee4, 0x181d0ff0, 0x109d94b3, 0x109f15ac, 0x109f969a, 0x10a0178b, 0x10a09879, 0x10a11963, 0x10a19a5c, 0x10a21b4a, 0x9229e0b, 0x9231f16, 0x1123a028, 0x11242137, 0x1124a242, 0x112e2351, 0x132e2465, 0x132e2570, 0x11272688, 0x1127a797, 0x112828ac, 0x1128a9b1, 0x11292ac5, 0x1129abdb, 0x112a2ce8, 0x112b2dfc, 0};
__constant__ uint32_t c_aop[NAOP + 1] = {0x6d0228, 0x170336, 0x178447, 0x180558, 0x188666, 0x190777, 0x198888, 0x1a0996, 0x1a8aa7, 0x1b0bb8, 0x1b8cc6, 0x1c0dd7, 0x1c8ee8, 0x1d0ff6, 0x1d93c2, 0x1f14b6, 0x1f95a8, 0x201697, 0x209782, 0x211876, 0x219968, 0x221a57, 0x229b42, 0xa32029, 0xa3a133, 0xa4224c, 0xa4a35a, 0xae2464, 0xa6257b, 0xa6a686, 0xa72799, 0xa7a8a3, 0xa829b2, 0xa8aaca, 0xa92bd4, 0xaa2ce6, 0xaaadf7, 0};
__constant__ uint32_t c_map[64] = {4, 5, 6, 7, 0, 16, 32, 48, 64, 80, 96, 112, 1, 17, 33, 49, 65, 81, 97, 113, 2, 18, 34, 50, 66, 82, 98, 114, 3, 19, 35, 51, 67, 83, 99, 115, 20, 36, 52, 68, 84, 100, 116, 21, 37, 53, 69, 85, 101, 117, 22, 38, 54, 70, 86, 102, 118, 23, 39, 55, 71, 87, 103, 119};
enum { MAP_WF = 0, MAP_WA = 2, MAP_WB = 4, MAP_WOA = 6, MAP_WOB = 8, MAP_X0 = 10, MAP_X = 11, MAP_O = 12, MAP_PHI = 13, NMAP = 14 };
struct Maps { CUtensorMap m[NMAP]; };

#define PL 2
#define PROFL(a, b)
#define SUBS 8
#define QORD 1
#define NCH 4
#define CHW 1
#define SUBS1 12
#define XRAT 10
#define XRN 4
#define BT1 1
#define CV0 0
#define ST1 8
#define O1P 2
#define X0AT 1
#define W1DL 400
#define SKA 0
#define SKB 0
#define BPRE 0
#define XST 3
#define NLAYERS 4
constexpr float L2E = 1.4426950408889634f;

#define D128(lo) desc64(lo, 0x40000040u)
struct Ctx { uint32_t zero, boff; const bf16* x0; bf16* out; };
#define BLK_CTX() \
  uint32_t bid_; asm volatile("mov.u32 %0, %%ctaid.x;" : "=r"(bid_)); \
  bid_ -= c.boff; \
  const uint32_t gr_ = c_map[bid_ >> 1]; \
  const int cr = bid_ & 1, g = gr_ & 7, rb = (gr_ >> 3) + cr, m0 = rb * 128; \
  const uint32_t sb = SB0 + (cr << 24); \
  const uint32_t bar = sb + SM_BAR; \
  (void)cr; (void)g; (void)rb; (void)m0; (void)bar;
extern __shared__ uint8_t smem_raw[];
constexpr uint32_t SB0 = 1024;

#define PHASE_CTX() \
  BLK_CTX(); \
  int tid_ = threadIdx.x; asm volatile("" : "+r"(tid_)); \
  const int lane = tid_ & 31, cw = (tid_ >> 5) - 4, wg = cw >> 2, wq = cw & 3, gq = lane >> 2, t = lane & 3, wrow0 = cw * 16; \
  const int lrow = (lane & 7) + ((lane >> 3) & 1) * 8, lchk = lane >> 4; \
  const bool elected = (tid_ & 127) == 0; \
  const uint32_t rowo = (wrow0 + lrow) * 128, X = (lchk ^ (lane & 7)) << 4; \
  const uint32_t Y = (wrow0 + (lane & 7)) * 128 + (((lane >> 3) ^ (lane & 7)) << 4); \
  const size_t gfr = (size_t)(m0 + wrow0 + gq) * D_ + g * 128 + 8 * t; \
  (void)bar; (void)wq; (void)gq; (void)lrow; (void)lchk; (void)elected; (void)wrow0; (void)wg; (void)rowo; (void)X; (void)t; (void)Y; (void)gfr;
#define MMA_CTX() \
  const uint32_t wu = __shfl_sync(0xffffffffu, wg, 0); \
  const uint32_t dA0 = ((SB0 >> 4) | (1u << 16)) + wu * 512, dB0 = (SB0 >> 4) | (512u << 16); \
  const uint32_t par = layer & 1;

__device__ __forceinline__ void slab_out_half(uint32_t slot, bf16* dst, int wrow0, int lane) {
  const int r0 = lane >> 3, ch = lane & 7;
  const uint32_t src = slot + (wrow0 + r0) * 128;
  uint4 v[4];
#pragma unroll
  for (int i = 0; i < 4; ++i) v[i] = lds128(src + i * 512 + (((ch ^ (4 * i + r0)) & 7) << 4));
  dst += (size_t)(wrow0 + r0) * D_ + ch * 8;
#pragma unroll
  for (int i = 0; i < 4; ++i) *reinterpret_cast<uint4*>(dst + (size_t)i * 4 * D_) = v[i];
}

__device__ __forceinline__ void consumer(const Ctx& c) {
  float acc[192];
  uint32_t xf[4][4];
  uint32_t xp[8][4];
  {
    PHASE_CTX();
    const unsigned int epoch = ld_relaxed(&g_epoch);
    PROFT(tid_ == 128, 0);
    const uint32_t wu = __shfl_sync(0xffffffffu, wg, 0);
    if (tid_ < 128 + 8) sts128(sb + SM_AP + lane * 16, make_uint4(0x3F803F80u, 0x3F803F80u, 0x3F803F80u, 0x3F803F80u));
#pragma unroll 1
    for (int it = 0; it < 2; ++it) {
      float p[4][16];
      mbar_wait(BA(B_RAW + it), 0);
      PROFT(tid_ == 128, it ? 15 : 2);
      const uint32_t da = ((SB0 >> 4) | (1u << 16)) + (wu ? 9 + it : 2 * it) * 1024, db = (SB0 + SM_SD) >> 4;
      wgmma_fence();
#pragma unroll
      for (int h = 0; h < 4; ++h) wgmma_n32_0(p[h], D128(da + (h >> 1) * 512 + (h & 1) * 4), desc64(db + h * 128, 0x80000020u));
#pragma unroll
      for (int h = 0; h < 4; ++h) wgmma_n32(p[h], D128(da + (h >> 1) * 512 + (h & 1) * 4 + 2), desc64(db + h * 128 + 64, 0x80000020u), 1);
      wgmma_commit();
      wgmma_wait<0>();
#pragma unroll
      for (int i = 0; i < 64; ++i) asm volatile("" : "+f"(p[i >> 4][i & 15]) :: "memory");
      const uint32_t base = sb + (wg ? 9 + it : 2 * it) * SLOT + (wq * 16 + gq) * 128;
      uint32_t w[4][4][2];
#pragma unroll
      for (int i = 0; i < 32; ++i) w[i >> 3][(i >> 1) & 3][i & 1] = pack_bf16(p[i >> 3][2 * (i & 7)], p[i >> 3][2 * (i & 7) + 1]);
      if (wu) {
#pragma unroll
        for (int i = 0; i < 8; ++i)
          sts128(base + (i >> 2) * 8192 + (i & 1) * 1024 + (((((i >> 1) & 1) * 4 + t) ^ gq) << 4), make_uint4(w[i >> 1][0][i & 1], w[i >> 1][1][i & 1], w[i >> 1][2][i & 1], w[i >> 1][3][i & 1]));
      } else {
#pragma unroll
        for (int i = 0; i < 16; ++i)
          sts64(base + (i >> 3) * 8192 + (i & 1) * 1024 + ((((t & 1) * 4 + ((i >> 1) & 3)) ^ gq) << 4) + (t >> 1) * 8, w[(i >> 3) * 2][(i >> 1) & 3][i & 1], w[(i >> 3) * 2 + 1][(i >> 1) & 3][i & 1]);
      }
      fence_async_smem();
      __syncwarp();
      if (it == cr && lane == 0) mbar_arrive(BA(B_WFD));
    }
    if (tid_ == 128) sts_f(sb + SM_EPOCH, __uint_as_float(epoch & 1));
#pragma unroll
    for (int i = 0; i < 32; ++i) xp[i >> 2][i & 3] = 0u;
    nbar<1, 256>();
    PROFT(tid_ == 128, 13);
    mbar_wait(BA(FM + cr), 0);
    float cs[3][4];
    wgmma_fence();
#pragma unroll
    for (int ks = 0; ks < 4; ++ks)
#pragma unroll
      for (int i = 0; i < 3; ++i) {
        const uint32_t bx = (i == 0 ? 2 * cr * 1024 : i == 1 ? (2 * cr + 1) * 1024 : (9 + cr) * 1024) + wu * 512;
        wgmma_n8_t(cs[i], D128(((SB0 >> 4) | (512u << 16)) + bx + ks * 128), desc64((SB0 + SM_AP) >> 4, 0), ks != 0);
      }
    wgmma_commit();
    mbar_wait(BA(FM), 0);
#pragma unroll
    for (int k = 0; k < 4; ++k) ldsm_x4(xf[k][0], xf[k][1], xf[k][2], xf[k][3], sb + XS * SLOT + rowo + (X ^ (k << 5)));
    wgmma_wait<0>();
#pragma unroll
    for (int i = 0; i < 12; ++i) asm volatile("" : "+f"(cs[i >> 2][i & 3]) :: "memory");
    if (t < 2) {
#pragma unroll
      for (int i = 0; i < 3; ++i) red_add1(g_cs + (epoch & 1) * 6144 + g * 384 + i * 128 + wg * 64 + wq * 16 + gq + t * 8, t ? cs[i][2] : cs[i][0]);
    }
    PROFT(tid_ == 128, 14);
  }
#pragma unroll 1
  for (int layer = 0;; ++layer) {
    {
      PHASE_CTX();
      MMA_CTX();
      {
        const uint32_t ep = __float_as_uint(lds_f(sb + SM_EPOCH));
        mbar_wait(BA(FM), par);
        wgmma_fence();
        wgmma_n256_rs0(acc, xf[0], D128(dB0));
#pragma unroll
        for (int k = 1; k < 4; ++k) wgmma_n256_rs(acc, xf[k], D128(dB0 + k * 128), 1);
        wgmma_commit();
        if (layer == 0) {
          mbar_wait(BA(B_X0), 0);
#pragma unroll
          for (int i = 0; i < 8; ++i) ldsm_x4(xp[i][0], xp[i][1], xp[i][2], xp[i][3], sb + (11 + (i >> 2)) * SLOT + (Y ^ ((i & 2) << 5)) + (i & 1) * 1024);
          if (lane == ((xp[0][0] ^ xp[1][0] ^ xp[2][0] ^ xp[3][0] ^ xp[7][0]) & c.zero)) REL2(B_XT);
        } else {
#pragma unroll
          for (int i = 0; i < 8; ++i) stsm_x4(sb + (XS + (i >> 2)) * SLOT + (Y ^ ((i & 2) << 5)) + (i & 1) * 1024, xp[i][0], xp[i][1], xp[i][2], xp[i][3]);
        }
        float s0 = 0.f, s1 = 0.f, q0 = 0.f, q1 = 0.f;
        auto stats = [&](int j0, int j1) {
#pragma unroll
          for (int j = j0; j < j1; ++j) {
            const uint32_t u0 = xp[(j >> 2) * 2][j & 3], u1 = xp[(j >> 2) * 2 + 1][j & 3];
            s0 += bf_lo(u0) + bf_hi(u0); s1 += bf_lo(u1) + bf_hi(u1);
            q0 = fmaf(bf_lo(u0), bf_lo(u0), fmaf(bf_hi(u0), bf_hi(u0), q0)); q1 = fmaf(bf_lo(u1), bf_lo(u1), fmaf(bf_hi(u1), bf_hi(u1), q1));
          }
        };
        stats(0, ST1);
        fence_async_smem();
        nbar_dyn(3 + wu + (__float_as_uint(s0 + s1 + q0 + q1) & c.zero), 128);
        mbar_wait(BA(FM + 1), par);
        wgmma_fence();
#pragma unroll
        for (int k = 0; k < 4; ++k) wgmma_n256(acc, D128(dA0 + (XS + 1) * 1024 + k * 2), D128(dB0 + 2048 + k * 128), 1);
        wgmma_commit();
        wgmma_wait<1>();
#pragma unroll
        for (int i = 4; i < 8; ++i) stg128_p(layer, g_x + gfr + (i & 1) * 8 * D_ + (i >> 1) * 32, xp[i][0], xp[i][1], xp[i][2], xp[i][3]);
        {
          uint32_t zc; asm volatile("mov.u32 %0, %%clock;" : "=r"(zc) :: "memory");
          q0 += __uint_as_float(zc & c.zero); q1 += __uint_as_float(zc & c.zero); s0 += __uint_as_float(zc & c.zero); s1 += __uint_as_float(zc & c.zero);
        }
        stats(ST1, 16);
        wgmma_fence();
        wgmma_n128_0(acc, D128(dA0 + XS * 1024), D128(dB0 + 9 * 1024));
#pragma unroll
        for (int k = 1; k < 4; ++k) wgmma_n128(acc, D128(dA0 + XS * 1024 + k * 2), D128(dB0 + 9 * 1024 + k * 128), 1);
        wgmma_commit();
        const bool od = t & 1;
        float sa = od ? s1 : s0, qa = od ? q1 : q0;
        sa += __shfl_xor_sync(0xffffffffu, od ? s0 : s1, 1);
        qa += __shfl_xor_sync(0xffffffffu, od ? q0 : q1, 1);
        wgmma_fence();
#pragma unroll
        for (int k = 0; k < 4; ++k) wgmma_n128(acc, D128(dA0 + (XS + 1) * 1024 + k * 2), D128(dB0 + 10 * 1024 + k * 128), 1);
        wgmma_commit();
        sa += __shfl_xor_sync(0xffffffffu, sa, 2);
        qa += __shfl_xor_sync(0xffffffffu, qa, 2);
        red_add2_p(t < 2, reinterpret_cast<float*>(g_stats + (ep * 4 + layer) * S_ + m0 + wrow0 + gq + t * 8), sa, qa);
        __syncwarp();
        if (lane == 0) mbar_arrive(BA(B_XDONE));
        wgmma_wait<1>();
        if (elected) REL2(CM);
      }
      uint32_t s = 2;
#pragma unroll 1
      for (int i = 2; i < NF; ++i) {
        PROFL(tid_ == 128 && layer == PL + 1, 244 + 2 * i);
        mbar_wait(BA(FM + i), par);
        PROFL(tid_ == 128 && layer == PL + 1, 245 + 2 * i);
        const uint32_t da = dA0 + (XS + s) * 1024, dk = dB0 + s * 2048, dq = dB0 + (9 + s) * 1024;
        wgmma_fence();
#pragma unroll
        for (int k = 0; k < 4; ++k) wgmma_n128(acc, D128(da + k * 2), D128(dq + k * 128), 1);
        wgmma_commit();
        wgmma_wait<1>();
        if (elected) REL2(CM + i - 1);
        wgmma_fence();
#pragma unroll
        for (int k = 0; k < 4; ++k) wgmma_n256(acc, D128(da + k * 2), D128(dk + k * 128), 1);
        wgmma_commit();
        if (++s == 3) s = 0;
      }
#pragma unroll 1
      for (int i = NF; i < 15; ++i) {
        mbar_wait(BA(FM + i), par);
        const uint32_t da = dA0 + (XS + s) * 1024, dk = dB0 + s * 2048;
        wgmma_fence();
#pragma unroll
        for (int k = 0; k < 4; ++k) wgmma_n256(acc, D128(da + k * 2), D128(dk + k * 128), 1);
        wgmma_commit();
        wgmma_wait<1>();
        if (elected) REL2(CM + i - 1);
        if (++s == 3) s = 0;
      }
      {
        const uint64_t dap = desc64(((SB0 + SM_AP) >> 4) + wu * 64, 8), dbp = make_desc_ns(SB0 + SM_BP, 0, 128);
        mbar_wait(BA(B_STAT), par);
        mbar_wait(BA(FM + 15), par);
        PROFT(tid_ == 128, layer * 16 + 9);
        wgmma_fence();
        wgmma_n256_k(acc, dap, dbp, 1);
#pragma unroll
        for (int k = 0; k < 4; ++k) wgmma_n256(acc, D128(dA0 + XS * 1024 + k * 2), D128(dB0 + k * 128), 1);
        wgmma_commit();
        wgmma_wait<1>();
        if (elected) REL2(CM + 14);
        mbar_wait(BA(FT), par);
        wgmma_fence();
        wgmma_n128_k(acc, dap, dbp + 256, 1);
#pragma unroll
        for (int k = 0; k < 4; ++k) wgmma_n128(acc, D128(dA0 + (uint32_t)(TL_A & 15) * 1024 + k * 2), D128(dB0 + (uint32_t)(TL_B & 15) * 1024 + k * 128), 1);
        wgmma_commit();
        wgmma_wait<1>();
        if (elected) REL2(CM + 15);
#pragma unroll
        for (int i = 0; i < 128; ++i) asm volatile("" : "+f"(acc[i]) :: "memory");
      }
    }
    uint32_t of[8][4], o1[4][4];
    {
      PHASE_CTX();
      MMA_CTX();
      PROFT(tid_ == 128, layer * 16 + 1);
      PROFT(lane == 0 && layer == PL, 192 + cw);
      PROFT(tid_ == 128 && layer == PL, 160);
      uint64_t ta = (TL_A >> 4), tw = TL_B >> 4;
      uint32_t da, db, dz = dA0;
      auto sub = [&](int n) {
        const int j = n >> 2, k = n & 3;
        if (k == 0) {
          dz += c.zero;
          da = dz + ((uint32_t)ta & 15) * 1024; db = dB0 + ((uint32_t)tw & 15) * 1024;
          ta >>= 4; tw >>= 4;
          mbar_wait(BA(FT + j), par);
          wgmma_fence();
        }
        wgmma_n128(acc, D128(da + k * 2), D128(db + k * 128), 1);
        if (k == 3) {
          wgmma_commit();
          wgmma_wait<1>();
          if (elected) REL2(CT + j - 1);
        }
      };
      auto run = [&](int j0, int j1) {
#pragma unroll 1
        for (int j = j0; j < j1; ++j) {
          mbar_wait(BA(FT + j), par);
          da = dA0 + ((uint32_t)ta & 15) * 1024; db = dB0 + ((uint32_t)tw & 15) * 1024;
          ta >>= 4; tw >>= 4;
          wgmma_fence();
#pragma unroll
          for (int k = 0; k < 4; ++k) wgmma_n128(acc, D128(da + k * 2), D128(db + k * 128), 1);
          wgmma_commit();
          wgmma_wait<1>();
          if (elected) REL2(CT + j - 1);
        }
        ta = TL_A >> (4 * j1); tw = TL_B >> (4 * j1);
      };
      auto rest = [&](int j0, int sk) {
        if (sk) {
          run(j0, ND - sk);
          if (wu == 0) nbar<6, 256>();
          j0 = ND - sk;
        }
        run(j0, ND);
        if (sk && wu) asm volatile("bar.arrive 6, 256;" ::: "memory");
      };
      auto rest_end = [&]() {
        wgmma_wait<0>();
        if (elected) REL2(CT + ND - 1);
#pragma unroll
        for (int i = 128; i < 192; ++i) asm volatile("" : "+f"(acc[i]) :: "memory");
      };
      const float rs0 = lds_f(sb + SM_RS + (16 + wrow0 + gq) * 4), rs1 = lds_f(sb + SM_RS + (24 + wrow0 + gq) * 4);
#define EPOCH() __float_as_uint(lds_f(sb + SM_EPOCH))
      mbar_wait(BA(CM + 14), par);
      if (par) {
        uint32_t kk[8][4], kp[8][4], vf[2][2][4][4];
        int sn = 4;
#pragma unroll
        for (int i = 0; i < 4 * BT1; ++i) sub(sn++);
        {
          uint32_t vv[8][4];
#pragma unroll
          for (int jp = 0; jp < 8; ++jp) {
            kk[jp][0] = pack_bf16(acc[8 * jp], acc[8 * jp + 1]); kk[jp][1] = pack_bf16(acc[8 * jp + 4], acc[8 * jp + 5]);
            kk[jp][2] = pack_bf16(acc[8 * jp + 2], acc[8 * jp + 3]); kk[jp][3] = pack_bf16(acc[8 * jp + 6], acc[8 * jp + 7]);
#pragma unroll
            for (int i = 0; i < 4; ++i) vv[jp][i] = pack_bf16(acc[64 + 8 * jp + 2 * i], acc[65 + 8 * jp + 2 * i]);
          }
          if (cw == 7) {
            uint32_t* const hbuf = g_halo + (size_t)(((layer >> 1) * 17 + rb + 1) * 8 + g) * 2048;
#pragma unroll
            for (int jp = 0; jp < 8; ++jp) stg128(hbuf + jp * 128 + lane * 4, kk[jp][0], kk[jp][1], kk[jp][2], kk[jp][3]);
#pragma unroll
            for (int i = 0; i < 32; ++i) hbuf[1024 + (i >> 4) * 512 + (gq + (i & 1) * 8) * 32 + ((((i >> 1) & 7) ^ gq) << 2) + t] = vv[i >> 2][i & 3];
            __syncwarp();
            if (lane == 0) mbar_arrive(BA(B_OF0));
          }
#pragma unroll
          for (int jp = 0; jp < 8; ++jp) {
            sub(sn++);
            stsm_x4(sb + VB + (jp >> 2) * SLOT + rowo + (X ^ ((jp & 3) << 5)), vv[jp][0], vv[jp][1], vv[jp][2], vv[jp][3]);
          }
        }
        PROFT(tid_ == 128, layer * 16 + 2);
        const int e = gq & 1;
        float f0[4], f1[4], b0[4], b1[4], rj[4];
#pragma unroll
        for (int nt = 0; nt < 4; ++nt) {
          const int kx = nt * 8 + 2 * t + e;
          const bool okk = (m0 + wrow0 + kx) >= 16;
          const int d0 = kx - gq, d1 = d0 - 8;
          rj[nt] = lds_f(sb + SM_RS + (wrow0 + kx) * 4);
          const bool m0_ = okk && d0 >= 2 && d0 <= 16, m1_ = okk && d1 >= 2 && d1 <= 16;
          f0[nt] = m0_ ? rj[nt] * rs0 * (0.17677669529663687f * L2E) : 0.f;
          f1[nt] = m1_ ? rj[nt] * rs1 * (0.17677669529663687f * L2E) : 0.f;
          b0[nt] = m0_ ? 0.f : -1e30f; b1[nt] = m1_ ? 0.f : -1e30f;
        }
        mbar_wait(BA(CM + 15), par);
#pragma unroll
        for (int jp = 0; jp < 8; ++jp) {
          sub(sn++);
          sts128(sb + PH + cw * 4096 + jp * 512 + lane * 16, make_uint4(kk[jp][0], kk[jp][1], kk[jp][2], kk[jp][3]));
        }
#pragma unroll
        for (int i = 0; i < 4; ++i) sub(sn++);
        nbar<1, 256>();
        PROFT(tid_ == 128, layer * 16 + 3);
        rest(sn >> 2, SKB);
        if (!BPRE) rest_end();
        PROFT(lane == 0 && layer == PL, 200 + cw);
        PROFT(tid_ == 128, layer * 16 + 10);
        if (cw == 0) mbar_wait(BA(B_HALO), (layer >> 1) & 1);
        PROFT(tid_ == 128, layer * 16 + 5);
        const uint32_t vs = sb + (cw ? VB + rowo - 2048 : SM_SD + 4096 + rowo), vst = cw ? SLOT : 2048;
        const uint32_t psel = e ? 0x1054u : 0x5410u;
#pragma unroll
        for (int hp = 0; hp < 2; ++hp) {
#pragma unroll
          for (int i = 4 * hp; i < 4 * hp + 4; ++i) {
            const uint4 u = lds128(sb + (cw ? PH + (cw - 1) * 4096 : SM_SD) + lane * 16 + i * 512);
            kp[i][0] = u.x; kp[i][1] = u.y; kp[i][2] = u.z; kp[i][3] = u.w;
          }
#pragma unroll
          for (int i = 4 * hp; i < 4 * hp + 4; ++i) {
            ldsm_x4_t(vf[0][i & 1][i >> 1][0], vf[0][i & 1][i >> 1][1], vf[0][i & 1][i >> 1][2], vf[0][i & 1][i >> 1][3], vs + (i >> 2) * vst + (X ^ ((i & 3) << 5)));
            ldsm_x4_t(vf[1][i & 1][i >> 1][0], vf[1][i & 1][i >> 1][1], vf[1][i & 1][i >> 1][2], vf[1][i & 1][i >> 1][3], sb + VB + (i >> 2) * SLOT + rowo + (X ^ ((i & 3) << 5)));
          }
          if (BPRE && !hp) rest_end();
          float l0[2][4], l1[2][4];
#pragma unroll
          for (int h = 0; h < 2; ++h) {
            const int H = 2 * hp + h;
            uint32_t qa[8];
#pragma unroll
            for (int i = 0; i < 8; ++i) qa[i] = pack_bf16(acc[128 + 16 * H + 2 * i], acc[129 + 16 * H + 2 * i]);
#pragma unroll
            for (int nt = 3; nt >= 0; --nt) {
              float sc[4] = {0.f, 0.f, 0.f, 0.f};
#pragma unroll
              for (int ks = 0; ks < 2; ++ks) {
                const uint32_t (&kf)[4] = nt < 2 ? kp[2 * H + ks] : kk[2 * H + ks];
                mma_bf16(sc, qa[4 * ks], qa[4 * ks + 1], qa[4 * ks + 2], qa[4 * ks + 3], kf[2 * (nt & 1)], kf[2 * (nt & 1) + 1]);
              }
              l0[h][nt] = fmaf(e ? sc[1] : sc[0], f0[nt], b0[nt]);
              l1[h][nt] = fmaf(e ? sc[3] : sc[2], f1[nt], b1[nt]);
            }
          }
          float mx0[2], mx1[2], s0[2], s1[2];
#pragma unroll
          for (int h = 0; h < 2; ++h) {
            mx0[h] = fmaxf(fmaxf(l0[h][0], l0[h][1]), l0[h][2]);
            mx1[h] = fmaxf(fmaxf(l1[h][1], l1[h][2]), l1[h][3]);
          }
#pragma unroll
          for (int o = 1; o <= 2; o <<= 1)
#pragma unroll
            for (int h = 0; h < 2; ++h) {
              mx0[h] = fmaxf(mx0[h], __shfl_xor_sync(0xffffffffu, mx0[h], o));
              mx1[h] = fmaxf(mx1[h], __shfl_xor_sync(0xffffffffu, mx1[h], o));
            }
#pragma unroll
          for (int h = 0; h < 2; ++h) {
#pragma unroll
            for (int nt = 0; nt < 3; ++nt) { l0[h][nt] = ex2(l0[h][nt] - mx0[h]); l1[h][nt + 1] = ex2(l1[h][nt + 1] - mx1[h]); }
            s0[h] = (l0[h][0] + l0[h][1]) + l0[h][2];
            s1[h] = (l1[h][1] + l1[h][2]) + l1[h][3];
          }
#pragma unroll
          for (int o = 1; o <= 2; o <<= 1)
#pragma unroll
            for (int h = 0; h < 2; ++h) {
              s0[h] += __shfl_xor_sync(0xffffffffu, s0[h], o);
              s1[h] += __shfl_xor_sync(0xffffffffu, s1[h], o);
            }
          uint32_t ow[2][2][4];
#pragma unroll
          for (int h = 0; h < 2; ++h) {
            const int H = 2 * hp + h;
            uint32_t pl[4], ph[4];
            const float i0 = rcp(s0[h]), i1 = rcp(s1[h]);
#pragma unroll
            for (int nt = 0; nt < 4; ++nt) {
              const uint32_t pk = pack_bf16(nt < 3 ? l0[h][nt] * i0 * rj[nt] : 0.f, nt > 0 ? l1[h][nt] * i1 * rj[nt] : 0.f);
              pl[nt] = nt < 3 ? __byte_perm(pk, 0u, psel) : 0u;
              ph[nt] = nt > 0 ? __byte_perm(pk, 0u, psel + 0x2222u) : 0u;
            }
#pragma unroll
            for (int nj = 0; nj < 4; ++nj) {
              float oa[4] = {0.f, 0.f, 0.f, 0.f};
#pragma unroll
              for (int ks = 0; ks < 2; ++ks)
                mma_bf16(oa, pl[2 * ks], ph[2 * ks], pl[2 * ks + 1], ph[2 * ks + 1], vf[ks][nj >> 1][H][2 * (nj & 1)], vf[ks][nj >> 1][H][2 * (nj & 1) + 1]);
              ow[h][0][nj] = pack_bf16(oa[0], oa[1]); ow[h][1][nj] = pack_bf16(oa[2], oa[3]);
            }
          }
          if (hp == 0) {
#pragma unroll
            for (int i = 0; i < 4; ++i) stg128(g_o + gfr + (i & 1) * 8 * D_ + (i >> 1) * 32, ow[i >> 1][i & 1][0], ow[i >> 1][i & 1][1], ow[i >> 1][i & 1][2], ow[i >> 1][i & 1][3]);
            __syncwarp();
            if (lane == 0) mbar_arrive(BA(B_OH0));
          } else {
#pragma unroll
            for (int i = 0; i < 16; ++i) o1[i >> 2][i & 3] = ow[i >> 3][(i >> 2) & 1][i & 3];
          }
#pragma unroll
          for (int i = 0; i < 16; ++i) of[4 * hp + (i >> 2)][i & 3] = ow[i >> 3][i & 1][(i >> 1) & 3];
          if (!hp) PROFT(tid_ == 128, layer * 16 + 15);
        }
      } else {
        float sc[2] = {rs0 * L2E, rs1 * L2E};
        {
          const uint32_t vb = sb + VB + (rowo >> 1), X0 = (lchk ^ ((lane & 7) >> 1)) << 4;
          const uint32_t pb = sb + PH + (t & 1) * SLOT + (wrow0 + gq) * 128 + ((((t & 1) * 4 + (t & 2)) ^ gq) << 4);
          float kva[20], en[32], mx[2][2], mn[2][2];
#define PV(hp, j) acc[32 * (hp) + (j)]
          auto mm = [&](int hp, int j) {
            const int r = (j >> 1) & 1;
            if (j < 4 && !(j & 1)) { mx[hp][r] = PV(hp, j); mn[hp][r] = PV(hp, j); }
            else { mx[hp][r] = fmaxf(mx[hp][r], PV(hp, j)); mn[hp][r] = fminf(mn[hp][r], PV(hp, j)); }
          };
          auto mmx = [&](int hp) {
#pragma unroll
            for (int r = 0; r < 2; ++r) {
              mx[hp][r] = fmaxf(mx[hp][r], __shfl_xor_sync(0xffffffffu, mx[hp][r], 2)) * -sc[r];
              mn[hp][r] = fmaf(fminf(mn[hp][r], __shfl_xor_sync(0xffffffffu, mn[hp][r], 2)), sc[r], mx[hp][r]);
            }
          };
          auto stage = [&](int hp) {
#pragma unroll
            for (int i = 0; i < 20; ++i) asm volatile("" : "+f"(kva[i]) :: "memory");
            nbar_dyn(3 + wu, 128);
#pragma unroll
            for (int i = 0; i < 4; ++i)
              sts128(sb + VB + hp * SLOT + wg * 8192 + (wq * 128 + i * 32 + lane) * 16,
                     make_uint4(__float_as_uint(kva[4 * i]), __float_as_uint(kva[4 * i + 1]), __float_as_uint(kva[4 * i + 2]), __float_as_uint(kva[4 * i + 3])));
            if (t == 0) sts_f2(sb + SM_AP + ((2 * hp + wg) * 64 + wq * 16 + gq * 2) * 4, kva[16], kva[18]);
            fence_async_smem();
            __syncwarp();
            if (lane == 0) mbar_arrive(BA(B_KVDONE));
          };
          int sn = 4;
#pragma unroll
          for (int j = 0; j < 32; ++j) mm(0, j);
          mmx(0);
#pragma unroll
          for (int hp = 0; hp < 2; ++hp) {
            float sp[2] = {0.f, 0.f}, sm[2] = {0.f, 0.f};
#pragma unroll
            for (int j = 0; j < 32; ++j) {
              const int r = (j >> 1) & 1, ns = hp ? SUBS1 : SUBS;
              if ((j * ns) / 32 != ((j + 1) * ns) / 32) {
                sub(sn++);
                if (hp && sn == 4 + SUBS + 4 + 4 * (XST & 1)) { stage(0); PROFT(tid_ == 128, layer * 16 + 12); }
              }
              const float x = fmaf(PV(hp, j), sc[r], mx[hp][r]);
              PV(hp, j) = ex2(x); en[j] = ex2(mn[hp][r] - x);
              sp[r] += PV(hp, j); sm[r] += en[j];
              if (hp == 0) {
                mm(1, j);
                if ((j & 3) == 0) {
                  const int jp = 8 + (j >> 2);
                  stsm_x4(vb + ((jp - 8) >> 1) * 8192 + (X0 ^ ((jp & 1) << 5)), pack_bf16(acc[8 * jp], acc[8 * jp + 1]), pack_bf16(acc[8 * jp + 2], acc[8 * jp + 3]),
                          pack_bf16(acc[8 * jp + 4], acc[8 * jp + 5]), pack_bf16(acc[8 * jp + 6], acc[8 * jp + 7]));
                }
              }
            }
#pragma unroll
            for (int i = 0; i < 4; ++i) if (XST & (1 << hp)) sub(sn++);
#pragma unroll
            for (int r = 0; r < 2; ++r) {
              sp[r] = rcp(sp[r] + __shfl_xor_sync(0xffffffffu, sp[r], 2)) * (r ? rs1 : rs0);
              sm[r] = rcp(sm[r] + __shfl_xor_sync(0xffffffffu, sm[r], 2)) * (r ? rs1 : rs0);
            }
            if (hp == 0) { mmx(1); mbar_wait(BA(CM + 15), par); }
            else { PROFT(tid_ == 128, layer * 16 + 11); nbar<1, 256>(); }
#pragma unroll
            for (int i = 0; i < 4; ++i) {
              const int r = i & 1, d = 16 * (i >> 1) + 2 * r;
              sts128((pb + r * 1024) ^ ((i >> 1) << 4), make_uint4(pack_bf16(PV(hp, d) * sp[r], PV(hp, d + 1) * sp[r]), pack_bf16(PV(hp, d + 4) * sp[r], PV(hp, d + 5) * sp[r]),
                                                                    pack_bf16(PV(hp, d + 8) * sp[r], PV(hp, d + 9) * sp[r]), pack_bf16(PV(hp, d + 12) * sp[r], PV(hp, d + 13) * sp[r])));
              sts128((pb + r * 1024) ^ ((i >> 1) << 4) ^ 64, make_uint4(pack_bf16(en[d] * sm[r], en[d + 1] * sm[r]), pack_bf16(en[d + 4] * sm[r], en[d + 5] * sm[r]),
                                                                         pack_bf16(en[d + 8] * sm[r], en[d + 9] * sm[r]), pack_bf16(en[d + 12] * sm[r], en[d + 13] * sm[r])));
            }
            fence_async_smem();
            nbar<1, 256>();
            const uint32_t dP = dB0 + (PH >> 4) + wu * 1024;
            const uint32_t dV = (dB0 & 0xFFFFu) + ((VB + hp * SLOT) >> 4) + (((SM_SD - VB - hp * SLOT) >> 4) << 16) + wu * (512u - (512u << 16));
            wgmma_fence();
#pragma unroll
            for (int ks = 0; ks < 8; ++ks) wgmma_n40_tt(kva, D128(dP + ks * 128), desc64(dV + ks * 64, 0x80000020u), ks != 0);
            wgmma_commit();
          }
#pragma unroll
          for (int i = 0; i < 4; ++i) sub(sn++);
          stage(1);
          PROFT(tid_ == 128, layer * 16 + 3);
          rest(sn >> 2, SKA);
          rest_end();
          PROFT(lane == 0 && layer == PL, 200 + cw);
          PROFT(tid_ == 128, layer * 16 + 10);
        }
#define QV(H, i) acc[128 + 16 * (H) + (i)]
        float mx[4][2], mn[4][2];
        uint32_t ph[4][4][4];
        auto mnx = [&](int hp) {
#pragma unroll
          for (int H = 2 * hp; H < 2 * hp + 2; ++H)
#pragma unroll
            for (int r = 0; r < 2; ++r) {
              mx[H][r] = fmaxf(fmaxf(fmaxf(QV(H, 2 * r), QV(H, 2 * r + 1)), fmaxf(QV(H, 4 + 2 * r), QV(H, 5 + 2 * r))),
                               fmaxf(fmaxf(QV(H, 8 + 2 * r), QV(H, 9 + 2 * r)), fmaxf(QV(H, 12 + 2 * r), QV(H, 13 + 2 * r))));
              mn[H][r] = fminf(fminf(fminf(QV(H, 2 * r), QV(H, 2 * r + 1)), fminf(QV(H, 4 + 2 * r), QV(H, 5 + 2 * r))),
                               fminf(fminf(QV(H, 8 + 2 * r), QV(H, 9 + 2 * r)), fminf(QV(H, 12 + 2 * r), QV(H, 13 + 2 * r))));
            }
#pragma unroll
          for (int o = 1; o <= 2; o <<= 1)
#pragma unroll
            for (int H = 2 * hp; H < 2 * hp + 2; ++H)
#pragma unroll
              for (int r = 0; r < 2; ++r) {
                mx[H][r] = fmaxf(mx[H][r], __shfl_xor_sync(0xffffffffu, mx[H][r], o));
                mn[H][r] = fminf(mn[H][r], __shfl_xor_sync(0xffffffffu, mn[H][r], o));
              }
#pragma unroll
          for (int H = 2 * hp; H < 2 * hp + 2; ++H)
#pragma unroll
            for (int r = 0; r < 2; ++r) { mx[H][r] *= -sc[r]; mn[H][r] = fmaf(mn[H][r], sc[r], mx[H][r]); }
        };
        auto fm = [&](int H) {
#pragma unroll
          for (int i = 0; i < 8; ++i) {
            const int r = i & 1;
            const float x0 = fmaf(QV(H, 2 * i), sc[r], mx[H][r]), x1 = fmaf(QV(H, 2 * i + 1), sc[r], mx[H][r]);
            ph[H][i >> 2][i & 3] = pack_bf16(ex2(x0), ex2(x1));
            ph[H][2 + (i >> 2)][i & 3] = pack_bf16(ex2(mn[H][r] - x0), ex2(mn[H][r] - x1));
          }
        };
        auto conv = [&](int hp) {
          mbar_wait(BA(hp ? B_KVF1 : B_KVF), (layer >> 1) & 1);
          PROFT(tid_ == 128, layer * 16 + (hp ? 4 : 5));
          if (hp) nbar_dyn(3 + wu, 128);
#pragma unroll
          for (int h = 0; h < 2; ++h) {
            uint4 u[4];
#pragma unroll
            for (int i = 0; i < 4; ++i) u[i] = lds128(sb + VB + hp * SLOT + h * 8192 + (wq * 128 + i * 32 + lane) * 16);
            const float zz = lds_f(sb + SM_AP + ((2 * hp + h) * 64 + wq * 16 + (lane & 7) * 2 + ((lane >> 3) & 1)) * 4);
            const uint32_t kb_ = sb + PH + wg * SLOT + h * 8192 + (wq * 16 + lrow) * 128;
#pragma unroll
            for (int i = 0; i < 4; i += 2)
              stsm_x4(kb_ + (X ^ (i << 4)),
                      pack_bf16(__uint_as_float(u[i].x), __uint_as_float(u[i].y)), pack_bf16(__uint_as_float(u[i].z), __uint_as_float(u[i].w)),
                      pack_bf16(__uint_as_float(u[i + 1].x), __uint_as_float(u[i + 1].y)), pack_bf16(__uint_as_float(u[i + 1].z), __uint_as_float(u[i + 1].w)));
            const uint32_t z1 = pack_bf16(zz, 1.f);
            if (lane < 16) sts128(kb_ + ((4 ^ (lane & 7)) << 4), make_uint4(z1, z1, z1, z1));
          }
          fence_async_smem();
        };
        mnx(0);
        fm(0);
        if (CV0) conv(0);
        fm(1);
        if (!CV0) conv(0);
#pragma unroll
        for (int hp = 0; hp < 2; ++hp) {
          nbar_dyn(3 + wu, 128);
          float oa[4][20];
          wgmma_fence();
#pragma unroll
          for (int s = 0; s < 2; ++s)
#pragma unroll
            for (int v = 0; v < 4; ++v) {
              const int h = v >> 1, s4 = 2 * (v & 1) + s;
              wgmma_n40_rs(oa[v], ph[2 * hp + h][s4], D128(dB0 + (PH >> 4) + wu * 1024 + h * 512 + (s4 ^ (2 * h)) * 128), s != 0);
            }
          wgmma_commit();
          if (hp == 0) mnx(1);
          wgmma_wait<0>();
#pragma unroll
          for (int i = 0; i < 20; ++i) asm volatile("" : "+f"(oa[0][i]), "+f"(oa[1][i]), "+f"(oa[2][i]), "+f"(oa[3][i]) :: "memory");
          uint32_t ow[2][2][4];
#pragma unroll
          for (int h = 0; h < 2; ++h)
#pragma unroll
            for (int r = 0; r < 2; ++r) {
              const float a = oa[2 * h + 1][17 + 2 * r], b = oa[2 * h][17 + 2 * r];
              const float id = rcp(fmaf(oa[2 * h][16 + 2 * r], a, fmaf(a, 1e-6f, oa[2 * h + 1][16 + 2 * r]) * b));
              const float fa = a * id, fb = b * id;
#pragma unroll
              for (int j = 0; j < 4; ++j)
                ow[h][r][j] = pack_bf16(fmaf(oa[2 * h][4 * j + 2 * r], fa, oa[2 * h + 1][4 * j + 2 * r] * fb),
                                        fmaf(oa[2 * h][4 * j + 2 * r + 1], fa, oa[2 * h + 1][4 * j + 2 * r + 1] * fb));
            }
#pragma unroll
          for (int i = 0; i < 16; ++i) of[4 * hp + (i >> 2)][i & 3] = ow[i >> 3][i & 1][(i >> 1) & 3];
          if (hp == 0) {
#pragma unroll
            for (int i = 0; i < 8; ++i) {
              if (!(i & 1)) stg128(g_o + gfr + ((i >> 1) & 1) * 8 * D_ + (i >> 2) * 32, ow[i >> 2][(i >> 1) & 1][0], ow[i >> 2][(i >> 1) & 1][1], ow[i >> 2][(i >> 1) & 1][2], ow[i >> 2][(i >> 1) & 1][3]);
              const int r = i & 1;
              const float x0 = fmaf(QV(2, 2 * i), sc[r], mx[2][r]), x1 = fmaf(QV(2, 2 * i + 1), sc[r], mx[2][r]);
              ph[2][i >> 2][i & 3] = pack_bf16(ex2v(x0), ex2v(x1));
              ph[2][2 + (i >> 2)][i & 3] = pack_bf16(ex2v(mn[2][r] - x0), ex2v(mn[2][r] - x1));
            }
            __syncwarp();
            if (lane == 0) mbar_arrive(BA(B_OH0));
            PROFT(tid_ == 128 && layer, layer * 16 + 15);
            if (QORD) { fm(3); conv(1); } else { conv(1); fm(3); }
          } else {
#pragma unroll
            for (int i = 0; i < 16; ++i) o1[i >> 2][i & 3] = ow[i >> 3][(i >> 2) & 1][i & 3];
          }
        }
      }
      PROFT(tid_ == 128, layer * 16 + 6);
    }
    {
      PHASE_CTX();
      MMA_CTX();
      auto o1st = [&]() {
#pragma unroll
        for (int i = 0; i < 4; ++i) stg128(g_o + gfr + (i & 1) * 8 * D_ + (2 + (i >> 1)) * 32, o1[i][0], o1[i][1], o1[i][2], o1[i][3]);
        __syncwarp();
        if (lane == 0) { mbar_arrive(BA(B_OH1)); if (!O1P) REL2(B_EF); }
        PROFT(lane == 0 && layer == PL, 208 + cw);
      };
      if (O1P) {
        __syncwarp();
        if (lane == 0) REL2(B_EF);
      } else o1st();
      mbar_wait(BA(FW), par);
      mbar_wait(BA(FW + 1), par);
      if (O1P == 1) o1st();
#pragma unroll
      for (int i = 0; i < 2; ++i) {
        wgmma_fence();
#pragma unroll
        for (int k = 0; k < 4; ++k) {
          if (i + k) wgmma_n128_rs(acc, of[4 * i + k], D128(dB0 + (uint32_t)((WO_B >> (4 * i)) & 15) * 1024 + k * 128), 1);
          else wgmma_n128_rs0(acc, of[0], D128(dB0 + (uint32_t)(WO_B & 15) * 1024));
        }
        wgmma_commit();
        if (O1P == 2 && i == 0) o1st();
      }
      wgmma_wait<1>();
      if (elected) REL2(CW);
      uint64_t ta = WO_A >> 8, tw = WO_B >> 8;
      auto run = [&](int i0, int i1) {
#pragma unroll 1
        for (int i = i0; i < i1; ++i) {
          mbar_wait(BA(FW + i), par);
          PROFL(tid_ == 128 && layer == PL, 160 + i);
          const uint32_t da = dA0 + ((uint32_t)ta & 15) * 1024, db = dB0 + ((uint32_t)tw & 15) * 1024;
          ta >>= 4; tw >>= 4;
          wgmma_fence();
#pragma unroll
          for (int k = 0; k < 4; ++k) wgmma_n128(acc, D128(da + k * 2), D128(db + k * 128), 1);
          wgmma_commit();
          wgmma_wait<1>();
          if (elected) REL2(CW + i - 1);
        }
        ta = WO_A >> (4 * (i1 & 15)); tw = WO_B >> (4 * (i1 & 15));
      };
      run(2, XRAT);
#pragma unroll
      for (int j = 0; j < 8 / XRN; ++j) {
#pragma unroll
        for (int i = j * XRN; i < (j + 1) * XRN; ++i) ldg128((layer ? g_x : c.x0) + gfr + (i & 1) * 8 * D_ + (i >> 1) * 32, xp[i][0], xp[i][1], xp[i][2], xp[i][3]);
        run(XRAT + j, j + 1 < 8 / XRN ? XRAT + j + 1 : 16);
      }
      if (layer == 0) {
#pragma unroll
        for (int o = 1; o <= 2; o <<= 1)
#pragma unroll
          for (int i = 0; i < 16; ++i) {
            const int j = o == 1 ? 2 * (i & 1) : (i & 1);
            uint32_t &a = xp[i >> 1][j], &b = xp[i >> 1][j + o];
            const uint32_t r = __shfl_xor_sync(0xffffffffu, (t & o) ? a : b, o);
            if (t & o) a = r; else b = r;
          }
      }
      wgmma_wait<0>();
#pragma unroll
      for (int i = 128; i < 192; ++i) asm volatile("" : "+f"(acc[i]) :: "memory");
      if (elected) REL2(CW + 15);
      PROFT(lane == 0 && layer == PL, 216 + cw);
      PROFT(tid_ == 128, layer * 16 + 7);
    }
    {
      PHASE_CTX();
#pragma unroll
      for (int i = 0; i < 32; ++i)
        xp[i >> 2][i & 3] = add_bf16x2(xp[i >> 2][i & 3], pack_bf16(acc[128 + 16 * (i >> 3) + 4 * (i & 3) + 2 * ((i >> 2) & 1)], acc[129 + 16 * (i >> 3) + 4 * (i & 3) + 2 * ((i >> 2) & 1)]));
      if (layer == NLAYERS - 1) {
#pragma unroll
        for (int i = 0; i < 8; ++i) stsm_x4(sb + (XS + (i >> 2)) * SLOT + (Y ^ ((i & 2) << 5)) + (i & 1) * 1024, xp[i][0], xp[i][1], xp[i][2], xp[i][3]);
        __syncwarp();
        slab_out_half(sb + XS * SLOT, c.out + (size_t)m0 * D_ + g * 128, wrow0, lane);
        slab_out_half(sb + (XS + 1) * SLOT, c.out + (size_t)m0 * D_ + g * 128 + 64, wrow0, lane);
        PROFT(tid_ == 128, layer * 16 + 24);
        break;
      }
#pragma unroll
      for (int i = 0; i < 4; ++i) stg128(g_x + gfr + (i & 1) * 8 * D_ + (i >> 1) * 32, xp[i][0], xp[i][1], xp[i][2], xp[i][3]);
      __syncwarp();
      if (lane == 0) mbar_arrive(BA(B_XH0));
#pragma unroll
      for (int i = 0; i < 16; ++i) xf[i >> 2][i & 3] = xp[2 * (i >> 3) + (i & 1)][(i >> 1) & 3];
      PROFT(tid_ == 128, layer * 16 + 24);
    }
  }
}

__device__ __forceinline__ uint64_t k_order(int o) {
  const uint32_t lo = (1u << (4 * o)) - 1u, h0 = (0xECA86420u & lo) | ((0xECA86420u >> 4) & ~lo);
  return (uint64_t)(2 * o) | ((uint64_t)(2 * o + 1) << 4) | ((uint64_t)(h0 & 0xFFFFFFFu) << 8) | ((uint64_t)((h0 & 0xFFFFFFFu) | 0x1111111u) << 36);
}

__global__ void __cluster_dims__(2, 1, 1) __launch_bounds__(384, 1)
mega_kernel(const __grid_constant__ Maps maps, const __grid_constant__ Ctx c, const bf16* __restrict__ wA, const bf16* __restrict__ wB,
            const bf16* __restrict__ woA, const bf16* __restrict__ woB) {
  if (blockIdx.x - c.boff >= 128u) {
    const unsigned int epoch = ld_relaxed(&g_epoch);
    const int e = (blockIdx.x - c.boff) & 3, tid = threadIdx.x;
    float s[8] = {0.f, 0.f, 0.f, 0.f, 0.f, 0.f, 0.f, 0.f};
    const uint32_t sb = smem_u32(smem_raw), bar = sb + SM_BAR;
    auto issue = [&](int i) {
      mbar_expect_tx(BA(i & 3), 49152);
      bulk_load(sb + (i & 3) * 49152, wB + (size_t)e * 256 * 3072 + i * 24576, 49152, BA(i & 3));
    };
    if (tid == 0) {
#pragma unroll 1
      for (int i = 0; i < 4; ++i) {
        mbar_init(BA(i), 1);
        fence_async_smem();
        issue(i);
      }
    }
    __syncthreads();
#pragma unroll 1
    for (int i = 0; i < 32; ++i) {
      mbar_wait(BA(i & 3), (i >> 2) & 1);
#pragma unroll 2
      for (int r = 0; r < 8; ++r) {
        const uint4 v = lds128(sb + (i & 3) * 49152 + r * 6144 + tid * 16);
        s[0] += bf_lo(v.x); s[1] += bf_hi(v.x); s[2] += bf_lo(v.y); s[3] += bf_hi(v.y);
        s[4] += bf_lo(v.z); s[5] += bf_hi(v.z); s[6] += bf_lo(v.w); s[7] += bf_hi(v.w);
      }
      __syncthreads();
      if (tid == 0 && i < 28) issue(i + 4);
    }
    float* cd = g_cs + (epoch & 1) * 6144 + 3072 + ((tid >> 4) & 7) * 384 + (tid < 128 ? 256 : (tid >> 7) * 128 - 128) + (tid & 15) * 8;
    red_add4(cd, s[0], s[1], s[2], s[3]);
    red_add4(cd + 4, s[4], s[5], s[6], s[7]);
    __syncthreads();
    if (tid == 0) flag_add(&g_csflag[8].v);
    const int op = (epoch & 1) ^ 1;
    float4* kz = reinterpret_cast<float4*>(g_kv + (size_t)op * (2 * 8 * 8448)) + e * 8448;
#pragma unroll 1
    for (int i = tid; i < 8448; i += 384) kz[i] = make_float4(0.f, 0.f, 0.f, 0.f);
    reinterpret_cast<float4*>(g_cs + op * 6144)[e * 384 + tid] = make_float4(0.f, 0.f, 0.f, 0.f);
#pragma unroll 1
    for (int i = tid; i < 1024; i += 384) reinterpret_cast<float4*>(g_stats + (op * 4 + e) * S_)[i] = make_float4(0.f, 0.f, 0.f, 0.f);
    return;
  }
  const int warp = __shfl_sync(0xffffffffu, threadIdx.x >> 5, 0), lane = threadIdx.x & 31;
  if (smem_u32(smem_raw) != SB0 + ((blockIdx.x & 1) << 24)) __trap();
  {
  const int cid = (blockIdx.x - c.boff) >> 1, u7 = ((cid - 36) * 37) >> 8, cr = blockIdx.x & 1;
  const int g = cid < 4 ? 4 + cid : cid < 36 ? (cid - 4) >> 3 : 4 + u7, rb = (cid < 4 ? 0 : cid < 36 ? (cid - 4) & 7 : cid - 35 - 7 * u7) * 2 + cr, m0 = rb * 128;
  const uint32_t sb = SB0 + (cr << 24), bar = sb + SM_BAR;
  PROFT(lane == 0 && (warp == 0 || warp == 4), 224 + (warp >> 2) * 8);
  uint32_t cx = 0;
  if (warp == 2) {
    if (lane < NMAP) asm volatile("prefetch.tensormap [%0];" ::"l"(&maps.m[lane]) : "memory");
    if (lane == 31) asm volatile("prefetch.global.L2 [%0];" ::"l"(&g_epoch));
  } else if (warp == 3) {
    cx = c_map[cid] + c_wop[lane] + c_wop[NWOP - lane] + c_aop[lane] + c_aop[NAOP - lane] + (uint32_t)(uintptr_t)g_x;
  } else if (warp >= 4 && warp < 8) {
    const int i = threadIdx.x - 128;
    asm volatile("prefetch.global.L2 [%0];" ::"l"(wA + (size_t)((rb & ~1) * 64 + cr * 32 + ((i >> 1) & 31)) * 3072 + (i >> 6) * 1024 + g * 128 + (i & 1) * 64));
  }
  if (warp < 2) {
    const int s = warp, kb = (rb & ~1) + s;
    if (lane == 0) {
      mbar_init(BA(FM + s), 1u);
      mbar_init(BA(B_RAW + warp), 1u);
      if (warp) mbar_init(BA(B_X0), 1u);
      asm volatile("fence.mbarrier_init.release.cluster;" ::: "memory");
    }
    __syncwarp();
    if (warp == 0) tma_2d_e(sb + SM_SD, &maps.m[MAP_PHI], 0, g * 128, BA(B_RAW));
    else if (W1DL) __nanosleep(W1DL);
#pragma unroll
    for (int j = 0; j < 6; ++j)
      tma_5d_e(sb + (j < 2 ? 2 * s : j < 4 ? 9 + s : 2 * s + 1) * SLOT + (j & 1) * 8192, &maps.m[MAP_WA], (j < 2 ? 1024 : j < 4 ? 0 : 2048) + g * 128 + (j & 1) * 64, 2 * kb,
               BA(j < 4 ? B_RAW + warp : FM + s));
    tma_2d_e(sb + (XS + s) * SLOT, &maps.m[MAP_X0], kb * 64, m0, BA(FM + s));
    expect_tx_e(BA(B_RAW + warp), warp ? 32768 : 32768 + 8192);
    expect_tx_e(BA(FM + s), 32768);
    if (X0AT == 0 && warp == 1) {
      tma_2d_e(sb + 11 * SLOT, &maps.m[MAP_X0], g * 128, m0, BA(B_X0));
      tma_2d_e(sb + 12 * SLOT, &maps.m[MAP_X0], g * 128 + 64, m0, BA(B_X0));
      expect_tx_e(BA(B_X0), 32768);
    }
  } else if (warp >= 4 && lane == 0) {
#pragma unroll 1
    for (int i = 2 + (warp - 4) * 13; i < 15 + (warp - 4) * 13; ++i)
      mbar_init(BA(i), 1u << ((i < CM ? 0u : i < B_EF ? 2u : (uint32_t)(BAR_LG >> (4 * ((i - B_EF) & 15)))) & 7u));
    asm volatile("fence.mbarrier_init.release.cluster;" ::: "memory");
  }
  __syncwarp();
  asm volatile("barrier.cluster.arrive.relaxed.aligned;" ::: "memory");
  if (threadIdx.x == 96 + c.zero) sts_f(sb + SM_EPOCH + 4, __uint_as_float(cx));
  PROFT(lane == 0 && (warp == 0 || warp == 4), 225 + (warp >> 2) * 8);
  __syncwarp();
  PROFT(lane == 0 && (warp == 0 || warp == 4), 226 + (warp >> 2) * 8);
  }

  if (warp < 4) {
    asm volatile("setmaxnreg.dec.sync.aligned.u32 40;");
    PROFT(threadIdx.x == 0, 227);
    cluster_wait();
    PROFT(threadIdx.x == 0, 228);
    if (warp == 0 || warp == 3) {
    if (warp == 0) {
      BLK_CTX();
      const unsigned int epoch = __shfl_sync(0xffffffffu, ld_relaxed(&g_epoch), 0), xbase = epoch * NLAYERS;
      (void)xbase;
      const uint64_t ordg = k_order(g);
      if (X0AT) {
        mbar_wait_u(BA(B_RAW + X0AT - 1), 0);
        tma_2d_e(sb + 11 * SLOT, &maps.m[MAP_X0], g * 128, m0, BA(B_X0));
        tma_2d_e(sb + 12 * SLOT, &maps.m[MAP_X0], g * 128 + 64, m0, BA(B_X0));
        expect_tx_e(BA(B_X0), 32768);
      }
#pragma unroll 1
      for (int lp = 0; lp < 2 * NLAYERS; ++lp) {
        const int layer = lp >> 1, n1 = (lp & 1) ? NAOP : NAOP - 14;
        int n = (lp & 1) ? NAOP - 14 : 0;
        const uint64_t ord = lp ? ordg : k_order(rb >> 1);
        uint32_t ready = lp ? 0u : 0xFFFFu, nop = c_aop[n];
        const unsigned int* fl = ((lp & 1) ? g_of : g_xf) + rb * 32;
        const CUtensorMap* tm = &maps.m[(lp & 1) ? MAP_O : lp ? MAP_X : MAP_X0];
        const uint32_t skip = layer ? 1u << 25 : 9u << 22;
#pragma unroll 1
        for (; n < n1; ++n) {
          const uint32_t op = nop;
          nop = c_aop[n + 1];
          const uint32_t kb = (uint32_t)(ord >> ((op >> 2) & 60)) & 15;
          uint32_t dst = sb + (op & 15) * SLOT, kc = kb * 64, fb = bar + ((op >> 5) & 0x3F8), need = ~ready & (1u << kb);
          asm volatile("" : "+r"(dst), "+r"(kc), "+r"(fb), "+r"(need));
          if (!(op & skip)) mbar_wait_u(bar + ((op >> 12) & 0x3F8), (layer ^ (op >> 22)) & 1);
          if (need) {
            PROFT(lane == 0 && (n == 0 || n == NAOP - 14), 64 + layer * 16 + (n ? 2 : 0));
            src_wait<0>(fl, xbase + layer + 1, need, ready, lane);
            fence_async_all();
          }
          tma_2d_e(dst, tm, kc, m0, fb);
          PROFT(lane == 0 && (n == 0 || n == NAOP - 14), 64 + layer * 16 + (n ? 3 : 1));
          PROFL(lane == 0 && layer == PL && n >= NAOP - 14, 178 + n - (NAOP - 14));
          PROFL(lane == 0 && layer == PL + 1 && n < 4, 242 + n);
        }
      }
    } else {
      BLK_CTX();
      const unsigned int epoch = __shfl_sync(0xffffffffu, ld_relaxed(&g_epoch), 0), xbase = epoch * NLAYERS;
      (void)xbase;
      const uint64_t ordg = k_order(g);
#pragma unroll 1
      for (int layer = 0; layer < NLAYERS; ++layer) {
        const uint64_t ordq = layer ? ordg : k_order(rb >> 1);
        uint32_t ready = layer ? 0xFFFFu : 0u, nop = c_wop[0];
        const CUtensorMap* tq = &maps.m[(layer & 1) ? MAP_WB : MAP_WF];
        const CUtensorMap* tk = &maps.m[(layer & 1) ? MAP_WB : cr ? MAP_WA : MAP_WF];
        const uint32_t skip = layer ? 1u << 25 : 9u << 22, pm = layer ? 0xE0u : 0u;
        int n = 0;
#pragma unroll 1
        for (; n < NWOP - 16; ++n) {
          const uint32_t op = nop;
          nop = c_wop[n + 1];
          const uint32_t isq = (op >> 23) & 1, fb = bar + ((op >> 5) & 0x3F8);
          const uint32_t kb = (uint32_t)(ordq >> ((op >> 2) & 60)) & 15;
          const CUtensorMap* tm = (isq ? tq : tk) + ((op & pm) ? 1 : 0);
          const uint32_t dst = sb + (op & 15) * SLOT + cr * (isq ? 8192 : SLOT);
          const int col = g * 128 + (isq ? cr * 64 : 1024 + cr * 1024);
          if (layer == 0) {
            if ((op & 0x7E00) == 0) continue;
            const uint32_t need = ((isq || !cr) ? 1u << kb : 0u) | (((op >> 22) & 1) ? 0u : (((op >> 15) & 127) == CM ? 1u : 3u) << (rb & ~1));
            if ((ready & need) != need) {
              src_wait<0>(g_wff + g * 32, epoch + 1, need, ready, lane);
              fence_async_all();
            }
            if ((op & 15) >= 11) mbar_wait_u(BA(B_XT), 0);
          }
          wait_tma_5d_mc(!(op & skip), bar + ((op >> 12) & 0x3F8), (layer ^ (op >> 22)) & 1, dst, tm, col, 2 * kb, fb);
          if (!isq) tma_5d_mc_e(dst + 8192, tm, col + 64, 2 * kb, fb);
          if (op >> 26) expect_tx_e(fb, (op >> 26) * 8192);
          PROFL(lane == 0 && layer == PL + 1 && n < 16, 128 + n);
        }
        const CUtensorMap* to = &maps.m[(layer & 1) ? MAP_WOB : MAP_WOA];
#pragma unroll 1
        for (; n < NWOP; ++n) {
          const uint32_t op = nop;
          nop = c_wop[n + 1];
          const uint32_t fb = bar + ((op >> 5) & 0x3F8), kb = (uint32_t)(ordg >> ((op >> 2) & 60)) & 15;
          wait_tma_5d_mc(!((op >> 25) & 1), bar + ((op >> 12) & 0x3F8), layer & 1, sb + (op & 15) * SLOT + cr * 8192, to + ((op & 0xE0) ? 1 : 0), g * 128 + cr * 64, 2 * kb, fb);
          expect_tx_e(fb, (op >> 26) * 8192);
          PROFL(lane == 0 && layer == PL, 144 + ((op >> 8) & 127) - FW);
        }
      }
    }
    } else if (warp == 1) {
      BLK_CTX();
      const unsigned int epoch = __shfl_sync(0xffffffffu, ld_relaxed(&g_epoch), 0), xbase = epoch * NLAYERS;
      (void)xbase;
      if (lane == 0) {
        mbar_wait(BA(B_WFD), 0);
        PROFT(true, 229);
#pragma unroll 1
        for (int j = 0; j < 4; ++j) tma_store_5d(&maps.m[MAP_WF], sb + (j < 2 ? 2 * cr : 9 + cr) * SLOT + (j & 1) * 8192, (j < 2 ? 1024 : 0) + g * 128 + (j & 1) * 64, 2 * rb);
        bulk_commit();
        bulk_wait0();
        PROFT(true, 230);
        fence_async_all();
        flag_set(g_wff + g * 32 + rb, epoch + 1);
        PROFT(true, 64 + 13);
#pragma unroll 1
        for (int e = 0; e < NLAYERS; ++e) {
          BLK_CTX();
          if (e > 0) {
            mbar_wait(BA(B_XH0), (e - 1) & 1);
            PROFT(e == PL + 1, 240);
            flag_set(g_xf + rb * 32 + 2 * g, xbase + e + 1);
            PROFT(e == PL + 1, 241);
          }
          mbar_wait(BA(B_XDONE), e & 1);
          PROFT(true, 64 + e * 16 + 4);
          flag_set(g_xf + rb * 32 + 2 * g + 1, xbase + e + 1);
          if (e == 0) {
            flag_add(&g_csflag[g].v);
            l2_prefetch(wB + (size_t)bid_ * 24576, 49152);
            l2_prefetch(woA + (size_t)bid_ * 8192, 16384);
            l2_prefetch(woB + (size_t)bid_ * 8192, 16384);
          }
          PROFT(true, 64 + e * 16 + 7);
          if ((e & 1) == 0) {
            float* kvl = g_kv + ((size_t)((epoch & 1) * 2 + (e >> 1)) * 8 + g) * 8448;
#pragma unroll 1
            for (int hp = 0; hp < 2; ++hp) {
              mbar_wait(BA(B_KVDONE), hp);
              bulk_red_add(kvl + 8192 + hp * 128, sb + SM_AP + hp * 512, 512);
#pragma unroll 1
              for (int i = 0; i < NCH; ++i) {
                const int ch = hp * NCH + ((i + rb * NCH / 16) & (NCH - 1));
                bulk_red_add(kvl + ch * (4096 / NCH), sb + VB + ch * (16384 / NCH), 16384 / NCH);
                bulk_commit();
                asm volatile("cp.async.bulk.wait_group %0;" :: "n"(CHW) : "memory");
              }
              bulk_wait0();
              PROFT(true, 64 + e * 16 + (hp ? 10 : 6));
              fence_async_all();
              flag_add(&g_kvflag[hp * 8 + g].v);
              PROFT(e > 0 && hp, 64 + e * 16 + 8);
            }
          }
          if (e & 1) {
            mbar_wait(BA(B_OF0), (e >> 1) & 1);
            flag_set(g_hf + rb * 32 + g, xbase + e + 1);
            if (rb) flag_wait(g_hf + (rb - 1) * 32 + g, xbase + e + 1);
            fence_async_all();
            mbar_expect_tx(BA(B_HALO), 8192);
            bulk_load(sb + SM_SD, g_halo + (size_t)(((e >> 1) * 17 + rb) * 8 + g) * 2048, 8192, BA(B_HALO));
            PROFT(true, 64 + e * 16 + 15);
          }
          mbar_wait(BA(B_OH0), e & 1);
          PROFT(e > 0, 64 + e * 16 + 13);
          flag_set(g_of + rb * 32 + 2 * g, xbase + e + 1);
          PROFT(true, 64 + e * 16 + 9);
          mbar_wait(BA(B_OH1), e & 1);
          PROFT(true, 64 + e * 16 + 5);
          flag_set(g_of + rb * 32 + 2 * g + 1, xbase + e + 1);
          PROFT(true, 64 + e * 16 + 11);
        }
        if (bid_ == 0) g_epoch = epoch + 1;
      }
    } else {
      BLK_CTX();
      const unsigned int epoch = __shfl_sync(0xffffffffu, ld_relaxed(&g_epoch), 0), xbase = epoch * NLAYERS;
      (void)xbase;
      if (lane < 16) sts_f(sb + SM_RS + lane * 4, 0.f);
#pragma unroll 1
      for (int layer = 0; layer < NLAYERS; ++layer) {
#define HLP_CTX() BLK_CTX(); int lane = threadIdx.x & 31; asm volatile("" : "+r"(lane)); const bool isB = layer & 1, hal = isB && rb > 0; (void)hal;
#pragma unroll 1
        for (int ph = 0; ph < 2; ++ph) {
          HLP_CTX();
          if (ph == (layer == 0)) {
            const float* cs = g_cs + (epoch & 1) * 6144 + g * 384;
            if (layer) mbar_wait_u(BA(CT), (layer - 1) & 1);
            if (layer < 2) {
              if (lane == 0) flag_wait_slow(&g_csflag[isB ? 8 : g].v, isB ? epoch * 4u + 4u : epoch * 16u + 16u);
              __syncwarp();
            }
#pragma unroll 1
            for (int i0 = 0; i0 < 12; i0 += 4) {
              float a[4];
#pragma unroll
              for (int i = 0; i < 4; ++i) a[i] = __ldcg(cs + isB * 3072 + (i0 + i) * 32 + lane);
#pragma unroll
              for (int i = 0; i < 4; ++i) {
                const float c1 = bf16r(a[i]), c2 = bf16r(a[i] - c1), c3 = (a[i] - c1) - c2;
                sts128(sb + SM_BP + ((i0 + i) * 32 + lane) * 16, make_uint4(pack_bf16(c1, c2), pack_bf16(c3, 0.f), 0u, 0u));
              }
            }
          } else {
            uint32_t rdy = 0u;
            src_wait<128>(g_xf + rb * 32, xbase + layer + 1, 0xAAAAu, rdy, lane);
            rdy = 0u;
            if (hal) src_wait<128>(g_xf + (rb - 1) * 32, xbase + layer + 1, 0xAAAAu, rdy, lane);
            const float2* sp = g_stats + ((epoch & 1) * 4 + layer) * S_ + m0 + lane;
            float2 u[5];
#pragma unroll
            for (int i = 0; i < 4; ++i) u[i] = __ldcg(sp + i * 32);
            u[4] = __ldcg(sp - (hal ? 16 : 0));
#pragma unroll 1
            for (int i = 0; i < 5; ++i) {
              const float mean = u[0].x * (1.f / D_);
              const float var = fmaxf(fmaf(-u[0].x, mean, u[0].y) * (1.f / D_), 0.f);
              const float sd = bf16r(sqrtf(bf16r(bf16r(var) + 1e-5f)));
              const int R = i * 32 + lane;
              if (i < 4) {
                const float hm = -0.5f * bf16r(mean);
                if (!isB) sts128(sb + SM_SD + R * 64 + ((R >> 1) & 3) * 16, make_uint4(__float_as_uint(sd) >> 16, 0u, 0u, 0u));
                sts128(sb + SM_AP + R * 16, make_uint4(pack_bf16(hm, hm), pack_bf16(hm, 0.f), 0u, 0u));
              }
              if (i < 4 || (hal && lane < 16)) sts_f(sb + SM_RS + (i < 4 ? 16 + R : lane) * 4, __fdividef(1.f, sd));
#pragma unroll
              for (int j = 0; j < 4; ++j) u[j] = u[j + 1];
            }
            PROFT(lane == 0, 64 + layer * 16 + 12);
          }
        }
        HLP_CTX();
        fence_async_smem();
        __syncwarp();
        if (lane == 0) mbar_arrive(BA(B_STAT));
        PROFT(lane == 0, 64 + layer * 16 + 14);
        if (!isB && lane == 0) {
#pragma unroll 1
          for (int hp = 0; hp < 2; ++hp) {
            mbar_wait(BA(B_KVDONE), hp);
            flag_wait(&g_kvflag[hp * 8 + g].v, epoch * (16u * ((NLAYERS + 1) / 2)) + 16u * ((layer >> 1) + 1));
            const float* kvl = g_kv + ((size_t)((epoch & 1) * 2 + (layer >> 1)) * 8 + g) * 8448;
            const uint32_t kb = BA(hp ? B_KVF1 : B_KVF);
            fence_async_all();
            mbar_expect_tx(kb, 16384 + 512);
            bulk_load(sb + VB + hp * SLOT, kvl + hp * 4096, 16384, kb);
            bulk_load(sb + SM_AP + hp * 512, kvl + 8192 + hp * 128, 512, kb);
            PROFT(hp == 0, 64 + layer * 16 + 15);
          }
        }
        __syncwarp();
      }
    }
    __syncwarp();
    asm volatile("barrier.cluster.arrive.relaxed.aligned;" ::: "memory");
    cluster_wait();
  } else {
    asm volatile("setmaxnreg.inc.sync.aligned.u32 232;");
    PROFT(threadIdx.x == 128, 235);
    cluster_wait();
    PROFT(threadIdx.x == 128, 236);
    consumer(c);
    asm volatile("bar.warp.sync 0xffffffff;\nbarrier.cluster.arrive.relaxed.aligned;\nbarrier.cluster.wait.aligned;\n" ::: "memory");
  }
}

typedef CUresult (*PFN_encodeTiled)(CUtensorMap*, CUtensorMapDataType, cuuint32_t, void*, const cuuint64_t*, const cuuint64_t*,
                                    const cuuint32_t*, const cuuint32_t*, CUtensorMapInterleave, CUtensorMapSwizzle,
                                    CUtensorMapL2promotion, CUtensorMapFloatOOBfill);

static void make_map2(PFN_encodeTiled enc, CUtensorMap* m, const void* ptr, uint64_t cols, uint64_t rows, uint32_t box_c, uint32_t box_r) {
  cuuint64_t dims[2] = {cols, rows};
  cuuint64_t strides[1] = {cols * 2};
  cuuint32_t box[2] = {box_c, box_r};
  cuuint32_t es[2] = {1, 1};
  CUresult r = enc(m, CU_TENSOR_MAP_DATA_TYPE_BFLOAT16, 2, const_cast<void*>(ptr), dims, strides, box, es, CU_TENSOR_MAP_INTERLEAVE_NONE,
                   box_c == 64 ? CU_TENSOR_MAP_SWIZZLE_128B : CU_TENSOR_MAP_SWIZZLE_64B, CU_TENSOR_MAP_L2_PROMOTION_L2_256B, CU_TENSOR_MAP_FLOAT_OOB_FILL_NONE);
  (void)r;
}
static void make_map5(PFN_encodeTiled enc, CUtensorMap* m, const void* ptr, uint64_t cols) {
  for (int p = 0; p < 2; ++p) {
    cuuint64_t dims[5] = {cols, 2, 4, 4, 32};
    cuuint64_t strides[4] = {cols * 2, cols * (p ? 16 : 4), cols * (p ? 4 : 16), cols * 64};
    cuuint32_t box[5] = {64, 2, 4, 4, 2};
    cuuint32_t es[5] = {1, 1, 1, 1, 1};
    CUresult r = enc(m + p, CU_TENSOR_MAP_DATA_TYPE_BFLOAT16, 5, const_cast<void*>(ptr), dims, strides, box, es, CU_TENSOR_MAP_INTERLEAVE_NONE,
                     CU_TENSOR_MAP_SWIZZLE_128B, CU_TENSOR_MAP_L2_PROMOTION_L2_256B, CU_TENSOR_MAP_FLOAT_OOB_FILL_NONE);
    (void)r;
  }
}

extern "C" void kernel_launch(void* const* d_in, const int* in_sizes, int n_in, void* d_out, int out_size) {
  const bf16* A_x = (const bf16*)d_in[0];
  const bf16* A_wqkv = (const bf16*)d_in[1];
  const bf16* A_wphi = (const bf16*)d_in[2];
  const bf16* A_wo = (const bf16*)d_in[3];
  const bf16* B_wqkv = (const bf16*)d_in[5];
  const bf16* B_wo = (const bf16*)d_in[6];
  bf16* out = (bf16*)d_out;

  static PFN_encodeTiled enc = nullptr;
  static bf16 *p_x, *p_o, *p_wf;
  static uint32_t boff;
  if (!enc) {
    void* fn = nullptr; cudaDriverEntryPointQueryResult qr;
    cudaGetDriverEntryPoint("cuTensorMapEncodeTiled", &fn, cudaEnableDefault, &qr);
    enc = (PFN_encodeTiled)fn;
    cudaGetSymbolAddress((void**)&p_x, g_x);
    cudaGetSymbolAddress((void**)&p_o, g_o);
    cudaGetSymbolAddress((void**)&p_wf, g_wf);
    cudaFuncSetAttribute(mega_kernel, cudaFuncAttributeMaxDynamicSharedMemorySize, SM_TOTAL);
    cudaLaunchConfig_t cfg = {};
    cudaLaunchAttribute at; at.id = cudaLaunchAttributeClusterDimension; at.val.clusterDim.x = 2; at.val.clusterDim.y = 1; at.val.clusterDim.z = 1;
    cfg.gridDim = dim3(132); cfg.blockDim = dim3(384); cfg.dynamicSmemBytes = SM_TOTAL; cfg.attrs = &at; cfg.numAttrs = 1;
    int nc = 0;
    if (cudaOccupancyMaxActiveClusters(&nc, mega_kernel, &cfg) != cudaSuccess) { nc = 0; (void)cudaGetLastError(); }
    boff = nc >= 66 ? 0u : 4u;
  }
  Maps maps;
  make_map5(enc, &maps.m[MAP_WF], p_wf, 2048);
  make_map5(enc, &maps.m[MAP_WA], A_wqkv, 3072);
  make_map5(enc, &maps.m[MAP_WB], B_wqkv, 3072);
  make_map5(enc, &maps.m[MAP_WOA], A_wo, 1024);
  make_map5(enc, &maps.m[MAP_WOB], B_wo, 1024);
  make_map2(enc, &maps.m[MAP_X0], A_x, 1024, 2048, 64, 128);
  make_map2(enc, &maps.m[MAP_X], p_x, 1024, 2048, 64, 128);
  make_map2(enc, &maps.m[MAP_O], p_o, 1024, 2048, 64, 128);
  make_map2(enc, &maps.m[MAP_PHI], A_wphi, 32, 1024, 32, 128);
  Ctx c; c.zero = 0u; c.boff = boff; c.x0 = A_x; c.out = out;
  mega_kernel<<<132, 384, SM_TOTAL, cudaStreamPerThread>>>(maps, c, A_wqkv, B_wqkv, A_wo, B_wo);
}
```

```cpp
#include <cuda_runtime.h>
#include <cuda_bf16.h>
#include <cuda.h>
#include <stdint.h>

typedef __nv_bfloat16 bf16;

constexpr int S_ = 2048, D_ = 1024;

struct __align__(128) Flag { unsigned int v; unsigned int pad[31]; };
__device__ __align__(1024) bf16 g_x[S_ * D_];
__device__ __align__(1024) bf16 g_o[S_ * D_];
__device__ __align__(1024) uint32_t g_halo[2 * 17 * 8 * 2048];
__device__ __align__(1024) float g_kv[2 * 2 * 8 * 8448];
__device__ __align__(1024) float2 g_stats[2 * 4 * S_];
__device__ __align__(1024) float g_cs[2 * 2 * 3072];
__device__ __align__(1024) bf16 g_wf[D_ * 2048];
__device__ Flag g_kvflag[16], g_csflag[13];
__device__ __align__(128) unsigned int g_xf[16 * 32], g_of[16 * 32];
__device__ __align__(128) unsigned int g_hf[16 * 32];
__device__ __align__(128) unsigned int g_wff[8 * 32];
__device__ unsigned int g_epoch, g_err;
#define PROFT(cond, idx) asm volatile("" ::: "memory")

__device__ __forceinline__ uint32_t smem_u32(const void* p) { return (uint32_t)__cvta_generic_to_shared(p); }
__device__ __forceinline__ void mbar_init(uint32_t bar, uint32_t count) {
  asm volatile("mbarrier.init.shared::cta.b64 [%0], %1;" ::"r"(bar), "r"(count) : "memory");
}
__device__ __forceinline__ void mbar_expect_tx(uint32_t bar, uint32_t bytes) {
  asm volatile("mbarrier.arrive.expect_tx.shared::cta.b64 _, [%0], %1;" ::"r"(bar), "r"(bytes) : "memory");
}
__device__ __forceinline__ void mbar_arrive(uint32_t bar) {
  asm volatile("mbarrier.arrive.shared::cta.b64 _, [%0];" ::"r"(bar) : "memory");
}
__device__ __forceinline__ bool mbar_try_wait(uint32_t bar, uint32_t parity) {
  uint32_t ok;
  asm volatile("{\n.reg .pred p;\nmbarrier.try_wait.parity.shared::cta.b64 p, [%1], %2;\nselp.b32 %0, 1, 0, p;\n}\n"
               : "=r"(ok) : "r"(bar), "r"(parity) : "memory");
  return ok != 0;
}
__device__ __forceinline__ uint64_t gtimer() {
  uint64_t t; asm volatile("mov.u64 %0, %globaltimer;" : "=l"(t)); return t;
}
__device__ __forceinline__ void mbar_wait(uint32_t bar, uint32_t parity) {
  uint32_t n = 0;
  bool ok;
#pragma unroll 1
  do { ++n; ok = mbar_try_wait(bar, parity); } while (!ok && n < (1u << 22));
}
__device__ __forceinline__ unsigned int ld_acquire(const unsigned int* p) {
  unsigned int v; asm volatile("ld.acquire.gpu.global.u32 %0, [%1];" : "=r"(v) : "l"(p) : "memory"); return v;
}
__device__ __forceinline__ void flag_add(unsigned int* p) {
  asm volatile("red.release.gpu.global.add.u32 [%0], 1;" ::"l"(p) : "memory");
}
__device__ __forceinline__ void flag_set(unsigned int* p, unsigned int v) {
  asm volatile("st.release.gpu.global.u32 [%0], %1;" ::"l"(p), "r"(v) : "memory");
}
template <int SLEEP>
__device__ __forceinline__ void src_wait(const unsigned int* f, unsigned int target, uint32_t need, uint32_t& ready, int lane) {
  uint32_t n = 0;
#pragma unroll 1
  while ((ready & need) != need) {
    const unsigned int v = ld_acquire(f + (lane & 15));
    ready = __ballot_sync(0xffffffffu, (int)(v - target) >= 0);
    if (SLEEP) { if ((ready & need) != need) __nanosleep(SLEEP); }
    if (++n > (1u << 20)) break;
  }
  __syncwarp();
}
__device__ __forceinline__ unsigned int ld_relaxed(const unsigned int* p);
__device__ __forceinline__ unsigned int ld_relaxed(const unsigned int* p) {
  unsigned int v; asm volatile("ld.relaxed.gpu.global.u32 %0, [%1];" : "=r"(v) : "l"(p) : "memory"); return v;
}
template <int SLEEP>
__device__ __forceinline__ void flag_wait_t(const unsigned int* p, unsigned int target) {
  uint32_t n = 0;
#pragma unroll 1
  while ((int)(ld_acquire(p) - target) < 0) {
    if (SLEEP) __nanosleep(SLEEP);
    if (++n > (1u << 20)) break;
  }
}
__device__ __forceinline__ void flag_wait(const unsigned int* p, unsigned int target) { flag_wait_t<0>(p, target); }
__device__ __forceinline__ void flag_wait_slow(const unsigned int* p, unsigned int target) { flag_wait_t<256>(p, target); }
__device__ __forceinline__ void mbar_wait_u(uint32_t bar, uint32_t parity) {
  uint32_t n = 0;
#pragma unroll 1
  while (!__all_sync(0xffffffffu, mbar_try_wait(bar, parity))) {
    if (++n > (1u << 22)) break;
  }
}
__device__ __forceinline__ void expect_tx_e(uint32_t bar, uint32_t bytes) {
  asm volatile("{\n.reg .pred p;\nelect.sync _|p, 0xffffffff;\n@p mbarrier.arrive.expect_tx.shared::cta.b64 _, [%0], %1;\n}\n" ::"r"(bar), "r"(bytes) : "memory");
}
__device__ __forceinline__ void tma_2d_e(uint32_t dst, const CUtensorMap* tm, int c0, int c1, uint32_t bar) {
  asm volatile("{\n.reg .pred p;\nelect.sync _|p, 0xffffffff;\n"
               "@p cp.async.bulk.tensor.2d.shared::cluster.global.mbarrier::complete_tx::bytes [%0], [%1, {%2, %3}], [%4];\n}\n"
               ::"r"(dst), "l"(tm), "r"(c0), "r"(c1), "r"(bar) : "memory");
}
__device__ __forceinline__ void tma_5d_e(uint32_t dst, const CUtensorMap* tm, int c0, int c4, uint32_t bar) {
  asm volatile("{\n.reg .pred p;\nelect.sync _|p, 0xffffffff;\n"
               "@p cp.async.bulk.tensor.5d.shared::cluster.global.mbarrier::complete_tx::bytes [%0], [%1, {%2, %5, %5, %5, %3}], [%4];\n}\n"
               ::"r"(dst), "l"(tm), "r"(c0), "r"(c4), "r"(bar), "r"(0) : "memory");
}
__device__ __forceinline__ void tma_5d_mc_e(uint32_t dst, const CUtensorMap* tm, int c0, int c4, uint32_t bar) {
  asm volatile("{\n.reg .pred p;\nelect.sync _|p, 0xffffffff;\n"
               "@p cp.async.bulk.tensor.5d.shared::cluster.global.mbarrier::complete_tx::bytes.multicast::cluster [%0], [%1, {%2, %6, %6, %6, %3}], [%4], %5;\n}\n"
               ::"r"(dst), "l"(tm), "r"(c0), "r"(c4), "r"(bar), "h"((uint16_t)3), "r"(0) : "memory");
}
__device__ __forceinline__ void wait_tma_5d_mc(bool w, uint32_t eb, uint32_t par, uint32_t dst, const CUtensorMap* tm, int c0, int c4, uint32_t fb) {
  asm volatile("" : "+r"(dst), "+l"(tm), "+r"(c0), "+r"(c4), "+r"(fb));
  if (w) mbar_wait_u(eb, par);
  tma_5d_mc_e(dst, tm, c0, c4, fb);
}
__device__ __forceinline__ void stg128(void* p, uint32_t a, uint32_t b, uint32_t c, uint32_t d) {
  asm volatile("st.global.v4.u32 [%0], {%1,%2,%3,%4};" ::"l"(p), "r"(a), "r"(b), "r"(c), "r"(d) : "memory");
}
__device__ __forceinline__ void stg128_p(bool on, void* p, uint32_t a, uint32_t b, uint32_t c, uint32_t d) {
  asm volatile("{\n.reg .pred p;\nsetp.ne.b32 p, %5, 0;\n@p st.global.v4.u32 [%0], {%1,%2,%3,%4};\n}\n" ::"l"(p), "r"(a), "r"(b), "r"(c), "r"(d), "r"((int)on) : "memory");
}
__device__ __forceinline__ void ldg128(const void* p, uint32_t& a, uint32_t& b, uint32_t& c, uint32_t& d) {
  asm volatile("ld.global.cg.v4.u32 {%0,%1,%2,%3}, [%4];" : "=r"(a), "=r"(b), "=r"(c), "=r"(d) : "l"(p) : "memory");
}
__device__ __forceinline__ void release2c(uint32_t off) {
  asm volatile("mbarrier.arrive.shared::cluster.b64 _, [%0];\nmbarrier.arrive.shared::cluster.b64 _, [%1];" ::"r"(off), "r"(off + (1u << 24)) : "memory");
}
__device__ __forceinline__ void tma_store_5d(const CUtensorMap* tm, uint32_t src, int c0, int c4) {
  asm volatile("cp.async.bulk.tensor.5d.global.shared::cta.bulk_group [%0, {%2, %4, %4, %4, %3}], [%1];"
               ::"l"(tm), "r"(src), "r"(c0), "r"(c4), "r"(0) : "memory");
}
__device__ __forceinline__ void bulk_load(uint32_t dst, const void* src, uint32_t bytes, uint32_t bar) {
  asm volatile("cp.async.bulk.shared::cluster.global.mbarrier::complete_tx::bytes [%0], [%1], %2, [%3];" ::"r"(dst), "l"(src), "r"(bytes), "r"(bar) : "memory");
}
__device__ __forceinline__ void bulk_red_add(void* dst, uint32_t src, uint32_t bytes) {
  asm volatile("cp.reduce.async.bulk.global.shared::cta.bulk_group.add.f32 [%0], [%1], %2;" ::"l"(dst), "r"(src), "r"(bytes) : "memory");
}
__device__ __forceinline__ void bulk_commit() { asm volatile("cp.async.bulk.commit_group;" ::: "memory"); }
__device__ __forceinline__ void bulk_wait0() { asm volatile("cp.async.bulk.wait_group 0;" ::: "memory"); }
__device__ __forceinline__ void fence_async_smem() { asm volatile("fence.proxy.async.shared::cta;" ::: "memory"); }
__device__ __forceinline__ void fence_async_all() { asm volatile("fence.proxy.async.global;" ::: "memory"); }
__device__ __forceinline__ void wgmma_fence() { asm volatile("wgmma.fence.sync.aligned;" ::: "memory"); }
__device__ __forceinline__ void wgmma_commit() { asm volatile("wgmma.commit_group.sync.aligned;" ::: "memory"); }
template <int N> __device__ __forceinline__ void wgmma_wait() { asm volatile("wgmma.wait_group.sync.aligned %0;" ::"n"(N) : "memory"); }
__device__ __forceinline__ void cluster_wait() { asm volatile("barrier.cluster.wait.acquire.aligned;" ::: "memory"); }
template <int ID, int N> __device__ __forceinline__ void nbar() { asm volatile("bar.sync %0, %1;" ::"n"(ID), "n"(N) : "memory"); }
__device__ __forceinline__ uint64_t desc64(uint32_t lo, uint32_t hi) { return (uint64_t)lo | ((uint64_t)hi << 32); }
__device__ __forceinline__ uint32_t pack_bf16(float lo, float hi) {
  uint32_t r; asm("cvt.rn.bf16x2.f32 %0, %1, %2;" : "=r"(r) : "f"(hi), "f"(lo)); return r;
}
__device__ __forceinline__ uint32_t add_bf16x2(uint32_t a, uint32_t b) {
  uint32_t r; asm("add.rn.bf16x2 %0, %1, %2;" : "=r"(r) : "r"(a), "r"(b)); return r;
}
__device__ __forceinline__ float bf16r(float x) { return __bfloat162float(__float2bfloat16_rn(x)); }
__device__ __forceinline__ float bf_lo(uint32_t u) { return __uint_as_float(u << 16); }
__device__ __forceinline__ float bf_hi(uint32_t u) { return __uint_as_float(u & 0xFFFF0000u); }
__device__ __forceinline__ float ex2(float x) { float r; asm("ex2.approx.ftz.f32 %0, %1;" : "=f"(r) : "f"(x)); return r; }
__device__ __forceinline__ float ex2v(float x) { float r; asm volatile("ex2.approx.ftz.f32 %0, %1;" : "=f"(r) : "f"(x) : "memory"); return r; }
__device__ __forceinline__ float rcp(float x) { float r; asm("rcp.approx.ftz.f32 %0, %1;" : "=f"(r) : "f"(x)); return r; }
__device__ __forceinline__ void mma_bf16(float (&d)[4], uint32_t a0, uint32_t a1, uint32_t a2, uint32_t a3, uint32_t b0, uint32_t b1) {
  asm("mma.sync.aligned.m16n8k16.row.col.f32.bf16.bf16.f32 {%0,%1,%2,%3}, {%4,%5,%6,%7}, {%8,%9}, {%0,%1,%2,%3};"
               : "+f"(d[0]), "+f"(d[1]), "+f"(d[2]), "+f"(d[3]) : "r"(a0), "r"(a1), "r"(a2), "r"(a3), "r"(b0), "r"(b1));
}
__device__ __forceinline__ void ldsm_x4(uint32_t& r0, uint32_t& r1, uint32_t& r2, uint32_t& r3, uint32_t addr) {
  asm volatile("ldmatrix.sync.aligned.m8n8.x4.shared.b16 {%0,%1,%2,%3}, [%4];"
               : "=r"(r0), "=r"(r1), "=r"(r2), "=r"(r3) : "r"(addr) : "memory");
}
__device__ __forceinline__ void ldsm_x4_t(uint32_t& r0, uint32_t& r1, uint32_t& r2, uint32_t& r3, uint32_t addr) {
  asm volatile("ldmatrix.sync.aligned.m8n8.x4.trans.shared.b16 {%0,%1,%2,%3}, [%4];"
               : "=r"(r0), "=r"(r1), "=r"(r2), "=r"(r3) : "r"(addr) : "memory");
}
__device__ __forceinline__ void stsm_x4(uint32_t addr, uint32_t r0, uint32_t r1, uint32_t r2, uint32_t r3) {
  asm volatile("stmatrix.sync.aligned.m8n8.x4.shared.b16 [%0], {%1,%2,%3,%4};"
               ::"r"(addr), "r"(r0), "r"(r1), "r"(r2), "r"(r3) : "memory");
}
__device__ __forceinline__ uint4 lds128(uint32_t addr) {
  uint4 v; asm volatile("ld.shared.v4.b32 {%0,%1,%2,%3}, [%4];" : "=r"(v.x), "=r"(v.y), "=r"(v.z), "=r"(v.w) : "r"(addr) : "memory"); return v;
}
__device__ __forceinline__ void sts128(uint32_t addr, uint4 v) {
  asm volatile("st.shared.v4.b32 [%0], {%1,%2,%3,%4};" ::"r"(addr), "r"(v.x), "r"(v.y), "r"(v.z), "r"(v.w) : "memory");
}
__device__ __forceinline__ float lds_f(uint32_t addr) {
  float v; asm volatile("ld.shared.f32 %0, [%1];" : "=f"(v) : "r"(addr) : "memory"); return v;
}
__device__ __forceinline__ void nbar_dyn(int id, int n) { asm volatile("bar.sync %0, %1;" ::"r"(id), "r"(n) : "memory"); }
__device__ __forceinline__ uint64_t make_desc_ns(uint32_t addr, uint32_t lbo_bytes, uint32_t sbo_bytes) {
  return (uint64_t)((addr & 0x3FFFF) >> 4) | ((uint64_t)(lbo_bytes >> 4) << 16) | ((uint64_t)(sbo_bytes >> 4) << 32);
}
__device__ __forceinline__ void sts_f(uint32_t addr, float v) { asm volatile("st.shared.f32 [%0], %1;" ::"r"(addr), "f"(v) : "memory"); }
__device__ __forceinline__ void sts64(uint32_t addr, uint32_t a, uint32_t b) {
  asm volatile("st.shared.v2.b32 [%0], {%1,%2};" ::"r"(addr), "r"(a), "r"(b) : "memory");
}
__device__ __forceinline__ void sts_f2(uint32_t addr, float a, float b) {
  asm volatile("st.shared.v2.f32 [%0], {%1,%2};" ::"r"(addr), "f"(a), "f"(b) : "memory");
}
__device__ __forceinline__ void red_add2_p(bool on, float* p, float a, float b) {
  asm volatile("{\n.reg .pred p;\nsetp.ne.b32 p, %3, 0;\n@p red.global.add.v2.f32 [%0], {%1,%2};\n}\n" ::"l"(p), "f"(a), "f"(b), "r"((int)on) : "memory");
}
__device__ __forceinline__ void red_add4(float* p, float a, float b, float c, float d) {
  asm volatile("red.global.add.v4.f32 [%0], {%1,%2,%3,%4};" ::"l"(p), "f"(a), "f"(b), "f"(c), "f"(d) : "memory");
}
__device__ __forceinline__ void red_add1(float* p, float a) {
  asm volatile("red.global.add.f32 [%0], %1;" ::"l"(p), "f"(a) : "memory");
}
__device__ __forceinline__ void l2_prefetch(const void* p, uint32_t bytes) {
  asm volatile("cp.async.bulk.prefetch.L2.global [%0], %1;" ::"l"(p), "r"(bytes) : "memory");
}

__device__ __forceinline__ void wgmma_n256(float (&d)[192], uint64_t da, uint64_t db, int scale_d) {
  asm volatile("{\n.reg .pred p;\nsetp.ne.b32 p, %130, 0;\n"
    "wgmma.mma_async.sync.aligned.m64n256k16.f32.bf16.bf16 {%0, %1, %2, %3, %4, %5, %6, %7, %8, %9, %10, %11, %12, %13, %14, %15, %16, %17, %18, %19, %20, %21, %22, %23, %24, %25, %26, %27, %28, %29, %30, %31, %32, %33, %34, %35, %36, %37, %38, %39, %40, %41, %42, %43, %44, %45, %46, %47, %48, %49, %50, %51, %52, %53, %54, %55, %56, %57, %58, %59, %60, %61, %62, %63, %64, %65, %66, %67, %68, %69, %70, %71, %72, %73, %74, %75, %76, %77, %78, %79, %80, %81, %82, %83, %84, %85, %86, %87, %88, %89, %90, %91, %92, %93, %94, %95, %96, %97, %98, %99, %100, %101, %102, %103, %104, %105, %106, %107, %108, %109, %110, %111, %112, %113, %114, %115, %116, %117, %118, %119, %120, %121, %122, %123, %124, %125, %126, %127}, %128, %129, p, 1, 1, 0, 1;\n}\n"
    : "+f"(d[0]), "+f"(d[1]), "+f"(d[2]), "+f"(d[3]), "+f"(d[4]), "+f"(d[5]), "+f"(d[6]), "+f"(d[7]), "+f"(d[8]), "+f"(d[9]), "+f"(d[10]), "+f"(d[11]), "+f"(d[12]), "+f"(d[13]), "+f"(d[14]), "+f"(d[15]), "+f"(d[16]), "+f"(d[17]), "+f"(d[18]), "+f"(d[19]), "+f"(d[20]), "+f"(d[21]), "+f"(d[22]), "+f"(d[23]), "+f"(d[24]), "+f"(d[25]), "+f"(d[26]), "+f"(d[27]), "+f"(d[28]), "+f"(d[29]), "+f"(d[30]), "+f"(d[31]), "+f"(d[32]), "+f"(d[33]), "+f"(d[34]), "+f"(d[35]), "+f"(d[36]), "+f"(d[37]), "+f"(d[38]), "+f"(d[39]), "+f"(d[40]), "+f"(d[41]), "+f"(d[42]), "+f"(d[43]), "+f"(d[44]), "+f"(d[45]), "+f"(d[46]), "+f"(d[47]), "+f"(d[48]), "+f"(d[49]), "+f"(d[50]), "+f"(d[51]), "+f"(d[52]), "+f"(d[53]), "+f"(d[54]), "+f"(d[55]), "+f"(d[56]), "+f"(d[57]), "+f"(d[58]), "+f"(d[59]), "+f"(d[60]), "+f"(d[61]), "+f"(d[62]), "+f"(d[63]), "+f"(d[64]), "+f"(d[65]), "+f"(d[66]), "+f"(d[67]), "+f"(d[68]), "+f"(d[69]), "+f"(d[70]), "+f"(d[71]), "+f"(d[72]), "+f"(d[73]), "+f"(d[74]), "+f"(d[75]), "+f"(d[76]), "+f"(d[77]), "+f"(d[78]), "+f"(d[79]), "+f"(d[80]), "+f"(d[81]), "+f"(d[82]), "+f"(d[83]), "+f"(d[84]), "+f"(d[85]), "+f"(d[86]), "+f"(d[87]), "+f"(d[88]), "+f"(d[89]), "+f"(d[90]), "+f"(d[91]), "+f"(d[92]), "+f"(d[93]), "+f"(d[94]), "+f"(d[95]), "+f"(d[96]), "+f"(d[97]), "+f"(d[98]), "+f"(d[99]), "+f"(d[100]), "+f"(d[101]), "+f"(d[102]), "+f"(d[103]), "+f"(d[104]), "+f"(d[105]), "+f"(d[106]), "+f"(d[107]), "+f"(d[108]), "+f"(d[109]), "+f"(d[110]), "+f"(d[111]), "+f"(d[112]), "+f"(d[113]), "+f"(d[114]), "+f"(d[115]), "+f"(d[116]), "+f"(d[117]), "+f"(d[118]), "+f"(d[119]), "+f"(d[120]), "+f"(d[121]), "+f"(d[122]), "+f"(d[123]), "+f"(d[124]), "+f"(d[125]), "+f"(d[126]), "+f"(d[127])
    : "l"(da), "l"(db), "r"(scale_d));
}
__device__ __forceinline__ void wgmma_n128(float (&d)[192], uint64_t da, uint64_t db, int scale_d) {
  asm volatile("{\n.reg .pred p;\nsetp.ne.b32 p, %66, 0;\n"
    "wgmma.mma_async.sync.aligned.m64n128k16.f32.bf16.bf16 {%0, %1, %2, %3, %4, %5, %6, %7, %8, %9, %10, %11, %12, %13, %14, %15, %16, %17, %18, %19, %20, %21, %22, %23, %24, %25, %26, %27, %28, %29, %30, %31, %32, %33, %34, %35, %36, %37, %38, %39, %40, %41, %42, %43, %44, %45, %46, %47, %48, %49, %50, %51, %52, %53, %54, %55, %56, %57, %58, %59, %60, %61, %62, %63}, %64, %65, p, 1, 1, 0, 1;\n}\n"
    : "+f"(d[128]), "+f"(d[129]), "+f"(d[130]), "+f"(d[131]), "+f"(d[132]), "+f"(d[133]), "+f"(d[134]), "+f"(d[135]), "+f"(d[136]), "+f"(d[137]), "+f"(d[138]), "+f"(d[139]), "+f"(d[140]), "+f"(d[141]), "+f"(d[142]), "+f"(d[143]), "+f"(d[144]), "+f"(d[145]), "+f"(d[146]), "+f"(d[147]), "+f"(d[148]), "+f"(d[149]), "+f"(d[150]), "+f"(d[151]), "+f"(d[152]), "+f"(d[153]), "+f"(d[154]), "+f"(d[155]), "+f"(d[156]), "+f"(d[157]), "+f"(d[158]), "+f"(d[159]), "+f"(d[160]), "+f"(d[161]), "+f"(d[162]), "+f"(d[163]), "+f"(d[164]), "+f"(d[165]), "+f"(d[166]), "+f"(d[167]), "+f"(d[168]), "+f"(d[169]), "+f"(d[170]), "+f"(d[171]), "+f"(d[172]), "+f"(d[173]), "+f"(d[174]), "+f"(d[175]), "+f"(d[176]), "+f"(d[177]), "+f"(d[178]), "+f"(d[179]), "+f"(d[180]), "+f"(d[181]), "+f"(d[182]), "+f"(d[183]), "+f"(d[184]), "+f"(d[185]), "+f"(d[186]), "+f"(d[187]), "+f"(d[188]), "+f"(d[189]), "+f"(d[190]), "+f"(d[191])
    : "l"(da), "l"(db), "r"(scale_d));
}
__device__ __forceinline__ void wgmma_n256_k(float (&d)[192], uint64_t da, uint64_t db, int scale_d) {
  asm volatile("{\n.reg .pred p;\nsetp.ne.b32 p, %130, 0;\n"
    "wgmma.mma_async.sync.aligned.m64n256k16.f32.bf16.bf16 {%0, %1, %2, %3, %4, %5, %6, %7, %8, %9, %10, %11, %12, %13, %14, %15, %16, %17, %18, %19, %20, %21, %22, %23, %24, %25, %26, %27, %28, %29, %30, %31, %32, %33, %34, %35, %36, %37, %38, %39, %40, %41, %42, %43, %44, %45, %46, %47, %48, %49, %50, %51, %52, %53, %54, %55, %56, %57, %58, %59, %60, %61, %62, %63, %64, %65, %66, %67, %68, %69, %70, %71, %72, %73, %74, %75, %76, %77, %78, %79, %80, %81, %82, %83, %84, %85, %86, %87, %88, %89, %90, %91, %92, %93, %94, %95, %96, %97, %98, %99, %100, %101, %102, %103, %104, %105, %106, %107, %108, %109, %110, %111, %112, %113, %114, %115, %116, %117, %118, %119, %120, %121, %122, %123, %124, %125, %126, %127}, %128, %129, p, 1, 1, 0, 0;\n}\n"
    : "+f"(d[0]), "+f"(d[1]), "+f"(d[2]), "+f"(d[3]), "+f"(d[4]), "+f"(d[5]), "+f"(d[6]), "+f"(d[7]), "+f"(d[8]), "+f"(d[9]), "+f"(d[10]), "+f"(d[11]), "+f"(d[12]), "+f"(d[13]), "+f"(d[14]), "+f"(d[15]), "+f"(d[16]), "+f"(d[17]), "+f"(d[18]), "+f"(d[19]), "+f"(d[20]), "+f"(d[21]), "+f"(d[22]), "+f"(d[23]), "+f"(d[24]), "+f"(d[25]), "+f"(d[26]), "+f"(d[27]), "+f"(d[28]), "+f"(d[29]), "+f"(d[30]), "+f"(d[31]), "+f"(d[32]), "+f"(d[33]), "+f"(d[34]), "+f"(d[35]), "+f"(d[36]), "+f"(d[37]), "+f"(d[38]), "+f"(d[39]), "+f"(d[40]), "+f"(d[41]), "+f"(d[42]), "+f"(d[43]), "+f"(d[44]), "+f"(d[45]), "+f"(d[46]), "+f"(d[47]), "+f"(d[48]), "+f"(d[49]), "+f"(d[50]), "+f"(d[51]), "+f"(d[52]), "+f"(d[53]), "+f"(d[54]), "+f"(d[55]), "+f"(d[56]), "+f"(d[57]), "+f"(d[58]), "+f"(d[59]), "+f"(d[60]), "+f"(d[61]), "+f"(d[62]), "+f"(d[63]), "+f"(d[64]), "+f"(d[65]), "+f"(d[66]), "+f"(d[67]), "+f"(d[68]), "+f"(d[69]), "+f"(d[70]), "+f"(d[71]), "+f"(d[72]), "+f"(d[73]), "+f"(d[74]), "+f"(d[75]), "+f"(d[76]), "+f"(d[77]), "+f"(d[78]), "+f"(d[79]), "+f"(d[80]), "+f"(d[81]), "+f"(d[82]), "+f"(d[83]), "+f"(d[84]), "+f"(d[85]), "+f"(d[86]), "+f"(d[87]), "+f"(d[88]), "+f"(d[89]), "+f"(d[90]), "+f"(d[91]), "+f"(d[92]), "+f"(d[93]), "+f"(d[94]), "+f"(d[95]), "+f"(d[96]), "+f"(d[97]), "+f"(d[98]), "+f"(d[99]), "+f"(d[100]), "+f"(d[101]), "+f"(d[102]), "+f"(d[103]), "+f"(d[104]), "+f"(d[105]), "+f"(d[106]), "+f"(d[107]), "+f"(d[108]), "+f"(d[109]), "+f"(d[110]), "+f"(d[111]), "+f"(d[112]), "+f"(d[113]), "+f"(d[114]), "+f"(d[115]), "+f"(d[116]), "+f"(d[117]), "+f"(d[118]), "+f"(d[119]), "+f"(d[120]), "+f"(d[121]), "+f"(d[122]), "+f"(d[123]), "+f"(d[124]), "+f"(d[125]), "+f"(d[126]), "+f"(d[127])
    : "l"(da), "l"(db), "r"(scale_d));
}
__device__ __forceinline__ void wgmma_n128_k(float (&d)[192], uint64_t da, uint64_t db, int scale_d) {
  asm volatile("{\n.reg .pred p;\nsetp.ne.b32 p, %66, 0;\n"
    "wgmma.mma_async.sync.aligned.m64n128k16.f32.bf16.bf16 {%0, %1, %2, %3, %4, %5, %6, %7, %8, %9, %10, %11, %12, %13, %14, %15, %16, %17, %18, %19, %20, %21, %22, %23, %24, %25, %26, %27, %28, %29, %30, %31, %32, %33, %34, %35, %36, %37, %38, %39, %40, %41, %42, %43, %44, %45, %46, %47, %48, %49, %50, %51, %52, %53, %54, %55, %56, %57, %58, %59, %60, %61, %62, %63}, %64, %65, p, 1, 1, 0, 0;\n}\n"
    : "+f"(d[128]), "+f"(d[129]), "+f"(d[130]), "+f"(d[131]), "+f"(d[132]), "+f"(d[133]), "+f"(d[134]), "+f"(d[135]), "+f"(d[136]), "+f"(d[137]), "+f"(d[138]), "+f"(d[139]), "+f"(d[140]), "+f"(d[141]), "+f"(d[142]), "+f"(d[143]), "+f"(d[144]), "+f"(d[145]), "+f"(d[146]), "+f"(d[147]), "+f"(d[148]), "+f"(d[149]), "+f"(d[150]), "+f"(d[151]), "+f"(d[152]), "+f"(d[153]), "+f"(d[154]), "+f"(d[155]), "+f"(d[156]), "+f"(d[157]), "+f"(d[158]), "+f"(d[159]), "+f"(d[160]), "+f"(d[161]), "+f"(d[162]), "+f"(d[163]), "+f"(d[164]), "+f"(d[165]), "+f"(d[166]), "+f"(d[167]), "+f"(d[168]), "+f"(d[169]), "+f"(d[170]), "+f"(d[171]), "+f"(d[172]), "+f"(d[173]), "+f"(d[174]), "+f"(d[175]), "+f"(d[176]), "+f"(d[177]), "+f"(d[178]), "+f"(d[179]), "+f"(d[180]), "+f"(d[181]), "+f"(d[182]), "+f"(d[183]), "+f"(d[184]), "+f"(d[185]), "+f"(d[186]), "+f"(d[187]), "+f"(d[188]), "+f"(d[189]), "+f"(d[190]), "+f"(d[191])
    : "l"(da), "l"(db), "r"(scale_d));
}
__device__ __forceinline__ void wgmma_n40_tt(float (&d)[20], uint64_t da, uint64_t db, int scale_d) {
  asm volatile("{\n.reg .pred p;\nsetp.ne.b32 p, %22, 0;\n"
    "wgmma.mma_async.sync.aligned.m64n40k16.f32.bf16.bf16 {%0, %1, %2, %3, %4, %5, %6, %7, %8, %9, %10, %11, %12, %13, %14, %15, %16, %17, %18, %19}, %20, %21, p, 1, 1, 1, 1;\n}\n"
    : "+f"(d[0]), "+f"(d[1]), "+f"(d[2]), "+f"(d[3]), "+f"(d[4]), "+f"(d[5]), "+f"(d[6]), "+f"(d[7]), "+f"(d[8]), "+f"(d[9]), "+f"(d[10]), "+f"(d[11]), "+f"(d[12]), "+f"(d[13]), "+f"(d[14]), "+f"(d[15]), "+f"(d[16]), "+f"(d[17]), "+f"(d[18]), "+f"(d[19])
    : "l"(da), "l"(db), "r"(scale_d));
}
__device__ __forceinline__ void wgmma_n40_rs(float (&d)[20], const uint32_t (&a)[4], uint64_t db, int scale_d) {
  asm volatile("{\n.reg .pred p;\nsetp.ne.b32 p, %25, 0;\n"
    "wgmma.mma_async.sync.aligned.m64n40k16.f32.bf16.bf16 {%0, %1, %2, %3, %4, %5, %6, %7, %8, %9, %10, %11, %12, %13, %14, %15, %16, %17, %18, %19}, {%20, %21, %22, %23}, %24, p, 1, 1, 1;\n}\n"
    : "+f"(d[0]), "+f"(d[1]), "+f"(d[2]), "+f"(d[3]), "+f"(d[4]), "+f"(d[5]), "+f"(d[6]), "+f"(d[7]), "+f"(d[8]), "+f"(d[9]), "+f"(d[10]), "+f"(d[11]), "+f"(d[12]), "+f"(d[13]), "+f"(d[14]), "+f"(d[15]), "+f"(d[16]), "+f"(d[17]), "+f"(d[18]), "+f"(d[19])
    : "r"(a[0]), "r"(a[1]), "r"(a[2]), "r"(a[3]), "l"(db), "r"(scale_d));
}
__device__ __forceinline__ void wgmma_n128_0(float (&d)[192], uint64_t da, uint64_t db) {
  asm volatile("{\n.reg .pred p;\nsetp.ne.b32 p, 0, 0;\n"
    "wgmma.mma_async.sync.aligned.m64n128k16.f32.bf16.bf16 {%0, %1, %2, %3, %4, %5, %6, %7, %8, %9, %10, %11, %12, %13, %14, %15, %16, %17, %18, %19, %20, %21, %22, %23, %24, %25, %26, %27, %28, %29, %30, %31, %32, %33, %34, %35, %36, %37, %38, %39, %40, %41, %42, %43, %44, %45, %46, %47, %48, %49, %50, %51, %52, %53, %54, %55, %56, %57, %58, %59, %60, %61, %62, %63}, %64, %65, p, 1, 1, 0, 1;\n}\n"
    : "=f"(d[128]), "=f"(d[129]), "=f"(d[130]), "=f"(d[131]), "=f"(d[132]), "=f"(d[133]), "=f"(d[134]), "=f"(d[135]), "=f"(d[136]), "=f"(d[137]), "=f"(d[138]), "=f"(d[139]), "=f"(d[140]), "=f"(d[141]), "=f"(d[142]), "=f"(d[143]), "=f"(d[144]), "=f"(d[145]), "=f"(d[146]), "=f"(d[147]), "=f"(d[148]), "=f"(d[149]), "=f"(d[150]), "=f"(d[151]), "=f"(d[152]), "=f"(d[153]), "=f"(d[154]), "=f"(d[155]), "=f"(d[156]), "=f"(d[157]), "=f"(d[158]), "=f"(d[159]), "=f"(d[160]), "=f"(d[161]), "=f"(d[162]), "=f"(d[163]), "=f"(d[164]), "=f"(d[165]), "=f"(d[166]), "=f"(d[167]), "=f"(d[168]), "=f"(d[169]), "=f"(d[170]), "=f"(d[171]), "=f"(d[172]), "=f"(d[173]), "=f"(d[174]), "=f"(d[175]), "=f"(d[176]), "=f"(d[177]), "=f"(d[178]), "=f"(d[179]), "=f"(d[180]), "=f"(d[181]), "=f"(d[182]), "=f"(d[183]), "=f"(d[184]), "=f"(d[185]), "=f"(d[186]), "=f"(d[187]), "=f"(d[188]), "=f"(d[189]), "=f"(d[190]), "=f"(d[191])
    : "l"(da), "l"(db));
}
__device__ __forceinline__ void wgmma_n128_rs(float (&d)[192], const uint32_t (&a)[4], uint64_t db, int scale_d) {
  asm volatile("{\n.reg .pred p;\nsetp.ne.b32 p, %69, 0;\n"
    "wgmma.mma_async.sync.aligned.m64n128k16.f32.bf16.bf16 {%0, %1, %2, %3, %4, %5, %6, %7, %8, %9, %10, %11, %12, %13, %14, %15, %16, %17, %18, %19, %20, %21, %22, %23, %24, %25, %26, %27, %28, %29, %30, %31, %32, %33, %34, %35, %36, %37, %38, %39, %40, %41, %42, %43, %44, %45, %46, %47, %48, %49, %50, %51, %52, %53, %54, %55, %56, %57, %58, %59, %60, %61, %62, %63}, {%64, %65, %66, %67}, %68, p, 1, 1, 1;\n}\n"
    : "+f"(d[128]), "+f"(d[129]), "+f"(d[130]), "+f"(d[131]), "+f"(d[132]), "+f"(d[133]), "+f"(d[134]), "+f"(d[135]), "+f"(d[136]), "+f"(d[137]), "+f"(d[138]), "+f"(d[139]), "+f"(d[140]), "+f"(d[141]), "+f"(d[142]), "+f"(d[143]), "+f"(d[144]), "+f"(d[145]), "+f"(d[146]), "+f"(d[147]), "+f"(d[148]), "+f"(d[149]), "+f"(d[150]), "+f"(d[151]), "+f"(d[152]), "+f"(d[153]), "+f"(d[154]), "+f"(d[155]), "+f"(d[156]), "+f"(d[157]), "+f"(d[158]), "+f"(d[159]), "+f"(d[160]), "+f"(d[161]), "+f"(d[162]), "+f"(d[163]), "+f"(d[164]), "+f"(d[165]), "+f"(d[166]), "+f"(d[167]), "+f"(d[168]), "+f"(d[169]), "+f"(d[170]), "+f"(d[171]), "+f"(d[172]), "+f"(d[173]), "+f"(d[174]), "+f"(d[175]), "+f"(d[176]), "+f"(d[177]), "+f"(d[178]), "+f"(d[179]), "+f"(d[180]), "+f"(d[181]), "+f"(d[182]), "+f"(d[183]), "+f"(d[184]), "+f"(d[185]), "+f"(d[186]), "+f"(d[187]), "+f"(d[188]), "+f"(d[189]), "+f"(d[190]), "+f"(d[191])
    : "r"(a[0]), "r"(a[1]), "r"(a[2]), "r"(a[3]), "l"(db), "r"(scale_d));
}
__device__ __forceinline__ void wgmma_n32_0(float (&d)[16], uint64_t da, uint64_t db) {
  asm volatile("{\n.reg .pred p;\nsetp.ne.b32 p, 0, 0;\n"
    "wgmma.mma_async.sync.aligned.m64n32k16.f32.bf16.bf16 {%0, %1, %2, %3, %4, %5, %6, %7, %8, %9, %10, %11, %12, %13, %14, %15}, %16, %17, p, 1, 1, 0, 1;\n}\n"
    : "=f"(d[0]), "=f"(d[1]), "=f"(d[2]), "=f"(d[3]), "=f"(d[4]), "=f"(d[5]), "=f"(d[6]), "=f"(d[7]), "=f"(d[8]), "=f"(d[9]), "=f"(d[10]), "=f"(d[11]), "=f"(d[12]), "=f"(d[13]), "=f"(d[14]), "=f"(d[15])
    : "l"(da), "l"(db));
}
__device__ __forceinline__ void wgmma_n32(float (&d)[16], uint64_t da, uint64_t db, int scale_d) {
  asm volatile("{\n.reg .pred p;\nsetp.ne.b32 p, %18, 0;\n"
    "wgmma.mma_async.sync.aligned.m64n32k16.f32.bf16.bf16 {%0, %1, %2, %3, %4, %5, %6, %7, %8, %9, %10, %11, %12, %13, %14, %15}, %16, %17, p, 1, 1, 0, 1;\n}\n"
    : "+f"(d[0]), "+f"(d[1]), "+f"(d[2]), "+f"(d[3]), "+f"(d[4]), "+f"(d[5]), "+f"(d[6]), "+f"(d[7]), "+f"(d[8]), "+f"(d[9]), "+f"(d[10]), "+f"(d[11]), "+f"(d[12]), "+f"(d[13]), "+f"(d[14]), "+f"(d[15])
    : "l"(da), "l"(db), "r"(scale_d));
}
__device__ __forceinline__ void wgmma_n8_t(float (&d)[4], uint64_t da, uint64_t db, int scale_d) {
  asm volatile("{\n.reg .pred p;\nsetp.ne.b32 p, %6, 0;\n"
    "wgmma.mma_async.sync.aligned.m64n8k16.f32.bf16.bf16 {%0, %1, %2, %3}, %4, %5, p, 1, 1, 1, 0;\n}\n"
    : "+f"(d[0]), "+f"(d[1]), "+f"(d[2]), "+f"(d[3])
    : "l"(da), "l"(db), "r"(scale_d));
}
__device__ __forceinline__ void wgmma_n128_rs0(float (&d)[192], const uint32_t (&a)[4], uint64_t db) {
  asm volatile("{\n.reg .pred p;\nsetp.ne.b32 p, 0, 0;\n"
    "wgmma.mma_async.sync.aligned.m64n128k16.f32.bf16.bf16 {%0, %1, %2, %3, %4, %5, %6, %7, %8, %9, %10, %11, %12, %13, %14, %15, %16, %17, %18, %19, %20, %21, %22, %23, %24, %25, %26, %27, %28, %29, %30, %31, %32, %33, %34, %35, %36, %37, %38, %39, %40, %41, %42, %43, %44, %45, %46, %47, %48, %49, %50, %51, %52, %53, %54, %55, %56, %57, %58, %59, %60, %61, %62, %63}, {%64, %65, %66, %67}, %68, p, 1, 1, 1;\n}\n"
    : "=f"(d[128]), "=f"(d[129]), "=f"(d[130]), "=f"(d[131]), "=f"(d[132]), "=f"(d[133]), "=f"(d[134]), "=f"(d[135]), "=f"(d[136]), "=f"(d[137]), "=f"(d[138]), "=f"(d[139]), "=f"(d[140]), "=f"(d[141]), "=f"(d[142]), "=f"(d[143]), "=f"(d[144]), "=f"(d[145]), "=f"(d[146]), "=f"(d[147]), "=f"(d[148]), "=f"(d[149]), "=f"(d[150]), "=f"(d[151]), "=f"(d[152]), "=f"(d[153]), "=f"(d[154]), "=f"(d[155]), "=f"(d[156]), "=f"(d[157]), "=f"(d[158]), "=f"(d[159]), "=f"(d[160]), "=f"(d[161]), "=f"(d[162]), "=f"(d[163]), "=f"(d[164]), "=f"(d[165]), "=f"(d[166]), "=f"(d[167]), "=f"(d[168]), "=f"(d[169]), "=f"(d[170]), "=f"(d[171]), "=f"(d[172]), "=f"(d[173]), "=f"(d[174]), "=f"(d[175]), "=f"(d[176]), "=f"(d[177]), "=f"(d[178]), "=f"(d[179]), "=f"(d[180]), "=f"(d[181]), "=f"(d[182]), "=f"(d[183]), "=f"(d[184]), "=f"(d[185]), "=f"(d[186]), "=f"(d[187]), "=f"(d[188]), "=f"(d[189]), "=f"(d[190]), "=f"(d[191])
    : "r"(a[0]), "r"(a[1]), "r"(a[2]), "r"(a[3]), "l"(db));
}
__device__ __forceinline__ void wgmma_n256_rs(float (&d)[192], const uint32_t (&a)[4], uint64_t db, int scale_d) {
  asm volatile("{\n.reg .pred p;\nsetp.ne.b32 p, %133, 0;\n"
    "wgmma.mma_async.sync.aligned.m64n256k16.f32.bf16.bf16 {%0, %1, %2, %3, %4, %5, %6, %7, %8, %9, %10, %11, %12, %13, %14, %15, %16, %17, %18, %19, %20, %21, %22, %23, %24, %25, %26, %27, %28, %29, %30, %31, %32, %33, %34, %35, %36, %37, %38, %39, %40, %41, %42, %43, %44, %45, %46, %47, %48, %49, %50, %51, %52, %53, %54, %55, %56, %57, %58, %59, %60, %61, %62, %63, %64, %65, %66, %67, %68, %69, %70, %71, %72, %73, %74, %75, %76, %77, %78, %79, %80, %81, %82, %83, %84, %85, %86, %87, %88, %89, %90, %91, %92, %93, %94, %95, %96, %97, %98, %99, %100, %101, %102, %103, %104, %105, %106, %107, %108, %109, %110, %111, %112, %113, %114, %115, %116, %117, %118, %119, %120, %121, %122, %123, %124, %125, %126, %127}, {%128, %129, %130, %131}, %132, p, 1, 1, 1;\n}\n"
    : "+f"(d[0]), "+f"(d[1]), "+f"(d[2]), "+f"(d[3]), "+f"(d[4]), "+f"(d[5]), "+f"(d[6]), "+f"(d[7]), "+f"(d[8]), "+f"(d[9]), "+f"(d[10]), "+f"(d[11]), "+f"(d[12]), "+f"(d[13]), "+f"(d[14]), "+f"(d[15]), "+f"(d[16]), "+f"(d[17]), "+f"(d[18]), "+f"(d[19]), "+f"(d[20]), "+f"(d[21]), "+f"(d[22]), "+f"(d[23]), "+f"(d[24]), "+f"(d[25]), "+f"(d[26]), "+f"(d[27]), "+f"(d[28]), "+f"(d[29]), "+f"(d[30]), "+f"(d[31]), "+f"(d[32]), "+f"(d[33]), "+f"(d[34]), "+f"(d[35]), "+f"(d[36]), "+f"(d[37]), "+f"(d[38]), "+f"(d[39]), "+f"(d[40]), "+f"(d[41]), "+f"(d[42]), "+f"(d[43]), "+f"(d[44]), "+f"(d[45]), "+f"(d[46]), "+f"(d[47]), "+f"(d[48]), "+f"(d[49]), "+f"(d[50]), "+f"(d[51]), "+f"(d[52]), "+f"(d[53]), "+f"(d[54]), "+f"(d[55]), "+f"(d[56]), "+f"(d[57]), "+f"(d[58]), "+f"(d[59]), "+f"(d[60]), "+f"(d[61]), "+f"(d[62]), "+f"(d[63]), "+f"(d[64]), "+f"(d[65]), "+f"(d[66]), "+f"(d[67]), "+f"(d[68]), "+f"(d[69]), "+f"(d[70]), "+f"(d[71]), "+f"(d[72]), "+f"(d[73]), "+f"(d[74]), "+f"(d[75]), "+f"(d[76]), "+f"(d[77]), "+f"(d[78]), "+f"(d[79]), "+f"(d[80]), "+f"(d[81]), "+f"(d[82]), "+f"(d[83]), "+f"(d[84]), "+f"(d[85]), "+f"(d[86]), "+f"(d[87]), "+f"(d[88]), "+f"(d[89]), "+f"(d[90]), "+f"(d[91]), "+f"(d[92]), "+f"(d[93]), "+f"(d[94]), "+f"(d[95]), "+f"(d[96]), "+f"(d[97]), "+f"(d[98]), "+f"(d[99]), "+f"(d[100]), "+f"(d[101]), "+f"(d[102]), "+f"(d[103]), "+f"(d[104]), "+f"(d[105]), "+f"(d[106]), "+f"(d[107]), "+f"(d[108]), "+f"(d[109]), "+f"(d[110]), "+f"(d[111]), "+f"(d[112]), "+f"(d[113]), "+f"(d[114]), "+f"(d[115]), "+f"(d[116]), "+f"(d[117]), "+f"(d[118]), "+f"(d[119]), "+f"(d[120]), "+f"(d[121]), "+f"(d[122]), "+f"(d[123]), "+f"(d[124]), "+f"(d[125]), "+f"(d[126]), "+f"(d[127])
    : "r"(a[0]), "r"(a[1]), "r"(a[2]), "r"(a[3]), "l"(db), "r"(scale_d));
}
__device__ __forceinline__ void wgmma_n256_rs0(float (&d)[192], const uint32_t (&a)[4], uint64_t db) {
  asm volatile("{\n.reg .pred p;\nsetp.ne.b32 p, 0, 0;\n"
    "wgmma.mma_async.sync.aligned.m64n256k16.f32.bf16.bf16 {%0, %1, %2, %3, %4, %5, %6, %7, %8, %9, %10, %11, %12, %13, %14, %15, %16, %17, %18, %19, %20, %21, %22, %23, %24, %25, %26, %27, %28, %29, %30, %31, %32, %33, %34, %35, %36, %37, %38, %39, %40, %41, %42, %43, %44, %45, %46, %47, %48, %49, %50, %51, %52, %53, %54, %55, %56, %57, %58, %59, %60, %61, %62, %63, %64, %65, %66, %67, %68, %69, %70, %71, %72, %73, %74, %75, %76, %77, %78, %79, %80, %81, %82, %83, %84, %85, %86, %87, %88, %89, %90, %91, %92, %93, %94, %95, %96, %97, %98, %99, %100, %101, %102, %103, %104, %105, %106, %107, %108, %109, %110, %111, %112, %113, %114, %115, %116, %117, %118, %119, %120, %121, %122, %123, %124, %125, %126, %127}, {%128, %129, %130, %131}, %132, p, 1, 1, 1;\n}\n"
    : "=f"(d[0]), "=f"(d[1]), "=f"(d[2]), "=f"(d[3]), "=f"(d[4]), "=f"(d[5]), "=f"(d[6]), "=f"(d[7]), "=f"(d[8]), "=f"(d[9]), "=f"(d[10]), "=f"(d[11]), "=f"(d[12]), "=f"(d[13]), "=f"(d[14]), "=f"(d[15]), "=f"(d[16]), "=f"(d[17]), "=f"(d[18]), "=f"(d[19]), "=f"(d[20]), "=f"(d[21]), "=f"(d[22]), "=f"(d[23]), "=f"(d[24]), "=f"(d[25]), "=f"(d[26]), "=f"(d[27]), "=f"(d[28]), "=f"(d[29]), "=f"(d[30]), "=f"(d[31]), "=f"(d[32]), "=f"(d[33]), "=f"(d[34]), "=f"(d[35]), "=f"(d[36]), "=f"(d[37]), "=f"(d[38]), "=f"(d[39]), "=f"(d[40]), "=f"(d[41]), "=f"(d[42]), "=f"(d[43]), "=f"(d[44]), "=f"(d[45]), "=f"(d[46]), "=f"(d[47]), "=f"(d[48]), "=f"(d[49]), "=f"(d[50]), "=f"(d[51]), "=f"(d[52]), "=f"(d[53]), "=f"(d[54]), "=f"(d[55]), "=f"(d[56]), "=f"(d[57]), "=f"(d[58]), "=f"(d[59]), "=f"(d[60]), "=f"(d[61]), "=f"(d[62]), "=f"(d[63]), "=f"(d[64]), "=f"(d[65]), "=f"(d[66]), "=f"(d[67]), "=f"(d[68]), "=f"(d[69]), "=f"(d[70]), "=f"(d[71]), "=f"(d[72]), "=f"(d[73]), "=f"(d[74]), "=f"(d[75]), "=f"(d[76]), "=f"(d[77]), "=f"(d[78]), "=f"(d[79]), "=f"(d[80]), "=f"(d[81]), "=f"(d[82]), "=f"(d[83]), "=f"(d[84]), "=f"(d[85]), "=f"(d[86]), "=f"(d[87]), "=f"(d[88]), "=f"(d[89]), "=f"(d[90]), "=f"(d[91]), "=f"(d[92]), "=f"(d[93]), "=f"(d[94]), "=f"(d[95]), "=f"(d[96]), "=f"(d[97]), "=f"(d[98]), "=f"(d[99]), "=f"(d[100]), "=f"(d[101]), "=f"(d[102]), "=f"(d[103]), "=f"(d[104]), "=f"(d[105]), "=f"(d[106]), "=f"(d[107]), "=f"(d[108]), "=f"(d[109]), "=f"(d[110]), "=f"(d[111]), "=f"(d[112]), "=f"(d[113]), "=f"(d[114]), "=f"(d[115]), "=f"(d[116]), "=f"(d[117]), "=f"(d[118]), "=f"(d[119]), "=f"(d[120]), "=f"(d[121]), "=f"(d[122]), "=f"(d[123]), "=f"(d[124]), "=f"(d[125]), "=f"(d[126]), "=f"(d[127])
    : "r"(a[0]), "r"(a[1]), "r"(a[2]), "r"(a[3]), "l"(db));
}

constexpr int SLOT = 16384;
constexpr int VB = 4 * SLOT, PH = 0, XS = 6;
constexpr int SM_SD = 13 * SLOT;
constexpr int SM_BAR = SM_SD + 8192;
constexpr int SM_RS = SM_BAR + 1024;
constexpr int SM_AP = SM_RS + 640;
constexpr int SM_BP = SM_AP + 2048;
constexpr int SM_EPOCH = SM_BP + 6144;
constexpr int SM_TOTAL = SM_EPOCH + 16;
constexpr int FM = 0, FT = 16, FW = 30, CM = 46, CT = 62, CW = 76, B_EF = 92, B_STAT = 93, B_KVF = 94, B_HALO = 95,
              B_KVDONE = 96, B_OH0 = 97, B_OH1 = 98, B_XH0 = 99, B_XDONE = 100, B_WFD = 101, B_XT = 102, B_OF0 = 103, B_KVF1 = 104, B_RAW = 106  , B_X0 = 108;
#define EFS 0
constexpr uint64_t BAR_LG = EFS ? 0x00043333330001ull : 0x00043333330004ull;
#define BA(i) (bar + (i) * 8)
#define REL2(i) release2c(SB0 + SM_BAR + (i) * 8)
constexpr int NF = 4, ND = 12, NR = 0, NWOP = 48, NAOP = 37;
constexpr uint64_t TL_A = 0x278627862786ull, TL_B = 0xac39bac39bacull, WO_A = 0x65427396540139ffull, WO_B = 0xc8ba01c8ba27c68bull;
__constant__ uint32_t c_wop[NWOP + 1] = {0xea8009, 0x186b8000, 0x6c0112, 0x1aec011a, 0xec822b, 0x206d0224, 0x170330, 0x22970339, 0x18178442, 0x18180554, 0x18188660, 0x18190772, 0x18198884, 0x181a0990, 0x181a8aa2, 0x181b0bb4, 0x181b8cc0, 0xaed90fc, 0xa9791ea, 0x181c0dd2, 0xa9812db, 0x129893c9, 0x181c8ee4, 0x181d0ff0, 0x109d94b3, 0x109f15ac, 0x109f969a, 0x10a0178b, 0x10a09879, 0x10a11963, 0x10a19a5c, 0x10a21b4a, 0x9229e0b, 0x11232026, 0x9239f18, 0x1124213c, 0x13242247, 0x1124a352, 0x1324a46a, 0x1126257b, 0x1126a688, 0x1127a79c, 0x112828a1, 0x1128a9b0, 0x11292aca, 0x1129abdb, 0x112a2ce8, 0x112aadfc, 0};
__constant__ uint32_t c_aop[NAOP + 1] = {0x6d0228, 0x170336, 0x178447, 0x180558, 0x188666, 0x190777, 0x198888, 0x1a0996, 0x1a8aa7, 0x1b0bb8, 0x1b8cc6, 0x1c0dd7, 0x1c8ee8, 0x1d0ff6, 0x1d93c2, 0x1f14b6, 0x1f95a8, 0x201697, 0x209782, 0x211876, 0x219968, 0x221a57, 0x229b42, 0xa32029, 0xa3a133, 0xae2241, 0x2ae2350, 0x2ae2464, 0xa62575, 0xa72686, 0x2a72799, 0xa7a8a3, 0xa829b7, 0xa8aac2, 0xa92bd4, 0xa9ace5, 0xaa2df6, 0};
__constant__ uint32_t c_map[64] = {4, 5, 6, 7, 0, 16, 32, 48, 64, 80, 96, 112, 1, 17, 33, 49, 65, 81, 97, 113, 2, 18, 34, 50, 66, 82, 98, 114, 3, 19, 35, 51, 67, 83, 99, 115, 20, 36, 52, 68, 84, 100, 116, 21, 37, 53, 69, 85, 101, 117, 22, 38, 54, 70, 86, 102, 118, 23, 39, 55, 71, 87, 103, 119};
enum { MAP_WF = 0, MAP_WA = 2, MAP_WB = 4, MAP_WOA = 6, MAP_WOB = 8, MAP_X0 = 10, MAP_X = 11, MAP_O = 12, MAP_PHI = 13, NMAP = 14 };
struct Maps { CUtensorMap m[NMAP]; };

#define PL 2
#define PROFL(a, b)
#define SUBS 8
#define QORD 1
#define NCH 4
#define CHW 1
#define SUBS1 12
#define XRAT 10
#define XRN 4
#define BT1 1
#define CV0 0
#define ST1 8
#define X0AT 1
#define W1DL 400
#define SKA 0
#define SKB 0
#define BPRE 0
#define XST 3
#define NLAYERS 4
constexpr float L2E = 1.4426950408889634f;

#define D128(lo) desc64(lo, 0x40000040u)
struct Ctx { uint32_t zero, boff; const bf16* x0; bf16* out; };
#define BLK_CTX() \
  uint32_t bid_; asm volatile("mov.u32 %0, %%ctaid.x;" : "=r"(bid_)); \
  bid_ -= c.boff; \
  const uint32_t gr_ = c_map[bid_ >> 1]; \
  const int cr = bid_ & 1, g = gr_ & 7, rb = (gr_ >> 3) + cr, m0 = rb * 128; \
  const uint32_t sb = SB0 + (cr << 24); \
  const uint32_t bar = sb + SM_BAR; \
  (void)cr; (void)g; (void)rb; (void)m0; (void)bar;
extern __shared__ uint8_t smem_raw[];
constexpr uint32_t SB0 = 1024;

#define PHASE_CTX() \
  BLK_CTX(); \
  int tid_ = threadIdx.x; asm volatile("" : "+r"(tid_)); \
  const int lane = tid_ & 31, cw = (tid_ >> 5) - 4, wg = cw >> 2, wq = cw & 3, gq = lane >> 2, t = lane & 3, wrow0 = cw * 16; \
  const int lrow = (lane & 7) + ((lane >> 3) & 1) * 8, lchk = lane >> 4; \
  const bool elected = (tid_ & 127) == 0; \
  const uint32_t rowo = (wrow0 + lrow) * 128, X = (lchk ^ (lane & 7)) << 4; \
  const uint32_t Y = (wrow0 + (lane & 7)) * 128 + (((lane >> 3) ^ (lane & 7)) << 4); \
  const size_t gfr = (size_t)(m0 + wrow0 + gq) * D_ + g * 128 + 8 * t; \
  (void)bar; (void)wq; (void)gq; (void)lrow; (void)lchk; (void)elected; (void)wrow0; (void)wg; (void)rowo; (void)X; (void)t; (void)Y; (void)gfr;
#define MMA_CTX() \
  const uint32_t wu = __shfl_sync(0xffffffffu, wg, 0); \
  const uint32_t dA0 = ((SB0 >> 4) | (1u << 16)) + wu * 512, dB0 = (SB0 >> 4) | (512u << 16); \
  const uint32_t par = layer & 1;

__device__ __forceinline__ void slab_out_half(uint32_t slot, bf16* dst, int wrow0, int lane) {
  const int r0 = lane >> 3, ch = lane & 7;
  const uint32_t src = slot + (wrow0 + r0) * 128;
  uint4 v[4];
#pragma unroll
  for (int i = 0; i < 4; ++i) v[i] = lds128(src + i * 512 + (((ch ^ (4 * i + r0)) & 7) << 4));
  dst += (size_t)(wrow0 + r0) * D_ + ch * 8;
#pragma unroll
  for (int i = 0; i < 4; ++i) *reinterpret_cast<uint4*>(dst + (size_t)i * 4 * D_) = v[i];
}

__device__ __forceinline__ void consumer(const Ctx& c) {
  float acc[192];
  uint32_t xf[4][4];
  uint32_t xp[8][4];
  {
    PHASE_CTX();
    const unsigned int epoch = ld_relaxed(&g_epoch);
    PROFT(tid_ == 128, 0);
    const uint32_t wu = __shfl_sync(0xffffffffu, wg, 0);
    if (tid_ < 128 + 8) sts128(sb + SM_AP + lane * 16, make_uint4(0x3F803F80u, 0x3F803F80u, 0x3F803F80u, 0x3F803F80u));
#pragma unroll 1
    for (int it = 0; it < 2; ++it) {
      float p[4][16];
      mbar_wait(BA(B_RAW + it), 0);
      PROFT(tid_ == 128, it ? 15 : 2);
      const uint32_t da = ((SB0 >> 4) | (1u << 16)) + (wu ? 9 + it : 2 * it) * 1024, db = (SB0 + SM_SD) >> 4;
      wgmma_fence();
#pragma unroll
      for (int h = 0; h < 4; ++h) wgmma_n32_0(p[h], D128(da + (h >> 1) * 512 + (h & 1) * 4), desc64(db + h * 128, 0x80000020u));
#pragma unroll
      for (int h = 0; h < 4; ++h) wgmma_n32(p[h], D128(da + (h >> 1) * 512 + (h & 1) * 4 + 2), desc64(db + h * 128 + 64, 0x80000020u), 1);
      wgmma_commit();
      wgmma_wait<0>();
#pragma unroll
      for (int i = 0; i < 64; ++i) asm volatile("" : "+f"(p[i >> 4][i & 15]) :: "memory");
      const uint32_t base = sb + (wg ? 9 + it : 2 * it) * SLOT + (wq * 16 + gq) * 128;
      uint32_t w[4][4][2];
#pragma unroll
      for (int i = 0; i < 32; ++i) w[i >> 3][(i >> 1) & 3][i & 1] = pack_bf16(p[i >> 3][2 * (i & 7)], p[i >> 3][2 * (i & 7) + 1]);
      if (wu) {
#pragma unroll
        for (int i = 0; i < 8; ++i)
          sts128(base + (i >> 2) * 8192 + (i & 1) * 1024 + (((((i >> 1) & 1) * 4 + t) ^ gq) << 4), make_uint4(w[i >> 1][0][i & 1], w[i >> 1][1][i & 1], w[i >> 1][2][i & 1], w[i >> 1][3][i & 1]));
      } else {
#pragma unroll
        for (int i = 0; i < 16; ++i)
          sts64(base + (i >> 3) * 8192 + (i & 1) * 1024 + ((((t & 1) * 4 + ((i >> 1) & 3)) ^ gq) << 4) + (t >> 1) * 8, w[(i >> 3) * 2][(i >> 1) & 3][i & 1], w[(i >> 3) * 2 + 1][(i >> 1) & 3][i & 1]);
      }
      fence_async_smem();
      __syncwarp();
      if (it == cr && lane == 0) mbar_arrive(BA(B_WFD));
    }
    if (tid_ == 128) sts_f(sb + SM_EPOCH, __uint_as_float(epoch & 1));
#pragma unroll
    for (int i = 0; i < 32; ++i) xp[i >> 2][i & 3] = 0u;
    nbar<1, 256>();
    PROFT(tid_ == 128, 13);
    mbar_wait(BA(FM + cr), 0);
    float cs[3][4];
    wgmma_fence();
#pragma unroll
    for (int ks = 0; ks < 4; ++ks)
#pragma unroll
      for (int i = 0; i < 3; ++i) {
        const uint32_t bx = (i == 0 ? 2 * cr * 1024 : i == 1 ? (2 * cr + 1) * 1024 : (9 + cr) * 1024) + wu * 512;
        wgmma_n8_t(cs[i], D128(((SB0 >> 4) | (512u << 16)) + bx + ks * 128), desc64((SB0 + SM_AP) >> 4, 0), ks != 0);
      }
    wgmma_commit();
    mbar_wait(BA(FM), 0);
#pragma unroll
    for (int k = 0; k < 4; ++k) ldsm_x4(xf[k][0], xf[k][1], xf[k][2], xf[k][3], sb + XS * SLOT + rowo + (X ^ (k << 5)));
    wgmma_wait<0>();
#pragma unroll
    for (int i = 0; i < 12; ++i) asm volatile("" : "+f"(cs[i >> 2][i & 3]) :: "memory");
    if (t < 2) {
#pragma unroll
      for (int i = 0; i < 3; ++i) red_add1(g_cs + (epoch & 1) * 6144 + g * 384 + i * 128 + wg * 64 + wq * 16 + gq + t * 8, t ? cs[i][2] : cs[i][0]);
    }
    PROFT(tid_ == 128, 14);
  }
#pragma unroll 1
  for (int layer = 0;; ++layer) {
    {
      wgmma_fence();
      wgmma_n256_rs0(acc, xf[0], D128((SB0 >> 4) | (512u << 16)));
#pragma unroll
      for (int k = 1; k < 4; ++k) wgmma_n256_rs(acc, xf[k], D128(((SB0 >> 4) | (512u << 16)) + k * 128), 1);
      wgmma_commit();
      PHASE_CTX();
      MMA_CTX();
      {
        const uint32_t ep = __float_as_uint(lds_f(sb + SM_EPOCH));
        if (layer == 0) {
          mbar_wait(BA(B_X0), 0);
#pragma unroll
          for (int i = 0; i < 8; ++i) ldsm_x4(xp[i][0], xp[i][1], xp[i][2], xp[i][3], sb + (11 + (i >> 2)) * SLOT + (Y ^ ((i & 2) << 5)) + (i & 1) * 1024);
          if (lane == ((xp[0][0] ^ xp[1][0] ^ xp[2][0] ^ xp[3][0] ^ xp[7][0]) & c.zero)) REL2(B_XT);
        } else {
#pragma unroll
          for (int i = 0; i < 8; ++i) stsm_x4(sb + (XS + (i >> 2)) * SLOT + (Y ^ ((i & 2) << 5)) + (i & 1) * 1024, xp[i][0], xp[i][1], xp[i][2], xp[i][3]);
        }
        float s0 = 0.f, s1 = 0.f, q0 = 0.f, q1 = 0.f;
        auto stats = [&](int j0, int j1) {
#pragma unroll
          for (int j = j0; j < j1; ++j) {
            const uint32_t u0 = xp[(j >> 2) * 2][j & 3], u1 = xp[(j >> 2) * 2 + 1][j & 3];
            s0 += bf_lo(u0) + bf_hi(u0); s1 += bf_lo(u1) + bf_hi(u1);
            q0 = fmaf(bf_lo(u0), bf_lo(u0), fmaf(bf_hi(u0), bf_hi(u0), q0)); q1 = fmaf(bf_lo(u1), bf_lo(u1), fmaf(bf_hi(u1), bf_hi(u1), q1));
          }
        };
        stats(0, ST1);
        fence_async_smem();
        nbar_dyn(3 + wu + (__float_as_uint(s0 + s1 + q0 + q1) & c.zero), 128);
        mbar_wait(BA(FM + 1), par);
        wgmma_fence();
#pragma unroll
        for (int k = 0; k < 4; ++k) wgmma_n256(acc, D128(dA0 + (XS + 1) * 1024 + k * 2), D128(dB0 + 2048 + k * 128), 1);
        wgmma_commit();
        wgmma_wait<1>();
#pragma unroll
        for (int i = 4; i < 8; ++i) stg128_p(layer, g_x + gfr + (i & 1) * 8 * D_ + (i >> 1) * 32, xp[i][0], xp[i][1], xp[i][2], xp[i][3]);
        {
          uint32_t zc; asm volatile("mov.u32 %0, %%clock;" : "=r"(zc) :: "memory");
          q0 += __uint_as_float(zc & c.zero); q1 += __uint_as_float(zc & c.zero); s0 += __uint_as_float(zc & c.zero); s1 += __uint_as_float(zc & c.zero);
        }
        stats(ST1, 16);
        wgmma_fence();
        wgmma_n128_0(acc, D128(dA0 + XS * 1024), D128(dB0 + 9 * 1024));
#pragma unroll
        for (int k = 1; k < 4; ++k) wgmma_n128(acc, D128(dA0 + XS * 1024 + k * 2), D128(dB0 + 9 * 1024 + k * 128), 1);
        wgmma_commit();
        const bool od = t & 1;
        float sa = od ? s1 : s0, qa = od ? q1 : q0;
        sa += __shfl_xor_sync(0xffffffffu, od ? s0 : s1, 1);
        qa += __shfl_xor_sync(0xffffffffu, od ? q0 : q1, 1);
        wgmma_fence();
#pragma unroll
        for (int k = 0; k < 4; ++k) wgmma_n128(acc, D128(dA0 + (XS + 1) * 1024 + k * 2), D128(dB0 + 10 * 1024 + k * 128), 1);
        wgmma_commit();
        sa += __shfl_xor_sync(0xffffffffu, sa, 2);
        qa += __shfl_xor_sync(0xffffffffu, qa, 2);
        red_add2_p(t < 2, reinterpret_cast<float*>(g_stats + (ep * 4 + layer) * S_ + m0 + wrow0 + gq + t * 8), sa, qa);
        __syncwarp();
        if (lane == 0) mbar_arrive(BA(B_XDONE));
        wgmma_wait<1>();
        if (elected) REL2(CM);
      }
      uint32_t s = 2;
#pragma unroll 1
      for (int i = 2; i < NF; ++i) {
        PROFL(tid_ == 128 && layer == PL + 1, 244 + 2 * i);
        mbar_wait(BA(FM + i), par);
        PROFL(tid_ == 128 && layer == PL + 1, 245 + 2 * i);
        const uint32_t da = dA0 + (XS + s) * 1024, dk = dB0 + s * 2048, dq = dB0 + (9 + s) * 1024;
        wgmma_fence();
#pragma unroll
        for (int k = 0; k < 4; ++k) wgmma_n128(acc, D128(da + k * 2), D128(dq + k * 128), 1);
        wgmma_commit();
        wgmma_wait<1>();
        if (elected) REL2(CM + i - 1);
        wgmma_fence();
#pragma unroll
        for (int k = 0; k < 4; ++k) wgmma_n256(acc, D128(da + k * 2), D128(dk + k * 128), 1);
        wgmma_commit();
        if (++s == 3) s = 0;
      }
#pragma unroll 1
      for (int i = NF; i < 15; ++i) {
        mbar_wait(BA(FM + i), par);
        const uint32_t da = dA0 + (XS + s) * 1024, dk = dB0 + s * 2048;
        wgmma_fence();
#pragma unroll
        for (int k = 0; k < 4; ++k) wgmma_n256(acc, D128(da + k * 2), D128(dk + k * 128), 1);
        wgmma_commit();
        wgmma_wait<1>();
        if (elected) REL2(CM + i - 1);
        if (++s == 3) s = 0;
      }
      {
        const uint64_t dap = desc64(((SB0 + SM_AP) >> 4) + wu * 64, 8), dbp = make_desc_ns(SB0 + SM_BP, 0, 128);
        mbar_wait(BA(B_STAT), par);
        mbar_wait(BA(FM + 15), par);
        PROFT(tid_ == 128, layer * 16 + 9);
        wgmma_fence();
        wgmma_n256_k(acc, dap, dbp, 1);
#pragma unroll
        for (int k = 0; k < 4; ++k) wgmma_n256(acc, D128(dA0 + XS * 1024 + k * 2), D128(dB0 + k * 128), 1);
        wgmma_commit();
        wgmma_wait<1>();
        if (elected) REL2(CM + 14);
        mbar_wait(BA(FT), par);
        wgmma_fence();
        wgmma_n128_k(acc, dap, dbp + 256, 1);
#pragma unroll
        for (int k = 0; k < 4; ++k) wgmma_n128(acc, D128(dA0 + (uint32_t)(TL_A & 15) * 1024 + k * 2), D128(dB0 + (uint32_t)(TL_B & 15) * 1024 + k * 128), 1);
        wgmma_commit();
        wgmma_wait<1>();
        if (elected) REL2(CM + 15);
#pragma unroll
        for (int i = 0; i < 128; ++i) asm volatile("" : "+f"(acc[i]) :: "memory");
      }
    }
    uint32_t of[8][4], o1[4][4];
    {
      PHASE_CTX();
      MMA_CTX();
      PROFT(tid_ == 128, layer * 16 + 1);
      PROFT(lane == 0 && layer == PL, 192 + cw);
      PROFT(tid_ == 128 && layer == PL, 160);
      uint64_t ta = (TL_A >> 4), tw = TL_B >> 4;
      uint32_t da, db, dz = dA0;
      auto sub = [&](int n) {
        const int j = n >> 2, k = n & 3;
        if (k == 0) {
          dz += c.zero;
          da = dz + ((uint32_t)ta & 15) * 1024; db = dB0 + ((uint32_t)tw & 15) * 1024;
          ta >>= 4; tw >>= 4;
          mbar_wait(BA(FT + j), par);
          wgmma_fence();
        }
        wgmma_n128(acc, D128(da + k * 2), D128(db + k * 128), 1);
        if (k == 3) {
          wgmma_commit();
          wgmma_wait<1>();
          if (elected) REL2(CT + j - 1);
        }
      };
      auto run = [&](int j0, int j1) {
#pragma unroll 1
        for (int j = j0; j < j1; ++j) {
          mbar_wait(BA(FT + j), par);
          da = dA0 + ((uint32_t)ta & 15) * 1024; db = dB0 + ((uint32_t)tw & 15) * 1024;
          ta >>= 4; tw >>= 4;
          wgmma_fence();
#pragma unroll
          for (int k = 0; k < 4; ++k) wgmma_n128(acc, D128(da + k * 2), D128(db + k * 128), 1);
          wgmma_commit();
          wgmma_wait<1>();
          if (elected) REL2(CT + j - 1);
        }
        ta = TL_A >> (4 * j1); tw = TL_B >> (4 * j1);
      };
      auto rest = [&](int j0, int sk) {
        if (sk) {
          run(j0, ND - sk);
          if (wu == 0) nbar<6, 256>();
          j0 = ND - sk;
        }
        run(j0, ND);
        if (sk && wu) asm volatile("bar.arrive 6, 256;" ::: "memory");
      };
      auto rest_end = [&]() {
        wgmma_wait<0>();
        if (elected) REL2(CT + ND - 1);
#pragma unroll
        for (int i = 128; i < 192; ++i) asm volatile("" : "+f"(acc[i]) :: "memory");
      };
      auto wo0 = [&]() {
        wgmma_fence();
        wgmma_n128_rs0(acc, of[0], D128(dB0 + (uint32_t)(WO_B & 15) * 1024));
#pragma unroll
        for (int k = 1; k < 4; ++k) wgmma_n128_rs(acc, of[k], D128(dB0 + (uint32_t)(WO_B & 15) * 1024 + k * 128), 1);
        wgmma_commit();
      };
      const float rs0 = lds_f(sb + SM_RS + (16 + wrow0 + gq) * 4), rs1 = lds_f(sb + SM_RS + (24 + wrow0 + gq) * 4);
#define EPOCH() __float_as_uint(lds_f(sb + SM_EPOCH))
      mbar_wait(BA(CM + 14), par);
      if (par) {
        uint32_t kk[8][4], kp[8][4], vf[2][2][4][4];
        int sn = 4;
#pragma unroll
        for (int i = 0; i < 4 * BT1; ++i) sub(sn++);
        {
          uint32_t vv[8][4];
#pragma unroll
          for (int jp = 0; jp < 8; ++jp) {
            kk[jp][0] = pack_bf16(acc[8 * jp], acc[8 * jp + 1]); kk[jp][1] = pack_bf16(acc[8 * jp + 4], acc[8 * jp + 5]);
            kk[jp][2] = pack_bf16(acc[8 * jp + 2], acc[8 * jp + 3]); kk[jp][3] = pack_bf16(acc[8 * jp + 6], acc[8 * jp + 7]);
#pragma unroll
            for (int i = 0; i < 4; ++i) vv[jp][i] = pack_bf16(acc[64 + 8 * jp + 2 * i], acc[65 + 8 * jp + 2 * i]);
          }
          if (cw == 7) {
            uint32_t* const hbuf = g_halo + (size_t)(((layer >> 1) * 17 + rb + 1) * 8 + g) * 2048;
#pragma unroll
            for (int jp = 0; jp < 8; ++jp) stg128(hbuf + jp * 128 + lane * 4, kk[jp][0], kk[jp][1], kk[jp][2], kk[jp][3]);
#pragma unroll
            for (int i = 0; i < 32; ++i) hbuf[1024 + (i >> 4) * 512 + (gq + (i & 1) * 8) * 32 + ((((i >> 1) & 7) ^ gq) << 2) + t] = vv[i >> 2][i & 3];
            __syncwarp();
            if (lane == 0) mbar_arrive(BA(B_OF0));
          }
#pragma unroll
          for (int jp = 0; jp < 8; ++jp) {
            sub(sn++);
            stsm_x4(sb + VB + (jp >> 2) * SLOT + rowo + (X ^ ((jp & 3) << 5)), vv[jp][0], vv[jp][1], vv[jp][2], vv[jp][3]);
          }
        }
        PROFT(tid_ == 128, layer * 16 + 2);
        const int e = gq & 1;
        float f0[4], f1[4], b0[4], b1[4], rj[4];
#pragma unroll
        for (int nt = 0; nt < 4; ++nt) {
          const int kx = nt * 8 + 2 * t + e;
          const bool okk = (m0 + wrow0 + kx) >= 16;
          const int d0 = kx - gq, d1 = d0 - 8;
          rj[nt] = lds_f(sb + SM_RS + (wrow0 + kx) * 4);
          const bool m0_ = okk && d0 >= 2 && d0 <= 16, m1_ = okk && d1 >= 2 && d1 <= 16;
          f0[nt] = m0_ ? rj[nt] * rs0 * (0.17677669529663687f * L2E) : 0.f;
          f1[nt] = m1_ ? rj[nt] * rs1 * (0.17677669529663687f * L2E) : 0.f;
          b0[nt] = m0_ ? 0.f : -1e30f; b1[nt] = m1_ ? 0.f : -1e30f;
        }
        mbar_wait(BA(CM + 15), par);
#pragma unroll
        for (int jp = 0; jp < 8; ++jp) {
          sub(sn++);
          sts128(sb + PH + cw * 4096 + jp * 512 + lane * 16, make_uint4(kk[jp][0], kk[jp][1], kk[jp][2], kk[jp][3]));
        }
#pragma unroll
        for (int i = 0; i < 4; ++i) sub(sn++);
        nbar<1, 256>();
        PROFT(tid_ == 128, layer * 16 + 3);
        rest(sn >> 2, SKB);
        if (!BPRE) rest_end();
        PROFT(lane == 0 && layer == PL, 200 + cw);
        PROFT(tid_ == 128, layer * 16 + 10);
        if (cw == 0) mbar_wait(BA(B_HALO), (layer >> 1) & 1);
        PROFT(tid_ == 128, layer * 16 + 5);
        const uint32_t vs = sb + (cw ? VB + rowo - 2048 : SM_SD + 4096 + rowo), vst = cw ? SLOT : 2048;
        const uint32_t psel = e ? 0x1054u : 0x5410u;
#pragma unroll
        for (int hp = 0; hp < 2; ++hp) {
#pragma unroll
          for (int i = 4 * hp; i < 4 * hp + 4; ++i) {
            const uint4 u = lds128(sb + (cw ? PH + (cw - 1) * 4096 : SM_SD) + lane * 16 + i * 512);
            kp[i][0] = u.x; kp[i][1] = u.y; kp[i][2] = u.z; kp[i][3] = u.w;
          }
#pragma unroll
          for (int i = 4 * hp; i < 4 * hp + 4; ++i) {
            ldsm_x4_t(vf[0][i & 1][i >> 1][0], vf[0][i & 1][i >> 1][1], vf[0][i & 1][i >> 1][2], vf[0][i & 1][i >> 1][3], vs + (i >> 2) * vst + (X ^ ((i & 3) << 5)));
            ldsm_x4_t(vf[1][i & 1][i >> 1][0], vf[1][i & 1][i >> 1][1], vf[1][i & 1][i >> 1][2], vf[1][i & 1][i >> 1][3], sb + VB + (i >> 2) * SLOT + rowo + (X ^ ((i & 3) << 5)));
          }
          if (BPRE && !hp) rest_end();
          float l0[2][4], l1[2][4];
#pragma unroll
          for (int h = 0; h < 2; ++h) {
            const int H = 2 * hp + h;
            uint32_t qa[8];
#pragma unroll
            for (int i = 0; i < 8; ++i) qa[i] = pack_bf16(acc[128 + 16 * H + 2 * i], acc[129 + 16 * H + 2 * i]);
#pragma unroll
            for (int nt = 3; nt >= 0; --nt) {
              float sc[4] = {0.f, 0.f, 0.f, 0.f};
#pragma unroll
              for (int ks = 0; ks < 2; ++ks) {
                const uint32_t (&kf)[4] = nt < 2 ? kp[2 * H + ks] : kk[2 * H + ks];
                mma_bf16(sc, qa[4 * ks], qa[4 * ks + 1], qa[4 * ks + 2], qa[4 * ks + 3], kf[2 * (nt & 1)], kf[2 * (nt & 1) + 1]);
              }
              l0[h][nt] = fmaf(e ? sc[1] : sc[0], f0[nt], b0[nt]);
              l1[h][nt] = fmaf(e ? sc[3] : sc[2], f1[nt], b1[nt]);
            }
          }
          float mx0[2], mx1[2], s0[2], s1[2];
#pragma unroll
          for (int h = 0; h < 2; ++h) {
            mx0[h] = fmaxf(fmaxf(l0[h][0], l0[h][1]), l0[h][2]);
            mx1[h] = fmaxf(fmaxf(l1[h][1], l1[h][2]), l1[h][3]);
          }
#pragma unroll
          for (int o = 1; o <= 2; o <<= 1)
#pragma unroll
            for (int h = 0; h < 2; ++h) {
              mx0[h] = fmaxf(mx0[h], __shfl_xor_sync(0xffffffffu, mx0[h], o));
              mx1[h] = fmaxf(mx1[h], __shfl_xor_sync(0xffffffffu, mx1[h], o));
            }
#pragma unroll
          for (int h = 0; h < 2; ++h) {
#pragma unroll
            for (int nt = 0; nt < 3; ++nt) { l0[h][nt] = ex2(l0[h][nt] - mx0[h]); l1[h][nt + 1] = ex2(l1[h][nt + 1] - mx1[h]); }
            s0[h] = (l0[h][0] + l0[h][1]) + l0[h][2];
            s1[h] = (l1[h][1] + l1[h][2]) + l1[h][3];
          }
#pragma unroll
          for (int o = 1; o <= 2; o <<= 1)
#pragma unroll
            for (int h = 0; h < 2; ++h) {
              s0[h] += __shfl_xor_sync(0xffffffffu, s0[h], o);
              s1[h] += __shfl_xor_sync(0xffffffffu, s1[h], o);
            }
          uint32_t ow[2][2][4];
#pragma unroll
          for (int h = 0; h < 2; ++h) {
            const int H = 2 * hp + h;
            uint32_t pl[4], ph[4];
            const float i0 = rcp(s0[h]), i1 = rcp(s1[h]);
#pragma unroll
            for (int nt = 0; nt < 4; ++nt) {
              const uint32_t pk = pack_bf16(nt < 3 ? l0[h][nt] * i0 * rj[nt] : 0.f, nt > 0 ? l1[h][nt] * i1 * rj[nt] : 0.f);
              pl[nt] = nt < 3 ? __byte_perm(pk, 0u, psel) : 0u;
              ph[nt] = nt > 0 ? __byte_perm(pk, 0u, psel + 0x2222u) : 0u;
            }
#pragma unroll
            for (int nj = 0; nj < 4; ++nj) {
              float oa[4] = {0.f, 0.f, 0.f, 0.f};
#pragma unroll
              for (int ks = 0; ks < 2; ++ks)
                mma_bf16(oa, pl[2 * ks], ph[2 * ks], pl[2 * ks + 1], ph[2 * ks + 1], vf[ks][nj >> 1][H][2 * (nj & 1)], vf[ks][nj >> 1][H][2 * (nj & 1) + 1]);
              ow[h][0][nj] = pack_bf16(oa[0], oa[1]); ow[h][1][nj] = pack_bf16(oa[2], oa[3]);
            }
          }
          if (hp == 0) {
#pragma unroll
            for (int i = 0; i < 4; ++i) stg128(g_o + gfr + (i & 1) * 8 * D_ + (i >> 1) * 32, ow[i >> 1][i & 1][0], ow[i >> 1][i & 1][1], ow[i >> 1][i & 1][2], ow[i >> 1][i & 1][3]);
            __syncwarp();
            if (lane == 0) mbar_arrive(BA(B_OH0));
          } else {
#pragma unroll
            for (int i = 0; i < 16; ++i) o1[i >> 2][i & 3] = ow[i >> 3][(i >> 2) & 1][i & 3];
          }
#pragma unroll
          for (int i = 0; i < 16; ++i) of[4 * hp + (i >> 2)][i & 3] = ow[i >> 3][i & 1][(i >> 1) & 3];
          if (!hp) { PROFT(tid_ == 128, layer * 16 + 15); mbar_wait(BA(FW), par); }
        }
      } else {
        float sc[2] = {rs0 * L2E, rs1 * L2E};
        {
          const uint32_t vb = sb + VB + (rowo >> 1), X0 = (lchk ^ ((lane & 7) >> 1)) << 4;
          const uint32_t pb = sb + PH + (t & 1) * SLOT + (wrow0 + gq) * 128 + ((((t & 1) * 4 + (t & 2)) ^ gq) << 4);
          float kva[20], en[32], mx[2][2], mn[2][2];
#define PV(hp, j) acc[32 * (hp) + (j)]
          auto mm = [&](int hp, int j) {
            const int r = (j >> 1) & 1;
            if (j < 4 && !(j & 1)) { mx[hp][r] = PV(hp, j); mn[hp][r] = PV(hp, j); }
            else { mx[hp][r] = fmaxf(mx[hp][r], PV(hp, j)); mn[hp][r] = fminf(mn[hp][r], PV(hp, j)); }
          };
          auto mmx = [&](int hp) {
#pragma unroll
            for (int r = 0; r < 2; ++r) {
              mx[hp][r] = fmaxf(mx[hp][r], __shfl_xor_sync(0xffffffffu, mx[hp][r], 2)) * -sc[r];
              mn[hp][r] = fmaf(fminf(mn[hp][r], __shfl_xor_sync(0xffffffffu, mn[hp][r], 2)), sc[r], mx[hp][r]);
            }
          };
          auto stage = [&](int hp) {
#pragma unroll
            for (int i = 0; i < 20; ++i) asm volatile("" : "+f"(kva[i]) :: "memory");
            nbar_dyn(3 + wu, 128);
#pragma unroll
            for (int i = 0; i < 4; ++i)
              sts128(sb + VB + hp * SLOT + wg * 8192 + (wq * 128 + i * 32 + lane) * 16,
                     make_uint4(__float_as_uint(kva[4 * i]), __float_as_uint(kva[4 * i + 1]), __float_as_uint(kva[4 * i + 2]), __float_as_uint(kva[4 * i + 3])));
            if (t == 0) sts_f2(sb + SM_AP + ((2 * hp + wg) * 64 + wq * 16 + gq * 2) * 4, kva[16], kva[18]);
            fence_async_smem();
            __syncwarp();
            if (lane == 0) mbar_arrive(BA(B_KVDONE));
          };
          int sn = 4;
#pragma unroll
          for (int j = 0; j < 32; ++j) mm(0, j);
          mmx(0);
#pragma unroll
          for (int hp = 0; hp < 2; ++hp) {
            float sp[2] = {0.f, 0.f}, sm[2] = {0.f, 0.f};
#pragma unroll
            for (int j = 0; j < 32; ++j) {
              const int r = (j >> 1) & 1, ns = hp ? SUBS1 : SUBS;
              if ((j * ns) / 32 != ((j + 1) * ns) / 32) {
                sub(sn++);
                if (hp && sn == 4 + SUBS + 4 + 4 * (XST & 1)) { stage(0); PROFT(tid_ == 128, layer * 16 + 12); }
              }
              const float x = fmaf(PV(hp, j), sc[r], mx[hp][r]);
              PV(hp, j) = ex2(x); en[j] = ex2(mn[hp][r] - x);
              sp[r] += PV(hp, j); sm[r] += en[j];
              if (hp == 0) {
                mm(1, j);
                if ((j & 3) == 0) {
                  const int jp = 8 + (j >> 2);
                  stsm_x4(vb + ((jp - 8) >> 1) * 8192 + (X0 ^ ((jp & 1) << 5)), pack_bf16(acc[8 * jp], acc[8 * jp + 1]), pack_bf16(acc[8 * jp + 2], acc[8 * jp + 3]),
                          pack_bf16(acc[8 * jp + 4], acc[8 * jp + 5]), pack_bf16(acc[8 * jp + 6], acc[8 * jp + 7]));
                }
              }
            }
#pragma unroll
            for (int i = 0; i < 4; ++i) if (XST & (1 << hp)) sub(sn++);
#pragma unroll
            for (int r = 0; r < 2; ++r) {
              sp[r] = rcp(sp[r] + __shfl_xor_sync(0xffffffffu, sp[r], 2)) * (r ? rs1 : rs0);
              sm[r] = rcp(sm[r] + __shfl_xor_sync(0xffffffffu, sm[r], 2)) * (r ? rs1 : rs0);
            }
            if (hp == 0) { mmx(1); mbar_wait(BA(CM + 15), par); }
            else { PROFT(tid_ == 128, layer * 16 + 11); nbar<1, 256>(); }
#pragma unroll
            for (int i = 0; i < 4; ++i) {
              const int r = i & 1, d = 16 * (i >> 1) + 2 * r;
              sts128((pb + r * 1024) ^ ((i >> 1) << 4), make_uint4(pack_bf16(PV(hp, d) * sp[r], PV(hp, d + 1) * sp[r]), pack_bf16(PV(hp, d + 4) * sp[r], PV(hp, d + 5) * sp[r]),
                                                                    pack_bf16(PV(hp, d + 8) * sp[r], PV(hp, d + 9) * sp[r]), pack_bf16(PV(hp, d + 12) * sp[r], PV(hp, d + 13) * sp[r])));
              sts128((pb + r * 1024) ^ ((i >> 1) << 4) ^ 64, make_uint4(pack_bf16(en[d] * sm[r], en[d + 1] * sm[r]), pack_bf16(en[d + 4] * sm[r], en[d + 5] * sm[r]),
                                                                         pack_bf16(en[d + 8] * sm[r], en[d + 9] * sm[r]), pack_bf16(en[d + 12] * sm[r], en[d + 13] * sm[r])));
            }
            fence_async_smem();
            nbar<1, 256>();
            const uint32_t dP = dB0 + (PH >> 4) + wu * 1024;
            const uint32_t dV = (dB0 & 0xFFFFu) + ((VB + hp * SLOT) >> 4) + (((SM_SD - VB - hp * SLOT) >> 4) << 16) + wu * (512u - (512u << 16));
            wgmma_fence();
#pragma unroll
            for (int ks = 0; ks < 8; ++ks) wgmma_n40_tt(kva, D128(dP + ks * 128), desc64(dV + ks * 64, 0x80000020u), ks != 0);
            wgmma_commit();
          }
#pragma unroll
          for (int i = 0; i < 4; ++i) sub(sn++);
          stage(1);
          PROFT(tid_ == 128, layer * 16 + 3);
          rest(sn >> 2, SKA);
          rest_end();
          PROFT(lane == 0 && layer == PL, 200 + cw);
          PROFT(tid_ == 128, layer * 16 + 10);
        }
#define QV(H, i) acc[128 + 16 * (H) + (i)]
        float mx[4][2], mn[4][2];
        uint32_t ph[4][4][4];
        auto mnx = [&](int hp) {
#pragma unroll
          for (int H = 2 * hp; H < 2 * hp + 2; ++H)
#pragma unroll
            for (int r = 0; r < 2; ++r) {
              mx[H][r] = fmaxf(fmaxf(fmaxf(QV(H, 2 * r), QV(H, 2 * r + 1)), fmaxf(QV(H, 4 + 2 * r), QV(H, 5 + 2 * r))),
                               fmaxf(fmaxf(QV(H, 8 + 2 * r), QV(H, 9 + 2 * r)), fmaxf(QV(H, 12 + 2 * r), QV(H, 13 + 2 * r))));
              mn[H][r] = fminf(fminf(fminf(QV(H, 2 * r), QV(H, 2 * r + 1)), fminf(QV(H, 4 + 2 * r), QV(H, 5 + 2 * r))),
                               fminf(fminf(QV(H, 8 + 2 * r), QV(H, 9 + 2 * r)), fminf(QV(H, 12 + 2 * r), QV(H, 13 + 2 * r))));
            }
#pragma unroll
          for (int o = 1; o <= 2; o <<= 1)
#pragma unroll
            for (int H = 2 * hp; H < 2 * hp + 2; ++H)
#pragma unroll
              for (int r = 0; r < 2; ++r) {
                mx[H][r] = fmaxf(mx[H][r], __shfl_xor_sync(0xffffffffu, mx[H][r], o));
                mn[H][r] = fminf(mn[H][r], __shfl_xor_sync(0xffffffffu, mn[H][r], o));
              }
#pragma unroll
          for (int H = 2 * hp; H < 2 * hp + 2; ++H)
#pragma unroll
            for (int r = 0; r < 2; ++r) { mx[H][r] *= -sc[r]; mn[H][r] = fmaf(mn[H][r], sc[r], mx[H][r]); }
        };
        auto fm = [&](int H) {
#pragma unroll
          for (int i = 0; i < 8; ++i) {
            const int r = i & 1;
            const float x0 = fmaf(QV(H, 2 * i), sc[r], mx[H][r]), x1 = fmaf(QV(H, 2 * i + 1), sc[r], mx[H][r]);
            ph[H][i >> 2][i & 3] = pack_bf16(ex2(x0), ex2(x1));
            ph[H][2 + (i >> 2)][i & 3] = pack_bf16(ex2(mn[H][r] - x0), ex2(mn[H][r] - x1));
          }
        };
        auto conv = [&](int hp) {
          mbar_wait(BA(hp ? B_KVF1 : B_KVF), (layer >> 1) & 1);
          PROFT(tid_ == 128, layer * 16 + (hp ? 4 : 5));
          if (hp) { mbar_wait(BA(FW), par); nbar_dyn(3 + wu, 128); }
#pragma unroll
          for (int h = 0; h < 2; ++h) {
            uint4 u[4];
#pragma unroll
            for (int i = 0; i < 4; ++i) u[i] = lds128(sb + VB + hp * SLOT + h * 8192 + (wq * 128 + i * 32 + lane) * 16);
            const float zz = lds_f(sb + SM_AP + ((2 * hp + h) * 64 + wq * 16 + (lane & 7) * 2 + ((lane >> 3) & 1)) * 4);
            const uint32_t kb_ = sb + PH + wg * SLOT + h * 8192 + (wq * 16 + lrow) * 128;
#pragma unroll
            for (int i = 0; i < 4; i += 2)
              stsm_x4(kb_ + (X ^ (i << 4)),
                      pack_bf16(__uint_as_float(u[i].x), __uint_as_float(u[i].y)), pack_bf16(__uint_as_float(u[i].z), __uint_as_float(u[i].w)),
                      pack_bf16(__uint_as_float(u[i + 1].x), __uint_as_float(u[i + 1].y)), pack_bf16(__uint_as_float(u[i + 1].z), __uint_as_float(u[i + 1].w)));
            const uint32_t z1 = pack_bf16(zz, 1.f);
            if (lane < 16) sts128(kb_ + ((4 ^ (lane & 7)) << 4), make_uint4(z1, z1, z1, z1));
          }
          fence_async_smem();
        };
        mnx(0);
        fm(0);
        if (CV0) conv(0);
        fm(1);
        if (!CV0) conv(0);
#pragma unroll
        for (int hp = 0; hp < 2; ++hp) {
          nbar_dyn(3 + wu, 128);
          float oa[4][20];
          wgmma_fence();
#pragma unroll
          for (int s = 0; s < 2; ++s)
#pragma unroll
            for (int v = 0; v < 4; ++v) {
              const int h = v >> 1, s4 = 2 * (v & 1) + s;
              wgmma_n40_rs(oa[v], ph[2 * hp + h][s4], D128(dB0 + (PH >> 4) + wu * 1024 + h * 512 + (s4 ^ (2 * h)) * 128), s != 0);
            }
          wgmma_commit();
          if (hp == 0) { mnx(1); wgmma_wait<0>(); }
          else wgmma_wait<0>();
#pragma unroll
          for (int i = 0; i < 20; ++i) asm volatile("" : "+f"(oa[0][i]), "+f"(oa[1][i]), "+f"(oa[2][i]), "+f"(oa[3][i]) :: "memory");
          uint32_t ow[2][2][4];
#pragma unroll
          for (int h = 0; h < 2; ++h)
#pragma unroll
            for (int r = 0; r < 2; ++r) {
              const float a = oa[2 * h + 1][17 + 2 * r], b = oa[2 * h][17 + 2 * r];
              const float id = rcp(fmaf(oa[2 * h][16 + 2 * r], a, fmaf(a, 1e-6f, oa[2 * h + 1][16 + 2 * r]) * b));
              const float fa = a * id, fb = b * id;
#pragma unroll
              for (int j = 0; j < 4; ++j)
                ow[h][r][j] = pack_bf16(fmaf(oa[2 * h][4 * j + 2 * r], fa, oa[2 * h + 1][4 * j + 2 * r] * fb),
                                        fmaf(oa[2 * h][4 * j + 2 * r + 1], fa, oa[2 * h + 1][4 * j + 2 * r + 1] * fb));
            }
#pragma unroll
          for (int i = 0; i < 16; ++i) of[4 * hp + (i >> 2)][i & 3] = ow[i >> 3][i & 1][(i >> 1) & 3];
          if (hp == 0) {
#pragma unroll
            for (int i = 0; i < 8; ++i) {
              if (!(i & 1)) stg128(g_o + gfr + ((i >> 1) & 1) * 8 * D_ + (i >> 2) * 32, ow[i >> 2][(i >> 1) & 1][0], ow[i >> 2][(i >> 1) & 1][1], ow[i >> 2][(i >> 1) & 1][2], ow[i >> 2][(i >> 1) & 1][3]);
              const int r = i & 1;
              const float x0 = fmaf(QV(2, 2 * i), sc[r], mx[2][r]), x1 = fmaf(QV(2, 2 * i + 1), sc[r], mx[2][r]);
              ph[2][i >> 2][i & 3] = pack_bf16(ex2v(x0), ex2v(x1));
              ph[2][2 + (i >> 2)][i & 3] = pack_bf16(ex2v(mn[2][r] - x0), ex2v(mn[2][r] - x1));
            }
            __syncwarp();
            if (lane == 0) mbar_arrive(BA(B_OH0));
            PROFT(tid_ == 128 && layer, layer * 16 + 15);
            if (QORD) { fm(3); conv(1); } else { conv(1); fm(3); }
          } else {
#pragma unroll
            for (int i = 0; i < 16; ++i) o1[i >> 2][i & 3] = ow[i >> 3][(i >> 2) & 1][i & 3];
          }
        }
      }
      PROFT(tid_ == 128, layer * 16 + 6);
#pragma unroll
      for (int i = 0; i < 4; ++i) stg128(g_o + gfr + (i & 1) * 8 * D_ + (2 + (i >> 1)) * 32, o1[i][0], o1[i][1], o1[i][2], o1[i][3]);
      __syncwarp();
      if (lane == 0) { mbar_arrive(BA(B_OH1)); if (!EFS) REL2(B_EF); }
      PROFT(lane == 0 && layer == PL, 208 + cw);
      wo0();
    }
    {
      PHASE_CTX();
      MMA_CTX();
      mbar_wait(BA(FW + 1), par);
      wgmma_fence();
#pragma unroll
      for (int k = 0; k < 4; ++k) wgmma_n128_rs(acc, of[4 + k], D128(dB0 + (uint32_t)((WO_B >> 4) & 15) * 1024 + k * 128), 1);
      wgmma_commit();
      wgmma_wait<1>();
      if (elected) REL2(CW);
      uint64_t ta = WO_A >> 8, tw = WO_B >> 8;
      auto run = [&](int i0, int i1) {
#pragma unroll 1
        for (int i = i0; i < i1; ++i) {
          mbar_wait(BA(FW + i), par);
          PROFL(tid_ == 128 && layer == PL, 160 + i);
          const uint32_t da = dA0 + ((uint32_t)ta & 15) * 1024, db = dB0 + ((uint32_t)tw & 15) * 1024;
          ta >>= 4; tw >>= 4;
          wgmma_fence();
#pragma unroll
          for (int k = 0; k < 4; ++k) wgmma_n128(acc, D128(da + k * 2), D128(db + k * 128), 1);
          wgmma_commit();
          wgmma_wait<1>();
          if (elected) REL2(CW + i - 1);
        }
        ta = WO_A >> (4 * (i1 & 15)); tw = WO_B >> (4 * (i1 & 15));
      };
      run(2, XRAT);
#pragma unroll
      for (int j = 0; j < 8 / XRN; ++j) {
#pragma unroll
        for (int i = j * XRN; i < (j + 1) * XRN; ++i) ldg128((layer ? g_x : c.x0) + gfr + (i & 1) * 8 * D_ + (i >> 1) * 32, xp[i][0], xp[i][1], xp[i][2], xp[i][3]);
        run(XRAT + j, j + 1 < 8 / XRN ? XRAT + j + 1 : 16);
      }
      if (layer == 0) {
#pragma unroll
        for (int o = 1; o <= 2; o <<= 1)
#pragma unroll
          for (int i = 0; i < 16; ++i) {
            const int j = o == 1 ? 2 * (i & 1) : (i & 1);
            uint32_t &a = xp[i >> 1][j], &b = xp[i >> 1][j + o];
            const uint32_t r = __shfl_xor_sync(0xffffffffu, (t & o) ? a : b, o);
            if (t & o) a = r; else b = r;
          }
      }
      if (layer != NLAYERS - 1) mbar_wait(BA(FM), par ^ 1);
      wgmma_wait<0>();
#pragma unroll
      for (int i = 128; i < 192; ++i) asm volatile("" : "+f"(acc[i]) :: "memory");
      if (elected) REL2(CW + 15);
      PROFT(lane == 0 && layer == PL, 216 + cw);
      PROFT(tid_ == 128, layer * 16 + 7);
#pragma unroll
      for (int i = 0; i < 32; ++i)
        xp[i >> 2][i & 3] = add_bf16x2(xp[i >> 2][i & 3], pack_bf16(acc[128 + 16 * (i >> 3) + 4 * (i & 3) + 2 * ((i >> 2) & 1)], acc[129 + 16 * (i >> 3) + 4 * (i & 3) + 2 * ((i >> 2) & 1)]));
      if (layer == NLAYERS - 1) {
#pragma unroll
        for (int i = 0; i < 8; ++i) stsm_x4(sb + (XS + (i >> 2)) * SLOT + (Y ^ ((i & 2) << 5)) + (i & 1) * 1024, xp[i][0], xp[i][1], xp[i][2], xp[i][3]);
        __syncwarp();
        slab_out_half(sb + XS * SLOT, c.out + (size_t)m0 * D_ + g * 128, wrow0, lane);
        slab_out_half(sb + (XS + 1) * SLOT, c.out + (size_t)m0 * D_ + g * 128 + 64, wrow0, lane);
        PROFT(tid_ == 128, layer * 16 + 24);
        break;
      }
#pragma unroll
      for (int i = 0; i < 4; ++i) stg128(g_x + gfr + (i & 1) * 8 * D_ + (i >> 1) * 32, xp[i][0], xp[i][1], xp[i][2], xp[i][3]);
      __syncwarp();
      if (lane == 0) mbar_arrive(BA(B_XH0));
#pragma unroll
      for (int i = 0; i < 16; ++i) xf[i >> 2][i & 3] = xp[2 * (i >> 3) + (i & 1)][(i >> 1) & 3];
      PROFT(tid_ == 128, layer * 16 + 24);
    }
  }
}

__device__ __forceinline__ uint64_t k_order(int o) {
  const uint32_t lo = (1u << (4 * o)) - 1u, h0 = (0xECA86420u & lo) | ((0xECA86420u >> 4) & ~lo);
  return (uint64_t)(2 * o) | ((uint64_t)(2 * o + 1) << 4) | ((uint64_t)(h0 & 0xFFFFFFFu) << 8) | ((uint64_t)((h0 & 0xFFFFFFFu) | 0x1111111u) << 36);
}

__global__ void __cluster_dims__(2, 1, 1) __launch_bounds__(384, 1)
mega_kernel(const __grid_constant__ Maps maps, const __grid_constant__ Ctx c, const bf16* __restrict__ wA, const bf16* __restrict__ wB,
            const bf16* __restrict__ woA, const bf16* __restrict__ woB) {
  if (blockIdx.x - c.boff >= 128u) {
    const unsigned int epoch = ld_relaxed(&g_epoch);
    const int e = (blockIdx.x - c.boff) & 3, tid = threadIdx.x;
    float s[8] = {0.f, 0.f, 0.f, 0.f, 0.f, 0.f, 0.f, 0.f};
    const uint32_t sb = smem_u32(smem_raw), bar = sb + SM_BAR;
    auto issue = [&](int i) {
      mbar_expect_tx(BA(i & 3), 49152);
      bulk_load(sb + (i & 3) * 49152, wB + (size_t)e * 256 * 3072 + i * 24576, 49152, BA(i & 3));
    };
    if (tid == 0) {
#pragma unroll 1
      for (int i = 0; i < 4; ++i) {
        mbar_init(BA(i), 1);
        fence_async_smem();
        issue(i);
      }
    }
    __syncthreads();
#pragma unroll 1
    for (int i = 0; i < 32; ++i) {
      mbar_wait(BA(i & 3), (i >> 2) & 1);
#pragma unroll 2
      for (int r = 0; r < 8; ++r) {
        const uint4 v = lds128(sb + (i & 3) * 49152 + r * 6144 + tid * 16);
        s[0] += bf_lo(v.x); s[1] += bf_hi(v.x); s[2] += bf_lo(v.y); s[3] += bf_hi(v.y);
        s[4] += bf_lo(v.z); s[5] += bf_hi(v.z); s[6] += bf_lo(v.w); s[7] += bf_hi(v.w);
      }
      __syncthreads();
      if (tid == 0 && i < 28) issue(i + 4);
    }
    float* cd = g_cs + (epoch & 1) * 6144 + 3072 + ((tid >> 4) & 7) * 384 + (tid < 128 ? 256 : (tid >> 7) * 128 - 128) + (tid & 15) * 8;
    red_add4(cd, s[0], s[1], s[2], s[3]);
    red_add4(cd + 4, s[4], s[5], s[6], s[7]);
    __syncthreads();
    if (tid == 0) flag_add(&g_csflag[8].v);
    const int op = (epoch & 1) ^ 1;
    float4* kz = reinterpret_cast<float4*>(g_kv + (size_t)op * (2 * 8 * 8448)) + e * 8448;
#pragma unroll 1
    for (int i = tid; i < 8448; i += 384) kz[i] = make_float4(0.f, 0.f, 0.f, 0.f);
    reinterpret_cast<float4*>(g_cs + op * 6144)[e * 384 + tid] = make_float4(0.f, 0.f, 0.f, 0.f);
#pragma unroll 1
    for (int i = tid; i < 1024; i += 384) reinterpret_cast<float4*>(g_stats + (op * 4 + e) * S_)[i] = make_float4(0.f, 0.f, 0.f, 0.f);
    return;
  }
  const int warp = __shfl_sync(0xffffffffu, threadIdx.x >> 5, 0), lane = threadIdx.x & 31;
  if (smem_u32(smem_raw) != SB0 + ((blockIdx.x & 1) << 24)) __trap();
  {
  const int cid = (blockIdx.x - c.boff) >> 1, u7 = ((cid - 36) * 37) >> 8, cr = blockIdx.x & 1;
  const int g = cid < 4 ? 4 + cid : cid < 36 ? (cid - 4) >> 3 : 4 + u7, rb = (cid < 4 ? 0 : cid < 36 ? (cid - 4) & 7 : cid - 35 - 7 * u7) * 2 + cr, m0 = rb * 128;
  const uint32_t sb = SB0 + (cr << 24), bar = sb + SM_BAR;
  PROFT(lane == 0 && (warp == 0 || warp == 4), 224 + (warp >> 2) * 8);
  uint32_t cx = 0;
  if (warp == 2) {
    if (lane < NMAP) asm volatile("prefetch.tensormap [%0];" ::"l"(&maps.m[lane]) : "memory");
    if (lane == 31) asm volatile("prefetch.global.L2 [%0];" ::"l"(&g_epoch));
  } else if (warp == 3) {
    cx = c_map[cid] + c_wop[lane] + c_wop[NWOP - lane] + c_aop[lane] + c_aop[NAOP - lane] + (uint32_t)(uintptr_t)g_x;
  } else if (warp >= 4 && warp < 8) {
    const int i = threadIdx.x - 128;
    asm volatile("prefetch.global.L2 [%0];" ::"l"(wA + (size_t)((rb & ~1) * 64 + cr * 32 + ((i >> 1) & 31)) * 3072 + (i >> 6) * 1024 + g * 128 + (i & 1) * 64));
  }
  if (warp < 2) {
    const int s = warp, kb = (rb & ~1) + s;
    if (lane == 0) {
      mbar_init(BA(FM + s), 1u);
      mbar_init(BA(B_RAW + warp), 1u);
      if (warp) mbar_init(BA(B_X0), 1u);
      asm volatile("fence.mbarrier_init.release.cluster;" ::: "memory");
    }
    __syncwarp();
    if (warp == 0) tma_2d_e(sb + SM_SD, &maps.m[MAP_PHI], 0, g * 128, BA(B_RAW));
    else if (W1DL) __nanosleep(W1DL);
#pragma unroll
    for (int j = 0; j < 6; ++j)
      tma_5d_e(sb + (j < 2 ? 2 * s : j < 4 ? 9 + s : 2 * s + 1) * SLOT + (j & 1) * 8192, &maps.m[MAP_WA], (j < 2 ? 1024 : j < 4 ? 0 : 2048) + g * 128 + (j & 1) * 64, 2 * kb,
               BA(j < 4 ? B_RAW + warp : FM + s));
    tma_2d_e(sb + (XS + s) * SLOT, &maps.m[MAP_X0], kb * 64, m0, BA(FM + s));
    expect_tx_e(BA(B_RAW + warp), warp ? 32768 : 32768 + 8192);
    expect_tx_e(BA(FM + s), 32768);
    if (X0AT == 0 && warp == 1) {
      tma_2d_e(sb + 11 * SLOT, &maps.m[MAP_X0], g * 128, m0, BA(B_X0));
      tma_2d_e(sb + 12 * SLOT, &maps.m[MAP_X0], g * 128 + 64, m0, BA(B_X0));
      expect_tx_e(BA(B_X0), 32768);
    }
  } else if (warp >= 4 && lane == 0) {
#pragma unroll 1
    for (int i = 2 + (warp - 4) * 13; i < 15 + (warp - 4) * 13; ++i)
      mbar_init(BA(i), 1u << ((i < CM ? 0u : i < B_EF ? 2u : (uint32_t)(BAR_LG >> (4 * ((i - B_EF) & 15)))) & 7u));
    asm volatile("fence.mbarrier_init.release.cluster;" ::: "memory");
  }
  __syncwarp();
  asm volatile("barrier.cluster.arrive.relaxed.aligned;" ::: "memory");
  if (threadIdx.x == 96 + c.zero) sts_f(sb + SM_EPOCH + 4, __uint_as_float(cx));
  PROFT(lane == 0 && (warp == 0 || warp == 4), 225 + (warp >> 2) * 8);
  __syncwarp();
  PROFT(lane == 0 && (warp == 0 || warp == 4), 226 + (warp >> 2) * 8);
  }

  if (warp < 4) {
    asm volatile("setmaxnreg.dec.sync.aligned.u32 40;");
    PROFT(threadIdx.x == 0, 227);
    cluster_wait();
    PROFT(threadIdx.x == 0, 228);
    if (warp == 0 || warp == 3) {
    if (warp == 0) {
      BLK_CTX();
      const unsigned int epoch = __shfl_sync(0xffffffffu, ld_relaxed(&g_epoch), 0), xbase = epoch * NLAYERS;
      (void)xbase;
      const uint64_t ordg = k_order(g);
      if (X0AT) {
        mbar_wait_u(BA(B_RAW + X0AT - 1), 0);
        tma_2d_e(sb + 11 * SLOT, &maps.m[MAP_X0], g * 128, m0, BA(B_X0));
        tma_2d_e(sb + 12 * SLOT, &maps.m[MAP_X0], g * 128 + 64, m0, BA(B_X0));
        expect_tx_e(BA(B_X0), 32768);
      }
#pragma unroll 1
      for (int lp = 0; lp < 2 * NLAYERS; ++lp) {
        const int layer = lp >> 1, n1 = (lp & 1) ? NAOP : NAOP - 14;
        int n = (lp & 1) ? NAOP - 14 : 0;
        const uint64_t ord = lp ? ordg : k_order(rb >> 1);
        uint32_t ready = lp ? 0u : 0xFFFFu, nop = c_aop[n];
        const unsigned int* fl = ((lp & 1) ? g_of : g_xf) + rb * 32;
        const CUtensorMap* tm = &maps.m[(lp & 1) ? MAP_O : lp ? MAP_X : MAP_X0];
        const uint32_t skip = layer ? 1u << 25 : 9u << 22;
#pragma unroll 1
        for (; n < n1; ++n) {
          const uint32_t op = nop;
          nop = c_aop[n + 1];
          const uint32_t kb = (uint32_t)(ord >> ((op >> 2) & 60)) & 15;
          uint32_t dst = sb + (op & 15) * SLOT, kc = kb * 64, fb = bar + ((op >> 5) & 0x3F8), need = ~ready & (1u << kb);
          asm volatile("" : "+r"(dst), "+r"(kc), "+r"(fb), "+r"(need));
          if (!(op & skip)) mbar_wait_u(bar + ((op >> 12) & 0x3F8), (layer ^ (op >> 22)) & 1);
          if (need) {
            PROFT(lane == 0 && (n == 0 || n == NAOP - 14), 64 + layer * 16 + (n ? 2 : 0));
            src_wait<0>(fl, xbase + layer + 1, need, ready, lane);
            fence_async_all();
          }
          tma_2d_e(dst, tm, kc, m0, fb);
          PROFT(lane == 0 && (n == 0 || n == NAOP - 14), 64 + layer * 16 + (n ? 3 : 1));
          PROFL(lane == 0 && layer == PL && n >= NAOP - 14, 178 + n - (NAOP - 14));
          PROFL(lane == 0 && layer == PL + 1 && n < 4, 242 + n);
        }
      }
    } else {
      BLK_CTX();
      const unsigned int epoch = __shfl_sync(0xffffffffu, ld_relaxed(&g_epoch), 0), xbase = epoch * NLAYERS;
      (void)xbase;
      const uint64_t ordg = k_order(g);
#pragma unroll 1
      for (int layer = 0; layer < NLAYERS; ++layer) {
        const uint64_t ordq = layer ? ordg : k_order(rb >> 1);
        uint32_t ready = layer ? 0xFFFFu : 0u, nop = c_wop[0];
        const CUtensorMap* tq = &maps.m[(layer & 1) ? MAP_WB : MAP_WF];
        const CUtensorMap* tk = &maps.m[(layer & 1) ? MAP_WB : cr ? MAP_WA : MAP_WF];
        const uint32_t skip = layer ? 1u << 25 : 9u << 22, pm = layer ? 0xE0u : 0u;
        int n = 0;
#pragma unroll 1
        for (; n < NWOP - 16; ++n) {
          const uint32_t op = nop;
          nop = c_wop[n + 1];
          const uint32_t isq = (op >> 23) & 1, fb = bar + ((op >> 5) & 0x3F8);
          const uint32_t kb = (uint32_t)(ordq >> ((op >> 2) & 60)) & 15;
          const CUtensorMap* tm = (isq ? tq : tk) + ((op & pm) ? 1 : 0);
          const uint32_t dst = sb + (op & 15) * SLOT + cr * (isq ? 8192 : SLOT);
          const int col = g * 128 + (isq ? cr * 64 : 1024 + cr * 1024);
          if (layer == 0) {
            if ((op & 0x7E00) == 0) continue;
            const uint32_t need = ((isq || !cr) ? 1u << kb : 0u) | (((op >> 22) & 1) ? 0u : (((op >> 15) & 127) == CM ? 1u : 3u) << (rb & ~1));
            if ((ready & need) != need) {
              src_wait<0>(g_wff + g * 32, epoch + 1, need, ready, lane);
              fence_async_all();
            }
            if ((op & 15) >= 11) mbar_wait_u(BA(B_XT), 0);
          }
          wait_tma_5d_mc(!(op & skip), bar + ((op >> 12) & 0x3F8), (layer ^ (op >> 22)) & 1, dst, tm, col, 2 * kb, fb);
          if (!isq) tma_5d_mc_e(dst + 8192, tm, col + 64, 2 * kb, fb);
          if (op >> 26) expect_tx_e(fb, (op >> 26) * 8192);
          PROFL(lane == 0 && layer == PL + 1 && n < 16, 128 + n);
        }
        const CUtensorMap* to = &maps.m[(layer & 1) ? MAP_WOB : MAP_WOA];
#pragma unroll 1
        for (; n < NWOP; ++n) {
          const uint32_t op = nop;
          nop = c_wop[n + 1];
          const uint32_t fb = bar + ((op >> 5) & 0x3F8), kb = (uint32_t)(ordg >> ((op >> 2) & 60)) & 15;
          wait_tma_5d_mc(!((op >> 25) & 1), bar + ((op >> 12) & 0x3F8), layer & 1, sb + (op & 15) * SLOT + cr * 8192, to + ((op & 0xE0) ? 1 : 0), g * 128 + cr * 64, 2 * kb, fb);
          expect_tx_e(fb, (op >> 26) * 8192);
          PROFL(lane == 0 && layer == PL, 144 + ((op >> 8) & 127) - FW);
        }
      }
    }
    } else if (warp == 1) {
      BLK_CTX();
      const unsigned int epoch = __shfl_sync(0xffffffffu, ld_relaxed(&g_epoch), 0), xbase = epoch * NLAYERS;
      (void)xbase;
      if (lane == 0) {
        mbar_wait(BA(B_WFD), 0);
        PROFT(true, 229);
#pragma unroll 1
        for (int j = 0; j < 4; ++j) tma_store_5d(&maps.m[MAP_WF], sb + (j < 2 ? 2 * cr : 9 + cr) * SLOT + (j & 1) * 8192, (j < 2 ? 1024 : 0) + g * 128 + (j & 1) * 64, 2 * rb);
        bulk_commit();
        bulk_wait0();
        PROFT(true, 230);
        fence_async_all();
        flag_set(g_wff + g * 32 + rb, epoch + 1);
        PROFT(true, 64 + 13);
#pragma unroll 1
        for (int e = 0; e < NLAYERS; ++e) {
          BLK_CTX();
          if (e > 0) {
            mbar_wait(BA(B_XH0), (e - 1) & 1);
            PROFT(e == PL + 1, 240);
            flag_set(g_xf + rb * 32 + 2 * g, xbase + e + 1);
            PROFT(e == PL + 1, 241);
          }
          mbar_wait(BA(B_XDONE), e & 1);
          PROFT(true, 64 + e * 16 + 4);
          flag_set(g_xf + rb * 32 + 2 * g + 1, xbase + e + 1);
          if (e == 0) {
            flag_add(&g_csflag[g].v);
            l2_prefetch(wB + (size_t)bid_ * 24576, 49152);
            l2_prefetch(woA + (size_t)bid_ * 8192, 16384);
            l2_prefetch(woB + (size_t)bid_ * 8192, 16384);
          }
          PROFT(true, 64 + e * 16 + 7);
          if ((e & 1) == 0) {
            float* kvl = g_kv + ((size_t)((epoch & 1) * 2 + (e >> 1)) * 8 + g) * 8448;
#pragma unroll 1
            for (int hp = 0; hp < 2; ++hp) {
              mbar_wait(BA(B_KVDONE), hp);
              bulk_red_add(kvl + 8192 + hp * 128, sb + SM_AP + hp * 512, 512);
#pragma unroll 1
              for (int i = 0; i < NCH; ++i) {
                const int ch = hp * NCH + ((i + rb * NCH / 16) & (NCH - 1));
                bulk_red_add(kvl + ch * (4096 / NCH), sb + VB + ch * (16384 / NCH), 16384 / NCH);
                bulk_commit();
                asm volatile("cp.async.bulk.wait_group %0;" :: "n"(CHW) : "memory");
              }
              bulk_wait0();
              PROFT(true, 64 + e * 16 + (hp ? 10 : 6));
              fence_async_all();
              flag_add(&g_kvflag[hp * 8 + g].v);
              PROFT(e > 0 && hp, 64 + e * 16 + 8);
            }
          }
          if (e & 1) {
            mbar_wait(BA(B_OF0), (e >> 1) & 1);
            flag_set(g_hf + rb * 32 + g, xbase + e + 1);
            if (rb) flag_wait(g_hf + (rb - 1) * 32 + g, xbase + e + 1);
            fence_async_all();
            mbar_expect_tx(BA(B_HALO), 8192);
            bulk_load(sb + SM_SD, g_halo + (size_t)(((e >> 1) * 17 + rb) * 8 + g) * 2048, 8192, BA(B_HALO));
            PROFT(true, 64 + e * 16 + 15);
          }
          mbar_wait(BA(B_OH0), e & 1);
          PROFT(e > 0, 64 + e * 16 + 13);
          flag_set(g_of + rb * 32 + 2 * g, xbase + e + 1);
          PROFT(true, 64 + e * 16 + 9);
          mbar_wait(BA(B_OH1), e & 1);
          PROFT(true, 64 + e * 16 + 5);
          flag_set(g_of + rb * 32 + 2 * g + 1, xbase + e + 1);
          if (EFS) REL2(B_EF);
          PROFT(true, 64 + e * 16 + 11);
        }
        if (bid_ == 0) g_epoch = epoch + 1;
      }
    } else {
      BLK_CTX();
      const unsigned int epoch = __shfl_sync(0xffffffffu, ld_relaxed(&g_epoch), 0), xbase = epoch * NLAYERS;
      (void)xbase;
      if (lane < 16) sts_f(sb + SM_RS + lane * 4, 0.f);
#pragma unroll 1
      for (int layer = 0; layer < NLAYERS; ++layer) {
#define HLP_CTX() BLK_CTX(); int lane = threadIdx.x & 31; asm volatile("" : "+r"(lane)); const bool isB = layer & 1, hal = isB && rb > 0; (void)hal;
#pragma unroll 1
        for (int ph = 0; ph < 2; ++ph) {
          HLP_CTX();
          if (ph == (layer == 0)) {
            const float* cs = g_cs + (epoch & 1) * 6144 + g * 384;
            if (layer) mbar_wait_u(BA(CT), (layer - 1) & 1);
            if (layer < 2) {
              if (lane == 0) flag_wait_slow(&g_csflag[isB ? 8 : g].v, isB ? epoch * 4u + 4u : epoch * 16u + 16u);
              __syncwarp();
            }
#pragma unroll 1
            for (int i0 = 0; i0 < 12; i0 += 4) {
              float a[4];
#pragma unroll
              for (int i = 0; i < 4; ++i) a[i] = __ldcg(cs + isB * 3072 + (i0 + i) * 32 + lane);
#pragma unroll
              for (int i = 0; i < 4; ++i) {
                const float c1 = bf16r(a[i]), c2 = bf16r(a[i] - c1), c3 = (a[i] - c1) - c2;
                sts128(sb + SM_BP + ((i0 + i) * 32 + lane) * 16, make_uint4(pack_bf16(c1, c2), pack_bf16(c3, 0.f), 0u, 0u));
              }
            }
          } else {
            uint32_t rdy = 0u;
            src_wait<128>(g_xf + rb * 32, xbase + layer + 1, 0xAAAAu, rdy, lane);
            rdy = 0u;
            if (hal) src_wait<128>(g_xf + (rb - 1) * 32, xbase + layer + 1, 0xAAAAu, rdy, lane);
            const float2* sp = g_stats + ((epoch & 1) * 4 + layer) * S_ + m0 + lane;
            float2 u[5];
#pragma unroll
            for (int i = 0; i < 4; ++i) u[i] = __ldcg(sp + i * 32);
            u[4] = __ldcg(sp - (hal ? 16 : 0));
#pragma unroll 1
            for (int i = 0; i < 5; ++i) {
              const float mean = u[0].x * (1.f / D_);
              const float var = fmaxf(fmaf(-u[0].x, mean, u[0].y) * (1.f / D_), 0.f);
              const float sd = bf16r(sqrtf(bf16r(bf16r(var) + 1e-5f)));
              const int R = i * 32 + lane;
              if (i < 4) {
                const float hm = -0.5f * bf16r(mean);
                if (!isB) sts128(sb + SM_SD + R * 64 + ((R >> 1) & 3) * 16, make_uint4(__float_as_uint(sd) >> 16, 0u, 0u, 0u));
                sts128(sb + SM_AP + R * 16, make_uint4(pack_bf16(hm, hm), pack_bf16(hm, 0.f), 0u, 0u));
              }
              if (i < 4 || (hal && lane < 16)) sts_f(sb + SM_RS + (i < 4 ? 16 + R : lane) * 4, __fdividef(1.f, sd));
#pragma unroll
              for (int j = 0; j < 4; ++j) u[j] = u[j + 1];
            }
            PROFT(lane == 0, 64 + layer * 16 + 12);
          }
        }
        HLP_CTX();
        fence_async_smem();
        __syncwarp();
        if (lane == 0) mbar_arrive(BA(B_STAT));
        PROFT(lane == 0, 64 + layer * 16 + 14);
        if (!isB && lane == 0) {
#pragma unroll 1
          for (int hp = 0; hp < 2; ++hp) {
            mbar_wait(BA(B_KVDONE), hp);
            flag_wait(&g_kvflag[hp * 8 + g].v, epoch * (16u * ((NLAYERS + 1) / 2)) + 16u * ((layer >> 1) + 1));
            const float* kvl = g_kv + ((size_t)((epoch & 1) * 2 + (layer >> 1)) * 8 + g) * 8448;
            const uint32_t kb = BA(hp ? B_KVF1 : B_KVF);
            fence_async_all();
            mbar_expect_tx(kb, 16384 + 512);
            bulk_load(sb + VB + hp * SLOT, kvl + hp * 4096, 16384, kb);
            bulk_load(sb + SM_AP + hp * 512, kvl + 8192 + hp * 128, 512, kb);
            PROFT(hp == 0, 64 + layer * 16 + 15);
          }
        }
        __syncwarp();
      }
    }
    __syncwarp();
    asm volatile("barrier.cluster.arrive.relaxed.aligned;" ::: "memory");
    cluster_wait();
  } else {
    asm volatile("setmaxnreg.inc.sync.aligned.u32 232;");
    PROFT(threadIdx.x == 128, 235);
    cluster_wait();
    PROFT(threadIdx.x == 128, 236);
    consumer(c);
    asm volatile("bar.warp.sync 0xffffffff;\nbarrier.cluster.arrive.relaxed.aligned;\nbarrier.cluster.wait.aligned;\n" ::: "memory");
  }
}

typedef CUresult (*PFN_encodeTiled)(CUtensorMap*, CUtensorMapDataType, cuuint32_t, void*, const cuuint64_t*, const cuuint64_t*,
                                    const cuuint32_t*, const cuuint32_t*, CUtensorMapInterleave, CUtensorMapSwizzle,
                                    CUtensorMapL2promotion, CUtensorMapFloatOOBfill);

static void make_map2(PFN_encodeTiled enc, CUtensorMap* m, const void* ptr, uint64_t cols, uint64_t rows, uint32_t box_c, uint32_t box_r) {
  cuuint64_t dims[2] = {cols, rows};
  cuuint64_t strides[1] = {cols * 2};
  cuuint32_t box[2] = {box_c, box_r};
  cuuint32_t es[2] = {1, 1};
  CUresult r = enc(m, CU_TENSOR_MAP_DATA_TYPE_BFLOAT16, 2, const_cast<void*>(ptr), dims, strides, box, es, CU_TENSOR_MAP_INTERLEAVE_NONE,
                   box_c == 64 ? CU_TENSOR_MAP_SWIZZLE_128B : CU_TENSOR_MAP_SWIZZLE_64B, CU_TENSOR_MAP_L2_PROMOTION_L2_256B, CU_TENSOR_MAP_FLOAT_OOB_FILL_NONE);
  (void)r;
}
static void make_map5(PFN_encodeTiled enc, CUtensorMap* m, const void* ptr, uint64_t cols) {
  for (int p = 0; p < 2; ++p) {
    cuuint64_t dims[5] = {cols, 2, 4, 4, 32};
    cuuint64_t strides[4] = {cols * 2, cols * (p ? 16 : 4), cols * (p ? 4 : 16), cols * 64};
    cuuint32_t box[5] = {64, 2, 4, 4, 2};
    cuuint32_t es[5] = {1, 1, 1, 1, 1};
    CUresult r = enc(m + p, CU_TENSOR_MAP_DATA_TYPE_BFLOAT16, 5, const_cast<void*>(ptr), dims, strides, box, es, CU_TENSOR_MAP_INTERLEAVE_NONE,
                     CU_TENSOR_MAP_SWIZZLE_128B, CU_TENSOR_MAP_L2_PROMOTION_L2_256B, CU_TENSOR_MAP_FLOAT_OOB_FILL_NONE);
    (void)r;
  }
}

extern "C" void kernel_launch(void* const* d_in, const int* in_sizes, int n_in, void* d_out, int out_size) {
  const bf16* A_x = (const bf16*)d_in[0];
  const bf16* A_wqkv = (const bf16*)d_in[1];
  const bf16* A_wphi = (const bf16*)d_in[2];
  const bf16* A_wo = (const bf16*)d_in[3];
  const bf16* B_wqkv = (const bf16*)d_in[5];
  const bf16* B_wo = (const bf16*)d_in[6];
  bf16* out = (bf16*)d_out;

  static PFN_encodeTiled enc = nullptr;
  static bf16 *p_x, *p_o, *p_wf;
  static uint32_t boff;
  if (!enc) {
    void* fn = nullptr; cudaDriverEntryPointQueryResult qr;
    cudaGetDriverEntryPoint("cuTensorMapEncodeTiled", &fn, cudaEnableDefault, &qr);
    enc = (PFN_encodeTiled)fn;
    cudaGetSymbolAddress((void**)&p_x, g_x);
    cudaGetSymbolAddress((void**)&p_o, g_o);
    cudaGetSymbolAddress((void**)&p_wf, g_wf);
    cudaFuncSetAttribute(mega_kernel, cudaFuncAttributeMaxDynamicSharedMemorySize, SM_TOTAL);
    cudaLaunchConfig_t cfg = {};
    cudaLaunchAttribute at; at.id = cudaLaunchAttributeClusterDimension; at.val.clusterDim.x = 2; at.val.clusterDim.y = 1; at.val.clusterDim.z = 1;
    cfg.gridDim = dim3(132); cfg.blockDim = dim3(384); cfg.dynamicSmemBytes = SM_TOTAL; cfg.attrs = &at; cfg.numAttrs = 1;
    int nc = 0;
    if (cudaOccupancyMaxActiveClusters(&nc, mega_kernel, &cfg) != cudaSuccess) { nc = 0; (void)cudaGetLastError(); }
    boff = nc >= 66 ? 0u : 4u;
  }
  Maps maps;
  make_map5(enc, &maps.m[MAP_WF], p_wf, 2048);
  make_map5(enc, &maps.m[MAP_WA], A_wqkv, 3072);
  make_map5(enc, &maps.m[MAP_WB], B_wqkv, 3072);
  make_map5(enc, &maps.m[MAP_WOA], A_wo, 1024);
  make_map5(enc, &maps.m[MAP_WOB], B_wo, 1024);
  make_map2(enc, &maps.m[MAP_X0], A_x, 1024, 2048, 64, 128);
  make_map2(enc, &maps.m[MAP_X], p_x, 1024, 2048, 64, 128);
  make_map2(enc, &maps.m[MAP_O], p_o, 1024, 2048, 64, 128);
  make_map2(enc, &maps.m[MAP_PHI], A_wphi, 32, 1024, 32, 128);
  Ctx c; c.zero = 0u; c.boff = boff; c.x0 = A_x; c.out = out;
  mega_kernel<<<132, 384, SM_TOTAL, cudaStreamPerThread>>>(maps, c, A_wqkv, B_wqkv, A_wo, B_wo);
}
```

```cpp
#include <cuda_runtime.h>
#include <cuda_bf16.h>
#include <cuda.h>
#include <stdint.h>

typedef __nv_bfloat16 bf16;

constexpr int S_ = 2048, D_ = 1024;

struct __align__(128) Flag { unsigned int v; unsigned int pad[31]; };
__device__ __align__(1024) bf16 g_x[S_ * D_];
__device__ __align__(1024) bf16 g_o[S_ * D_];
__device__ __align__(1024) uint32_t g_halo[2 * 17 * 8 * 2048];
__device__ __align__(1024) float g_kv[2 * 2 * 8 * 8448];
__device__ __align__(1024) float2 g_stats[2 * 4 * S_];
__device__ __align__(1024) float g_cs[2 * 2 * 3072];
__device__ __align__(1024) bf16 g_wf[D_ * 2048];
__device__ Flag g_kvflag[16], g_csflag[13];
__device__ __align__(128) unsigned int g_xf[16 * 32], g_of[16 * 32];
__device__ __align__(128) unsigned int g_hf[16 * 32];
__device__ __align__(128) unsigned int g_wff[8 * 32];
__device__ unsigned int g_epoch, g_err;
#define PROFT(cond, idx) asm volatile("" ::: "memory")

__device__ __forceinline__ uint32_t smem_u32(const void* p) { return (uint32_t)__cvta_generic_to_shared(p); }
__device__ __forceinline__ void mbar_init(uint32_t bar, uint32_t count) {
  asm volatile("mbarrier.init.shared::cta.b64 [%0], %1;" ::"r"(bar), "r"(count) : "memory");
}
__device__ __forceinline__ void mbar_expect_tx(uint32_t bar, uint32_t bytes) {
  asm volatile("mbarrier.arrive.expect_tx.shared::cta.b64 _, [%0], %1;" ::"r"(bar), "r"(bytes) : "memory");
}
__device__ __forceinline__ void mbar_arrive(uint32_t bar) {
  asm volatile("mbarrier.arrive.shared::cta.b64 _, [%0];" ::"r"(bar) : "memory");
}
__device__ __forceinline__ bool mbar_try_wait(uint32_t bar, uint32_t parity) {
  uint32_t ok;
  asm volatile("{\n.reg .pred p;\nmbarrier.try_wait.parity.shared::cta.b64 p, [%1], %2;\nselp.b32 %0, 1, 0, p;\n}\n"
               : "=r"(ok) : "r"(bar), "r"(parity) : "memory");
  return ok != 0;
}
__device__ __forceinline__ bool mbar_test_wait(uint32_t bar, uint32_t parity) {
  uint32_t ok;
  asm volatile("{\n.reg .pred p;\nmbarrier.test_wait.parity.shared::cta.b64 p, [%1], %2;\nselp.b32 %0, 1, 0, p;\n}\n"
               : "=r"(ok) : "r"(bar), "r"(parity) : "memory");
  return ok != 0;
}
__device__ __forceinline__ uint64_t gtimer() {
  uint64_t t; asm volatile("mov.u64 %0, %globaltimer;" : "=l"(t)); return t;
}
__device__ __forceinline__ void mbar_wait(uint32_t bar, uint32_t parity) {
  uint32_t n = 0;
  bool ok;
#pragma unroll 1
  do { ++n; ok = mbar_try_wait(bar, parity); } while (!ok && n < (1u << 22));
}
__device__ __forceinline__ unsigned int ld_acquire(const unsigned int* p) {
  unsigned int v; asm volatile("ld.acquire.gpu.global.u32 %0, [%1];" : "=r"(v) : "l"(p) : "memory"); return v;
}
__device__ __forceinline__ void flag_add(unsigned int* p) {
  asm volatile("red.release.gpu.global.add.u32 [%0], 1;" ::"l"(p) : "memory");
}
__device__ __forceinline__ void flag_set(unsigned int* p, unsigned int v) {
  asm volatile("st.release.gpu.global.u32 [%0], %1;" ::"l"(p), "r"(v) : "memory");
}
template <int SLEEP>
__device__ __forceinline__ void src_wait(const unsigned int* f, unsigned int target, uint32_t need, uint32_t& ready, int lane) {
  uint32_t n = 0;
#pragma unroll 1
  while ((ready & need) != need) {
    const unsigned int v = ld_acquire(f + (lane & 15));
    ready = __ballot_sync(0xffffffffu, (int)(v - target) >= 0);
    if (SLEEP) { if ((ready & need) != need) __nanosleep(SLEEP); }
    if (++n > (1u << 20)) break;
  }
  __syncwarp();
}
__device__ __forceinline__ unsigned int ld_relaxed(const unsigned int* p);
__device__ __forceinline__ unsigned int ld_relaxed(const unsigned int* p) {
  unsigned int v; asm volatile("ld.relaxed.gpu.global.u32 %0, [%1];" : "=r"(v) : "l"(p) : "memory"); return v;
}
template <int SLEEP>
__device__ __forceinline__ void flag_wait_t(const unsigned int* p, unsigned int target) {
  uint32_t n = 0;
#pragma unroll 1
  while ((int)(ld_acquire(p) - target) < 0) {
    if (SLEEP) __nanosleep(SLEEP);
    if (++n > (1u << 20)) break;
  }
}
__device__ __forceinline__ void flag_wait(const unsigned int* p, unsigned int target) { flag_wait_t<0>(p, target); }
__device__ __forceinline__ void flag_wait_slow(const unsigned int* p, unsigned int target) { flag_wait_t<256>(p, target); }
__device__ __forceinline__ void mbar_wait_u(uint32_t bar, uint32_t parity) {
  uint32_t n = 0;
#pragma unroll 1
  while (!__all_sync(0xffffffffu, mbar_try_wait(bar, parity))) {
    if (++n > (1u << 22)) break;
  }
}
__device__ __forceinline__ void expect_tx_e(uint32_t bar, uint32_t bytes) {
  asm volatile("{\n.reg .pred p;\nelect.sync _|p, 0xffffffff;\n@p mbarrier.arrive.expect_tx.shared::cta.b64 _, [%0], %1;\n}\n" ::"r"(bar), "r"(bytes) : "memory");
}
__device__ __forceinline__ void tma_2d_e(uint32_t dst, const CUtensorMap* tm, int c0, int c1, uint32_t bar) {
  asm volatile("{\n.reg .pred p;\nelect.sync _|p, 0xffffffff;\n"
               "@p cp.async.bulk.tensor.2d.shared::cluster.global.mbarrier::complete_tx::bytes [%0], [%1, {%2, %3}], [%4];\n}\n"
               ::"r"(dst), "l"(tm), "r"(c0), "r"(c1), "r"(bar) : "memory");
}
__device__ __forceinline__ void tma_5d_e(uint32_t dst, const CUtensorMap* tm, int c0, int c4, uint32_t bar) {
  asm volatile("{\n.reg .pred p;\nelect.sync _|p, 0xffffffff;\n"
               "@p cp.async.bulk.tensor.5d.shared::cluster.global.mbarrier::complete_tx::bytes [%0], [%1, {%2, %5, %5, %5, %3}], [%4];\n}\n"
               ::"r"(dst), "l"(tm), "r"(c0), "r"(c4), "r"(bar), "r"(0) : "memory");
}
__device__ __forceinline__ void tma_5d_mc_e(uint32_t dst, const CUtensorMap* tm, int c0, int c4, uint32_t bar) {
  asm volatile("{\n.reg .pred p;\nelect.sync _|p, 0xffffffff;\n"
               "@p cp.async.bulk.tensor.5d.shared::cluster.global.mbarrier::complete_tx::bytes.multicast::cluster [%0], [%1, {%2, %6, %6, %6, %3}], [%4], %5;\n}\n"
               ::"r"(dst), "l"(tm), "r"(c0), "r"(c4), "r"(bar), "h"((uint16_t)3), "r"(0) : "memory");
}
__device__ __forceinline__ void wait_tma_5d_mc(bool w, uint32_t eb, uint32_t par, uint32_t dst, const CUtensorMap* tm, int c0, int c4, uint32_t fb) {
  asm volatile("" : "+r"(dst), "+l"(tm), "+r"(c0), "+r"(c4), "+r"(fb));
  if (w) mbar_wait_u(eb, par);
  tma_5d_mc_e(dst, tm, c0, c4, fb);
}
__device__ __forceinline__ void stg128(void* p, uint32_t a, uint32_t b, uint32_t c, uint32_t d) {
  asm volatile("st.global.v4.u32 [%0], {%1,%2,%3,%4};" ::"l"(p), "r"(a), "r"(b), "r"(c), "r"(d) : "memory");
}
__device__ __forceinline__ void stg128_p(bool on, void* p, uint32_t a, uint32_t b, uint32_t c, uint32_t d) {
  asm volatile("{\n.reg .pred p;\nsetp.ne.b32 p, %5, 0;\n@p st.global.v4.u32 [%0], {%1,%2,%3,%4};\n}\n" ::"l"(p), "r"(a), "r"(b), "r"(c), "r"(d), "r"((int)on) : "memory");
}
__device__ __forceinline__ void ldg128(const void* p, uint32_t& a, uint32_t& b, uint32_t& c, uint32_t& d) {
  asm volatile("ld.global.cg.v4.u32 {%0,%1,%2,%3}, [%4];" : "=r"(a), "=r"(b), "=r"(c), "=r"(d) : "l"(p) : "memory");
}
__device__ __forceinline__ void release2c(uint32_t off) {
  asm volatile("mbarrier.arrive.shared::cluster.b64 _, [%0];\nmbarrier.arrive.shared::cluster.b64 _, [%1];" ::"r"(off), "r"(off + (1u << 24)) : "memory");
}
__device__ __forceinline__ void tma_store_5d(const CUtensorMap* tm, uint32_t src, int c0, int c4) {
  asm volatile("cp.async.bulk.tensor.5d.global.shared::cta.bulk_group [%0, {%2, %4, %4, %4, %3}], [%1];"
               ::"l"(tm), "r"(src), "r"(c0), "r"(c4), "r"(0) : "memory");
}
__device__ __forceinline__ void bulk_load(uint32_t dst, const void* src, uint32_t bytes, uint32_t bar) {
  asm volatile("cp.async.bulk.shared::cluster.global.mbarrier::complete_tx::bytes [%0], [%1], %2, [%3];" ::"r"(dst), "l"(src), "r"(bytes), "r"(bar) : "memory");
}
__device__ __forceinline__ void bulk_red_add(void* dst, uint32_t src, uint32_t bytes) {
  asm volatile("cp.reduce.async.bulk.global.shared::cta.bulk_group.add.f32 [%0], [%1], %2;" ::"l"(dst), "r"(src), "r"(bytes) : "memory");
}
__device__ __forceinline__ void bulk_commit() { asm volatile("cp.async.bulk.commit_group;" ::: "memory"); }
__device__ __forceinline__ void bulk_wait0() { asm volatile("cp.async.bulk.wait_group 0;" ::: "memory"); }
__device__ __forceinline__ void fence_async_smem() { asm volatile("fence.proxy.async.shared::cta;" ::: "memory"); }
__device__ __forceinline__ void fence_async_all() { asm volatile("fence.proxy.async.global;" ::: "memory"); }
__device__ __forceinline__ void wgmma_fence() { asm volatile("wgmma.fence.sync.aligned;" ::: "memory"); }
__device__ __forceinline__ void wgmma_commit() { asm volatile("wgmma.commit_group.sync.aligned;" ::: "memory"); }
template <int N> __device__ __forceinline__ void wgmma_wait() { asm volatile("wgmma.wait_group.sync.aligned %0;" ::"n"(N) : "memory"); }
__device__ __forceinline__ void cluster_wait() { asm volatile("barrier.cluster.wait.acquire.aligned;" ::: "memory"); }
template <int ID, int N> __device__ __forceinline__ void nbar() { asm volatile("bar.sync %0, %1;" ::"n"(ID), "n"(N) : "memory"); }
__device__ __forceinline__ uint64_t desc64(uint32_t lo, uint32_t hi) { return (uint64_t)lo | ((uint64_t)hi << 32); }
__device__ __forceinline__ uint32_t pack_bf16(float lo, float hi) {
  uint32_t r; asm("cvt.rn.bf16x2.f32 %0, %1, %2;" : "=r"(r) : "f"(hi), "f"(lo)); return r;
}
__device__ __forceinline__ uint32_t add_bf16x2(uint32_t a, uint32_t b) {
  uint32_t r; asm("add.rn.bf16x2 %0, %1, %2;" : "=r"(r) : "r"(a), "r"(b)); return r;
}
__device__ __forceinline__ float bf16r(float x) { return __bfloat162float(__float2bfloat16_rn(x)); }
__device__ __forceinline__ float bf_lo(uint32_t u) { return __uint_as_float(u << 16); }
__device__ __forceinline__ float bf_hi(uint32_t u) { return __uint_as_float(u & 0xFFFF0000u); }
__device__ __forceinline__ float ex2(float x) { float r; asm("ex2.approx.ftz.f32 %0, %1;" : "=f"(r) : "f"(x)); return r; }
__device__ __forceinline__ float ex2v(float x) { float r; asm volatile("ex2.approx.ftz.f32 %0, %1;" : "=f"(r) : "f"(x) : "memory"); return r; }
__device__ __forceinline__ float rcp(float x) { float r; asm("rcp.approx.ftz.f32 %0, %1;" : "=f"(r) : "f"(x)); return r; }
__device__ __forceinline__ void mma_bf16(float (&d)[4], uint32_t a0, uint32_t a1, uint32_t a2, uint32_t a3, uint32_t b0, uint32_t b1) {
  asm("mma.sync.aligned.m16n8k16.row.col.f32.bf16.bf16.f32 {%0,%1,%2,%3}, {%4,%5,%6,%7}, {%8,%9}, {%0,%1,%2,%3};"
               : "+f"(d[0]), "+f"(d[1]), "+f"(d[2]), "+f"(d[3]) : "r"(a0), "r"(a1), "r"(a2), "r"(a3), "r"(b0), "r"(b1));
}
__device__ __forceinline__ void ldsm_x4(uint32_t& r0, uint32_t& r1, uint32_t& r2, uint32_t& r3, uint32_t addr) {
  asm volatile("ldmatrix.sync.aligned.m8n8.x4.shared.b16 {%0,%1,%2,%3}, [%4];"
               : "=r"(r0), "=r"(r1), "=r"(r2), "=r"(r3) : "r"(addr) : "memory");
}
__device__ __forceinline__ void ldsm_x4_t(uint32_t& r0, uint32_t& r1, uint32_t& r2, uint32_t& r3, uint32_t addr) {
  asm volatile("ldmatrix.sync.aligned.m8n8.x4.trans.shared.b16 {%0,%1,%2,%3}, [%4];"
               : "=r"(r0), "=r"(r1), "=r"(r2), "=r"(r3) : "r"(addr) : "memory");
}
__device__ __forceinline__ void stsm_x4(uint32_t addr, uint32_t r0, uint32_t r1, uint32_t r2, uint32_t r3) {
  asm volatile("stmatrix.sync.aligned.m8n8.x4.shared.b16 [%0], {%1,%2,%3,%4};"
               ::"r"(addr), "r"(r0), "r"(r1), "r"(r2), "r"(r3) : "memory");
}
__device__ __forceinline__ uint4 lds128(uint32_t addr) {
  uint4 v; asm volatile("ld.shared.v4.b32 {%0,%1,%2,%3}, [%4];" : "=r"(v.x), "=r"(v.y), "=r"(v.z), "=r"(v.w) : "r"(addr) : "memory"); return v;
}
__device__ __forceinline__ void sts128(uint32_t addr, uint4 v) {
  asm volatile("st.shared.v4.b32 [%0], {%1,%2,%3,%4};" ::"r"(addr), "r"(v.x), "r"(v.y), "r"(v.z), "r"(v.w) : "memory");
}
__device__ __forceinline__ float lds_f(uint32_t addr) {
  float v; asm volatile("ld.shared.f32 %0, [%1];" : "=f"(v) : "r"(addr) : "memory"); return v;
}
__device__ __forceinline__ void nbar_dyn(int id, int n) { asm volatile("bar.sync %0, %1;" ::"r"(id), "r"(n) : "memory"); }
__device__ __forceinline__ uint64_t make_desc_ns(uint32_t addr, uint32_t lbo_bytes, uint32_t sbo_bytes) {
  return (uint64_t)((addr & 0x3FFFF) >> 4) | ((uint64_t)(lbo_bytes >> 4) << 16) | ((uint64_t)(sbo_bytes >> 4) << 32);
}
__device__ __forceinline__ void sts_f(uint32_t addr, float v) { asm volatile("st.shared.f32 [%0], %1;" ::"r"(addr), "f"(v) : "memory"); }
__device__ __forceinline__ void sts64(uint32_t addr, uint32_t a, uint32_t b) {
  asm volatile("st.shared.v2.b32 [%0], {%1,%2};" ::"r"(addr), "r"(a), "r"(b) : "memory");
}
__device__ __forceinline__ void sts_f2(uint32_t addr, float a, float b) {
  asm volatile("st.shared.v2.f32 [%0], {%1,%2};" ::"r"(addr), "f"(a), "f"(b) : "memory");
}
__device__ __forceinline__ void red_add2_p(bool on, float* p, float a, float b) {
  asm volatile("{\n.reg .pred p;\nsetp.ne.b32 p, %3, 0;\n@p red.global.add.v2.f32 [%0], {%1,%2};\n}\n" ::"l"(p), "f"(a), "f"(b), "r"((int)on) : "memory");
}
__device__ __forceinline__ void red_add4(float* p, float a, float b, float c, float d) {
  asm volatile("red.global.add.v4.f32 [%0], {%1,%2,%3,%4};" ::"l"(p), "f"(a), "f"(b), "f"(c), "f"(d) : "memory");
}
__device__ __forceinline__ void red_add1(float* p, float a) {
  asm volatile("red.global.add.f32 [%0], %1;" ::"l"(p), "f"(a) : "memory");
}
__device__ __forceinline__ void l2_prefetch(const void* p, uint32_t bytes) {
  asm volatile("cp.async.bulk.prefetch.L2.global [%0], %1;" ::"l"(p), "r"(bytes) : "memory");
}

__device__ __forceinline__ void wgmma_n256(float (&d)[192], uint64_t da, uint64_t db, int scale_d) {
  asm volatile("{\n.reg .pred p;\nsetp.ne.b32 p, %130, 0;\n"
    "wgmma.mma_async.sync.aligned.m64n256k16.f32.bf16.bf16 {%0, %1, %2, %3, %4, %5, %6, %7, %8, %9, %10, %11, %12, %13, %14, %15, %16, %17, %18, %19, %20, %21, %22, %23, %24, %25, %26, %27, %28, %29, %30, %31, %32, %33, %34, %35, %36, %37, %38, %39, %40, %41, %42, %43, %44, %45, %46, %47, %48, %49, %50, %51, %52, %53, %54, %55, %56, %57, %58, %59, %60, %61, %62, %63, %64, %65, %66, %67, %68, %69, %70, %71, %72, %73, %74, %75, %76, %77, %78, %79, %80, %81, %82, %83, %84, %85, %86, %87, %88, %89, %90, %91, %92, %93, %94, %95, %96, %97, %98, %99, %100, %101, %102, %103, %104, %105, %106, %107, %108, %109, %110, %111, %112, %113, %114, %115, %116, %117, %118, %119, %120, %121, %122, %123, %124, %125, %126, %127}, %128, %129, p, 1, 1, 0, 1;\n}\n"
    : "+f"(d[0]), "+f"(d[1]), "+f"(d[2]), "+f"(d[3]), "+f"(d[4]), "+f"(d[5]), "+f"(d[6]), "+f"(d[7]), "+f"(d[8]), "+f"(d[9]), "+f"(d[10]), "+f"(d[11]), "+f"(d[12]), "+f"(d[13]), "+f"(d[14]), "+f"(d[15]), "+f"(d[16]), "+f"(d[17]), "+f"(d[18]), "+f"(d[19]), "+f"(d[20]), "+f"(d[21]), "+f"(d[22]), "+f"(d[23]), "+f"(d[24]), "+f"(d[25]), "+f"(d[26]), "+f"(d[27]), "+f"(d[28]), "+f"(d[29]), "+f"(d[30]), "+f"(d[31]), "+f"(d[32]), "+f"(d[33]), "+f"(d[34]), "+f"(d[35]), "+f"(d[36]), "+f"(d[37]), "+f"(d[38]), "+f"(d[39]), "+f"(d[40]), "+f"(d[41]), "+f"(d[42]), "+f"(d[43]), "+f"(d[44]), "+f"(d[45]), "+f"(d[46]), "+f"(d[47]), "+f"(d[48]), "+f"(d[49]), "+f"(d[50]), "+f"(d[51]), "+f"(d[52]), "+f"(d[53]), "+f"(d[54]), "+f"(d[55]), "+f"(d[56]), "+f"(d[57]), "+f"(d[58]), "+f"(d[59]), "+f"(d[60]), "+f"(d[61]), "+f"(d[62]), "+f"(d[63]), "+f"(d[64]), "+f"(d[65]), "+f"(d[66]), "+f"(d[67]), "+f"(d[68]), "+f"(d[69]), "+f"(d[70]), "+f"(d[71]), "+f"(d[72]), "+f"(d[73]), "+f"(d[74]), "+f"(d[75]), "+f"(d[76]), "+f"(d[77]), "+f"(d[78]), "+f"(d[79]), "+f"(d[80]), "+f"(d[81]), "+f"(d[82]), "+f"(d[83]), "+f"(d[84]), "+f"(d[85]), "+f"(d[86]), "+f"(d[87]), "+f"(d[88]), "+f"(d[89]), "+f"(d[90]), "+f"(d[91]), "+f"(d[92]), "+f"(d[93]), "+f"(d[94]), "+f"(d[95]), "+f"(d[96]), "+f"(d[97]), "+f"(d[98]), "+f"(d[99]), "+f"(d[100]), "+f"(d[101]), "+f"(d[102]), "+f"(d[103]), "+f"(d[104]), "+f"(d[105]), "+f"(d[106]), "+f"(d[107]), "+f"(d[108]), "+f"(d[109]), "+f"(d[110]), "+f"(d[111]), "+f"(d[112]), "+f"(d[113]), "+f"(d[114]), "+f"(d[115]), "+f"(d[116]), "+f"(d[117]), "+f"(d[118]), "+f"(d[119]), "+f"(d[120]), "+f"(d[121]), "+f"(d[122]), "+f"(d[123]), "+f"(d[124]), "+f"(d[125]), "+f"(d[126]), "+f"(d[127])
    : "l"(da), "l"(db), "r"(scale_d));
}
__device__ __forceinline__ void wgmma_n128(float (&d)[192], uint64_t da, uint64_t db, int scale_d) {
  asm volatile("{\n.reg .pred p;\nsetp.ne.b32 p, %66, 0;\n"
    "wgmma.mma_async.sync.aligned.m64n128k16.f32.bf16.bf16 {%0, %1, %2, %3, %4, %5, %6, %7, %8, %9, %10, %11, %12, %13, %14, %15, %16, %17, %18, %19, %20, %21, %22, %23, %24, %25, %26, %27, %28, %29, %30, %31, %32, %33, %34, %35, %36, %37, %38, %39, %40, %41, %42, %43, %44, %45, %46, %47, %48, %49, %50, %51, %52, %53, %54, %55, %56, %57, %58, %59, %60, %61, %62, %63}, %64, %65, p, 1, 1, 0, 1;\n}\n"
    : "+f"(d[128]), "+f"(d[129]), "+f"(d[130]), "+f"(d[131]), "+f"(d[132]), "+f"(d[133]), "+f"(d[134]), "+f"(d[135]), "+f"(d[136]), "+f"(d[137]), "+f"(d[138]), "+f"(d[139]), "+f"(d[140]), "+f"(d[141]), "+f"(d[142]), "+f"(d[143]), "+f"(d[144]), "+f"(d[145]), "+f"(d[146]), "+f"(d[147]), "+f"(d[148]), "+f"(d[149]), "+f"(d[150]), "+f"(d[151]), "+f"(d[152]), "+f"(d[153]), "+f"(d[154]), "+f"(d[155]), "+f"(d[156]), "+f"(d[157]), "+f"(d[158]), "+f"(d[159]), "+f"(d[160]), "+f"(d[161]), "+f"(d[162]), "+f"(d[163]), "+f"(d[164]), "+f"(d[165]), "+f"(d[166]), "+f"(d[167]), "+f"(d[168]), "+f"(d[169]), "+f"(d[170]), "+f"(d[171]), "+f"(d[172]), "+f"(d[173]), "+f"(d[174]), "+f"(d[175]), "+f"(d[176]), "+f"(d[177]), "+f"(d[178]), "+f"(d[179]), "+f"(d[180]), "+f"(d[181]), "+f"(d[182]), "+f"(d[183]), "+f"(d[184]), "+f"(d[185]), "+f"(d[186]), "+f"(d[187]), "+f"(d[188]), "+f"(d[189]), "+f"(d[190]), "+f"(d[191])
    : "l"(da), "l"(db), "r"(scale_d));
}
__device__ __forceinline__ void wgmma_n256_k(float (&d)[192], uint64_t da, uint64_t db, int scale_d) {
  asm volatile("{\n.reg .pred p;\nsetp.ne.b32 p, %130, 0;\n"
    "wgmma.mma_async.sync.aligned.m64n256k16.f32.bf16.bf16 {%0, %1, %2, %3, %4, %5, %6, %7, %8, %9, %10, %11, %12, %13, %14, %15, %16, %17, %18, %19, %20, %21, %22, %23, %24, %25, %26, %27, %28, %29, %30, %31, %32, %33, %34, %35, %36, %37, %38, %39, %40, %41, %42, %43, %44, %45, %46, %47, %48, %49, %50, %51, %52, %53, %54, %55, %56, %57, %58, %59, %60, %61, %62, %63, %64, %65, %66, %67, %68, %69, %70, %71, %72, %73, %74, %75, %76, %77, %78, %79, %80, %81, %82, %83, %84, %85, %86, %87, %88, %89, %90, %91, %92, %93, %94, %95, %96, %97, %98, %99, %100, %101, %102, %103, %104, %105, %106, %107, %108, %109, %110, %111, %112, %113, %114, %115, %116, %117, %118, %119, %120, %121, %122, %123, %124, %125, %126, %127}, %128, %129, p, 1, 1, 0, 0;\n}\n"
    : "+f"(d[0]), "+f"(d[1]), "+f"(d[2]), "+f"(d[3]), "+f"(d[4]), "+f"(d[5]), "+f"(d[6]), "+f"(d[7]), "+f"(d[8]), "+f"(d[9]), "+f"(d[10]), "+f"(d[11]), "+f"(d[12]), "+f"(d[13]), "+f"(d[14]), "+f"(d[15]), "+f"(d[16]), "+f"(d[17]), "+f"(d[18]), "+f"(d[19]), "+f"(d[20]), "+f"(d[21]), "+f"(d[22]), "+f"(d[23]), "+f"(d[24]), "+f"(d[25]), "+f"(d[26]), "+f"(d[27]), "+f"(d[28]), "+f"(d[29]), "+f"(d[30]), "+f"(d[31]), "+f"(d[32]), "+f"(d[33]), "+f"(d[34]), "+f"(d[35]), "+f"(d[36]), "+f"(d[37]), "+f"(d[38]), "+f"(d[39]), "+f"(d[40]), "+f"(d[41]), "+f"(d[42]), "+f"(d[43]), "+f"(d[44]), "+f"(d[45]), "+f"(d[46]), "+f"(d[47]), "+f"(d[48]), "+f"(d[49]), "+f"(d[50]), "+f"(d[51]), "+f"(d[52]), "+f"(d[53]), "+f"(d[54]), "+f"(d[55]), "+f"(d[56]), "+f"(d[57]), "+f"(d[58]), "+f"(d[59]), "+f"(d[60]), "+f"(d[61]), "+f"(d[62]), "+f"(d[63]), "+f"(d[64]), "+f"(d[65]), "+f"(d[66]), "+f"(d[67]), "+f"(d[68]), "+f"(d[69]), "+f"(d[70]), "+f"(d[71]), "+f"(d[72]), "+f"(d[73]), "+f"(d[74]), "+f"(d[75]), "+f"(d[76]), "+f"(d[77]), "+f"(d[78]), "+f"(d[79]), "+f"(d[80]), "+f"(d[81]), "+f"(d[82]), "+f"(d[83]), "+f"(d[84]), "+f"(d[85]), "+f"(d[86]), "+f"(d[87]), "+f"(d[88]), "+f"(d[89]), "+f"(d[90]), "+f"(d[91]), "+f"(d[92]), "+f"(d[93]), "+f"(d[94]), "+f"(d[95]), "+f"(d[96]), "+f"(d[97]), "+f"(d[98]), "+f"(d[99]), "+f"(d[100]), "+f"(d[101]), "+f"(d[102]), "+f"(d[103]), "+f"(d[104]), "+f"(d[105]), "+f"(d[106]), "+f"(d[107]), "+f"(d[108]), "+f"(d[109]), "+f"(d[110]), "+f"(d[111]), "+f"(d[112]), "+f"(d[113]), "+f"(d[114]), "+f"(d[115]), "+f"(d[116]), "+f"(d[117]), "+f"(d[118]), "+f"(d[119]), "+f"(d[120]), "+f"(d[121]), "+f"(d[122]), "+f"(d[123]), "+f"(d[124]), "+f"(d[125]), "+f"(d[126]), "+f"(d[127])
    : "l"(da), "l"(db), "r"(scale_d));
}
__device__ __forceinline__ void wgmma_n128_k(float (&d)[192], uint64_t da, uint64_t db, int scale_d) {
  asm volatile("{\n.reg .pred p;\nsetp.ne.b32 p, %66, 0;\n"
    "wgmma.mma_async.sync.aligned.m64n128k16.f32.bf16.bf16 {%0, %1, %2, %3, %4, %5, %6, %7, %8, %9, %10, %11, %12, %13, %14, %15, %16, %17, %18, %19, %20, %21, %22, %23, %24, %25, %26, %27, %28, %29, %30, %31, %32, %33, %34, %35, %36, %37, %38, %39, %40, %41, %42, %43, %44, %45, %46, %47, %48, %49, %50, %51, %52, %53, %54, %55, %56, %57, %58, %59, %60, %61, %62, %63}, %64, %65, p, 1, 1, 0, 0;\n}\n"
    : "+f"(d[128]), "+f"(d[129]), "+f"(d[130]), "+f"(d[131]), "+f"(d[132]), "+f"(d[133]), "+f"(d[134]), "+f"(d[135]), "+f"(d[136]), "+f"(d[137]), "+f"(d[138]), "+f"(d[139]), "+f"(d[140]), "+f"(d[141]), "+f"(d[142]), "+f"(d[143]), "+f"(d[144]), "+f"(d[145]), "+f"(d[146]), "+f"(d[147]), "+f"(d[148]), "+f"(d[149]), "+f"(d[150]), "+f"(d[151]), "+f"(d[152]), "+f"(d[153]), "+f"(d[154]), "+f"(d[155]), "+f"(d[156]), "+f"(d[157]), "+f"(d[158]), "+f"(d[159]), "+f"(d[160]), "+f"(d[161]), "+f"(d[162]), "+f"(d[163]), "+f"(d[164]), "+f"(d[165]), "+f"(d[166]), "+f"(d[167]), "+f"(d[168]), "+f"(d[169]), "+f"(d[170]), "+f"(d[171]), "+f"(d[172]), "+f"(d[173]), "+f"(d[174]), "+f"(d[175]), "+f"(d[176]), "+f"(d[177]), "+f"(d[178]), "+f"(d[179]), "+f"(d[180]), "+f"(d[181]), "+f"(d[182]), "+f"(d[183]), "+f"(d[184]), "+f"(d[185]), "+f"(d[186]), "+f"(d[187]), "+f"(d[188]), "+f"(d[189]), "+f"(d[190]), "+f"(d[191])
    : "l"(da), "l"(db), "r"(scale_d));
}
__device__ __forceinline__ void wgmma_n40_tt(float (&d)[20], uint64_t da, uint64_t db, int scale_d) {
  asm volatile("{\n.reg .pred p;\nsetp.ne.b32 p, %22, 0;\n"
    "wgmma.mma_async.sync.aligned.m64n40k16.f32.bf16.bf16 {%0, %1, %2, %3, %4, %5, %6, %7, %8, %9, %10, %11, %12, %13, %14, %15, %16, %17, %18, %19}, %20, %21, p, 1, 1, 1, 1;\n}\n"
    : "+f"(d[0]), "+f"(d[1]), "+f"(d[2]), "+f"(d[3]), "+f"(d[4]), "+f"(d[5]), "+f"(d[6]), "+f"(d[7]), "+f"(d[8]), "+f"(d[9]), "+f"(d[10]), "+f"(d[11]), "+f"(d[12]), "+f"(d[13]), "+f"(d[14]), "+f"(d[15]), "+f"(d[16]), "+f"(d[17]), "+f"(d[18]), "+f"(d[19])
    : "l"(da), "l"(db), "r"(scale_d));
}
__device__ __forceinline__ void wgmma_n40_rs(float (&d)[20], const uint32_t (&a)[4], uint64_t db, int scale_d) {
  asm volatile("{\n.reg .pred p;\nsetp.ne.b32 p, %25, 0;\n"
    "wgmma.mma_async.sync.aligned.m64n40k16.f32.bf16.bf16 {%0, %1, %2, %3, %4, %5, %6, %7, %8, %9, %10, %11, %12, %13, %14, %15, %16, %17, %18, %19}, {%20, %21, %22, %23}, %24, p, 1, 1, 1;\n}\n"
    : "+f"(d[0]), "+f"(d[1]), "+f"(d[2]), "+f"(d[3]), "+f"(d[4]), "+f"(d[5]), "+f"(d[6]), "+f"(d[7]), "+f"(d[8]), "+f"(d[9]), "+f"(d[10]), "+f"(d[11]), "+f"(d[12]), "+f"(d[13]), "+f"(d[14]), "+f"(d[15]), "+f"(d[16]), "+f"(d[17]), "+f"(d[18]), "+f"(d[19])
    : "r"(a[0]), "r"(a[1]), "r"(a[2]), "r"(a[3]), "l"(db), "r"(scale_d));
}
__device__ __forceinline__ void wgmma_n128_0(float (&d)[192], uint64_t da, uint64_t db) {
  asm volatile("{\n.reg .pred p;\nsetp.ne.b32 p, 0, 0;\n"
    "wgmma.mma_async.sync.aligned.m64n128k16.f32.bf16.bf16 {%0, %1, %2, %3, %4, %5, %6, %7, %8, %9, %10, %11, %12, %13, %14, %15, %16, %17, %18, %19, %20, %21, %22, %23, %24, %25, %26, %27, %28, %29, %30, %31, %32, %33, %34, %35, %36, %37, %38, %39, %40, %41, %42, %43, %44, %45, %46, %47, %48, %49, %50, %51, %52, %53, %54, %55, %56, %57, %58, %59, %60, %61, %62, %63}, %64, %65, p, 1, 1, 0, 1;\n}\n"
    : "=f"(d[128]), "=f"(d[129]), "=f"(d[130]), "=f"(d[131]), "=f"(d[132]), "=f"(d[133]), "=f"(d[134]), "=f"(d[135]), "=f"(d[136]), "=f"(d[137]), "=f"(d[138]), "=f"(d[139]), "=f"(d[140]), "=f"(d[141]), "=f"(d[142]), "=f"(d[143]), "=f"(d[144]), "=f"(d[145]), "=f"(d[146]), "=f"(d[147]), "=f"(d[148]), "=f"(d[149]), "=f"(d[150]), "=f"(d[151]), "=f"(d[152]), "=f"(d[153]), "=f"(d[154]), "=f"(d[155]), "=f"(d[156]), "=f"(d[157]), "=f"(d[158]), "=f"(d[159]), "=f"(d[160]), "=f"(d[161]), "=f"(d[162]), "=f"(d[163]), "=f"(d[164]), "=f"(d[165]), "=f"(d[166]), "=f"(d[167]), "=f"(d[168]), "=f"(d[169]), "=f"(d[170]), "=f"(d[171]), "=f"(d[172]), "=f"(d[173]), "=f"(d[174]), "=f"(d[175]), "=f"(d[176]), "=f"(d[177]), "=f"(d[178]), "=f"(d[179]), "=f"(d[180]), "=f"(d[181]), "=f"(d[182]), "=f"(d[183]), "=f"(d[184]), "=f"(d[185]), "=f"(d[186]), "=f"(d[187]), "=f"(d[188]), "=f"(d[189]), "=f"(d[190]), "=f"(d[191])
    : "l"(da), "l"(db));
}
__device__ __forceinline__ void wgmma_n128_rs(float (&d)[192], const uint32_t (&a)[4], uint64_t db, int scale_d) {
  asm volatile("{\n.reg .pred p;\nsetp.ne.b32 p, %69, 0;\n"
    "wgmma.mma_async.sync.aligned.m64n128k16.f32.bf16.bf16 {%0, %1, %2, %3, %4, %5, %6, %7, %8, %9, %10, %11, %12, %13, %14, %15, %16, %17, %18, %19, %20, %21, %22, %23, %24, %25, %26, %27, %28, %29, %30, %31, %32, %33, %34, %35, %36, %37, %38, %39, %40, %41, %42, %43, %44, %45, %46, %47, %48, %49, %50, %51, %52, %53, %54, %55, %56, %57, %58, %59, %60, %61, %62, %63}, {%64, %65, %66, %67}, %68, p, 1, 1, 1;\n}\n"
    : "+f"(d[128]), "+f"(d[129]), "+f"(d[130]), "+f"(d[131]), "+f"(d[132]), "+f"(d[133]), "+f"(d[134]), "+f"(d[135]), "+f"(d[136]), "+f"(d[137]), "+f"(d[138]), "+f"(d[139]), "+f"(d[140]), "+f"(d[141]), "+f"(d[142]), "+f"(d[143]), "+f"(d[144]), "+f"(d[145]), "+f"(d[146]), "+f"(d[147]), "+f"(d[148]), "+f"(d[149]), "+f"(d[150]), "+f"(d[151]), "+f"(d[152]), "+f"(d[153]), "+f"(d[154]), "+f"(d[155]), "+f"(d[156]), "+f"(d[157]), "+f"(d[158]), "+f"(d[159]), "+f"(d[160]), "+f"(d[161]), "+f"(d[162]), "+f"(d[163]), "+f"(d[164]), "+f"(d[165]), "+f"(d[166]), "+f"(d[167]), "+f"(d[168]), "+f"(d[169]), "+f"(d[170]), "+f"(d[171]), "+f"(d[172]), "+f"(d[173]), "+f"(d[174]), "+f"(d[175]), "+f"(d[176]), "+f"(d[177]), "+f"(d[178]), "+f"(d[179]), "+f"(d[180]), "+f"(d[181]), "+f"(d[182]), "+f"(d[183]), "+f"(d[184]), "+f"(d[185]), "+f"(d[186]), "+f"(d[187]), "+f"(d[188]), "+f"(d[189]), "+f"(d[190]), "+f"(d[191])
    : "r"(a[0]), "r"(a[1]), "r"(a[2]), "r"(a[3]), "l"(db), "r"(scale_d));
}
__device__ __forceinline__ void wgmma_n32_0(float (&d)[16], uint64_t da, uint64_t db) {
  asm volatile("{\n.reg .pred p;\nsetp.ne.b32 p, 0, 0;\n"
    "wgmma.mma_async.sync.aligned.m64n32k16.f32.bf16.bf16 {%0, %1, %2, %3, %4, %5, %6, %7, %8, %9, %10, %11, %12, %13, %14, %15}, %16, %17, p, 1, 1, 0, 1;\n}\n"
    : "=f"(d[0]), "=f"(d[1]), "=f"(d[2]), "=f"(d[3]), "=f"(d[4]), "=f"(d[5]), "=f"(d[6]), "=f"(d[7]), "=f"(d[8]), "=f"(d[9]), "=f"(d[10]), "=f"(d[11]), "=f"(d[12]), "=f"(d[13]), "=f"(d[14]), "=f"(d[15])
    : "l"(da), "l"(db));
}
__device__ __forceinline__ void wgmma_n32(float (&d)[16], uint64_t da, uint64_t db, int scale_d) {
  asm volatile("{\n.reg .pred p;\nsetp.ne.b32 p, %18, 0;\n"
    "wgmma.mma_async.sync.aligned.m64n32k16.f32.bf16.bf16 {%0, %1, %2, %3, %4, %5, %6, %7, %8, %9, %10, %11, %12, %13, %14, %15}, %16, %17, p, 1, 1, 0, 1;\n}\n"
    : "+f"(d[0]), "+f"(d[1]), "+f"(d[2]), "+f"(d[3]), "+f"(d[4]), "+f"(d[5]), "+f"(d[6]), "+f"(d[7]), "+f"(d[8]), "+f"(d[9]), "+f"(d[10]), "+f"(d[11]), "+f"(d[12]), "+f"(d[13]), "+f"(d[14]), "+f"(d[15])
    : "l"(da), "l"(db), "r"(scale_d));
}
__device__ __forceinline__ void wgmma_n8_t(float (&d)[4], uint64_t da, uint64_t db, int scale_d) {
  asm volatile("{\n.reg .pred p;\nsetp.ne.b32 p, %6, 0;\n"
    "wgmma.mma_async.sync.aligned.m64n8k16.f32.bf16.bf16 {%0, %1, %2, %3}, %4, %5, p, 1, 1, 1, 0;\n}\n"
    : "+f"(d[0]), "+f"(d[1]), "+f"(d[2]), "+f"(d[3])
    : "l"(da), "l"(db), "r"(scale_d));
}
__device__ __forceinline__ void wgmma_n128_rs0(float (&d)[192], const uint32_t (&a)[4], uint64_t db) {
  asm volatile("{\n.reg .pred p;\nsetp.ne.b32 p, 0, 0;\n"
    "wgmma.mma_async.sync.aligned.m64n128k16.f32.bf16.bf16 {%0, %1, %2, %3, %4, %5, %6, %7, %8, %9, %10, %11, %12, %13, %14, %15, %16, %17, %18, %19, %20, %21, %22, %23, %24, %25, %26, %27, %28, %29, %30, %31, %32, %33, %34, %35, %36, %37, %38, %39, %40, %41, %42, %43, %44, %45, %46, %47, %48, %49, %50, %51, %52, %53, %54, %55, %56, %57, %58, %59, %60, %61, %62, %63}, {%64, %65, %66, %67}, %68, p, 1, 1, 1;\n}\n"
    : "=f"(d[128]), "=f"(d[129]), "=f"(d[130]), "=f"(d[131]), "=f"(d[132]), "=f"(d[133]), "=f"(d[134]), "=f"(d[135]), "=f"(d[136]), "=f"(d[137]), "=f"(d[138]), "=f"(d[139]), "=f"(d[140]), "=f"(d[141]), "=f"(d[142]), "=f"(d[143]), "=f"(d[144]), "=f"(d[145]), "=f"(d[146]), "=f"(d[147]), "=f"(d[148]), "=f"(d[149]), "=f"(d[150]), "=f"(d[151]), "=f"(d[152]), "=f"(d[153]), "=f"(d[154]), "=f"(d[155]), "=f"(d[156]), "=f"(d[157]), "=f"(d[158]), "=f"(d[159]), "=f"(d[160]), "=f"(d[161]), "=f"(d[162]), "=f"(d[163]), "=f"(d[164]), "=f"(d[165]), "=f"(d[166]), "=f"(d[167]), "=f"(d[168]), "=f"(d[169]), "=f"(d[170]), "=f"(d[171]), "=f"(d[172]), "=f"(d[173]), "=f"(d[174]), "=f"(d[175]), "=f"(d[176]), "=f"(d[177]), "=f"(d[178]), "=f"(d[179]), "=f"(d[180]), "=f"(d[181]), "=f"(d[182]), "=f"(d[183]), "=f"(d[184]), "=f"(d[185]), "=f"(d[186]), "=f"(d[187]), "=f"(d[188]), "=f"(d[189]), "=f"(d[190]), "=f"(d[191])
    : "r"(a[0]), "r"(a[1]), "r"(a[2]), "r"(a[3]), "l"(db));
}
__device__ __forceinline__ void wgmma_n256_rs(float (&d)[192], const uint32_t (&a)[4], uint64_t db, int scale_d) {
  asm volatile("{\n.reg .pred p;\nsetp.ne.b32 p, %133, 0;\n"
    "wgmma.mma_async.sync.aligned.m64n256k16.f32.bf16.bf16 {%0, %1, %2, %3, %4, %5, %6, %7, %8, %9, %10, %11, %12, %13, %14, %15, %16, %17, %18, %19, %20, %21, %22, %23, %24, %25, %26, %27, %28, %29, %30, %31, %32, %33, %34, %35, %36, %37, %38, %39, %40, %41, %42, %43, %44, %45, %46, %47, %48, %49, %50, %51, %52, %53, %54, %55, %56, %57, %58, %59, %60, %61, %62, %63, %64, %65, %66, %67, %68, %69, %70, %71, %72, %73, %74, %75, %76, %77, %78, %79, %80, %81, %82, %83, %84, %85, %86, %87, %88, %89, %90, %91, %92, %93, %94, %95, %96, %97, %98, %99, %100, %101, %102, %103, %104, %105, %106, %107, %108, %109, %110, %111, %112, %113, %114, %115, %116, %117, %118, %119, %120, %121, %122, %123, %124, %125, %126, %127}, {%128, %129, %130, %131}, %132, p, 1, 1, 1;\n}\n"
    : "+f"(d[0]), "+f"(d[1]), "+f"(d[2]), "+f"(d[3]), "+f"(d[4]), "+f"(d[5]), "+f"(d[6]), "+f"(d[7]), "+f"(d[8]), "+f"(d[9]), "+f"(d[10]), "+f"(d[11]), "+f"(d[12]), "+f"(d[13]), "+f"(d[14]), "+f"(d[15]), "+f"(d[16]), "+f"(d[17]), "+f"(d[18]), "+f"(d[19]), "+f"(d[20]), "+f"(d[21]), "+f"(d[22]), "+f"(d[23]), "+f"(d[24]), "+f"(d[25]), "+f"(d[26]), "+f"(d[27]), "+f"(d[28]), "+f"(d[29]), "+f"(d[30]), "+f"(d[31]), "+f"(d[32]), "+f"(d[33]), "+f"(d[34]), "+f"(d[35]), "+f"(d[36]), "+f"(d[37]), "+f"(d[38]), "+f"(d[39]), "+f"(d[40]), "+f"(d[41]), "+f"(d[42]), "+f"(d[43]), "+f"(d[44]), "+f"(d[45]), "+f"(d[46]), "+f"(d[47]), "+f"(d[48]), "+f"(d[49]), "+f"(d[50]), "+f"(d[51]), "+f"(d[52]), "+f"(d[53]), "+f"(d[54]), "+f"(d[55]), "+f"(d[56]), "+f"(d[57]), "+f"(d[58]), "+f"(d[59]), "+f"(d[60]), "+f"(d[61]), "+f"(d[62]), "+f"(d[63]), "+f"(d[64]), "+f"(d[65]), "+f"(d[66]), "+f"(d[67]), "+f"(d[68]), "+f"(d[69]), "+f"(d[70]), "+f"(d[71]), "+f"(d[72]), "+f"(d[73]), "+f"(d[74]), "+f"(d[75]), "+f"(d[76]), "+f"(d[77]), "+f"(d[78]), "+f"(d[79]), "+f"(d[80]), "+f"(d[81]), "+f"(d[82]), "+f"(d[83]), "+f"(d[84]), "+f"(d[85]), "+f"(d[86]), "+f"(d[87]), "+f"(d[88]), "+f"(d[89]), "+f"(d[90]), "+f"(d[91]), "+f"(d[92]), "+f"(d[93]), "+f"(d[94]), "+f"(d[95]), "+f"(d[96]), "+f"(d[97]), "+f"(d[98]), "+f"(d[99]), "+f"(d[100]), "+f"(d[101]), "+f"(d[102]), "+f"(d[103]), "+f"(d[104]), "+f"(d[105]), "+f"(d[106]), "+f"(d[107]), "+f"(d[108]), "+f"(d[109]), "+f"(d[110]), "+f"(d[111]), "+f"(d[112]), "+f"(d[113]), "+f"(d[114]), "+f"(d[115]), "+f"(d[116]), "+f"(d[117]), "+f"(d[118]), "+f"(d[119]), "+f"(d[120]), "+f"(d[121]), "+f"(d[122]), "+f"(d[123]), "+f"(d[124]), "+f"(d[125]), "+f"(d[126]), "+f"(d[127])
    : "r"(a[0]), "r"(a[1]), "r"(a[2]), "r"(a[3]), "l"(db), "r"(scale_d));
}
__device__ __forceinline__ void wgmma_n256_rs0(float (&d)[192], const uint32_t (&a)[4], uint64_t db) {
  asm volatile("{\n.reg .pred p;\nsetp.ne.b32 p, 0, 0;\n"
    "wgmma.mma_async.sync.aligned.m64n256k16.f32.bf16.bf16 {%0, %1, %2, %3, %4, %5, %6, %7, %8, %9, %10, %11, %12, %13, %14, %15, %16, %17, %18, %19, %20, %21, %22, %23, %24, %25, %26, %27, %28, %29, %30, %31, %32, %33, %34, %35, %36, %37, %38, %39, %40, %41, %42, %43, %44, %45, %46, %47, %48, %49, %50, %51, %52, %53, %54, %55, %56, %57, %58, %59, %60, %61, %62, %63, %64, %65, %66, %67, %68, %69, %70, %71, %72, %73, %74, %75, %76, %77, %78, %79, %80, %81, %82, %83, %84, %85, %86, %87, %88, %89, %90, %91, %92, %93, %94, %95, %96, %97, %98, %99, %100, %101, %102, %103, %104, %105, %106, %107, %108, %109, %110, %111, %112, %113, %114, %115, %116, %117, %118, %119, %120, %121, %122, %123, %124, %125, %126, %127}, {%128, %129, %130, %131}, %132, p, 1, 1, 1;\n}\n"
    : "=f"(d[0]), "=f"(d[1]), "=f"(d[2]), "=f"(d[3]), "=f"(d[4]), "=f"(d[5]), "=f"(d[6]), "=f"(d[7]), "=f"(d[8]), "=f"(d[9]), "=f"(d[10]), "=f"(d[11]), "=f"(d[12]), "=f"(d[13]), "=f"(d[14]), "=f"(d[15]), "=f"(d[16]), "=f"(d[17]), "=f"(d[18]), "=f"(d[19]), "=f"(d[20]), "=f"(d[21]), "=f"(d[22]), "=f"(d[23]), "=f"(d[24]), "=f"(d[25]), "=f"(d[26]), "=f"(d[27]), "=f"(d[28]), "=f"(d[29]), "=f"(d[30]), "=f"(d[31]), "=f"(d[32]), "=f"(d[33]), "=f"(d[34]), "=f"(d[35]), "=f"(d[36]), "=f"(d[37]), "=f"(d[38]), "=f"(d[39]), "=f"(d[40]), "=f"(d[41]), "=f"(d[42]), "=f"(d[43]), "=f"(d[44]), "=f"(d[45]), "=f"(d[46]), "=f"(d[47]), "=f"(d[48]), "=f"(d[49]), "=f"(d[50]), "=f"(d[51]), "=f"(d[52]), "=f"(d[53]), "=f"(d[54]), "=f"(d[55]), "=f"(d[56]), "=f"(d[57]), "=f"(d[58]), "=f"(d[59]), "=f"(d[60]), "=f"(d[61]), "=f"(d[62]), "=f"(d[63]), "=f"(d[64]), "=f"(d[65]), "=f"(d[66]), "=f"(d[67]), "=f"(d[68]), "=f"(d[69]), "=f"(d[70]), "=f"(d[71]), "=f"(d[72]), "=f"(d[73]), "=f"(d[74]), "=f"(d[75]), "=f"(d[76]), "=f"(d[77]), "=f"(d[78]), "=f"(d[79]), "=f"(d[80]), "=f"(d[81]), "=f"(d[82]), "=f"(d[83]), "=f"(d[84]), "=f"(d[85]), "=f"(d[86]), "=f"(d[87]), "=f"(d[88]), "=f"(d[89]), "=f"(d[90]), "=f"(d[91]), "=f"(d[92]), "=f"(d[93]), "=f"(d[94]), "=f"(d[95]), "=f"(d[96]), "=f"(d[97]), "=f"(d[98]), "=f"(d[99]), "=f"(d[100]), "=f"(d[101]), "=f"(d[102]), "=f"(d[103]), "=f"(d[104]), "=f"(d[105]), "=f"(d[106]), "=f"(d[107]), "=f"(d[108]), "=f"(d[109]), "=f"(d[110]), "=f"(d[111]), "=f"(d[112]), "=f"(d[113]), "=f"(d[114]), "=f"(d[115]), "=f"(d[116]), "=f"(d[117]), "=f"(d[118]), "=f"(d[119]), "=f"(d[120]), "=f"(d[121]), "=f"(d[122]), "=f"(d[123]), "=f"(d[124]), "=f"(d[125]), "=f"(d[126]), "=f"(d[127])
    : "r"(a[0]), "r"(a[1]), "r"(a[2]), "r"(a[3]), "l"(db));
}

constexpr int SLOT = 16384;
constexpr int VB = 4 * SLOT, PH = 0, XS = 6;
constexpr int SM_SD = 13 * SLOT;
constexpr int SM_BAR = SM_SD + 8192;
constexpr int SM_RS = SM_BAR + 1024;
constexpr int SM_AP = SM_RS + 640;
constexpr int SM_BP = SM_AP + 2048;
constexpr int SM_EPOCH = SM_BP + 6144;
constexpr int SM_TOTAL = SM_EPOCH + 16;
constexpr int FM = 0, FT = 16, FW = 30, CM = 46, CT = 62, CW = 76, B_EF = 92, B_STAT = 93, B_KVF = 94, B_HALO = 95,
              B_KVDONE = 96, B_OH0 = 97, B_OH1 = 98, B_XH0 = 99, B_XDONE = 100, B_WFD = 101, B_XT = 102, B_OF0 = 103, B_KVF1 = 104, B_RAW = 106  , B_X0 = 108;
#define EFS 0
constexpr uint64_t BAR_LG = EFS ? 0x00043333330001ull : 0x00043333330004ull;
#define BA(i) (bar + (i) * 8)
#define REL2(i) release2c(SB0 + SM_BAR + (i) * 8)
constexpr int NF = 3, ND = 13, NR = 0, NWOP = 48, NAOP = 38;
constexpr uint64_t TL_A = 0x6278627862786ull, TL_B = 0xa9c3ba9c3ba9cull, WO_A = 0x76b24038b51403ffull, WO_B = 0x8c5a197c6a297c8bull;
__constant__ uint32_t c_wop[NWOP + 1] = {0xeb0009, 0x186b8000, 0x6c0112, 0x1aec011a, 0x6c8224, 0x22ec822b, 0x18170330, 0x18178442, 0x18180554, 0x18188660, 0x18190772, 0x18198884, 0x181a0990, 0x181a8aa2, 0x181b0bb4, 0x181b8cc0, 0xaed10fc, 0xa9711e9, 0x181c0dd2, 0xa9792da, 0x129813cb, 0x181c8ee4, 0x181d0ff0, 0x109d94b3, 0x109f15ac, 0x109f9699, 0x10a0178a, 0x10a0987b, 0x10a11963, 0x10a19a5c, 0x10a21b49, 0x10a29c3a, 0x9231e0b, 0x9239f18, 0x1124202c, 0x13242137, 0x1124a249, 0x1324a352, 0x1125246a, 0x13252576, 0x1127268c, 0x1127a797, 0x112828a9, 0x1128a9b1, 0x11292aca, 0x13292bd5, 0x112a2cec, 0x132a2df8, 0};
__constant__ uint32_t c_aop[NAOP + 1] = {0x6d8228, 0x170336, 0x178447, 0x180558, 0x188666, 0x190777, 0x198888, 0x1a0996, 0x1a8aa7, 0x1b0bb8, 0x1b8cc6, 0x1c0dd7, 0x1c8ee8, 0x1d0ff6, 0x1d93c2, 0x1f14b6, 0x1f95a8, 0x201697, 0x209782, 0x211876, 0x219968, 0x221a57, 0x229b42, 0x231c36, 0xa3a023, 0xae2130, 0x2ae2244, 0x2ae2351, 0x2ae2465, 0xa6257b, 0xa6a688, 0xa72793, 0xa7a8a0, 0xa829b4, 0xa8aac2, 0xa9abdb, 0x2a9ace6, 0xaaadf7, 0};
__constant__ uint32_t c_map[64] = {4, 5, 6, 7, 0, 16, 32, 48, 64, 80, 96, 112, 1, 17, 33, 49, 65, 81, 97, 113, 2, 18, 34, 50, 66, 82, 98, 114, 3, 19, 35, 51, 67, 83, 99, 115, 20, 36, 52, 68, 84, 100, 116, 21, 37, 53, 69, 85, 101, 117, 22, 38, 54, 70, 86, 102, 118, 23, 39, 55, 71, 87, 103, 119};
enum { MAP_WF = 0, MAP_WA = 2, MAP_WB = 4, MAP_WOA = 6, MAP_WOB = 8, MAP_X0 = 10, MAP_X = 11, MAP_O = 12, MAP_PHI = 13, NMAP = 14 };
struct Maps { CUtensorMap m[NMAP]; };

#define PL 2
#define PROFL(a, b)
#define SUBS 8
#define QORD 1
#define NCH 4
#define CHW 1
#define SUBS1 12
#define XRAT 10
#define XRN 4
#define BT1 1
#define CV0 0
#define ST1 8
#define X0AT 1
#define W1DL 400
#define SKA 0
#define SKB 0
#define BPRE 0
#define XST 3
#define NLAYERS 4
constexpr float L2E = 1.4426950408889634f;

#define D128(lo) desc64(lo, 0x40000040u)
struct Ctx { uint32_t zero, boff; const bf16* x0; bf16* out; };
#define BLK_CTX() \
  uint32_t bid_; asm volatile("mov.u32 %0, %%ctaid.x;" : "=r"(bid_)); \
  bid_ -= c.boff; \
  const uint32_t gr_ = c_map[bid_ >> 1]; \
  const int cr = bid_ & 1, g = gr_ & 7, rb = (gr_ >> 3) + cr, m0 = rb * 128; \
  const uint32_t sb = SB0 + (cr << 24); \
  const uint32_t bar = sb + SM_BAR; \
  (void)cr; (void)g; (void)rb; (void)m0; (void)bar;
extern __shared__ uint8_t smem_raw[];
constexpr uint32_t SB0 = 1024;

#define PHASE_CTX() \
  BLK_CTX(); \
  int tid_ = threadIdx.x; asm volatile("" : "+r"(tid_)); \
  const int lane = tid_ & 31, cw = (tid_ >> 5) - 4, wg = cw >> 2, wq = cw & 3, gq = lane >> 2, t = lane & 3, wrow0 = cw * 16; \
  const int lrow = (lane & 7) + ((lane >> 3) & 1) * 8, lchk = lane >> 4; \
  const bool elected = (tid_ & 127) == 0; \
  const uint32_t rowo = (wrow0 + lrow) * 128, X = (lchk ^ (lane & 7)) << 4; \
  const uint32_t Y = (wrow0 + (lane & 7)) * 128 + (((lane >> 3) ^ (lane & 7)) << 4); \
  const size_t gfr = (size_t)(m0 + wrow0 + gq) * D_ + g * 128 + 8 * t; \
  (void)bar; (void)wq; (void)gq; (void)lrow; (void)lchk; (void)elected; (void)wrow0; (void)wg; (void)rowo; (void)X; (void)t; (void)Y; (void)gfr;
#define MMA_CTX() \
  const uint32_t wu = __shfl_sync(0xffffffffu, wg, 0); \
  const uint32_t dA0 = ((SB0 >> 4) | (1u << 16)) + wu * 512, dB0 = (SB0 >> 4) | (512u << 16); \
  const uint32_t par = layer & 1;

__device__ __forceinline__ void slab_out_half(uint32_t slot, bf16* dst, int wrow0, int lane) {
  const int r0 = lane >> 3, ch = lane & 7;
  const uint32_t src = slot + (wrow0 + r0) * 128;
  uint4 v[4];
#pragma unroll
  for (int i = 0; i < 4; ++i) v[i] = lds128(src + i * 512 + (((ch ^ (4 * i + r0)) & 7) << 4));
  dst += (size_t)(wrow0 + r0) * D_ + ch * 8;
#pragma unroll
  for (int i = 0; i < 4; ++i) *reinterpret_cast<uint4*>(dst + (size_t)i * 4 * D_) = v[i];
}

__device__ __forceinline__ void consumer(const Ctx& c) {
  float acc[192];
  uint32_t xf[4][4];
  uint32_t xp[8][4];
  {
    PHASE_CTX();
    const unsigned int epoch = ld_relaxed(&g_epoch);
    PROFT(tid_ == 128, 0);
    const uint32_t wu = __shfl_sync(0xffffffffu, wg, 0);
    if (tid_ < 128 + 8) sts128(sb + SM_AP + lane * 16, make_uint4(0x3F803F80u, 0x3F803F80u, 0x3F803F80u, 0x3F803F80u));
#pragma unroll 1
    for (int it = 0; it < 2; ++it) {
      float p[4][16];
      mbar_wait(BA(B_RAW + it), 0);
      PROFT(tid_ == 128, it ? 15 : 2);
      const uint32_t da = ((SB0 >> 4) | (1u << 16)) + (wu ? 9 + it : 2 * it) * 1024, db = (SB0 + SM_SD) >> 4;
      wgmma_fence();
#pragma unroll
      for (int h = 0; h < 4; ++h) wgmma_n32_0(p[h], D128(da + (h >> 1) * 512 + (h & 1) * 4), desc64(db + h * 128, 0x80000020u));
#pragma unroll
      for (int h = 0; h < 4; ++h) wgmma_n32(p[h], D128(da + (h >> 1) * 512 + (h & 1) * 4 + 2), desc64(db + h * 128 + 64, 0x80000020u), 1);
      wgmma_commit();
      wgmma_wait<0>();
#pragma unroll
      for (int i = 0; i < 64; ++i) asm volatile("" : "+f"(p[i >> 4][i & 15]) :: "memory");
      const uint32_t base = sb + (wg ? 9 + it : 2 * it) * SLOT + (wq * 16 + gq) * 128;
      uint32_t w[4][4][2];
#pragma unroll
      for (int i = 0; i < 32; ++i) w[i >> 3][(i >> 1) & 3][i & 1] = pack_bf16(p[i >> 3][2 * (i & 7)], p[i >> 3][2 * (i & 7) + 1]);
      if (wu) {
#pragma unroll
        for (int i = 0; i < 8; ++i)
          sts128(base + (i >> 2) * 8192 + (i & 1) * 1024 + (((((i >> 1) & 1) * 4 + t) ^ gq) << 4), make_uint4(w[i >> 1][0][i & 1], w[i >> 1][1][i & 1], w[i >> 1][2][i & 1], w[i >> 1][3][i & 1]));
      } else {
#pragma unroll
        for (int i = 0; i < 16; ++i)
          sts64(base + (i >> 3) * 8192 + (i & 1) * 1024 + ((((t & 1) * 4 + ((i >> 1) & 3)) ^ gq) << 4) + (t >> 1) * 8, w[(i >> 3) * 2][(i >> 1) & 3][i & 1], w[(i >> 3) * 2 + 1][(i >> 1) & 3][i & 1]);
      }
      fence_async_smem();
      __syncwarp();
      if (it == cr && lane == 0) mbar_arrive(BA(B_WFD));
    }
    if (tid_ == 128) sts_f(sb + SM_EPOCH, __uint_as_float(epoch & 1));
#pragma unroll
    for (int i = 0; i < 32; ++i) xp[i >> 2][i & 3] = 0u;
    nbar<1, 256>();
    PROFT(tid_ == 128, 13);
    mbar_wait(BA(FM + cr), 0);
    float cs[3][4];
    wgmma_fence();
#pragma unroll
    for (int ks = 0; ks < 4; ++ks)
#pragma unroll
      for (int i = 0; i < 3; ++i) {
        const uint32_t bx = (i == 0 ? 2 * cr * 1024 : i == 1 ? (2 * cr + 1) * 1024 : (9 + cr) * 1024) + wu * 512;
        wgmma_n8_t(cs[i], D128(((SB0 >> 4) | (512u << 16)) + bx + ks * 128), desc64((SB0 + SM_AP) >> 4, 0), ks != 0);
      }
    wgmma_commit();
    mbar_wait(BA(FM), 0);
#pragma unroll
    for (int k = 0; k < 4; ++k) ldsm_x4(xf[k][0], xf[k][1], xf[k][2], xf[k][3], sb + XS * SLOT + rowo + (X ^ (k << 5)));
    wgmma_wait<0>();
#pragma unroll
    for (int i = 0; i < 12; ++i) asm volatile("" : "+f"(cs[i >> 2][i & 3]) :: "memory");
    if (t < 2) {
#pragma unroll
      for (int i = 0; i < 3; ++i) red_add1(g_cs + (epoch & 1) * 6144 + g * 384 + i * 128 + wg * 64 + wq * 16 + gq + t * 8, t ? cs[i][2] : cs[i][0]);
    }
    PROFT(tid_ == 128, 14);
  }
#pragma unroll 1
  for (int layer = 0;; ++layer) {
    {
      wgmma_fence();
      wgmma_n256_rs0(acc, xf[0], D128((SB0 >> 4) | (512u << 16)));
#pragma unroll
      for (int k = 1; k < 4; ++k) wgmma_n256_rs(acc, xf[k], D128(((SB0 >> 4) | (512u << 16)) + k * 128), 1);
      wgmma_commit();
      PHASE_CTX();
      MMA_CTX();
      {
        const uint32_t ep = __float_as_uint(lds_f(sb + SM_EPOCH));
        if (layer == 0) {
          mbar_wait(BA(B_X0), 0);
#pragma unroll
          for (int i = 0; i < 8; ++i) ldsm_x4(xp[i][0], xp[i][1], xp[i][2], xp[i][3], sb + (11 + (i >> 2)) * SLOT + (Y ^ ((i & 2) << 5)) + (i & 1) * 1024);
          if (lane == ((xp[0][0] ^ xp[1][0] ^ xp[2][0] ^ xp[3][0] ^ xp[7][0]) & c.zero)) REL2(B_XT);
        } else {
#pragma unroll
          for (int i = 0; i < 8; ++i) stsm_x4(sb + (XS + (i >> 2)) * SLOT + (Y ^ ((i & 2) << 5)) + (i & 1) * 1024, xp[i][0], xp[i][1], xp[i][2], xp[i][3]);
        }
        float s0 = 0.f, s1 = 0.f, q0 = 0.f, q1 = 0.f;
        auto stats = [&](int j0, int j1) {
#pragma unroll
          for (int j = j0; j < j1; ++j) {
            const uint32_t u0 = xp[(j >> 2) * 2][j & 3], u1 = xp[(j >> 2) * 2 + 1][j & 3];
            s0 += bf_lo(u0) + bf_hi(u0); s1 += bf_lo(u1) + bf_hi(u1);
            q0 = fmaf(bf_lo(u0), bf_lo(u0), fmaf(bf_hi(u0), bf_hi(u0), q0)); q1 = fmaf(bf_lo(u1), bf_lo(u1), fmaf(bf_hi(u1), bf_hi(u1), q1));
          }
        };
        stats(0, ST1);
        fence_async_smem();
        nbar_dyn(3 + wu + (__float_as_uint(s0 + s1 + q0 + q1) & c.zero), 128);
        mbar_wait(BA(FM + 1), par);
        wgmma_fence();
#pragma unroll
        for (int k = 0; k < 4; ++k) wgmma_n256(acc, D128(dA0 + (XS + 1) * 1024 + k * 2), D128(dB0 + 2048 + k * 128), 1);
        wgmma_commit();
        wgmma_wait<1>();
#pragma unroll
        for (int i = 4; i < 8; ++i) stg128_p(layer, g_x + gfr + (i & 1) * 8 * D_ + (i >> 1) * 32, xp[i][0], xp[i][1], xp[i][2], xp[i][3]);
        {
          uint32_t zc; asm volatile("mov.u32 %0, %%clock;" : "=r"(zc) :: "memory");
          q0 += __uint_as_float(zc & c.zero); q1 += __uint_as_float(zc & c.zero); s0 += __uint_as_float(zc & c.zero); s1 += __uint_as_float(zc & c.zero);
        }
        stats(ST1, 16);
        wgmma_fence();
        wgmma_n128_0(acc, D128(dA0 + XS * 1024), D128(dB0 + 9 * 1024));
#pragma unroll
        for (int k = 1; k < 4; ++k) wgmma_n128(acc, D128(dA0 + XS * 1024 + k * 2), D128(dB0 + 9 * 1024 + k * 128), 1);
        wgmma_commit();
        const bool od = t & 1;
        float sa = od ? s1 : s0, qa = od ? q1 : q0;
        sa += __shfl_xor_sync(0xffffffffu, od ? s0 : s1, 1);
        qa += __shfl_xor_sync(0xffffffffu, od ? q0 : q1, 1);
        wgmma_fence();
#pragma unroll
        for (int k = 0; k < 4; ++k) wgmma_n128(acc, D128(dA0 + (XS + 1) * 1024 + k * 2), D128(dB0 + 10 * 1024 + k * 128), 1);
        wgmma_commit();
        sa += __shfl_xor_sync(0xffffffffu, sa, 2);
        qa += __shfl_xor_sync(0xffffffffu, qa, 2);
        red_add2_p(t < 2, reinterpret_cast<float*>(g_stats + (ep * 4 + layer) * S_ + m0 + wrow0 + gq + t * 8), sa, qa);
        __syncwarp();
        if (lane == 0) mbar_arrive(BA(B_XDONE));
        wgmma_wait<1>();
        if (elected) REL2(CM);
      }
      uint32_t s = 2;
#pragma unroll 1
      for (int i = 2; i < NF; ++i) {
        PROFL(tid_ == 128 && layer == PL + 1, 244 + 2 * i);
        mbar_wait(BA(FM + i), par);
        PROFL(tid_ == 128 && layer == PL + 1, 245 + 2 * i);
        const uint32_t da = dA0 + (XS + s) * 1024, dk = dB0 + s * 2048, dq = dB0 + (9 + s) * 1024;
        wgmma_fence();
#pragma unroll
        for (int k = 0; k < 4; ++k) wgmma_n128(acc, D128(da + k * 2), D128(dq + k * 128), 1);
        wgmma_commit();
        wgmma_wait<1>();
        if (elected) REL2(CM + i - 1);
        wgmma_fence();
#pragma unroll
        for (int k = 0; k < 4; ++k) wgmma_n256(acc, D128(da + k * 2), D128(dk + k * 128), 1);
        wgmma_commit();
        if (++s == 3) s = 0;
      }
#pragma unroll 1
      for (int i = NF; i < 15; ++i) {
        mbar_wait(BA(FM + i), par);
        const uint32_t da = dA0 + (XS + s) * 1024, dk = dB0 + s * 2048;
        wgmma_fence();
#pragma unroll
        for (int k = 0; k < 4; ++k) wgmma_n256(acc, D128(da + k * 2), D128(dk + k * 128), 1);
        wgmma_commit();
        wgmma_wait<1>();
        if (elected) REL2(CM + i - 1);
        if (++s == 3) s = 0;
      }
      {
        const uint64_t dap = desc64(((SB0 + SM_AP) >> 4) + wu * 64, 8), dbp = make_desc_ns(SB0 + SM_BP, 0, 128);
        mbar_wait(BA(B_STAT), par);
        mbar_wait(BA(FM + 15), par);
        PROFT(tid_ == 128, layer * 16 + 9);
        wgmma_fence();
        wgmma_n256_k(acc, dap, dbp, 1);
#pragma unroll
        for (int k = 0; k < 4; ++k) wgmma_n256(acc, D128(dA0 + XS * 1024 + k * 2), D128(dB0 + k * 128), 1);
        wgmma_commit();
        wgmma_wait<1>();
        if (elected) REL2(CM + 14);
        mbar_wait(BA(FT), par);
        wgmma_fence();
        wgmma_n128_k(acc, dap, dbp + 256, 1);
#pragma unroll
        for (int k = 0; k < 4; ++k) wgmma_n128(acc, D128(dA0 + (uint32_t)(TL_A & 15) * 1024 + k * 2), D128(dB0 + (uint32_t)(TL_B & 15) * 1024 + k * 128), 1);
        wgmma_commit();
        wgmma_wait<1>();
        if (elected) REL2(CM + 15);
#pragma unroll
        for (int i = 0; i < 128; ++i) asm volatile("" : "+f"(acc[i]) :: "memory");
      }
    }
    uint32_t of[8][4], o1[4][4];
    {
      PHASE_CTX();
      MMA_CTX();
      PROFT(tid_ == 128, layer * 16 + 1);
      PROFT(lane == 0 && layer == PL, 192 + cw);
      PROFT(tid_ == 128 && layer == PL, 160);
      uint64_t ta = (TL_A >> 4), tw = TL_B >> 4;
      uint32_t da, db, dz = dA0;
      auto sub = [&](int n) {
        const int j = n >> 2, k = n & 3;
        if (k == 0) {
          dz += c.zero;
          da = dz + ((uint32_t)ta & 15) * 1024; db = dB0 + ((uint32_t)tw & 15) * 1024;
          ta >>= 4; tw >>= 4;
          mbar_wait(BA(FT + j), par);
          wgmma_fence();
        }
        wgmma_n128(acc, D128(da + k * 2), D128(db + k * 128), 1);
        if (k == 3) {
          wgmma_commit();
          wgmma_wait<1>();
          if (elected) REL2(CT + j - 1);
        }
      };
      auto run = [&](int j0, int j1) {
#pragma unroll 1
        for (int j = j0; j < j1; ++j) {
          mbar_wait(BA(FT + j), par);
          da = dA0 + ((uint32_t)ta & 15) * 1024; db = dB0 + ((uint32_t)tw & 15) * 1024;
          ta >>= 4; tw >>= 4;
          wgmma_fence();
#pragma unroll
          for (int k = 0; k < 4; ++k) wgmma_n128(acc, D128(da + k * 2), D128(db + k * 128), 1);
          wgmma_commit();
          wgmma_wait<1>();
          if (elected) REL2(CT + j - 1);
        }
        ta = TL_A >> (4 * j1); tw = TL_B >> (4 * j1);
      };
      auto rest = [&](int j0, int sk) {
        if (sk) {
          run(j0, ND - sk);
          if (wu == 0) nbar<6, 256>();
          j0 = ND - sk;
        }
        run(j0, ND);
        if (sk && wu) asm volatile("bar.arrive 6, 256;" ::: "memory");
      };
      auto rest_end = [&]() {
        wgmma_wait<0>();
        if (elected) REL2(CT + ND - 1);
#pragma unroll
        for (int i = 128; i < 192; ++i) asm volatile("" : "+f"(acc[i]) :: "memory");
      };
      auto wo0 = [&]() {
        wgmma_fence();
        wgmma_n128_rs0(acc, of[0], D128(dB0 + (uint32_t)(WO_B & 15) * 1024));
#pragma unroll
        for (int k = 1; k < 4; ++k) wgmma_n128_rs(acc, of[k], D128(dB0 + (uint32_t)(WO_B & 15) * 1024 + k * 128), 1);
        wgmma_commit();
      };
      const float rs0 = lds_f(sb + SM_RS + (16 + wrow0 + gq) * 4), rs1 = lds_f(sb + SM_RS + (24 + wrow0 + gq) * 4);
#define EPOCH() __float_as_uint(lds_f(sb + SM_EPOCH))
      mbar_wait(BA(CM + 14), par);
      if (par) {
        uint32_t kk[8][4], kp[8][4], vf[2][2][4][4];
        int sn = 4;
#pragma unroll
        for (int i = 0; i < 4 * BT1; ++i) sub(sn++);
        {
          uint32_t vv[8][4];
#pragma unroll
          for (int jp = 0; jp < 8; ++jp) {
            kk[jp][0] = pack_bf16(acc[8 * jp], acc[8 * jp + 1]); kk[jp][1] = pack_bf16(acc[8 * jp + 4], acc[8 * jp + 5]);
            kk[jp][2] = pack_bf16(acc[8 * jp + 2], acc[8 * jp + 3]); kk[jp][3] = pack_bf16(acc[8 * jp + 6], acc[8 * jp + 7]);
#pragma unroll
            for (int i = 0; i < 4; ++i) vv[jp][i] = pack_bf16(acc[64 + 8 * jp + 2 * i], acc[65 + 8 * jp + 2 * i]);
          }
          if (cw == 7) {
            uint32_t* const hbuf = g_halo + (size_t)(((layer >> 1) * 17 + rb + 1) * 8 + g) * 2048;
#pragma unroll
            for (int jp = 0; jp < 8; ++jp) stg128(hbuf + jp * 128 + lane * 4, kk[jp][0], kk[jp][1], kk[jp][2], kk[jp][3]);
#pragma unroll
            for (int i = 0; i < 32; ++i) hbuf[1024 + (i >> 4) * 512 + (gq + (i & 1) * 8) * 32 + ((((i >> 1) & 7) ^ gq) << 2) + t] = vv[i >> 2][i & 3];
            __syncwarp();
            if (lane == 0) mbar_arrive(BA(B_OF0));
          }
#pragma unroll
          for (int jp = 0; jp < 8; ++jp) {
            sub(sn++);
            stsm_x4(sb + VB + (jp >> 2) * SLOT + rowo + (X ^ ((jp & 3) << 5)), vv[jp][0], vv[jp][1], vv[jp][2], vv[jp][3]);
          }
        }
        PROFT(tid_ == 128, layer * 16 + 2);
        const int e = gq & 1;
        float f0[4], f1[4], b0[4], b1[4], rj[4];
#pragma unroll
        for (int nt = 0; nt < 4; ++nt) {
          const int kx = nt * 8 + 2 * t + e;
          const bool okk = (m0 + wrow0 + kx) >= 16;
          const int d0 = kx - gq, d1 = d0 - 8;
          rj[nt] = lds_f(sb + SM_RS + (wrow0 + kx) * 4);
          const bool m0_ = okk && d0 >= 2 && d0 <= 16, m1_ = okk && d1 >= 2 && d1 <= 16;
          f0[nt] = m0_ ? rj[nt] * rs0 * (0.17677669529663687f * L2E) : 0.f;
          f1[nt] = m1_ ? rj[nt] * rs1 * (0.17677669529663687f * L2E) : 0.f;
          b0[nt] = m0_ ? 0.f : -1e30f; b1[nt] = m1_ ? 0.f : -1e30f;
        }
        mbar_wait(BA(CM + 15), par);
#pragma unroll
        for (int jp = 0; jp < 8; ++jp) {
          sub(sn++);
          sts128(sb + PH + cw * 4096 + jp * 512 + lane * 16, make_uint4(kk[jp][0], kk[jp][1], kk[jp][2], kk[jp][3]));
        }
#pragma unroll
        for (int i = 0; i < 4; ++i) sub(sn++);
        nbar<1, 256>();
        PROFT(tid_ == 128, layer * 16 + 3);
        rest(sn >> 2, SKB);
        if (!BPRE) rest_end();
        PROFT(lane == 0 && layer == PL, 200 + cw);
        PROFT(tid_ == 128, layer * 16 + 10);
        if (cw == 0) mbar_wait(BA(B_HALO), (layer >> 1) & 1);
        PROFT(tid_ == 128, layer * 16 + 5);
        const uint32_t vs = sb + (cw ? VB + rowo - 2048 : SM_SD + 4096 + rowo), vst = cw ? SLOT : 2048;
        const uint32_t psel = e ? 0x1054u : 0x5410u;
#pragma unroll
        for (int hp = 0; hp < 2; ++hp) {
#pragma unroll
          for (int i = 4 * hp; i < 4 * hp + 4; ++i) {
            const uint4 u = lds128(sb + (cw ? PH + (cw - 1) * 4096 : SM_SD) + lane * 16 + i * 512);
            kp[i][0] = u.x; kp[i][1] = u.y; kp[i][2] = u.z; kp[i][3] = u.w;
          }
#pragma unroll
          for (int i = 4 * hp; i < 4 * hp + 4; ++i) {
            ldsm_x4_t(vf[0][i & 1][i >> 1][0], vf[0][i & 1][i >> 1][1], vf[0][i & 1][i >> 1][2], vf[0][i & 1][i >> 1][3], vs + (i >> 2) * vst + (X ^ ((i & 3) << 5)));
            ldsm_x4_t(vf[1][i & 1][i >> 1][0], vf[1][i & 1][i >> 1][1], vf[1][i & 1][i >> 1][2], vf[1][i & 1][i >> 1][3], sb + VB + (i >> 2) * SLOT + rowo + (X ^ ((i & 3) << 5)));
          }
          if (BPRE && !hp) rest_end();
          float l0[2][4], l1[2][4];
#pragma unroll
          for (int h = 0; h < 2; ++h) {
            const int H = 2 * hp + h;
            uint32_t qa[8];
#pragma unroll
            for (int i = 0; i < 8; ++i) qa[i] = pack_bf16(acc[128 + 16 * H + 2 * i], acc[129 + 16 * H + 2 * i]);
#pragma unroll
            for (int nt = 3; nt >= 0; --nt) {
              float sc[4] = {0.f, 0.f, 0.f, 0.f};
#pragma unroll
              for (int ks = 0; ks < 2; ++ks) {
                const uint32_t (&kf)[4] = nt < 2 ? kp[2 * H + ks] : kk[2 * H + ks];
                mma_bf16(sc, qa[4 * ks], qa[4 * ks + 1], qa[4 * ks + 2], qa[4 * ks + 3], kf[2 * (nt & 1)], kf[2 * (nt & 1) + 1]);
              }
              l0[h][nt] = fmaf(e ? sc[1] : sc[0], f0[nt], b0[nt]);
              l1[h][nt] = fmaf(e ? sc[3] : sc[2], f1[nt], b1[nt]);
            }
          }
          float mx0[2], mx1[2], s0[2], s1[2];
#pragma unroll
          for (int h = 0; h < 2; ++h) {
            mx0[h] = fmaxf(fmaxf(l0[h][0], l0[h][1]), l0[h][2]);
            mx1[h] = fmaxf(fmaxf(l1[h][1], l1[h][2]), l1[h][3]);
          }
#pragma unroll
          for (int o = 1; o <= 2; o <<= 1)
#pragma unroll
            for (int h = 0; h < 2; ++h) {
              mx0[h] = fmaxf(mx0[h], __shfl_xor_sync(0xffffffffu, mx0[h], o));
              mx1[h] = fmaxf(mx1[h], __shfl_xor_sync(0xffffffffu, mx1[h], o));
            }
#pragma unroll
          for (int h = 0; h < 2; ++h) {
#pragma unroll
            for (int nt = 0; nt < 3; ++nt) { l0[h][nt] = ex2(l0[h][nt] - mx0[h]); l1[h][nt + 1] = ex2(l1[h][nt + 1] - mx1[h]); }
            s0[h] = (l0[h][0] + l0[h][1]) + l0[h][2];
            s1[h] = (l1[h][1] + l1[h][2]) + l1[h][3];
          }
#pragma unroll
          for (int o = 1; o <= 2; o <<= 1)
#pragma unroll
            for (int h = 0; h < 2; ++h) {
              s0[h] += __shfl_xor_sync(0xffffffffu, s0[h], o);
              s1[h] += __shfl_xor_sync(0xffffffffu, s1[h], o);
            }
          uint32_t ow[2][2][4];
#pragma unroll
          for (int h = 0; h < 2; ++h) {
            const int H = 2 * hp + h;
            uint32_t pl[4], ph[4];
            const float i0 = rcp(s0[h]), i1 = rcp(s1[h]);
#pragma unroll
            for (int nt = 0; nt < 4; ++nt) {
              const uint32_t pk = pack_bf16(nt < 3 ? l0[h][nt] * i0 * rj[nt] : 0.f, nt > 0 ? l1[h][nt] * i1 * rj[nt] : 0.f);
              pl[nt] = nt < 3 ? __byte_perm(pk, 0u, psel) : 0u;
              ph[nt] = nt > 0 ? __byte_perm(pk, 0u, psel + 0x2222u) : 0u;
            }
#pragma unroll
            for (int nj = 0; nj < 4; ++nj) {
              float oa[4] = {0.f, 0.f, 0.f, 0.f};
#pragma unroll
              for (int ks = 0; ks < 2; ++ks)
                mma_bf16(oa, pl[2 * ks], ph[2 * ks], pl[2 * ks + 1], ph[2 * ks + 1], vf[ks][nj >> 1][H][2 * (nj & 1)], vf[ks][nj >> 1][H][2 * (nj & 1) + 1]);
              ow[h][0][nj] = pack_bf16(oa[0], oa[1]); ow[h][1][nj] = pack_bf16(oa[2], oa[3]);
            }
          }
          if (hp == 0) {
#pragma unroll
            for (int i = 0; i < 4; ++i) stg128(g_o + gfr + (i & 1) * 8 * D_ + (i >> 1) * 32, ow[i >> 1][i & 1][0], ow[i >> 1][i & 1][1], ow[i >> 1][i & 1][2], ow[i >> 1][i & 1][3]);
            __syncwarp();
            if (lane == 0) mbar_arrive(BA(B_OH0));
          } else {
#pragma unroll
            for (int i = 0; i < 16; ++i) o1[i >> 2][i & 3] = ow[i >> 3][(i >> 2) & 1][i & 3];
          }
#pragma unroll
          for (int i = 0; i < 16; ++i) of[4 * hp + (i >> 2)][i & 3] = ow[i >> 3][i & 1][(i >> 1) & 3];
          if (!hp) { PROFT(tid_ == 128, layer * 16 + 15); mbar_wait(BA(FW), par); }
        }
      } else {
        float sc[2] = {rs0 * L2E, rs1 * L2E};
        {
          const uint32_t vb = sb + VB + (rowo >> 1), X0 = (lchk ^ ((lane & 7) >> 1)) << 4;
          const uint32_t pb = sb + PH + (t & 1) * SLOT + (wrow0 + gq) * 128 + ((((t & 1) * 4 + (t & 2)) ^ gq) << 4);
          float kva[20], en[32], mx[2][2], mn[2][2];
#define PV(hp, j) acc[32 * (hp) + (j)]
          auto mm = [&](int hp, int j) {
            const int r = (j >> 1) & 1;
            if (j < 4 && !(j & 1)) { mx[hp][r] = PV(hp, j); mn[hp][r] = PV(hp, j); }
            else { mx[hp][r] = fmaxf(mx[hp][r], PV(hp, j)); mn[hp][r] = fminf(mn[hp][r], PV(hp, j)); }
          };
          auto mmx = [&](int hp) {
#pragma unroll
            for (int r = 0; r < 2; ++r) {
              mx[hp][r] = fmaxf(mx[hp][r], __shfl_xor_sync(0xffffffffu, mx[hp][r], 2)) * -sc[r];
              mn[hp][r] = fmaf(fminf(mn[hp][r], __shfl_xor_sync(0xffffffffu, mn[hp][r], 2)), sc[r], mx[hp][r]);
            }
          };
          auto stage = [&](int hp) {
#pragma unroll
            for (int i = 0; i < 20; ++i) asm volatile("" : "+f"(kva[i]) :: "memory");
            nbar_dyn(3 + wu, 128);
#pragma unroll
            for (int i = 0; i < 4; ++i)
              sts128(sb + VB + hp * SLOT + wg * 8192 + (wq * 128 + i * 32 + lane) * 16,
                     make_uint4(__float_as_uint(kva[4 * i]), __float_as_uint(kva[4 * i + 1]), __float_as_uint(kva[4 * i + 2]), __float_as_uint(kva[4 * i + 3])));
            if (t == 0) sts_f2(sb + SM_AP + ((2 * hp + wg) * 64 + wq * 16 + gq * 2) * 4, kva[16], kva[18]);
            fence_async_smem();
            __syncwarp();
            if (lane == 0) mbar_arrive(BA(B_KVDONE));
          };
          int sn = 4;
#pragma unroll
          for (int j = 0; j < 32; ++j) mm(0, j);
          mmx(0);
#pragma unroll
          for (int hp = 0; hp < 2; ++hp) {
            float sp[2] = {0.f, 0.f}, sm[2] = {0.f, 0.f};
#pragma unroll
            for (int j = 0; j < 32; ++j) {
              const int r = (j >> 1) & 1, ns = hp ? SUBS1 : SUBS;
              if ((j * ns) / 32 != ((j + 1) * ns) / 32) {
                sub(sn++);
                if (hp && sn == 4 + SUBS + 4 + 4 * (XST & 1)) { stage(0); PROFT(tid_ == 128, layer * 16 + 12); }
              }
              const float x = fmaf(PV(hp, j), sc[r], mx[hp][r]);
              PV(hp, j) = ex2(x); en[j] = ex2(mn[hp][r] - x);
              sp[r] += PV(hp, j); sm[r] += en[j];
              if (hp == 0) {
                mm(1, j);
                if ((j & 3) == 0) {
                  const int jp = 8 + (j >> 2);
                  stsm_x4(vb + ((jp - 8) >> 1) * 8192 + (X0 ^ ((jp & 1) << 5)), pack_bf16(acc[8 * jp], acc[8 * jp + 1]), pack_bf16(acc[8 * jp + 2], acc[8 * jp + 3]),
                          pack_bf16(acc[8 * jp + 4], acc[8 * jp + 5]), pack_bf16(acc[8 * jp + 6], acc[8 * jp + 7]));
                }
              }
            }
#pragma unroll
            for (int i = 0; i < 4; ++i) if (XST & (1 << hp)) sub(sn++);
#pragma unroll
            for (int r = 0; r < 2; ++r) {
              sp[r] = rcp(sp[r] + __shfl_xor_sync(0xffffffffu, sp[r], 2)) * (r ? rs1 : rs0);
              sm[r] = rcp(sm[r] + __shfl_xor_sync(0xffffffffu, sm[r], 2)) * (r ? rs1 : rs0);
            }
            if (hp == 0) { mmx(1); mbar_wait(BA(CM + 15), par); }
            else { PROFT(tid_ == 128, layer * 16 + 11); nbar<1, 256>(); }
#pragma unroll
            for (int i = 0; i < 4; ++i) {
              const int r = i & 1, d = 16 * (i >> 1) + 2 * r;
              sts128((pb + r * 1024) ^ ((i >> 1) << 4), make_uint4(pack_bf16(PV(hp, d) * sp[r], PV(hp, d + 1) * sp[r]), pack_bf16(PV(hp, d + 4) * sp[r], PV(hp, d + 5) * sp[r]),
                                                                    pack_bf16(PV(hp, d + 8) * sp[r], PV(hp, d + 9) * sp[r]), pack_bf16(PV(hp, d + 12) * sp[r], PV(hp, d + 13) * sp[r])));
              sts128((pb + r * 1024) ^ ((i >> 1) << 4) ^ 64, make_uint4(pack_bf16(en[d] * sm[r], en[d + 1] * sm[r]), pack_bf16(en[d + 4] * sm[r], en[d + 5] * sm[r]),
                                                                         pack_bf16(en[d + 8] * sm[r], en[d + 9] * sm[r]), pack_bf16(en[d + 12] * sm[r], en[d + 13] * sm[r])));
            }
            fence_async_smem();
            nbar<1, 256>();
            const uint32_t dP = dB0 + (PH >> 4) + wu * 1024;
            const uint32_t dV = (dB0 & 0xFFFFu) + ((VB + hp * SLOT) >> 4) + (((SM_SD - VB - hp * SLOT) >> 4) << 16) + wu * (512u - (512u << 16));
            wgmma_fence();
#pragma unroll
            for (int ks = 0; ks < 8; ++ks) wgmma_n40_tt(kva, D128(dP + ks * 128), desc64(dV + ks * 64, 0x80000020u), ks != 0);
            wgmma_commit();
          }
#pragma unroll
          for (int i = 0; i < 4; ++i) sub(sn++);
          stage(1);
          PROFT(tid_ == 128, layer * 16 + 3);
          rest(sn >> 2, SKA);
          rest_end();
          PROFT(lane == 0 && layer == PL, 200 + cw);
          PROFT(tid_ == 128, layer * 16 + 10);
        }
#define QV(H, i) acc[128 + 16 * (H) + (i)]
        float mx[4][2], mn[4][2];
        uint32_t ph[4][4][4];
        auto mnx = [&](int hp) {
#pragma unroll
          for (int H = 2 * hp; H < 2 * hp + 2; ++H)
#pragma unroll
            for (int r = 0; r < 2; ++r) {
              mx[H][r] = fmaxf(fmaxf(fmaxf(QV(H, 2 * r), QV(H, 2 * r + 1)), fmaxf(QV(H, 4 + 2 * r), QV(H, 5 + 2 * r))),
                               fmaxf(fmaxf(QV(H, 8 + 2 * r), QV(H, 9 + 2 * r)), fmaxf(QV(H, 12 + 2 * r), QV(H, 13 + 2 * r))));
              mn[H][r] = fminf(fminf(fminf(QV(H, 2 * r), QV(H, 2 * r + 1)), fminf(QV(H, 4 + 2 * r), QV(H, 5 + 2 * r))),
                               fminf(fminf(QV(H, 8 + 2 * r), QV(H, 9 + 2 * r)), fminf(QV(H, 12 + 2 * r), QV(H, 13 + 2 * r))));
            }
#pragma unroll
          for (int o = 1; o <= 2; o <<= 1)
#pragma unroll
            for (int H = 2 * hp; H < 2 * hp + 2; ++H)
#pragma unroll
              for (int r = 0; r < 2; ++r) {
                mx[H][r] = fmaxf(mx[H][r], __shfl_xor_sync(0xffffffffu, mx[H][r], o));
                mn[H][r] = fminf(mn[H][r], __shfl_xor_sync(0xffffffffu, mn[H][r], o));
              }
#pragma unroll
          for (int H = 2 * hp; H < 2 * hp + 2; ++H)
#pragma unroll
            for (int r = 0; r < 2; ++r) { mx[H][r] *= -sc[r]; mn[H][r] = fmaf(mn[H][r], sc[r], mx[H][r]); }
        };
        auto fm = [&](int H) {
#pragma unroll
          for (int i = 0; i < 8; ++i) {
            const int r = i & 1;
            const float x0 = fmaf(QV(H, 2 * i), sc[r], mx[H][r]), x1 = fmaf(QV(H, 2 * i + 1), sc[r], mx[H][r]);
            ph[H][i >> 2][i & 3] = pack_bf16(ex2(x0), ex2(x1));
            ph[H][2 + (i >> 2)][i & 3] = pack_bf16(ex2(mn[H][r] - x0), ex2(mn[H][r] - x1));
          }
        };
        auto conv = [&](int hp) {
          mbar_wait(BA(hp ? B_KVF1 : B_KVF), (layer >> 1) & 1);
          PROFT(tid_ == 128, layer * 16 + (hp ? 4 : 5));
          if (hp) { mbar_wait(BA(FW), par); nbar_dyn(3 + wu, 128); }
#pragma unroll
          for (int h = 0; h < 2; ++h) {
            uint4 u[4];
#pragma unroll
            for (int i = 0; i < 4; ++i) u[i] = lds128(sb + VB + hp * SLOT + h * 8192 + (wq * 128 + i * 32 + lane) * 16);
            const float zz = lds_f(sb + SM_AP + ((2 * hp + h) * 64 + wq * 16 + (lane & 7) * 2 + ((lane >> 3) & 1)) * 4);
            const uint32_t kb_ = sb + PH + wg * SLOT + h * 8192 + (wq * 16 + lrow) * 128;
#pragma unroll
            for (int i = 0; i < 4; i += 2)
              stsm_x4(kb_ + (X ^ (i << 4)),
                      pack_bf16(__uint_as_float(u[i].x), __uint_as_float(u[i].y)), pack_bf16(__uint_as_float(u[i].z), __uint_as_float(u[i].w)),
                      pack_bf16(__uint_as_float(u[i + 1].x), __uint_as_float(u[i + 1].y)), pack_bf16(__uint_as_float(u[i + 1].z), __uint_as_float(u[i + 1].w)));
            const uint32_t z1 = pack_bf16(zz, 1.f);
            if (lane < 16) sts128(kb_ + ((4 ^ (lane & 7)) << 4), make_uint4(z1, z1, z1, z1));
          }
          fence_async_smem();
        };
        mnx(0);
        fm(0);
        if (CV0) conv(0);
        fm(1);
        if (!CV0) conv(0);
#pragma unroll
        for (int hp = 0; hp < 2; ++hp) {
          nbar_dyn(3 + wu, 128);
          float oa[4][20];
          wgmma_fence();
#pragma unroll
          for (int s = 0; s < 2; ++s)
#pragma unroll
            for (int v = 0; v < 4; ++v) {
              const int h = v >> 1, s4 = 2 * (v & 1) + s;
              wgmma_n40_rs(oa[v], ph[2 * hp + h][s4], D128(dB0 + (PH >> 4) + wu * 1024 + h * 512 + (s4 ^ (2 * h)) * 128), s != 0);
            }
          wgmma_commit();
          if (hp == 0) { mnx(1); wgmma_wait<0>(); }
          else wgmma_wait<0>();
#pragma unroll
          for (int i = 0; i < 20; ++i) asm volatile("" : "+f"(oa[0][i]), "+f"(oa[1][i]), "+f"(oa[2][i]), "+f"(oa[3][i]) :: "memory");
          uint32_t ow[2][2][4];
#pragma unroll
          for (int h = 0; h < 2; ++h)
#pragma unroll
            for (int r = 0; r < 2; ++r) {
              const float a = oa[2 * h + 1][17 + 2 * r], b = oa[2 * h][17 + 2 * r];
              const float id = rcp(fmaf(oa[2 * h][16 + 2 * r], a, fmaf(a, 1e-6f, oa[2 * h + 1][16 + 2 * r]) * b));
              const float fa = a * id, fb = b * id;
#pragma unroll
              for (int j = 0; j < 4; ++j)
                ow[h][r][j] = pack_bf16(fmaf(oa[2 * h][4 * j + 2 * r], fa, oa[2 * h + 1][4 * j + 2 * r] * fb),
                                        fmaf(oa[2 * h][4 * j + 2 * r + 1], fa, oa[2 * h + 1][4 * j + 2 * r + 1] * fb));
            }
#pragma unroll
          for (int i = 0; i < 16; ++i) of[4 * hp + (i >> 2)][i & 3] = ow[i >> 3][i & 1][(i >> 1) & 3];
          if (hp == 0) {
#pragma unroll
            for (int i = 0; i < 8; ++i) {
              if (!(i & 1)) stg128(g_o + gfr + ((i >> 1) & 1) * 8 * D_ + (i >> 2) * 32, ow[i >> 2][(i >> 1) & 1][0], ow[i >> 2][(i >> 1) & 1][1], ow[i >> 2][(i >> 1) & 1][2], ow[i >> 2][(i >> 1) & 1][3]);
              const int r = i & 1;
              const float x0 = fmaf(QV(2, 2 * i), sc[r], mx[2][r]), x1 = fmaf(QV(2, 2 * i + 1), sc[r], mx[2][r]);
              ph[2][i >> 2][i & 3] = pack_bf16(ex2v(x0), ex2v(x1));
              ph[2][2 + (i >> 2)][i & 3] = pack_bf16(ex2v(mn[2][r] - x0), ex2v(mn[2][r] - x1));
            }
            __syncwarp();
            if (lane == 0) mbar_arrive(BA(B_OH0));
            PROFT(tid_ == 128 && layer, layer * 16 + 15);
            if (QORD) { fm(3); conv(1); } else { conv(1); fm(3); }
          } else {
#pragma unroll
            for (int i = 0; i < 16; ++i) o1[i >> 2][i & 3] = ow[i >> 3][(i >> 2) & 1][i & 3];
          }
        }
      }
      PROFT(tid_ == 128, layer * 16 + 6);
#pragma unroll
      for (int i = 0; i < 4; ++i) stg128(g_o + gfr + (i & 1) * 8 * D_ + (2 + (i >> 1)) * 32, o1[i][0], o1[i][1], o1[i][2], o1[i][3]);
      __syncwarp();
      if (lane == 0) { mbar_arrive(BA(B_OH1)); if (!EFS) REL2(B_EF); }
      PROFT(lane == 0 && layer == PL, 208 + cw);
      wo0();
    }
    {
      PHASE_CTX();
      MMA_CTX();
      mbar_wait(BA(FW + 1), par);
      wgmma_fence();
#pragma unroll
      for (int k = 0; k < 4; ++k) wgmma_n128_rs(acc, of[4 + k], D128(dB0 + (uint32_t)((WO_B >> 4) & 15) * 1024 + k * 128), 1);
      wgmma_commit();
      wgmma_wait<1>();
      if (elected) REL2(CW);
      uint64_t ta = WO_A >> 8, tw = WO_B >> 8;
      auto run = [&](int i0, int i1) {
#pragma unroll 1
        for (int i = i0; i < i1; ++i) {
          mbar_wait(BA(FW + i), par);
          PROFL(tid_ == 128 && layer == PL, 160 + i);
          const uint32_t da = dA0 + ((uint32_t)ta & 15) * 1024, db = dB0 + ((uint32_t)tw & 15) * 1024;
          ta >>= 4; tw >>= 4;
          wgmma_fence();
#pragma unroll
          for (int k = 0; k < 4; ++k) wgmma_n128(acc, D128(da + k * 2), D128(db + k * 128), 1);
          wgmma_commit();
          wgmma_wait<1>();
          if (elected) REL2(CW + i - 1);
        }
        ta = WO_A >> (4 * (i1 & 15)); tw = WO_B >> (4 * (i1 & 15));
      };
      run(2, XRAT);
#pragma unroll
      for (int j = 0; j < 8 / XRN; ++j) {
#pragma unroll
        for (int i = j * XRN; i < (j + 1) * XRN; ++i) ldg128((layer ? g_x : c.x0) + gfr + (i & 1) * 8 * D_ + (i >> 1) * 32, xp[i][0], xp[i][1], xp[i][2], xp[i][3]);
        run(XRAT + j, j + 1 < 8 / XRN ? XRAT + j + 1 : 16);
      }
      if (layer == 0) {
#pragma unroll
        for (int o = 1; o <= 2; o <<= 1)
#pragma unroll
          for (int i = 0; i < 16; ++i) {
            const int j = o == 1 ? 2 * (i & 1) : (i & 1);
            uint32_t &a = xp[i >> 1][j], &b = xp[i >> 1][j + o];
            const uint32_t r = __shfl_xor_sync(0xffffffffu, (t & o) ? a : b, o);
            if (t & o) a = r; else b = r;
          }
      }
      if (layer != NLAYERS - 1) mbar_wait(BA(FM), par ^ 1);
      wgmma_wait<0>();
#pragma unroll
      for (int i = 128; i < 192; ++i) asm volatile("" : "+f"(acc[i]) :: "memory");
      if (elected) REL2(CW + 15);
      PROFT(lane == 0 && layer == PL, 216 + cw);
      PROFT(tid_ == 128, layer * 16 + 7);
#pragma unroll
      for (int i = 0; i < 32; ++i)
        xp[i >> 2][i & 3] = add_bf16x2(xp[i >> 2][i & 3], pack_bf16(acc[128 + 16 * (i >> 3) + 4 * (i & 3) + 2 * ((i >> 2) & 1)], acc[129 + 16 * (i >> 3) + 4 * (i & 3) + 2 * ((i >> 2) & 1)]));
      if (layer == NLAYERS - 1) {
#pragma unroll
        for (int i = 0; i < 8; ++i) stsm_x4(sb + (XS + (i >> 2)) * SLOT + (Y ^ ((i & 2) << 5)) + (i & 1) * 1024, xp[i][0], xp[i][1], xp[i][2], xp[i][3]);
        __syncwarp();
        slab_out_half(sb + XS * SLOT, c.out + (size_t)m0 * D_ + g * 128, wrow0, lane);
        slab_out_half(sb + (XS + 1) * SLOT, c.out + (size_t)m0 * D_ + g * 128 + 64, wrow0, lane);
        PROFT(tid_ == 128, layer * 16 + 24);
        break;
      }
#pragma unroll
      for (int i = 0; i < 4; ++i) stg128(g_x + gfr + (i & 1) * 8 * D_ + (i >> 1) * 32, xp[i][0], xp[i][1], xp[i][2], xp[i][3]);
      __syncwarp();
      if (lane == 0) mbar_arrive(BA(B_XH0));
#pragma unroll
      for (int i = 0; i < 16; ++i) xf[i >> 2][i & 3] = xp[2 * (i >> 3) + (i & 1)][(i >> 1) & 3];
      PROFT(tid_ == 128, layer * 16 + 24);
    }
  }
}

__device__ __forceinline__ uint64_t k_order(int o) {
  const uint32_t lo = (1u << (4 * o)) - 1u, h0 = (0xECA86420u & lo) | ((0xECA86420u >> 4) & ~lo);
  return (uint64_t)(2 * o) | ((uint64_t)(2 * o + 1) << 4) | ((uint64_t)(h0 & 0xFFFFFFFu) << 8) | ((uint64_t)((h0 & 0xFFFFFFFu) | 0x1111111u) << 36);
}

__global__ void __cluster_dims__(2, 1, 1) __launch_bounds__(384, 1)
mega_kernel(const __grid_constant__ Maps maps, const __grid_constant__ Ctx c, const bf16* __restrict__ wA, const bf16* __restrict__ wB,
            const bf16* __restrict__ woA, const bf16* __restrict__ woB) {
  if (blockIdx.x - c.boff >= 128u) {
    const unsigned int epoch = ld_relaxed(&g_epoch);
    const int e = (blockIdx.x - c.boff) & 3, tid = threadIdx.x;
    float s[8] = {0.f, 0.f, 0.f, 0.f, 0.f, 0.f, 0.f, 0.f};
    const uint32_t sb = smem_u32(smem_raw), bar = sb + SM_BAR;
    auto issue = [&](int i) {
      mbar_expect_tx(BA(i & 3), 49152);
      bulk_load(sb + (i & 3) * 49152, wB + (size_t)e * 256 * 3072 + i * 24576, 49152, BA(i & 3));
    };
    if (tid == 0) {
#pragma unroll 1
      for (int i = 0; i < 4; ++i) {
        mbar_init(BA(i), 1);
        fence_async_smem();
        issue(i);
      }
    }
    __syncthreads();
#pragma unroll 1
    for (int i = 0; i < 32; ++i) {
      mbar_wait(BA(i & 3), (i >> 2) & 1);
#pragma unroll 2
      for (int r = 0; r < 8; ++r) {
        const uint4 v = lds128(sb + (i & 3) * 49152 + r * 6144 + tid * 16);
        s[0] += bf_lo(v.x); s[1] += bf_hi(v.x); s[2] += bf_lo(v.y); s[3] += bf_hi(v.y);
        s[4] += bf_lo(v.z); s[5] += bf_hi(v.z); s[6] += bf_lo(v.w); s[7] += bf_hi(v.w);
      }
      __syncthreads();
      if (tid == 0 && i < 28) issue(i + 4);
    }
    float* cd = g_cs + (epoch & 1) * 6144 + 3072 + ((tid >> 4) & 7) * 384 + (tid < 128 ? 256 : (tid >> 7) * 128 - 128) + (tid & 15) * 8;
    red_add4(cd, s[0], s[1], s[2], s[3]);
    red_add4(cd + 4, s[4], s[5], s[6], s[7]);
    __syncthreads();
    if (tid == 0) flag_add(&g_csflag[8].v);
    const int op = (epoch & 1) ^ 1;
    float4* kz = reinterpret_cast<float4*>(g_kv + (size_t)op * (2 * 8 * 8448)) + e * 8448;
#pragma unroll 1
    for (int i = tid; i < 8448; i += 384) kz[i] = make_float4(0.f, 0.f, 0.f, 0.f);
    reinterpret_cast<float4*>(g_cs + op * 6144)[e * 384 + tid] = make_float4(0.f, 0.f, 0.f, 0.f);
#pragma unroll 1
    for (int i = tid; i < 1024; i += 384) reinterpret_cast<float4*>(g_stats + (op * 4 + e) * S_)[i] = make_float4(0.f, 0.f, 0.f, 0.f);
    return;
  }
  const int warp = __shfl_sync(0xffffffffu, threadIdx.x >> 5, 0), lane = threadIdx.x & 31;
  if (smem_u32(smem_raw) != SB0 + ((blockIdx.x & 1) << 24)) __trap();
  {
  const int cid = (blockIdx.x - c.boff) >> 1, u7 = ((cid - 36) * 37) >> 8, cr = blockIdx.x & 1;
  const int g = cid < 4 ? 4 + cid : cid < 36 ? (cid - 4) >> 3 : 4 + u7, rb = (cid < 4 ? 0 : cid < 36 ? (cid - 4) & 7 : cid - 35 - 7 * u7) * 2 + cr, m0 = rb * 128;
  const uint32_t sb = SB0 + (cr << 24), bar = sb + SM_BAR;
  PROFT(lane == 0 && (warp == 0 || warp == 4), 224 + (warp >> 2) * 8);
  uint32_t cx = 0;
  if (warp == 2) {
    if (lane < NMAP) asm volatile("prefetch.tensormap [%0];" ::"l"(&maps.m[lane]) : "memory");
    if (lane == 31) asm volatile("prefetch.global.L2 [%0];" ::"l"(&g_epoch));
  } else if (warp == 3) {
    cx = c_map[cid] + c_wop[lane] + c_wop[NWOP - lane] + c_aop[lane] + c_aop[NAOP - lane] + (uint32_t)(uintptr_t)g_x;
  } else if (warp >= 4 && warp < 8) {
    const int i = threadIdx.x - 128;
    asm volatile("prefetch.global.L2 [%0];" ::"l"(wA + (size_t)((rb & ~1) * 64 + cr * 32 + ((i >> 1) & 31)) * 3072 + (i >> 6) * 1024 + g * 128 + (i & 1) * 64));
  }
  if (warp < 2) {
    const int s = warp, kb = (rb & ~1) + s;
    if (lane == 0) {
      mbar_init(BA(FM + s), 1u);
      mbar_init(BA(B_RAW + warp), 1u);
      if (warp) mbar_init(BA(B_X0), 1u);
      asm volatile("fence.mbarrier_init.release.cluster;" ::: "memory");
    }
    __syncwarp();
    if (warp == 0) tma_2d_e(sb + SM_SD, &maps.m[MAP_PHI], 0, g * 128, BA(B_RAW));
    else if (W1DL) __nanosleep(W1DL);
#pragma unroll
    for (int j = 0; j < 6; ++j)
      tma_5d_e(sb + (j < 2 ? 2 * s : j < 4 ? 9 + s : 2 * s + 1) * SLOT + (j & 1) * 8192, &maps.m[MAP_WA], (j < 2 ? 1024 : j < 4 ? 0 : 2048) + g * 128 + (j & 1) * 64, 2 * kb,
               BA(j < 4 ? B_RAW + warp : FM + s));
    tma_2d_e(sb + (XS + s) * SLOT, &maps.m[MAP_X0], kb * 64, m0, BA(FM + s));
    expect_tx_e(BA(B_RAW + warp), warp ? 32768 : 32768 + 8192);
    expect_tx_e(BA(FM + s), 32768);
    if (X0AT == 0 && warp == 1) {
      tma_2d_e(sb + 11 * SLOT, &maps.m[MAP_X0], g * 128, m0, BA(B_X0));
      tma_2d_e(sb + 12 * SLOT, &maps.m[MAP_X0], g * 128 + 64, m0, BA(B_X0));
      expect_tx_e(BA(B_X0), 32768);
    }
  } else if (warp >= 4 && lane == 0) {
#pragma unroll 1
    for (int i = 2 + (warp - 4) * 13; i < 15 + (warp - 4) * 13; ++i)
      mbar_init(BA(i), 1u << ((i < CM ? 0u : i < B_EF ? 2u : (uint32_t)(BAR_LG >> (4 * ((i - B_EF) & 15)))) & 7u));
    asm volatile("fence.mbarrier_init.release.cluster;" ::: "memory");
  }
  __syncwarp();
  asm volatile("barrier.cluster.arrive.relaxed.aligned;" ::: "memory");
  if (threadIdx.x == 96 + c.zero) sts_f(sb + SM_EPOCH + 4, __uint_as_float(cx));
  PROFT(lane == 0 && (warp == 0 || warp == 4), 225 + (warp >> 2) * 8);
  __syncwarp();
  PROFT(lane == 0 && (warp == 0 || warp == 4), 226 + (warp >> 2) * 8);
  }

  if (warp < 4) {
    asm volatile("setmaxnreg.dec.sync.aligned.u32 40;");
    PROFT(threadIdx.x == 0, 227);
    cluster_wait();
    PROFT(threadIdx.x == 0, 228);
    if (warp == 0 || warp == 3) {
    if (warp == 0) {
      BLK_CTX();
      const unsigned int epoch = __shfl_sync(0xffffffffu, ld_relaxed(&g_epoch), 0), xbase = epoch * NLAYERS;
      (void)xbase;
      const uint64_t ordg = k_order(g);
      if (X0AT) {
        mbar_wait_u(BA(B_RAW + X0AT - 1), 0);
        tma_2d_e(sb + 11 * SLOT, &maps.m[MAP_X0], g * 128, m0, BA(B_X0));
        tma_2d_e(sb + 12 * SLOT, &maps.m[MAP_X0], g * 128 + 64, m0, BA(B_X0));
        expect_tx_e(BA(B_X0), 32768);
      }
#pragma unroll 1
      for (int lp = 0; lp < 2 * NLAYERS; ++lp) {
        const int layer = lp >> 1, n1 = (lp & 1) ? NAOP : NAOP - 14;
        int n = (lp & 1) ? NAOP - 14 : 0;
        const uint64_t ord = lp ? ordg : k_order(rb >> 1);
        uint32_t ready = lp ? 0u : 0xFFFFu, nop = c_aop[n];
        const unsigned int* fl = ((lp & 1) ? g_of : g_xf) + rb * 32;
        const CUtensorMap* tm = &maps.m[(lp & 1) ? MAP_O : lp ? MAP_X : MAP_X0];
        const uint32_t skip = layer ? 1u << 25 : 9u << 22;
#pragma unroll 1
        for (; n < n1; ++n) {
          const uint32_t op = nop;
          nop = c_aop[n + 1];
          const uint32_t kb = (uint32_t)(ord >> ((op >> 2) & 60)) & 15;
          uint32_t dst = sb + (op & 15) * SLOT, kc = kb * 64, fb = bar + ((op >> 5) & 0x3F8), need = ~ready & (1u << kb);
          asm volatile("" : "+r"(dst), "+r"(kc), "+r"(fb), "+r"(need));
          const uint32_t eb = bar + ((op >> 12) & 0x3F8), ep = (layer ^ (op >> 22)) & 1;
          bool fr = op & skip;
          if (need) {
            if (!fr) fr = __all_sync(0xffffffffu, mbar_test_wait(eb, ep));
            PROFT(lane == 0 && (n == 0 || n == NAOP - 14), 64 + layer * 16 + (n ? 2 : 0));
            src_wait<0>(fl, xbase + layer + 1, need, ready, lane);
            fence_async_all();
          }
          if (!fr) mbar_wait_u(eb, ep);
          tma_2d_e(dst, tm, kc, m0, fb);
          PROFT(lane == 0 && (n == 0 || n == NAOP - 14), 64 + layer * 16 + (n ? 3 : 1));
          PROFL(lane == 0 && layer == PL && n >= NAOP - 14, 178 + n - (NAOP - 14));
          PROFL(lane == 0 && layer == PL + 1 && n < 4, 242 + n);
        }
      }
    } else {
      BLK_CTX();
      const unsigned int epoch = __shfl_sync(0xffffffffu, ld_relaxed(&g_epoch), 0), xbase = epoch * NLAYERS;
      (void)xbase;
      const uint64_t ordg = k_order(g);
#pragma unroll 1
      for (int layer = 0; layer < NLAYERS; ++layer) {
        const uint64_t ordq = layer ? ordg : k_order(rb >> 1);
        uint32_t ready = layer ? 0xFFFFu : 0u, nop = c_wop[0];
        const CUtensorMap* tq = &maps.m[(layer & 1) ? MAP_WB : MAP_WF];
        const CUtensorMap* tk = &maps.m[(layer & 1) ? MAP_WB : cr ? MAP_WA : MAP_WF];
        const uint32_t skip = layer ? 1u << 25 : 9u << 22, pm = layer ? 0xE0u : 0u;
        int n = 0;
#pragma unroll 1
        for (; n < NWOP - 16; ++n) {
          const uint32_t op = nop;
          nop = c_wop[n + 1];
          const uint32_t isq = (op >> 23) & 1, fb = bar + ((op >> 5) & 0x3F8);
          const uint32_t kb = (uint32_t)(ordq >> ((op >> 2) & 60)) & 15;
          const CUtensorMap* tm = (isq ? tq : tk) + ((op & pm) ? 1 : 0);
          const uint32_t dst = sb + (op & 15) * SLOT + cr * (isq ? 8192 : SLOT);
          const int col = g * 128 + (isq ? cr * 64 : 1024 + cr * 1024);
          if (layer == 0) {
            if ((op & 0x7E00) == 0) continue;
            const uint32_t need = ((isq || !cr) ? 1u << kb : 0u) | (((op >> 22) & 1) ? 0u : (((op >> 15) & 127) == CM ? 1u : 3u) << (rb & ~1));
            if ((ready & need) != need) {
              src_wait<0>(g_wff + g * 32, epoch + 1, need, ready, lane);
              fence_async_all();
            }
            if ((op & 15) >= 11) mbar_wait_u(BA(B_XT), 0);
          }
          wait_tma_5d_mc(!(op & skip), bar + ((op >> 12) & 0x3F8), (layer ^ (op >> 22)) & 1, dst, tm, col, 2 * kb, fb);
          if (!isq) tma_5d_mc_e(dst + 8192, tm, col + 64, 2 * kb, fb);
          if (op >> 26) expect_tx_e(fb, (op >> 26) * 8192);
          PROFL(lane == 0 && layer == PL + 1 && n < 16, 128 + n);
        }
        const CUtensorMap* to = &maps.m[(layer & 1) ? MAP_WOB : MAP_WOA];
#pragma unroll 1
        for (; n < NWOP; ++n) {
          const uint32_t op = nop;
          nop = c_wop[n + 1];
          const uint32_t fb = bar + ((op >> 5) & 0x3F8), kb = (uint32_t)(ordg >> ((op >> 2) & 60)) & 15;
          wait_tma_5d_mc(!((op >> 25) & 1), bar + ((op >> 12) & 0x3F8), layer & 1, sb + (op & 15) * SLOT + cr * 8192, to + ((op & 0xE0) ? 1 : 0), g * 128 + cr * 64, 2 * kb, fb);
          expect_tx_e(fb, (op >> 26) * 8192);
          PROFL(lane == 0 && layer == PL, 144 + ((op >> 8) & 127) - FW);
        }
      }
    }
    } else if (warp == 1) {
      BLK_CTX();
      const unsigned int epoch = __shfl_sync(0xffffffffu, ld_relaxed(&g_epoch), 0), xbase = epoch * NLAYERS;
      (void)xbase;
      if (lane == 0) {
        mbar_wait(BA(B_WFD), 0);
        PROFT(true, 229);
#pragma unroll 1
        for (int j = 0; j < 4; ++j) tma_store_5d(&maps.m[MAP_WF], sb + (j < 2 ? 2 * cr : 9 + cr) * SLOT + (j & 1) * 8192, (j < 2 ? 1024 : 0) + g * 128 + (j & 1) * 64, 2 * rb);
        bulk_commit();
        bulk_wait0();
        PROFT(true, 230);
        fence_async_all();
        flag_set(g_wff + g * 32 + rb, epoch + 1);
        PROFT(true, 64 + 13);
#pragma unroll 1
        for (int e = 0; e < NLAYERS; ++e) {
          BLK_CTX();
          if (e > 0) {
            mbar_wait(BA(B_XH0), (e - 1) & 1);
            PROFT(e == PL + 1, 240);
            flag_set(g_xf + rb * 32 + 2 * g, xbase + e + 1);
            PROFT(e == PL + 1, 241);
          }
          mbar_wait(BA(B_XDONE), e & 1);
          PROFT(true, 64 + e * 16 + 4);
          flag_set(g_xf + rb * 32 + 2 * g + 1, xbase + e + 1);
          if (e == 0) {
            flag_add(&g_csflag[g].v);
            l2_prefetch(wB + (size_t)bid_ * 24576, 49152);
            l2_prefetch(woA + (size_t)bid_ * 8192, 16384);
            l2_prefetch(woB + (size_t)bid_ * 8192, 16384);
          }
          PROFT(true, 64 + e * 16 + 7);
          if ((e & 1) == 0) {
            float* kvl = g_kv + ((size_t)((epoch & 1) * 2 + (e >> 1)) * 8 + g) * 8448;
#pragma unroll 1
            for (int hp = 0; hp < 2; ++hp) {
              mbar_wait(BA(B_KVDONE), hp);
              bulk_red_add(kvl + 8192 + hp * 128, sb + SM_AP + hp * 512, 512);
#pragma unroll 1
              for (int i = 0; i < NCH; ++i) {
                const int ch = hp * NCH + ((i + rb * NCH / 16) & (NCH - 1));
                bulk_red_add(kvl + ch * (4096 / NCH), sb + VB + ch * (16384 / NCH), 16384 / NCH);
                bulk_commit();
                asm volatile("cp.async.bulk.wait_group %0;" :: "n"(CHW) : "memory");
              }
              bulk_wait0();
              PROFT(true, 64 + e * 16 + (hp ? 10 : 6));
              fence_async_all();
              flag_add(&g_kvflag[hp * 8 + g].v);
              PROFT(e > 0 && hp, 64 + e * 16 + 8);
            }
          }
          if (e & 1) {
            mbar_wait(BA(B_OF0), (e >> 1) & 1);
            flag_set(g_hf + rb * 32 + g, xbase + e + 1);
            if (rb) flag_wait(g_hf + (rb - 1) * 32 + g, xbase + e + 1);
            fence_async_all();
            mbar_expect_tx(BA(B_HALO), 8192);
            bulk_load(sb + SM_SD, g_halo + (size_t)(((e >> 1) * 17 + rb) * 8 + g) * 2048, 8192, BA(B_HALO));
            PROFT(true, 64 + e * 16 + 15);
          }
          mbar_wait(BA(B_OH0), e & 1);
          PROFT(e > 0, 64 + e * 16 + 13);
          flag_set(g_of + rb * 32 + 2 * g, xbase + e + 1);
          PROFT(true, 64 + e * 16 + 9);
          mbar_wait(BA(B_OH1), e & 1);
          PROFT(true, 64 + e * 16 + 5);
          flag_set(g_of + rb * 32 + 2 * g + 1, xbase + e + 1);
          if (EFS) REL2(B_EF);
          PROFT(true, 64 + e * 16 + 11);
        }
        if (bid_ == 0) g_epoch = epoch + 1;
      }
    } else {
      BLK_CTX();
      const unsigned int epoch = __shfl_sync(0xffffffffu, ld_relaxed(&g_epoch), 0), xbase = epoch * NLAYERS;
      (void)xbase;
      if (lane < 16) sts_f(sb + SM_RS + lane * 4, 0.f);
#pragma unroll 1
      for (int layer = 0; layer < NLAYERS; ++layer) {
#define HLP_CTX() BLK_CTX(); int lane = threadIdx.x & 31; asm volatile("" : "+r"(lane)); const bool isB = layer & 1, hal = isB && rb > 0; (void)hal;
#pragma unroll 1
        for (int ph = 0; ph < 2; ++ph) {
          HLP_CTX();
          if (ph == (layer == 0)) {
            const float* cs = g_cs + (epoch & 1) * 6144 + g * 384;
            if (layer) mbar_wait_u(BA(CT), (layer - 1) & 1);
            if (layer < 2) {
              if (lane == 0) flag_wait_slow(&g_csflag[isB ? 8 : g].v, isB ? epoch * 4u + 4u : epoch * 16u + 16u);
              __syncwarp();
            }
#pragma unroll 1
            for (int i0 = 0; i0 < 12; i0 += 4) {
              float a[4];
#pragma unroll
              for (int i = 0; i < 4; ++i) a[i] = __ldcg(cs + isB * 3072 + (i0 + i) * 32 + lane);
#pragma unroll
              for (int i = 0; i < 4; ++i) {
                const float c1 = bf16r(a[i]), c2 = bf16r(a[i] - c1), c3 = (a[i] - c1) - c2;
                sts128(sb + SM_BP + ((i0 + i) * 32 + lane) * 16, make_uint4(pack_bf16(c1, c2), pack_bf16(c3, 0.f), 0u, 0u));
              }
            }
          } else {
            uint32_t rdy = 0u;
            src_wait<128>(g_xf + rb * 32, xbase + layer + 1, 0xAAAAu, rdy, lane);
            rdy = 0u;
            if (hal) src_wait<128>(g_xf + (rb - 1) * 32, xbase + layer + 1, 0xAAAAu, rdy, lane);
            const float2* sp = g_stats + ((epoch & 1) * 4 + layer) * S_ + m0 + lane;
            float2 u[5];
#pragma unroll
            for (int i = 0; i < 4; ++i) u[i] = __ldcg(sp + i * 32);
            u[4] = __ldcg(sp - (hal ? 16 : 0));
#pragma unroll 1
            for (int i = 0; i < 5; ++i) {
              const float mean = u[0].x * (1.f / D_);
              const float var = fmaxf(fmaf(-u[0].x, mean, u[0].y) * (1.f / D_), 0.f);
              const float sd = bf16r(sqrtf(bf16r(bf16r(var) + 1e-5f)));
              const int R = i * 32 + lane;
              if (i < 4) {
                const float hm = -0.5f * bf16r(mean);
                if (!isB) sts128(sb + SM_SD + R * 64 + ((R >> 1) & 3) * 16, make_uint4(__float_as_uint(sd) >> 16, 0u, 0u, 0u));
                sts128(sb + SM_AP + R * 16, make_uint4(pack_bf16(hm, hm), pack_bf16(hm, 0.f), 0u, 0u));
              }
              if (i < 4 || (hal && lane < 16)) sts_f(sb + SM_RS + (i < 4 ? 16 + R : lane) * 4, __fdividef(1.f, sd));
#pragma unroll
              for (int j = 0; j < 4; ++j) u[j] = u[j + 1];
            }
            PROFT(lane == 0, 64 + layer * 16 + 12);
          }
        }
        HLP_CTX();
        fence_async_smem();
        __syncwarp();
        if (lane == 0) mbar_arrive(BA(B_STAT));
        PROFT(lane == 0, 64 + layer * 16 + 14);
        if (!isB && lane == 0) {
#pragma unroll 1
          for (int hp = 0; hp < 2; ++hp) {
            mbar_wait(BA(B_KVDONE), hp);
            flag_wait(&g_kvflag[hp * 8 + g].v, epoch * (16u * ((NLAYERS + 1) / 2)) + 16u * ((layer >> 1) + 1));
            const float* kvl = g_kv + ((size_t)((epoch & 1) * 2 + (layer >> 1)) * 8 + g) * 8448;
            const uint32_t kb = BA(hp ? B_KVF1 : B_KVF);
            fence_async_all();
            mbar_expect_tx(kb, 16384 + 512);
            bulk_load(sb + VB + hp * SLOT, kvl + hp * 4096, 16384, kb);
            bulk_load(sb + SM_AP + hp * 512, kvl + 8192 + hp * 128, 512, kb);
            PROFT(hp == 0, 64 + layer * 16 + 15);
          }
        }
        __syncwarp();
      }
    }
    __syncwarp();
    asm volatile("barrier.cluster.arrive.relaxed.aligned;" ::: "memory");
    cluster_wait();
  } else {
    asm volatile("setmaxnreg.inc.sync.aligned.u32 232;");
    PROFT(threadIdx.x == 128, 235);
    cluster_wait();
    PROFT(threadIdx.x == 128, 236);
    consumer(c);
    asm volatile("bar.warp.sync 0xffffffff;\nbarrier.cluster.arrive.relaxed.aligned;\nbarrier.cluster.wait.aligned;\n" ::: "memory");
  }
}

typedef CUresult (*PFN_encodeTiled)(CUtensorMap*, CUtensorMapDataType, cuuint32_t, void*, const cuuint64_t*, const cuuint64_t*,
                                    const cuuint32_t*, const cuuint32_t*, CUtensorMapInterleave, CUtensorMapSwizzle,
                                    CUtensorMapL2promotion, CUtensorMapFloatOOBfill);

static void make_map2(PFN_encodeTiled enc, CUtensorMap* m, const void* ptr, uint64_t cols, uint64_t rows, uint32_t box_c, uint32_t box_r) {
  cuuint64_t dims[2] = {cols, rows};
  cuuint64_t strides[1] = {cols * 2};
  cuuint32_t box[2] = {box_c, box_r};
  cuuint32_t es[2] = {1, 1};
  CUresult r = enc(m, CU_TENSOR_MAP_DATA_TYPE_BFLOAT16, 2, const_cast<void*>(ptr), dims, strides, box, es, CU_TENSOR_MAP_INTERLEAVE_NONE,
                   box_c == 64 ? CU_TENSOR_MAP_SWIZZLE_128B : CU_TENSOR_MAP_SWIZZLE_64B, CU_TENSOR_MAP_L2_PROMOTION_L2_256B, CU_TENSOR_MAP_FLOAT_OOB_FILL_NONE);
  (void)r;
}
static void make_map5(PFN_encodeTiled enc, CUtensorMap* m, const void* ptr, uint64_t cols) {
  for (int p = 0; p < 2; ++p) {
    cuuint64_t dims[5] = {cols, 2, 4, 4, 32};
    cuuint64_t strides[4] = {cols * 2, cols * (p ? 16 : 4), cols * (p ? 4 : 16), cols * 64};
    cuuint32_t box[5] = {64, 2, 4, 4, 2};
    cuuint32_t es[5] = {1, 1, 1, 1, 1};
    CUresult r = enc(m + p, CU_TENSOR_MAP_DATA_TYPE_BFLOAT16, 5, const_cast<void*>(ptr), dims, strides, box, es, CU_TENSOR_MAP_INTERLEAVE_NONE,
                     CU_TENSOR_MAP_SWIZZLE_128B, CU_TENSOR_MAP_L2_PROMOTION_L2_256B, CU_TENSOR_MAP_FLOAT_OOB_FILL_NONE);
    (void)r;
  }
}

extern "C" void kernel_launch(void* const* d_in, const int* in_sizes, int n_in, void* d_out, int out_size) {
  const bf16* A_x = (const bf16*)d_in[0];
  const bf16* A_wqkv = (const bf16*)d_in[1];
  const bf16* A_wphi = (const bf16*)d_in[2];
  const bf16* A_wo = (const bf16*)d_in[3];
  const bf16* B_wqkv = (const bf16*)d_in[5];
  const bf16* B_wo = (const bf16*)d_in[6];
  bf16* out = (bf16*)d_out;

  static PFN_encodeTiled enc = nullptr;
  static bf16 *p_x, *p_o, *p_wf;
  static uint32_t boff;
  if (!enc) {
    void* fn = nullptr; cudaDriverEntryPointQueryResult qr;
    cudaGetDriverEntryPoint("cuTensorMapEncodeTiled", &fn, cudaEnableDefault, &qr);
    enc = (PFN_encodeTiled)fn;
    cudaGetSymbolAddress((void**)&p_x, g_x);
    cudaGetSymbolAddress((void**)&p_o, g_o);
    cudaGetSymbolAddress((void**)&p_wf, g_wf);
    cudaFuncSetAttribute(mega_kernel, cudaFuncAttributeMaxDynamicSharedMemorySize, SM_TOTAL);
    cudaLaunchConfig_t cfg = {};
    cudaLaunchAttribute at; at.id = cudaLaunchAttributeClusterDimension; at.val.clusterDim.x = 2; at.val.clusterDim.y = 1; at.val.clusterDim.z = 1;
    cfg.gridDim = dim3(132); cfg.blockDim = dim3(384); cfg.dynamicSmemBytes = SM_TOTAL; cfg.attrs = &at; cfg.numAttrs = 1;
    int nc = 0;
    if (cudaOccupancyMaxActiveClusters(&nc, mega_kernel, &cfg) != cudaSuccess) { nc = 0; (void)cudaGetLastError(); }
    boff = nc >= 66 ? 0u : 4u;
  }
  Maps maps;
  make_map5(enc, &maps.m[MAP_WF], p_wf, 2048);
  make_map5(enc, &maps.m[MAP_WA], A_wqkv, 3072);
  make_map5(enc, &maps.m[MAP_WB], B_wqkv, 3072);
  make_map5(enc, &maps.m[MAP_WOA], A_wo, 1024);
  make_map5(enc, &maps.m[MAP_WOB], B_wo, 1024);
  make_map2(enc, &maps.m[MAP_X0], A_x, 1024, 2048, 64, 128);
  make_map2(enc, &maps.m[MAP_X], p_x, 1024, 2048, 64, 128);
  make_map2(enc, &maps.m[MAP_O], p_o, 1024, 2048, 64, 128);
  make_map2(enc, &maps.m[MAP_PHI], A_wphi, 32, 1024, 32, 128);
  Ctx c; c.zero = 0u; c.boff = boff; c.x0 = A_x; c.out = out;
  mega_kernel<<<132, 384, SM_TOTAL, cudaStreamPerThread>>>(maps, c, A_wqkv, B_wqkv, A_wo, B_wo);
}
```

```cpp
#include <cuda_runtime.h>
#include <cuda_bf16.h>
#include <cuda.h>
#include <stdint.h>

typedef __nv_bfloat16 bf16;

constexpr int S_ = 2048, D_ = 1024;

struct __align__(128) Flag { unsigned int v; unsigned int pad[31]; };
__device__ __align__(1024) bf16 g_x[S_ * D_];
__device__ __align__(1024) bf16 g_o[S_ * D_];
__device__ __align__(1024) uint32_t g_halo[2 * 17 * 8 * 2048];
__device__ __align__(1024) float g_kv[2 * 2 * 8 * 8448];
__device__ __align__(1024) float2 g_stats[2 * 4 * S_];
__device__ __align__(1024) float g_cs[2 * 2 * 3072];
__device__ __align__(1024) bf16 g_wf[D_ * 2048];
__device__ Flag g_kvflag[16], g_csflag[13];
__device__ __align__(128) unsigned int g_xf[16 * 32], g_of[16 * 32];
__device__ __align__(128) unsigned int g_hf[16 * 32];
__device__ __align__(128) unsigned int g_wff[8 * 32];
__device__ unsigned int g_epoch, g_err;
#define PROFT(cond, idx) asm volatile("" ::: "memory")

__device__ __forceinline__ uint32_t smem_u32(const void* p) { return (uint32_t)__cvta_generic_to_shared(p); }
__device__ __forceinline__ void mbar_init(uint32_t bar, uint32_t count) {
  asm volatile("mbarrier.init.shared::cta.b64 [%0], %1;" ::"r"(bar), "r"(count) : "memory");
}
__device__ __forceinline__ void mbar_expect_tx(uint32_t bar, uint32_t bytes) {
  asm volatile("mbarrier.arrive.expect_tx.shared::cta.b64 _, [%0], %1;" ::"r"(bar), "r"(bytes) : "memory");
}
__device__ __forceinline__ void mbar_arrive(uint32_t bar) {
  asm volatile("mbarrier.arrive.shared::cta.b64 _, [%0];" ::"r"(bar) : "memory");
}
__device__ __forceinline__ bool mbar_try_wait(uint32_t bar, uint32_t parity) {
  uint32_t ok;
  asm volatile("{\n.reg .pred p;\nmbarrier.try_wait.parity.shared::cta.b64 p, [%1], %2;\nselp.b32 %0, 1, 0, p;\n}\n"
               : "=r"(ok) : "r"(bar), "r"(parity) : "memory");
  return ok != 0;
}
__device__ __forceinline__ bool mbar_test_wait(uint32_t bar, uint32_t parity) {
  uint32_t ok;
  asm volatile("{\n.reg .pred p;\nmbarrier.test_wait.parity.shared::cta.b64 p, [%1], %2;\nselp.b32 %0, 1, 0, p;\n}\n"
               : "=r"(ok) : "r"(bar), "r"(parity) : "memory");
  return ok != 0;
}
__device__ __forceinline__ uint64_t gtimer() {
  uint64_t t; asm volatile("mov.u64 %0, %globaltimer;" : "=l"(t)); return t;
}
__device__ __forceinline__ void mbar_wait(uint32_t bar, uint32_t parity) {
  uint32_t n = 0;
  bool ok;
#pragma unroll 1
  do { ++n; ok = mbar_try_wait(bar, parity); } while (!ok && n < (1u << 22));
}
__device__ __forceinline__ unsigned int ld_acquire(const unsigned int* p) {
  unsigned int v; asm volatile("ld.acquire.gpu.global.u32 %0, [%1];" : "=r"(v) : "l"(p) : "memory"); return v;
}
__device__ __forceinline__ void flag_add(unsigned int* p) {
  asm volatile("red.release.gpu.global.add.u32 [%0], 1;" ::"l"(p) : "memory");
}
__device__ __forceinline__ void flag_set(unsigned int* p, unsigned int v) {
  asm volatile("st.release.gpu.global.u32 [%0], %1;" ::"l"(p), "r"(v) : "memory");
}
template <int SLEEP>
__device__ __forceinline__ void src_wait(const unsigned int* f, unsigned int target, uint32_t need, uint32_t& ready, int lane) {
  uint32_t n = 0;
#pragma unroll 1
  while ((ready & need) != need) {
    const unsigned int v = ld_acquire(f + (lane & 15));
    ready = __ballot_sync(0xffffffffu, (int)(v - target) >= 0);
    if (SLEEP) { if ((ready & need) != need) __nanosleep(SLEEP); }
    if (++n > (1u << 20)) break;
  }
  __syncwarp();
}
__device__ __forceinline__ unsigned int ld_relaxed(const unsigned int* p);
__device__ __forceinline__ unsigned int ld_relaxed(const unsigned int* p) {
  unsigned int v; asm volatile("ld.relaxed.gpu.global.u32 %0, [%1];" : "=r"(v) : "l"(p) : "memory"); return v;
}
template <int SLEEP>
__device__ __forceinline__ void flag_wait_t(const unsigned int* p, unsigned int target) {
  uint32_t n = 0;
#pragma unroll 1
  while ((int)(ld_acquire(p) - target) < 0) {
    if (SLEEP) __nanosleep(SLEEP);
    if (++n > (1u << 20)) break;
  }
}
__device__ __forceinline__ void flag_wait(const unsigned int* p, unsigned int target) { flag_wait_t<0>(p, target); }
__device__ __forceinline__ void flag_wait_slow(const unsigned int* p, unsigned int target) { flag_wait_t<256>(p, target); }
__device__ __forceinline__ void mbar_wait_u(uint32_t bar, uint32_t parity) {
  uint32_t n = 0;
#pragma unroll 1
  while (!__all_sync(0xffffffffu, mbar_try_wait(bar, parity))) {
    if (++n > (1u << 22)) break;
  }
}
__device__ __forceinline__ void expect_tx_e(uint32_t bar, uint32_t bytes) {
  asm volatile("{\n.reg .pred p;\nelect.sync _|p, 0xffffffff;\n@p mbarrier.arrive.expect_tx.shared::cta.b64 _, [%0], %1;\n}\n" ::"r"(bar), "r"(bytes) : "memory");
}
__device__ __forceinline__ void tma_2d_e(uint32_t dst, const CUtensorMap* tm, int c0, int c1, uint32_t bar) {
  asm volatile("{\n.reg .pred p;\nelect.sync _|p, 0xffffffff;\n"
               "@p cp.async.bulk.tensor.2d.shared::cluster.global.mbarrier::complete_tx::bytes [%0], [%1, {%2, %3}], [%4];\n}\n"
               ::"r"(dst), "l"(tm), "r"(c0), "r"(c1), "r"(bar) : "memory");
}
__device__ __forceinline__ void tma_5d_e(uint32_t dst, const CUtensorMap* tm, int c0, int c4, uint32_t bar) {
  asm volatile("{\n.reg .pred p;\nelect.sync _|p, 0xffffffff;\n"
               "@p cp.async.bulk.tensor.5d.shared::cluster.global.mbarrier::complete_tx::bytes [%0], [%1, {%2, %5, %5, %5, %3}], [%4];\n}\n"
               ::"r"(dst), "l"(tm), "r"(c0), "r"(c4), "r"(bar), "r"(0) : "memory");
}
__device__ __forceinline__ void tma_5d_mc_e(uint32_t dst, const CUtensorMap* tm, int c0, int c4, uint32_t bar) {
  asm volatile("{\n.reg .pred p;\nelect.sync _|p, 0xffffffff;\n"
               "@p cp.async.bulk.tensor.5d.shared::cluster.global.mbarrier::complete_tx::bytes.multicast::cluster [%0], [%1, {%2, %6, %6, %6, %3}], [%4], %5;\n}\n"
               ::"r"(dst), "l"(tm), "r"(c0), "r"(c4), "r"(bar), "h"((uint16_t)3), "r"(0) : "memory");
}
__device__ __forceinline__ void wait_tma_5d_mc(bool w, uint32_t eb, uint32_t par, uint32_t dst, const CUtensorMap* tm, int c0, int c4, uint32_t fb) {
  asm volatile("" : "+r"(dst), "+l"(tm), "+r"(c0), "+r"(c4), "+r"(fb));
  if (w) mbar_wait_u(eb, par);
  tma_5d_mc_e(dst, tm, c0, c4, fb);
}
__device__ __forceinline__ void stg128(void* p, uint32_t a, uint32_t b, uint32_t c, uint32_t d) {
  asm volatile("st.global.v4.u32 [%0], {%1,%2,%3,%4};" ::"l"(p), "r"(a), "r"(b), "r"(c), "r"(d) : "memory");
}
__device__ __forceinline__ void stg128_p(bool on, void* p, uint32_t a, uint32_t b, uint32_t c, uint32_t d) {
  asm volatile("{\n.reg .pred p;\nsetp.ne.b32 p, %5, 0;\n@p st.global.v4.u32 [%0], {%1,%2,%3,%4};\n}\n" ::"l"(p), "r"(a), "r"(b), "r"(c), "r"(d), "r"((int)on) : "memory");
}
__device__ __forceinline__ void ldg128(const void* p, uint32_t& a, uint32_t& b, uint32_t& c, uint32_t& d) {
  asm volatile("ld.global.cg.v4.u32 {%0,%1,%2,%3}, [%4];" : "=r"(a), "=r"(b), "=r"(c), "=r"(d) : "l"(p) : "memory");
}
__device__ __forceinline__ void release2c(uint32_t off) {
  asm volatile("mbarrier.arrive.shared::cluster.b64 _, [%0];\nmbarrier.arrive.shared::cluster.b64 _, [%1];" ::"r"(off), "r"(off + (1u << 24)) : "memory");
}
__device__ __forceinline__ void tma_store_5d(const CUtensorMap* tm, uint32_t src, int c0, int c4) {
  asm volatile("cp.async.bulk.tensor.5d.global.shared::cta.bulk_group [%0, {%2, %4, %4, %4, %3}], [%1];"
               ::"l"(tm), "r"(src), "r"(c0), "r"(c4), "r"(0) : "memory");
}
__device__ __forceinline__ void bulk_load(uint32_t dst, const void* src, uint32_t bytes, uint32_t bar) {
  asm volatile("cp.async.bulk.shared::cluster.global.mbarrier::complete_tx::bytes [%0], [%1], %2, [%3];" ::"r"(dst), "l"(src), "r"(bytes), "r"(bar) : "memory");
}
__device__ __forceinline__ void bulk_red_add(void* dst, uint32_t src, uint32_t bytes) {
  asm volatile("cp.reduce.async.bulk.global.shared::cta.bulk_group.add.f32 [%0], [%1], %2;" ::"l"(dst), "r"(src), "r"(bytes) : "memory");
}
__device__ __forceinline__ void bulk_commit() { asm volatile("cp.async.bulk.commit_group;" ::: "memory"); }
__device__ __forceinline__ void bulk_wait0() { asm volatile("cp.async.bulk.wait_group 0;" ::: "memory"); }
__device__ __forceinline__ void fence_async_smem() { asm volatile("fence.proxy.async.shared::cta;" ::: "memory"); }
__device__ __forceinline__ void fence_async_all() { asm volatile("fence.proxy.async.global;" ::: "memory"); }
__device__ __forceinline__ void wgmma_fence() { asm volatile("wgmma.fence.sync.aligned;" ::: "memory"); }
__device__ __forceinline__ void wgmma_commit() { asm volatile("wgmma.commit_group.sync.aligned;" ::: "memory"); }
template <int N> __device__ __forceinline__ void wgmma_wait() { asm volatile("wgmma.wait_group.sync.aligned %0;" ::"n"(N) : "memory"); }
__device__ __forceinline__ void cluster_wait() { asm volatile("barrier.cluster.wait.acquire.aligned;" ::: "memory"); }
template <int ID, int N> __device__ __forceinline__ void nbar() { asm volatile("bar.sync %0, %1;" ::"n"(ID), "n"(N) : "memory"); }
__device__ __forceinline__ uint64_t desc64(uint32_t lo, uint32_t hi) { return (uint64_t)lo | ((uint64_t)hi << 32); }
__device__ __forceinline__ uint32_t pack_bf16(float lo, float hi) {
  uint32_t r; asm("cvt.rn.bf16x2.f32 %0, %1, %2;" : "=r"(r) : "f"(hi), "f"(lo)); return r;
}
__device__ __forceinline__ uint32_t add_bf16x2(uint32_t a, uint32_t b) {
  uint32_t r; asm("add.rn.bf16x2 %0, %1, %2;" : "=r"(r) : "r"(a), "r"(b)); return r;
}
__device__ __forceinline__ float bf16r(float x) { return __bfloat162float(__float2bfloat16_rn(x)); }
__device__ __forceinline__ float bf_lo(uint32_t u) { return __uint_as_float(u << 16); }
__device__ __forceinline__ float bf_hi(uint32_t u) { return __uint_as_float(u & 0xFFFF0000u); }
__device__ __forceinline__ float ex2(float x) { float r; asm("ex2.approx.ftz.f32 %0, %1;" : "=f"(r) : "f"(x)); return r; }
__device__ __forceinline__ float ex2v(float x) { float r; asm volatile("ex2.approx.ftz.f32 %0, %1;" : "=f"(r) : "f"(x) : "memory"); return r; }
__device__ __forceinline__ float rcp(float x) { float r; asm("rcp.approx.ftz.f32 %0, %1;" : "=f"(r) : "f"(x)); return r; }
__device__ __forceinline__ void mma_bf16(float (&d)[4], uint32_t a0, uint32_t a1, uint32_t a2, uint32_t a3, uint32_t b0, uint32_t b1) {
  asm("mma.sync.aligned.m16n8k16.row.col.f32.bf16.bf16.f32 {%0,%1,%2,%3}, {%4,%5,%6,%7}, {%8,%9}, {%0,%1,%2,%3};"
               : "+f"(d[0]), "+f"(d[1]), "+f"(d[2]), "+f"(d[3]) : "r"(a0), "r"(a1), "r"(a2), "r"(a3), "r"(b0), "r"(b1));
}
__device__ __forceinline__ void ldsm_x4(uint32_t& r0, uint32_t& r1, uint32_t& r2, uint32_t& r3, uint32_t addr) {
  asm volatile("ldmatrix.sync.aligned.m8n8.x4.shared.b16 {%0,%1,%2,%3}, [%4];"
               : "=r"(r0), "=r"(r1), "=r"(r2), "=r"(r3) : "r"(addr) : "memory");
}
__device__ __forceinline__ void ldsm_x4_t(uint32_t& r0, uint32_t& r1, uint32_t& r2, uint32_t& r3, uint32_t addr) {
  asm volatile("ldmatrix.sync.aligned.m8n8.x4.trans.shared.b16 {%0,%1,%2,%3}, [%4];"
               : "=r"(r0), "=r"(r1), "=r"(r2), "=r"(r3) : "r"(addr) : "memory");
}
__device__ __forceinline__ void stsm_x4(uint32_t addr, uint32_t r0, uint32_t r1, uint32_t r2, uint32_t r3) {
  asm volatile("stmatrix.sync.aligned.m8n8.x4.shared.b16 [%0], {%1,%2,%3,%4};"
               ::"r"(addr), "r"(r0), "r"(r1), "r"(r2), "r"(r3) : "memory");
}
__device__ __forceinline__ uint4 lds128(uint32_t addr) {
  uint4 v; asm volatile("ld.shared.v4.b32 {%0,%1,%2,%3}, [%4];" : "=r"(v.x), "=r"(v.y), "=r"(v.z), "=r"(v.w) : "r"(addr) : "memory"); return v;
}
__device__ __forceinline__ void sts128(uint32_t addr, uint4 v) {
  asm volatile("st.shared.v4.b32 [%0], {%1,%2,%3,%4};" ::"r"(addr), "r"(v.x), "r"(v.y), "r"(v.z), "r"(v.w) : "memory");
}
__device__ __forceinline__ float lds_f(uint32_t addr) {
  float v; asm volatile("ld.shared.f32 %0, [%1];" : "=f"(v) : "r"(addr) : "memory"); return v;
}
__device__ __forceinline__ void nbar_dyn(int id, int n) { asm volatile("bar.sync %0, %1;" ::"r"(id), "r"(n) : "memory"); }
__device__ __forceinline__ uint64_t make_desc_ns(uint32_t addr, uint32_t lbo_bytes, uint32_t sbo_bytes) {
  return (uint64_t)((addr & 0x3FFFF) >> 4) | ((uint64_t)(lbo_bytes >> 4) << 16) | ((uint64_t)(sbo_bytes >> 4) << 32);
}
__device__ __forceinline__ void sts_f(uint32_t addr, float v) { asm volatile("st.shared.f32 [%0], %1;" ::"r"(addr), "f"(v) : "memory"); }
__device__ __forceinline__ void sts64(uint32_t addr, uint32_t a, uint32_t b) {
  asm volatile("st.shared.v2.b32 [%0], {%1,%2};" ::"r"(addr), "r"(a), "r"(b) : "memory");
}
__device__ __forceinline__ void sts_f2(uint32_t addr, float a, float b) {
  asm volatile("st.shared.v2.f32 [%0], {%1,%2};" ::"r"(addr), "f"(a), "f"(b) : "memory");
}
__device__ __forceinline__ void red_add2_p(bool on, float* p, float a, float b) {
  asm volatile("{\n.reg .pred p;\nsetp.ne.b32 p, %3, 0;\n@p red.global.add.v2.f32 [%0], {%1,%2};\n}\n" ::"l"(p), "f"(a), "f"(b), "r"((int)on) : "memory");
}
__device__ __forceinline__ void red_add4(float* p, float a, float b, float c, float d) {
  asm volatile("red.global.add.v4.f32 [%0], {%1,%2,%3,%4};" ::"l"(p), "f"(a), "f"(b), "f"(c), "f"(d) : "memory");
}
__device__ __forceinline__ void red_add1(float* p, float a) {
  asm volatile("red.global.add.f32 [%0], %1;" ::"l"(p), "f"(a) : "memory");
}
__device__ __forceinline__ void l2_prefetch(const void* p, uint32_t bytes) {
  asm volatile("cp.async.bulk.prefetch.L2.global [%0], %1;" ::"l"(p), "r"(bytes) : "memory");
}

__device__ __forceinline__ void wgmma_n256(float (&d)[192], uint64_t da, uint64_t db, int scale_d) {
  asm volatile("{\n.reg .pred p;\nsetp.ne.b32 p, %130, 0;\n"
    "wgmma.mma_async.sync.aligned.m64n256k16.f32.bf16.bf16 {%0, %1, %2, %3, %4, %5, %6, %7, %8, %9, %10, %11, %12, %13, %14, %15, %16, %17, %18, %19, %20, %21, %22, %23, %24, %25, %26, %27, %28, %29, %30, %31, %32, %33, %34, %35, %36, %37, %38, %39, %40, %41, %42, %43, %44, %45, %46, %47, %48, %49, %50, %51, %52, %53, %54, %55, %56, %57, %58, %59, %60, %61, %62, %63, %64, %65, %66, %67, %68, %69, %70, %71, %72, %73, %74, %75, %76, %77, %78, %79, %80, %81, %82, %83, %84, %85, %86, %87, %88, %89, %90, %91, %92, %93, %94, %95, %96, %97, %98, %99, %100, %101, %102, %103, %104, %105, %106, %107, %108, %109, %110, %111, %112, %113, %114, %115, %116, %117, %118, %119, %120, %121, %122, %123, %124, %125, %126, %127}, %128, %129, p, 1, 1, 0, 1;\n}\n"
    : "+f"(d[0]), "+f"(d[1]), "+f"(d[2]), "+f"(d[3]), "+f"(d[4]), "+f"(d[5]), "+f"(d[6]), "+f"(d[7]), "+f"(d[8]), "+f"(d[9]), "+f"(d[10]), "+f"(d[11]), "+f"(d[12]), "+f"(d[13]), "+f"(d[14]), "+f"(d[15]), "+f"(d[16]), "+f"(d[17]), "+f"(d[18]), "+f"(d[19]), "+f"(d[20]), "+f"(d[21]), "+f"(d[22]), "+f"(d[23]), "+f"(d[24]), "+f"(d[25]), "+f"(d[26]), "+f"(d[27]), "+f"(d[28]), "+f"(d[29]), "+f"(d[30]), "+f"(d[31]), "+f"(d[32]), "+f"(d[33]), "+f"(d[34]), "+f"(d[35]), "+f"(d[36]), "+f"(d[37]), "+f"(d[38]), "+f"(d[39]), "+f"(d[40]), "+f"(d[41]), "+f"(d[42]), "+f"(d[43]), "+f"(d[44]), "+f"(d[45]), "+f"(d[46]), "+f"(d[47]), "+f"(d[48]), "+f"(d[49]), "+f"(d[50]), "+f"(d[51]), "+f"(d[52]), "+f"(d[53]), "+f"(d[54]), "+f"(d[55]), "+f"(d[56]), "+f"(d[57]), "+f"(d[58]), "+f"(d[59]), "+f"(d[60]), "+f"(d[61]), "+f"(d[62]), "+f"(d[63]), "+f"(d[64]), "+f"(d[65]), "+f"(d[66]), "+f"(d[67]), "+f"(d[68]), "+f"(d[69]), "+f"(d[70]), "+f"(d[71]), "+f"(d[72]), "+f"(d[73]), "+f"(d[74]), "+f"(d[75]), "+f"(d[76]), "+f"(d[77]), "+f"(d[78]), "+f"(d[79]), "+f"(d[80]), "+f"(d[81]), "+f"(d[82]), "+f"(d[83]), "+f"(d[84]), "+f"(d[85]), "+f"(d[86]), "+f"(d[87]), "+f"(d[88]), "+f"(d[89]), "+f"(d[90]), "+f"(d[91]), "+f"(d[92]), "+f"(d[93]), "+f"(d[94]), "+f"(d[95]), "+f"(d[96]), "+f"(d[97]), "+f"(d[98]), "+f"(d[99]), "+f"(d[100]), "+f"(d[101]), "+f"(d[102]), "+f"(d[103]), "+f"(d[104]), "+f"(d[105]), "+f"(d[106]), "+f"(d[107]), "+f"(d[108]), "+f"(d[109]), "+f"(d[110]), "+f"(d[111]), "+f"(d[112]), "+f"(d[113]), "+f"(d[114]), "+f"(d[115]), "+f"(d[116]), "+f"(d[117]), "+f"(d[118]), "+f"(d[119]), "+f"(d[120]), "+f"(d[121]), "+f"(d[122]), "+f"(d[123]), "+f"(d[124]), "+f"(d[125]), "+f"(d[126]), "+f"(d[127])
    : "l"(da), "l"(db), "r"(scale_d));
}
__device__ __forceinline__ void wgmma_n128(float (&d)[192], uint64_t da, uint64_t db, int scale_d) {
  asm volatile("{\n.reg .pred p;\nsetp.ne.b32 p, %66, 0;\n"
    "wgmma.mma_async.sync.aligned.m64n128k16.f32.bf16.bf16 {%0, %1, %2, %3, %4, %5, %6, %7, %8, %9, %10, %11, %12, %13, %14, %15, %16, %17, %18, %19, %20, %21, %22, %23, %24, %25, %26, %27, %28, %29, %30, %31, %32, %33, %34, %35, %36, %37, %38, %39, %40, %41, %42, %43, %44, %45, %46, %47, %48, %49, %50, %51, %52, %53, %54, %55, %56, %57, %58, %59, %60, %61, %62, %63}, %64, %65, p, 1, 1, 0, 1;\n}\n"
    : "+f"(d[128]), "+f"(d[129]), "+f"(d[130]), "+f"(d[131]), "+f"(d[132]), "+f"(d[133]), "+f"(d[134]), "+f"(d[135]), "+f"(d[136]), "+f"(d[137]), "+f"(d[138]), "+f"(d[139]), "+f"(d[140]), "+f"(d[141]), "+f"(d[142]), "+f"(d[143]), "+f"(d[144]), "+f"(d[145]), "+f"(d[146]), "+f"(d[147]), "+f"(d[148]), "+f"(d[149]), "+f"(d[150]), "+f"(d[151]), "+f"(d[152]), "+f"(d[153]), "+f"(d[154]), "+f"(d[155]), "+f"(d[156]), "+f"(d[157]), "+f"(d[158]), "+f"(d[159]), "+f"(d[160]), "+f"(d[161]), "+f"(d[162]), "+f"(d[163]), "+f"(d[164]), "+f"(d[165]), "+f"(d[166]), "+f"(d[167]), "+f"(d[168]), "+f"(d[169]), "+f"(d[170]), "+f"(d[171]), "+f"(d[172]), "+f"(d[173]), "+f"(d[174]), "+f"(d[175]), "+f"(d[176]), "+f"(d[177]), "+f"(d[178]), "+f"(d[179]), "+f"(d[180]), "+f"(d[181]), "+f"(d[182]), "+f"(d[183]), "+f"(d[184]), "+f"(d[185]), "+f"(d[186]), "+f"(d[187]), "+f"(d[188]), "+f"(d[189]), "+f"(d[190]), "+f"(d[191])
    : "l"(da), "l"(db), "r"(scale_d));
}
__device__ __forceinline__ void wgmma_n256_k(float (&d)[192], uint64_t da, uint64_t db, int scale_d) {
  asm volatile("{\n.reg .pred p;\nsetp.ne.b32 p, %130, 0;\n"
    "wgmma.mma_async.sync.aligned.m64n256k16.f32.bf16.bf16 {%0, %1, %2, %3, %4, %5, %6, %7, %8, %9, %10, %11, %12, %13, %14, %15, %16, %17, %18, %19, %20, %21, %22, %23, %24, %25, %26, %27, %28, %29, %30, %31, %32, %33, %34, %35, %36, %37, %38, %39, %40, %41, %42, %43, %44, %45, %46, %47, %48, %49, %50, %51, %52, %53, %54, %55, %56, %57, %58, %59, %60, %61, %62, %63, %64, %65, %66, %67, %68, %69, %70, %71, %72, %73, %74, %75, %76, %77, %78, %79, %80, %81, %82, %83, %84, %85, %86, %87, %88, %89, %90, %91, %92, %93, %94, %95, %96, %97, %98, %99, %100, %101, %102, %103, %104, %105, %106, %107, %108, %109, %110, %111, %112, %113, %114, %115, %116, %117, %118, %119, %120, %121, %122, %123, %124, %125, %126, %127}, %128, %129, p, 1, 1, 0, 0;\n}\n"
    : "+f"(d[0]), "+f"(d[1]), "+f"(d[2]), "+f"(d[3]), "+f"(d[4]), "+f"(d[5]), "+f"(d[6]), "+f"(d[7]), "+f"(d[8]), "+f"(d[9]), "+f"(d[10]), "+f"(d[11]), "+f"(d[12]), "+f"(d[13]), "+f"(d[14]), "+f"(d[15]), "+f"(d[16]), "+f"(d[17]), "+f"(d[18]), "+f"(d[19]), "+f"(d[20]), "+f"(d[21]), "+f"(d[22]), "+f"(d[23]), "+f"(d[24]), "+f"(d[25]), "+f"(d[26]), "+f"(d[27]), "+f"(d[28]), "+f"(d[29]), "+f"(d[30]), "+f"(d[31]), "+f"(d[32]), "+f"(d[33]), "+f"(d[34]), "+f"(d[35]), "+f"(d[36]), "+f"(d[37]), "+f"(d[38]), "+f"(d[39]), "+f"(d[40]), "+f"(d[41]), "+f"(d[42]), "+f"(d[43]), "+f"(d[44]), "+f"(d[45]), "+f"(d[46]), "+f"(d[47]), "+f"(d[48]), "+f"(d[49]), "+f"(d[50]), "+f"(d[51]), "+f"(d[52]), "+f"(d[53]), "+f"(d[54]), "+f"(d[55]), "+f"(d[56]), "+f"(d[57]), "+f"(d[58]), "+f"(d[59]), "+f"(d[60]), "+f"(d[61]), "+f"(d[62]), "+f"(d[63]), "+f"(d[64]), "+f"(d[65]), "+f"(d[66]), "+f"(d[67]), "+f"(d[68]), "+f"(d[69]), "+f"(d[70]), "+f"(d[71]), "+f"(d[72]), "+f"(d[73]), "+f"(d[74]), "+f"(d[75]), "+f"(d[76]), "+f"(d[77]), "+f"(d[78]), "+f"(d[79]), "+f"(d[80]), "+f"(d[81]), "+f"(d[82]), "+f"(d[83]), "+f"(d[84]), "+f"(d[85]), "+f"(d[86]), "+f"(d[87]), "+f"(d[88]), "+f"(d[89]), "+f"(d[90]), "+f"(d[91]), "+f"(d[92]), "+f"(d[93]), "+f"(d[94]), "+f"(d[95]), "+f"(d[96]), "+f"(d[97]), "+f"(d[98]), "+f"(d[99]), "+f"(d[100]), "+f"(d[101]), "+f"(d[102]), "+f"(d[103]), "+f"(d[104]), "+f"(d[105]), "+f"(d[106]), "+f"(d[107]), "+f"(d[108]), "+f"(d[109]), "+f"(d[110]), "+f"(d[111]), "+f"(d[112]), "+f"(d[113]), "+f"(d[114]), "+f"(d[115]), "+f"(d[116]), "+f"(d[117]), "+f"(d[118]), "+f"(d[119]), "+f"(d[120]), "+f"(d[121]), "+f"(d[122]), "+f"(d[123]), "+f"(d[124]), "+f"(d[125]), "+f"(d[126]), "+f"(d[127])
    : "l"(da), "l"(db), "r"(scale_d));
}
__device__ __forceinline__ void wgmma_n128_k(float (&d)[192], uint64_t da, uint64_t db, int scale_d) {
  asm volatile("{\n.reg .pred p;\nsetp.ne.b32 p, %66, 0;\n"
    "wgmma.mma_async.sync.aligned.m64n128k16.f32.bf16.bf16 {%0, %1, %2, %3, %4, %5, %6, %7, %8, %9, %10, %11, %12, %13, %14, %15, %16, %17, %18, %19, %20, %21, %22, %23, %24, %25, %26, %27, %28, %29, %30, %31, %32, %33, %34, %35, %36, %37, %38, %39, %40, %41, %42, %43, %44, %45, %46, %47, %48, %49, %50, %51, %52, %53, %54, %55, %56, %57, %58, %59, %60, %61, %62, %63}, %64, %65, p, 1, 1, 0, 0;\n}\n"
    : "+f"(d[128]), "+f"(d[129]), "+f"(d[130]), "+f"(d[131]), "+f"(d[132]), "+f"(d[133]), "+f"(d[134]), "+f"(d[135]), "+f"(d[136]), "+f"(d[137]), "+f"(d[138]), "+f"(d[139]), "+f"(d[140]), "+f"(d[141]), "+f"(d[142]), "+f"(d[143]), "+f"(d[144]), "+f"(d[145]), "+f"(d[146]), "+f"(d[147]), "+f"(d[148]), "+f"(d[149]), "+f"(d[150]), "+f"(d[151]), "+f"(d[152]), "+f"(d[153]), "+f"(d[154]), "+f"(d[155]), "+f"(d[156]), "+f"(d[157]), "+f"(d[158]), "+f"(d[159]), "+f"(d[160]), "+f"(d[161]), "+f"(d[162]), "+f"(d[163]), "+f"(d[164]), "+f"(d[165]), "+f"(d[166]), "+f"(d[167]), "+f"(d[168]), "+f"(d[169]), "+f"(d[170]), "+f"(d[171]), "+f"(d[172]), "+f"(d[173]), "+f"(d[174]), "+f"(d[175]), "+f"(d[176]), "+f"(d[177]), "+f"(d[178]), "+f"(d[179]), "+f"(d[180]), "+f"(d[181]), "+f"(d[182]), "+f"(d[183]), "+f"(d[184]), "+f"(d[185]), "+f"(d[186]), "+f"(d[187]), "+f"(d[188]), "+f"(d[189]), "+f"(d[190]), "+f"(d[191])
    : "l"(da), "l"(db), "r"(scale_d));
}
__device__ __forceinline__ void wgmma_n40_tt(float (&d)[20], uint64_t da, uint64_t db, int scale_d) {
  asm volatile("{\n.reg .pred p;\nsetp.ne.b32 p, %22, 0;\n"
    "wgmma.mma_async.sync.aligned.m64n40k16.f32.bf16.bf16 {%0, %1, %2, %3, %4, %5, %6, %7, %8, %9, %10, %11, %12, %13, %14, %15, %16, %17, %18, %19}, %20, %21, p, 1, 1, 1, 1;\n}\n"
    : "+f"(d[0]), "+f"(d[1]), "+f"(d[2]), "+f"(d[3]), "+f"(d[4]), "+f"(d[5]), "+f"(d[6]), "+f"(d[7]), "+f"(d[8]), "+f"(d[9]), "+f"(d[10]), "+f"(d[11]), "+f"(d[12]), "+f"(d[13]), "+f"(d[14]), "+f"(d[15]), "+f"(d[16]), "+f"(d[17]), "+f"(d[18]), "+f"(d[19])
    : "l"(da), "l"(db), "r"(scale_d));
}
__device__ __forceinline__ void wgmma_n40_rs(float (&d)[20], const uint32_t (&a)[4], uint64_t db, int scale_d) {
  asm volatile("{\n.reg .pred p;\nsetp.ne.b32 p, %25, 0;\n"
    "wgmma.mma_async.sync.aligned.m64n40k16.f32.bf16.bf16 {%0, %1, %2, %3, %4, %5, %6, %7, %8, %9, %10, %11, %12, %13, %14, %15, %16, %17, %18, %19}, {%20, %21, %22, %23}, %24, p, 1, 1, 1;\n}\n"
    : "+f"(d[0]), "+f"(d[1]), "+f"(d[2]), "+f"(d[3]), "+f"(d[4]), "+f"(d[5]), "+f"(d[6]), "+f"(d[7]), "+f"(d[8]), "+f"(d[9]), "+f"(d[10]), "+f"(d[11]), "+f"(d[12]), "+f"(d[13]), "+f"(d[14]), "+f"(d[15]), "+f"(d[16]), "+f"(d[17]), "+f"(d[18]), "+f"(d[19])
    : "r"(a[0]), "r"(a[1]), "r"(a[2]), "r"(a[3]), "l"(db), "r"(scale_d));
}
__device__ __forceinline__ void wgmma_n128_0(float (&d)[192], uint64_t da, uint64_t db) {
  asm volatile("{\n.reg .pred p;\nsetp.ne.b32 p, 0, 0;\n"
    "wgmma.mma_async.sync.aligned.m64n128k16.f32.bf16.bf16 {%0, %1, %2, %3, %4, %5, %6, %7, %8, %9, %10, %11, %12, %13, %14, %15, %16, %17, %18, %19, %20, %21, %22, %23, %24, %25, %26, %27, %28, %29, %30, %31, %32, %33, %34, %35, %36, %37, %38, %39, %40, %41, %42, %43, %44, %45, %46, %47, %48, %49, %50, %51, %52, %53, %54, %55, %56, %57, %58, %59, %60, %61, %62, %63}, %64, %65, p, 1, 1, 0, 1;\n}\n"
    : "=f"(d[128]), "=f"(d[129]), "=f"(d[130]), "=f"(d[131]), "=f"(d[132]), "=f"(d[133]), "=f"(d[134]), "=f"(d[135]), "=f"(d[136]), "=f"(d[137]), "=f"(d[138]), "=f"(d[139]), "=f"(d[140]), "=f"(d[141]), "=f"(d[142]), "=f"(d[143]), "=f"(d[144]), "=f"(d[145]), "=f"(d[146]), "=f"(d[147]), "=f"(d[148]), "=f"(d[149]), "=f"(d[150]), "=f"(d[151]), "=f"(d[152]), "=f"(d[153]), "=f"(d[154]), "=f"(d[155]), "=f"(d[156]), "=f"(d[157]), "=f"(d[158]), "=f"(d[159]), "=f"(d[160]), "=f"(d[161]), "=f"(d[162]), "=f"(d[163]), "=f"(d[164]), "=f"(d[165]), "=f"(d[166]), "=f"(d[167]), "=f"(d[168]), "=f"(d[169]), "=f"(d[170]), "=f"(d[171]), "=f"(d[172]), "=f"(d[173]), "=f"(d[174]), "=f"(d[175]), "=f"(d[176]), "=f"(d[177]), "=f"(d[178]), "=f"(d[179]), "=f"(d[180]), "=f"(d[181]), "=f"(d[182]), "=f"(d[183]), "=f"(d[184]), "=f"(d[185]), "=f"(d[186]), "=f"(d[187]), "=f"(d[188]), "=f"(d[189]), "=f"(d[190]), "=f"(d[191])
    : "l"(da), "l"(db));
}
__device__ __forceinline__ void wgmma_n128_rs(float (&d)[192], const uint32_t (&a)[4], uint64_t db, int scale_d) {
  asm volatile("{\n.reg .pred p;\nsetp.ne.b32 p, %69, 0;\n"
    "wgmma.mma_async.sync.aligned.m64n128k16.f32.bf16.bf16 {%0, %1, %2, %3, %4, %5, %6, %7, %8, %9, %10, %11, %12, %13, %14, %15, %16, %17, %18, %19, %20, %21, %22, %23, %24, %25, %26, %27, %28, %29, %30, %31, %32, %33, %34, %35, %36, %37, %38, %39, %40, %41, %42, %43, %44, %45, %46, %47, %48, %49, %50, %51, %52, %53, %54, %55, %56, %57, %58, %59, %60, %61, %62, %63}, {%64, %65, %66, %67}, %68, p, 1, 1, 1;\n}\n"
    : "+f"(d[128]), "+f"(d[129]), "+f"(d[130]), "+f"(d[131]), "+f"(d[132]), "+f"(d[133]), "+f"(d[134]), "+f"(d[135]), "+f"(d[136]), "+f"(d[137]), "+f"(d[138]), "+f"(d[139]), "+f"(d[140]), "+f"(d[141]), "+f"(d[142]), "+f"(d[143]), "+f"(d[144]), "+f"(d[145]), "+f"(d[146]), "+f"(d[147]), "+f"(d[148]), "+f"(d[149]), "+f"(d[150]), "+f"(d[151]), "+f"(d[152]), "+f"(d[153]), "+f"(d[154]), "+f"(d[155]), "+f"(d[156]), "+f"(d[157]), "+f"(d[158]), "+f"(d[159]), "+f"(d[160]), "+f"(d[161]), "+f"(d[162]), "+f"(d[163]), "+f"(d[164]), "+f"(d[165]), "+f"(d[166]), "+f"(d[167]), "+f"(d[168]), "+f"(d[169]), "+f"(d[170]), "+f"(d[171]), "+f"(d[172]), "+f"(d[173]), "+f"(d[174]), "+f"(d[175]), "+f"(d[176]), "+f"(d[177]), "+f"(d[178]), "+f"(d[179]), "+f"(d[180]), "+f"(d[181]), "+f"(d[182]), "+f"(d[183]), "+f"(d[184]), "+f"(d[185]), "+f"(d[186]), "+f"(d[187]), "+f"(d[188]), "+f"(d[189]), "+f"(d[190]), "+f"(d[191])
    : "r"(a[0]), "r"(a[1]), "r"(a[2]), "r"(a[3]), "l"(db), "r"(scale_d));
}
__device__ __forceinline__ void wgmma_n32_0(float (&d)[16], uint64_t da, uint64_t db) {
  asm volatile("{\n.reg .pred p;\nsetp.ne.b32 p, 0, 0;\n"
    "wgmma.mma_async.sync.aligned.m64n32k16.f32.bf16.bf16 {%0, %1, %2, %3, %4, %5, %6, %7, %8, %9, %10, %11, %12, %13, %14, %15}, %16, %17, p, 1, 1, 0, 1;\n}\n"
    : "=f"(d[0]), "=f"(d[1]), "=f"(d[2]), "=f"(d[3]), "=f"(d[4]), "=f"(d[5]), "=f"(d[6]), "=f"(d[7]), "=f"(d[8]), "=f"(d[9]), "=f"(d[10]), "=f"(d[11]), "=f"(d[12]), "=f"(d[13]), "=f"(d[14]), "=f"(d[15])
    : "l"(da), "l"(db));
}
__device__ __forceinline__ void wgmma_n32(float (&d)[16], uint64_t da, uint64_t db, int scale_d) {
  asm volatile("{\n.reg .pred p;\nsetp.ne.b32 p, %18, 0;\n"
    "wgmma.mma_async.sync.aligned.m64n32k16.f32.bf16.bf16 {%0, %1, %2, %3, %4, %5, %6, %7, %8, %9, %10, %11, %12, %13, %14, %15}, %16, %17, p, 1, 1, 0, 1;\n}\n"
    : "+f"(d[0]), "+f"(d[1]), "+f"(d[2]), "+f"(d[3]), "+f"(d[4]), "+f"(d[5]), "+f"(d[6]), "+f"(d[7]), "+f"(d[8]), "+f"(d[9]), "+f"(d[10]), "+f"(d[11]), "+f"(d[12]), "+f"(d[13]), "+f"(d[14]), "+f"(d[15])
    : "l"(da), "l"(db), "r"(scale_d));
}
__device__ __forceinline__ void wgmma_n8_t(float (&d)[4], uint64_t da, uint64_t db, int scale_d) {
  asm volatile("{\n.reg .pred p;\nsetp.ne.b32 p, %6, 0;\n"
    "wgmma.mma_async.sync.aligned.m64n8k16.f32.bf16.bf16 {%0, %1, %2, %3}, %4, %5, p, 1, 1, 1, 0;\n}\n"
    : "+f"(d[0]), "+f"(d[1]), "+f"(d[2]), "+f"(d[3])
    : "l"(da), "l"(db), "r"(scale_d));
}
__device__ __forceinline__ void wgmma_n128_rs0(float (&d)[192], const uint32_t (&a)[4], uint64_t db) {
  asm volatile("{\n.reg .pred p;\nsetp.ne.b32 p, 0, 0;\n"
    "wgmma.mma_async.sync.aligned.m64n128k16.f32.bf16.bf16 {%0, %1, %2, %3, %4, %5, %6, %7, %8, %9, %10, %11, %12, %13, %14, %15, %16, %17, %18, %19, %20, %21, %22, %23, %24, %25, %26, %27, %28, %29, %30, %31, %32, %33, %34, %35, %36, %37, %38, %39, %40, %41, %42, %43, %44, %45, %46, %47, %48, %49, %50, %51, %52, %53, %54, %55, %56, %57, %58, %59, %60, %61, %62, %63}, {%64, %65, %66, %67}, %68, p, 1, 1, 1;\n}\n"
    : "=f"(d[128]), "=f"(d[129]), "=f"(d[130]), "=f"(d[131]), "=f"(d[132]), "=f"(d[133]), "=f"(d[134]), "=f"(d[135]), "=f"(d[136]), "=f"(d[137]), "=f"(d[138]), "=f"(d[139]), "=f"(d[140]), "=f"(d[141]), "=f"(d[142]), "=f"(d[143]), "=f"(d[144]), "=f"(d[145]), "=f"(d[146]), "=f"(d[147]), "=f"(d[148]), "=f"(d[149]), "=f"(d[150]), "=f"(d[151]), "=f"(d[152]), "=f"(d[153]), "=f"(d[154]), "=f"(d[155]), "=f"(d[156]), "=f"(d[157]), "=f"(d[158]), "=f"(d[159]), "=f"(d[160]), "=f"(d[161]), "=f"(d[162]), "=f"(d[163]), "=f"(d[164]), "=f"(d[165]), "=f"(d[166]), "=f"(d[167]), "=f"(d[168]), "=f"(d[169]), "=f"(d[170]), "=f"(d[171]), "=f"(d[172]), "=f"(d[173]), "=f"(d[174]), "=f"(d[175]), "=f"(d[176]), "=f"(d[177]), "=f"(d[178]), "=f"(d[179]), "=f"(d[180]), "=f"(d[181]), "=f"(d[182]), "=f"(d[183]), "=f"(d[184]), "=f"(d[185]), "=f"(d[186]), "=f"(d[187]), "=f"(d[188]), "=f"(d[189]), "=f"(d[190]), "=f"(d[191])
    : "r"(a[0]), "r"(a[1]), "r"(a[2]), "r"(a[3]), "l"(db));
}
__device__ __forceinline__ void wgmma_n256_rs(float (&d)[192], const uint32_t (&a)[4], uint64_t db, int scale_d) {
  asm volatile("{\n.reg .pred p;\nsetp.ne.b32 p, %133, 0;\n"
    "wgmma.mma_async.sync.aligned.m64n256k16.f32.bf16.bf16 {%0, %1, %2, %3, %4, %5, %6, %7, %8, %9, %10, %11, %12, %13, %14, %15, %16, %17, %18, %19, %20, %21, %22, %23, %24, %25, %26, %27, %28, %29, %30, %31, %32, %33, %34, %35, %36, %37, %38, %39, %40, %41, %42, %43, %44, %45, %46, %47, %48, %49, %50, %51, %52, %53, %54, %55, %56, %57, %58, %59, %60, %61, %62, %63, %64, %65, %66, %67, %68, %69, %70, %71, %72, %73, %74, %75, %76, %77, %78, %79, %80, %81, %82, %83, %84, %85, %86, %87, %88, %89, %90, %91, %92, %93, %94, %95, %96, %97, %98, %99, %100, %101, %102, %103, %104, %105, %106, %107, %108, %109, %110, %111, %112, %113, %114, %115, %116, %117, %118, %119, %120, %121, %122, %123, %124, %125, %126, %127}, {%128, %129, %130, %131}, %132, p, 1, 1, 1;\n}\n"
    : "+f"(d[0]), "+f"(d[1]), "+f"(d[2]), "+f"(d[3]), "+f"(d[4]), "+f"(d[5]), "+f"(d[6]), "+f"(d[7]), "+f"(d[8]), "+f"(d[9]), "+f"(d[10]), "+f"(d[11]), "+f"(d[12]), "+f"(d[13]), "+f"(d[14]), "+f"(d[15]), "+f"(d[16]), "+f"(d[17]), "+f"(d[18]), "+f"(d[19]), "+f"(d[20]), "+f"(d[21]), "+f"(d[22]), "+f"(d[23]), "+f"(d[24]), "+f"(d[25]), "+f"(d[26]), "+f"(d[27]), "+f"(d[28]), "+f"(d[29]), "+f"(d[30]), "+f"(d[31]), "+f"(d[32]), "+f"(d[33]), "+f"(d[34]), "+f"(d[35]), "+f"(d[36]), "+f"(d[37]), "+f"(d[38]), "+f"(d[39]), "+f"(d[40]), "+f"(d[41]), "+f"(d[42]), "+f"(d[43]), "+f"(d[44]), "+f"(d[45]), "+f"(d[46]), "+f"(d[47]), "+f"(d[48]), "+f"(d[49]), "+f"(d[50]), "+f"(d[51]), "+f"(d[52]), "+f"(d[53]), "+f"(d[54]), "+f"(d[55]), "+f"(d[56]), "+f"(d[57]), "+f"(d[58]), "+f"(d[59]), "+f"(d[60]), "+f"(d[61]), "+f"(d[62]), "+f"(d[63]), "+f"(d[64]), "+f"(d[65]), "+f"(d[66]), "+f"(d[67]), "+f"(d[68]), "+f"(d[69]), "+f"(d[70]), "+f"(d[71]), "+f"(d[72]), "+f"(d[73]), "+f"(d[74]), "+f"(d[75]), "+f"(d[76]), "+f"(d[77]), "+f"(d[78]), "+f"(d[79]), "+f"(d[80]), "+f"(d[81]), "+f"(d[82]), "+f"(d[83]), "+f"(d[84]), "+f"(d[85]), "+f"(d[86]), "+f"(d[87]), "+f"(d[88]), "+f"(d[89]), "+f"(d[90]), "+f"(d[91]), "+f"(d[92]), "+f"(d[93]), "+f"(d[94]), "+f"(d[95]), "+f"(d[96]), "+f"(d[97]), "+f"(d[98]), "+f"(d[99]), "+f"(d[100]), "+f"(d[101]), "+f"(d[102]), "+f"(d[103]), "+f"(d[104]), "+f"(d[105]), "+f"(d[106]), "+f"(d[107]), "+f"(d[108]), "+f"(d[109]), "+f"(d[110]), "+f"(d[111]), "+f"(d[112]), "+f"(d[113]), "+f"(d[114]), "+f"(d[115]), "+f"(d[116]), "+f"(d[117]), "+f"(d[118]), "+f"(d[119]), "+f"(d[120]), "+f"(d[121]), "+f"(d[122]), "+f"(d[123]), "+f"(d[124]), "+f"(d[125]), "+f"(d[126]), "+f"(d[127])
    : "r"(a[0]), "r"(a[1]), "r"(a[2]), "r"(a[3]), "l"(db), "r"(scale_d));
}
__device__ __forceinline__ void wgmma_n256_rs0(float (&d)[192], const uint32_t (&a)[4], uint64_t db) {
  asm volatile("{\n.reg .pred p;\nsetp.ne.b32 p, 0, 0;\n"
    "wgmma.mma_async.sync.aligned.m64n256k16.f32.bf16.bf16 {%0, %1, %2, %3, %4, %5, %6, %7, %8, %9, %10, %11, %12, %13, %14, %15, %16, %17, %18, %19, %20, %21, %22, %23, %24, %25, %26, %27, %28, %29, %30, %31, %32, %33, %34, %35, %36, %37, %38, %39, %40, %41, %42, %43, %44, %45, %46, %47, %48, %49, %50, %51, %52, %53, %54, %55, %56, %57, %58, %59, %60, %61, %62, %63, %64, %65, %66, %67, %68, %69, %70, %71, %72, %73, %74, %75, %76, %77, %78, %79, %80, %81, %82, %83, %84, %85, %86, %87, %88, %89, %90, %91, %92, %93, %94, %95, %96, %97, %98, %99, %100, %101, %102, %103, %104, %105, %106, %107, %108, %109, %110, %111, %112, %113, %114, %115, %116, %117, %118, %119, %120, %121, %122, %123, %124, %125, %126, %127}, {%128, %129, %130, %131}, %132, p, 1, 1, 1;\n}\n"
    : "=f"(d[0]), "=f"(d[1]), "=f"(d[2]), "=f"(d[3]), "=f"(d[4]), "=f"(d[5]), "=f"(d[6]), "=f"(d[7]), "=f"(d[8]), "=f"(d[9]), "=f"(d[10]), "=f"(d[11]), "=f"(d[12]), "=f"(d[13]), "=f"(d[14]), "=f"(d[15]), "=f"(d[16]), "=f"(d[17]), "=f"(d[18]), "=f"(d[19]), "=f"(d[20]), "=f"(d[21]), "=f"(d[22]), "=f"(d[23]), "=f"(d[24]), "=f"(d[25]), "=f"(d[26]), "=f"(d[27]), "=f"(d[28]), "=f"(d[29]), "=f"(d[30]), "=f"(d[31]), "=f"(d[32]), "=f"(d[33]), "=f"(d[34]), "=f"(d[35]), "=f"(d[36]), "=f"(d[37]), "=f"(d[38]), "=f"(d[39]), "=f"(d[40]), "=f"(d[41]), "=f"(d[42]), "=f"(d[43]), "=f"(d[44]), "=f"(d[45]), "=f"(d[46]), "=f"(d[47]), "=f"(d[48]), "=f"(d[49]), "=f"(d[50]), "=f"(d[51]), "=f"(d[52]), "=f"(d[53]), "=f"(d[54]), "=f"(d[55]), "=f"(d[56]), "=f"(d[57]), "=f"(d[58]), "=f"(d[59]), "=f"(d[60]), "=f"(d[61]), "=f"(d[62]), "=f"(d[63]), "=f"(d[64]), "=f"(d[65]), "=f"(d[66]), "=f"(d[67]), "=f"(d[68]), "=f"(d[69]), "=f"(d[70]), "=f"(d[71]), "=f"(d[72]), "=f"(d[73]), "=f"(d[74]), "=f"(d[75]), "=f"(d[76]), "=f"(d[77]), "=f"(d[78]), "=f"(d[79]), "=f"(d[80]), "=f"(d[81]), "=f"(d[82]), "=f"(d[83]), "=f"(d[84]), "=f"(d[85]), "=f"(d[86]), "=f"(d[87]), "=f"(d[88]), "=f"(d[89]), "=f"(d[90]), "=f"(d[91]), "=f"(d[92]), "=f"(d[93]), "=f"(d[94]), "=f"(d[95]), "=f"(d[96]), "=f"(d[97]), "=f"(d[98]), "=f"(d[99]), "=f"(d[100]), "=f"(d[101]), "=f"(d[102]), "=f"(d[103]), "=f"(d[104]), "=f"(d[105]), "=f"(d[106]), "=f"(d[107]), "=f"(d[108]), "=f"(d[109]), "=f"(d[110]), "=f"(d[111]), "=f"(d[112]), "=f"(d[113]), "=f"(d[114]), "=f"(d[115]), "=f"(d[116]), "=f"(d[117]), "=f"(d[118]), "=f"(d[119]), "=f"(d[120]), "=f"(d[121]), "=f"(d[122]), "=f"(d[123]), "=f"(d[124]), "=f"(d[125]), "=f"(d[126]), "=f"(d[127])
    : "r"(a[0]), "r"(a[1]), "r"(a[2]), "r"(a[3]), "l"(db));
}

constexpr int SLOT = 16384;
constexpr int VB = 4 * SLOT, PH = 0, XS = 6;
constexpr int SM_SD = 13 * SLOT;
constexpr int SM_BAR = SM_SD + 8192;
constexpr int SM_RS = SM_BAR + 1024;
constexpr int SM_AP = SM_RS + 640;
constexpr int SM_BP = SM_AP + 2048;
constexpr int SM_EPOCH = SM_BP + 6144;
constexpr int SM_TOTAL = SM_EPOCH + 16;
constexpr int FM = 0, FT = 16, FW = 30, CM = 46, CT = 62, CW = 76, B_EF = 92, B_STAT = 93, B_KVF = 94, B_HALO = 95,
              B_KVDONE = 96, B_OH0 = 97, B_OH1 = 98, B_XH0 = 99, B_XDONE = 100, B_WFD = 101, B_XT = 102, B_OF0 = 103, B_KVF1 = 104, B_KVS = 105, B_RAW = 106  , B_X0 = 108;
constexpr uint64_t BAR_LG = 0x00043333330004ull;
#define BA(i) (bar + (i) * 8)
#define REL2(i) release2c(SB0 + SM_BAR + (i) * 8)
constexpr int NF = 3, ND = 13, NR = 0, NWOP = 48, NAOP = 38;
constexpr bool EF_USED = false;
constexpr uint64_t TL_A = 0x6278627862786ull, TL_B = 0xa9c3ba9c3ba9cull, WO_A = 0x76b24038b51403ffull, WO_B = 0x8c5a197c6a297c8bull;
__constant__ uint32_t c_wop[NWOP + 1] = {0xeb0009, 0x186b8000, 0x6c0112, 0x1aec011a, 0x6c8224, 0x22ec822b, 0x18170330, 0x18178442, 0x18180554, 0x18188660, 0x18190772, 0x18198884, 0x181a0990, 0x181a8aa2, 0x181b0bb4, 0x181b8cc0, 0xaed10fc, 0xa9711e9, 0x181c0dd2, 0xa9792da, 0x129813cb, 0x181c8ee4, 0x181d0ff0, 0x109d94b3, 0x109f15ac, 0x109f9699, 0x10a0178a, 0x10a0987b, 0x10a11963, 0x10a19a5c, 0x10a21b49, 0x10a29c3a, 0x9231e0b, 0x9239f18, 0x1124202c, 0x13242137, 0x1124a249, 0x1324a352, 0x1125246a, 0x13252576, 0x1127268c, 0x1127a797, 0x112828a9, 0x1128a9b1, 0x11292aca, 0x13292bd5, 0x112a2cec, 0x132a2df8, 0};
__constant__ uint32_t c_aop[NAOP + 1] = {0x6d8228, 0x170336, 0x178447, 0x180558, 0x188666, 0x190777, 0x198888, 0x1a0996, 0x1a8aa7, 0x1b0bb8, 0x1b8cc6, 0x1c0dd7, 0x1c8ee8, 0x1d0ff6, 0x1d93c2, 0x1f14b6, 0x1f95a8, 0x201697, 0x209782, 0x211876, 0x219968, 0x221a57, 0x229b42, 0x231c36, 0xa3a023, 0xb12130, 0x2b12244, 0x2b12351, 0x2b12465, 0xa6257b, 0xa6a688, 0xa72793, 0xa7a8a0, 0xa829b4, 0xa8aac2, 0xa9abdb, 0x2a9ace6, 0xaaadf7, 0};
__constant__ uint32_t c_map[64] = {4, 5, 6, 7, 0, 16, 32, 48, 64, 80, 96, 112, 1, 17, 33, 49, 65, 81, 97, 113, 2, 18, 34, 50, 66, 82, 98, 114, 3, 19, 35, 51, 67, 83, 99, 115, 20, 36, 52, 68, 84, 100, 116, 21, 37, 53, 69, 85, 101, 117, 22, 38, 54, 70, 86, 102, 118, 23, 39, 55, 71, 87, 103, 119};
enum { MAP_WF = 0, MAP_WA = 2, MAP_WB = 4, MAP_WOA = 6, MAP_WOB = 8, MAP_X0 = 10, MAP_X = 11, MAP_O = 12, MAP_PHI = 13, NMAP = 14 };
struct Maps { CUtensorMap m[NMAP]; };

#define PL 2
#define PROFL(a, b)
#define SUBS 8
#define QORD 1
#define NCH 4
#define CHW 1
#define SUBS1 12
#define XRAT 10
#define XRN 4
#define BT1 1
#define CV0 0
#define ST1 8
#define X0AT 1
#define W1DL 400
#define SKA 0
#define SKB 0
#define BPRE 0
#define XST 3
#define WH 4
#define NLAYERS 4
constexpr float L2E = 1.4426950408889634f;

#define D128(lo) desc64(lo, 0x40000040u)
struct Ctx { uint32_t zero, boff; const bf16* x0; bf16* out; };
#define BLK_CTX() \
  uint32_t bid_; asm volatile("mov.u32 %0, %%ctaid.x;" : "=r"(bid_)); \
  bid_ -= c.boff; \
  const uint32_t gr_ = c_map[bid_ >> 1]; \
  const int cr = bid_ & 1, g = gr_ & 7, rb = (gr_ >> 3) + cr, m0 = rb * 128; \
  const uint32_t sb = SB0 + (cr << 24); \
  const uint32_t bar = sb + SM_BAR; \
  (void)cr; (void)g; (void)rb; (void)m0; (void)bar;
extern __shared__ uint8_t smem_raw[];
constexpr uint32_t SB0 = 1024;

#define PHASE_CTX() \
  BLK_CTX(); \
  int tid_ = threadIdx.x; asm volatile("" : "+r"(tid_)); \
  const int lane = tid_ & 31, cw = (tid_ >> 5) - 4, wg = cw >> 2, wq = cw & 3, gq = lane >> 2, t = lane & 3, wrow0 = cw * 16; \
  const int lrow = (lane & 7) + ((lane >> 3) & 1) * 8, lchk = lane >> 4; \
  const bool elected = (tid_ & 127) == 0; \
  const uint32_t rowo = (wrow0 + lrow) * 128, X = (lchk ^ (lane & 7)) << 4; \
  const uint32_t Y = (wrow0 + (lane & 7)) * 128 + (((lane >> 3) ^ (lane & 7)) << 4); \
  const size_t gfr = (size_t)(m0 + wrow0 + gq) * D_ + g * 128 + 8 * t; \
  (void)bar; (void)wq; (void)gq; (void)lrow; (void)lchk; (void)elected; (void)wrow0; (void)wg; (void)rowo; (void)X; (void)t; (void)Y; (void)gfr;
#define MMA_CTX() \
  const uint32_t wu = __shfl_sync(0xffffffffu, wg, 0); \
  const uint32_t dA0 = ((SB0 >> 4) | (1u << 16)) + wu * 512, dB0 = (SB0 >> 4) | (512u << 16); \
  const uint32_t par = layer & 1;

__device__ __forceinline__ void slab_out_half(uint32_t slot, bf16* dst, int wrow0, int lane) {
  const int r0 = lane >> 3, ch = lane & 7;
  const uint32_t src = slot + (wrow0 + r0) * 128;
  uint4 v[4];
#pragma unroll
  for (int i = 0; i < 4; ++i) v[i] = lds128(src + i * 512 + (((ch ^ (4 * i + r0)) & 7) << 4));
  dst += (size_t)(wrow0 + r0) * D_ + ch * 8;
#pragma unroll
  for (int i = 0; i < 4; ++i) *reinterpret_cast<uint4*>(dst + (size_t)i * 4 * D_) = v[i];
}

__device__ __forceinline__ void consumer(const Ctx& c) {
  float acc[192];
  uint32_t xf[4][4];
  uint32_t xp[8][4];
  {
    PHASE_CTX();
    const unsigned int epoch = ld_relaxed(&g_epoch);
    PROFT(tid_ == 128, 0);
    const uint32_t wu = __shfl_sync(0xffffffffu, wg, 0);
    if (tid_ < 128 + 8) sts128(sb + SM_AP + lane * 16, make_uint4(0x3F803F80u, 0x3F803F80u, 0x3F803F80u, 0x3F803F80u));
#pragma unroll 1
    for (int it = 0; it < 2; ++it) {
      float p[4][16];
      mbar_wait(BA(B_RAW + it), 0);
      PROFT(tid_ == 128, it ? 15 : 2);
      const uint32_t da = ((SB0 >> 4) | (1u << 16)) + (wu ? 9 + it : 2 * it) * 1024, db = (SB0 + SM_SD) >> 4;
      wgmma_fence();
#pragma unroll
      for (int h = 0; h < 4; ++h) wgmma_n32_0(p[h], D128(da + (h >> 1) * 512 + (h & 1) * 4), desc64(db + h * 128, 0x80000020u));
#pragma unroll
      for (int h = 0; h < 4; ++h) wgmma_n32(p[h], D128(da + (h >> 1) * 512 + (h & 1) * 4 + 2), desc64(db + h * 128 + 64, 0x80000020u), 1);
      wgmma_commit();
      wgmma_wait<0>();
#pragma unroll
      for (int i = 0; i < 64; ++i) asm volatile("" : "+f"(p[i >> 4][i & 15]) :: "memory");
      const uint32_t base = sb + (wg ? 9 + it : 2 * it) * SLOT + (wq * 16 + gq) * 128;
      uint32_t w[4][4][2];
#pragma unroll
      for (int i = 0; i < 32; ++i) w[i >> 3][(i >> 1) & 3][i & 1] = pack_bf16(p[i >> 3][2 * (i & 7)], p[i >> 3][2 * (i & 7) + 1]);
      if (wu) {
#pragma unroll
        for (int i = 0; i < 8; ++i)
          sts128(base + (i >> 2) * 8192 + (i & 1) * 1024 + (((((i >> 1) & 1) * 4 + t) ^ gq) << 4), make_uint4(w[i >> 1][0][i & 1], w[i >> 1][1][i & 1], w[i >> 1][2][i & 1], w[i >> 1][3][i & 1]));
      } else {
#pragma unroll
        for (int i = 0; i < 16; ++i)
          sts64(base + (i >> 3) * 8192 + (i & 1) * 1024 + ((((t & 1) * 4 + ((i >> 1) & 3)) ^ gq) << 4) + (t >> 1) * 8, w[(i >> 3) * 2][(i >> 1) & 3][i & 1], w[(i >> 3) * 2 + 1][(i >> 1) & 3][i & 1]);
      }
      fence_async_smem();
      __syncwarp();
      if (it == cr && lane == 0) mbar_arrive(BA(B_WFD));
    }
    if (tid_ == 128) sts_f(sb + SM_EPOCH, __uint_as_float(epoch & 1));
#pragma unroll
    for (int i = 0; i < 32; ++i) xp[i >> 2][i & 3] = 0u;
    nbar<1, 256>();
    PROFT(tid_ == 128, 13);
    mbar_wait(BA(FM + cr), 0);
    float cs[3][4];
    wgmma_fence();
#pragma unroll
    for (int ks = 0; ks < 4; ++ks)
#pragma unroll
      for (int i = 0; i < 3; ++i) {
        const uint32_t bx = (i == 0 ? 2 * cr * 1024 : i == 1 ? (2 * cr + 1) * 1024 : (9 + cr) * 1024) + wu * 512;
        wgmma_n8_t(cs[i], D128(((SB0 >> 4) | (512u << 16)) + bx + ks * 128), desc64((SB0 + SM_AP) >> 4, 0), ks != 0);
      }
    wgmma_commit();
    mbar_wait(BA(FM), 0);
#pragma unroll
    for (int k = 0; k < 4; ++k) ldsm_x4(xf[k][0], xf[k][1], xf[k][2], xf[k][3], sb + XS * SLOT + rowo + (X ^ (k << 5)));
    wgmma_wait<0>();
#pragma unroll
    for (int i = 0; i < 12; ++i) asm volatile("" : "+f"(cs[i >> 2][i & 3]) :: "memory");
    if (t < 2) {
#pragma unroll
      for (int i = 0; i < 3; ++i) red_add1(g_cs + (epoch & 1) * 6144 + g * 384 + i * 128 + wg * 64 + wq * 16 + gq + t * 8, t ? cs[i][2] : cs[i][0]);
    }
    PROFT(tid_ == 128, 14);
  }
#pragma unroll 1
  for (int layer = 0;; ++layer) {
    {
      wgmma_fence();
      wgmma_n256_rs0(acc, xf[0], D128((SB0 >> 4) | (512u << 16)));
#pragma unroll
      for (int k = 1; k < 4; ++k) wgmma_n256_rs(acc, xf[k], D128(((SB0 >> 4) | (512u << 16)) + k * 128), 1);
      wgmma_commit();
      PHASE_CTX();
      MMA_CTX();
      {
        const uint32_t ep = __float_as_uint(lds_f(sb + SM_EPOCH));
        if (layer == 0) {
          mbar_wait(BA(B_X0), 0);
#pragma unroll
          for (int i = 0; i < 8; ++i) ldsm_x4(xp[i][0], xp[i][1], xp[i][2], xp[i][3], sb + (11 + (i >> 2)) * SLOT + (Y ^ ((i & 2) << 5)) + (i & 1) * 1024);
          if (lane == ((xp[0][0] ^ xp[1][0] ^ xp[2][0] ^ xp[3][0] ^ xp[7][0]) & c.zero)) REL2(B_XT);
        } else {
#pragma unroll
          for (int i = 0; i < 8; ++i) stsm_x4(sb + (XS + (i >> 2)) * SLOT + (Y ^ ((i & 2) << 5)) + (i & 1) * 1024, xp[i][0], xp[i][1], xp[i][2], xp[i][3]);
        }
        float s0 = 0.f, s1 = 0.f, q0 = 0.f, q1 = 0.f;
        auto stats = [&](int j0, int j1) {
#pragma unroll
          for (int j = j0; j < j1; ++j) {
            const uint32_t u0 = xp[(j >> 2) * 2][j & 3], u1 = xp[(j >> 2) * 2 + 1][j & 3];
            s0 += bf_lo(u0) + bf_hi(u0); s1 += bf_lo(u1) + bf_hi(u1);
            q0 = fmaf(bf_lo(u0), bf_lo(u0), fmaf(bf_hi(u0), bf_hi(u0), q0)); q1 = fmaf(bf_lo(u1), bf_lo(u1), fmaf(bf_hi(u1), bf_hi(u1), q1));
          }
        };
        stats(0, ST1);
        fence_async_smem();
        nbar_dyn(3 + wu + (__float_as_uint(s0 + s1 + q0 + q1) & c.zero), 128);
        mbar_wait(BA(FM + 1), par);
        wgmma_fence();
#pragma unroll
        for (int k = 0; k < 4; ++k) wgmma_n256(acc, D128(dA0 + (XS + 1) * 1024 + k * 2), D128(dB0 + 2048 + k * 128), 1);
        wgmma_commit();
        wgmma_wait<1>();
#pragma unroll
        for (int i = 4; i < 8; ++i) stg128_p(layer, g_x + gfr + (i & 1) * 8 * D_ + (i >> 1) * 32, xp[i][0], xp[i][1], xp[i][2], xp[i][3]);
        {
          uint32_t zc; asm volatile("mov.u32 %0, %%clock;" : "=r"(zc) :: "memory");
          q0 += __uint_as_float(zc & c.zero); q1 += __uint_as_float(zc & c.zero); s0 += __uint_as_float(zc & c.zero); s1 += __uint_as_float(zc & c.zero);
        }
        stats(ST1, 16);
        wgmma_fence();
        wgmma_n128_0(acc, D128(dA0 + XS * 1024), D128(dB0 + 9 * 1024));
#pragma unroll
        for (int k = 1; k < 4; ++k) wgmma_n128(acc, D128(dA0 + XS * 1024 + k * 2), D128(dB0 + 9 * 1024 + k * 128), 1);
        wgmma_commit();
        const bool od = t & 1;
        float sa = od ? s1 : s0, qa = od ? q1 : q0;
        sa += __shfl_xor_sync(0xffffffffu, od ? s0 : s1, 1);
        qa += __shfl_xor_sync(0xffffffffu, od ? q0 : q1, 1);
        wgmma_fence();
#pragma unroll
        for (int k = 0; k < 4; ++k) wgmma_n128(acc, D128(dA0 + (XS + 1) * 1024 + k * 2), D128(dB0 + 10 * 1024 + k * 128), 1);
        wgmma_commit();
        sa += __shfl_xor_sync(0xffffffffu, sa, 2);
        qa += __shfl_xor_sync(0xffffffffu, qa, 2);
        red_add2_p(t < 2, reinterpret_cast<float*>(g_stats + (ep * 4 + layer) * S_ + m0 + wrow0 + gq + t * 8), sa, qa);
        __syncwarp();
        if (lane == 0) mbar_arrive(BA(B_XDONE));
        wgmma_wait<1>();
        if (elected) REL2(CM);
      }
      uint32_t s = 2;
#pragma unroll 1
      for (int i = 2; i < NF; ++i) {
        PROFL(tid_ == 128 && layer == PL + 1, 244 + 2 * i);
        mbar_wait(BA(FM + i), par);
        PROFL(tid_ == 128 && layer == PL + 1, 245 + 2 * i);
        const uint32_t da = dA0 + (XS + s) * 1024, dk = dB0 + s * 2048, dq = dB0 + (9 + s) * 1024;
        wgmma_fence();
#pragma unroll
        for (int k = 0; k < 4; ++k) wgmma_n128(acc, D128(da + k * 2), D128(dq + k * 128), 1);
        wgmma_commit();
        wgmma_wait<1>();
        if (elected) REL2(CM + i - 1);
        wgmma_fence();
#pragma unroll
        for (int k = 0; k < 4; ++k) wgmma_n256(acc, D128(da + k * 2), D128(dk + k * 128), 1);
        wgmma_commit();
        if (++s == 3) s = 0;
      }
#pragma unroll 1
      for (int i = NF; i < 15; ++i) {
        mbar_wait(BA(FM + i), par);
        const uint32_t da = dA0 + (XS + s) * 1024, dk = dB0 + s * 2048;
        wgmma_fence();
#pragma unroll
        for (int k = 0; k < 4; ++k) wgmma_n256(acc, D128(da + k * 2), D128(dk + k * 128), 1);
        wgmma_commit();
        wgmma_wait<1>();
        if (elected) REL2(CM + i - 1);
        if (++s == 3) s = 0;
      }
      {
        const uint64_t dap = desc64(((SB0 + SM_AP) >> 4) + wu * 64, 8), dbp = make_desc_ns(SB0 + SM_BP, 0, 128);
        mbar_wait(BA(B_STAT), par);
        mbar_wait(BA(FM + 15), par);
        PROFT(tid_ == 128, layer * 16 + 9);
        wgmma_fence();
        wgmma_n256_k(acc, dap, dbp, 1);
#pragma unroll
        for (int k = 0; k < 4; ++k) wgmma_n256(acc, D128(dA0 + XS * 1024 + k * 2), D128(dB0 + k * 128), 1);
        wgmma_commit();
        wgmma_wait<1>();
        if (elected) REL2(CM + 14);
        mbar_wait(BA(FT), par);
        wgmma_fence();
        wgmma_n128_k(acc, dap, dbp + 256, 1);
#pragma unroll
        for (int k = 0; k < 4; ++k) wgmma_n128(acc, D128(dA0 + (uint32_t)(TL_A & 15) * 1024 + k * 2), D128(dB0 + (uint32_t)(TL_B & 15) * 1024 + k * 128), 1);
        wgmma_commit();
        wgmma_wait<1>();
        if (elected) REL2(CM + 15);
#pragma unroll
        for (int i = 0; i < 128; ++i) asm volatile("" : "+f"(acc[i]) :: "memory");
      }
    }
    uint32_t of[8][4], o1[4][4];
    {
      PHASE_CTX();
      MMA_CTX();
      PROFT(tid_ == 128, layer * 16 + 1);
      PROFT(lane == 0 && layer == PL, 192 + cw);
      PROFT(tid_ == 128 && layer == PL, 160);
      uint64_t ta = (TL_A >> 4), tw = TL_B >> 4;
      uint32_t da, db, dz = dA0;
      auto sub = [&](int n) {
        const int j = n >> 2, k = n & 3;
        if (k == 0) {
          dz += c.zero;
          da = dz + ((uint32_t)ta & 15) * 1024; db = dB0 + ((uint32_t)tw & 15) * 1024;
          ta >>= 4; tw >>= 4;
          mbar_wait(BA(FT + j), par);
          wgmma_fence();
        }
        wgmma_n128(acc, D128(da + k * 2), D128(db + k * 128), 1);
        if (k == 3) {
          wgmma_commit();
          wgmma_wait<1>();
          if (elected) REL2(CT + j - 1);
        }
      };
      auto run = [&](int j0, int j1) {
#pragma unroll 1
        for (int j = j0; j < j1; ++j) {
          mbar_wait(BA(FT + j), par);
          da = dA0 + ((uint32_t)ta & 15) * 1024; db = dB0 + ((uint32_t)tw & 15) * 1024;
          ta >>= 4; tw >>= 4;
          wgmma_fence();
#pragma unroll
          for (int k = 0; k < 4; ++k) wgmma_n128(acc, D128(da + k * 2), D128(db + k * 128), 1);
          wgmma_commit();
          wgmma_wait<1>();
          if (elected) REL2(CT + j - 1);
        }
        ta = TL_A >> (4 * j1); tw = TL_B >> (4 * j1);
      };
      auto rest = [&](int j0, int sk) {
        if (sk) {
          run(j0, ND - sk);
          if (wu == 0) nbar<6, 256>();
          j0 = ND - sk;
        }
        run(j0, ND);
        if (sk && wu) asm volatile("bar.arrive 6, 256;" ::: "memory");
      };
      auto rest_end = [&]() {
        wgmma_wait<0>();
        if (elected) REL2(CT + ND - 1);
#pragma unroll
        for (int i = 128; i < 192; ++i) asm volatile("" : "+f"(acc[i]) :: "memory");
      };
      auto wo0 = [&]() {
        wgmma_fence();
        wgmma_n128_rs0(acc, of[0], D128(dB0 + (uint32_t)(WO_B & 15) * 1024));
#pragma unroll
        for (int k = 1; k < 4; ++k) wgmma_n128_rs(acc, of[k], D128(dB0 + (uint32_t)(WO_B & 15) * 1024 + k * 128), 1);
        wgmma_commit();
      };
      const float rs0 = lds_f(sb + SM_RS + (16 + wrow0 + gq) * 4), rs1 = lds_f(sb + SM_RS + (24 + wrow0 + gq) * 4);
#define EPOCH() __float_as_uint(lds_f(sb + SM_EPOCH))
      mbar_wait(BA(CM + 14), par);
      if (par) {
        uint32_t kk[8][4], kp[8][4], vf[2][2][4][4];
        int sn = 4;
#pragma unroll
        for (int i = 0; i < 4 * BT1; ++i) sub(sn++);
        {
          uint32_t vv[8][4];
#pragma unroll
          for (int jp = 0; jp < 8; ++jp) {
            kk[jp][0] = pack_bf16(acc[8 * jp], acc[8 * jp + 1]); kk[jp][1] = pack_bf16(acc[8 * jp + 4], acc[8 * jp + 5]);
            kk[jp][2] = pack_bf16(acc[8 * jp + 2], acc[8 * jp + 3]); kk[jp][3] = pack_bf16(acc[8 * jp + 6], acc[8 * jp + 7]);
#pragma unroll
            for (int i = 0; i < 4; ++i) vv[jp][i] = pack_bf16(acc[64 + 8 * jp + 2 * i], acc[65 + 8 * jp + 2 * i]);
          }
          if (cw == 7) {
            uint32_t* const hbuf = g_halo + (size_t)(((layer >> 1) * 17 + rb + 1) * 8 + g) * 2048;
#pragma unroll
            for (int jp = 0; jp < 8; ++jp) stg128(hbuf + jp * 128 + lane * 4, kk[jp][0], kk[jp][1], kk[jp][2], kk[jp][3]);
#pragma unroll
            for (int i = 0; i < 32; ++i) hbuf[1024 + (i >> 4) * 512 + (gq + (i & 1) * 8) * 32 + ((((i >> 1) & 7) ^ gq) << 2) + t] = vv[i >> 2][i & 3];
            __syncwarp();
            if (lane == 0) mbar_arrive(BA(B_OF0));
          }
#pragma unroll
          for (int jp = 0; jp < 8; ++jp) {
            sub(sn++);
            stsm_x4(sb + VB + (jp >> 2) * SLOT + rowo + (X ^ ((jp & 3) << 5)), vv[jp][0], vv[jp][1], vv[jp][2], vv[jp][3]);
          }
        }
        PROFT(tid_ == 128, layer * 16 + 2);
        const int e = gq & 1;
        float f0[4], f1[4], b0[4], b1[4], rj[4];
#pragma unroll
        for (int nt = 0; nt < 4; ++nt) {
          const int kx = nt * 8 + 2 * t + e;
          const bool okk = (m0 + wrow0 + kx) >= 16;
          const int d0 = kx - gq, d1 = d0 - 8;
          rj[nt] = lds_f(sb + SM_RS + (wrow0 + kx) * 4);
          const bool m0_ = okk && d0 >= 2 && d0 <= 16, m1_ = okk && d1 >= 2 && d1 <= 16;
          f0[nt] = m0_ ? rj[nt] * rs0 * (0.17677669529663687f * L2E) : 0.f;
          f1[nt] = m1_ ? rj[nt] * rs1 * (0.17677669529663687f * L2E) : 0.f;
          b0[nt] = m0_ ? 0.f : -1e30f; b1[nt] = m1_ ? 0.f : -1e30f;
        }
        mbar_wait(BA(CM + 15), par);
#pragma unroll
        for (int jp = 0; jp < 8; ++jp) {
          sub(sn++);
          sts128(sb + PH + cw * 4096 + jp * 512 + lane * 16, make_uint4(kk[jp][0], kk[jp][1], kk[jp][2], kk[jp][3]));
        }
#pragma unroll
        for (int i = 0; i < 4; ++i) sub(sn++);
        nbar<1, 256>();
        PROFT(tid_ == 128, layer * 16 + 3);
        rest(sn >> 2, SKB);
        if (!BPRE) rest_end();
        PROFT(lane == 0 && layer == PL, 200 + cw);
        PROFT(tid_ == 128, layer * 16 + 10);
        if (cw == 0) mbar_wait(BA(B_HALO), (layer >> 1) & 1);
        PROFT(tid_ == 128, layer * 16 + 5);
        const uint32_t vs = sb + (cw ? VB + rowo - 2048 : SM_SD + 4096 + rowo), vst = cw ? SLOT : 2048;
        const uint32_t psel = e ? 0x1054u : 0x5410u;
#pragma unroll
        for (int hp = 0; hp < 2; ++hp) {
#pragma unroll
          for (int i = 4 * hp; i < 4 * hp + 4; ++i) {
            const uint4 u = lds128(sb + (cw ? PH + (cw - 1) * 4096 : SM_SD) + lane * 16 + i * 512);
            kp[i][0] = u.x; kp[i][1] = u.y; kp[i][2] = u.z; kp[i][3] = u.w;
          }
#pragma unroll
          for (int i = 4 * hp; i < 4 * hp + 4; ++i) {
            ldsm_x4_t(vf[0][i & 1][i >> 1][0], vf[0][i & 1][i >> 1][1], vf[0][i & 1][i >> 1][2], vf[0][i & 1][i >> 1][3], vs + (i >> 2) * vst + (X ^ ((i & 3) << 5)));
            ldsm_x4_t(vf[1][i & 1][i >> 1][0], vf[1][i & 1][i >> 1][1], vf[1][i & 1][i >> 1][2], vf[1][i & 1][i >> 1][3], sb + VB + (i >> 2) * SLOT + rowo + (X ^ ((i & 3) << 5)));
          }
          if (BPRE && !hp) rest_end();
          float l0[2][4], l1[2][4];
#pragma unroll
          for (int h = 0; h < 2; ++h) {
            const int H = 2 * hp + h;
            uint32_t qa[8];
#pragma unroll
            for (int i = 0; i < 8; ++i) qa[i] = pack_bf16(acc[128 + 16 * H + 2 * i], acc[129 + 16 * H + 2 * i]);
#pragma unroll
            for (int nt = 3; nt >= 0; --nt) {
              float sc[4] = {0.f, 0.f, 0.f, 0.f};
#pragma unroll
              for (int ks = 0; ks < 2; ++ks) {
                const uint32_t (&kf)[4] = nt < 2 ? kp[2 * H + ks] : kk[2 * H + ks];
                mma_bf16(sc, qa[4 * ks], qa[4 * ks + 1], qa[4 * ks + 2], qa[4 * ks + 3], kf[2 * (nt & 1)], kf[2 * (nt & 1) + 1]);
              }
              l0[h][nt] = fmaf(e ? sc[1] : sc[0], f0[nt], b0[nt]);
              l1[h][nt] = fmaf(e ? sc[3] : sc[2], f1[nt], b1[nt]);
            }
          }
          float mx0[2], mx1[2], s0[2], s1[2];
#pragma unroll
          for (int h = 0; h < 2; ++h) {
            mx0[h] = fmaxf(fmaxf(l0[h][0], l0[h][1]), l0[h][2]);
            mx1[h] = fmaxf(fmaxf(l1[h][1], l1[h][2]), l1[h][3]);
          }
#pragma unroll
          for (int o = 1; o <= 2; o <<= 1)
#pragma unroll
            for (int h = 0; h < 2; ++h) {
              mx0[h] = fmaxf(mx0[h], __shfl_xor_sync(0xffffffffu, mx0[h], o));
              mx1[h] = fmaxf(mx1[h], __shfl_xor_sync(0xffffffffu, mx1[h], o));
            }
#pragma unroll
          for (int h = 0; h < 2; ++h) {
#pragma unroll
            for (int nt = 0; nt < 3; ++nt) { l0[h][nt] = ex2(l0[h][nt] - mx0[h]); l1[h][nt + 1] = ex2(l1[h][nt + 1] - mx1[h]); }
            s0[h] = (l0[h][0] + l0[h][1]) + l0[h][2];
            s1[h] = (l1[h][1] + l1[h][2]) + l1[h][3];
          }
#pragma unroll
          for (int o = 1; o <= 2; o <<= 1)
#pragma unroll
            for (int h = 0; h < 2; ++h) {
              s0[h] += __shfl_xor_sync(0xffffffffu, s0[h], o);
              s1[h] += __shfl_xor_sync(0xffffffffu, s1[h], o);
            }
          uint32_t ow[2][2][4];
#pragma unroll
          for (int h = 0; h < 2; ++h) {
            const int H = 2 * hp + h;
            uint32_t pl[4], ph[4];
            const float i0 = rcp(s0[h]), i1 = rcp(s1[h]);
#pragma unroll
            for (int nt = 0; nt < 4; ++nt) {
              const uint32_t pk = pack_bf16(nt < 3 ? l0[h][nt] * i0 * rj[nt] : 0.f, nt > 0 ? l1[h][nt] * i1 * rj[nt] : 0.f);
              pl[nt] = nt < 3 ? __byte_perm(pk, 0u, psel) : 0u;
              ph[nt] = nt > 0 ? __byte_perm(pk, 0u, psel + 0x2222u) : 0u;
            }
#pragma unroll
            for (int nj = 0; nj < 4; ++nj) {
              float oa[4] = {0.f, 0.f, 0.f, 0.f};
#pragma unroll
              for (int ks = 0; ks < 2; ++ks)
                mma_bf16(oa, pl[2 * ks], ph[2 * ks], pl[2 * ks + 1], ph[2 * ks + 1], vf[ks][nj >> 1][H][2 * (nj & 1)], vf[ks][nj >> 1][H][2 * (nj & 1) + 1]);
              ow[h][0][nj] = pack_bf16(oa[0], oa[1]); ow[h][1][nj] = pack_bf16(oa[2], oa[3]);
            }
          }
          if (hp == 0) {
#pragma unroll
            for (int i = 0; i < 4; ++i) stg128(g_o + gfr + (i & 1) * 8 * D_ + (i >> 1) * 32, ow[i >> 1][i & 1][0], ow[i >> 1][i & 1][1], ow[i >> 1][i & 1][2], ow[i >> 1][i & 1][3]);
            __syncwarp();
            if (lane == 0) mbar_arrive(BA(B_OH0));
          } else {
#pragma unroll
            for (int i = 0; i < 16; ++i) o1[i >> 2][i & 3] = ow[i >> 3][(i >> 2) & 1][i & 3];
          }
#pragma unroll
          for (int i = 0; i < 16; ++i) of[4 * hp + (i >> 2)][i & 3] = ow[i >> 3][i & 1][(i >> 1) & 3];
          if (!hp) { PROFT(tid_ == 128, layer * 16 + 15); mbar_wait(BA(FW), par); }
        }
      } else {
        float sc[2] = {rs0 * L2E, rs1 * L2E};
        {
          const uint32_t vb = sb + VB + (rowo >> 1), X0 = (lchk ^ ((lane & 7) >> 1)) << 4;
          const uint32_t pb = sb + PH + (t & 1) * SLOT + (wrow0 + gq) * 128 + ((((t & 1) * 4 + (t & 2)) ^ gq) << 4);
          float kva[20], en[32], mx[2][2], mn[2][2];
#define PV(hp, j) acc[32 * (hp) + (j)]
          auto mm = [&](int hp, int j) {
            const int r = (j >> 1) & 1;
            if (j < 4 && !(j & 1)) { mx[hp][r] = PV(hp, j); mn[hp][r] = PV(hp, j); }
            else { mx[hp][r] = fmaxf(mx[hp][r], PV(hp, j)); mn[hp][r] = fminf(mn[hp][r], PV(hp, j)); }
          };
          auto mmx = [&](int hp) {
#pragma unroll
            for (int r = 0; r < 2; ++r) {
              mx[hp][r] = fmaxf(mx[hp][r], __shfl_xor_sync(0xffffffffu, mx[hp][r], 2)) * -sc[r];
              mn[hp][r] = fmaf(fminf(mn[hp][r], __shfl_xor_sync(0xffffffffu, mn[hp][r], 2)), sc[r], mx[hp][r]);
            }
          };
          auto stage = [&](int hp) {
#pragma unroll
            for (int i = 0; i < 20; ++i) asm volatile("" : "+f"(kva[i]) :: "memory");
            nbar_dyn(3 + wu, 128);
#pragma unroll
            for (int i = 0; i < 4; ++i)
              sts128(sb + VB + hp * SLOT + wg * 8192 + (wq * 128 + i * 32 + lane) * 16,
                     make_uint4(__float_as_uint(kva[4 * i]), __float_as_uint(kva[4 * i + 1]), __float_as_uint(kva[4 * i + 2]), __float_as_uint(kva[4 * i + 3])));
            if (t == 0) sts_f2(sb + SM_AP + ((2 * hp + wg) * 64 + wq * 16 + gq * 2) * 4, kva[16], kva[18]);
            fence_async_smem();
            __syncwarp();
            if (lane == 0) mbar_arrive(BA(B_KVDONE));
          };
          int sn = 4;
#pragma unroll
          for (int j = 0; j < 32; ++j) mm(0, j);
          mmx(0);
#pragma unroll
          for (int hp = 0; hp < 2; ++hp) {
            float sp[2] = {0.f, 0.f}, sm[2] = {0.f, 0.f};
#pragma unroll
            for (int j = 0; j < 32; ++j) {
              const int r = (j >> 1) & 1, ns = hp ? SUBS1 : SUBS;
              if ((j * ns) / 32 != ((j + 1) * ns) / 32) {
                sub(sn++);
                if (hp && sn == 4 + SUBS + 4 + 4 * (XST & 1)) { stage(0); PROFT(tid_ == 128, layer * 16 + 12); }
              }
              const float x = fmaf(PV(hp, j), sc[r], mx[hp][r]);
              PV(hp, j) = ex2(x); en[j] = ex2(mn[hp][r] - x);
              sp[r] += PV(hp, j); sm[r] += en[j];
              if (hp == 0) {
                mm(1, j);
                if ((j & 3) == 0) {
                  const int jp = 8 + (j >> 2);
                  stsm_x4(vb + ((jp - 8) >> 1) * 8192 + (X0 ^ ((jp & 1) << 5)), pack_bf16(acc[8 * jp], acc[8 * jp + 1]), pack_bf16(acc[8 * jp + 2], acc[8 * jp + 3]),
                          pack_bf16(acc[8 * jp + 4], acc[8 * jp + 5]), pack_bf16(acc[8 * jp + 6], acc[8 * jp + 7]));
                }
              }
            }
#pragma unroll
            for (int i = 0; i < 4; ++i) if (XST & (1 << hp)) sub(sn++);
#pragma unroll
            for (int r = 0; r < 2; ++r) {
              sp[r] = rcp(sp[r] + __shfl_xor_sync(0xffffffffu, sp[r], 2)) * (r ? rs1 : rs0);
              sm[r] = rcp(sm[r] + __shfl_xor_sync(0xffffffffu, sm[r], 2)) * (r ? rs1 : rs0);
            }
            if (hp == 0) { mmx(1); mbar_wait(BA(CM + 15), par); }
            else { PROFT(tid_ == 128, layer * 16 + 11); nbar<1, 256>(); }
#pragma unroll
            for (int i = 0; i < 4; ++i) {
              const int r = i & 1, d = 16 * (i >> 1) + 2 * r;
              sts128((pb + r * 1024) ^ ((i >> 1) << 4), make_uint4(pack_bf16(PV(hp, d) * sp[r], PV(hp, d + 1) * sp[r]), pack_bf16(PV(hp, d + 4) * sp[r], PV(hp, d + 5) * sp[r]),
                                                                    pack_bf16(PV(hp, d + 8) * sp[r], PV(hp, d + 9) * sp[r]), pack_bf16(PV(hp, d + 12) * sp[r], PV(hp, d + 13) * sp[r])));
              sts128((pb + r * 1024) ^ ((i >> 1) << 4) ^ 64, make_uint4(pack_bf16(en[d] * sm[r], en[d + 1] * sm[r]), pack_bf16(en[d + 4] * sm[r], en[d + 5] * sm[r]),
                                                                         pack_bf16(en[d + 8] * sm[r], en[d + 9] * sm[r]), pack_bf16(en[d + 12] * sm[r], en[d + 13] * sm[r])));
            }
            fence_async_smem();
            nbar<1, 256>();
            const uint32_t dP = dB0 + (PH >> 4) + wu * 1024;
            const uint32_t dV = (dB0 & 0xFFFFu) + ((VB + hp * SLOT) >> 4) + (((SM_SD - VB - hp * SLOT) >> 4) << 16) + wu * (512u - (512u << 16));
            wgmma_fence();
#pragma unroll
            for (int ks = 0; ks < 8; ++ks) wgmma_n40_tt(kva, D128(dP + ks * 128), desc64(dV + ks * 64, 0x80000020u), ks != 0);
            wgmma_commit();
          }
#pragma unroll
          for (int i = 0; i < 4; ++i) sub(sn++);
          stage(1);
          PROFT(tid_ == 128, layer * 16 + 3);
          rest(sn >> 2, SKA);
          rest_end();
          PROFT(lane == 0 && layer == PL, 200 + cw);
          PROFT(tid_ == 128, layer * 16 + 10);
        }
#define QV(H, i) acc[128 + 16 * (H) + (i)]
        float mx[4][2], mn[4][2];
        uint32_t ph[4][4][4];
        auto mnx = [&](int hp) {
#pragma unroll
          for (int H = 2 * hp; H < 2 * hp + 2; ++H)
#pragma unroll
            for (int r = 0; r < 2; ++r) {
              mx[H][r] = fmaxf(fmaxf(fmaxf(QV(H, 2 * r), QV(H, 2 * r + 1)), fmaxf(QV(H, 4 + 2 * r), QV(H, 5 + 2 * r))),
                               fmaxf(fmaxf(QV(H, 8 + 2 * r), QV(H, 9 + 2 * r)), fmaxf(QV(H, 12 + 2 * r), QV(H, 13 + 2 * r))));
              mn[H][r] = fminf(fminf(fminf(QV(H, 2 * r), QV(H, 2 * r + 1)), fminf(QV(H, 4 + 2 * r), QV(H, 5 + 2 * r))),
                               fminf(fminf(QV(H, 8 + 2 * r), QV(H, 9 + 2 * r)), fminf(QV(H, 12 + 2 * r), QV(H, 13 + 2 * r))));
            }
#pragma unroll
          for (int o = 1; o <= 2; o <<= 1)
#pragma unroll
            for (int H = 2 * hp; H < 2 * hp + 2; ++H)
#pragma unroll
              for (int r = 0; r < 2; ++r) {
                mx[H][r] = fmaxf(mx[H][r], __shfl_xor_sync(0xffffffffu, mx[H][r], o));
                mn[H][r] = fminf(mn[H][r], __shfl_xor_sync(0xffffffffu, mn[H][r], o));
              }
#pragma unroll
          for (int H = 2 * hp; H < 2 * hp + 2; ++H)
#pragma unroll
            for (int r = 0; r < 2; ++r) { mx[H][r] *= -sc[r]; mn[H][r] = fmaf(mn[H][r], sc[r], mx[H][r]); }
        };
        auto fm = [&](int H) {
#pragma unroll
          for (int i = 0; i < 8; ++i) {
            const int r = i & 1;
            const float x0 = fmaf(QV(H, 2 * i), sc[r], mx[H][r]), x1 = fmaf(QV(H, 2 * i + 1), sc[r], mx[H][r]);
            ph[H][i >> 2][i & 3] = pack_bf16(ex2(x0), ex2(x1));
            ph[H][2 + (i >> 2)][i & 3] = pack_bf16(ex2(mn[H][r] - x0), ex2(mn[H][r] - x1));
          }
        };
        auto conv = [&](int hp) {
          mbar_wait(BA(hp ? B_KVF1 : B_KVF), (layer >> 1) & 1);
          PROFT(tid_ == 128, layer * 16 + (hp ? 4 : 5));
          if (hp) { mbar_wait(BA(FW), par); nbar_dyn(3 + wu, 128); }
#pragma unroll
          for (int h = 0; h < 2; ++h) {
            uint4 u[4];
#pragma unroll
            for (int i = 0; i < 4; ++i) u[i] = lds128(sb + VB + hp * SLOT + h * 8192 + (wq * 128 + i * 32 + lane) * 16);
            const float zz = lds_f(sb + SM_AP + ((2 * hp + h) * 64 + wq * 16 + (lane & 7) * 2 + ((lane >> 3) & 1)) * 4);
            const uint32_t kb_ = sb + PH + wg * SLOT + h * 8192 + (wq * 16 + lrow) * 128;
#pragma unroll
            for (int i = 0; i < 4; i += 2)
              stsm_x4(kb_ + (X ^ (i << 4)),
                      pack_bf16(__uint_as_float(u[i].x), __uint_as_float(u[i].y)), pack_bf16(__uint_as_float(u[i].z), __uint_as_float(u[i].w)),
                      pack_bf16(__uint_as_float(u[i + 1].x), __uint_as_float(u[i + 1].y)), pack_bf16(__uint_as_float(u[i + 1].z), __uint_as_float(u[i + 1].w)));
            const uint32_t z1 = pack_bf16(zz, 1.f);
            if (lane < 16) sts128(kb_ + ((4 ^ (lane & 7)) << 4), make_uint4(z1, z1, z1, z1));
          }
          fence_async_smem();
        };
        mnx(0);
        fm(0);
        if (CV0) conv(0);
        fm(1);
        if (!CV0) conv(0);
#pragma unroll
        for (int hp = 0; hp < 2; ++hp) {
          nbar_dyn(3 + wu, 128);
          float oa[4][20];
          wgmma_fence();
#pragma unroll
          for (int s = 0; s < 2; ++s)
#pragma unroll
            for (int v = 0; v < 4; ++v) {
              const int h = v >> 1, s4 = 2 * (v & 1) + s;
              wgmma_n40_rs(oa[v], ph[2 * hp + h][s4], D128(dB0 + (PH >> 4) + wu * 1024 + h * 512 + (s4 ^ (2 * h)) * 128), s != 0);
            }
          wgmma_commit();
          if (hp == 0) { mnx(1); wgmma_wait<0>(); }
          else wgmma_wait<0>();
#pragma unroll
          for (int i = 0; i < 20; ++i) asm volatile("" : "+f"(oa[0][i]), "+f"(oa[1][i]), "+f"(oa[2][i]), "+f"(oa[3][i]) :: "memory");
          uint32_t ow[2][2][4];
#pragma unroll
          for (int h = 0; h < 2; ++h)
#pragma unroll
            for (int r = 0; r < 2; ++r) {
              const float a = oa[2 * h + 1][17 + 2 * r], b = oa[2 * h][17 + 2 * r];
              const float id = rcp(fmaf(oa[2 * h][16 + 2 * r], a, fmaf(a, 1e-6f, oa[2 * h + 1][16 + 2 * r]) * b));
              const float fa = a * id, fb = b * id;
#pragma unroll
              for (int j = 0; j < 4; ++j)
                ow[h][r][j] = pack_bf16(fmaf(oa[2 * h][4 * j + 2 * r], fa, oa[2 * h + 1][4 * j + 2 * r] * fb),
                                        fmaf(oa[2 * h][4 * j + 2 * r + 1], fa, oa[2 * h + 1][4 * j + 2 * r + 1] * fb));
            }
#pragma unroll
          for (int i = 0; i < 16; ++i) of[4 * hp + (i >> 2)][i & 3] = ow[i >> 3][i & 1][(i >> 1) & 3];
          if (hp == 0) {
#pragma unroll
            for (int i = 0; i < 8; ++i) {
              if (!(i & 1)) stg128(g_o + gfr + ((i >> 1) & 1) * 8 * D_ + (i >> 2) * 32, ow[i >> 2][(i >> 1) & 1][0], ow[i >> 2][(i >> 1) & 1][1], ow[i >> 2][(i >> 1) & 1][2], ow[i >> 2][(i >> 1) & 1][3]);
              const int r = i & 1;
              const float x0 = fmaf(QV(2, 2 * i), sc[r], mx[2][r]), x1 = fmaf(QV(2, 2 * i + 1), sc[r], mx[2][r]);
              ph[2][i >> 2][i & 3] = pack_bf16(ex2v(x0), ex2v(x1));
              ph[2][2 + (i >> 2)][i & 3] = pack_bf16(ex2v(mn[2][r] - x0), ex2v(mn[2][r] - x1));
            }
            __syncwarp();
            if (lane == 0) mbar_arrive(BA(B_OH0));
            PROFT(tid_ == 128 && layer, layer * 16 + 15);
            if (QORD) { fm(3); conv(1); } else { conv(1); fm(3); }
          } else {
#pragma unroll
            for (int i = 0; i < 16; ++i) o1[i >> 2][i & 3] = ow[i >> 3][(i >> 2) & 1][i & 3];
          }
        }
      }
      PROFT(tid_ == 128, layer * 16 + 6);
#pragma unroll
      for (int i = 0; i < 4; ++i) stg128(g_o + gfr + (i & 1) * 8 * D_ + (2 + (i >> 1)) * 32, o1[i][0], o1[i][1], o1[i][2], o1[i][3]);
      __syncwarp();
      if (lane == 0) { mbar_arrive(BA(B_OH1)); if (EF_USED) REL2(B_EF); }
      PROFT(lane == 0 && layer == PL, 208 + cw);
      wo0();
    }
    {
      PHASE_CTX();
      MMA_CTX();
      mbar_wait(BA(FW + 1), par);
      wgmma_fence();
#pragma unroll
      for (int k = 0; k < 4; ++k) wgmma_n128_rs(acc, of[4 + k], D128(dB0 + (uint32_t)((WO_B >> 4) & 15) * 1024 + k * 128), 1);
      wgmma_commit();
      wgmma_wait<1>();
      if (elected) REL2(CW);
      uint64_t ta = WO_A >> 8, tw = WO_B >> 8;
      auto run = [&](int i0, int i1) {
#pragma unroll 1
        for (int i = i0; i < i1; ++i) {
          mbar_wait(BA(FW + i), par);
          PROFL(tid_ == 128 && layer == PL, 160 + i);
          const uint32_t da = dA0 + ((uint32_t)ta & 15) * 1024, db = dB0 + ((uint32_t)tw & 15) * 1024;
          ta >>= 4; tw >>= 4;
          wgmma_fence();
#pragma unroll
          for (int k = 0; k < 4; ++k) wgmma_n128(acc, D128(da + k * 2), D128(db + k * 128), 1);
          wgmma_commit();
          wgmma_wait<1>();
          if (elected) REL2(CW + i - 1);
        }
        ta = WO_A >> (4 * (i1 & 15)); tw = WO_B >> (4 * (i1 & 15));
      };
      run(2, XRAT);
#pragma unroll
      for (int j = 0; j < 8 / XRN; ++j) {
#pragma unroll
        for (int i = j * XRN; i < (j + 1) * XRN; ++i) ldg128((layer ? g_x : c.x0) + gfr + (i & 1) * 8 * D_ + (i >> 1) * 32, xp[i][0], xp[i][1], xp[i][2], xp[i][3]);
        run(XRAT + j, j + 1 < 8 / XRN ? XRAT + j + 1 : 16);
      }
      if (layer == 0) {
#pragma unroll
        for (int o = 1; o <= 2; o <<= 1)
#pragma unroll
          for (int i = 0; i < 16; ++i) {
            const int j = o == 1 ? 2 * (i & 1) : (i & 1);
            uint32_t &a = xp[i >> 1][j], &b = xp[i >> 1][j + o];
            const uint32_t r = __shfl_xor_sync(0xffffffffu, (t & o) ? a : b, o);
            if (t & o) a = r; else b = r;
          }
      }
      if (layer != NLAYERS - 1) mbar_wait(BA(FM), par ^ 1);
      wgmma_wait<0>();
#pragma unroll
      for (int i = 128; i < 192; ++i) asm volatile("" : "+f"(acc[i]) :: "memory");
      if (elected) REL2(CW + 15);
      PROFT(lane == 0 && layer == PL, 216 + cw);
      PROFT(tid_ == 128, layer * 16 + 7);
#pragma unroll
      for (int i = 0; i < 32; ++i)
        xp[i >> 2][i & 3] = add_bf16x2(xp[i >> 2][i & 3], pack_bf16(acc[128 + 16 * (i >> 3) + 4 * (i & 3) + 2 * ((i >> 2) & 1)], acc[129 + 16 * (i >> 3) + 4 * (i & 3) + 2 * ((i >> 2) & 1)]));
      if (layer == NLAYERS - 1) {
#pragma unroll
        for (int i = 0; i < 8; ++i) stsm_x4(sb + (XS + (i >> 2)) * SLOT + (Y ^ ((i & 2) << 5)) + (i & 1) * 1024, xp[i][0], xp[i][1], xp[i][2], xp[i][3]);
        __syncwarp();
        slab_out_half(sb + XS * SLOT, c.out + (size_t)m0 * D_ + g * 128, wrow0, lane);
        slab_out_half(sb + (XS + 1) * SLOT, c.out + (size_t)m0 * D_ + g * 128 + 64, wrow0, lane);
        PROFT(tid_ == 128, layer * 16 + 24);
        break;
      }
#pragma unroll
      for (int i = 0; i < 4; ++i) stg128(g_x + gfr + (i & 1) * 8 * D_ + (i >> 1) * 32, xp[i][0], xp[i][1], xp[i][2], xp[i][3]);
      __syncwarp();
      if (lane == 0) mbar_arrive(BA(B_XH0));
#pragma unroll
      for (int i = 0; i < 16; ++i) xf[i >> 2][i & 3] = xp[2 * (i >> 3) + (i & 1)][(i >> 1) & 3];
      PROFT(tid_ == 128, layer * 16 + 24);
    }
  }
}

__device__ __forceinline__ uint64_t k_order(int o) {
  const uint32_t lo = (1u << (4 * o)) - 1u, h0 = (0xECA86420u & lo) | ((0xECA86420u >> 4) & ~lo);
  return (uint64_t)(2 * o) | ((uint64_t)(2 * o + 1) << 4) | ((uint64_t)(h0 & 0xFFFFFFFu) << 8) | ((uint64_t)((h0 & 0xFFFFFFFu) | 0x1111111u) << 36);
}

__global__ void __cluster_dims__(2, 1, 1) __launch_bounds__(384, 1)
mega_kernel(const __grid_constant__ Maps maps, const __grid_constant__ Ctx c, const bf16* __restrict__ wA, const bf16* __restrict__ wB,
            const bf16* __restrict__ woA, const bf16* __restrict__ woB) {
  if (blockIdx.x - c.boff >= 128u) {
    const unsigned int epoch = ld_relaxed(&g_epoch);
    const int e = (blockIdx.x - c.boff) & 3, tid = threadIdx.x;
    float s[8] = {0.f, 0.f, 0.f, 0.f, 0.f, 0.f, 0.f, 0.f};
    const uint32_t sb = smem_u32(smem_raw), bar = sb + SM_BAR;
    auto issue = [&](int i) {
      mbar_expect_tx(BA(i & 3), 49152);
      bulk_load(sb + (i & 3) * 49152, wB + (size_t)e * 256 * 3072 + i * 24576, 49152, BA(i & 3));
    };
    if (tid == 0) {
#pragma unroll 1
      for (int i = 0; i < 4; ++i) {
        mbar_init(BA(i), 1);
        fence_async_smem();
        issue(i);
      }
    }
    __syncthreads();
#pragma unroll 1
    for (int i = 0; i < 32; ++i) {
      mbar_wait(BA(i & 3), (i >> 2) & 1);
#pragma unroll 2
      for (int r = 0; r < 8; ++r) {
        const uint4 v = lds128(sb + (i & 3) * 49152 + r * 6144 + tid * 16);
        s[0] += bf_lo(v.x); s[1] += bf_hi(v.x); s[2] += bf_lo(v.y); s[3] += bf_hi(v.y);
        s[4] += bf_lo(v.z); s[5] += bf_hi(v.z); s[6] += bf_lo(v.w); s[7] += bf_hi(v.w);
      }
      __syncthreads();
      if (tid == 0 && i < 28) issue(i + 4);
    }
    float* cd = g_cs + (epoch & 1) * 6144 + 3072 + ((tid >> 4) & 7) * 384 + (tid < 128 ? 256 : (tid >> 7) * 128 - 128) + (tid & 15) * 8;
    red_add4(cd, s[0], s[1], s[2], s[3]);
    red_add4(cd + 4, s[4], s[5], s[6], s[7]);
    __syncthreads();
    if (tid == 0) flag_add(&g_csflag[8].v);
    const int op = (epoch & 1) ^ 1;
    float4* kz = reinterpret_cast<float4*>(g_kv + (size_t)op * (2 * 8 * 8448)) + e * 8448;
#pragma unroll 1
    for (int i = tid; i < 8448; i += 384) kz[i] = make_float4(0.f, 0.f, 0.f, 0.f);
    reinterpret_cast<float4*>(g_cs + op * 6144)[e * 384 + tid] = make_float4(0.f, 0.f, 0.f, 0.f);
#pragma unroll 1
    for (int i = tid; i < 1024; i += 384) reinterpret_cast<float4*>(g_stats + (op * 4 + e) * S_)[i] = make_float4(0.f, 0.f, 0.f, 0.f);
    return;
  }
  const int warp = __shfl_sync(0xffffffffu, threadIdx.x >> 5, 0), lane = threadIdx.x & 31;
  if (smem_u32(smem_raw) != SB0 + ((blockIdx.x & 1) << 24)) __trap();
  {
  const int cid = (blockIdx.x - c.boff) >> 1, u7 = ((cid - 36) * 37) >> 8, cr = blockIdx.x & 1;
  const int g = cid < 4 ? 4 + cid : cid < 36 ? (cid - 4) >> 3 : 4 + u7, rb = (cid < 4 ? 0 : cid < 36 ? (cid - 4) & 7 : cid - 35 - 7 * u7) * 2 + cr, m0 = rb * 128;
  const uint32_t sb = SB0 + (cr << 24), bar = sb + SM_BAR;
  PROFT(lane == 0 && (warp == 0 || warp == 4), 224 + (warp >> 2) * 8);
  uint32_t cx = 0;
  if (warp == 2) {
    if (lane < NMAP) asm volatile("prefetch.tensormap [%0];" ::"l"(&maps.m[lane]) : "memory");
    if (lane == 31) asm volatile("prefetch.global.L2 [%0];" ::"l"(&g_epoch));
  } else if (warp == 3) {
    cx = c_map[cid] + c_wop[lane] + c_wop[NWOP - lane] + c_aop[lane] + c_aop[NAOP - lane] + (uint32_t)(uintptr_t)g_x;
  } else if (warp >= 4 && warp < 8) {
    const int i = threadIdx.x - 128;
    asm volatile("prefetch.global.L2 [%0];" ::"l"(wA + (size_t)((rb & ~1) * 64 + cr * 32 + ((i >> 1) & 31)) * 3072 + (i >> 6) * 1024 + g * 128 + (i & 1) * 64));
  }
  if (warp < 2) {
    const int s = warp, kb = (rb & ~1) + s;
    if (lane == 0) {
      mbar_init(BA(FM + s), 1u);
      mbar_init(BA(B_RAW + warp), 1u);
      if (warp) mbar_init(BA(B_X0), 1u);
      asm volatile("fence.mbarrier_init.release.cluster;" ::: "memory");
    }
    __syncwarp();
    if (warp == 0) tma_2d_e(sb + SM_SD, &maps.m[MAP_PHI], 0, g * 128, BA(B_RAW));
    else if (W1DL) __nanosleep(W1DL);
#pragma unroll
    for (int j = 0; j < 6; ++j)
      tma_5d_e(sb + (j < 2 ? 2 * s : j < 4 ? 9 + s : 2 * s + 1) * SLOT + (j & 1) * 8192, &maps.m[MAP_WA], (j < 2 ? 1024 : j < 4 ? 0 : 2048) + g * 128 + (j & 1) * 64, 2 * kb,
               BA(j < 4 ? B_RAW + warp : FM + s));
    tma_2d_e(sb + (XS + s) * SLOT, &maps.m[MAP_X0], kb * 64, m0, BA(FM + s));
    expect_tx_e(BA(B_RAW + warp), warp ? 32768 : 32768 + 8192);
    expect_tx_e(BA(FM + s), 32768);
    if (X0AT == 0 && warp == 1) {
      tma_2d_e(sb + 11 * SLOT, &maps.m[MAP_X0], g * 128, m0, BA(B_X0));
      tma_2d_e(sb + 12 * SLOT, &maps.m[MAP_X0], g * 128 + 64, m0, BA(B_X0));
      expect_tx_e(BA(B_X0), 32768);
    }
  } else if (warp >= 4 && lane == 0) {
#pragma unroll 1
    for (int i = 2 + (warp - 4) * 13; i < 15 + (warp - 4) * 13; ++i)
      mbar_init(BA(i), 1u << ((i < CM ? 0u : i < B_EF ? 2u : (uint32_t)(BAR_LG >> (4 * ((i - B_EF) & 15)))) & 7u));
    asm volatile("fence.mbarrier_init.release.cluster;" ::: "memory");
  }
  __syncwarp();
  asm volatile("barrier.cluster.arrive.relaxed.aligned;" ::: "memory");
  if (threadIdx.x == 96 + c.zero) sts_f(sb + SM_EPOCH + 4, __uint_as_float(cx));
  PROFT(lane == 0 && (warp == 0 || warp == 4), 225 + (warp >> 2) * 8);
  __syncwarp();
  PROFT(lane == 0 && (warp == 0 || warp == 4), 226 + (warp >> 2) * 8);
  }

  if (warp < 4) {
    asm volatile("setmaxnreg.dec.sync.aligned.u32 40;");
    PROFT(threadIdx.x == 0, 227);
    cluster_wait();
    PROFT(threadIdx.x == 0, 228);
    if (warp == 0 || warp == 3) {
    if (warp == 0) {
      BLK_CTX();
      const unsigned int epoch = __shfl_sync(0xffffffffu, ld_relaxed(&g_epoch), 0), xbase = epoch * NLAYERS;
      (void)xbase;
      const uint64_t ordg = k_order(g);
      if (X0AT) {
        mbar_wait_u(BA(B_RAW + X0AT - 1), 0);
        tma_2d_e(sb + 11 * SLOT, &maps.m[MAP_X0], g * 128, m0, BA(B_X0));
        tma_2d_e(sb + 12 * SLOT, &maps.m[MAP_X0], g * 128 + 64, m0, BA(B_X0));
        expect_tx_e(BA(B_X0), 32768);
      }
#pragma unroll 1
      for (int lp = 0; lp < 2 * NLAYERS; ++lp) {
        const int layer = lp >> 1, n1 = (lp & 1) ? NAOP : NAOP - 14;
        int n = (lp & 1) ? NAOP - 14 : 0;
        const uint64_t ord = lp ? ordg : k_order(rb >> 1);
        uint32_t ready = lp ? 0u : 0xFFFFu, nop = c_aop[n];
        const unsigned int* fl = ((lp & 1) ? g_of : g_xf) + rb * 32;
        const CUtensorMap* tm = &maps.m[(lp & 1) ? MAP_O : lp ? MAP_X : MAP_X0];
        const uint32_t skip = layer ? 1u << 25 : 9u << 22;
#pragma unroll 1
        for (; n < n1; ++n) {
          const uint32_t op = nop;
          nop = c_aop[n + 1];
          const uint32_t kb = (uint32_t)(ord >> ((op >> 2) & 60)) & 15;
          uint32_t dst = sb + (op & 15) * SLOT, kc = kb * 64, fb = bar + ((op >> 5) & 0x3F8), need = ~ready & (1u << kb);
          asm volatile("" : "+r"(dst), "+r"(kc), "+r"(fb), "+r"(need));
          const uint32_t eb = bar + ((op >> 12) & 0x3F8), ep = (layer ^ (op >> 22)) & 1;
          bool fr = op & skip;
          if (need) {
            if (!fr) fr = __all_sync(0xffffffffu, mbar_test_wait(eb, ep));
            PROFT(lane == 0 && (n == 0 || n == NAOP - 14), 64 + layer * 16 + (n ? 2 : 0));
            src_wait<0>(fl, xbase + layer + 1, need, ready, lane);
            fence_async_all();
          }
          if (!fr) mbar_wait_u(eb, ep);
          tma_2d_e(dst, tm, kc, m0, fb);
          PROFT(lane == 0 && (n == 0 || n == NAOP - 14), 64 + layer * 16 + (n ? 3 : 1));
          PROFL(lane == 0 && layer == PL && n >= NAOP - 14, 178 + n - (NAOP - 14));
          PROFL(lane == 0 && layer == PL + 1 && n < 4, 242 + n);
        }
      }
    } else {
      BLK_CTX();
      const unsigned int epoch = __shfl_sync(0xffffffffu, ld_relaxed(&g_epoch), 0), xbase = epoch * NLAYERS;
      (void)xbase;
      const uint64_t ordg = k_order(g);
#pragma unroll 1
      for (int layer = 0; layer < NLAYERS; ++layer) {
        const uint64_t ordq = layer ? ordg : k_order(rb >> 1);
        uint32_t ready = layer ? 0xFFFFu : 0u, nop = c_wop[0];
        const CUtensorMap* tq = &maps.m[(layer & 1) ? MAP_WB : MAP_WF];
        const CUtensorMap* tk = &maps.m[(layer & 1) ? MAP_WB : cr ? MAP_WA : MAP_WF];
        const uint32_t skip = layer ? 1u << 25 : 9u << 22, pm = layer ? 0xE0u : 0u;
        int n = 0;
#pragma unroll 1
        for (; n < NWOP - 16; ++n) {
          const uint32_t op = nop;
          nop = c_wop[n + 1];
          const uint32_t isq = (op >> 23) & 1, fb = bar + ((op >> 5) & 0x3F8);
          const uint32_t kb = (uint32_t)(ordq >> ((op >> 2) & 60)) & 15;
          const CUtensorMap* tm = (isq ? tq : tk) + ((op & pm) ? 1 : 0);
          const uint32_t dst = sb + (op & 15) * SLOT + cr * (isq ? 8192 : SLOT);
          const int col = g * 128 + (isq ? cr * 64 : 1024 + cr * 1024);
          if (layer == 0) {
            if ((op & 0x7E00) == 0) continue;
            const uint32_t need = ((isq || !cr) ? 1u << kb : 0u) | (((op >> 22) & 1) ? 0u : (((op >> 15) & 127) == CM ? 1u : 3u) << (rb & ~1));
            if ((ready & need) != need) {
              src_wait<0>(g_wff + g * 32, epoch + 1, need, ready, lane);
              fence_async_all();
            }
            if ((op & 15) >= 11) mbar_wait_u(BA(B_XT), 0);
          }
          wait_tma_5d_mc(!(op & skip), bar + ((op >> 12) & 0x3F8), (layer ^ (op >> 22)) & 1, dst, tm, col, 2 * kb, fb);
          if (!isq) tma_5d_mc_e(dst + 8192, tm, col + 64, 2 * kb, fb);
          if (op >> 26) expect_tx_e(fb, (op >> 26) * 8192);
          PROFL(lane == 0 && layer == PL + 1 && n < 16, 128 + n);
        }
        const CUtensorMap* to = &maps.m[(layer & 1) ? MAP_WOB : MAP_WOA];
#pragma unroll 1
        for (; n < NWOP; ++n) {
          const uint32_t op = nop;
          nop = c_wop[n + 1];
          const uint32_t fb = bar + ((op >> 5) & 0x3F8), kb = (uint32_t)(ordg >> ((op >> 2) & 60)) & 15;
          if (WH < 16 && n == NWOP - 16 + WH && !(layer & 1)) mbar_wait_u(BA(B_KVS), (layer >> 1) & 1);
          wait_tma_5d_mc(!((op >> 25) & 1), bar + ((op >> 12) & 0x3F8), layer & 1, sb + (op & 15) * SLOT + cr * 8192, to + ((op & 0xE0) ? 1 : 0), g * 128 + cr * 64, 2 * kb, fb);
          expect_tx_e(fb, (op >> 26) * 8192);
          PROFL(lane == 0 && layer == PL, 144 + ((op >> 8) & 127) - FW);
        }
      }
    }
    } else if (warp == 1) {
      BLK_CTX();
      const unsigned int epoch = __shfl_sync(0xffffffffu, ld_relaxed(&g_epoch), 0), xbase = epoch * NLAYERS;
      (void)xbase;
      if (lane == 0) {
        mbar_wait(BA(B_WFD), 0);
        PROFT(true, 229);
#pragma unroll 1
        for (int j = 0; j < 4; ++j) tma_store_5d(&maps.m[MAP_WF], sb + (j < 2 ? 2 * cr : 9 + cr) * SLOT + (j & 1) * 8192, (j < 2 ? 1024 : 0) + g * 128 + (j & 1) * 64, 2 * rb);
        bulk_commit();
        bulk_wait0();
        PROFT(true, 230);
        fence_async_all();
        flag_set(g_wff + g * 32 + rb, epoch + 1);
        PROFT(true, 64 + 13);
#pragma unroll 1
        for (int e = 0; e < NLAYERS; ++e) {
          BLK_CTX();
          if (e > 0) {
            mbar_wait(BA(B_XH0), (e - 1) & 1);
            PROFT(e == PL + 1, 240);
            flag_set(g_xf + rb * 32 + 2 * g, xbase + e + 1);
            PROFT(e == PL + 1, 241);
          }
          mbar_wait(BA(B_XDONE), e & 1);
          PROFT(true, 64 + e * 16 + 4);
          flag_set(g_xf + rb * 32 + 2 * g + 1, xbase + e + 1);
          if (e == 0) {
            flag_add(&g_csflag[g].v);
            l2_prefetch(wB + (size_t)bid_ * 24576, 49152);
            l2_prefetch(woA + (size_t)bid_ * 8192, 16384);
            l2_prefetch(woB + (size_t)bid_ * 8192, 16384);
          }
          PROFT(true, 64 + e * 16 + 7);
          if ((e & 1) == 0) {
            float* kvl = g_kv + ((size_t)((epoch & 1) * 2 + (e >> 1)) * 8 + g) * 8448;
#pragma unroll 1
            for (int hp = 0; hp < 2; ++hp) {
              mbar_wait(BA(B_KVDONE), hp);
              bulk_red_add(kvl + 8192 + hp * 128, sb + SM_AP + hp * 512, 512);
#pragma unroll 1
              for (int i = 0; i < NCH; ++i) {
                const int ch = hp * NCH + ((i + rb * NCH / 16) & (NCH - 1));
                bulk_red_add(kvl + ch * (4096 / NCH), sb + VB + ch * (16384 / NCH), 16384 / NCH);
                bulk_commit();
                asm volatile("cp.async.bulk.wait_group %0;" :: "n"(CHW) : "memory");
              }
              bulk_wait0();
              PROFT(true, 64 + e * 16 + (hp ? 10 : 6));
              fence_async_all();
              flag_add(&g_kvflag[hp * 8 + g].v);
              if (WH < 16 && hp) mbar_arrive(BA(B_KVS));
              PROFT(e > 0 && hp, 64 + e * 16 + 8);
            }
          }
          if (e & 1) {
            mbar_wait(BA(B_OF0), (e >> 1) & 1);
            flag_set(g_hf + rb * 32 + g, xbase + e + 1);
            if (rb) flag_wait(g_hf + (rb - 1) * 32 + g, xbase + e + 1);
            fence_async_all();
            mbar_expect_tx(BA(B_HALO), 8192);
            bulk_load(sb + SM_SD, g_halo + (size_t)(((e >> 1) * 17 + rb) * 8 + g) * 2048, 8192, BA(B_HALO));
            PROFT(true, 64 + e * 16 + 15);
          }
          mbar_wait(BA(B_OH0), e & 1);
          PROFT(e > 0, 64 + e * 16 + 13);
          flag_set(g_of + rb * 32 + 2 * g, xbase + e + 1);
          PROFT(true, 64 + e * 16 + 9);
          mbar_wait(BA(B_OH1), e & 1);
          PROFT(true, 64 + e * 16 + 5);
          flag_set(g_of + rb * 32 + 2 * g + 1, xbase + e + 1);
          PROFT(true, 64 + e * 16 + 11);
        }
        if (bid_ == 0) g_epoch = epoch + 1;
      }
    } else {
      BLK_CTX();
      const unsigned int epoch = __shfl_sync(0xffffffffu, ld_relaxed(&g_epoch), 0), xbase = epoch * NLAYERS;
      (void)xbase;
      if (lane < 16) sts_f(sb + SM_RS + lane * 4, 0.f);
#pragma unroll 1
      for (int layer = 0; layer < NLAYERS; ++layer) {
#define HLP_CTX() BLK_CTX(); int lane = threadIdx.x & 31; asm volatile("" : "+r"(lane)); const bool isB = layer & 1, hal = isB && rb > 0; (void)hal;
#pragma unroll 1
        for (int ph = 0; ph < 2; ++ph) {
          HLP_CTX();
          if (ph == (layer == 0)) {
            const float* cs = g_cs + (epoch & 1) * 6144 + g * 384;
            if (layer) mbar_wait_u(BA(CT), (layer - 1) & 1);
            if (layer < 2) {
              if (lane == 0) flag_wait_slow(&g_csflag[isB ? 8 : g].v, isB ? epoch * 4u + 4u : epoch * 16u + 16u);
              __syncwarp();
            }
#pragma unroll 1
            for (int i0 = 0; i0 < 12; i0 += 4) {
              float a[4];
#pragma unroll
              for (int i = 0; i < 4; ++i) a[i] = __ldcg(cs + isB * 3072 + (i0 + i) * 32 + lane);
#pragma unroll
              for (int i = 0; i < 4; ++i) {
                const float c1 = bf16r(a[i]), c2 = bf16r(a[i] - c1), c3 = (a[i] - c1) - c2;
                sts128(sb + SM_BP + ((i0 + i) * 32 + lane) * 16, make_uint4(pack_bf16(c1, c2), pack_bf16(c3, 0.f), 0u, 0u));
              }
            }
          } else {
            uint32_t rdy = 0u;
            src_wait<128>(g_xf + rb * 32, xbase + layer + 1, 0xAAAAu, rdy, lane);
            rdy = 0u;
            if (hal) src_wait<128>(g_xf + (rb - 1) * 32, xbase + layer + 1, 0xAAAAu, rdy, lane);
            const float2* sp = g_stats + ((epoch & 1) * 4 + layer) * S_ + m0 + lane;
            float2 u[5];
#pragma unroll
            for (int i = 0; i < 4; ++i) u[i] = __ldcg(sp + i * 32);
            u[4] = __ldcg(sp - (hal ? 16 : 0));
#pragma unroll 1
            for (int i = 0; i < 5; ++i) {
              const float mean = u[0].x * (1.f / D_);
              const float var = fmaxf(fmaf(-u[0].x, mean, u[0].y) * (1.f / D_), 0.f);
              const float sd = bf16r(sqrtf(bf16r(bf16r(var) + 1e-5f)));
              const int R = i * 32 + lane;
              if (i < 4) {
                const float hm = -0.5f * bf16r(mean);
                if (!isB) sts128(sb + SM_SD + R * 64 + ((R >> 1) & 3) * 16, make_uint4(__float_as_uint(sd) >> 16, 0u, 0u, 0u));
                sts128(sb + SM_AP + R * 16, make_uint4(pack_bf16(hm, hm), pack_bf16(hm, 0.f), 0u, 0u));
              }
              if (i < 4 || (hal && lane < 16)) sts_f(sb + SM_RS + (i < 4 ? 16 + R : lane) * 4, __fdividef(1.f, sd));
#pragma unroll
              for (int j = 0; j < 4; ++j) u[j] = u[j + 1];
            }
            PROFT(lane == 0, 64 + layer * 16 + 12);
          }
        }
        HLP_CTX();
        fence_async_smem();
        __syncwarp();
        if (lane == 0) mbar_arrive(BA(B_STAT));
        PROFT(lane == 0, 64 + layer * 16 + 14);
        if (!isB && lane == 0) {
#pragma unroll 1
          for (int hp = 0; hp < 2; ++hp) {
            mbar_wait(BA(B_KVDONE), hp);
            flag_wait(&g_kvflag[hp * 8 + g].v, epoch * (16u * ((NLAYERS + 1) / 2)) + 16u * ((layer >> 1) + 1));
            const float* kvl = g_kv + ((size_t)((epoch & 1) * 2 + (layer >> 1)) * 8 + g) * 8448;
            const uint32_t kb = BA(hp ? B_KVF1 : B_KVF);
            fence_async_all();
            mbar_expect_tx(kb, 16384 + 512);
            bulk_load(sb + VB + hp * SLOT, kvl + hp * 4096, 16384, kb);
            bulk_load(sb + SM_AP + hp * 512, kvl + 8192 + hp * 128, 512, kb);
            PROFT(hp == 0, 64 + layer * 16 + 15);
          }
        }
        __syncwarp();
      }
    }
    __syncwarp();
    asm volatile("barrier.cluster.arrive.relaxed.aligned;" ::: "memory");
    cluster_wait();
  } else {
    asm volatile("setmaxnreg.inc.sync.aligned.u32 232;");
    PROFT(threadIdx.x == 128, 235);
    cluster_wait();
    PROFT(threadIdx.x == 128, 236);
    consumer(c);
    asm volatile("bar.warp.sync 0xffffffff;\nbarrier.cluster.arrive.relaxed.aligned;\nbarrier.cluster.wait.aligned;\n" ::: "memory");
  }
}

typedef CUresult (*PFN_encodeTiled)(CUtensorMap*, CUtensorMapDataType, cuuint32_t, void*, const cuuint64_t*, const cuuint64_t*,
                                    const cuuint32_t*, const cuuint32_t*, CUtensorMapInterleave, CUtensorMapSwizzle,
                                    CUtensorMapL2promotion, CUtensorMapFloatOOBfill);

static void make_map2(PFN_encodeTiled enc, CUtensorMap* m, const void* ptr, uint64_t cols, uint64_t rows, uint32_t box_c, uint32_t box_r) {
  cuuint64_t dims[2] = {cols, rows};
  cuuint64_t strides[1] = {cols * 2};
  cuuint32_t box[2] = {box_c, box_r};
  cuuint32_t es[2] = {1, 1};
  CUresult r = enc(m, CU_TENSOR_MAP_DATA_TYPE_BFLOAT16, 2, const_cast<void*>(ptr), dims, strides, box, es, CU_TENSOR_MAP_INTERLEAVE_NONE,
                   box_c == 64 ? CU_TENSOR_MAP_SWIZZLE_128B : CU_TENSOR_MAP_SWIZZLE_64B, CU_TENSOR_MAP_L2_PROMOTION_L2_256B, CU_TENSOR_MAP_FLOAT_OOB_FILL_NONE);
  (void)r;
}
static void make_map5(PFN_encodeTiled enc, CUtensorMap* m, const void* ptr, uint64_t cols) {
  for (int p = 0; p < 2; ++p) {
    cuuint64_t dims[5] = {cols, 2, 4, 4, 32};
    cuuint64_t strides[4] = {cols * 2, cols * (p ? 16 : 4), cols * (p ? 4 : 16), cols * 64};
    cuuint32_t box[5] = {64, 2, 4, 4, 2};
    cuuint32_t es[5] = {1, 1, 1, 1, 1};
    CUresult r = enc(m + p, CU_TENSOR_MAP_DATA_TYPE_BFLOAT16, 5, const_cast<void*>(ptr), dims, strides, box, es, CU_TENSOR_MAP_INTERLEAVE_NONE,
                     CU_TENSOR_MAP_SWIZZLE_128B, CU_TENSOR_MAP_L2_PROMOTION_L2_256B, CU_TENSOR_MAP_FLOAT_OOB_FILL_NONE);
    (void)r;
  }
}

extern "C" void kernel_launch(void* const* d_in, const int* in_sizes, int n_in, void* d_out, int out_size) {
  const bf16* A_x = (const bf16*)d_in[0];
  const bf16* A_wqkv = (const bf16*)d_in[1];
  const bf16* A_wphi = (const bf16*)d_in[2];
  const bf16* A_wo = (const bf16*)d_in[3];
  const bf16* B_wqkv = (const bf16*)d_in[5];
  const bf16* B_wo = (const bf16*)d_in[6];
  bf16* out = (bf16*)d_out;

  static PFN_encodeTiled enc = nullptr;
  static bf16 *p_x, *p_o, *p_wf;
  static uint32_t boff;
  if (!enc) {
    void* fn = nullptr; cudaDriverEntryPointQueryResult qr;
    cudaGetDriverEntryPoint("cuTensorMapEncodeTiled", &fn, cudaEnableDefault, &qr);
    enc = (PFN_encodeTiled)fn;
    cudaGetSymbolAddress((void**)&p_x, g_x);
    cudaGetSymbolAddress((void**)&p_o, g_o);
    cudaGetSymbolAddress((void**)&p_wf, g_wf);
    cudaFuncSetAttribute(mega_kernel, cudaFuncAttributeMaxDynamicSharedMemorySize, SM_TOTAL);
    cudaLaunchConfig_t cfg = {};
    cudaLaunchAttribute at; at.id = cudaLaunchAttributeClusterDimension; at.val.clusterDim.x = 2; at.val.clusterDim.y = 1; at.val.clusterDim.z = 1;
    cfg.gridDim = dim3(132); cfg.blockDim = dim3(384); cfg.dynamicSmemBytes = SM_TOTAL; cfg.attrs = &at; cfg.numAttrs = 1;
    int nc = 0;
    if (cudaOccupancyMaxActiveClusters(&nc, mega_kernel, &cfg) != cudaSuccess) { nc = 0; (void)cudaGetLastError(); }
    boff = nc >= 66 ? 0u : 4u;
  }
  Maps maps;
  make_map5(enc, &maps.m[MAP_WF], p_wf, 2048);
  make_map5(enc, &maps.m[MAP_WA], A_wqkv, 3072);
  make_map5(enc, &maps.m[MAP_WB], B_wqkv, 3072);
  make_map5(enc, &maps.m[MAP_WOA], A_wo, 1024);
  make_map5(enc, &maps.m[MAP_WOB], B_wo, 1024);
  make_map2(enc, &maps.m[MAP_X0], A_x, 1024, 2048, 64, 128);
  make_map2(enc, &maps.m[MAP_X], p_x, 1024, 2048, 64, 128);
  make_map2(enc, &maps.m[MAP_O], p_o, 1024, 2048, 64, 128);
  make_map2(enc, &maps.m[MAP_PHI], A_wphi, 32, 1024, 32, 128);
  Ctx c; c.zero = 0u; c.boff = boff; c.x0 = A_x; c.out = out;
  mega_kernel<<<132, 384, SM_TOTAL, cudaStreamPerThread>>>(maps, c, A_wqkv, B_wqkv, A_wo, B_wo);
}
```

```cpp
#include <cuda_runtime.h>
#include <cuda_bf16.h>
#include <cuda.h>
#include <stdint.h>

typedef __nv_bfloat16 bf16;

constexpr int S_ = 2048, D_ = 1024;

struct __align__(128) Flag { unsigned int v; unsigned int pad[31]; };
__device__ __align__(1024) bf16 g_x[S_ * D_];
__device__ __align__(1024) bf16 g_o[S_ * D_];
__device__ __align__(1024) uint32_t g_halo[2 * 17 * 8 * 2048];
__device__ __align__(1024) float g_kv[2 * 2 * 8 * 8448];
__device__ __align__(1024) float2 g_stats[2 * 4 * S_];
__device__ __align__(1024) float g_cs[2 * 2 * 3072];
__device__ __align__(1024) bf16 g_wf[D_ * 2048];
__device__ Flag g_kvflag[16], g_csflag[13];
__device__ __align__(128) unsigned int g_xf[16 * 32], g_of[16 * 32];
__device__ __align__(128) unsigned int g_hf[16 * 32];
__device__ __align__(128) unsigned int g_wff[8 * 32];
__device__ unsigned int g_epoch, g_err;
#define PROFT(cond, idx) asm volatile("" ::: "memory")

__device__ __forceinline__ uint32_t smem_u32(const void* p) { return (uint32_t)__cvta_generic_to_shared(p); }
__device__ __forceinline__ void mbar_init(uint32_t bar, uint32_t count) {
  asm volatile("mbarrier.init.shared::cta.b64 [%0], %1;" ::"r"(bar), "r"(count) : "memory");
}
__device__ __forceinline__ void mbar_expect_tx(uint32_t bar, uint32_t bytes) {
  asm volatile("mbarrier.arrive.expect_tx.shared::cta.b64 _, [%0], %1;" ::"r"(bar), "r"(bytes) : "memory");
}
__device__ __forceinline__ void mbar_arrive(uint32_t bar) {
  asm volatile("mbarrier.arrive.shared::cta.b64 _, [%0];" ::"r"(bar) : "memory");
}
__device__ __forceinline__ bool mbar_try_wait(uint32_t bar, uint32_t parity) {
  uint32_t ok;
  asm volatile("{\n.reg .pred p;\nmbarrier.try_wait.parity.shared::cta.b64 p, [%1], %2;\nselp.b32 %0, 1, 0, p;\n}\n"
               : "=r"(ok) : "r"(bar), "r"(parity) : "memory");
  return ok != 0;
}
__device__ __forceinline__ bool mbar_test_wait(uint32_t bar, uint32_t parity) {
  uint32_t ok;
  asm volatile("{\n.reg .pred p;\nmbarrier.test_wait.parity.shared::cta.b64 p, [%1], %2;\nselp.b32 %0, 1, 0, p;\n}\n"
               : "=r"(ok) : "r"(bar), "r"(parity) : "memory");
  return ok != 0;
}
__device__ __forceinline__ uint64_t gtimer() {
  uint64_t t; asm volatile("mov.u64 %0, %globaltimer;" : "=l"(t)); return t;
}
__device__ __forceinline__ void mbar_wait(uint32_t bar, uint32_t parity) {
  uint32_t n = 0;
  bool ok;
#pragma unroll 1
  do { ++n; ok = mbar_try_wait(bar, parity); } while (!ok && n < (1u << 22));
}
__device__ __forceinline__ unsigned int ld_acquire(const unsigned int* p) {
  unsigned int v; asm volatile("ld.acquire.gpu.global.u32 %0, [%1];" : "=r"(v) : "l"(p) : "memory"); return v;
}
__device__ __forceinline__ void flag_add(unsigned int* p) {
  asm volatile("red.release.gpu.global.add.u32 [%0], 1;" ::"l"(p) : "memory");
}
__device__ __forceinline__ void flag_set(unsigned int* p, unsigned int v) {
  asm volatile("st.release.gpu.global.u32 [%0], %1;" ::"l"(p), "r"(v) : "memory");
}
template <int SLEEP>
__device__ __forceinline__ void src_wait(const unsigned int* f, unsigned int target, uint32_t need, uint32_t& ready, int lane) {
  uint32_t n = 0;
#pragma unroll 1
  while ((ready & need) != need) {
    const unsigned int v = ld_acquire(f + (lane & 15));
    ready = __ballot_sync(0xffffffffu, (int)(v - target) >= 0);
    if (SLEEP) { if ((ready & need) != need) __nanosleep(SLEEP); }
    if (++n > (1u << 20)) break;
  }
  __syncwarp();
}
__device__ __forceinline__ unsigned int ld_relaxed(const unsigned int* p);
__device__ __forceinline__ unsigned int ld_relaxed(const unsigned int* p) {
  unsigned int v; asm volatile("ld.relaxed.gpu.global.u32 %0, [%1];" : "=r"(v) : "l"(p) : "memory"); return v;
}
template <int SLEEP>
__device__ __forceinline__ void flag_wait_t(const unsigned int* p, unsigned int target) {
  uint32_t n = 0;
#pragma unroll 1
  while ((int)(ld_acquire(p) - target) < 0) {
    if (SLEEP) __nanosleep(SLEEP);
    if (++n > (1u << 20)) break;
  }
}
__device__ __forceinline__ void flag_wait(const unsigned int* p, unsigned int target) { flag_wait_t<0>(p, target); }
__device__ __forceinline__ void flag_wait_slow(const unsigned int* p, unsigned int target) { flag_wait_t<256>(p, target); }
__device__ __forceinline__ void mbar_wait_u(uint32_t bar, uint32_t parity) {
  uint32_t n = 0;
#pragma unroll 1
  while (!__all_sync(0xffffffffu, mbar_try_wait(bar, parity))) {
    if (++n > (1u << 22)) break;
  }
}
__device__ __forceinline__ void expect_tx_e(uint32_t bar, uint32_t bytes) {
  asm volatile("{\n.reg .pred p;\nelect.sync _|p, 0xffffffff;\n@p mbarrier.arrive.expect_tx.shared::cta.b64 _, [%0], %1;\n}\n" ::"r"(bar), "r"(bytes) : "memory");
}
__device__ __forceinline__ void tma_2d_e(uint32_t dst, const CUtensorMap* tm, int c0, int c1, uint32_t bar) {
  asm volatile("{\n.reg .pred p;\nelect.sync _|p, 0xffffffff;\n"
               "@p cp.async.bulk.tensor.2d.shared::cluster.global.mbarrier::complete_tx::bytes [%0], [%1, {%2, %3}], [%4];\n}\n"
               ::"r"(dst), "l"(tm), "r"(c0), "r"(c1), "r"(bar) : "memory");
}
__device__ __forceinline__ void tma_5d_e(uint32_t dst, const CUtensorMap* tm, int c0, int c4, uint32_t bar) {
  asm volatile("{\n.reg .pred p;\nelect.sync _|p, 0xffffffff;\n"
               "@p cp.async.bulk.tensor.5d.shared::cluster.global.mbarrier::complete_tx::bytes [%0], [%1, {%2, %5, %5, %5, %3}], [%4];\n}\n"
               ::"r"(dst), "l"(tm), "r"(c0), "r"(c4), "r"(bar), "r"(0) : "memory");
}
__device__ __forceinline__ void tma_5d_mc_e(uint32_t dst, const CUtensorMap* tm, int c0, int c4, uint32_t bar) {
  asm volatile("{\n.reg .pred p;\nelect.sync _|p, 0xffffffff;\n"
               "@p cp.async.bulk.tensor.5d.shared::cluster.global.mbarrier::complete_tx::bytes.multicast::cluster [%0], [%1, {%2, %6, %6, %6, %3}], [%4], %5;\n}\n"
               ::"r"(dst), "l"(tm), "r"(c0), "r"(c4), "r"(bar), "h"((uint16_t)3), "r"(0) : "memory");
}
__device__ __forceinline__ void wait_tma_5d_mc(bool w, uint32_t eb, uint32_t par, uint32_t dst, const CUtensorMap* tm, int c0, int c4, uint32_t fb) {
  asm volatile("" : "+r"(dst), "+l"(tm), "+r"(c0), "+r"(c4), "+r"(fb));
  if (w) mbar_wait_u(eb, par);
  tma_5d_mc_e(dst, tm, c0, c4, fb);
}
__device__ __forceinline__ void stg128(void* p, uint32_t a, uint32_t b, uint32_t c, uint32_t d) {
  asm volatile("st.global.v4.u32 [%0], {%1,%2,%3,%4};" ::"l"(p), "r"(a), "r"(b), "r"(c), "r"(d) : "memory");
}
__device__ __forceinline__ void stg128_p(bool on, void* p, uint32_t a, uint32_t b, uint32_t c, uint32_t d) {
  asm volatile("{\n.reg .pred p;\nsetp.ne.b32 p, %5, 0;\n@p st.global.v4.u32 [%0], {%1,%2,%3,%4};\n}\n" ::"l"(p), "r"(a), "r"(b), "r"(c), "r"(d), "r"((int)on) : "memory");
}
__device__ __forceinline__ void ldg128(const void* p, uint32_t& a, uint32_t& b, uint32_t& c, uint32_t& d) {
  asm volatile("ld.global.cg.v4.u32 {%0,%1,%2,%3}, [%4];" : "=r"(a), "=r"(b), "=r"(c), "=r"(d) : "l"(p) : "memory");
}
__device__ __forceinline__ void release2c(uint32_t off) {
  asm volatile("mbarrier.arrive.shared::cluster.b64 _, [%0];\nmbarrier.arrive.shared::cluster.b64 _, [%1];" ::"r"(off), "r"(off + (1u << 24)) : "memory");
}
__device__ __forceinline__ void tma_store_5d(const CUtensorMap* tm, uint32_t src, int c0, int c4) {
  asm volatile("cp.async.bulk.tensor.5d.global.shared::cta.bulk_group [%0, {%2, %4, %4, %4, %3}], [%1];"
               ::"l"(tm), "r"(src), "r"(c0), "r"(c4), "r"(0) : "memory");
}
__device__ __forceinline__ void bulk_load(uint32_t dst, const void* src, uint32_t bytes, uint32_t bar) {
  asm volatile("cp.async.bulk.shared::cluster.global.mbarrier::complete_tx::bytes [%0], [%1], %2, [%3];" ::"r"(dst), "l"(src), "r"(bytes), "r"(bar) : "memory");
}
__device__ __forceinline__ void bulk_red_add(void* dst, uint32_t src, uint32_t bytes) {
  asm volatile("cp.reduce.async.bulk.global.shared::cta.bulk_group.add.f32 [%0], [%1], %2;" ::"l"(dst), "r"(src), "r"(bytes) : "memory");
}
__device__ __forceinline__ void bulk_commit() { asm volatile("cp.async.bulk.commit_group;" ::: "memory"); }
__device__ __forceinline__ void bulk_wait0() { asm volatile("cp.async.bulk.wait_group 0;" ::: "memory"); }
__device__ __forceinline__ void fence_async_smem() { asm volatile("fence.proxy.async.shared::cta;" ::: "memory"); }
__device__ __forceinline__ void fence_async_all() { asm volatile("fence.proxy.async.global;" ::: "memory"); }
__device__ __forceinline__ void wgmma_fence() { asm volatile("wgmma.fence.sync.aligned;" ::: "memory"); }
__device__ __forceinline__ void wgmma_commit() { asm volatile("wgmma.commit_group.sync.aligned;" ::: "memory"); }
template <int N> __device__ __forceinline__ void wgmma_wait() { asm volatile("wgmma.wait_group.sync.aligned %0;" ::"n"(N) : "memory"); }
__device__ __forceinline__ void cluster_wait() { asm volatile("barrier.cluster.wait.acquire.aligned;" ::: "memory"); }
template <int ID, int N> __device__ __forceinline__ void nbar() { asm volatile("bar.sync %0, %1;" ::"n"(ID), "n"(N) : "memory"); }
__device__ __forceinline__ uint64_t desc64(uint32_t lo, uint32_t hi) { return (uint64_t)lo | ((uint64_t)hi << 32); }
__device__ __forceinline__ uint32_t pack_bf16(float lo, float hi) {
  uint32_t r; asm("cvt.rn.bf16x2.f32 %0, %1, %2;" : "=r"(r) : "f"(hi), "f"(lo)); return r;
}
__device__ __forceinline__ uint32_t add_bf16x2(uint32_t a, uint32_t b) {
  uint32_t r; asm("add.rn.bf16x2 %0, %1, %2;" : "=r"(r) : "r"(a), "r"(b)); return r;
}
__device__ __forceinline__ float bf16r(float x) { return __bfloat162float(__float2bfloat16_rn(x)); }
__device__ __forceinline__ float bf_lo(uint32_t u) { return __uint_as_float(u << 16); }
__device__ __forceinline__ float bf_hi(uint32_t u) { return __uint_as_float(u & 0xFFFF0000u); }
__device__ __forceinline__ float ex2(float x) { float r; asm("ex2.approx.ftz.f32 %0, %1;" : "=f"(r) : "f"(x)); return r; }
__device__ __forceinline__ float ex2v(float x) { float r; asm volatile("ex2.approx.ftz.f32 %0, %1;" : "=f"(r) : "f"(x) : "memory"); return r; }
__device__ __forceinline__ float rcp(float x) { float r; asm("rcp.approx.ftz.f32 %0, %1;" : "=f"(r) : "f"(x)); return r; }
__device__ __forceinline__ void mma_bf16(float (&d)[4], uint32_t a0, uint32_t a1, uint32_t a2, uint32_t a3, uint32_t b0, uint32_t b1) {
  asm("mma.sync.aligned.m16n8k16.row.col.f32.bf16.bf16.f32 {%0,%1,%2,%3}, {%4,%5,%6,%7}, {%8,%9}, {%0,%1,%2,%3};"
               : "+f"(d[0]), "+f"(d[1]), "+f"(d[2]), "+f"(d[3]) : "r"(a0), "r"(a1), "r"(a2), "r"(a3), "r"(b0), "r"(b1));
}
__device__ __forceinline__ void ldsm_x4(uint32_t& r0, uint32_t& r1, uint32_t& r2, uint32_t& r3, uint32_t addr) {
  asm volatile("ldmatrix.sync.aligned.m8n8.x4.shared.b16 {%0,%1,%2,%3}, [%4];"
               : "=r"(r0), "=r"(r1), "=r"(r2), "=r"(r3) : "r"(addr) : "memory");
}
__device__ __forceinline__ void ldsm_x4_t(uint32_t& r0, uint32_t& r1, uint32_t& r2, uint32_t& r3, uint32_t addr) {
  asm volatile("ldmatrix.sync.aligned.m8n8.x4.trans.shared.b16 {%0,%1,%2,%3}, [%4];"
               : "=r"(r0), "=r"(r1), "=r"(r2), "=r"(r3) : "r"(addr) : "memory");
}
__device__ __forceinline__ void stsm_x4(uint32_t addr, uint32_t r0, uint32_t r1, uint32_t r2, uint32_t r3) {
  asm volatile("stmatrix.sync.aligned.m8n8.x4.shared.b16 [%0], {%1,%2,%3,%4};"
               ::"r"(addr), "r"(r0), "r"(r1), "r"(r2), "r"(r3) : "memory");
}
__device__ __forceinline__ uint4 lds128(uint32_t addr) {
  uint4 v; asm volatile("ld.shared.v4.b32 {%0,%1,%2,%3}, [%4];" : "=r"(v.x), "=r"(v.y), "=r"(v.z), "=r"(v.w) : "r"(addr) : "memory"); return v;
}
__device__ __forceinline__ void sts128(uint32_t addr, uint4 v) {
  asm volatile("st.shared.v4.b32 [%0], {%1,%2,%3,%4};" ::"r"(addr), "r"(v.x), "r"(v.y), "r"(v.z), "r"(v.w) : "memory");
}
__device__ __forceinline__ float lds_f(uint32_t addr) {
  float v; asm volatile("ld.shared.f32 %0, [%1];" : "=f"(v) : "r"(addr) : "memory"); return v;
}
__device__ __forceinline__ void nbar_dyn(int id, int n) { asm volatile("bar.sync %0, %1;" ::"r"(id), "r"(n) : "memory"); }
__device__ __forceinline__ uint64_t make_desc_ns(uint32_t addr, uint32_t lbo_bytes, uint32_t sbo_bytes) {
  return (uint64_t)((addr & 0x3FFFF) >> 4) | ((uint64_t)(lbo_bytes >> 4) << 16) | ((uint64_t)(sbo_bytes >> 4) << 32);
}
__device__ __forceinline__ void sts_f(uint32_t addr, float v) { asm volatile("st.shared.f32 [%0], %1;" ::"r"(addr), "f"(v) : "memory"); }
__device__ __forceinline__ void sts64(uint32_t addr, uint32_t a, uint32_t b) {
  asm volatile("st.shared.v2.b32 [%0], {%1,%2};" ::"r"(addr), "r"(a), "r"(b) : "memory");
}
__device__ __forceinline__ void sts_f2(uint32_t addr, float a, float b) {
  asm volatile("st.shared.v2.f32 [%0], {%1,%2};" ::"r"(addr), "f"(a), "f"(b) : "memory");
}
__device__ __forceinline__ void red_add2_p(bool on, float* p, float a, float b) {
  asm volatile("{\n.reg .pred p;\nsetp.ne.b32 p, %3, 0;\n@p red.global.add.v2.f32 [%0], {%1,%2};\n}\n" ::"l"(p), "f"(a), "f"(b), "r"((int)on) : "memory");
}
__device__ __forceinline__ void red_add4(float* p, float a, float b, float c, float d) {
  asm volatile("red.global.add.v4.f32 [%0], {%1,%2,%3,%4};" ::"l"(p), "f"(a), "f"(b), "f"(c), "f"(d) : "memory");
}
__device__ __forceinline__ void red_add1(float* p, float a) {
  asm volatile("red.global.add.f32 [%0], %1;" ::"l"(p), "f"(a) : "memory");
}
__device__ __forceinline__ void l2_prefetch(const void* p, uint32_t bytes) {
  asm volatile("cp.async.bulk.prefetch.L2.global [%0], %1;" ::"l"(p), "r"(bytes) : "memory");
}

__device__ __forceinline__ void wgmma_n256(float (&d)[192], uint64_t da, uint64_t db, int scale_d) {
  asm volatile("{\n.reg .pred p;\nsetp.ne.b32 p, %130, 0;\n"
    "wgmma.mma_async.sync.aligned.m64n256k16.f32.bf16.bf16 {%0, %1, %2, %3, %4, %5, %6, %7, %8, %9, %10, %11, %12, %13, %14, %15, %16, %17, %18, %19, %20, %21, %22, %23, %24, %25, %26, %27, %28, %29, %30, %31, %32, %33, %34, %35, %36, %37, %38, %39, %40, %41, %42, %43, %44, %45, %46, %47, %48, %49, %50, %51, %52, %53, %54, %55, %56, %57, %58, %59, %60, %61, %62, %63, %64, %65, %66, %67, %68, %69, %70, %71, %72, %73, %74, %75, %76, %77, %78, %79, %80, %81, %82, %83, %84, %85, %86, %87, %88, %89, %90, %91, %92, %93, %94, %95, %96, %97, %98, %99, %100, %101, %102, %103, %104, %105, %106, %107, %108, %109, %110, %111, %112, %113, %114, %115, %116, %117, %118, %119, %120, %121, %122, %123, %124, %125, %126, %127}, %128, %129, p, 1, 1, 0, 1;\n}\n"
    : "+f"(d[0]), "+f"(d[1]), "+f"(d[2]), "+f"(d[3]), "+f"(d[4]), "+f"(d[5]), "+f"(d[6]), "+f"(d[7]), "+f"(d[8]), "+f"(d[9]), "+f"(d[10]), "+f"(d[11]), "+f"(d[12]), "+f"(d[13]), "+f"(d[14]), "+f"(d[15]), "+f"(d[16]), "+f"(d[17]), "+f"(d[18]), "+f"(d[19]), "+f"(d[20]), "+f"(d[21]), "+f"(d[22]), "+f"(d[23]), "+f"(d[24]), "+f"(d[25]), "+f"(d[26]), "+f"(d[27]), "+f"(d[28]), "+f"(d[29]), "+f"(d[30]), "+f"(d[31]), "+f"(d[32]), "+f"(d[33]), "+f"(d[34]), "+f"(d[35]), "+f"(d[36]), "+f"(d[37]), "+f"(d[38]), "+f"(d[39]), "+f"(d[40]), "+f"(d[41]), "+f"(d[42]), "+f"(d[43]), "+f"(d[44]), "+f"(d[45]), "+f"(d[46]), "+f"(d[47]), "+f"(d[48]), "+f"(d[49]), "+f"(d[50]), "+f"(d[51]), "+f"(d[52]), "+f"(d[53]), "+f"(d[54]), "+f"(d[55]), "+f"(d[56]), "+f"(d[57]), "+f"(d[58]), "+f"(d[59]), "+f"(d[60]), "+f"(d[61]), "+f"(d[62]), "+f"(d[63]), "+f"(d[64]), "+f"(d[65]), "+f"(d[66]), "+f"(d[67]), "+f"(d[68]), "+f"(d[69]), "+f"(d[70]), "+f"(d[71]), "+f"(d[72]), "+f"(d[73]), "+f"(d[74]), "+f"(d[75]), "+f"(d[76]), "+f"(d[77]), "+f"(d[78]), "+f"(d[79]), "+f"(d[80]), "+f"(d[81]), "+f"(d[82]), "+f"(d[83]), "+f"(d[84]), "+f"(d[85]), "+f"(d[86]), "+f"(d[87]), "+f"(d[88]), "+f"(d[89]), "+f"(d[90]), "+f"(d[91]), "+f"(d[92]), "+f"(d[93]), "+f"(d[94]), "+f"(d[95]), "+f"(d[96]), "+f"(d[97]), "+f"(d[98]), "+f"(d[99]), "+f"(d[100]), "+f"(d[101]), "+f"(d[102]), "+f"(d[103]), "+f"(d[104]), "+f"(d[105]), "+f"(d[106]), "+f"(d[107]), "+f"(d[108]), "+f"(d[109]), "+f"(d[110]), "+f"(d[111]), "+f"(d[112]), "+f"(d[113]), "+f"(d[114]), "+f"(d[115]), "+f"(d[116]), "+f"(d[117]), "+f"(d[118]), "+f"(d[119]), "+f"(d[120]), "+f"(d[121]), "+f"(d[122]), "+f"(d[123]), "+f"(d[124]), "+f"(d[125]), "+f"(d[126]), "+f"(d[127])
    : "l"(da), "l"(db), "r"(scale_d));
}
__device__ __forceinline__ void wgmma_n128(float (&d)[192], uint64_t da, uint64_t db, int scale_d) {
  asm volatile("{\n.reg .pred p;\nsetp.ne.b32 p, %66, 0;\n"
    "wgmma.mma_async.sync.aligned.m64n128k16.f32.bf16.bf16 {%0, %1, %2, %3, %4, %5, %6, %7, %8, %9, %10, %11, %12, %13, %14, %15, %16, %17, %18, %19, %20, %21, %22, %23, %24, %25, %26, %27, %28, %29, %30, %31, %32, %33, %34, %35, %36, %37, %38, %39, %40, %41, %42, %43, %44, %45, %46, %47, %48, %49, %50, %51, %52, %53, %54, %55, %56, %57, %58, %59, %60, %61, %62, %63}, %64, %65, p, 1, 1, 0, 1;\n}\n"
    : "+f"(d[128]), "+f"(d[129]), "+f"(d[130]), "+f"(d[131]), "+f"(d[132]), "+f"(d[133]), "+f"(d[134]), "+f"(d[135]), "+f"(d[136]), "+f"(d[137]), "+f"(d[138]), "+f"(d[139]), "+f"(d[140]), "+f"(d[141]), "+f"(d[142]), "+f"(d[143]), "+f"(d[144]), "+f"(d[145]), "+f"(d[146]), "+f"(d[147]), "+f"(d[148]), "+f"(d[149]), "+f"(d[150]), "+f"(d[151]), "+f"(d[152]), "+f"(d[153]), "+f"(d[154]), "+f"(d[155]), "+f"(d[156]), "+f"(d[157]), "+f"(d[158]), "+f"(d[159]), "+f"(d[160]), "+f"(d[161]), "+f"(d[162]), "+f"(d[163]), "+f"(d[164]), "+f"(d[165]), "+f"(d[166]), "+f"(d[167]), "+f"(d[168]), "+f"(d[169]), "+f"(d[170]), "+f"(d[171]), "+f"(d[172]), "+f"(d[173]), "+f"(d[174]), "+f"(d[175]), "+f"(d[176]), "+f"(d[177]), "+f"(d[178]), "+f"(d[179]), "+f"(d[180]), "+f"(d[181]), "+f"(d[182]), "+f"(d[183]), "+f"(d[184]), "+f"(d[185]), "+f"(d[186]), "+f"(d[187]), "+f"(d[188]), "+f"(d[189]), "+f"(d[190]), "+f"(d[191])
    : "l"(da), "l"(db), "r"(scale_d));
}
__device__ __forceinline__ void wgmma_n256_k(float (&d)[192], uint64_t da, uint64_t db, int scale_d) {
  asm volatile("{\n.reg .pred p;\nsetp.ne.b32 p, %130, 0;\n"
    "wgmma.mma_async.sync.aligned.m64n256k16.f32.bf16.bf16 {%0, %1, %2, %3, %4, %5, %6, %7, %8, %9, %10, %11, %12, %13, %14, %15, %16, %17, %18, %19, %20, %21, %22, %23, %24, %25, %26, %27, %28, %29, %30, %31, %32, %33, %34, %35, %36, %37, %38, %39, %40, %41, %42, %43, %44, %45, %46, %47, %48, %49, %50, %51, %52, %53, %54, %55, %56, %57, %58, %59, %60, %61, %62, %63, %64, %65, %66, %67, %68, %69, %70, %71, %72, %73, %74, %75, %76, %77, %78, %79, %80, %81, %82, %83, %84, %85, %86, %87, %88, %89, %90, %91, %92, %93, %94, %95, %96, %97, %98, %99, %100, %101, %102, %103, %104, %105, %106, %107, %108, %109, %110, %111, %112, %113, %114, %115, %116, %117, %118, %119, %120, %121, %122, %123, %124, %125, %126, %127}, %128, %129, p, 1, 1, 0, 0;\n}\n"
    : "+f"(d[0]), "+f"(d[1]), "+f"(d[2]), "+f"(d[3]), "+f"(d[4]), "+f"(d[5]), "+f"(d[6]), "+f"(d[7]), "+f"(d[8]), "+f"(d[9]), "+f"(d[10]), "+f"(d[11]), "+f"(d[12]), "+f"(d[13]), "+f"(d[14]), "+f"(d[15]), "+f"(d[16]), "+f"(d[17]), "+f"(d[18]), "+f"(d[19]), "+f"(d[20]), "+f"(d[21]), "+f"(d[22]), "+f"(d[23]), "+f"(d[24]), "+f"(d[25]), "+f"(d[26]), "+f"(d[27]), "+f"(d[28]), "+f"(d[29]), "+f"(d[30]), "+f"(d[31]), "+f"(d[32]), "+f"(d[33]), "+f"(d[34]), "+f"(d[35]), "+f"(d[36]), "+f"(d[37]), "+f"(d[38]), "+f"(d[39]), "+f"(d[40]), "+f"(d[41]), "+f"(d[42]), "+f"(d[43]), "+f"(d[44]), "+f"(d[45]), "+f"(d[46]), "+f"(d[47]), "+f"(d[48]), "+f"(d[49]), "+f"(d[50]), "+f"(d[51]), "+f"(d[52]), "+f"(d[53]), "+f"(d[54]), "+f"(d[55]), "+f"(d[56]), "+f"(d[57]), "+f"(d[58]), "+f"(d[59]), "+f"(d[60]), "+f"(d[61]), "+f"(d[62]), "+f"(d[63]), "+f"(d[64]), "+f"(d[65]), "+f"(d[66]), "+f"(d[67]), "+f"(d[68]), "+f"(d[69]), "+f"(d[70]), "+f"(d[71]), "+f"(d[72]), "+f"(d[73]), "+f"(d[74]), "+f"(d[75]), "+f"(d[76]), "+f"(d[77]), "+f"(d[78]), "+f"(d[79]), "+f"(d[80]), "+f"(d[81]), "+f"(d[82]), "+f"(d[83]), "+f"(d[84]), "+f"(d[85]), "+f"(d[86]), "+f"(d[87]), "+f"(d[88]), "+f"(d[89]), "+f"(d[90]), "+f"(d[91]), "+f"(d[92]), "+f"(d[93]), "+f"(d[94]), "+f"(d[95]), "+f"(d[96]), "+f"(d[97]), "+f"(d[98]), "+f"(d[99]), "+f"(d[100]), "+f"(d[101]), "+f"(d[102]), "+f"(d[103]), "+f"(d[104]), "+f"(d[105]), "+f"(d[106]), "+f"(d[107]), "+f"(d[108]), "+f"(d[109]), "+f"(d[110]), "+f"(d[111]), "+f"(d[112]), "+f"(d[113]), "+f"(d[114]), "+f"(d[115]), "+f"(d[116]), "+f"(d[117]), "+f"(d[118]), "+f"(d[119]), "+f"(d[120]), "+f"(d[121]), "+f"(d[122]), "+f"(d[123]), "+f"(d[124]), "+f"(d[125]), "+f"(d[126]), "+f"(d[127])
    : "l"(da), "l"(db), "r"(scale_d));
}
__device__ __forceinline__ void wgmma_n128_k(float (&d)[192], uint64_t da, uint64_t db, int scale_d) {
  asm volatile("{\n.reg .pred p;\nsetp.ne.b32 p, %66, 0;\n"
    "wgmma.mma_async.sync.aligned.m64n128k16.f32.bf16.bf16 {%0, %1, %2, %3, %4, %5, %6, %7, %8, %9, %10, %11, %12, %13, %14, %15, %16, %17, %18, %19, %20, %21, %22, %23, %24, %25, %26, %27, %28, %29, %30, %31, %32, %33, %34, %35, %36, %37, %38, %39, %40, %41, %42, %43, %44, %45, %46, %47, %48, %49, %50, %51, %52, %53, %54, %55, %56, %57, %58, %59, %60, %61, %62, %63}, %64, %65, p, 1, 1, 0, 0;\n}\n"
    : "+f"(d[128]), "+f"(d[129]), "+f"(d[130]), "+f"(d[131]), "+f"(d[132]), "+f"(d[133]), "+f"(d[134]), "+f"(d[135]), "+f"(d[136]), "+f"(d[137]), "+f"(d[138]), "+f"(d[139]), "+f"(d[140]), "+f"(d[141]), "+f"(d[142]), "+f"(d[143]), "+f"(d[144]), "+f"(d[145]), "+f"(d[146]), "+f"(d[147]), "+f"(d[148]), "+f"(d[149]), "+f"(d[150]), "+f"(d[151]), "+f"(d[152]), "+f"(d[153]), "+f"(d[154]), "+f"(d[155]), "+f"(d[156]), "+f"(d[157]), "+f"(d[158]), "+f"(d[159]), "+f"(d[160]), "+f"(d[161]), "+f"(d[162]), "+f"(d[163]), "+f"(d[164]), "+f"(d[165]), "+f"(d[166]), "+f"(d[167]), "+f"(d[168]), "+f"(d[169]), "+f"(d[170]), "+f"(d[171]), "+f"(d[172]), "+f"(d[173]), "+f"(d[174]), "+f"(d[175]), "+f"(d[176]), "+f"(d[177]), "+f"(d[178]), "+f"(d[179]), "+f"(d[180]), "+f"(d[181]), "+f"(d[182]), "+f"(d[183]), "+f"(d[184]), "+f"(d[185]), "+f"(d[186]), "+f"(d[187]), "+f"(d[188]), "+f"(d[189]), "+f"(d[190]), "+f"(d[191])
    : "l"(da), "l"(db), "r"(scale_d));
}
__device__ __forceinline__ void wgmma_n40_tt(float (&d)[20], uint64_t da, uint64_t db, int scale_d) {
  asm volatile("{\n.reg .pred p;\nsetp.ne.b32 p, %22, 0;\n"
    "wgmma.mma_async.sync.aligned.m64n40k16.f32.bf16.bf16 {%0, %1, %2, %3, %4, %5, %6, %7, %8, %9, %10, %11, %12, %13, %14, %15, %16, %17, %18, %19}, %20, %21, p, 1, 1, 1, 1;\n}\n"
    : "+f"(d[0]), "+f"(d[1]), "+f"(d[2]), "+f"(d[3]), "+f"(d[4]), "+f"(d[5]), "+f"(d[6]), "+f"(d[7]), "+f"(d[8]), "+f"(d[9]), "+f"(d[10]), "+f"(d[11]), "+f"(d[12]), "+f"(d[13]), "+f"(d[14]), "+f"(d[15]), "+f"(d[16]), "+f"(d[17]), "+f"(d[18]), "+f"(d[19])
    : "l"(da), "l"(db), "r"(scale_d));
}
__device__ __forceinline__ void wgmma_n40_rs(float (&d)[20], const uint32_t (&a)[4], uint64_t db, int scale_d) {
  asm volatile("{\n.reg .pred p;\nsetp.ne.b32 p, %25, 0;\n"
    "wgmma.mma_async.sync.aligned.m64n40k16.f32.bf16.bf16 {%0, %1, %2, %3, %4, %5, %6, %7, %8, %9, %10, %11, %12, %13, %14, %15, %16, %17, %18, %19}, {%20, %21, %22, %23}, %24, p, 1, 1, 1;\n}\n"
    : "+f"(d[0]), "+f"(d[1]), "+f"(d[2]), "+f"(d[3]), "+f"(d[4]), "+f"(d[5]), "+f"(d[6]), "+f"(d[7]), "+f"(d[8]), "+f"(d[9]), "+f"(d[10]), "+f"(d[11]), "+f"(d[12]), "+f"(d[13]), "+f"(d[14]), "+f"(d[15]), "+f"(d[16]), "+f"(d[17]), "+f"(d[18]), "+f"(d[19])
    : "r"(a[0]), "r"(a[1]), "r"(a[2]), "r"(a[3]), "l"(db), "r"(scale_d));
}
__device__ __forceinline__ void wgmma_n128_0(float (&d)[192], uint64_t da, uint64_t db) {
  asm volatile("{\n.reg .pred p;\nsetp.ne.b32 p, 0, 0;\n"
    "wgmma.mma_async.sync.aligned.m64n128k16.f32.bf16.bf16 {%0, %1, %2, %3, %4, %5, %6, %7, %8, %9, %10, %11, %12, %13, %14, %15, %16, %17, %18, %19, %20, %21, %22, %23, %24, %25, %26, %27, %28, %29, %30, %31, %32, %33, %34, %35, %36, %37, %38, %39, %40, %41, %42, %43, %44, %45, %46, %47, %48, %49, %50, %51, %52, %53, %54, %55, %56, %57, %58, %59, %60, %61, %62, %63}, %64, %65, p, 1, 1, 0, 1;\n}\n"
    : "=f"(d[128]), "=f"(d[129]), "=f"(d[130]), "=f"(d[131]), "=f"(d[132]), "=f"(d[133]), "=f"(d[134]), "=f"(d[135]), "=f"(d[136]), "=f"(d[137]), "=f"(d[138]), "=f"(d[139]), "=f"(d[140]), "=f"(d[141]), "=f"(d[142]), "=f"(d[143]), "=f"(d[144]), "=f"(d[145]), "=f"(d[146]), "=f"(d[147]), "=f"(d[148]), "=f"(d[149]), "=f"(d[150]), "=f"(d[151]), "=f"(d[152]), "=f"(d[153]), "=f"(d[154]), "=f"(d[155]), "=f"(d[156]), "=f"(d[157]), "=f"(d[158]), "=f"(d[159]), "=f"(d[160]), "=f"(d[161]), "=f"(d[162]), "=f"(d[163]), "=f"(d[164]), "=f"(d[165]), "=f"(d[166]), "=f"(d[167]), "=f"(d[168]), "=f"(d[169]), "=f"(d[170]), "=f"(d[171]), "=f"(d[172]), "=f"(d[173]), "=f"(d[174]), "=f"(d[175]), "=f"(d[176]), "=f"(d[177]), "=f"(d[178]), "=f"(d[179]), "=f"(d[180]), "=f"(d[181]), "=f"(d[182]), "=f"(d[183]), "=f"(d[184]), "=f"(d[185]), "=f"(d[186]), "=f"(d[187]), "=f"(d[188]), "=f"(d[189]), "=f"(d[190]), "=f"(d[191])
    : "l"(da), "l"(db));
}
__device__ __forceinline__ void wgmma_n128_rs(float (&d)[192], const uint32_t (&a)[4], uint64_t db, int scale_d) {
  asm volatile("{\n.reg .pred p;\nsetp.ne.b32 p, %69, 0;\n"
    "wgmma.mma_async.sync.aligned.m64n128k16.f32.bf16.bf16 {%0, %1, %2, %3, %4, %5, %6, %7, %8, %9, %10, %11, %12, %13, %14, %15, %16, %17, %18, %19, %20, %21, %22, %23, %24, %25, %26, %27, %28, %29, %30, %31, %32, %33, %34, %35, %36, %37, %38, %39, %40, %41, %42, %43, %44, %45, %46, %47, %48, %49, %50, %51, %52, %53, %54, %55, %56, %57, %58, %59, %60, %61, %62, %63}, {%64, %65, %66, %67}, %68, p, 1, 1, 1;\n}\n"
    : "+f"(d[128]), "+f"(d[129]), "+f"(d[130]), "+f"(d[131]), "+f"(d[132]), "+f"(d[133]), "+f"(d[134]), "+f"(d[135]), "+f"(d[136]), "+f"(d[137]), "+f"(d[138]), "+f"(d[139]), "+f"(d[140]), "+f"(d[141]), "+f"(d[142]), "+f"(d[143]), "+f"(d[144]), "+f"(d[145]), "+f"(d[146]), "+f"(d[147]), "+f"(d[148]), "+f"(d[149]), "+f"(d[150]), "+f"(d[151]), "+f"(d[152]), "+f"(d[153]), "+f"(d[154]), "+f"(d[155]), "+f"(d[156]), "+f"(d[157]), "+f"(d[158]), "+f"(d[159]), "+f"(d[160]), "+f"(d[161]), "+f"(d[162]), "+f"(d[163]), "+f"(d[164]), "+f"(d[165]), "+f"(d[166]), "+f"(d[167]), "+f"(d[168]), "+f"(d[169]), "+f"(d[170]), "+f"(d[171]), "+f"(d[172]), "+f"(d[173]), "+f"(d[174]), "+f"(d[175]), "+f"(d[176]), "+f"(d[177]), "+f"(d[178]), "+f"(d[179]), "+f"(d[180]), "+f"(d[181]), "+f"(d[182]), "+f"(d[183]), "+f"(d[184]), "+f"(d[185]), "+f"(d[186]), "+f"(d[187]), "+f"(d[188]), "+f"(d[189]), "+f"(d[190]), "+f"(d[191])
    : "r"(a[0]), "r"(a[1]), "r"(a[2]), "r"(a[3]), "l"(db), "r"(scale_d));
}
__device__ __forceinline__ void wgmma_n32_0(float (&d)[16], uint64_t da, uint64_t db) {
  asm volatile("{\n.reg .pred p;\nsetp.ne.b32 p, 0, 0;\n"
    "wgmma.mma_async.sync.aligned.m64n32k16.f32.bf16.bf16 {%0, %1, %2, %3, %4, %5, %6, %7, %8, %9, %10, %11, %12, %13, %14, %15}, %16, %17, p, 1, 1, 0, 1;\n}\n"
    : "=f"(d[0]), "=f"(d[1]), "=f"(d[2]), "=f"(d[3]), "=f"(d[4]), "=f"(d[5]), "=f"(d[6]), "=f"(d[7]), "=f"(d[8]), "=f"(d[9]), "=f"(d[10]), "=f"(d[11]), "=f"(d[12]), "=f"(d[13]), "=f"(d[14]), "=f"(d[15])
    : "l"(da), "l"(db));
}
__device__ __forceinline__ void wgmma_n32(float (&d)[16], uint64_t da, uint64_t db, int scale_d) {
  asm volatile("{\n.reg .pred p;\nsetp.ne.b32 p, %18, 0;\n"
    "wgmma.mma_async.sync.aligned.m64n32k16.f32.bf16.bf16 {%0, %1, %2, %3, %4, %5, %6, %7, %8, %9, %10, %11, %12, %13, %14, %15}, %16, %17, p, 1, 1, 0, 1;\n}\n"
    : "+f"(d[0]), "+f"(d[1]), "+f"(d[2]), "+f"(d[3]), "+f"(d[4]), "+f"(d[5]), "+f"(d[6]), "+f"(d[7]), "+f"(d[8]), "+f"(d[9]), "+f"(d[10]), "+f"(d[11]), "+f"(d[12]), "+f"(d[13]), "+f"(d[14]), "+f"(d[15])
    : "l"(da), "l"(db), "r"(scale_d));
}
__device__ __forceinline__ void wgmma_n8_t(float (&d)[4], uint64_t da, uint64_t db, int scale_d) {
  asm volatile("{\n.reg .pred p;\nsetp.ne.b32 p, %6, 0;\n"
    "wgmma.mma_async.sync.aligned.m64n8k16.f32.bf16.bf16 {%0, %1, %2, %3}, %4, %5, p, 1, 1, 1, 0;\n}\n"
    : "+f"(d[0]), "+f"(d[1]), "+f"(d[2]), "+f"(d[3])
    : "l"(da), "l"(db), "r"(scale_d));
}
__device__ __forceinline__ void wgmma_n128_rs0(float (&d)[192], const uint32_t (&a)[4], uint64_t db) {
  asm volatile("{\n.reg .pred p;\nsetp.ne.b32 p, 0, 0;\n"
    "wgmma.mma_async.sync.aligned.m64n128k16.f32.bf16.bf16 {%0, %1, %2, %3, %4, %5, %6, %7, %8, %9, %10, %11, %12, %13, %14, %15, %16, %17, %18, %19, %20, %21, %22, %23, %24, %25, %26, %27, %28, %29, %30, %31, %32, %33, %34, %35, %36, %37, %38, %39, %40, %41, %42, %43, %44, %45, %46, %47, %48, %49, %50, %51, %52, %53, %54, %55, %56, %57, %58, %59, %60, %61, %62, %63}, {%64, %65, %66, %67}, %68, p, 1, 1, 1;\n}\n"
    : "=f"(d[128]), "=f"(d[129]), "=f"(d[130]), "=f"(d[131]), "=f"(d[132]), "=f"(d[133]), "=f"(d[134]), "=f"(d[135]), "=f"(d[136]), "=f"(d[137]), "=f"(d[138]), "=f"(d[139]), "=f"(d[140]), "=f"(d[141]), "=f"(d[142]), "=f"(d[143]), "=f"(d[144]), "=f"(d[145]), "=f"(d[146]), "=f"(d[147]), "=f"(d[148]), "=f"(d[149]), "=f"(d[150]), "=f"(d[151]), "=f"(d[152]), "=f"(d[153]), "=f"(d[154]), "=f"(d[155]), "=f"(d[156]), "=f"(d[157]), "=f"(d[158]), "=f"(d[159]), "=f"(d[160]), "=f"(d[161]), "=f"(d[162]), "=f"(d[163]), "=f"(d[164]), "=f"(d[165]), "=f"(d[166]), "=f"(d[167]), "=f"(d[168]), "=f"(d[169]), "=f"(d[170]), "=f"(d[171]), "=f"(d[172]), "=f"(d[173]), "=f"(d[174]), "=f"(d[175]), "=f"(d[176]), "=f"(d[177]), "=f"(d[178]), "=f"(d[179]), "=f"(d[180]), "=f"(d[181]), "=f"(d[182]), "=f"(d[183]), "=f"(d[184]), "=f"(d[185]), "=f"(d[186]), "=f"(d[187]), "=f"(d[188]), "=f"(d[189]), "=f"(d[190]), "=f"(d[191])
    : "r"(a[0]), "r"(a[1]), "r"(a[2]), "r"(a[3]), "l"(db));
}
__device__ __forceinline__ void wgmma_n256_rs(float (&d)[192], const uint32_t (&a)[4], uint64_t db, int scale_d) {
  asm volatile("{\n.reg .pred p;\nsetp.ne.b32 p, %133, 0;\n"
    "wgmma.mma_async.sync.aligned.m64n256k16.f32.bf16.bf16 {%0, %1, %2, %3, %4, %5, %6, %7, %8, %9, %10, %11, %12, %13, %14, %15, %16, %17, %18, %19, %20, %21, %22, %23, %24, %25, %26, %27, %28, %29, %30, %31, %32, %33, %34, %35, %36, %37, %38, %39, %40, %41, %42, %43, %44, %45, %46, %47, %48, %49, %50, %51, %52, %53, %54, %55, %56, %57, %58, %59, %60, %61, %62, %63, %64, %65, %66, %67, %68, %69, %70, %71, %72, %73, %74, %75, %76, %77, %78, %79, %80, %81, %82, %83, %84, %85, %86, %87, %88, %89, %90, %91, %92, %93, %94, %95, %96, %97, %98, %99, %100, %101, %102, %103, %104, %105, %106, %107, %108, %109, %110, %111, %112, %113, %114, %115, %116, %117, %118, %119, %120, %121, %122, %123, %124, %125, %126, %127}, {%128, %129, %130, %131}, %132, p, 1, 1, 1;\n}\n"
    : "+f"(d[0]), "+f"(d[1]), "+f"(d[2]), "+f"(d[3]), "+f"(d[4]), "+f"(d[5]), "+f"(d[6]), "+f"(d[7]), "+f"(d[8]), "+f"(d[9]), "+f"(d[10]), "+f"(d[11]), "+f"(d[12]), "+f"(d[13]), "+f"(d[14]), "+f"(d[15]), "+f"(d[16]), "+f"(d[17]), "+f"(d[18]), "+f"(d[19]), "+f"(d[20]), "+f"(d[21]), "+f"(d[22]), "+f"(d[23]), "+f"(d[24]), "+f"(d[25]), "+f"(d[26]), "+f"(d[27]), "+f"(d[28]), "+f"(d[29]), "+f"(d[30]), "+f"(d[31]), "+f"(d[32]), "+f"(d[33]), "+f"(d[34]), "+f"(d[35]), "+f"(d[36]), "+f"(d[37]), "+f"(d[38]), "+f"(d[39]), "+f"(d[40]), "+f"(d[41]), "+f"(d[42]), "+f"(d[43]), "+f"(d[44]), "+f"(d[45]), "+f"(d[46]), "+f"(d[47]), "+f"(d[48]), "+f"(d[49]), "+f"(d[50]), "+f"(d[51]), "+f"(d[52]), "+f"(d[53]), "+f"(d[54]), "+f"(d[55]), "+f"(d[56]), "+f"(d[57]), "+f"(d[58]), "+f"(d[59]), "+f"(d[60]), "+f"(d[61]), "+f"(d[62]), "+f"(d[63]), "+f"(d[64]), "+f"(d[65]), "+f"(d[66]), "+f"(d[67]), "+f"(d[68]), "+f"(d[69]), "+f"(d[70]), "+f"(d[71]), "+f"(d[72]), "+f"(d[73]), "+f"(d[74]), "+f"(d[75]), "+f"(d[76]), "+f"(d[77]), "+f"(d[78]), "+f"(d[79]), "+f"(d[80]), "+f"(d[81]), "+f"(d[82]), "+f"(d[83]), "+f"(d[84]), "+f"(d[85]), "+f"(d[86]), "+f"(d[87]), "+f"(d[88]), "+f"(d[89]), "+f"(d[90]), "+f"(d[91]), "+f"(d[92]), "+f"(d[93]), "+f"(d[94]), "+f"(d[95]), "+f"(d[96]), "+f"(d[97]), "+f"(d[98]), "+f"(d[99]), "+f"(d[100]), "+f"(d[101]), "+f"(d[102]), "+f"(d[103]), "+f"(d[104]), "+f"(d[105]), "+f"(d[106]), "+f"(d[107]), "+f"(d[108]), "+f"(d[109]), "+f"(d[110]), "+f"(d[111]), "+f"(d[112]), "+f"(d[113]), "+f"(d[114]), "+f"(d[115]), "+f"(d[116]), "+f"(d[117]), "+f"(d[118]), "+f"(d[119]), "+f"(d[120]), "+f"(d[121]), "+f"(d[122]), "+f"(d[123]), "+f"(d[124]), "+f"(d[125]), "+f"(d[126]), "+f"(d[127])
    : "r"(a[0]), "r"(a[1]), "r"(a[2]), "r"(a[3]), "l"(db), "r"(scale_d));
}
__device__ __forceinline__ void wgmma_n256_rs0(float (&d)[192], const uint32_t (&a)[4], uint64_t db) {
  asm volatile("{\n.reg .pred p;\nsetp.ne.b32 p, 0, 0;\n"
    "wgmma.mma_async.sync.aligned.m64n256k16.f32.bf16.bf16 {%0, %1, %2, %3, %4, %5, %6, %7, %8, %9, %10, %11, %12, %13, %14, %15, %16, %17, %18, %19, %20, %21, %22, %23, %24, %25, %26, %27, %28, %29, %30, %31, %32, %33, %34, %35, %36, %37, %38, %39, %40, %41, %42, %43, %44, %45, %46, %47, %48, %49, %50, %51, %52, %53, %54, %55, %56, %57, %58, %59, %60, %61, %62, %63, %64, %65, %66, %67, %68, %69, %70, %71, %72, %73, %74, %75, %76, %77, %78, %79, %80, %81, %82, %83, %84, %85, %86, %87, %88, %89, %90, %91, %92, %93, %94, %95, %96, %97, %98, %99, %100, %101, %102, %103, %104, %105, %106, %107, %108, %109, %110, %111, %112, %113, %114, %115, %116, %117, %118, %119, %120, %121, %122, %123, %124, %125, %126, %127}, {%128, %129, %130, %131}, %132, p, 1, 1, 1;\n}\n"
    : "=f"(d[0]), "=f"(d[1]), "=f"(d[2]), "=f"(d[3]), "=f"(d[4]), "=f"(d[5]), "=f"(d[6]), "=f"(d[7]), "=f"(d[8]), "=f"(d[9]), "=f"(d[10]), "=f"(d[11]), "=f"(d[12]), "=f"(d[13]), "=f"(d[14]), "=f"(d[15]), "=f"(d[16]), "=f"(d[17]), "=f"(d[18]), "=f"(d[19]), "=f"(d[20]), "=f"(d[21]), "=f"(d[22]), "=f"(d[23]), "=f"(d[24]), "=f"(d[25]), "=f"(d[26]), "=f"(d[27]), "=f"(d[28]), "=f"(d[29]), "=f"(d[30]), "=f"(d[31]), "=f"(d[32]), "=f"(d[33]), "=f"(d[34]), "=f"(d[35]), "=f"(d[36]), "=f"(d[37]), "=f"(d[38]), "=f"(d[39]), "=f"(d[40]), "=f"(d[41]), "=f"(d[42]), "=f"(d[43]), "=f"(d[44]), "=f"(d[45]), "=f"(d[46]), "=f"(d[47]), "=f"(d[48]), "=f"(d[49]), "=f"(d[50]), "=f"(d[51]), "=f"(d[52]), "=f"(d[53]), "=f"(d[54]), "=f"(d[55]), "=f"(d[56]), "=f"(d[57]), "=f"(d[58]), "=f"(d[59]), "=f"(d[60]), "=f"(d[61]), "=f"(d[62]), "=f"(d[63]), "=f"(d[64]), "=f"(d[65]), "=f"(d[66]), "=f"(d[67]), "=f"(d[68]), "=f"(d[69]), "=f"(d[70]), "=f"(d[71]), "=f"(d[72]), "=f"(d[73]), "=f"(d[74]), "=f"(d[75]), "=f"(d[76]), "=f"(d[77]), "=f"(d[78]), "=f"(d[79]), "=f"(d[80]), "=f"(d[81]), "=f"(d[82]), "=f"(d[83]), "=f"(d[84]), "=f"(d[85]), "=f"(d[86]), "=f"(d[87]), "=f"(d[88]), "=f"(d[89]), "=f"(d[90]), "=f"(d[91]), "=f"(d[92]), "=f"(d[93]), "=f"(d[94]), "=f"(d[95]), "=f"(d[96]), "=f"(d[97]), "=f"(d[98]), "=f"(d[99]), "=f"(d[100]), "=f"(d[101]), "=f"(d[102]), "=f"(d[103]), "=f"(d[104]), "=f"(d[105]), "=f"(d[106]), "=f"(d[107]), "=f"(d[108]), "=f"(d[109]), "=f"(d[110]), "=f"(d[111]), "=f"(d[112]), "=f"(d[113]), "=f"(d[114]), "=f"(d[115]), "=f"(d[116]), "=f"(d[117]), "=f"(d[118]), "=f"(d[119]), "=f"(d[120]), "=f"(d[121]), "=f"(d[122]), "=f"(d[123]), "=f"(d[124]), "=f"(d[125]), "=f"(d[126]), "=f"(d[127])
    : "r"(a[0]), "r"(a[1]), "r"(a[2]), "r"(a[3]), "l"(db));
}

constexpr int SLOT = 16384;
constexpr int VB = 4 * SLOT, PH = 0, XS = 6;
constexpr int SM_SD = 13 * SLOT;
constexpr int SM_BAR = SM_SD + 8192;
constexpr int SM_RS = SM_BAR + 1024;
constexpr int SM_AP = SM_RS + 640;
constexpr int SM_BP = SM_AP + 2048;
constexpr int SM_EPOCH = SM_BP + 6144;
constexpr int SM_TOTAL = SM_EPOCH + 16;
constexpr int FM = 0, FT = 16, FW = 30, CM = 46, CT = 62, CW = 76, B_EF = 92, B_STAT = 93, B_KVF = 94, B_HALO = 95,
              B_KVDONE = 96, B_OH0 = 97, B_OH1 = 98, B_XH0 = 99, B_XDONE = 100, B_WFD = 101, B_XT = 102, B_OF0 = 103, B_KVF1 = 104, B_KVS = 105, B_RAW = 106  , B_X0 = 108, B_KVS0 = 109;
constexpr uint64_t BAR_LG = 0x00043333330004ull;
#define BA(i) (bar + (i) * 8)
#define REL2(i) release2c(SB0 + SM_BAR + (i) * 8)
constexpr int NF = 3, ND = 13, NR = 0, NWOP = 48, NAOP = 38;
constexpr bool EF_USED = false;
constexpr uint64_t TL_A = 0x6278627862786ull, TL_B = 0xa9c3ba9c3ba9cull, WO_A = 0x76b24038b51403ffull, WO_B = 0x8c5a197c6a297c8bull;
__constant__ uint32_t c_wop[NWOP + 1] = {0xeb0009, 0x186b8000, 0x6c0112, 0x1aec011a, 0x6c8224, 0x22ec822b, 0x18170330, 0x18178442, 0x18180554, 0x18188660, 0x18190772, 0x18198884, 0x181a0990, 0x181a8aa2, 0x181b0bb4, 0x181b8cc0, 0xaed10fc, 0xa9711e9, 0x181c0dd2, 0xa9792da, 0x129813cb, 0x181c8ee4, 0x181d0ff0, 0x109d94b3, 0x109f15ac, 0x109f9699, 0x10a0178a, 0x10a0987b, 0x10a11963, 0x10a19a5c, 0x10a21b49, 0x10a29c3a, 0x9231e0b, 0x9239f18, 0x1124202c, 0x13242137, 0x1124a249, 0x1324a352, 0x1125246a, 0x13252576, 0x1127268c, 0x1127a797, 0x112828a9, 0x1128a9b1, 0x11292aca, 0x13292bd5, 0x112a2cec, 0x132a2df8, 0};
__constant__ uint32_t c_aop[NAOP + 1] = {0x6d8228, 0x170336, 0x178447, 0x180558, 0x188666, 0x190777, 0x198888, 0x1a0996, 0x1a8aa7, 0x1b0bb8, 0x1b8cc6, 0x1c0dd7, 0x1c8ee8, 0x1d0ff6, 0x1d93c2, 0x1f14b6, 0x1f95a8, 0x201697, 0x209782, 0x211876, 0x219968, 0x221a57, 0x229b42, 0x231c36, 0xa3a023, 0xb12130, 0x2b12244, 0x2b12351, 0x2b12465, 0xa6257b, 0xa6a688, 0xa72793, 0xa7a8a0, 0xa829b4, 0xa8aac2, 0xa9abdb, 0x2a9ace6, 0xaaadf7, 0};
__constant__ uint32_t c_map[64] = {4, 5, 6, 7, 0, 16, 32, 48, 64, 80, 96, 112, 1, 17, 33, 49, 65, 81, 97, 113, 2, 18, 34, 50, 66, 82, 98, 114, 3, 19, 35, 51, 67, 83, 99, 115, 20, 36, 52, 68, 84, 100, 116, 21, 37, 53, 69, 85, 101, 117, 22, 38, 54, 70, 86, 102, 118, 23, 39, 55, 71, 87, 103, 119};
enum { MAP_WF = 0, MAP_WA = 2, MAP_WB = 4, MAP_WOA = 6, MAP_WOB = 8, MAP_X0 = 10, MAP_X = 11, MAP_O = 12, MAP_PHI = 13, NMAP = 14 };
struct Maps { CUtensorMap m[NMAP]; };

#define PL 2
#define PROFL(a, b)
#define SUBS 8
#define QORD 1
#define NCH 4
#define CHW 1
#define SUBS1 12
#define XRAT 10
#define XRN 4
#define BT1 1
#define CV0 0
#define ST1 8
#define X0AT 1
#define W1DL 400
#define SKA 0
#define SKB 0
#define BPRE 0
#define XST 3
#define WH 4
#define NLAYERS 4
constexpr float L2E = 1.4426950408889634f;

#define D128(lo) desc64(lo, 0x40000040u)
struct Ctx { uint32_t zero, boff; const bf16* x0; bf16* out; };
#define BLK_CTX() \
  uint32_t bid_; asm volatile("mov.u32 %0, %%ctaid.x;" : "=r"(bid_)); \
  bid_ -= c.boff; \
  const uint32_t gr_ = c_map[bid_ >> 1]; \
  const int cr = bid_ & 1, g = gr_ & 7, rb = (gr_ >> 3) + cr, m0 = rb * 128; \
  const uint32_t sb = SB0 + (cr << 24); \
  const uint32_t bar = sb + SM_BAR; \
  (void)cr; (void)g; (void)rb; (void)m0; (void)bar;
extern __shared__ uint8_t smem_raw[];
constexpr uint32_t SB0 = 1024;

#define PHASE_CTX() \
  BLK_CTX(); \
  int tid_ = threadIdx.x; asm volatile("" : "+r"(tid_)); \
  const int lane = tid_ & 31, cw = (tid_ >> 5) - 4, wg = cw >> 2, wq = cw & 3, gq = lane >> 2, t = lane & 3, wrow0 = cw * 16; \
  const int lrow = (lane & 7) + ((lane >> 3) & 1) * 8, lchk = lane >> 4; \
  const bool elected = (tid_ & 127) == 0; \
  const uint32_t rowo = (wrow0 + lrow) * 128, X = (lchk ^ (lane & 7)) << 4; \
  const uint32_t Y = (wrow0 + (lane & 7)) * 128 + (((lane >> 3) ^ (lane & 7)) << 4); \
  const size_t gfr = (size_t)(m0 + wrow0 + gq) * D_ + g * 128 + 8 * t; \
  (void)bar; (void)wq; (void)gq; (void)lrow; (void)lchk; (void)elected; (void)wrow0; (void)wg; (void)rowo; (void)X; (void)t; (void)Y; (void)gfr;
#define MMA_CTX() \
  const uint32_t wu = __shfl_sync(0xffffffffu, wg, 0); \
  const uint32_t dA0 = ((SB0 >> 4) | (1u << 16)) + wu * 512, dB0 = (SB0 >> 4) | (512u << 16); \
  const uint32_t par = layer & 1;

__device__ __forceinline__ void slab_out_half(uint32_t slot, bf16* dst, int wrow0, int lane) {
  const int r0 = lane >> 3, ch = lane & 7;
  const uint32_t src = slot + (wrow0 + r0) * 128;
  uint4 v[4];
#pragma unroll
  for (int i = 0; i < 4; ++i) v[i] = lds128(src + i * 512 + (((ch ^ (4 * i + r0)) & 7) << 4));
  dst += (size_t)(wrow0 + r0) * D_ + ch * 8;
#pragma unroll
  for (int i = 0; i < 4; ++i) *reinterpret_cast<uint4*>(dst + (size_t)i * 4 * D_) = v[i];
}

__device__ __forceinline__ void consumer(const Ctx& c) {
  float acc[192];
  uint32_t xf[4][4];
  uint32_t xp[8][4];
  {
    PHASE_CTX();
    const unsigned int epoch = ld_relaxed(&g_epoch);
    PROFT(tid_ == 128, 0);
    const uint32_t wu = __shfl_sync(0xffffffffu, wg, 0);
    if (tid_ < 128 + 8) sts128(sb + SM_AP + lane * 16, make_uint4(0x3F803F80u, 0x3F803F80u, 0x3F803F80u, 0x3F803F80u));
#pragma unroll 1
    for (int it = 0; it < 2; ++it) {
      float p[4][16];
      mbar_wait(BA(B_RAW + it), 0);
      PROFT(tid_ == 128, it ? 15 : 2);
      const uint32_t da = ((SB0 >> 4) | (1u << 16)) + (wu ? 9 + it : 2 * it) * 1024, db = (SB0 + SM_SD) >> 4;
      wgmma_fence();
#pragma unroll
      for (int h = 0; h < 4; ++h) wgmma_n32_0(p[h], D128(da + (h >> 1) * 512 + (h & 1) * 4), desc64(db + h * 128, 0x80000020u));
#pragma unroll
      for (int h = 0; h < 4; ++h) wgmma_n32(p[h], D128(da + (h >> 1) * 512 + (h & 1) * 4 + 2), desc64(db + h * 128 + 64, 0x80000020u), 1);
      wgmma_commit();
      wgmma_wait<0>();
#pragma unroll
      for (int i = 0; i < 64; ++i) asm volatile("" : "+f"(p[i >> 4][i & 15]) :: "memory");
      const uint32_t base = sb + (wg ? 9 + it : 2 * it) * SLOT + (wq * 16 + gq) * 128;
      uint32_t w[4][4][2];
#pragma unroll
      for (int i = 0; i < 32; ++i) w[i >> 3][(i >> 1) & 3][i & 1] = pack_bf16(p[i >> 3][2 * (i & 7)], p[i >> 3][2 * (i & 7) + 1]);
      if (wu) {
#pragma unroll
        for (int i = 0; i < 8; ++i)
          sts128(base + (i >> 2) * 8192 + (i & 1) * 1024 + (((((i >> 1) & 1) * 4 + t) ^ gq) << 4), make_uint4(w[i >> 1][0][i & 1], w[i >> 1][1][i & 1], w[i >> 1][2][i & 1], w[i >> 1][3][i & 1]));
      } else {
#pragma unroll
        for (int i = 0; i < 16; ++i)
          sts64(base + (i >> 3) * 8192 + (i & 1) * 1024 + ((((t & 1) * 4 + ((i >> 1) & 3)) ^ gq) << 4) + (t >> 1) * 8, w[(i >> 3) * 2][(i >> 1) & 3][i & 1], w[(i >> 3) * 2 + 1][(i >> 1) & 3][i & 1]);
      }
      fence_async_smem();
      __syncwarp();
      if (it == cr && lane == 0) mbar_arrive(BA(B_WFD));
    }
    if (tid_ == 128) sts_f(sb + SM_EPOCH, __uint_as_float(epoch & 1));
#pragma unroll
    for (int i = 0; i < 32; ++i) xp[i >> 2][i & 3] = 0u;
    nbar<1, 256>();
    PROFT(tid_ == 128, 13);
    mbar_wait(BA(FM + cr), 0);
    float cs[3][4];
    wgmma_fence();
#pragma unroll
    for (int ks = 0; ks < 4; ++ks)
#pragma unroll
      for (int i = 0; i < 3; ++i) {
        const uint32_t bx = (i == 0 ? 2 * cr * 1024 : i == 1 ? (2 * cr + 1) * 1024 : (9 + cr) * 1024) + wu * 512;
        wgmma_n8_t(cs[i], D128(((SB0 >> 4) | (512u << 16)) + bx + ks * 128), desc64((SB0 + SM_AP) >> 4, 0), ks != 0);
      }
    wgmma_commit();
    mbar_wait(BA(FM), 0);
#pragma unroll
    for (int k = 0; k < 4; ++k) ldsm_x4(xf[k][0], xf[k][1], xf[k][2], xf[k][3], sb + XS * SLOT + rowo + (X ^ (k << 5)));
    wgmma_wait<0>();
#pragma unroll
    for (int i = 0; i < 12; ++i) asm volatile("" : "+f"(cs[i >> 2][i & 3]) :: "memory");
    if (t < 2) {
#pragma unroll
      for (int i = 0; i < 3; ++i) red_add1(g_cs + (epoch & 1) * 6144 + g * 384 + i * 128 + wg * 64 + wq * 16 + gq + t * 8, t ? cs[i][2] : cs[i][0]);
    }
    PROFT(tid_ == 128, 14);
  }
#pragma unroll 1
  for (int layer = 0;; ++layer) {
    {
      wgmma_fence();
      wgmma_n256_rs0(acc, xf[0], D128((SB0 >> 4) | (512u << 16)));
#pragma unroll
      for (int k = 1; k < 4; ++k) wgmma_n256_rs(acc, xf[k], D128(((SB0 >> 4) | (512u << 16)) + k * 128), 1);
      wgmma_commit();
      PHASE_CTX();
      MMA_CTX();
      {
        const uint32_t ep = __float_as_uint(lds_f(sb + SM_EPOCH));
        if (layer == 0) {
          mbar_wait(BA(B_X0), 0);
#pragma unroll
          for (int i = 0; i < 8; ++i) ldsm_x4(xp[i][0], xp[i][1], xp[i][2], xp[i][3], sb + (11 + (i >> 2)) * SLOT + (Y ^ ((i & 2) << 5)) + (i & 1) * 1024);
          if (lane == ((xp[0][0] ^ xp[1][0] ^ xp[2][0] ^ xp[3][0] ^ xp[7][0]) & c.zero)) REL2(B_XT);
        } else {
#pragma unroll
          for (int i = 0; i < 8; ++i) stsm_x4(sb + (XS + (i >> 2)) * SLOT + (Y ^ ((i & 2) << 5)) + (i & 1) * 1024, xp[i][0], xp[i][1], xp[i][2], xp[i][3]);
        }
        float s0 = 0.f, s1 = 0.f, q0 = 0.f, q1 = 0.f;
        auto stats = [&](int j0, int j1) {
#pragma unroll
          for (int j = j0; j < j1; ++j) {
            const uint32_t u0 = xp[(j >> 2) * 2][j & 3], u1 = xp[(j >> 2) * 2 + 1][j & 3];
            s0 += bf_lo(u0) + bf_hi(u0); s1 += bf_lo(u1) + bf_hi(u1);
            q0 = fmaf(bf_lo(u0), bf_lo(u0), fmaf(bf_hi(u0), bf_hi(u0), q0)); q1 = fmaf(bf_lo(u1), bf_lo(u1), fmaf(bf_hi(u1), bf_hi(u1), q1));
          }
        };
        stats(0, ST1);
        fence_async_smem();
        nbar_dyn(3 + wu + (__float_as_uint(s0 + s1 + q0 + q1) & c.zero), 128);
        mbar_wait(BA(FM + 1), par);
        wgmma_fence();
#pragma unroll
        for (int k = 0; k < 4; ++k) wgmma_n256(acc, D128(dA0 + (XS + 1) * 1024 + k * 2), D128(dB0 + 2048 + k * 128), 1);
        wgmma_commit();
        wgmma_wait<1>();
#pragma unroll
        for (int i = 4; i < 8; ++i) stg128_p(layer, g_x + gfr + (i & 1) * 8 * D_ + (i >> 1) * 32, xp[i][0], xp[i][1], xp[i][2], xp[i][3]);
        {
          uint32_t zc; asm volatile("mov.u32 %0, %%clock;" : "=r"(zc) :: "memory");
          q0 += __uint_as_float(zc & c.zero); q1 += __uint_as_float(zc & c.zero); s0 += __uint_as_float(zc & c.zero); s1 += __uint_as_float(zc & c.zero);
        }
        stats(ST1, 16);
        wgmma_fence();
        wgmma_n128_0(acc, D128(dA0 + XS * 1024), D128(dB0 + 9 * 1024));
#pragma unroll
        for (int k = 1; k < 4; ++k) wgmma_n128(acc, D128(dA0 + XS * 1024 + k * 2), D128(dB0 + 9 * 1024 + k * 128), 1);
        wgmma_commit();
        const bool od = t & 1;
        float sa = od ? s1 : s0, qa = od ? q1 : q0;
        sa += __shfl_xor_sync(0xffffffffu, od ? s0 : s1, 1);
        qa += __shfl_xor_sync(0xffffffffu, od ? q0 : q1, 1);
        wgmma_fence();
#pragma unroll
        for (int k = 0; k < 4; ++k) wgmma_n128(acc, D128(dA0 + (XS + 1) * 1024 + k * 2), D128(dB0 + 10 * 1024 + k * 128), 1);
        wgmma_commit();
        sa += __shfl_xor_sync(0xffffffffu, sa, 2);
        qa += __shfl_xor_sync(0xffffffffu, qa, 2);
        red_add2_p(t < 2, reinterpret_cast<float*>(g_stats + (ep * 4 + layer) * S_ + m0 + wrow0 + gq + t * 8), sa, qa);
        __syncwarp();
        if (lane == 0) mbar_arrive(BA(B_XDONE));
        wgmma_wait<1>();
        if (elected) REL2(CM);
      }
      uint32_t s = 2;
#pragma unroll 1
      for (int i = 2; i < NF; ++i) {
        PROFL(tid_ == 128 && layer == PL + 1, 244 + 2 * i);
        mbar_wait(BA(FM + i), par);
        PROFL(tid_ == 128 && layer == PL + 1, 245 + 2 * i);
        const uint32_t da = dA0 + (XS + s) * 1024, dk = dB0 + s * 2048, dq = dB0 + (9 + s) * 1024;
        wgmma_fence();
#pragma unroll
        for (int k = 0; k < 4; ++k) wgmma_n128(acc, D128(da + k * 2), D128(dq + k * 128), 1);
        wgmma_commit();
        wgmma_wait<1>();
        if (elected) REL2(CM + i - 1);
        wgmma_fence();
#pragma unroll
        for (int k = 0; k < 4; ++k) wgmma_n256(acc, D128(da + k * 2), D128(dk + k * 128), 1);
        wgmma_commit();
        if (++s == 3) s = 0;
      }
#pragma unroll 1
      for (int i = NF; i < 15; ++i) {
        mbar_wait(BA(FM + i), par);
        const uint32_t da = dA0 + (XS + s) * 1024, dk = dB0 + s * 2048;
        wgmma_fence();
#pragma unroll
        for (int k = 0; k < 4; ++k) wgmma_n256(acc, D128(da + k * 2), D128(dk + k * 128), 1);
        wgmma_commit();
        wgmma_wait<1>();
        if (elected) REL2(CM + i - 1);
        if (++s == 3) s = 0;
      }
      {
        const uint64_t dap = desc64(((SB0 + SM_AP) >> 4) + wu * 64, 8), dbp = make_desc_ns(SB0 + SM_BP, 0, 128);
        mbar_wait(BA(B_STAT), par);
        mbar_wait(BA(FM + 15), par);
        PROFT(tid_ == 128, layer * 16 + 9);
        wgmma_fence();
        wgmma_n256_k(acc, dap, dbp, 1);
#pragma unroll
        for (int k = 0; k < 4; ++k) wgmma_n256(acc, D128(dA0 + XS * 1024 + k * 2), D128(dB0 + k * 128), 1);
        wgmma_commit();
        wgmma_wait<1>();
        if (elected) REL2(CM + 14);
        mbar_wait(BA(FT), par);
        wgmma_fence();
        wgmma_n128_k(acc, dap, dbp + 256, 1);
#pragma unroll
        for (int k = 0; k < 4; ++k) wgmma_n128(acc, D128(dA0 + (uint32_t)(TL_A & 15) * 1024 + k * 2), D128(dB0 + (uint32_t)(TL_B & 15) * 1024 + k * 128), 1);
        wgmma_commit();
        wgmma_wait<1>();
        if (elected) REL2(CM + 15);
#pragma unroll
        for (int i = 0; i < 128; ++i) asm volatile("" : "+f"(acc[i]) :: "memory");
      }
    }
    uint32_t of[8][4], o1[4][4];
    {
      PHASE_CTX();
      MMA_CTX();
      PROFT(tid_ == 128, layer * 16 + 1);
      PROFT(lane == 0 && layer == PL, 192 + cw);
      PROFT(tid_ == 128 && layer == PL, 160);
      uint64_t ta = (TL_A >> 4), tw = TL_B >> 4;
      uint32_t da, db, dz = dA0;
      auto sub = [&](int n) {
        const int j = n >> 2, k = n & 3;
        if (k == 0) {
          dz += c.zero;
          da = dz + ((uint32_t)ta & 15) * 1024; db = dB0 + ((uint32_t)tw & 15) * 1024;
          ta >>= 4; tw >>= 4;
          mbar_wait(BA(FT + j), par);
          wgmma_fence();
        }
        wgmma_n128(acc, D128(da + k * 2), D128(db + k * 128), 1);
        if (k == 3) {
          wgmma_commit();
          wgmma_wait<1>();
          if (elected) REL2(CT + j - 1);
        }
      };
      auto run = [&](int j0, int j1) {
#pragma unroll 1
        for (int j = j0; j < j1; ++j) {
          mbar_wait(BA(FT + j), par);
          da = dA0 + ((uint32_t)ta & 15) * 1024; db = dB0 + ((uint32_t)tw & 15) * 1024;
          ta >>= 4; tw >>= 4;
          wgmma_fence();
#pragma unroll
          for (int k = 0; k < 4; ++k) wgmma_n128(acc, D128(da + k * 2), D128(db + k * 128), 1);
          wgmma_commit();
          wgmma_wait<1>();
          if (elected) REL2(CT + j - 1);
        }
        ta = TL_A >> (4 * j1); tw = TL_B >> (4 * j1);
      };
      auto rest = [&](int j0, int sk) {
        if (sk) {
          run(j0, ND - sk);
          if (wu == 0) nbar<6, 256>();
          j0 = ND - sk;
        }
        run(j0, ND);
        if (sk && wu) asm volatile("bar.arrive 6, 256;" ::: "memory");
      };
      auto rest_end = [&]() {
        wgmma_wait<0>();
        if (elected) REL2(CT + ND - 1);
#pragma unroll
        for (int i = 128; i < 192; ++i) asm volatile("" : "+f"(acc[i]) :: "memory");
      };
      auto wo0 = [&]() {
        wgmma_fence();
        wgmma_n128_rs0(acc, of[0], D128(dB0 + (uint32_t)(WO_B & 15) * 1024));
#pragma unroll
        for (int k = 1; k < 4; ++k) wgmma_n128_rs(acc, of[k], D128(dB0 + (uint32_t)(WO_B & 15) * 1024 + k * 128), 1);
        wgmma_commit();
      };
      const float rs0 = lds_f(sb + SM_RS + (16 + wrow0 + gq) * 4), rs1 = lds_f(sb + SM_RS + (24 + wrow0 + gq) * 4);
#define EPOCH() __float_as_uint(lds_f(sb + SM_EPOCH))
      mbar_wait(BA(CM + 14), par);
      if (par) {
        uint32_t kk[8][4], kp[8][4], vf[2][2][4][4];
        int sn = 4;
#pragma unroll
        for (int i = 0; i < 4 * BT1; ++i) sub(sn++);
        {
          uint32_t vv[8][4];
#pragma unroll
          for (int jp = 0; jp < 8; ++jp) {
            kk[jp][0] = pack_bf16(acc[8 * jp], acc[8 * jp + 1]); kk[jp][1] = pack_bf16(acc[8 * jp + 4], acc[8 * jp + 5]);
            kk[jp][2] = pack_bf16(acc[8 * jp + 2], acc[8 * jp + 3]); kk[jp][3] = pack_bf16(acc[8 * jp + 6], acc[8 * jp + 7]);
#pragma unroll
            for (int i = 0; i < 4; ++i) vv[jp][i] = pack_bf16(acc[64 + 8 * jp + 2 * i], acc[65 + 8 * jp + 2 * i]);
          }
          if (cw == 7) {
            uint32_t* const hbuf = g_halo + (size_t)(((layer >> 1) * 17 + rb + 1) * 8 + g) * 2048;
#pragma unroll
            for (int jp = 0; jp < 8; ++jp) stg128(hbuf + jp * 128 + lane * 4, kk[jp][0], kk[jp][1], kk[jp][2], kk[jp][3]);
#pragma unroll
            for (int i = 0; i < 32; ++i) hbuf[1024 + (i >> 4) * 512 + (gq + (i & 1) * 8) * 32 + ((((i >> 1) & 7) ^ gq) << 2) + t] = vv[i >> 2][i & 3];
            __syncwarp();
            if (lane == 0) mbar_arrive(BA(B_OF0));
          }
#pragma unroll
          for (int jp = 0; jp < 8; ++jp) {
            sub(sn++);
            stsm_x4(sb + VB + (jp >> 2) * SLOT + rowo + (X ^ ((jp & 3) << 5)), vv[jp][0], vv[jp][1], vv[jp][2], vv[jp][3]);
          }
        }
        PROFT(tid_ == 128, layer * 16 + 2);
        const int e = gq & 1;
        float f0[4], f1[4], b0[4], b1[4], rj[4];
#pragma unroll
        for (int nt = 0; nt < 4; ++nt) {
          const int kx = nt * 8 + 2 * t + e;
          const bool okk = (m0 + wrow0 + kx) >= 16;
          const int d0 = kx - gq, d1 = d0 - 8;
          rj[nt] = lds_f(sb + SM_RS + (wrow0 + kx) * 4);
          const bool m0_ = okk && d0 >= 2 && d0 <= 16, m1_ = okk && d1 >= 2 && d1 <= 16;
          f0[nt] = m0_ ? rj[nt] * rs0 * (0.17677669529663687f * L2E) : 0.f;
          f1[nt] = m1_ ? rj[nt] * rs1 * (0.17677669529663687f * L2E) : 0.f;
          b0[nt] = m0_ ? 0.f : -1e30f; b1[nt] = m1_ ? 0.f : -1e30f;
        }
        mbar_wait(BA(CM + 15), par);
#pragma unroll
        for (int jp = 0; jp < 8; ++jp) {
          sub(sn++);
          sts128(sb + PH + cw * 4096 + jp * 512 + lane * 16, make_uint4(kk[jp][0], kk[jp][1], kk[jp][2], kk[jp][3]));
        }
#pragma unroll
        for (int i = 0; i < 4; ++i) sub(sn++);
        nbar<1, 256>();
        PROFT(tid_ == 128, layer * 16 + 3);
        rest(sn >> 2, SKB);
        if (!BPRE) rest_end();
        PROFT(lane == 0 && layer == PL, 200 + cw);
        PROFT(tid_ == 128, layer * 16 + 10);
        if (cw == 0) mbar_wait(BA(B_HALO), (layer >> 1) & 1);
        PROFT(tid_ == 128, layer * 16 + 5);
        const uint32_t vs = sb + (cw ? VB + rowo - 2048 : SM_SD + 4096 + rowo), vst = cw ? SLOT : 2048;
        const uint32_t psel = e ? 0x1054u : 0x5410u;
#pragma unroll
        for (int hp = 0; hp < 2; ++hp) {
#pragma unroll
          for (int i = 4 * hp; i < 4 * hp + 4; ++i) {
            const uint4 u = lds128(sb + (cw ? PH + (cw - 1) * 4096 : SM_SD) + lane * 16 + i * 512);
            kp[i][0] = u.x; kp[i][1] = u.y; kp[i][2] = u.z; kp[i][3] = u.w;
          }
#pragma unroll
          for (int i = 4 * hp; i < 4 * hp + 4; ++i) {
            ldsm_x4_t(vf[0][i & 1][i >> 1][0], vf[0][i & 1][i >> 1][1], vf[0][i & 1][i >> 1][2], vf[0][i & 1][i >> 1][3], vs + (i >> 2) * vst + (X ^ ((i & 3) << 5)));
            ldsm_x4_t(vf[1][i & 1][i >> 1][0], vf[1][i & 1][i >> 1][1], vf[1][i & 1][i >> 1][2], vf[1][i & 1][i >> 1][3], sb + VB + (i >> 2) * SLOT + rowo + (X ^ ((i & 3) << 5)));
          }
          if (BPRE && !hp) rest_end();
          float l0[2][4], l1[2][4];
#pragma unroll
          for (int h = 0; h < 2; ++h) {
            const int H = 2 * hp + h;
            uint32_t qa[8];
#pragma unroll
            for (int i = 0; i < 8; ++i) qa[i] = pack_bf16(acc[128 + 16 * H + 2 * i], acc[129 + 16 * H + 2 * i]);
#pragma unroll
            for (int nt = 3; nt >= 0; --nt) {
              float sc[4] = {0.f, 0.f, 0.f, 0.f};
#pragma unroll
              for (int ks = 0; ks < 2; ++ks) {
                const uint32_t (&kf)[4] = nt < 2 ? kp[2 * H + ks] : kk[2 * H + ks];
                mma_bf16(sc, qa[4 * ks], qa[4 * ks + 1], qa[4 * ks + 2], qa[4 * ks + 3], kf[2 * (nt & 1)], kf[2 * (nt & 1) + 1]);
              }
              l0[h][nt] = fmaf(e ? sc[1] : sc[0], f0[nt], b0[nt]);
              l1[h][nt] = fmaf(e ? sc[3] : sc[2], f1[nt], b1[nt]);
            }
          }
          float mx0[2], mx1[2], s0[2], s1[2];
#pragma unroll
          for (int h = 0; h < 2; ++h) {
            mx0[h] = fmaxf(fmaxf(l0[h][0], l0[h][1]), l0[h][2]);
            mx1[h] = fmaxf(fmaxf(l1[h][1], l1[h][2]), l1[h][3]);
          }
#pragma unroll
          for (int o = 1; o <= 2; o <<= 1)
#pragma unroll
            for (int h = 0; h < 2; ++h) {
              mx0[h] = fmaxf(mx0[h], __shfl_xor_sync(0xffffffffu, mx0[h], o));
              mx1[h] = fmaxf(mx1[h], __shfl_xor_sync(0xffffffffu, mx1[h], o));
            }
#pragma unroll
          for (int h = 0; h < 2; ++h) {
#pragma unroll
            for (int nt = 0; nt < 3; ++nt) { l0[h][nt] = ex2(l0[h][nt] - mx0[h]); l1[h][nt + 1] = ex2(l1[h][nt + 1] - mx1[h]); }
            s0[h] = (l0[h][0] + l0[h][1]) + l0[h][2];
            s1[h] = (l1[h][1] + l1[h][2]) + l1[h][3];
          }
#pragma unroll
          for (int o = 1; o <= 2; o <<= 1)
#pragma unroll
            for (int h = 0; h < 2; ++h) {
              s0[h] += __shfl_xor_sync(0xffffffffu, s0[h], o);
              s1[h] += __shfl_xor_sync(0xffffffffu, s1[h], o);
            }
          uint32_t ow[2][2][4];
#pragma unroll
          for (int h = 0; h < 2; ++h) {
            const int H = 2 * hp + h;
            uint32_t pl[4], ph[4];
            const float i0 = rcp(s0[h]), i1 = rcp(s1[h]);
#pragma unroll
            for (int nt = 0; nt < 4; ++nt) {
              const uint32_t pk = pack_bf16(nt < 3 ? l0[h][nt] * i0 * rj[nt] : 0.f, nt > 0 ? l1[h][nt] * i1 * rj[nt] : 0.f);
              pl[nt] = nt < 3 ? __byte_perm(pk, 0u, psel) : 0u;
              ph[nt] = nt > 0 ? __byte_perm(pk, 0u, psel + 0x2222u) : 0u;
            }
#pragma unroll
            for (int nj = 0; nj < 4; ++nj) {
              float oa[4] = {0.f, 0.f, 0.f, 0.f};
#pragma unroll
              for (int ks = 0; ks < 2; ++ks)
                mma_bf16(oa, pl[2 * ks], ph[2 * ks], pl[2 * ks + 1], ph[2 * ks + 1], vf[ks][nj >> 1][H][2 * (nj & 1)], vf[ks][nj >> 1][H][2 * (nj & 1) + 1]);
              ow[h][0][nj] = pack_bf16(oa[0], oa[1]); ow[h][1][nj] = pack_bf16(oa[2], oa[3]);
            }
          }
          if (hp == 0) {
#pragma unroll
            for (int i = 0; i < 4; ++i) stg128(g_o + gfr + (i & 1) * 8 * D_ + (i >> 1) * 32, ow[i >> 1][i & 1][0], ow[i >> 1][i & 1][1], ow[i >> 1][i & 1][2], ow[i >> 1][i & 1][3]);
            __syncwarp();
            if (lane == 0) mbar_arrive(BA(B_OH0));
          } else {
#pragma unroll
            for (int i = 0; i < 16; ++i) o1[i >> 2][i & 3] = ow[i >> 3][(i >> 2) & 1][i & 3];
          }
#pragma unroll
          for (int i = 0; i < 16; ++i) of[4 * hp + (i >> 2)][i & 3] = ow[i >> 3][i & 1][(i >> 1) & 3];
          if (!hp) { PROFT(tid_ == 128, layer * 16 + 15); mbar_wait(BA(FW), par); }
        }
      } else {
        float sc[2] = {rs0 * L2E, rs1 * L2E};
        {
          const uint32_t vb = sb + VB + (rowo >> 1), X0 = (lchk ^ ((lane & 7) >> 1)) << 4;
          const uint32_t pb = sb + PH + (t & 1) * SLOT + (wrow0 + gq) * 128 + ((((t & 1) * 4 + (t & 2)) ^ gq) << 4);
          float kva[20], en[32], mx[2][2], mn[2][2];
#define PV(hp, j) acc[32 * (hp) + (j)]
          auto mm = [&](int hp, int j) {
            const int r = (j >> 1) & 1;
            if (j < 4 && !(j & 1)) { mx[hp][r] = PV(hp, j); mn[hp][r] = PV(hp, j); }
            else { mx[hp][r] = fmaxf(mx[hp][r], PV(hp, j)); mn[hp][r] = fminf(mn[hp][r], PV(hp, j)); }
          };
          auto mmx = [&](int hp) {
#pragma unroll
            for (int r = 0; r < 2; ++r) {
              mx[hp][r] = fmaxf(mx[hp][r], __shfl_xor_sync(0xffffffffu, mx[hp][r], 2)) * -sc[r];
              mn[hp][r] = fmaf(fminf(mn[hp][r], __shfl_xor_sync(0xffffffffu, mn[hp][r], 2)), sc[r], mx[hp][r]);
            }
          };
          auto stage = [&](int hp) {
#pragma unroll
            for (int i = 0; i < 20; ++i) asm volatile("" : "+f"(kva[i]) :: "memory");
            nbar_dyn(3 + wu, 128);
#pragma unroll
            for (int i = 0; i < 4; ++i)
              sts128(sb + VB + hp * SLOT + wg * 8192 + (wq * 128 + i * 32 + lane) * 16,
                     make_uint4(__float_as_uint(kva[4 * i]), __float_as_uint(kva[4 * i + 1]), __float_as_uint(kva[4 * i + 2]), __float_as_uint(kva[4 * i + 3])));
            if (t == 0) sts_f2(sb + SM_AP + ((2 * hp + wg) * 64 + wq * 16 + gq * 2) * 4, kva[16], kva[18]);
            fence_async_smem();
            __syncwarp();
            if (lane == 0) mbar_arrive(BA(B_KVDONE));
          };
          int sn = 4;
#pragma unroll
          for (int j = 0; j < 32; ++j) mm(0, j);
          mmx(0);
#pragma unroll
          for (int hp = 0; hp < 2; ++hp) {
            float sp[2] = {0.f, 0.f}, sm[2] = {0.f, 0.f};
#pragma unroll
            for (int j = 0; j < 32; ++j) {
              const int r = (j >> 1) & 1, ns = hp ? SUBS1 : SUBS;
              if ((j * ns) / 32 != ((j + 1) * ns) / 32) {
                sub(sn++);
                if (hp && sn == 4 + SUBS + 4 + 4 * (XST & 1)) { stage(0); PROFT(tid_ == 128, layer * 16 + 12); }
              }
              const float x = fmaf(PV(hp, j), sc[r], mx[hp][r]);
              PV(hp, j) = ex2(x); en[j] = ex2(mn[hp][r] - x);
              sp[r] += PV(hp, j); sm[r] += en[j];
              if (hp == 0) {
                mm(1, j);
                if ((j & 3) == 0) {
                  const int jp = 8 + (j >> 2);
                  stsm_x4(vb + ((jp - 8) >> 1) * 8192 + (X0 ^ ((jp & 1) << 5)), pack_bf16(acc[8 * jp], acc[8 * jp + 1]), pack_bf16(acc[8 * jp + 2], acc[8 * jp + 3]),
                          pack_bf16(acc[8 * jp + 4], acc[8 * jp + 5]), pack_bf16(acc[8 * jp + 6], acc[8 * jp + 7]));
                }
              }
            }
#pragma unroll
            for (int i = 0; i < 4; ++i) if (XST & (1 << hp)) sub(sn++);
#pragma unroll
            for (int r = 0; r < 2; ++r) {
              sp[r] = rcp(sp[r] + __shfl_xor_sync(0xffffffffu, sp[r], 2)) * (r ? rs1 : rs0);
              sm[r] = rcp(sm[r] + __shfl_xor_sync(0xffffffffu, sm[r], 2)) * (r ? rs1 : rs0);
            }
            if (hp == 0) { mmx(1); mbar_wait(BA(CM + 15), par); }
            else { PROFT(tid_ == 128, layer * 16 + 11); nbar<1, 256>(); }
#pragma unroll
            for (int i = 0; i < 4; ++i) {
              const int r = i & 1, d = 16 * (i >> 1) + 2 * r;
              sts128((pb + r * 1024) ^ ((i >> 1) << 4), make_uint4(pack_bf16(PV(hp, d) * sp[r], PV(hp, d + 1) * sp[r]), pack_bf16(PV(hp, d + 4) * sp[r], PV(hp, d + 5) * sp[r]),
                                                                    pack_bf16(PV(hp, d + 8) * sp[r], PV(hp, d + 9) * sp[r]), pack_bf16(PV(hp, d + 12) * sp[r], PV(hp, d + 13) * sp[r])));
              sts128((pb + r * 1024) ^ ((i >> 1) << 4) ^ 64, make_uint4(pack_bf16(en[d] * sm[r], en[d + 1] * sm[r]), pack_bf16(en[d + 4] * sm[r], en[d + 5] * sm[r]),
                                                                         pack_bf16(en[d + 8] * sm[r], en[d + 9] * sm[r]), pack_bf16(en[d + 12] * sm[r], en[d + 13] * sm[r])));
            }
            fence_async_smem();
            nbar<1, 256>();
            const uint32_t dP = dB0 + (PH >> 4) + wu * 1024;
            const uint32_t dV = (dB0 & 0xFFFFu) + ((VB + hp * SLOT) >> 4) + (((SM_SD - VB - hp * SLOT) >> 4) << 16) + wu * (512u - (512u << 16));
            wgmma_fence();
#pragma unroll
            for (int ks = 0; ks < 8; ++ks) wgmma_n40_tt(kva, D128(dP + ks * 128), desc64(dV + ks * 64, 0x80000020u), ks != 0);
            wgmma_commit();
          }
#pragma unroll
          for (int i = 0; i < 4; ++i) sub(sn++);
          stage(1);
          PROFT(tid_ == 128, layer * 16 + 3);
          rest(sn >> 2, SKA);
          rest_end();
          PROFT(lane == 0 && layer == PL, 200 + cw);
          PROFT(tid_ == 128, layer * 16 + 10);
        }
#define QV(H, i) acc[128 + 16 * (H) + (i)]
        float mx[4][2], mn[4][2];
        uint32_t ph[4][4][4];
        auto mnx = [&](int hp) {
#pragma unroll
          for (int H = 2 * hp; H < 2 * hp + 2; ++H)
#pragma unroll
            for (int r = 0; r < 2; ++r) {
              mx[H][r] = fmaxf(fmaxf(fmaxf(QV(H, 2 * r), QV(H, 2 * r + 1)), fmaxf(QV(H, 4 + 2 * r), QV(H, 5 + 2 * r))),
                               fmaxf(fmaxf(QV(H, 8 + 2 * r), QV(H, 9 + 2 * r)), fmaxf(QV(H, 12 + 2 * r), QV(H, 13 + 2 * r))));
              mn[H][r] = fminf(fminf(fminf(QV(H, 2 * r), QV(H, 2 * r + 1)), fminf(QV(H, 4 + 2 * r), QV(H, 5 + 2 * r))),
                               fminf(fminf(QV(H, 8 + 2 * r), QV(H, 9 + 2 * r)), fminf(QV(H, 12 + 2 * r), QV(H, 13 + 2 * r))));
            }
#pragma unroll
          for (int o = 1; o <= 2; o <<= 1)
#pragma unroll
            for (int H = 2 * hp; H < 2 * hp + 2; ++H)
#pragma unroll
              for (int r = 0; r < 2; ++r) {
                mx[H][r] = fmaxf(mx[H][r], __shfl_xor_sync(0xffffffffu, mx[H][r], o));
                mn[H][r] = fminf(mn[H][r], __shfl_xor_sync(0xffffffffu, mn[H][r], o));
              }
#pragma unroll
          for (int H = 2 * hp; H < 2 * hp + 2; ++H)
#pragma unroll
            for (int r = 0; r < 2; ++r) { mx[H][r] *= -sc[r]; mn[H][r] = fmaf(mn[H][r], sc[r], mx[H][r]); }
        };
        auto fm = [&](int H) {
#pragma unroll
          for (int i = 0; i < 8; ++i) {
            const int r = i & 1;
            const float x0 = fmaf(QV(H, 2 * i), sc[r], mx[H][r]), x1 = fmaf(QV(H, 2 * i + 1), sc[r], mx[H][r]);
            ph[H][i >> 2][i & 3] = pack_bf16(ex2(x0), ex2(x1));
            ph[H][2 + (i >> 2)][i & 3] = pack_bf16(ex2(mn[H][r] - x0), ex2(mn[H][r] - x1));
          }
        };
        auto conv = [&](int hp) {
          mbar_wait(BA(hp ? B_KVF1 : B_KVF), (layer >> 1) & 1);
          PROFT(tid_ == 128, layer * 16 + (hp ? 4 : 5));
          if (hp) { mbar_wait(BA(FW), par); nbar_dyn(3 + wu, 128); }
#pragma unroll
          for (int h = 0; h < 2; ++h) {
            uint4 u[4];
#pragma unroll
            for (int i = 0; i < 4; ++i) u[i] = lds128(sb + VB + hp * SLOT + h * 8192 + (wq * 128 + i * 32 + lane) * 16);
            const float zz = lds_f(sb + SM_AP + ((2 * hp + h) * 64 + wq * 16 + (lane & 7) * 2 + ((lane >> 3) & 1)) * 4);
            const uint32_t kb_ = sb + PH + wg * SLOT + h * 8192 + (wq * 16 + lrow) * 128;
#pragma unroll
            for (int i = 0; i < 4; i += 2)
              stsm_x4(kb_ + (X ^ (i << 4)),
                      pack_bf16(__uint_as_float(u[i].x), __uint_as_float(u[i].y)), pack_bf16(__uint_as_float(u[i].z), __uint_as_float(u[i].w)),
                      pack_bf16(__uint_as_float(u[i + 1].x), __uint_as_float(u[i + 1].y)), pack_bf16(__uint_as_float(u[i + 1].z), __uint_as_float(u[i + 1].w)));
            const uint32_t z1 = pack_bf16(zz, 1.f);
            if (lane < 16) sts128(kb_ + ((4 ^ (lane & 7)) << 4), make_uint4(z1, z1, z1, z1));
          }
          fence_async_smem();
        };
        mnx(0);
        fm(0);
        if (CV0) conv(0);
        fm(1);
        if (!CV0) conv(0);
#pragma unroll
        for (int hp = 0; hp < 2; ++hp) {
          nbar_dyn(3 + wu, 128);
          float oa[4][20];
          wgmma_fence();
#pragma unroll
          for (int s = 0; s < 2; ++s)
#pragma unroll
            for (int v = 0; v < 4; ++v) {
              const int h = v >> 1, s4 = 2 * (v & 1) + s;
              wgmma_n40_rs(oa[v], ph[2 * hp + h][s4], D128(dB0 + (PH >> 4) + wu * 1024 + h * 512 + (s4 ^ (2 * h)) * 128), s != 0);
            }
          wgmma_commit();
          if (hp == 0) { mnx(1); wgmma_wait<0>(); }
          else wgmma_wait<0>();
#pragma unroll
          for (int i = 0; i < 20; ++i) asm volatile("" : "+f"(oa[0][i]), "+f"(oa[1][i]), "+f"(oa[2][i]), "+f"(oa[3][i]) :: "memory");
          uint32_t ow[2][2][4];
#pragma unroll
          for (int h = 0; h < 2; ++h)
#pragma unroll
            for (int r = 0; r < 2; ++r) {
              const float a = oa[2 * h + 1][17 + 2 * r], b = oa[2 * h][17 + 2 * r];
              const float id = rcp(fmaf(oa[2 * h][16 + 2 * r], a, fmaf(a, 1e-6f, oa[2 * h + 1][16 + 2 * r]) * b));
              const float fa = a * id, fb = b * id;
#pragma unroll
              for (int j = 0; j < 4; ++j)
                ow[h][r][j] = pack_bf16(fmaf(oa[2 * h][4 * j + 2 * r], fa, oa[2 * h + 1][4 * j + 2 * r] * fb),
                                        fmaf(oa[2 * h][4 * j + 2 * r + 1], fa, oa[2 * h + 1][4 * j + 2 * r + 1] * fb));
            }
#pragma unroll
          for (int i = 0; i < 16; ++i) of[4 * hp + (i >> 2)][i & 3] = ow[i >> 3][i & 1][(i >> 1) & 3];
          if (hp == 0) {
#pragma unroll
            for (int i = 0; i < 8; ++i) {
              if (!(i & 1)) stg128(g_o + gfr + ((i >> 1) & 1) * 8 * D_ + (i >> 2) * 32, ow[i >> 2][(i >> 1) & 1][0], ow[i >> 2][(i >> 1) & 1][1], ow[i >> 2][(i >> 1) & 1][2], ow[i >> 2][(i >> 1) & 1][3]);
              const int r = i & 1;
              const float x0 = fmaf(QV(2, 2 * i), sc[r], mx[2][r]), x1 = fmaf(QV(2, 2 * i + 1), sc[r], mx[2][r]);
              ph[2][i >> 2][i & 3] = pack_bf16(ex2v(x0), ex2v(x1));
              ph[2][2 + (i >> 2)][i & 3] = pack_bf16(ex2v(mn[2][r] - x0), ex2v(mn[2][r] - x1));
            }
            __syncwarp();
            if (lane == 0) mbar_arrive(BA(B_OH0));
            PROFT(tid_ == 128 && layer, layer * 16 + 15);
            if (QORD) { fm(3); conv(1); } else { conv(1); fm(3); }
          } else {
#pragma unroll
            for (int i = 0; i < 16; ++i) o1[i >> 2][i & 3] = ow[i >> 3][(i >> 2) & 1][i & 3];
          }
        }
      }
      PROFT(tid_ == 128, layer * 16 + 6);
#pragma unroll
      for (int i = 0; i < 4; ++i) stg128(g_o + gfr + (i & 1) * 8 * D_ + (2 + (i >> 1)) * 32, o1[i][0], o1[i][1], o1[i][2], o1[i][3]);
      __syncwarp();
      if (lane == 0) { mbar_arrive(BA(B_OH1)); if (EF_USED) REL2(B_EF); }
      PROFT(lane == 0 && layer == PL, 208 + cw);
      wo0();
    }
    {
      PHASE_CTX();
      MMA_CTX();
      mbar_wait(BA(FW + 1), par);
      wgmma_fence();
#pragma unroll
      for (int k = 0; k < 4; ++k) wgmma_n128_rs(acc, of[4 + k], D128(dB0 + (uint32_t)((WO_B >> 4) & 15) * 1024 + k * 128), 1);
      wgmma_commit();
      wgmma_wait<1>();
      if (elected) REL2(CW);
      uint64_t ta = WO_A >> 8, tw = WO_B >> 8;
      auto run = [&](int i0, int i1) {
#pragma unroll 1
        for (int i = i0; i < i1; ++i) {
          mbar_wait(BA(FW + i), par);
          PROFL(tid_ == 128 && layer == PL, 160 + i);
          const uint32_t da = dA0 + ((uint32_t)ta & 15) * 1024, db = dB0 + ((uint32_t)tw & 15) * 1024;
          ta >>= 4; tw >>= 4;
          wgmma_fence();
#pragma unroll
          for (int k = 0; k < 4; ++k) wgmma_n128(acc, D128(da + k * 2), D128(db + k * 128), 1);
          wgmma_commit();
          wgmma_wait<1>();
          if (elected) REL2(CW + i - 1);
        }
        ta = WO_A >> (4 * (i1 & 15)); tw = WO_B >> (4 * (i1 & 15));
      };
      run(2, XRAT);
#pragma unroll
      for (int j = 0; j < 8 / XRN; ++j) {
#pragma unroll
        for (int i = j * XRN; i < (j + 1) * XRN; ++i) ldg128((layer ? g_x : c.x0) + gfr + (i & 1) * 8 * D_ + (i >> 1) * 32, xp[i][0], xp[i][1], xp[i][2], xp[i][3]);
        run(XRAT + j, j + 1 < 8 / XRN ? XRAT + j + 1 : 16);
      }
      if (layer == 0) {
#pragma unroll
        for (int o = 1; o <= 2; o <<= 1)
#pragma unroll
          for (int i = 0; i < 16; ++i) {
            const int j = o == 1 ? 2 * (i & 1) : (i & 1);
            uint32_t &a = xp[i >> 1][j], &b = xp[i >> 1][j + o];
            const uint32_t r = __shfl_xor_sync(0xffffffffu, (t & o) ? a : b, o);
            if (t & o) a = r; else b = r;
          }
      }
      if (layer != NLAYERS - 1) mbar_wait(BA(FM), par ^ 1);
      wgmma_wait<0>();
#pragma unroll
      for (int i = 128; i < 192; ++i) asm volatile("" : "+f"(acc[i]) :: "memory");
      if (elected) REL2(CW + 15);
      PROFT(lane == 0 && layer == PL, 216 + cw);
      PROFT(tid_ == 128, layer * 16 + 7);
#pragma unroll
      for (int i = 0; i < 32; ++i)
        xp[i >> 2][i & 3] = add_bf16x2(xp[i >> 2][i & 3], pack_bf16(acc[128 + 16 * (i >> 3) + 4 * (i & 3) + 2 * ((i >> 2) & 1)], acc[129 + 16 * (i >> 3) + 4 * (i & 3) + 2 * ((i >> 2) & 1)]));
      if (layer == NLAYERS - 1) {
#pragma unroll
        for (int i = 0; i < 8; ++i) stsm_x4(sb + (XS + (i >> 2)) * SLOT + (Y ^ ((i & 2) << 5)) + (i & 1) * 1024, xp[i][0], xp[i][1], xp[i][2], xp[i][3]);
        __syncwarp();
        slab_out_half(sb + XS * SLOT, c.out + (size_t)m0 * D_ + g * 128, wrow0, lane);
        slab_out_half(sb + (XS + 1) * SLOT, c.out + (size_t)m0 * D_ + g * 128 + 64, wrow0, lane);
        PROFT(tid_ == 128, layer * 16 + 24);
        break;
      }
#pragma unroll
      for (int i = 0; i < 4; ++i) stg128(g_x + gfr + (i & 1) * 8 * D_ + (i >> 1) * 32, xp[i][0], xp[i][1], xp[i][2], xp[i][3]);
      __syncwarp();
      if (lane == 0) mbar_arrive(BA(B_XH0));
#pragma unroll
      for (int i = 0; i < 16; ++i) xf[i >> 2][i & 3] = xp[2 * (i >> 3) + (i & 1)][(i >> 1) & 3];
      PROFT(tid_ == 128, layer * 16 + 24);
    }
  }
}

__device__ __forceinline__ uint64_t k_order(int o) {
  const uint32_t lo = (1u << (4 * o)) - 1u, h0 = (0xECA86420u & lo) | ((0xECA86420u >> 4) & ~lo);
  return (uint64_t)(2 * o) | ((uint64_t)(2 * o + 1) << 4) | ((uint64_t)(h0 & 0xFFFFFFFu) << 8) | ((uint64_t)((h0 & 0xFFFFFFFu) | 0x1111111u) << 36);
}

__global__ void __cluster_dims__(2, 1, 1) __launch_bounds__(384, 1)
mega_kernel(const __grid_constant__ Maps maps, const __grid_constant__ Ctx c, const bf16* __restrict__ wA, const bf16* __restrict__ wB,
            const bf16* __restrict__ woA, const bf16* __restrict__ woB) {
  if (blockIdx.x - c.boff >= 128u) {
    const unsigned int epoch = ld_relaxed(&g_epoch);
    const int e = (blockIdx.x - c.boff) & 3, tid = threadIdx.x;
    float s[8] = {0.f, 0.f, 0.f, 0.f, 0.f, 0.f, 0.f, 0.f};
    const uint32_t sb = smem_u32(smem_raw), bar = sb + SM_BAR;
    auto issue = [&](int i) {
      mbar_expect_tx(BA(i & 3), 49152);
      bulk_load(sb + (i & 3) * 49152, wB + (size_t)e * 256 * 3072 + i * 24576, 49152, BA(i & 3));
    };
    if (tid == 0) {
#pragma unroll 1
      for (int i = 0; i < 4; ++i) {
        mbar_init(BA(i), 1);
        fence_async_smem();
        issue(i);
      }
    }
    __syncthreads();
#pragma unroll 1
    for (int i = 0; i < 32; ++i) {
      mbar_wait(BA(i & 3), (i >> 2) & 1);
#pragma unroll 2
      for (int r = 0; r < 8; ++r) {
        const uint4 v = lds128(sb + (i & 3) * 49152 + r * 6144 + tid * 16);
        s[0] += bf_lo(v.x); s[1] += bf_hi(v.x); s[2] += bf_lo(v.y); s[3] += bf_hi(v.y);
        s[4] += bf_lo(v.z); s[5] += bf_hi(v.z); s[6] += bf_lo(v.w); s[7] += bf_hi(v.w);
      }
      __syncthreads();
      if (tid == 0 && i < 28) issue(i + 4);
    }
    float* cd = g_cs + (epoch & 1) * 6144 + 3072 + ((tid >> 4) & 7) * 384 + (tid < 128 ? 256 : (tid >> 7) * 128 - 128) + (tid & 15) * 8;
    red_add4(cd, s[0], s[1], s[2], s[3]);
    red_add4(cd + 4, s[4], s[5], s[6], s[7]);
    __syncthreads();
    if (tid == 0) flag_add(&g_csflag[8].v);
    const int op = (epoch & 1) ^ 1;
    float4* kz = reinterpret_cast<float4*>(g_kv + (size_t)op * (2 * 8 * 8448)) + e * 8448;
#pragma unroll 1
    for (int i = tid; i < 8448; i += 384) kz[i] = make_float4(0.f, 0.f, 0.f, 0.f);
    reinterpret_cast<float4*>(g_cs + op * 6144)[e * 384 + tid] = make_float4(0.f, 0.f, 0.f, 0.f);
#pragma unroll 1
    for (int i = tid; i < 1024; i += 384) reinterpret_cast<float4*>(g_stats + (op * 4 + e) * S_)[i] = make_float4(0.f, 0.f, 0.f, 0.f);
    return;
  }
  const int warp = __shfl_sync(0xffffffffu, threadIdx.x >> 5, 0), lane = threadIdx.x & 31;
  if (smem_u32(smem_raw) != SB0 + ((blockIdx.x & 1) << 24)) __trap();
  {
  const int cid = (blockIdx.x - c.boff) >> 1, u7 = ((cid - 36) * 37) >> 8, cr = blockIdx.x & 1;
  const int g = cid < 4 ? 4 + cid : cid < 36 ? (cid - 4) >> 3 : 4 + u7, rb = (cid < 4 ? 0 : cid < 36 ? (cid - 4) & 7 : cid - 35 - 7 * u7) * 2 + cr, m0 = rb * 128;
  const uint32_t sb = SB0 + (cr << 24), bar = sb + SM_BAR;
  PROFT(lane == 0 && (warp == 0 || warp == 4), 224 + (warp >> 2) * 8);
  uint32_t cx = 0;
  if (warp == 2) {
    if (lane < NMAP) asm volatile("prefetch.tensormap [%0];" ::"l"(&maps.m[lane]) : "memory");
    if (lane == 31) asm volatile("prefetch.global.L2 [%0];" ::"l"(&g_epoch));
  } else if (warp == 3) {
    cx = c_map[cid] + c_wop[lane] + c_wop[NWOP - lane] + c_aop[lane] + c_aop[NAOP - lane] + (uint32_t)(uintptr_t)g_x;
  } else if (warp >= 4 && warp < 8) {
    const int i = threadIdx.x - 128;
    asm volatile("prefetch.global.L2 [%0];" ::"l"(wA + (size_t)((rb & ~1) * 64 + cr * 32 + ((i >> 1) & 31)) * 3072 + (i >> 6) * 1024 + g * 128 + (i & 1) * 64));
  }
  if (warp < 2) {
    const int s = warp, kb = (rb & ~1) + s;
    if (lane == 0) {
      mbar_init(BA(FM + s), 1u);
      mbar_init(BA(B_RAW + warp), 1u);
      mbar_init(BA(warp ? B_X0 : B_KVS0), 1u);
      asm volatile("fence.mbarrier_init.release.cluster;" ::: "memory");
    }
    __syncwarp();
    if (warp == 0) tma_2d_e(sb + SM_SD, &maps.m[MAP_PHI], 0, g * 128, BA(B_RAW));
    else if (W1DL) __nanosleep(W1DL);
#pragma unroll
    for (int j = 0; j < 6; ++j)
      tma_5d_e(sb + (j < 2 ? 2 * s : j < 4 ? 9 + s : 2 * s + 1) * SLOT + (j & 1) * 8192, &maps.m[MAP_WA], (j < 2 ? 1024 : j < 4 ? 0 : 2048) + g * 128 + (j & 1) * 64, 2 * kb,
               BA(j < 4 ? B_RAW + warp : FM + s));
    tma_2d_e(sb + (XS + s) * SLOT, &maps.m[MAP_X0], kb * 64, m0, BA(FM + s));
    expect_tx_e(BA(B_RAW + warp), warp ? 32768 : 32768 + 8192);
    expect_tx_e(BA(FM + s), 32768);
    if (X0AT == 0 && warp == 1) {
      tma_2d_e(sb + 11 * SLOT, &maps.m[MAP_X0], g * 128, m0, BA(B_X0));
      tma_2d_e(sb + 12 * SLOT, &maps.m[MAP_X0], g * 128 + 64, m0, BA(B_X0));
      expect_tx_e(BA(B_X0), 32768);
    }
  } else if (warp >= 4 && lane == 0) {
#pragma unroll 1
    for (int i = 2 + (warp - 4) * 13; i < 15 + (warp - 4) * 13; ++i)
      mbar_init(BA(i), 1u << ((i < CM ? 0u : i < B_EF ? 2u : (uint32_t)(BAR_LG >> (4 * ((i - B_EF) & 15)))) & 7u));
    asm volatile("fence.mbarrier_init.release.cluster;" ::: "memory");
  }
  __syncwarp();
  asm volatile("barrier.cluster.arrive.relaxed.aligned;" ::: "memory");
  if (threadIdx.x == 96 + c.zero) sts_f(sb + SM_EPOCH + 4, __uint_as_float(cx));
  PROFT(lane == 0 && (warp == 0 || warp == 4), 225 + (warp >> 2) * 8);
  __syncwarp();
  PROFT(lane == 0 && (warp == 0 || warp == 4), 226 + (warp >> 2) * 8);
  }

  if (warp < 4) {
    asm volatile("setmaxnreg.dec.sync.aligned.u32 40;");
    PROFT(threadIdx.x == 0, 227);
    cluster_wait();
    PROFT(threadIdx.x == 0, 228);
    if (warp == 0 || warp == 3) {
    if (warp == 0) {
      BLK_CTX();
      const unsigned int epoch = __shfl_sync(0xffffffffu, ld_relaxed(&g_epoch), 0), xbase = epoch * NLAYERS;
      (void)xbase;
      const uint64_t ordg = k_order(g);
      if (X0AT) {
        mbar_wait_u(BA(B_RAW + X0AT - 1), 0);
        tma_2d_e(sb + 11 * SLOT, &maps.m[MAP_X0], g * 128, m0, BA(B_X0));
        tma_2d_e(sb + 12 * SLOT, &maps.m[MAP_X0], g * 128 + 64, m0, BA(B_X0));
        expect_tx_e(BA(B_X0), 32768);
      }
#pragma unroll 1
      for (int lp = 0; lp < 2 * NLAYERS; ++lp) {
        const int layer = lp >> 1, n1 = (lp & 1) ? NAOP : NAOP - 14;
        int n = (lp & 1) ? NAOP - 14 : 0;
        const uint64_t ord = lp ? ordg : k_order(rb >> 1);
        uint32_t ready = lp ? 0u : 0xFFFFu, nop = c_aop[n];
        const unsigned int* fl = ((lp & 1) ? g_of : g_xf) + rb * 32;
        const CUtensorMap* tm = &maps.m[(lp & 1) ? MAP_O : lp ? MAP_X : MAP_X0];
        const uint32_t skip = layer ? 1u << 25 : 9u << 22;
#pragma unroll 1
        for (; n < n1; ++n) {
          const uint32_t op = nop;
          nop = c_aop[n + 1];
          const uint32_t kb = (uint32_t)(ord >> ((op >> 2) & 60)) & 15;
          uint32_t dst = sb + (op & 15) * SLOT, kc = kb * 64, fb = bar + ((op >> 5) & 0x3F8), need = ~ready & (1u << kb);
          asm volatile("" : "+r"(dst), "+r"(kc), "+r"(fb), "+r"(need));
          const uint32_t eb = bar + ((op >> 12) & 0x3F8), ep = (layer ^ (op >> 22)) & 1;
          bool fr = op & skip;
          if (need) {
            if (!fr) fr = __all_sync(0xffffffffu, mbar_test_wait(eb, ep));
            PROFT(lane == 0 && (n == 0 || n == NAOP - 14), 64 + layer * 16 + (n ? 2 : 0));
            src_wait<0>(fl, xbase + layer + 1, need, ready, lane);
            fence_async_all();
          }
          if (!fr) mbar_wait_u(eb, ep);
          tma_2d_e(dst, tm, kc, m0, fb);
          PROFT(lane == 0 && (n == 0 || n == NAOP - 14), 64 + layer * 16 + (n ? 3 : 1));
          PROFL(lane == 0 && layer == PL && n >= NAOP - 14, 178 + n - (NAOP - 14));
          PROFL(lane == 0 && layer == PL + 1 && n < 4, 242 + n);
        }
      }
    } else {
      BLK_CTX();
      const unsigned int epoch = __shfl_sync(0xffffffffu, ld_relaxed(&g_epoch), 0), xbase = epoch * NLAYERS;
      (void)xbase;
      const uint64_t ordg = k_order(g);
#pragma unroll 1
      for (int layer = 0; layer < NLAYERS; ++layer) {
        const uint64_t ordq = layer ? ordg : k_order(rb >> 1);
        uint32_t ready = layer ? 0xFFFFu : 0u, nop = c_wop[0];
        const CUtensorMap* tq = &maps.m[(layer & 1) ? MAP_WB : MAP_WF];
        const CUtensorMap* tk = &maps.m[(layer & 1) ? MAP_WB : cr ? MAP_WA : MAP_WF];
        const uint32_t skip = layer ? 1u << 25 : 9u << 22, pm = layer ? 0xE0u : 0u;
        int n = 0;
#pragma unroll 1
        for (; n < NWOP - 16; ++n) {
          const uint32_t op = nop;
          nop = c_wop[n + 1];
          const uint32_t isq = (op >> 23) & 1, fb = bar + ((op >> 5) & 0x3F8);
          const uint32_t kb = (uint32_t)(ordq >> ((op >> 2) & 60)) & 15;
          const CUtensorMap* tm = (isq ? tq : tk) + ((op & pm) ? 1 : 0);
          const uint32_t dst = sb + (op & 15) * SLOT + cr * (isq ? 8192 : SLOT);
          const int col = g * 128 + (isq ? cr * 64 : 1024 + cr * 1024);
          if (layer == 0) {
            if ((op & 0x7E00) == 0) continue;
            const uint32_t need = ((isq || !cr) ? 1u << kb : 0u) | (((op >> 22) & 1) ? 0u : (((op >> 15) & 127) == CM ? 1u : 3u) << (rb & ~1));
            if ((ready & need) != need) {
              src_wait<0>(g_wff + g * 32, epoch + 1, need, ready, lane);
              fence_async_all();
            }
            if ((op & 15) >= 11) mbar_wait_u(BA(B_XT), 0);
          }
          wait_tma_5d_mc(!(op & skip), bar + ((op >> 12) & 0x3F8), (layer ^ (op >> 22)) & 1, dst, tm, col, 2 * kb, fb);
          if (!isq) tma_5d_mc_e(dst + 8192, tm, col + 64, 2 * kb, fb);
          if (op >> 26) expect_tx_e(fb, (op >> 26) * 8192);
          PROFL(lane == 0 && layer == PL + 1 && n < 16, 128 + n);
        }
        const CUtensorMap* to = &maps.m[(layer & 1) ? MAP_WOB : MAP_WOA];
#pragma unroll 1
        for (; n < NWOP; ++n) {
          const uint32_t op = nop;
          nop = c_wop[n + 1];
          const uint32_t fb = bar + ((op >> 5) & 0x3F8), kb = (uint32_t)(ordg >> ((op >> 2) & 60)) & 15;
          if (WH < 16 && n == NWOP - 16 + WH && !(layer & 1)) mbar_wait_u(BA(B_KVS), (layer >> 1) & 1);
          wait_tma_5d_mc(!((op >> 25) & 1), bar + ((op >> 12) & 0x3F8), layer & 1, sb + (op & 15) * SLOT + cr * 8192, to + ((op & 0xE0) ? 1 : 0), g * 128 + cr * 64, 2 * kb, fb);
          expect_tx_e(fb, (op >> 26) * 8192);
          PROFL(lane == 0 && layer == PL, 144 + ((op >> 8) & 127) - FW);
        }
      }
    }
    } else if (warp == 1) {
      BLK_CTX();
      const unsigned int epoch = __shfl_sync(0xffffffffu, ld_relaxed(&g_epoch), 0), xbase = epoch * NLAYERS;
      (void)xbase;
      if (lane == 0) {
        mbar_wait(BA(B_WFD), 0);
        PROFT(true, 229);
#pragma unroll 1
        for (int j = 0; j < 4; ++j) tma_store_5d(&maps.m[MAP_WF], sb + (j < 2 ? 2 * cr : 9 + cr) * SLOT + (j & 1) * 8192, (j < 2 ? 1024 : 0) + g * 128 + (j & 1) * 64, 2 * rb);
        bulk_commit();
        bulk_wait0();
        PROFT(true, 230);
        fence_async_all();
        flag_set(g_wff + g * 32 + rb, epoch + 1);
        PROFT(true, 64 + 13);
#pragma unroll 1
        for (int e = 0; e < NLAYERS; ++e) {
          BLK_CTX();
          if (e > 0) {
            mbar_wait(BA(B_XH0), (e - 1) & 1);
            PROFT(e == PL + 1, 240);
            flag_set(g_xf + rb * 32 + 2 * g, xbase + e + 1);
            PROFT(e == PL + 1, 241);
          }
          mbar_wait(BA(B_XDONE), e & 1);
          PROFT(true, 64 + e * 16 + 4);
          flag_set(g_xf + rb * 32 + 2 * g + 1, xbase + e + 1);
          if (e == 0) {
            flag_add(&g_csflag[g].v);
            l2_prefetch(wB + (size_t)bid_ * 24576, 49152);
            l2_prefetch(woA + (size_t)bid_ * 8192, 16384);
            l2_prefetch(woB + (size_t)bid_ * 8192, 16384);
          }
          PROFT(true, 64 + e * 16 + 7);
          if ((e & 1) == 0) {
            float* kvl = g_kv + ((size_t)((epoch & 1) * 2 + (e >> 1)) * 8 + g) * 8448;
#pragma unroll 1
            for (int hp = 0; hp < 2; ++hp) {
              mbar_wait(BA(B_KVDONE), hp);
              bulk_red_add(kvl + 8192 + hp * 128, sb + SM_AP + hp * 512, 512);
#pragma unroll 1
              for (int i = 0; i < NCH; ++i) {
                const int ch = hp * NCH + ((i + rb * NCH / 16) & (NCH - 1));
                bulk_red_add(kvl + ch * (4096 / NCH), sb + VB + ch * (16384 / NCH), 16384 / NCH);
                bulk_commit();
                asm volatile("cp.async.bulk.wait_group %0;" :: "n"(CHW) : "memory");
              }
              bulk_wait0();
              PROFT(true, 64 + e * 16 + (hp ? 10 : 6));
              fence_async_all();
              flag_add(&g_kvflag[hp * 8 + g].v);
              mbar_arrive(BA(hp ? B_KVS : B_KVS0));
              PROFT(e > 0 && hp, 64 + e * 16 + 8);
            }
          }
          if (e & 1) {
            mbar_wait(BA(B_OF0), (e >> 1) & 1);
            flag_set(g_hf + rb * 32 + g, xbase + e + 1);
            if (rb) flag_wait(g_hf + (rb - 1) * 32 + g, xbase + e + 1);
            fence_async_all();
            mbar_expect_tx(BA(B_HALO), 8192);
            bulk_load(sb + SM_SD, g_halo + (size_t)(((e >> 1) * 17 + rb) * 8 + g) * 2048, 8192, BA(B_HALO));
            PROFT(true, 64 + e * 16 + 15);
          }
          mbar_wait(BA(B_OH0), e & 1);
          PROFT(e > 0, 64 + e * 16 + 13);
          flag_set(g_of + rb * 32 + 2 * g, xbase + e + 1);
          PROFT(true, 64 + e * 16 + 9);
          mbar_wait(BA(B_OH1), e & 1);
          PROFT(true, 64 + e * 16 + 5);
          flag_set(g_of + rb * 32 + 2 * g + 1, xbase + e + 1);
          PROFT(true, 64 + e * 16 + 11);
        }
        if (bid_ == 0) g_epoch = epoch + 1;
      }
    } else {
      BLK_CTX();
      const unsigned int epoch = __shfl_sync(0xffffffffu, ld_relaxed(&g_epoch), 0), xbase = epoch * NLAYERS;
      (void)xbase;
      if (lane < 16) sts_f(sb + SM_RS + lane * 4, 0.f);
#pragma unroll 1
      for (int layer = 0; layer < NLAYERS; ++layer) {
#define HLP_CTX() BLK_CTX(); int lane = threadIdx.x & 31; asm volatile("" : "+r"(lane)); const bool isB = layer & 1, hal = isB && rb > 0; (void)hal;
#pragma unroll 1
        for (int ph = 0; ph < 2; ++ph) {
          HLP_CTX();
          if (ph == (layer == 0)) {
            const float* cs = g_cs + (epoch & 1) * 6144 + g * 384;
            if (layer) mbar_wait_u(BA(CT), (layer - 1) & 1);
            if (layer < 2) {
              if (lane == 0) flag_wait_slow(&g_csflag[isB ? 8 : g].v, isB ? epoch * 4u + 4u : epoch * 16u + 16u);
              __syncwarp();
            }
#pragma unroll 1
            for (int i0 = 0; i0 < 12; i0 += 4) {
              float a[4];
#pragma unroll
              for (int i = 0; i < 4; ++i) a[i] = __ldcg(cs + isB * 3072 + (i0 + i) * 32 + lane);
#pragma unroll
              for (int i = 0; i < 4; ++i) {
                const float c1 = bf16r(a[i]), c2 = bf16r(a[i] - c1), c3 = (a[i] - c1) - c2;
                sts128(sb + SM_BP + ((i0 + i) * 32 + lane) * 16, make_uint4(pack_bf16(c1, c2), pack_bf16(c3, 0.f), 0u, 0u));
              }
            }
          } else {
            uint32_t rdy = 0u;
            src_wait<128>(g_xf + rb * 32, xbase + layer + 1, 0xAAAAu, rdy, lane);
            rdy = 0u;
            if (hal) src_wait<128>(g_xf + (rb - 1) * 32, xbase + layer + 1, 0xAAAAu, rdy, lane);
            const float2* sp = g_stats + ((epoch & 1) * 4 + layer) * S_ + m0 + lane;
            float2 u[5];
#pragma unroll
            for (int i = 0; i < 4; ++i) u[i] = __ldcg(sp + i * 32);
            u[4] = __ldcg(sp - (hal ? 16 : 0));
#pragma unroll 1
            for (int i = 0; i < 5; ++i) {
              const float mean = u[0].x * (1.f / D_);
              const float var = fmaxf(fmaf(-u[0].x, mean, u[0].y) * (1.f / D_), 0.f);
              const float sd = bf16r(sqrtf(bf16r(bf16r(var) + 1e-5f)));
              const int R = i * 32 + lane;
              if (i < 4) {
                const float hm = -0.5f * bf16r(mean);
                if (!isB) sts128(sb + SM_SD + R * 64 + ((R >> 1) & 3) * 16, make_uint4(__float_as_uint(sd) >> 16, 0u, 0u, 0u));
                sts128(sb + SM_AP + R * 16, make_uint4(pack_bf16(hm, hm), pack_bf16(hm, 0.f), 0u, 0u));
              }
              if (i < 4 || (hal && lane < 16)) sts_f(sb + SM_RS + (i < 4 ? 16 + R : lane) * 4, __fdividef(1.f, sd));
#pragma unroll
              for (int j = 0; j < 4; ++j) u[j] = u[j + 1];
            }
            PROFT(lane == 0, 64 + layer * 16 + 12);
          }
        }
        HLP_CTX();
        fence_async_smem();
        __syncwarp();
        if (lane == 0) mbar_arrive(BA(B_STAT));
        PROFT(lane == 0, 64 + layer * 16 + 14);
        if (!isB && lane == 0) {
#pragma unroll 1
          for (int hp = 0; hp < 2; ++hp) {
            mbar_wait(BA(hp ? B_KVS : B_KVS0), (layer >> 1) & 1);
            flag_wait(&g_kvflag[hp * 8 + g].v, epoch * (16u * ((NLAYERS + 1) / 2)) + 16u * ((layer >> 1) + 1));
            const float* kvl = g_kv + ((size_t)((epoch & 1) * 2 + (layer >> 1)) * 8 + g) * 8448;
            const uint32_t kb = BA(hp ? B_KVF1 : B_KVF);
            fence_async_all();
            mbar_expect_tx(kb, 16384 + 512);
            bulk_load(sb + VB + hp * SLOT, kvl + hp * 4096, 16384, kb);
            bulk_load(sb + SM_AP + hp * 512, kvl + 8192 + hp * 128, 512, kb);
            PROFT(hp == 0, 64 + layer * 16 + 15);
          }
        }
        __syncwarp();
      }
    }
    __syncwarp();
    asm volatile("barrier.cluster.arrive.relaxed.aligned;" ::: "memory");
    cluster_wait();
  } else {
    asm volatile("setmaxnreg.inc.sync.aligned.u32 232;");
    PROFT(threadIdx.x == 128, 235);
    cluster_wait();
    PROFT(threadIdx.x == 128, 236);
    consumer(c);
    asm volatile("bar.warp.sync 0xffffffff;\nbarrier.cluster.arrive.relaxed.aligned;\nbarrier.cluster.wait.aligned;\n" ::: "memory");
  }
}

typedef CUresult (*PFN_encodeTiled)(CUtensorMap*, CUtensorMapDataType, cuuint32_t, void*, const cuuint64_t*, const cuuint64_t*,
                                    const cuuint32_t*, const cuuint32_t*, CUtensorMapInterleave, CUtensorMapSwizzle,
                                    CUtensorMapL2promotion, CUtensorMapFloatOOBfill);

static void make_map2(PFN_encodeTiled enc, CUtensorMap* m, const void* ptr, uint64_t cols, uint64_t rows, uint32_t box_c, uint32_t box_r) {
  cuuint64_t dims[2] = {cols, rows};
  cuuint64_t strides[1] = {cols * 2};
  cuuint32_t box[2] = {box_c, box_r};
  cuuint32_t es[2] = {1, 1};
  CUresult r = enc(m, CU_TENSOR_MAP_DATA_TYPE_BFLOAT16, 2, const_cast<void*>(ptr), dims, strides, box, es, CU_TENSOR_MAP_INTERLEAVE_NONE,
                   box_c == 64 ? CU_TENSOR_MAP_SWIZZLE_128B : CU_TENSOR_MAP_SWIZZLE_64B, CU_TENSOR_MAP_L2_PROMOTION_L2_256B, CU_TENSOR_MAP_FLOAT_OOB_FILL_NONE);
  (void)r;
}
static void make_map5(PFN_encodeTiled enc, CUtensorMap* m, const void* ptr, uint64_t cols) {
  for (int p = 0; p < 2; ++p) {
    cuuint64_t dims[5] = {cols, 2, 4, 4, 32};
    cuuint64_t strides[4] = {cols * 2, cols * (p ? 16 : 4), cols * (p ? 4 : 16), cols * 64};
    cuuint32_t box[5] = {64, 2, 4, 4, 2};
    cuuint32_t es[5] = {1, 1, 1, 1, 1};
    CUresult r = enc(m + p, CU_TENSOR_MAP_DATA_TYPE_BFLOAT16, 5, const_cast<void*>(ptr), dims, strides, box, es, CU_TENSOR_MAP_INTERLEAVE_NONE,
                     CU_TENSOR_MAP_SWIZZLE_128B, CU_TENSOR_MAP_L2_PROMOTION_L2_256B, CU_TENSOR_MAP_FLOAT_OOB_FILL_NONE);
    (void)r;
  }
}

extern "C" void kernel_launch(void* const* d_in, const int* in_sizes, int n_in, void* d_out, int out_size) {
  const bf16* A_x = (const bf16*)d_in[0];
  const bf16* A_wqkv = (const bf16*)d_in[1];
  const bf16* A_wphi = (const bf16*)d_in[2];
  const bf16* A_wo = (const bf16*)d_in[3];
  const bf16* B_wqkv = (const bf16*)d_in[5];
  const bf16* B_wo = (const bf16*)d_in[6];
  bf16* out = (bf16*)d_out;

  static PFN_encodeTiled enc = nullptr;
  static bf16 *p_x, *p_o, *p_wf;
  static uint32_t boff;
  if (!enc) {
    void* fn = nullptr; cudaDriverEntryPointQueryResult qr;
    cudaGetDriverEntryPoint("cuTensorMapEncodeTiled", &fn, cudaEnableDefault, &qr);
    enc = (PFN_encodeTiled)fn;
    cudaGetSymbolAddress((void**)&p_x, g_x);
    cudaGetSymbolAddress((void**)&p_o, g_o);
    cudaGetSymbolAddress((void**)&p_wf, g_wf);
    cudaFuncSetAttribute(mega_kernel, cudaFuncAttributeMaxDynamicSharedMemorySize, SM_TOTAL);
    cudaLaunchConfig_t cfg = {};
    cudaLaunchAttribute at; at.id = cudaLaunchAttributeClusterDimension; at.val.clusterDim.x = 2; at.val.clusterDim.y = 1; at.val.clusterDim.z = 1;
    cfg.gridDim = dim3(132); cfg.blockDim = dim3(384); cfg.dynamicSmemBytes = SM_TOTAL; cfg.attrs = &at; cfg.numAttrs = 1;
    int nc = 0;
    if (cudaOccupancyMaxActiveClusters(&nc, mega_kernel, &cfg) != cudaSuccess) { nc = 0; (void)cudaGetLastError(); }
    boff = nc >= 66 ? 0u : 4u;
  }
  Maps maps;
  make_map5(enc, &maps.m[MAP_WF], p_wf, 2048);
  make_map5(enc, &maps.m[MAP_WA], A_wqkv, 3072);
  make_map5(enc, &maps.m[MAP_WB], B_wqkv, 3072);
  make_map5(enc, &maps.m[MAP_WOA], A_wo, 1024);
  make_map5(enc, &maps.m[MAP_WOB], B_wo, 1024);
  make_map2(enc, &maps.m[MAP_X0], A_x, 1024, 2048, 64, 128);
  make_map2(enc, &maps.m[MAP_X], p_x, 1024, 2048, 64, 128);
  make_map2(enc, &maps.m[MAP_O], p_o, 1024, 2048, 64, 128);
  make_map2(enc, &maps.m[MAP_PHI], A_wphi, 32, 1024, 32, 128);
  Ctx c; c.zero = 0u; c.boff = boff; c.x0 = A_x; c.out = out;
  mega_kernel<<<132, 384, SM_TOTAL, cudaStreamPerThread>>>(maps, c, A_wqkv, B_wqkv, A_wo, B_wo);
}
```

```cpp
#include <cuda_runtime.h>
#include <cuda_bf16.h>
#include <cuda.h>
#include <stdint.h>

typedef __nv_bfloat16 bf16;

constexpr int S_ = 2048, D_ = 1024;

struct __align__(128) Flag { unsigned int v; unsigned int pad[31]; };
__device__ __align__(1024) bf16 g_x[S_ * D_];
__device__ __align__(1024) bf16 g_o[S_ * D_];
__device__ __align__(1024) uint32_t g_halo[2 * 17 * 8 * 2048];
__device__ __align__(1024) float g_kv[2 * 2 * 8 * 8448];
__device__ __align__(1024) float2 g_stats[2 * 4 * S_];
__device__ __align__(1024) float g_cs[2 * 2 * 3072];
__device__ __align__(1024) bf16 g_wf[D_ * 2048];
__device__ Flag g_kvflag[16], g_csflag[13];
__device__ __align__(128) unsigned int g_xf[16 * 32], g_of[16 * 32];
__device__ __align__(128) unsigned int g_hf[16 * 32];
__device__ __align__(128) unsigned int g_wff[8 * 32];
__device__ unsigned int g_epoch, g_err;
#define PROFT(cond, idx) asm volatile("" ::: "memory")

__device__ __forceinline__ uint32_t smem_u32(const void* p) { return (uint32_t)__cvta_generic_to_shared(p); }
__device__ __forceinline__ void mbar_init(uint32_t bar, uint32_t count) {
  asm volatile("mbarrier.init.shared::cta.b64 [%0], %1;" ::"r"(bar), "r"(count) : "memory");
}
__device__ __forceinline__ void mbar_expect_tx(uint32_t bar, uint32_t bytes) {
  asm volatile("mbarrier.arrive.expect_tx.shared::cta.b64 _, [%0], %1;" ::"r"(bar), "r"(bytes) : "memory");
}
__device__ __forceinline__ void mbar_arrive(uint32_t bar) {
  asm volatile("mbarrier.arrive.shared::cta.b64 _, [%0];" ::"r"(bar) : "memory");
}
__device__ __forceinline__ bool mbar_try_wait(uint32_t bar, uint32_t parity) {
  uint32_t ok;
  asm volatile("{\n.reg .pred p;\nmbarrier.try_wait.parity.shared::cta.b64 p, [%1], %2;\nselp.b32 %0, 1, 0, p;\n}\n"
               : "=r"(ok) : "r"(bar), "r"(parity) : "memory");
  return ok != 0;
}
__device__ __forceinline__ bool mbar_test_wait(uint32_t bar, uint32_t parity) {
  uint32_t ok;
  asm volatile("{\n.reg .pred p;\nmbarrier.test_wait.parity.shared::cta.b64 p, [%1], %2;\nselp.b32 %0, 1, 0, p;\n}\n"
               : "=r"(ok) : "r"(bar), "r"(parity) : "memory");
  return ok != 0;
}
__device__ __forceinline__ uint64_t gtimer() {
  uint64_t t; asm volatile("mov.u64 %0, %globaltimer;" : "=l"(t)); return t;
}
__device__ __forceinline__ void mbar_wait(uint32_t bar, uint32_t parity) {
  uint32_t n = 0;
  bool ok;
#pragma unroll 1
  do { ++n; ok = mbar_try_wait(bar, parity); } while (!ok && n < (1u << 22));
}
__device__ __forceinline__ unsigned int ld_acquire(const unsigned int* p) {
  unsigned int v; asm volatile("ld.acquire.gpu.global.u32 %0, [%1];" : "=r"(v) : "l"(p) : "memory"); return v;
}
__device__ __forceinline__ void flag_add(unsigned int* p) {
  asm volatile("red.release.gpu.global.add.u32 [%0], 1;" ::"l"(p) : "memory");
}
__device__ __forceinline__ void flag_set(unsigned int* p, unsigned int v) {
  asm volatile("st.release.gpu.global.u32 [%0], %1;" ::"l"(p), "r"(v) : "memory");
}
template <int SLEEP>
__device__ __forceinline__ void src_wait(const unsigned int* f, unsigned int target, uint32_t need, uint32_t& ready, int lane) {
  uint32_t n = 0;
#pragma unroll 1
  while ((ready & need) != need) {
    const unsigned int v = ld_acquire(f + (lane & 15));
    ready = __ballot_sync(0xffffffffu, (int)(v - target) >= 0);
    if (SLEEP) { if ((ready & need) != need) __nanosleep(SLEEP); }
    if (++n > (1u << 20)) break;
  }
  __syncwarp();
}
__device__ __forceinline__ unsigned int ld_relaxed(const unsigned int* p);
__device__ __forceinline__ unsigned int ld_relaxed(const unsigned int* p) {
  unsigned int v; asm volatile("ld.relaxed.gpu.global.u32 %0, [%1];" : "=r"(v) : "l"(p) : "memory"); return v;
}
template <int SLEEP>
__device__ __forceinline__ void flag_wait_t(const unsigned int* p, unsigned int target) {
  uint32_t n = 0;
#pragma unroll 1
  while ((int)(ld_acquire(p) - target) < 0) {
    if (SLEEP) __nanosleep(SLEEP);
    if (++n > (1u << 20)) break;
  }
}
__device__ __forceinline__ void flag_wait(const unsigned int* p, unsigned int target) { flag_wait_t<0>(p, target); }
__device__ __forceinline__ void flag_wait_slow(const unsigned int* p, unsigned int target) { flag_wait_t<256>(p, target); }
__device__ __forceinline__ void mbar_wait_u(uint32_t bar, uint32_t parity) {
  uint32_t n = 0;
#pragma unroll 1
  while (!__all_sync(0xffffffffu, mbar_try_wait(bar, parity))) {
    if (++n > (1u << 22)) break;
  }
}
__device__ __forceinline__ void expect_tx_e(uint32_t bar, uint32_t bytes) {
  asm volatile("{\n.reg .pred p;\nelect.sync _|p, 0xffffffff;\n@p mbarrier.arrive.expect_tx.shared::cta.b64 _, [%0], %1;\n}\n" ::"r"(bar), "r"(bytes) : "memory");
}
__device__ __forceinline__ void tma_2d_e(uint32_t dst, const CUtensorMap* tm, int c0, int c1, uint32_t bar) {
  asm volatile("{\n.reg .pred p;\nelect.sync _|p, 0xffffffff;\n"
               "@p cp.async.bulk.tensor.2d.shared::cluster.global.mbarrier::complete_tx::bytes [%0], [%1, {%2, %3}], [%4];\n}\n"
               ::"r"(dst), "l"(tm), "r"(c0), "r"(c1), "r"(bar) : "memory");
}
__device__ __forceinline__ void tma_5d_e(uint32_t dst, const CUtensorMap* tm, int c0, int c4, uint32_t bar) {
  asm volatile("{\n.reg .pred p;\nelect.sync _|p, 0xffffffff;\n"
               "@p cp.async.bulk.tensor.5d.shared::cluster.global.mbarrier::complete_tx::bytes [%0], [%1, {%2, %5, %5, %5, %3}], [%4];\n}\n"
               ::"r"(dst), "l"(tm), "r"(c0), "r"(c4), "r"(bar), "r"(0) : "memory");
}
__device__ __forceinline__ void tma_5d_mc_e(uint32_t dst, const CUtensorMap* tm, int c0, int c4, uint32_t bar) {
  asm volatile("{\n.reg .pred p;\nelect.sync _|p, 0xffffffff;\n"
               "@p cp.async.bulk.tensor.5d.shared::cluster.global.mbarrier::complete_tx::bytes.multicast::cluster [%0], [%1, {%2, %6, %6, %6, %3}], [%4], %5;\n}\n"
               ::"r"(dst), "l"(tm), "r"(c0), "r"(c4), "r"(bar), "h"((uint16_t)3), "r"(0) : "memory");
}
__device__ __forceinline__ void wait_tma_5d_mc(bool w, uint32_t eb, uint32_t par, uint32_t dst, const CUtensorMap* tm, int c0, int c4, uint32_t fb) {
  asm volatile("" : "+r"(dst), "+l"(tm), "+r"(c0), "+r"(c4), "+r"(fb));
  if (w) mbar_wait_u(eb, par);
  tma_5d_mc_e(dst, tm, c0, c4, fb);
}
__device__ __forceinline__ void stg128(void* p, uint32_t a, uint32_t b, uint32_t c, uint32_t d) {
  asm volatile("st.global.v4.u32 [%0], {%1,%2,%3,%4};" ::"l"(p), "r"(a), "r"(b), "r"(c), "r"(d) : "memory");
}
__device__ __forceinline__ void stg128_p(bool on, void* p, uint32_t a, uint32_t b, uint32_t c, uint32_t d) {
  asm volatile("{\n.reg .pred p;\nsetp.ne.b32 p, %5, 0;\n@p st.global.v4.u32 [%0], {%1,%2,%3,%4};\n}\n" ::"l"(p), "r"(a), "r"(b), "r"(c), "r"(d), "r"((int)on) : "memory");
}
__device__ __forceinline__ void ldg128(const void* p, uint32_t& a, uint32_t& b, uint32_t& c, uint32_t& d) {
  asm volatile("ld.global.cg.v4.u32 {%0,%1,%2,%3}, [%4];" : "=r"(a), "=r"(b), "=r"(c), "=r"(d) : "l"(p) : "memory");
}
__device__ __forceinline__ void release2c(uint32_t off) {
  asm volatile("mbarrier.arrive.shared::cluster.b64 _, [%0];\nmbarrier.arrive.shared::cluster.b64 _, [%1];" ::"r"(off), "r"(off + (1u << 24)) : "memory");
}
__device__ __forceinline__ void tma_store_5d(const CUtensorMap* tm, uint32_t src, int c0, int c4) {
  asm volatile("cp.async.bulk.tensor.5d.global.shared::cta.bulk_group [%0, {%2, %4, %4, %4, %3}], [%1];"
               ::"l"(tm), "r"(src), "r"(c0), "r"(c4), "r"(0) : "memory");
}
__device__ __forceinline__ void bulk_load(uint32_t dst, const void* src, uint32_t bytes, uint32_t bar) {
  asm volatile("cp.async.bulk.shared::cluster.global.mbarrier::complete_tx::bytes [%0], [%1], %2, [%3];" ::"r"(dst), "l"(src), "r"(bytes), "r"(bar) : "memory");
}
__device__ __forceinline__ void bulk_red_add(void* dst, uint32_t src, uint32_t bytes) {
  asm volatile("cp.reduce.async.bulk.global.shared::cta.bulk_group.add.f32 [%0], [%1], %2;" ::"l"(dst), "r"(src), "r"(bytes) : "memory");
}
__device__ __forceinline__ void bulk_commit() { asm volatile("cp.async.bulk.commit_group;" ::: "memory"); }
__device__ __forceinline__ void bulk_wait0() { asm volatile("cp.async.bulk.wait_group 0;" ::: "memory"); }
__device__ __forceinline__ void fence_async_smem() { asm volatile("fence.proxy.async.shared::cta;" ::: "memory"); }
__device__ __forceinline__ void fence_async_all() { asm volatile("fence.proxy.async.global;" ::: "memory"); }
__device__ __forceinline__ void wgmma_fence() { asm volatile("wgmma.fence.sync.aligned;" ::: "memory"); }
__device__ __forceinline__ void wgmma_commit() { asm volatile("wgmma.commit_group.sync.aligned;" ::: "memory"); }
template <int N> __device__ __forceinline__ void wgmma_wait() { asm volatile("wgmma.wait_group.sync.aligned %0;" ::"n"(N) : "memory"); }
__device__ __forceinline__ void cluster_wait() { asm volatile("barrier.cluster.wait.acquire.aligned;" ::: "memory"); }
template <int ID, int N> __device__ __forceinline__ void nbar() { asm volatile("bar.sync %0, %1;" ::"n"(ID), "n"(N) : "memory"); }
__device__ __forceinline__ uint64_t desc64(uint32_t lo, uint32_t hi) { return (uint64_t)lo | ((uint64_t)hi << 32); }
__device__ __forceinline__ uint32_t pack_bf16(float lo, float hi) {
  uint32_t r; asm("cvt.rn.bf16x2.f32 %0, %1, %2;" : "=r"(r) : "f"(hi), "f"(lo)); return r;
}
__device__ __forceinline__ uint32_t add_bf16x2(uint32_t a, uint32_t b) {
  uint32_t r; asm("add.rn.bf16x2 %0, %1, %2;" : "=r"(r) : "r"(a), "r"(b)); return r;
}
__device__ __forceinline__ float bf16r(float x) { return __bfloat162float(__float2bfloat16_rn(x)); }
__device__ __forceinline__ float bf_lo(uint32_t u) { return __uint_as_float(u << 16); }
__device__ __forceinline__ float bf_hi(uint32_t u) { return __uint_as_float(u & 0xFFFF0000u); }
__device__ __forceinline__ float ex2(float x) { float r; asm("ex2.approx.ftz.f32 %0, %1;" : "=f"(r) : "f"(x)); return r; }
__device__ __forceinline__ float ex2v(float x) { float r; asm volatile("ex2.approx.ftz.f32 %0, %1;" : "=f"(r) : "f"(x) : "memory"); return r; }
__device__ __forceinline__ float rcp(float x) { float r; asm("rcp.approx.ftz.f32 %0, %1;" : "=f"(r) : "f"(x)); return r; }
__device__ __forceinline__ void mma_bf16(float (&d)[4], uint32_t a0, uint32_t a1, uint32_t a2, uint32_t a3, uint32_t b0, uint32_t b1) {
  asm("mma.sync.aligned.m16n8k16.row.col.f32.bf16.bf16.f32 {%0,%1,%2,%3}, {%4,%5,%6,%7}, {%8,%9}, {%0,%1,%2,%3};"
               : "+f"(d[0]), "+f"(d[1]), "+f"(d[2]), "+f"(d[3]) : "r"(a0), "r"(a1), "r"(a2), "r"(a3), "r"(b0), "r"(b1));
}
__device__ __forceinline__ void ldsm_x4(uint32_t& r0, uint32_t& r1, uint32_t& r2, uint32_t& r3, uint32_t addr) {
  asm volatile("ldmatrix.sync.aligned.m8n8.x4.shared.b16 {%0,%1,%2,%3}, [%4];"
               : "=r"(r0), "=r"(r1), "=r"(r2), "=r"(r3) : "r"(addr) : "memory");
}
__device__ __forceinline__ void ldsm_x4_t(uint32_t& r0, uint32_t& r1, uint32_t& r2, uint32_t& r3, uint32_t addr) {
  asm volatile("ldmatrix.sync.aligned.m8n8.x4.trans.shared.b16 {%0,%1,%2,%3}, [%4];"
               : "=r"(r0), "=r"(r1), "=r"(r2), "=r"(r3) : "r"(addr) : "memory");
}
__device__ __forceinline__ void stsm_x4(uint32_t addr, uint32_t r0, uint32_t r1, uint32_t r2, uint32_t r3) {
  asm volatile("stmatrix.sync.aligned.m8n8.x4.shared.b16 [%0], {%1,%2,%3,%4};"
               ::"r"(addr), "r"(r0), "r"(r1), "r"(r2), "r"(r3) : "memory");
}
__device__ __forceinline__ uint4 lds128(uint32_t addr) {
  uint4 v; asm volatile("ld.shared.v4.b32 {%0,%1,%2,%3}, [%4];" : "=r"(v.x), "=r"(v.y), "=r"(v.z), "=r"(v.w) : "r"(addr) : "memory"); return v;
}
__device__ __forceinline__ void sts128(uint32_t addr, uint4 v) {
  asm volatile("st.shared.v4.b32 [%0], {%1,%2,%3,%4};" ::"r"(addr), "r"(v.x), "r"(v.y), "r"(v.z), "r"(v.w) : "memory");
}
__device__ __forceinline__ float lds_f(uint32_t addr) {
  float v; asm volatile("ld.shared.f32 %0, [%1];" : "=f"(v) : "r"(addr) : "memory"); return v;
}
__device__ __forceinline__ void nbar_dyn(int id, int n) { asm volatile("bar.sync %0, %1;" ::"r"(id), "r"(n) : "memory"); }
__device__ __forceinline__ uint64_t make_desc_ns(uint32_t addr, uint32_t lbo_bytes, uint32_t sbo_bytes) {
  return (uint64_t)((addr & 0x3FFFF) >> 4) | ((uint64_t)(lbo_bytes >> 4) << 16) | ((uint64_t)(sbo_bytes >> 4) << 32);
}
__device__ __forceinline__ void sts_f(uint32_t addr, float v) { asm volatile("st.shared.f32 [%0], %1;" ::"r"(addr), "f"(v) : "memory"); }
__device__ __forceinline__ void sts64(uint32_t addr, uint32_t a, uint32_t b) {
  asm volatile("st.shared.v2.b32 [%0], {%1,%2};" ::"r"(addr), "r"(a), "r"(b) : "memory");
}
__device__ __forceinline__ void sts_f2(uint32_t addr, float a, float b) {
  asm volatile("st.shared.v2.f32 [%0], {%1,%2};" ::"r"(addr), "f"(a), "f"(b) : "memory");
}
__device__ __forceinline__ void red_add2_p(bool on, float* p, float a, float b) {
  asm volatile("{\n.reg .pred p;\nsetp.ne.b32 p, %3, 0;\n@p red.global.add.v2.f32 [%0], {%1,%2};\n}\n" ::"l"(p), "f"(a), "f"(b), "r"((int)on) : "memory");
}
__device__ __forceinline__ void red_add4(float* p, float a, float b, float c, float d) {
  asm volatile("red.global.add.v4.f32 [%0], {%1,%2,%3,%4};" ::"l"(p), "f"(a), "f"(b), "f"(c), "f"(d) : "memory");
}
__device__ __forceinline__ void red_add1(float* p, float a) {
  asm volatile("red.global.add.f32 [%0], %1;" ::"l"(p), "f"(a) : "memory");
}
__device__ __forceinline__ void l2_prefetch(const void* p, uint32_t bytes) {
  asm volatile("cp.async.bulk.prefetch.L2.global [%0], %1;" ::"l"(p), "r"(bytes) : "memory");
}

__device__ __forceinline__ void wgmma_n256(float (&d)[192], uint64_t da, uint64_t db, int scale_d) {
  asm volatile("{\n.reg .pred p;\nsetp.ne.b32 p, %130, 0;\n"
    "wgmma.mma_async.sync.aligned.m64n256k16.f32.bf16.bf16 {%0, %1, %2, %3, %4, %5, %6, %7, %8, %9, %10, %11, %12, %13, %14, %15, %16, %17, %18, %19, %20, %21, %22, %23, %24, %25, %26, %27, %28, %29, %30, %31, %32, %33, %34, %35, %36, %37, %38, %39, %40, %41, %42, %43, %44, %45, %46, %47, %48, %49, %50, %51, %52, %53, %54, %55, %56, %57, %58, %59, %60, %61, %62, %63, %64, %65, %66, %67, %68, %69, %70, %71, %72, %73, %74, %75, %76, %77, %78, %79, %80, %81, %82, %83, %84, %85, %86, %87, %88, %89, %90, %91, %92, %93, %94, %95, %96, %97, %98, %99, %100, %101, %102, %103, %104, %105, %106, %107, %108, %109, %110, %111, %112, %113, %114, %115, %116, %117, %118, %119, %120, %121, %122, %123, %124, %125, %126, %127}, %128, %129, p, 1, 1, 0, 1;\n}\n"
    : "+f"(d[0]), "+f"(d[1]), "+f"(d[2]), "+f"(d[3]), "+f"(d[4]), "+f"(d[5]), "+f"(d[6]), "+f"(d[7]), "+f"(d[8]), "+f"(d[9]), "+f"(d[10]), "+f"(d[11]), "+f"(d[12]), "+f"(d[13]), "+f"(d[14]), "+f"(d[15]), "+f"(d[16]), "+f"(d[17]), "+f"(d[18]), "+f"(d[19]), "+f"(d[20]), "+f"(d[21]), "+f"(d[22]), "+f"(d[23]), "+f"(d[24]), "+f"(d[25]), "+f"(d[26]), "+f"(d[27]), "+f"(d[28]), "+f"(d[29]), "+f"(d[30]), "+f"(d[31]), "+f"(d[32]), "+f"(d[33]), "+f"(d[34]), "+f"(d[35]), "+f"(d[36]), "+f"(d[37]), "+f"(d[38]), "+f"(d[39]), "+f"(d[40]), "+f"(d[41]), "+f"(d[42]), "+f"(d[43]), "+f"(d[44]), "+f"(d[45]), "+f"(d[46]), "+f"(d[47]), "+f"(d[48]), "+f"(d[49]), "+f"(d[50]), "+f"(d[51]), "+f"(d[52]), "+f"(d[53]), "+f"(d[54]), "+f"(d[55]), "+f"(d[56]), "+f"(d[57]), "+f"(d[58]), "+f"(d[59]), "+f"(d[60]), "+f"(d[61]), "+f"(d[62]), "+f"(d[63]), "+f"(d[64]), "+f"(d[65]), "+f"(d[66]), "+f"(d[67]), "+f"(d[68]), "+f"(d[69]), "+f"(d[70]), "+f"(d[71]), "+f"(d[72]), "+f"(d[73]), "+f"(d[74]), "+f"(d[75]), "+f"(d[76]), "+f"(d[77]), "+f"(d[78]), "+f"(d[79]), "+f"(d[80]), "+f"(d[81]), "+f"(d[82]), "+f"(d[83]), "+f"(d[84]), "+f"(d[85]), "+f"(d[86]), "+f"(d[87]), "+f"(d[88]), "+f"(d[89]), "+f"(d[90]), "+f"(d[91]), "+f"(d[92]), "+f"(d[93]), "+f"(d[94]), "+f"(d[95]), "+f"(d[96]), "+f"(d[97]), "+f"(d[98]), "+f"(d[99]), "+f"(d[100]), "+f"(d[101]), "+f"(d[102]), "+f"(d[103]), "+f"(d[104]), "+f"(d[105]), "+f"(d[106]), "+f"(d[107]), "+f"(d[108]), "+f"(d[109]), "+f"(d[110]), "+f"(d[111]), "+f"(d[112]), "+f"(d[113]), "+f"(d[114]), "+f"(d[115]), "+f"(d[116]), "+f"(d[117]), "+f"(d[118]), "+f"(d[119]), "+f"(d[120]), "+f"(d[121]), "+f"(d[122]), "+f"(d[123]), "+f"(d[124]), "+f"(d[125]), "+f"(d[126]), "+f"(d[127])
    : "l"(da), "l"(db), "r"(scale_d));
}
__device__ __forceinline__ void wgmma_n128(float (&d)[192], uint64_t da, uint64_t db, int scale_d) {
  asm volatile("{\n.reg .pred p;\nsetp.ne.b32 p, %66, 0;\n"
    "wgmma.mma_async.sync.aligned.m64n128k16.f32.bf16.bf16 {%0, %1, %2, %3, %4, %5, %6, %7, %8, %9, %10, %11, %12, %13, %14, %15, %16, %17, %18, %19, %20, %21, %22, %23, %24, %25, %26, %27, %28, %29, %30, %31, %32, %33, %34, %35, %36, %37, %38, %39, %40, %41, %42, %43, %44, %45, %46, %47, %48, %49, %50, %51, %52, %53, %54, %55, %56, %57, %58, %59, %60, %61, %62, %63}, %64, %65, p, 1, 1, 0, 1;\n}\n"
    : "+f"(d[128]), "+f"(d[129]), "+f"(d[130]), "+f"(d[131]), "+f"(d[132]), "+f"(d[133]), "+f"(d[134]), "+f"(d[135]), "+f"(d[136]), "+f"(d[137]), "+f"(d[138]), "+f"(d[139]), "+f"(d[140]), "+f"(d[141]), "+f"(d[142]), "+f"(d[143]), "+f"(d[144]), "+f"(d[145]), "+f"(d[146]), "+f"(d[147]), "+f"(d[148]), "+f"(d[149]), "+f"(d[150]), "+f"(d[151]), "+f"(d[152]), "+f"(d[153]), "+f"(d[154]), "+f"(d[155]), "+f"(d[156]), "+f"(d[157]), "+f"(d[158]), "+f"(d[159]), "+f"(d[160]), "+f"(d[161]), "+f"(d[162]), "+f"(d[163]), "+f"(d[164]), "+f"(d[165]), "+f"(d[166]), "+f"(d[167]), "+f"(d[168]), "+f"(d[169]), "+f"(d[170]), "+f"(d[171]), "+f"(d[172]), "+f"(d[173]), "+f"(d[174]), "+f"(d[175]), "+f"(d[176]), "+f"(d[177]), "+f"(d[178]), "+f"(d[179]), "+f"(d[180]), "+f"(d[181]), "+f"(d[182]), "+f"(d[183]), "+f"(d[184]), "+f"(d[185]), "+f"(d[186]), "+f"(d[187]), "+f"(d[188]), "+f"(d[189]), "+f"(d[190]), "+f"(d[191])
    : "l"(da), "l"(db), "r"(scale_d));
}
__device__ __forceinline__ void wgmma_n256_k(float (&d)[192], uint64_t da, uint64_t db, int scale_d) {
  asm volatile("{\n.reg .pred p;\nsetp.ne.b32 p, %130, 0;\n"
    "wgmma.mma_async.sync.aligned.m64n256k16.f32.bf16.bf16 {%0, %1, %2, %3, %4, %5, %6, %7, %8, %9, %10, %11, %12, %13, %14, %15, %16, %17, %18, %19, %20, %21, %22, %23, %24, %25, %26, %27, %28, %29, %30, %31, %32, %33, %34, %35, %36, %37, %38, %39, %40, %41, %42, %43, %44, %45, %46, %47, %48, %49, %50, %51, %52, %53, %54, %55, %56, %57, %58, %59, %60, %61, %62, %63, %64, %65, %66, %67, %68, %69, %70, %71, %72, %73, %74, %75, %76, %77, %78, %79, %80, %81, %82, %83, %84, %85, %86, %87, %88, %89, %90, %91, %92, %93, %94, %95, %96, %97, %98, %99, %100, %101, %102, %103, %104, %105, %106, %107, %108, %109, %110, %111, %112, %113, %114, %115, %116, %117, %118, %119, %120, %121, %122, %123, %124, %125, %126, %127}, %128, %129, p, 1, 1, 0, 0;\n}\n"
    : "+f"(d[0]), "+f"(d[1]), "+f"(d[2]), "+f"(d[3]), "+f"(d[4]), "+f"(d[5]), "+f"(d[6]), "+f"(d[7]), "+f"(d[8]), "+f"(d[9]), "+f"(d[10]), "+f"(d[11]), "+f"(d[12]), "+f"(d[13]), "+f"(d[14]), "+f"(d[15]), "+f"(d[16]), "+f"(d[17]), "+f"(d[18]), "+f"(d[19]), "+f"(d[20]), "+f"(d[21]), "+f"(d[22]), "+f"(d[23]), "+f"(d[24]), "+f"(d[25]), "+f"(d[26]), "+f"(d[27]), "+f"(d[28]), "+f"(d[29]), "+f"(d[30]), "+f"(d[31]), "+f"(d[32]), "+f"(d[33]), "+f"(d[34]), "+f"(d[35]), "+f"(d[36]), "+f"(d[37]), "+f"(d[38]), "+f"(d[39]), "+f"(d[40]), "+f"(d[41]), "+f"(d[42]), "+f"(d[43]), "+f"(d[44]), "+f"(d[45]), "+f"(d[46]), "+f"(d[47]), "+f"(d[48]), "+f"(d[49]), "+f"(d[50]), "+f"(d[51]), "+f"(d[52]), "+f"(d[53]), "+f"(d[54]), "+f"(d[55]), "+f"(d[56]), "+f"(d[57]), "+f"(d[58]), "+f"(d[59]), "+f"(d[60]), "+f"(d[61]), "+f"(d[62]), "+f"(d[63]), "+f"(d[64]), "+f"(d[65]), "+f"(d[66]), "+f"(d[67]), "+f"(d[68]), "+f"(d[69]), "+f"(d[70]), "+f"(d[71]), "+f"(d[72]), "+f"(d[73]), "+f"(d[74]), "+f"(d[75]), "+f"(d[76]), "+f"(d[77]), "+f"(d[78]), "+f"(d[79]), "+f"(d[80]), "+f"(d[81]), "+f"(d[82]), "+f"(d[83]), "+f"(d[84]), "+f"(d[85]), "+f"(d[86]), "+f"(d[87]), "+f"(d[88]), "+f"(d[89]), "+f"(d[90]), "+f"(d[91]), "+f"(d[92]), "+f"(d[93]), "+f"(d[94]), "+f"(d[95]), "+f"(d[96]), "+f"(d[97]), "+f"(d[98]), "+f"(d[99]), "+f"(d[100]), "+f"(d[101]), "+f"(d[102]), "+f"(d[103]), "+f"(d[104]), "+f"(d[105]), "+f"(d[106]), "+f"(d[107]), "+f"(d[108]), "+f"(d[109]), "+f"(d[110]), "+f"(d[111]), "+f"(d[112]), "+f"(d[113]), "+f"(d[114]), "+f"(d[115]), "+f"(d[116]), "+f"(d[117]), "+f"(d[118]), "+f"(d[119]), "+f"(d[120]), "+f"(d[121]), "+f"(d[122]), "+f"(d[123]), "+f"(d[124]), "+f"(d[125]), "+f"(d[126]), "+f"(d[127])
    : "l"(da), "l"(db), "r"(scale_d));
}
__device__ __forceinline__ void wgmma_n128_k(float (&d)[192], uint64_t da, uint64_t db, int scale_d) {
  asm volatile("{\n.reg .pred p;\nsetp.ne.b32 p, %66, 0;\n"
    "wgmma.mma_async.sync.aligned.m64n128k16.f32.bf16.bf16 {%0, %1, %2, %3, %4, %5, %6, %7, %8, %9, %10, %11, %12, %13, %14, %15, %16, %17, %18, %19, %20, %21, %22, %23, %24, %25, %26, %27, %28, %29, %30, %31, %32, %33, %34, %35, %36, %37, %38, %39, %40, %41, %42, %43, %44, %45, %46, %47, %48, %49, %50, %51, %52, %53, %54, %55, %56, %57, %58, %59, %60, %61, %62, %63}, %64, %65, p, 1, 1, 0, 0;\n}\n"
    : "+f"(d[128]), "+f"(d[129]), "+f"(d[130]), "+f"(d[131]), "+f"(d[132]), "+f"(d[133]), "+f"(d[134]), "+f"(d[135]), "+f"(d[136]), "+f"(d[137]), "+f"(d[138]), "+f"(d[139]), "+f"(d[140]), "+f"(d[141]), "+f"(d[142]), "+f"(d[143]), "+f"(d[144]), "+f"(d[145]), "+f"(d[146]), "+f"(d[147]), "+f"(d[148]), "+f"(d[149]), "+f"(d[150]), "+f"(d[151]), "+f"(d[152]), "+f"(d[153]), "+f"(d[154]), "+f"(d[155]), "+f"(d[156]), "+f"(d[157]), "+f"(d[158]), "+f"(d[159]), "+f"(d[160]), "+f"(d[161]), "+f"(d[162]), "+f"(d[163]), "+f"(d[164]), "+f"(d[165]), "+f"(d[166]), "+f"(d[167]), "+f"(d[168]), "+f"(d[169]), "+f"(d[170]), "+f"(d[171]), "+f"(d[172]), "+f"(d[173]), "+f"(d[174]), "+f"(d[175]), "+f"(d[176]), "+f"(d[177]), "+f"(d[178]), "+f"(d[179]), "+f"(d[180]), "+f"(d[181]), "+f"(d[182]), "+f"(d[183]), "+f"(d[184]), "+f"(d[185]), "+f"(d[186]), "+f"(d[187]), "+f"(d[188]), "+f"(d[189]), "+f"(d[190]), "+f"(d[191])
    : "l"(da), "l"(db), "r"(scale_d));
}
__device__ __forceinline__ void wgmma_n40_tt(float (&d)[20], uint64_t da, uint64_t db, int scale_d) {
  asm volatile("{\n.reg .pred p;\nsetp.ne.b32 p, %22, 0;\n"
    "wgmma.mma_async.sync.aligned.m64n40k16.f32.bf16.bf16 {%0, %1, %2, %3, %4, %5, %6, %7, %8, %9, %10, %11, %12, %13, %14, %15, %16, %17, %18, %19}, %20, %21, p, 1, 1, 1, 1;\n}\n"
    : "+f"(d[0]), "+f"(d[1]), "+f"(d[2]), "+f"(d[3]), "+f"(d[4]), "+f"(d[5]), "+f"(d[6]), "+f"(d[7]), "+f"(d[8]), "+f"(d[9]), "+f"(d[10]), "+f"(d[11]), "+f"(d[12]), "+f"(d[13]), "+f"(d[14]), "+f"(d[15]), "+f"(d[16]), "+f"(d[17]), "+f"(d[18]), "+f"(d[19])
    : "l"(da), "l"(db), "r"(scale_d));
}
__device__ __forceinline__ void wgmma_n40_rs(float (&d)[20], const uint32_t (&a)[4], uint64_t db, int scale_d) {
  asm volatile("{\n.reg .pred p;\nsetp.ne.b32 p, %25, 0;\n"
    "wgmma.mma_async.sync.aligned.m64n40k16.f32.bf16.bf16 {%0, %1, %2, %3, %4, %5, %6, %7, %8, %9, %10, %11, %12, %13, %14, %15, %16, %17, %18, %19}, {%20, %21, %22, %23}, %24, p, 1, 1, 1;\n}\n"
    : "+f"(d[0]), "+f"(d[1]), "+f"(d[2]), "+f"(d[3]), "+f"(d[4]), "+f"(d[5]), "+f"(d[6]), "+f"(d[7]), "+f"(d[8]), "+f"(d[9]), "+f"(d[10]), "+f"(d[11]), "+f"(d[12]), "+f"(d[13]), "+f"(d[14]), "+f"(d[15]), "+f"(d[16]), "+f"(d[17]), "+f"(d[18]), "+f"(d[19])
    : "r"(a[0]), "r"(a[1]), "r"(a[2]), "r"(a[3]), "l"(db), "r"(scale_d));
}
__device__ __forceinline__ void wgmma_n128_0(float (&d)[192], uint64_t da, uint64_t db) {
  asm volatile("{\n.reg .pred p;\nsetp.ne.b32 p, 0, 0;\n"
    "wgmma.mma_async.sync.aligned.m64n128k16.f32.bf16.bf16 {%0, %1, %2, %3, %4, %5, %6, %7, %8, %9, %10, %11, %12, %13, %14, %15, %16, %17, %18, %19, %20, %21, %22, %23, %24, %25, %26, %27, %28, %29, %30, %31, %32, %33, %34, %35, %36, %37, %38, %39, %40, %41, %42, %43, %44, %45, %46, %47, %48, %49, %50, %51, %52, %53, %54, %55, %56, %57, %58, %59, %60, %61, %62, %63}, %64, %65, p, 1, 1, 0, 1;\n}\n"
    : "=f"(d[128]), "=f"(d[129]), "=f"(d[130]), "=f"(d[131]), "=f"(d[132]), "=f"(d[133]), "=f"(d[134]), "=f"(d[135]), "=f"(d[136]), "=f"(d[137]), "=f"(d[138]), "=f"(d[139]), "=f"(d[140]), "=f"(d[141]), "=f"(d[142]), "=f"(d[143]), "=f"(d[144]), "=f"(d[145]), "=f"(d[146]), "=f"(d[147]), "=f"(d[148]), "=f"(d[149]), "=f"(d[150]), "=f"(d[151]), "=f"(d[152]), "=f"(d[153]), "=f"(d[154]), "=f"(d[155]), "=f"(d[156]), "=f"(d[157]), "=f"(d[158]), "=f"(d[159]), "=f"(d[160]), "=f"(d[161]), "=f"(d[162]), "=f"(d[163]), "=f"(d[164]), "=f"(d[165]), "=f"(d[166]), "=f"(d[167]), "=f"(d[168]), "=f"(d[169]), "=f"(d[170]), "=f"(d[171]), "=f"(d[172]), "=f"(d[173]), "=f"(d[174]), "=f"(d[175]), "=f"(d[176]), "=f"(d[177]), "=f"(d[178]), "=f"(d[179]), "=f"(d[180]), "=f"(d[181]), "=f"(d[182]), "=f"(d[183]), "=f"(d[184]), "=f"(d[185]), "=f"(d[186]), "=f"(d[187]), "=f"(d[188]), "=f"(d[189]), "=f"(d[190]), "=f"(d[191])
    : "l"(da), "l"(db));
}
__device__ __forceinline__ void wgmma_n128_rs(float (&d)[192], const uint32_t (&a)[4], uint64_t db, int scale_d) {
  asm volatile("{\n.reg .pred p;\nsetp.ne.b32 p, %69, 0;\n"
    "wgmma.mma_async.sync.aligned.m64n128k16.f32.bf16.bf16 {%0, %1, %2, %3, %4, %5, %6, %7, %8, %9, %10, %11, %12, %13, %14, %15, %16, %17, %18, %19, %20, %21, %22, %23, %24, %25, %26, %27, %28, %29, %30, %31, %32, %33, %34, %35, %36, %37, %38, %39, %40, %41, %42, %43, %44, %45, %46, %47, %48, %49, %50, %51, %52, %53, %54, %55, %56, %57, %58, %59, %60, %61, %62, %63}, {%64, %65, %66, %67}, %68, p, 1, 1, 1;\n}\n"
    : "+f"(d[128]), "+f"(d[129]), "+f"(d[130]), "+f"(d[131]), "+f"(d[132]), "+f"(d[133]), "+f"(d[134]), "+f"(d[135]), "+f"(d[136]), "+f"(d[137]), "+f"(d[138]), "+f"(d[139]), "+f"(d[140]), "+f"(d[141]), "+f"(d[142]), "+f"(d[143]), "+f"(d[144]), "+f"(d[145]), "+f"(d[146]), "+f"(d[147]), "+f"(d[148]), "+f"(d[149]), "+f"(d[150]), "+f"(d[151]), "+f"(d[152]), "+f"(d[153]), "+f"(d[154]), "+f"(d[155]), "+f"(d[156]), "+f"(d[157]), "+f"(d[158]), "+f"(d[159]), "+f"(d[160]), "+f"(d[161]), "+f"(d[162]), "+f"(d[163]), "+f"(d[164]), "+f"(d[165]), "+f"(d[166]), "+f"(d[167]), "+f"(d[168]), "+f"(d[169]), "+f"(d[170]), "+f"(d[171]), "+f"(d[172]), "+f"(d[173]), "+f"(d[174]), "+f"(d[175]), "+f"(d[176]), "+f"(d[177]), "+f"(d[178]), "+f"(d[179]), "+f"(d[180]), "+f"(d[181]), "+f"(d[182]), "+f"(d[183]), "+f"(d[184]), "+f"(d[185]), "+f"(d[186]), "+f"(d[187]), "+f"(d[188]), "+f"(d[189]), "+f"(d[190]), "+f"(d[191])
    : "r"(a[0]), "r"(a[1]), "r"(a[2]), "r"(a[3]), "l"(db), "r"(scale_d));
}
__device__ __forceinline__ void wgmma_n32_0(float (&d)[16], uint64_t da, uint64_t db) {
  asm volatile("{\n.reg .pred p;\nsetp.ne.b32 p, 0, 0;\n"
    "wgmma.mma_async.sync.aligned.m64n32k16.f32.bf16.bf16 {%0, %1, %2, %3, %4, %5, %6, %7, %8, %9, %10, %11, %12, %13, %14, %15}, %16, %17, p, 1, 1, 0, 1;\n}\n"
    : "=f"(d[0]), "=f"(d[1]), "=f"(d[2]), "=f"(d[3]), "=f"(d[4]), "=f"(d[5]), "=f"(d[6]), "=f"(d[7]), "=f"(d[8]), "=f"(d[9]), "=f"(d[10]), "=f"(d[11]), "=f"(d[12]), "=f"(d[13]), "=f"(d[14]), "=f"(d[15])
    : "l"(da), "l"(db));
}
__device__ __forceinline__ void wgmma_n32(float (&d)[16], uint64_t da, uint64_t db, int scale_d) {
  asm volatile("{\n.reg .pred p;\nsetp.ne.b32 p, %18, 0;\n"
    "wgmma.mma_async.sync.aligned.m64n32k16.f32.bf16.bf16 {%0, %1, %2, %3, %4, %5, %6, %7, %8, %9, %10, %11, %12, %13, %14, %15}, %16, %17, p, 1, 1, 0, 1;\n}\n"
    : "+f"(d[0]), "+f"(d[1]), "+f"(d[2]), "+f"(d[3]), "+f"(d[4]), "+f"(d[5]), "+f"(d[6]), "+f"(d[7]), "+f"(d[8]), "+f"(d[9]), "+f"(d[10]), "+f"(d[11]), "+f"(d[12]), "+f"(d[13]), "+f"(d[14]), "+f"(d[15])
    : "l"(da), "l"(db), "r"(scale_d));
}
__device__ __forceinline__ void wgmma_n8_t(float (&d)[4], uint64_t da, uint64_t db, int scale_d) {
  asm volatile("{\n.reg .pred p;\nsetp.ne.b32 p, %6, 0;\n"
    "wgmma.mma_async.sync.aligned.m64n8k16.f32.bf16.bf16 {%0, %1, %2, %3}, %4, %5, p, 1, 1, 1, 0;\n}\n"
    : "+f"(d[0]), "+f"(d[1]), "+f"(d[2]), "+f"(d[3])
    : "l"(da), "l"(db), "r"(scale_d));
}
__device__ __forceinline__ void wgmma_n128_rs0(float (&d)[192], const uint32_t (&a)[4], uint64_t db) {
  asm volatile("{\n.reg .pred p;\nsetp.ne.b32 p, 0, 0;\n"
    "wgmma.mma_async.sync.aligned.m64n128k16.f32.bf16.bf16 {%0, %1, %2, %3, %4, %5, %6, %7, %8, %9, %10, %11, %12, %13, %14, %15, %16, %17, %18, %19, %20, %21, %22, %23, %24, %25, %26, %27, %28, %29, %30, %31, %32, %33, %34, %35, %36, %37, %38, %39, %40, %41, %42, %43, %44, %45, %46, %47, %48, %49, %50, %51, %52, %53, %54, %55, %56, %57, %58, %59, %60, %61, %62, %63}, {%64, %65, %66, %67}, %68, p, 1, 1, 1;\n}\n"
    : "=f"(d[128]), "=f"(d[129]), "=f"(d[130]), "=f"(d[131]), "=f"(d[132]), "=f"(d[133]), "=f"(d[134]), "=f"(d[135]), "=f"(d[136]), "=f"(d[137]), "=f"(d[138]), "=f"(d[139]), "=f"(d[140]), "=f"(d[141]), "=f"(d[142]), "=f"(d[143]), "=f"(d[144]), "=f"(d[145]), "=f"(d[146]), "=f"(d[147]), "=f"(d[148]), "=f"(d[149]), "=f"(d[150]), "=f"(d[151]), "=f"(d[152]), "=f"(d[153]), "=f"(d[154]), "=f"(d[155]), "=f"(d[156]), "=f"(d[157]), "=f"(d[158]), "=f"(d[159]), "=f"(d[160]), "=f"(d[161]), "=f"(d[162]), "=f"(d[163]), "=f"(d[164]), "=f"(d[165]), "=f"(d[166]), "=f"(d[167]), "=f"(d[168]), "=f"(d[169]), "=f"(d[170]), "=f"(d[171]), "=f"(d[172]), "=f"(d[173]), "=f"(d[174]), "=f"(d[175]), "=f"(d[176]), "=f"(d[177]), "=f"(d[178]), "=f"(d[179]), "=f"(d[180]), "=f"(d[181]), "=f"(d[182]), "=f"(d[183]), "=f"(d[184]), "=f"(d[185]), "=f"(d[186]), "=f"(d[187]), "=f"(d[188]), "=f"(d[189]), "=f"(d[190]), "=f"(d[191])
    : "r"(a[0]), "r"(a[1]), "r"(a[2]), "r"(a[3]), "l"(db));
}
__device__ __forceinline__ void wgmma_n256_rs(float (&d)[192], const uint32_t (&a)[4], uint64_t db, int scale_d) {
  asm volatile("{\n.reg .pred p;\nsetp.ne.b32 p, %133, 0;\n"
    "wgmma.mma_async.sync.aligned.m64n256k16.f32.bf16.bf16 {%0, %1, %2, %3, %4, %5, %6, %7, %8, %9, %10, %11, %12, %13, %14, %15, %16, %17, %18, %19, %20, %21, %22, %23, %24, %25, %26, %27, %28, %29, %30, %31, %32, %33, %34, %35, %36, %37, %38, %39, %40, %41, %42, %43, %44, %45, %46, %47, %48, %49, %50, %51, %52, %53, %54, %55, %56, %57, %58, %59, %60, %61, %62, %63, %64, %65, %66, %67, %68, %69, %70, %71, %72, %73, %74, %75, %76, %77, %78, %79, %80, %81, %82, %83, %84, %85, %86, %87, %88, %89, %90, %91, %92, %93, %94, %95, %96, %97, %98, %99, %100, %101, %102, %103, %104, %105, %106, %107, %108, %109, %110, %111, %112, %113, %114, %115, %116, %117, %118, %119, %120, %121, %122, %123, %124, %125, %126, %127}, {%128, %129, %130, %131}, %132, p, 1, 1, 1;\n}\n"
    : "+f"(d[0]), "+f"(d[1]), "+f"(d[2]), "+f"(d[3]), "+f"(d[4]), "+f"(d[5]), "+f"(d[6]), "+f"(d[7]), "+f"(d[8]), "+f"(d[9]), "+f"(d[10]), "+f"(d[11]), "+f"(d[12]), "+f"(d[13]), "+f"(d[14]), "+f"(d[15]), "+f"(d[16]), "+f"(d[17]), "+f"(d[18]), "+f"(d[19]), "+f"(d[20]), "+f"(d[21]), "+f"(d[22]), "+f"(d[23]), "+f"(d[24]), "+f"(d[25]), "+f"(d[26]), "+f"(d[27]), "+f"(d[28]), "+f"(d[29]), "+f"(d[30]), "+f"(d[31]), "+f"(d[32]), "+f"(d[33]), "+f"(d[34]), "+f"(d[35]), "+f"(d[36]), "+f"(d[37]), "+f"(d[38]), "+f"(d[39]), "+f"(d[40]), "+f"(d[41]), "+f"(d[42]), "+f"(d[43]), "+f"(d[44]), "+f"(d[45]), "+f"(d[46]), "+f"(d[47]), "+f"(d[48]), "+f"(d[49]), "+f"(d[50]), "+f"(d[51]), "+f"(d[52]), "+f"(d[53]), "+f"(d[54]), "+f"(d[55]), "+f"(d[56]), "+f"(d[57]), "+f"(d[58]), "+f"(d[59]), "+f"(d[60]), "+f"(d[61]), "+f"(d[62]), "+f"(d[63]), "+f"(d[64]), "+f"(d[65]), "+f"(d[66]), "+f"(d[67]), "+f"(d[68]), "+f"(d[69]), "+f"(d[70]), "+f"(d[71]), "+f"(d[72]), "+f"(d[73]), "+f"(d[74]), "+f"(d[75]), "+f"(d[76]), "+f"(d[77]), "+f"(d[78]), "+f"(d[79]), "+f"(d[80]), "+f"(d[81]), "+f"(d[82]), "+f"(d[83]), "+f"(d[84]), "+f"(d[85]), "+f"(d[86]), "+f"(d[87]), "+f"(d[88]), "+f"(d[89]), "+f"(d[90]), "+f"(d[91]), "+f"(d[92]), "+f"(d[93]), "+f"(d[94]), "+f"(d[95]), "+f"(d[96]), "+f"(d[97]), "+f"(d[98]), "+f"(d[99]), "+f"(d[100]), "+f"(d[101]), "+f"(d[102]), "+f"(d[103]), "+f"(d[104]), "+f"(d[105]), "+f"(d[106]), "+f"(d[107]), "+f"(d[108]), "+f"(d[109]), "+f"(d[110]), "+f"(d[111]), "+f"(d[112]), "+f"(d[113]), "+f"(d[114]), "+f"(d[115]), "+f"(d[116]), "+f"(d[117]), "+f"(d[118]), "+f"(d[119]), "+f"(d[120]), "+f"(d[121]), "+f"(d[122]), "+f"(d[123]), "+f"(d[124]), "+f"(d[125]), "+f"(d[126]), "+f"(d[127])
    : "r"(a[0]), "r"(a[1]), "r"(a[2]), "r"(a[3]), "l"(db), "r"(scale_d));
}
__device__ __forceinline__ void wgmma_n256_rs0(float (&d)[192], const uint32_t (&a)[4], uint64_t db) {
  asm volatile("{\n.reg .pred p;\nsetp.ne.b32 p, 0, 0;\n"
    "wgmma.mma_async.sync.aligned.m64n256k16.f32.bf16.bf16 {%0, %1, %2, %3, %4, %5, %6, %7, %8, %9, %10, %11, %12, %13, %14, %15, %16, %17, %18, %19, %20, %21, %22, %23, %24, %25, %26, %27, %28, %29, %30, %31, %32, %33, %34, %35, %36, %37, %38, %39, %40, %41, %42, %43, %44, %45, %46, %47, %48, %49, %50, %51, %52, %53, %54, %55, %56, %57, %58, %59, %60, %61, %62, %63, %64, %65, %66, %67, %68, %69, %70, %71, %72, %73, %74, %75, %76, %77, %78, %79, %80, %81, %82, %83, %84, %85, %86, %87, %88, %89, %90, %91, %92, %93, %94, %95, %96, %97, %98, %99, %100, %101, %102, %103, %104, %105, %106, %107, %108, %109, %110, %111, %112, %113, %114, %115, %116, %117, %118, %119, %120, %121, %122, %123, %124, %125, %126, %127}, {%128, %129, %130, %131}, %132, p, 1, 1, 1;\n}\n"
    : "=f"(d[0]), "=f"(d[1]), "=f"(d[2]), "=f"(d[3]), "=f"(d[4]), "=f"(d[5]), "=f"(d[6]), "=f"(d[7]), "=f"(d[8]), "=f"(d[9]), "=f"(d[10]), "=f"(d[11]), "=f"(d[12]), "=f"(d[13]), "=f"(d[14]), "=f"(d[15]), "=f"(d[16]), "=f"(d[17]), "=f"(d[18]), "=f"(d[19]), "=f"(d[20]), "=f"(d[21]), "=f"(d[22]), "=f"(d[23]), "=f"(d[24]), "=f"(d[25]), "=f"(d[26]), "=f"(d[27]), "=f"(d[28]), "=f"(d[29]), "=f"(d[30]), "=f"(d[31]), "=f"(d[32]), "=f"(d[33]), "=f"(d[34]), "=f"(d[35]), "=f"(d[36]), "=f"(d[37]), "=f"(d[38]), "=f"(d[39]), "=f"(d[40]), "=f"(d[41]), "=f"(d[42]), "=f"(d[43]), "=f"(d[44]), "=f"(d[45]), "=f"(d[46]), "=f"(d[47]), "=f"(d[48]), "=f"(d[49]), "=f"(d[50]), "=f"(d[51]), "=f"(d[52]), "=f"(d[53]), "=f"(d[54]), "=f"(d[55]), "=f"(d[56]), "=f"(d[57]), "=f"(d[58]), "=f"(d[59]), "=f"(d[60]), "=f"(d[61]), "=f"(d[62]), "=f"(d[63]), "=f"(d[64]), "=f"(d[65]), "=f"(d[66]), "=f"(d[67]), "=f"(d[68]), "=f"(d[69]), "=f"(d[70]), "=f"(d[71]), "=f"(d[72]), "=f"(d[73]), "=f"(d[74]), "=f"(d[75]), "=f"(d[76]), "=f"(d[77]), "=f"(d[78]), "=f"(d[79]), "=f"(d[80]), "=f"(d[81]), "=f"(d[82]), "=f"(d[83]), "=f"(d[84]), "=f"(d[85]), "=f"(d[86]), "=f"(d[87]), "=f"(d[88]), "=f"(d[89]), "=f"(d[90]), "=f"(d[91]), "=f"(d[92]), "=f"(d[93]), "=f"(d[94]), "=f"(d[95]), "=f"(d[96]), "=f"(d[97]), "=f"(d[98]), "=f"(d[99]), "=f"(d[100]), "=f"(d[101]), "=f"(d[102]), "=f"(d[103]), "=f"(d[104]), "=f"(d[105]), "=f"(d[106]), "=f"(d[107]), "=f"(d[108]), "=f"(d[109]), "=f"(d[110]), "=f"(d[111]), "=f"(d[112]), "=f"(d[113]), "=f"(d[114]), "=f"(d[115]), "=f"(d[116]), "=f"(d[117]), "=f"(d[118]), "=f"(d[119]), "=f"(d[120]), "=f"(d[121]), "=f"(d[122]), "=f"(d[123]), "=f"(d[124]), "=f"(d[125]), "=f"(d[126]), "=f"(d[127])
    : "r"(a[0]), "r"(a[1]), "r"(a[2]), "r"(a[3]), "l"(db));
}

constexpr int SLOT = 16384;
constexpr int VB = 4 * SLOT, PH = 0, XS = 6;
constexpr int SM_SD = 13 * SLOT;
constexpr int SM_BAR = SM_SD + 8192;
constexpr int SM_RS = SM_BAR + 1024;
constexpr int SM_AP = SM_RS + 640;
constexpr int SM_BP = SM_AP + 2048;
constexpr int SM_EPOCH = SM_BP + 6144;
constexpr int SM_TOTAL = SM_EPOCH + 16;
constexpr int FM = 0, FT = 16, FW = 30, CM = 46, CT = 62, CW = 76, B_EF = 92, B_STAT = 93, B_KVF = 94, B_HALO = 95,
              B_KVDONE = 96, B_OH0 = 97, B_OH1 = 98, B_XH0 = 99, B_XDONE = 100, B_WFD = 101, B_XT = 102, B_OF0 = 103, B_KVF1 = 104, B_KVS = 105, B_RAW = 106  , B_X0 = 108, B_KVS0 = 109;
constexpr uint64_t BAR_LG = 0x00043333330004ull;
#define BA(i) (bar + (i) * 8)
#define REL2(i) release2c(SB0 + SM_BAR + (i) * 8)
constexpr int NF = 3, ND = 13, NR = 0, NWOP = 48, NAOP = 38;
constexpr bool EF_USED = false;
constexpr uint64_t TL_A = 0x6278627862786ull, TL_B = 0xa9c3ba9c3ba9cull, WO_A = 0x76b24038b51403ffull, WO_B = 0x8c5a197c6a297c8bull;
__constant__ uint32_t c_wop[NWOP + 1] = {0xeb0009, 0x186b8000, 0x6c0112, 0x1aec011a, 0x6c8224, 0x22ec822b, 0x18170330, 0x18178442, 0x18180554, 0x18188660, 0x18190772, 0x18198884, 0x181a0990, 0x181a8aa2, 0x181b0bb4, 0x181b8cc0, 0xaed10fc, 0xa9711e9, 0x181c0dd2, 0xa9792da, 0x129813cb, 0x181c8ee4, 0x181d0ff0, 0x109d94b3, 0x109f15ac, 0x109f9699, 0x10a0178a, 0x10a0987b, 0x10a11963, 0x10a19a5c, 0x10a21b49, 0x10a29c3a, 0x9231e0b, 0x9239f18, 0x1124202c, 0x13242137, 0x1124a249, 0x1324a352, 0x1125246a, 0x13252576, 0x1127268c, 0x1127a797, 0x112828a9, 0x1128a9b1, 0x11292aca, 0x13292bd5, 0x112a2cec, 0x132a2df8, 0};
__constant__ uint32_t c_aop[NAOP + 1] = {0x6d8228, 0x170336, 0x178447, 0x180558, 0x188666, 0x190777, 0x198888, 0x1a0996, 0x1a8aa7, 0x1b0bb8, 0x1b8cc6, 0x1c0dd7, 0x1c8ee8, 0x1d0ff6, 0x1d93c2, 0x1f14b6, 0x1f95a8, 0x201697, 0x209782, 0x211876, 0x219968, 0x221a57, 0x229b42, 0x231c36, 0xa3a023, 0xb12130, 0x2b12244, 0x2b12351, 0x2b12465, 0xa6257b, 0xa6a688, 0xa72793, 0xa7a8a0, 0xa829b4, 0xa8aac2, 0xa9abdb, 0x2a9ace6, 0xaaadf7, 0};
__constant__ uint32_t c_map[64] = {4, 5, 6, 7, 0, 16, 32, 48, 64, 80, 96, 112, 1, 17, 33, 49, 65, 81, 97, 113, 2, 18, 34, 50, 66, 82, 98, 114, 3, 19, 35, 51, 67, 83, 99, 115, 20, 36, 52, 68, 84, 100, 116, 21, 37, 53, 69, 85, 101, 117, 22, 38, 54, 70, 86, 102, 118, 23, 39, 55, 71, 87, 103, 119};
enum { MAP_WF = 0, MAP_WA = 2, MAP_WB = 4, MAP_WOA = 6, MAP_WOB = 8, MAP_X0 = 10, MAP_X = 11, MAP_O = 12, MAP_PHI = 13, NMAP = 14 };
struct Maps { CUtensorMap m[NMAP]; };

#define PL 2
#define PROFL(a, b)
#define SUBS 8
#define QORD 1
#define NCH 4
#define CHW 1
#define SUBS1 12
#define XRAT 10
#define XRN 4
#define BT1 1
#define CV0 0
#define ST1 8
#define X0AT 1
#define W1DL 400
#define SKA 0
#define SKB 0
#define BPRE 0
#define XST 3
#define WH 4
#define PFM 3
#define PFS 2
#define NLAYERS 4
constexpr float L2E = 1.4426950408889634f;

#define D128(lo) desc64(lo, 0x40000040u)
struct Ctx { uint32_t zero, boff; const bf16* x0; bf16* out; };
#define BLK_CTX() \
  uint32_t bid_; asm volatile("mov.u32 %0, %%ctaid.x;" : "=r"(bid_)); \
  bid_ -= c.boff; \
  const uint32_t gr_ = c_map[bid_ >> 1]; \
  const int cr = bid_ & 1, g = gr_ & 7, rb = (gr_ >> 3) + cr, m0 = rb * 128; \
  const uint32_t sb = SB0 + (cr << 24); \
  const uint32_t bar = sb + SM_BAR; \
  (void)cr; (void)g; (void)rb; (void)m0; (void)bar;
extern __shared__ uint8_t smem_raw[];
constexpr uint32_t SB0 = 1024;

#define PHASE_CTX() \
  BLK_CTX(); \
  int tid_ = threadIdx.x; asm volatile("" : "+r"(tid_)); \
  const int lane = tid_ & 31, cw = (tid_ >> 5) - 4, wg = cw >> 2, wq = cw & 3, gq = lane >> 2, t = lane & 3, wrow0 = cw * 16; \
  const int lrow = (lane & 7) + ((lane >> 3) & 1) * 8, lchk = lane >> 4; \
  const bool elected = (tid_ & 127) == 0; \
  const uint32_t rowo = (wrow0 + lrow) * 128, X = (lchk ^ (lane & 7)) << 4; \
  const uint32_t Y = (wrow0 + (lane & 7)) * 128 + (((lane >> 3) ^ (lane & 7)) << 4); \
  const size_t gfr = (size_t)(m0 + wrow0 + gq) * D_ + g * 128 + 8 * t; \
  (void)bar; (void)wq; (void)gq; (void)lrow; (void)lchk; (void)elected; (void)wrow0; (void)wg; (void)rowo; (void)X; (void)t; (void)Y; (void)gfr;
#define MMA_CTX() \
  const uint32_t wu = __shfl_sync(0xffffffffu, wg, 0); \
  const uint32_t dA0 = ((SB0 >> 4) | (1u << 16)) + wu * 512, dB0 = (SB0 >> 4) | (512u << 16); \
  const uint32_t par = layer & 1;

__device__ __forceinline__ void slab_out_half(uint32_t slot, bf16* dst, int wrow0, int lane) {
  const int r0 = lane >> 3, ch = lane & 7;
  const uint32_t src = slot + (wrow0 + r0) * 128;
  uint4 v[4];
#pragma unroll
  for (int i = 0; i < 4; ++i) v[i] = lds128(src + i * 512 + (((ch ^ (4 * i + r0)) & 7) << 4));
  dst += (size_t)(wrow0 + r0) * D_ + ch * 8;
#pragma unroll
  for (int i = 0; i < 4; ++i) *reinterpret_cast<uint4*>(dst + (size_t)i * 4 * D_) = v[i];
}

__device__ __forceinline__ void consumer(const Ctx& c) {
  float acc[192];
  uint32_t xf[4][4];
  uint32_t xp[8][4];
  {
    PHASE_CTX();
    const unsigned int epoch = ld_relaxed(&g_epoch);
    PROFT(tid_ == 128, 0);
    const uint32_t wu = __shfl_sync(0xffffffffu, wg, 0);
    if (tid_ < 128 + 8) sts128(sb + SM_AP + lane * 16, make_uint4(0x3F803F80u, 0x3F803F80u, 0x3F803F80u, 0x3F803F80u));
#pragma unroll 1
    for (int it = 0; it < 2; ++it) {
      float p[4][16];
      mbar_wait(BA(B_RAW + it), 0);
      PROFT(tid_ == 128, it ? 15 : 2);
      const uint32_t da = ((SB0 >> 4) | (1u << 16)) + (wu ? 9 + it : 2 * it) * 1024, db = (SB0 + SM_SD) >> 4;
      wgmma_fence();
#pragma unroll
      for (int h = 0; h < 4; ++h) wgmma_n32_0(p[h], D128(da + (h >> 1) * 512 + (h & 1) * 4), desc64(db + h * 128, 0x80000020u));
#pragma unroll
      for (int h = 0; h < 4; ++h) wgmma_n32(p[h], D128(da + (h >> 1) * 512 + (h & 1) * 4 + 2), desc64(db + h * 128 + 64, 0x80000020u), 1);
      wgmma_commit();
      wgmma_wait<0>();
#pragma unroll
      for (int i = 0; i < 64; ++i) asm volatile("" : "+f"(p[i >> 4][i & 15]) :: "memory");
      const uint32_t base = sb + (wg ? 9 + it : 2 * it) * SLOT + (wq * 16 + gq) * 128;
      uint32_t w[4][4][2];
#pragma unroll
      for (int i = 0; i < 32; ++i) w[i >> 3][(i >> 1) & 3][i & 1] = pack_bf16(p[i >> 3][2 * (i & 7)], p[i >> 3][2 * (i & 7) + 1]);
      if (wu) {
#pragma unroll
        for (int i = 0; i < 8; ++i)
          sts128(base + (i >> 2) * 8192 + (i & 1) * 1024 + (((((i >> 1) & 1) * 4 + t) ^ gq) << 4), make_uint4(w[i >> 1][0][i & 1], w[i >> 1][1][i & 1], w[i >> 1][2][i & 1], w[i >> 1][3][i & 1]));
      } else {
#pragma unroll
        for (int i = 0; i < 16; ++i)
          sts64(base + (i >> 3) * 8192 + (i & 1) * 1024 + ((((t & 1) * 4 + ((i >> 1) & 3)) ^ gq) << 4) + (t >> 1) * 8, w[(i >> 3) * 2][(i >> 1) & 3][i & 1], w[(i >> 3) * 2 + 1][(i >> 1) & 3][i & 1]);
      }
      fence_async_smem();
      __syncwarp();
      if (it == cr && lane == 0) mbar_arrive(BA(B_WFD));
    }
    if (tid_ == 128) sts_f(sb + SM_EPOCH, __uint_as_float(epoch & 1));
#pragma unroll
    for (int i = 0; i < 32; ++i) xp[i >> 2][i & 3] = 0u;
    nbar<1, 256>();
    PROFT(tid_ == 128, 13);
    mbar_wait(BA(FM + cr), 0);
    float cs[3][4];
    wgmma_fence();
#pragma unroll
    for (int ks = 0; ks < 4; ++ks)
#pragma unroll
      for (int i = 0; i < 3; ++i) {
        const uint32_t bx = (i == 0 ? 2 * cr * 1024 : i == 1 ? (2 * cr + 1) * 1024 : (9 + cr) * 1024) + wu * 512;
        wgmma_n8_t(cs[i], D128(((SB0 >> 4) | (512u << 16)) + bx + ks * 128), desc64((SB0 + SM_AP) >> 4, 0), ks != 0);
      }
    wgmma_commit();
    mbar_wait(BA(FM), 0);
#pragma unroll
    for (int k = 0; k < 4; ++k) ldsm_x4(xf[k][0], xf[k][1], xf[k][2], xf[k][3], sb + XS * SLOT + rowo + (X ^ (k << 5)));
    wgmma_wait<0>();
#pragma unroll
    for (int i = 0; i < 12; ++i) asm volatile("" : "+f"(cs[i >> 2][i & 3]) :: "memory");
    if (t < 2) {
#pragma unroll
      for (int i = 0; i < 3; ++i) red_add1(g_cs + (epoch & 1) * 6144 + g * 384 + i * 128 + wg * 64 + wq * 16 + gq + t * 8, t ? cs[i][2] : cs[i][0]);
    }
    PROFT(tid_ == 128, 14);
  }
#pragma unroll 1
  for (int layer = 0;; ++layer) {
    {
      wgmma_fence();
      wgmma_n256_rs0(acc, xf[0], D128((SB0 >> 4) | (512u << 16)));
#pragma unroll
      for (int k = 1; k < 4; ++k) wgmma_n256_rs(acc, xf[k], D128(((SB0 >> 4) | (512u << 16)) + k * 128), 1);
      wgmma_commit();
      PHASE_CTX();
      MMA_CTX();
      {
        const uint32_t ep = __float_as_uint(lds_f(sb + SM_EPOCH));
        if (layer == 0) {
          mbar_wait(BA(B_X0), 0);
#pragma unroll
          for (int i = 0; i < 8; ++i) ldsm_x4(xp[i][0], xp[i][1], xp[i][2], xp[i][3], sb + (11 + (i >> 2)) * SLOT + (Y ^ ((i & 2) << 5)) + (i & 1) * 1024);
          if (lane == ((xp[0][0] ^ xp[1][0] ^ xp[2][0] ^ xp[3][0] ^ xp[7][0]) & c.zero)) REL2(B_XT);
        } else {
#pragma unroll
          for (int i = 0; i < 8; ++i) stsm_x4(sb + (XS + (i >> 2)) * SLOT + (Y ^ ((i & 2) << 5)) + (i & 1) * 1024, xp[i][0], xp[i][1], xp[i][2], xp[i][3]);
        }
        float s0 = 0.f, s1 = 0.f, q0 = 0.f, q1 = 0.f;
        auto stats = [&](int j0, int j1) {
#pragma unroll
          for (int j = j0; j < j1; ++j) {
            const uint32_t u0 = xp[(j >> 2) * 2][j & 3], u1 = xp[(j >> 2) * 2 + 1][j & 3];
            s0 += bf_lo(u0) + bf_hi(u0); s1 += bf_lo(u1) + bf_hi(u1);
            q0 = fmaf(bf_lo(u0), bf_lo(u0), fmaf(bf_hi(u0), bf_hi(u0), q0)); q1 = fmaf(bf_lo(u1), bf_lo(u1), fmaf(bf_hi(u1), bf_hi(u1), q1));
          }
        };
        stats(0, ST1);
        fence_async_smem();
        nbar_dyn(3 + wu + (__float_as_uint(s0 + s1 + q0 + q1) & c.zero), 128);
        mbar_wait(BA(FM + 1), par);
        wgmma_fence();
#pragma unroll
        for (int k = 0; k < 4; ++k) wgmma_n256(acc, D128(dA0 + (XS + 1) * 1024 + k * 2), D128(dB0 + 2048 + k * 128), 1);
        wgmma_commit();
        wgmma_wait<1>();
#pragma unroll
        for (int i = 4; i < 8; ++i) stg128_p(layer, g_x + gfr + (i & 1) * 8 * D_ + (i >> 1) * 32, xp[i][0], xp[i][1], xp[i][2], xp[i][3]);
        {
          uint32_t zc; asm volatile("mov.u32 %0, %%clock;" : "=r"(zc) :: "memory");
          q0 += __uint_as_float(zc & c.zero); q1 += __uint_as_float(zc & c.zero); s0 += __uint_as_float(zc & c.zero); s1 += __uint_as_float(zc & c.zero);
        }
        stats(ST1, 16);
        wgmma_fence();
        wgmma_n128_0(acc, D128(dA0 + XS * 1024), D128(dB0 + 9 * 1024));
#pragma unroll
        for (int k = 1; k < 4; ++k) wgmma_n128(acc, D128(dA0 + XS * 1024 + k * 2), D128(dB0 + 9 * 1024 + k * 128), 1);
        wgmma_commit();
        const bool od = t & 1;
        float sa = od ? s1 : s0, qa = od ? q1 : q0;
        sa += __shfl_xor_sync(0xffffffffu, od ? s0 : s1, 1);
        qa += __shfl_xor_sync(0xffffffffu, od ? q0 : q1, 1);
        wgmma_fence();
#pragma unroll
        for (int k = 0; k < 4; ++k) wgmma_n128(acc, D128(dA0 + (XS + 1) * 1024 + k * 2), D128(dB0 + 10 * 1024 + k * 128), 1);
        wgmma_commit();
        sa += __shfl_xor_sync(0xffffffffu, sa, 2);
        qa += __shfl_xor_sync(0xffffffffu, qa, 2);
        red_add2_p(t < 2, reinterpret_cast<float*>(g_stats + (ep * 4 + layer) * S_ + m0 + wrow0 + gq + t * 8), sa, qa);
        __syncwarp();
        if (lane == 0) mbar_arrive(BA(B_XDONE));
        wgmma_wait<1>();
        if (elected) REL2(CM);
      }
      uint32_t s = 2;
#pragma unroll 1
      for (int i = 2; i < NF; ++i) {
        PROFL(tid_ == 128 && layer == PL + 1, 244 + 2 * i);
        mbar_wait(BA(FM + i), par);
        PROFL(tid_ == 128 && layer == PL + 1, 245 + 2 * i);
        const uint32_t da = dA0 + (XS + s) * 1024, dk = dB0 + s * 2048, dq = dB0 + (9 + s) * 1024;
        wgmma_fence();
#pragma unroll
        for (int k = 0; k < 4; ++k) wgmma_n128(acc, D128(da + k * 2), D128(dq + k * 128), 1);
        wgmma_commit();
        wgmma_wait<1>();
        if (elected) REL2(CM + i - 1);
        wgmma_fence();
#pragma unroll
        for (int k = 0; k < 4; ++k) wgmma_n256(acc, D128(da + k * 2), D128(dk + k * 128), 1);
        wgmma_commit();
        if (++s == 3) s = 0;
      }
#pragma unroll 1
      for (int i = NF; i < 15; ++i) {
        mbar_wait(BA(FM + i), par);
        const uint32_t da = dA0 + (XS + s) * 1024, dk = dB0 + s * 2048;
        wgmma_fence();
#pragma unroll
        for (int k = 0; k < 4; ++k) wgmma_n256(acc, D128(da + k * 2), D128(dk + k * 128), 1);
        wgmma_commit();
        wgmma_wait<1>();
        if (elected) REL2(CM + i - 1);
        if (++s == 3) s = 0;
      }
      {
        const uint64_t dap = desc64(((SB0 + SM_AP) >> 4) + wu * 64, 8), dbp = make_desc_ns(SB0 + SM_BP, 0, 128);
        mbar_wait(BA(B_STAT), par);
        mbar_wait(BA(FM + 15), par);
        PROFT(tid_ == 128, layer * 16 + 9);
        wgmma_fence();
        wgmma_n256_k(acc, dap, dbp, 1);
#pragma unroll
        for (int k = 0; k < 4; ++k) wgmma_n256(acc, D128(dA0 + XS * 1024 + k * 2), D128(dB0 + k * 128), 1);
        wgmma_commit();
        wgmma_wait<1>();
        if (elected) REL2(CM + 14);
        mbar_wait(BA(FT), par);
        wgmma_fence();
        wgmma_n128_k(acc, dap, dbp + 256, 1);
#pragma unroll
        for (int k = 0; k < 4; ++k) wgmma_n128(acc, D128(dA0 + (uint32_t)(TL_A & 15) * 1024 + k * 2), D128(dB0 + (uint32_t)(TL_B & 15) * 1024 + k * 128), 1);
        wgmma_commit();
        wgmma_wait<1>();
        if (elected) REL2(CM + 15);
#pragma unroll
        for (int i = 0; i < 128; ++i) asm volatile("" : "+f"(acc[i]) :: "memory");
      }
    }
    uint32_t of[8][4], o1[4][4];
    {
      PHASE_CTX();
      MMA_CTX();
      PROFT(tid_ == 128, layer * 16 + 1);
      PROFT(lane == 0 && layer == PL, 192 + cw);
      PROFT(tid_ == 128 && layer == PL, 160);
      uint64_t ta = (TL_A >> 4), tw = TL_B >> 4;
      uint32_t da, db, dz = dA0;
      auto sub = [&](int n) {
        const int j = n >> 2, k = n & 3;
        if (k == 0) {
          dz += c.zero;
          da = dz + ((uint32_t)ta & 15) * 1024; db = dB0 + ((uint32_t)tw & 15) * 1024;
          ta >>= 4; tw >>= 4;
          mbar_wait(BA(FT + j), par);
          wgmma_fence();
        }
        wgmma_n128(acc, D128(da + k * 2), D128(db + k * 128), 1);
        if (k == 3) {
          wgmma_commit();
          wgmma_wait<1>();
          if (elected) REL2(CT + j - 1);
        }
      };
      auto run = [&](int j0, int j1) {
#pragma unroll 1
        for (int j = j0; j < j1; ++j) {
          mbar_wait(BA(FT + j), par);
          da = dA0 + ((uint32_t)ta & 15) * 1024; db = dB0 + ((uint32_t)tw & 15) * 1024;
          ta >>= 4; tw >>= 4;
          wgmma_fence();
#pragma unroll
          for (int k = 0; k < 4; ++k) wgmma_n128(acc, D128(da + k * 2), D128(db + k * 128), 1);
          wgmma_commit();
          wgmma_wait<1>();
          if (elected) REL2(CT + j - 1);
        }
        ta = TL_A >> (4 * j1); tw = TL_B >> (4 * j1);
      };
      auto rest = [&](int j0, int sk) {
        if (sk) {
          run(j0, ND - sk);
          if (wu == 0) nbar<6, 256>();
          j0 = ND - sk;
        }
        run(j0, ND);
        if (sk && wu) asm volatile("bar.arrive 6, 256;" ::: "memory");
      };
      auto rest_end = [&]() {
        wgmma_wait<0>();
        if (elected) REL2(CT + ND - 1);
#pragma unroll
        for (int i = 128; i < 192; ++i) asm volatile("" : "+f"(acc[i]) :: "memory");
      };
      auto wo0 = [&]() {
        wgmma_fence();
        wgmma_n128_rs0(acc, of[0], D128(dB0 + (uint32_t)(WO_B & 15) * 1024));
#pragma unroll
        for (int k = 1; k < 4; ++k) wgmma_n128_rs(acc, of[k], D128(dB0 + (uint32_t)(WO_B & 15) * 1024 + k * 128), 1);
        wgmma_commit();
      };
      const float rs0 = lds_f(sb + SM_RS + (16 + wrow0 + gq) * 4), rs1 = lds_f(sb + SM_RS + (24 + wrow0 + gq) * 4);
#define EPOCH() __float_as_uint(lds_f(sb + SM_EPOCH))
      mbar_wait(BA(CM + 14), par);
      if (par) {
        uint32_t kk[8][4], kp[8][4], vf[2][2][4][4];
        int sn = 4;
#pragma unroll
        for (int i = 0; i < 4 * BT1; ++i) sub(sn++);
        {
          uint32_t vv[8][4];
#pragma unroll
          for (int jp = 0; jp < 8; ++jp) {
            kk[jp][0] = pack_bf16(acc[8 * jp], acc[8 * jp + 1]); kk[jp][1] = pack_bf16(acc[8 * jp + 4], acc[8 * jp + 5]);
            kk[jp][2] = pack_bf16(acc[8 * jp + 2], acc[8 * jp + 3]); kk[jp][3] = pack_bf16(acc[8 * jp + 6], acc[8 * jp + 7]);
#pragma unroll
            for (int i = 0; i < 4; ++i) vv[jp][i] = pack_bf16(acc[64 + 8 * jp + 2 * i], acc[65 + 8 * jp + 2 * i]);
          }
          if (cw == 7) {
            uint32_t* const hbuf = g_halo + (size_t)(((layer >> 1) * 17 + rb + 1) * 8 + g) * 2048;
#pragma unroll
            for (int jp = 0; jp < 8; ++jp) stg128(hbuf + jp * 128 + lane * 4, kk[jp][0], kk[jp][1], kk[jp][2], kk[jp][3]);
#pragma unroll
            for (int i = 0; i < 32; ++i) hbuf[1024 + (i >> 4) * 512 + (gq + (i & 1) * 8) * 32 + ((((i >> 1) & 7) ^ gq) << 2) + t] = vv[i >> 2][i & 3];
            __syncwarp();
            if (lane == 0) mbar_arrive(BA(B_OF0));
          }
#pragma unroll
          for (int jp = 0; jp < 8; ++jp) {
            sub(sn++);
            stsm_x4(sb + VB + (jp >> 2) * SLOT + rowo + (X ^ ((jp & 3) << 5)), vv[jp][0], vv[jp][1], vv[jp][2], vv[jp][3]);
          }
        }
        PROFT(tid_ == 128, layer * 16 + 2);
        const int e = gq & 1;
        float f0[4], f1[4], b0[4], b1[4], rj[4];
#pragma unroll
        for (int nt = 0; nt < 4; ++nt) {
          const int kx = nt * 8 + 2 * t + e;
          const bool okk = (m0 + wrow0 + kx) >= 16;
          const int d0 = kx - gq, d1 = d0 - 8;
          rj[nt] = lds_f(sb + SM_RS + (wrow0 + kx) * 4);
          const bool m0_ = okk && d0 >= 2 && d0 <= 16, m1_ = okk && d1 >= 2 && d1 <= 16;
          f0[nt] = m0_ ? rj[nt] * rs0 * (0.17677669529663687f * L2E) : 0.f;
          f1[nt] = m1_ ? rj[nt] * rs1 * (0.17677669529663687f * L2E) : 0.f;
          b0[nt] = m0_ ? 0.f : -1e30f; b1[nt] = m1_ ? 0.f : -1e30f;
        }
        mbar_wait(BA(CM + 15), par);
#pragma unroll
        for (int jp = 0; jp < 8; ++jp) {
          sub(sn++);
          sts128(sb + PH + cw * 4096 + jp * 512 + lane * 16, make_uint4(kk[jp][0], kk[jp][1], kk[jp][2], kk[jp][3]));
        }
#pragma unroll
        for (int i = 0; i < 4; ++i) sub(sn++);
        nbar<1, 256>();
        PROFT(tid_ == 128, layer * 16 + 3);
        rest(sn >> 2, SKB);
        if (!BPRE) rest_end();
        PROFT(lane == 0 && layer == PL, 200 + cw);
        PROFT(tid_ == 128, layer * 16 + 10);
        if (cw == 0) mbar_wait(BA(B_HALO), (layer >> 1) & 1);
        PROFT(tid_ == 128, layer * 16 + 5);
        const uint32_t vs = sb + (cw ? VB + rowo - 2048 : SM_SD + 4096 + rowo), vst = cw ? SLOT : 2048;
        const uint32_t psel = e ? 0x1054u : 0x5410u;
#pragma unroll
        for (int hp = 0; hp < 2; ++hp) {
#pragma unroll
          for (int i = 4 * hp; i < 4 * hp + 4; ++i) {
            const uint4 u = lds128(sb + (cw ? PH + (cw - 1) * 4096 : SM_SD) + lane * 16 + i * 512);
            kp[i][0] = u.x; kp[i][1] = u.y; kp[i][2] = u.z; kp[i][3] = u.w;
          }
#pragma unroll
          for (int i = 4 * hp; i < 4 * hp + 4; ++i) {
            ldsm_x4_t(vf[0][i & 1][i >> 1][0], vf[0][i & 1][i >> 1][1], vf[0][i & 1][i >> 1][2], vf[0][i & 1][i >> 1][3], vs + (i >> 2) * vst + (X ^ ((i & 3) << 5)));
            ldsm_x4_t(vf[1][i & 1][i >> 1][0], vf[1][i & 1][i >> 1][1], vf[1][i & 1][i >> 1][2], vf[1][i & 1][i >> 1][3], sb + VB + (i >> 2) * SLOT + rowo + (X ^ ((i & 3) << 5)));
          }
          if (BPRE && !hp) rest_end();
          float l0[2][4], l1[2][4];
#pragma unroll
          for (int h = 0; h < 2; ++h) {
            const int H = 2 * hp + h;
            uint32_t qa[8];
#pragma unroll
            for (int i = 0; i < 8; ++i) qa[i] = pack_bf16(acc[128 + 16 * H + 2 * i], acc[129 + 16 * H + 2 * i]);
#pragma unroll
            for (int nt = 3; nt >= 0; --nt) {
              float sc[4] = {0.f, 0.f, 0.f, 0.f};
#pragma unroll
              for (int ks = 0; ks < 2; ++ks) {
                const uint32_t (&kf)[4] = nt < 2 ? kp[2 * H + ks] : kk[2 * H + ks];
                mma_bf16(sc, qa[4 * ks], qa[4 * ks + 1], qa[4 * ks + 2], qa[4 * ks + 3], kf[2 * (nt & 1)], kf[2 * (nt & 1) + 1]);
              }
              l0[h][nt] = fmaf(e ? sc[1] : sc[0], f0[nt], b0[nt]);
              l1[h][nt] = fmaf(e ? sc[3] : sc[2], f1[nt], b1[nt]);
            }
          }
          float mx0[2], mx1[2], s0[2], s1[2];
#pragma unroll
          for (int h = 0; h < 2; ++h) {
            mx0[h] = fmaxf(fmaxf(l0[h][0], l0[h][1]), l0[h][2]);
            mx1[h] = fmaxf(fmaxf(l1[h][1], l1[h][2]), l1[h][3]);
          }
#pragma unroll
          for (int o = 1; o <= 2; o <<= 1)
#pragma unroll
            for (int h = 0; h < 2; ++h) {
              mx0[h] = fmaxf(mx0[h], __shfl_xor_sync(0xffffffffu, mx0[h], o));
              mx1[h] = fmaxf(mx1[h], __shfl_xor_sync(0xffffffffu, mx1[h], o));
            }
#pragma unroll
          for (int h = 0; h < 2; ++h) {
#pragma unroll
            for (int nt = 0; nt < 3; ++nt) { l0[h][nt] = ex2(l0[h][nt] - mx0[h]); l1[h][nt + 1] = ex2(l1[h][nt + 1] - mx1[h]); }
            s0[h] = (l0[h][0] + l0[h][1]) + l0[h][2];
            s1[h] = (l1[h][1] + l1[h][2]) + l1[h][3];
          }
#pragma unroll
          for (int o = 1; o <= 2; o <<= 1)
#pragma unroll
            for (int h = 0; h < 2; ++h) {
              s0[h] += __shfl_xor_sync(0xffffffffu, s0[h], o);
              s1[h] += __shfl_xor_sync(0xffffffffu, s1[h], o);
            }
          uint32_t ow[2][2][4];
#pragma unroll
          for (int h = 0; h < 2; ++h) {
            const int H = 2 * hp + h;
            uint32_t pl[4], ph[4];
            const float i0 = rcp(s0[h]), i1 = rcp(s1[h]);
#pragma unroll
            for (int nt = 0; nt < 4; ++nt) {
              const uint32_t pk = pack_bf16(nt < 3 ? l0[h][nt] * i0 * rj[nt] : 0.f, nt > 0 ? l1[h][nt] * i1 * rj[nt] : 0.f);
              pl[nt] = nt < 3 ? __byte_perm(pk, 0u, psel) : 0u;
              ph[nt] = nt > 0 ? __byte_perm(pk, 0u, psel + 0x2222u) : 0u;
            }
#pragma unroll
            for (int nj = 0; nj < 4; ++nj) {
              float oa[4] = {0.f, 0.f, 0.f, 0.f};
#pragma unroll
              for (int ks = 0; ks < 2; ++ks)
                mma_bf16(oa, pl[2 * ks], ph[2 * ks], pl[2 * ks + 1], ph[2 * ks + 1], vf[ks][nj >> 1][H][2 * (nj & 1)], vf[ks][nj >> 1][H][2 * (nj & 1) + 1]);
              ow[h][0][nj] = pack_bf16(oa[0], oa[1]); ow[h][1][nj] = pack_bf16(oa[2], oa[3]);
            }
          }
          if (hp == 0) {
#pragma unroll
            for (int i = 0; i < 4; ++i) stg128(g_o + gfr + (i & 1) * 8 * D_ + (i >> 1) * 32, ow[i >> 1][i & 1][0], ow[i >> 1][i & 1][1], ow[i >> 1][i & 1][2], ow[i >> 1][i & 1][3]);
            __syncwarp();
            if (lane == 0) mbar_arrive(BA(B_OH0));
          } else {
#pragma unroll
            for (int i = 0; i < 16; ++i) o1[i >> 2][i & 3] = ow[i >> 3][(i >> 2) & 1][i & 3];
          }
#pragma unroll
          for (int i = 0; i < 16; ++i) of[4 * hp + (i >> 2)][i & 3] = ow[i >> 3][i & 1][(i >> 1) & 3];
          if (!hp) { PROFT(tid_ == 128, layer * 16 + 15); mbar_wait(BA(FW), par); }
        }
      } else {
        float sc[2] = {rs0 * L2E, rs1 * L2E};
        {
          const uint32_t vb = sb + VB + (rowo >> 1), X0 = (lchk ^ ((lane & 7) >> 1)) << 4;
          const uint32_t pb = sb + PH + (t & 1) * SLOT + (wrow0 + gq) * 128 + ((((t & 1) * 4 + (t & 2)) ^ gq) << 4);
          float kva[20], en[32], mx[2][2], mn[2][2];
#define PV(hp, j) acc[32 * (hp) + (j)]
          auto mm = [&](int hp, int j) {
            const int r = (j >> 1) & 1;
            if (j < 4 && !(j & 1)) { mx[hp][r] = PV(hp, j); mn[hp][r] = PV(hp, j); }
            else { mx[hp][r] = fmaxf(mx[hp][r], PV(hp, j)); mn[hp][r] = fminf(mn[hp][r], PV(hp, j)); }
          };
          auto mmx = [&](int hp) {
#pragma unroll
            for (int r = 0; r < 2; ++r) {
              mx[hp][r] = fmaxf(mx[hp][r], __shfl_xor_sync(0xffffffffu, mx[hp][r], 2)) * -sc[r];
              mn[hp][r] = fmaf(fminf(mn[hp][r], __shfl_xor_sync(0xffffffffu, mn[hp][r], 2)), sc[r], mx[hp][r]);
            }
          };
          auto stage = [&](int hp) {
#pragma unroll
            for (int i = 0; i < 20; ++i) asm volatile("" : "+f"(kva[i]) :: "memory");
            nbar_dyn(3 + wu, 128);
#pragma unroll
            for (int i = 0; i < 4; ++i)
              sts128(sb + VB + hp * SLOT + wg * 8192 + (wq * 128 + i * 32 + lane) * 16,
                     make_uint4(__float_as_uint(kva[4 * i]), __float_as_uint(kva[4 * i + 1]), __float_as_uint(kva[4 * i + 2]), __float_as_uint(kva[4 * i + 3])));
            if (t == 0) sts_f2(sb + SM_AP + ((2 * hp + wg) * 64 + wq * 16 + gq * 2) * 4, kva[16], kva[18]);
            fence_async_smem();
            __syncwarp();
            if (lane == 0) mbar_arrive(BA(B_KVDONE));
          };
          int sn = 4;
#pragma unroll
          for (int j = 0; j < 32; ++j) mm(0, j);
          mmx(0);
#pragma unroll
          for (int hp = 0; hp < 2; ++hp) {
            float sp[2] = {0.f, 0.f}, sm[2] = {0.f, 0.f};
#pragma unroll
            for (int j = 0; j < 32; ++j) {
              const int r = (j >> 1) & 1, ns = hp ? SUBS1 : SUBS;
              if ((j * ns) / 32 != ((j + 1) * ns) / 32) {
                sub(sn++);
                if (hp && sn == 4 + SUBS + 4 + 4 * (XST & 1)) { stage(0); PROFT(tid_ == 128, layer * 16 + 12); }
              }
              const float x = fmaf(PV(hp, j), sc[r], mx[hp][r]);
              PV(hp, j) = ex2(x); en[j] = ex2(mn[hp][r] - x);
              sp[r] += PV(hp, j); sm[r] += en[j];
              if (hp == 0) {
                mm(1, j);
                if ((j & 3) == 0) {
                  const int jp = 8 + (j >> 2);
                  stsm_x4(vb + ((jp - 8) >> 1) * 8192 + (X0 ^ ((jp & 1) << 5)), pack_bf16(acc[8 * jp], acc[8 * jp + 1]), pack_bf16(acc[8 * jp + 2], acc[8 * jp + 3]),
                          pack_bf16(acc[8 * jp + 4], acc[8 * jp + 5]), pack_bf16(acc[8 * jp + 6], acc[8 * jp + 7]));
                }
              }
            }
#pragma unroll
            for (int i = 0; i < 4; ++i) if (XST & (1 << hp)) sub(sn++);
#pragma unroll
            for (int r = 0; r < 2; ++r) {
              sp[r] = rcp(sp[r] + __shfl_xor_sync(0xffffffffu, sp[r], 2)) * (r ? rs1 : rs0);
              sm[r] = rcp(sm[r] + __shfl_xor_sync(0xffffffffu, sm[r], 2)) * (r ? rs1 : rs0);
            }
            if (hp == 0) { mmx(1); mbar_wait(BA(CM + 15), par); }
            else { PROFT(tid_ == 128, layer * 16 + 11); nbar<1, 256>(); }
#pragma unroll
            for (int i = 0; i < 4; ++i) {
              const int r = i & 1, d = 16 * (i >> 1) + 2 * r;
              sts128((pb + r * 1024) ^ ((i >> 1) << 4), make_uint4(pack_bf16(PV(hp, d) * sp[r], PV(hp, d + 1) * sp[r]), pack_bf16(PV(hp, d + 4) * sp[r], PV(hp, d + 5) * sp[r]),
                                                                    pack_bf16(PV(hp, d + 8) * sp[r], PV(hp, d + 9) * sp[r]), pack_bf16(PV(hp, d + 12) * sp[r], PV(hp, d + 13) * sp[r])));
              sts128((pb + r * 1024) ^ ((i >> 1) << 4) ^ 64, make_uint4(pack_bf16(en[d] * sm[r], en[d + 1] * sm[r]), pack_bf16(en[d + 4] * sm[r], en[d + 5] * sm[r]),
                                                                         pack_bf16(en[d + 8] * sm[r], en[d + 9] * sm[r]), pack_bf16(en[d + 12] * sm[r], en[d + 13] * sm[r])));
            }
            fence_async_smem();
            nbar<1, 256>();
            const uint32_t dP = dB0 + (PH >> 4) + wu * 1024;
            const uint32_t dV = (dB0 & 0xFFFFu) + ((VB + hp * SLOT) >> 4) + (((SM_SD - VB - hp * SLOT) >> 4) << 16) + wu * (512u - (512u << 16));
            wgmma_fence();
#pragma unroll
            for (int ks = 0; ks < 8; ++ks) wgmma_n40_tt(kva, D128(dP + ks * 128), desc64(dV + ks * 64, 0x80000020u), ks != 0);
            wgmma_commit();
          }
#pragma unroll
          for (int i = 0; i < 4; ++i) sub(sn++);
          stage(1);
          PROFT(tid_ == 128, layer * 16 + 3);
          rest(sn >> 2, SKA);
          rest_end();
          PROFT(lane == 0 && layer == PL, 200 + cw);
          PROFT(tid_ == 128, layer * 16 + 10);
        }
#define QV(H, i) acc[128 + 16 * (H) + (i)]
        float mx[4][2], mn[4][2];
        uint32_t ph[4][4][4];
        auto mnx = [&](int hp) {
#pragma unroll
          for (int H = 2 * hp; H < 2 * hp + 2; ++H)
#pragma unroll
            for (int r = 0; r < 2; ++r) {
              mx[H][r] = fmaxf(fmaxf(fmaxf(QV(H, 2 * r), QV(H, 2 * r + 1)), fmaxf(QV(H, 4 + 2 * r), QV(H, 5 + 2 * r))),
                               fmaxf(fmaxf(QV(H, 8 + 2 * r), QV(H, 9 + 2 * r)), fmaxf(QV(H, 12 + 2 * r), QV(H, 13 + 2 * r))));
              mn[H][r] = fminf(fminf(fminf(QV(H, 2 * r), QV(H, 2 * r + 1)), fminf(QV(H, 4 + 2 * r), QV(H, 5 + 2 * r))),
                               fminf(fminf(QV(H, 8 + 2 * r), QV(H, 9 + 2 * r)), fminf(QV(H, 12 + 2 * r), QV(H, 13 + 2 * r))));
            }
#pragma unroll
          for (int o = 1; o <= 2; o <<= 1)
#pragma unroll
            for (int H = 2 * hp; H < 2 * hp + 2; ++H)
#pragma unroll
              for (int r = 0; r < 2; ++r) {
                mx[H][r] = fmaxf(mx[H][r], __shfl_xor_sync(0xffffffffu, mx[H][r], o));
                mn[H][r] = fminf(mn[H][r], __shfl_xor_sync(0xffffffffu, mn[H][r], o));
              }
#pragma unroll
          for (int H = 2 * hp; H < 2 * hp + 2; ++H)
#pragma unroll
            for (int r = 0; r < 2; ++r) { mx[H][r] *= -sc[r]; mn[H][r] = fmaf(mn[H][r], sc[r], mx[H][r]); }
        };
        auto fm = [&](int H) {
#pragma unroll
          for (int i = 0; i < 8; ++i) {
            const int r = i & 1;
            const float x0 = fmaf(QV(H, 2 * i), sc[r], mx[H][r]), x1 = fmaf(QV(H, 2 * i + 1), sc[r], mx[H][r]);
            ph[H][i >> 2][i & 3] = pack_bf16(ex2(x0), ex2(x1));
            ph[H][2 + (i >> 2)][i & 3] = pack_bf16(ex2(mn[H][r] - x0), ex2(mn[H][r] - x1));
          }
        };
        auto conv = [&](int hp) {
          mbar_wait(BA(hp ? B_KVF1 : B_KVF), (layer >> 1) & 1);
          PROFT(tid_ == 128, layer * 16 + (hp ? 4 : 5));
          if (hp) { mbar_wait(BA(FW), par); nbar_dyn(3 + wu, 128); }
#pragma unroll
          for (int h = 0; h < 2; ++h) {
            uint4 u[4];
#pragma unroll
            for (int i = 0; i < 4; ++i) u[i] = lds128(sb + VB + hp * SLOT + h * 8192 + (wq * 128 + i * 32 + lane) * 16);
            const float zz = lds_f(sb + SM_AP + ((2 * hp + h) * 64 + wq * 16 + (lane & 7) * 2 + ((lane >> 3) & 1)) * 4);
            const uint32_t kb_ = sb + PH + wg * SLOT + h * 8192 + (wq * 16 + lrow) * 128;
#pragma unroll
            for (int i = 0; i < 4; i += 2)
              stsm_x4(kb_ + (X ^ (i << 4)),
                      pack_bf16(__uint_as_float(u[i].x), __uint_as_float(u[i].y)), pack_bf16(__uint_as_float(u[i].z), __uint_as_float(u[i].w)),
                      pack_bf16(__uint_as_float(u[i + 1].x), __uint_as_float(u[i + 1].y)), pack_bf16(__uint_as_float(u[i + 1].z), __uint_as_float(u[i + 1].w)));
            const uint32_t z1 = pack_bf16(zz, 1.f);
            if (lane < 16) sts128(kb_ + ((4 ^ (lane & 7)) << 4), make_uint4(z1, z1, z1, z1));
          }
          fence_async_smem();
        };
        mnx(0);
        fm(0);
        if (CV0) conv(0);
        fm(1);
        if (!CV0) conv(0);
#pragma unroll
        for (int hp = 0; hp < 2; ++hp) {
          nbar_dyn(3 + wu, 128);
          float oa[4][20];
          wgmma_fence();
#pragma unroll
          for (int s = 0; s < 2; ++s)
#pragma unroll
            for (int v = 0; v < 4; ++v) {
              const int h = v >> 1, s4 = 2 * (v & 1) + s;
              wgmma_n40_rs(oa[v], ph[2 * hp + h][s4], D128(dB0 + (PH >> 4) + wu * 1024 + h * 512 + (s4 ^ (2 * h)) * 128), s != 0);
            }
          wgmma_commit();
          if (hp == 0) { mnx(1); wgmma_wait<0>(); }
          else wgmma_wait<0>();
#pragma unroll
          for (int i = 0; i < 20; ++i) asm volatile("" : "+f"(oa[0][i]), "+f"(oa[1][i]), "+f"(oa[2][i]), "+f"(oa[3][i]) :: "memory");
          uint32_t ow[2][2][4];
#pragma unroll
          for (int h = 0; h < 2; ++h)
#pragma unroll
            for (int r = 0; r < 2; ++r) {
              const float a = oa[2 * h + 1][17 + 2 * r], b = oa[2 * h][17 + 2 * r];
              const float id = rcp(fmaf(oa[2 * h][16 + 2 * r], a, fmaf(a, 1e-6f, oa[2 * h + 1][16 + 2 * r]) * b));
              const float fa = a * id, fb = b * id;
#pragma unroll
              for (int j = 0; j < 4; ++j)
                ow[h][r][j] = pack_bf16(fmaf(oa[2 * h][4 * j + 2 * r], fa, oa[2 * h + 1][4 * j + 2 * r] * fb),
                                        fmaf(oa[2 * h][4 * j + 2 * r + 1], fa, oa[2 * h + 1][4 * j + 2 * r + 1] * fb));
            }
#pragma unroll
          for (int i = 0; i < 16; ++i) of[4 * hp + (i >> 2)][i & 3] = ow[i >> 3][i & 1][(i >> 1) & 3];
          if (hp == 0) {
#pragma unroll
            for (int i = 0; i < 8; ++i) {
              if (!(i & 1)) stg128(g_o + gfr + ((i >> 1) & 1) * 8 * D_ + (i >> 2) * 32, ow[i >> 2][(i >> 1) & 1][0], ow[i >> 2][(i >> 1) & 1][1], ow[i >> 2][(i >> 1) & 1][2], ow[i >> 2][(i >> 1) & 1][3]);
              const int r = i & 1;
              const float x0 = fmaf(QV(2, 2 * i), sc[r], mx[2][r]), x1 = fmaf(QV(2, 2 * i + 1), sc[r], mx[2][r]);
              ph[2][i >> 2][i & 3] = pack_bf16(ex2v(x0), ex2v(x1));
              ph[2][2 + (i >> 2)][i & 3] = pack_bf16(ex2v(mn[2][r] - x0), ex2v(mn[2][r] - x1));
            }
            __syncwarp();
            if (lane == 0) mbar_arrive(BA(B_OH0));
            PROFT(tid_ == 128 && layer, layer * 16 + 15);
            if (QORD) { fm(3); conv(1); } else { conv(1); fm(3); }
          } else {
#pragma unroll
            for (int i = 0; i < 16; ++i) o1[i >> 2][i & 3] = ow[i >> 3][(i >> 2) & 1][i & 3];
          }
        }
      }
      PROFT(tid_ == 128, layer * 16 + 6);
#pragma unroll
      for (int i = 0; i < 4; ++i) stg128(g_o + gfr + (i & 1) * 8 * D_ + (2 + (i >> 1)) * 32, o1[i][0], o1[i][1], o1[i][2], o1[i][3]);
      __syncwarp();
      if (lane == 0) { mbar_arrive(BA(B_OH1)); if (EF_USED) REL2(B_EF); }
      PROFT(lane == 0 && layer == PL, 208 + cw);
      wo0();
    }
    {
      PHASE_CTX();
      MMA_CTX();
      mbar_wait(BA(FW + 1), par);
      wgmma_fence();
#pragma unroll
      for (int k = 0; k < 4; ++k) wgmma_n128_rs(acc, of[4 + k], D128(dB0 + (uint32_t)((WO_B >> 4) & 15) * 1024 + k * 128), 1);
      wgmma_commit();
      wgmma_wait<1>();
      if (elected) REL2(CW);
      uint64_t ta = WO_A >> 8, tw = WO_B >> 8;
      auto run = [&](int i0, int i1) {
#pragma unroll 1
        for (int i = i0; i < i1; ++i) {
          mbar_wait(BA(FW + i), par);
          PROFL(tid_ == 128 && layer == PL, 160 + i);
          const uint32_t da = dA0 + ((uint32_t)ta & 15) * 1024, db = dB0 + ((uint32_t)tw & 15) * 1024;
          ta >>= 4; tw >>= 4;
          wgmma_fence();
#pragma unroll
          for (int k = 0; k < 4; ++k) wgmma_n128(acc, D128(da + k * 2), D128(db + k * 128), 1);
          wgmma_commit();
          wgmma_wait<1>();
          if (elected) REL2(CW + i - 1);
        }
        ta = WO_A >> (4 * (i1 & 15)); tw = WO_B >> (4 * (i1 & 15));
      };
      run(2, XRAT);
#pragma unroll
      for (int j = 0; j < 8 / XRN; ++j) {
#pragma unroll
        for (int i = j * XRN; i < (j + 1) * XRN; ++i) ldg128((layer ? g_x : c.x0) + gfr + (i & 1) * 8 * D_ + (i >> 1) * 32, xp[i][0], xp[i][1], xp[i][2], xp[i][3]);
        run(XRAT + j, j + 1 < 8 / XRN ? XRAT + j + 1 : 16);
      }
      if (layer == 0) {
#pragma unroll
        for (int o = 1; o <= 2; o <<= 1)
#pragma unroll
          for (int i = 0; i < 16; ++i) {
            const int j = o == 1 ? 2 * (i & 1) : (i & 1);
            uint32_t &a = xp[i >> 1][j], &b = xp[i >> 1][j + o];
            const uint32_t r = __shfl_xor_sync(0xffffffffu, (t & o) ? a : b, o);
            if (t & o) a = r; else b = r;
          }
      }
      if (layer != NLAYERS - 1) mbar_wait(BA(FM), par ^ 1);
      wgmma_wait<0>();
#pragma unroll
      for (int i = 128; i < 192; ++i) asm volatile("" : "+f"(acc[i]) :: "memory");
      if (elected) REL2(CW + 15);
      PROFT(lane == 0 && layer == PL, 216 + cw);
      PROFT(tid_ == 128, layer * 16 + 7);
#pragma unroll
      for (int i = 0; i < 32; ++i)
        xp[i >> 2][i & 3] = add_bf16x2(xp[i >> 2][i & 3], pack_bf16(acc[128 + 16 * (i >> 3) + 4 * (i & 3) + 2 * ((i >> 2) & 1)], acc[129 + 16 * (i >> 3) + 4 * (i & 3) + 2 * ((i >> 2) & 1)]));
      if (layer == NLAYERS - 1) {
#pragma unroll
        for (int i = 0; i < 8; ++i) stsm_x4(sb + (XS + (i >> 2)) * SLOT + (Y ^ ((i & 2) << 5)) + (i & 1) * 1024, xp[i][0], xp[i][1], xp[i][2], xp[i][3]);
        __syncwarp();
        slab_out_half(sb + XS * SLOT, c.out + (size_t)m0 * D_ + g * 128, wrow0, lane);
        slab_out_half(sb + (XS + 1) * SLOT, c.out + (size_t)m0 * D_ + g * 128 + 64, wrow0, lane);
        PROFT(tid_ == 128, layer * 16 + 24);
        break;
      }
#pragma unroll
      for (int i = 0; i < 4; ++i) stg128(g_x + gfr + (i & 1) * 8 * D_ + (i >> 1) * 32, xp[i][0], xp[i][1], xp[i][2], xp[i][3]);
      __syncwarp();
      if (lane == 0) mbar_arrive(BA(B_XH0));
#pragma unroll
      for (int i = 0; i < 16; ++i) xf[i >> 2][i & 3] = xp[2 * (i >> 3) + (i & 1)][(i >> 1) & 3];
      PROFT(tid_ == 128, layer * 16 + 24);
    }
  }
}

__device__ __forceinline__ uint64_t k_order(int o) {
  const uint32_t lo = (1u << (4 * o)) - 1u, h0 = (0xECA86420u & lo) | ((0xECA86420u >> 4) & ~lo);
  return (uint64_t)(2 * o) | ((uint64_t)(2 * o + 1) << 4) | ((uint64_t)(h0 & 0xFFFFFFFu) << 8) | ((uint64_t)((h0 & 0xFFFFFFFu) | 0x1111111u) << 36);
}

__global__ void __cluster_dims__(2, 1, 1) __launch_bounds__(384, 1)
mega_kernel(const __grid_constant__ Maps maps, const __grid_constant__ Ctx c, const bf16* __restrict__ wA, const bf16* __restrict__ wB,
            const bf16* __restrict__ woA, const bf16* __restrict__ woB) {
  if (blockIdx.x - c.boff >= 128u) {
    const unsigned int epoch = ld_relaxed(&g_epoch);
    const int e = (blockIdx.x - c.boff) & 3, tid = threadIdx.x;
    float s[8] = {0.f, 0.f, 0.f, 0.f, 0.f, 0.f, 0.f, 0.f};
    const uint32_t sb = smem_u32(smem_raw), bar = sb + SM_BAR;
    auto issue = [&](int i) {
      mbar_expect_tx(BA(i & 3), 49152);
      bulk_load(sb + (i & 3) * 49152, wB + (size_t)e * 256 * 3072 + i * 24576, 49152, BA(i & 3));
    };
    if (tid == 0) {
#pragma unroll 1
      for (int i = 0; i < 4; ++i) {
        mbar_init(BA(i), 1);
        fence_async_smem();
        issue(i);
      }
    }
    __syncthreads();
#pragma unroll 1
    for (int i = 0; i < 32; ++i) {
      mbar_wait(BA(i & 3), (i >> 2) & 1);
#pragma unroll 2
      for (int r = 0; r < 8; ++r) {
        const uint4 v = lds128(sb + (i & 3) * 49152 + r * 6144 + tid * 16);
        s[0] += bf_lo(v.x); s[1] += bf_hi(v.x); s[2] += bf_lo(v.y); s[3] += bf_hi(v.y);
        s[4] += bf_lo(v.z); s[5] += bf_hi(v.z); s[6] += bf_lo(v.w); s[7] += bf_hi(v.w);
      }
      __syncthreads();
      if (tid == 0 && i < 28) issue(i + 4);
    }
    float* cd = g_cs + (epoch & 1) * 6144 + 3072 + ((tid >> 4) & 7) * 384 + (tid < 128 ? 256 : (tid >> 7) * 128 - 128) + (tid & 15) * 8;
    red_add4(cd, s[0], s[1], s[2], s[3]);
    red_add4(cd + 4, s[4], s[5], s[6], s[7]);
    __syncthreads();
    if (tid == 0) flag_add(&g_csflag[8].v);
    const int op = (epoch & 1) ^ 1;
    float4* kz = reinterpret_cast<float4*>(g_kv + (size_t)op * (2 * 8 * 8448)) + e * 8448;
#pragma unroll 1
    for (int i = tid; i < 8448; i += 384) kz[i] = make_float4(0.f, 0.f, 0.f, 0.f);
    reinterpret_cast<float4*>(g_cs + op * 6144)[e * 384 + tid] = make_float4(0.f, 0.f, 0.f, 0.f);
#pragma unroll 1
    for (int i = tid; i < 1024; i += 384) reinterpret_cast<float4*>(g_stats + (op * 4 + e) * S_)[i] = make_float4(0.f, 0.f, 0.f, 0.f);
    return;
  }
  const int warp = __shfl_sync(0xffffffffu, threadIdx.x >> 5, 0), lane = threadIdx.x & 31;
  if (smem_u32(smem_raw) != SB0 + ((blockIdx.x & 1) << 24)) __trap();
  {
  const int cid = (blockIdx.x - c.boff) >> 1, u7 = ((cid - 36) * 37) >> 8, cr = blockIdx.x & 1;
  const int g = cid < 4 ? 4 + cid : cid < 36 ? (cid - 4) >> 3 : 4 + u7, rb = (cid < 4 ? 0 : cid < 36 ? (cid - 4) & 7 : cid - 35 - 7 * u7) * 2 + cr, m0 = rb * 128;
  const uint32_t sb = SB0 + (cr << 24), bar = sb + SM_BAR;
  PROFT(lane == 0 && (warp == 0 || warp == 4), 224 + (warp >> 2) * 8);
  uint32_t cx = 0;
  if (warp == 2) {
    if (lane < NMAP) asm volatile("prefetch.tensormap [%0];" ::"l"(&maps.m[lane]) : "memory");
    if (lane == 31) asm volatile("prefetch.global.L2 [%0];" ::"l"(&g_epoch));
  } else if (warp == 3) {
    cx = c_map[cid] + c_wop[lane] + c_wop[NWOP - lane] + c_aop[lane] + c_aop[NAOP - lane] + (uint32_t)(uintptr_t)g_x;
  } else if (warp >= 4 && warp < 8) {
    const int i = threadIdx.x - 128;
    asm volatile("prefetch.global.L2 [%0];" ::"l"(wA + (size_t)((rb & ~1) * 64 + cr * 32 + ((i >> 1) & 31)) * 3072 + (i >> 6) * 1024 + g * 128 + (i & 1) * 64));
  }
  if (warp < 2) {
    const int s = warp, kb = (rb & ~1) + s;
    if (lane == 0) {
      mbar_init(BA(FM + s), 1u);
      mbar_init(BA(B_RAW + warp), 1u);
      mbar_init(BA(warp ? B_X0 : B_KVS0), 1u);
      asm volatile("fence.mbarrier_init.release.cluster;" ::: "memory");
    }
    __syncwarp();
    if (warp == 0) tma_2d_e(sb + SM_SD, &maps.m[MAP_PHI], 0, g * 128, BA(B_RAW));
    else if (W1DL) __nanosleep(W1DL);
#pragma unroll
    for (int j = 0; j < 6; ++j)
      tma_5d_e(sb + (j < 2 ? 2 * s : j < 4 ? 9 + s : 2 * s + 1) * SLOT + (j & 1) * 8192, &maps.m[MAP_WA], (j < 2 ? 1024 : j < 4 ? 0 : 2048) + g * 128 + (j & 1) * 64, 2 * kb,
               BA(j < 4 ? B_RAW + warp : FM + s));
    tma_2d_e(sb + (XS + s) * SLOT, &maps.m[MAP_X0], kb * 64, m0, BA(FM + s));
    expect_tx_e(BA(B_RAW + warp), warp ? 32768 : 32768 + 8192);
    expect_tx_e(BA(FM + s), 32768);
    if (X0AT == 0 && warp == 1) {
      tma_2d_e(sb + 11 * SLOT, &maps.m[MAP_X0], g * 128, m0, BA(B_X0));
      tma_2d_e(sb + 12 * SLOT, &maps.m[MAP_X0], g * 128 + 64, m0, BA(B_X0));
      expect_tx_e(BA(B_X0), 32768);
    }
  } else if (warp >= 4 && lane == 0) {
#pragma unroll 1
    for (int i = 2 + (warp - 4) * 13; i < 15 + (warp - 4) * 13; ++i)
      mbar_init(BA(i), 1u << ((i < CM ? 0u : i < B_EF ? 2u : (uint32_t)(BAR_LG >> (4 * ((i - B_EF) & 15)))) & 7u));
    asm volatile("fence.mbarrier_init.release.cluster;" ::: "memory");
  }
  __syncwarp();
  asm volatile("barrier.cluster.arrive.relaxed.aligned;" ::: "memory");
  if (threadIdx.x == 96 + c.zero) sts_f(sb + SM_EPOCH + 4, __uint_as_float(cx));
  PROFT(lane == 0 && (warp == 0 || warp == 4), 225 + (warp >> 2) * 8);
  __syncwarp();
  PROFT(lane == 0 && (warp == 0 || warp == 4), 226 + (warp >> 2) * 8);
  }

  if (warp < 4) {
    asm volatile("setmaxnreg.dec.sync.aligned.u32 40;");
    PROFT(threadIdx.x == 0, 227);
    cluster_wait();
    PROFT(threadIdx.x == 0, 228);
    if (warp == 0 || warp == 3) {
    if (warp == 0) {
      BLK_CTX();
      const unsigned int epoch = __shfl_sync(0xffffffffu, ld_relaxed(&g_epoch), 0), xbase = epoch * NLAYERS;
      (void)xbase;
      const uint64_t ordg = k_order(g);
      if (X0AT) {
        mbar_wait_u(BA(B_RAW + X0AT - 1), 0);
        tma_2d_e(sb + 11 * SLOT, &maps.m[MAP_X0], g * 128, m0, BA(B_X0));
        tma_2d_e(sb + 12 * SLOT, &maps.m[MAP_X0], g * 128 + 64, m0, BA(B_X0));
        expect_tx_e(BA(B_X0), 32768);
      }
#pragma unroll 1
      for (int lp = 0; lp < 2 * NLAYERS; ++lp) {
        const int layer = lp >> 1, n1 = (lp & 1) ? NAOP : NAOP - 14;
        int n = (lp & 1) ? NAOP - 14 : 0;
        const uint64_t ord = lp ? ordg : k_order(rb >> 1);
        uint32_t ready = lp ? 0u : 0xFFFFu, nop = c_aop[n];
        const unsigned int* fl = ((lp & 1) ? g_of : g_xf) + rb * 32;
        const CUtensorMap* tm = &maps.m[(lp & 1) ? MAP_O : lp ? MAP_X : MAP_X0];
        const uint32_t skip = layer ? 1u << 25 : 9u << 22;
#pragma unroll 1
        for (; n < n1; ++n) {
          const uint32_t op = nop;
          nop = c_aop[n + 1];
          const uint32_t kb = (uint32_t)(ord >> ((op >> 2) & 60)) & 15;
          uint32_t dst = sb + (op & 15) * SLOT, kc = kb * 64, fb = bar + ((op >> 5) & 0x3F8), need = ~ready & (1u << kb);
          asm volatile("" : "+r"(dst), "+r"(kc), "+r"(fb), "+r"(need));
          const uint32_t eb = bar + ((op >> 12) & 0x3F8), ep = (layer ^ (op >> 22)) & 1;
          bool fr = op & skip;
          if (need) {
            if (!fr) fr = __all_sync(0xffffffffu, mbar_test_wait(eb, ep));
            PROFT(lane == 0 && (n == 0 || n == NAOP - 14), 64 + layer * 16 + (n ? 2 : 0));
            src_wait<0>(fl, xbase + layer + 1, need, ready, lane);
            fence_async_all();
          }
          if (!fr) mbar_wait_u(eb, ep);
          tma_2d_e(dst, tm, kc, m0, fb);
          PROFT(lane == 0 && (n == 0 || n == NAOP - 14), 64 + layer * 16 + (n ? 3 : 1));
          PROFL(lane == 0 && layer == PL && n >= NAOP - 14, 178 + n - (NAOP - 14));
          PROFL(lane == 0 && layer == PL + 1 && n < 4, 242 + n);
        }
      }
    } else {
      BLK_CTX();
      const unsigned int epoch = __shfl_sync(0xffffffffu, ld_relaxed(&g_epoch), 0), xbase = epoch * NLAYERS;
      (void)xbase;
      const uint64_t ordg = k_order(g);
#pragma unroll 1
      for (int layer = 0; layer < NLAYERS; ++layer) {
        const uint64_t ordq = layer ? ordg : k_order(rb >> 1);
        uint32_t ready = layer ? 0xFFFFu : 0u, nop = c_wop[0];
        const CUtensorMap* tq = &maps.m[(layer & 1) ? MAP_WB : MAP_WF];
        const CUtensorMap* tk = &maps.m[(layer & 1) ? MAP_WB : cr ? MAP_WA : MAP_WF];
        const uint32_t skip = layer ? 1u << 25 : 9u << 22, pm = layer ? 0xE0u : 0u;
        int n = 0;
#pragma unroll 1
        for (; n < NWOP - 16; ++n) {
          const uint32_t op = nop;
          nop = c_wop[n + 1];
          const uint32_t isq = (op >> 23) & 1, fb = bar + ((op >> 5) & 0x3F8);
          const uint32_t kb = (uint32_t)(ordq >> ((op >> 2) & 60)) & 15;
          const CUtensorMap* tm = (isq ? tq : tk) + ((op & pm) ? 1 : 0);
          const uint32_t dst = sb + (op & 15) * SLOT + cr * (isq ? 8192 : SLOT);
          const int col = g * 128 + (isq ? cr * 64 : 1024 + cr * 1024);
          if (layer == 0) {
            if ((op & 0x7E00) == 0) continue;
            const uint32_t need = ((isq || !cr) ? 1u << kb : 0u) | (((op >> 22) & 1) ? 0u : (((op >> 15) & 127) == CM ? 1u : 3u) << (rb & ~1));
            if ((ready & need) != need) {
              src_wait<0>(g_wff + g * 32, epoch + 1, need, ready, lane);
              fence_async_all();
            }
            if ((op & 15) >= 11) mbar_wait_u(BA(B_XT), 0);
          }
          wait_tma_5d_mc(!(op & skip), bar + ((op >> 12) & 0x3F8), (layer ^ (op >> 22)) & 1, dst, tm, col, 2 * kb, fb);
          if (!isq) tma_5d_mc_e(dst + 8192, tm, col + 64, 2 * kb, fb);
          if (op >> 26) expect_tx_e(fb, (op >> 26) * 8192);
          PROFL(lane == 0 && layer == PL + 1 && n < 16, 128 + n);
        }
        const CUtensorMap* to = &maps.m[(layer & 1) ? MAP_WOB : MAP_WOA];
#pragma unroll 1
        for (; n < NWOP; ++n) {
          const uint32_t op = nop;
          nop = c_wop[n + 1];
          const uint32_t fb = bar + ((op >> 5) & 0x3F8), kb = (uint32_t)(ordg >> ((op >> 2) & 60)) & 15;
          if (WH < 16 && n == NWOP - 16 + WH && !(layer & 1)) mbar_wait_u(BA(B_KVS), (layer >> 1) & 1);
          wait_tma_5d_mc(!((op >> 25) & 1), bar + ((op >> 12) & 0x3F8), layer & 1, sb + (op & 15) * SLOT + cr * 8192, to + ((op & 0xE0) ? 1 : 0), g * 128 + cr * 64, 2 * kb, fb);
          expect_tx_e(fb, (op >> 26) * 8192);
          PROFL(lane == 0 && layer == PL, 144 + ((op >> 8) & 127) - FW);
        }
      }
    }
    } else if (warp == 1) {
      BLK_CTX();
      const unsigned int epoch = __shfl_sync(0xffffffffu, ld_relaxed(&g_epoch), 0), xbase = epoch * NLAYERS;
      (void)xbase;
      if (lane == 0) {
        mbar_wait(BA(B_WFD), 0);
        PROFT(true, 229);
#pragma unroll 1
        for (int j = 0; j < 4; ++j) tma_store_5d(&maps.m[MAP_WF], sb + (j < 2 ? 2 * cr : 9 + cr) * SLOT + (j & 1) * 8192, (j < 2 ? 1024 : 0) + g * 128 + (j & 1) * 64, 2 * rb);
        bulk_commit();
        bulk_wait0();
        PROFT(true, 230);
        fence_async_all();
        flag_set(g_wff + g * 32 + rb, epoch + 1);
        PROFT(true, 64 + 13);
#pragma unroll 1
        for (int e = 0; e < NLAYERS; ++e) {
          BLK_CTX();
          if (e > 0) {
            mbar_wait(BA(B_XH0), (e - 1) & 1);
            PROFT(e == PL + 1, 240);
            flag_set(g_xf + rb * 32 + 2 * g, xbase + e + 1);
            PROFT(e == PL + 1, 241);
          }
          mbar_wait(BA(B_XDONE), e & 1);
          PROFT(true, 64 + e * 16 + 4);
          flag_set(g_xf + rb * 32 + 2 * g + 1, xbase + e + 1);
          if (e == 0) {
            flag_add(&g_csflag[g].v);
#pragma unroll 1
            for (int i = 0; i < 4; ++i) {
              mbar_wait(BA(CM + PFM + PFS * i), 0);
              l2_prefetch(i < 3 ? wB + (size_t)(i * 128 + bid_) * 8192 : woA + (size_t)bid_ * 8192, 16384);
            }
          }
          if (PFM && e == 1) l2_prefetch(woB + (size_t)bid_ * 8192, 16384);
          PROFT(true, 64 + e * 16 + 7);
          if ((e & 1) == 0) {
            float* kvl = g_kv + ((size_t)((epoch & 1) * 2 + (e >> 1)) * 8 + g) * 8448;
#pragma unroll 1
            for (int hp = 0; hp < 2; ++hp) {
              mbar_wait(BA(B_KVDONE), hp);
              bulk_red_add(kvl + 8192 + hp * 128, sb + SM_AP + hp * 512, 512);
#pragma unroll 1
              for (int i = 0; i < NCH; ++i) {
                const int ch = hp * NCH + ((i + rb * NCH / 16) & (NCH - 1));
                bulk_red_add(kvl + ch * (4096 / NCH), sb + VB + ch * (16384 / NCH), 16384 / NCH);
                bulk_commit();
                asm volatile("cp.async.bulk.wait_group %0;" :: "n"(CHW) : "memory");
              }
              bulk_wait0();
              PROFT(true, 64 + e * 16 + (hp ? 10 : 6));
              fence_async_all();
              flag_add(&g_kvflag[hp * 8 + g].v);
              mbar_arrive(BA(hp ? B_KVS : B_KVS0));
              PROFT(e > 0 && hp, 64 + e * 16 + 8);
            }
          }
          if (e & 1) {
            mbar_wait(BA(B_OF0), (e >> 1) & 1);
            flag_set(g_hf + rb * 32 + g, xbase + e + 1);
            if (rb) flag_wait(g_hf + (rb - 1) * 32 + g, xbase + e + 1);
            fence_async_all();
            mbar_expect_tx(BA(B_HALO), 8192);
            bulk_load(sb + SM_SD, g_halo + (size_t)(((e >> 1) * 17 + rb) * 8 + g) * 2048, 8192, BA(B_HALO));
            PROFT(true, 64 + e * 16 + 15);
          }
          mbar_wait(BA(B_OH0), e & 1);
          PROFT(e > 0, 64 + e * 16 + 13);
          flag_set(g_of + rb * 32 + 2 * g, xbase + e + 1);
          PROFT(true, 64 + e * 16 + 9);
          mbar_wait(BA(B_OH1), e & 1);
          PROFT(true, 64 + e * 16 + 5);
          flag_set(g_of + rb * 32 + 2 * g + 1, xbase + e + 1);
          PROFT(true, 64 + e * 16 + 11);
        }
        if (bid_ == 0) g_epoch = epoch + 1;
      }
    } else {
      BLK_CTX();
      const unsigned int epoch = __shfl_sync(0xffffffffu, ld_relaxed(&g_epoch), 0), xbase = epoch * NLAYERS;
      (void)xbase;
      if (lane < 16) sts_f(sb + SM_RS + lane * 4, 0.f);
#pragma unroll 1
      for (int layer = 0; layer < NLAYERS; ++layer) {
#define HLP_CTX() BLK_CTX(); int lane = threadIdx.x & 31; asm volatile("" : "+r"(lane)); const bool isB = layer & 1, hal = isB && rb > 0; (void)hal;
#pragma unroll 1
        for (int ph = 0; ph < 2; ++ph) {
          HLP_CTX();
          if (ph == (layer == 0)) {
            const float* cs = g_cs + (epoch & 1) * 6144 + g * 384;
            if (layer) mbar_wait_u(BA(CT), (layer - 1) & 1);
            if (layer < 2) {
              if (lane == 0) flag_wait_slow(&g_csflag[isB ? 8 : g].v, isB ? epoch * 4u + 4u : epoch * 16u + 16u);
              __syncwarp();
            }
#pragma unroll 1
            for (int i0 = 0; i0 < 12; i0 += 4) {
              float a[4];
#pragma unroll
              for (int i = 0; i < 4; ++i) a[i] = __ldcg(cs + isB * 3072 + (i0 + i) * 32 + lane);
#pragma unroll
              for (int i = 0; i < 4; ++i) {
                const float c1 = bf16r(a[i]), c2 = bf16r(a[i] - c1), c3 = (a[i] - c1) - c2;
                sts128(sb + SM_BP + ((i0 + i) * 32 + lane) * 16, make_uint4(pack_bf16(c1, c2), pack_bf16(c3, 0.f), 0u, 0u));
              }
            }
          } else {
            uint32_t rdy = 0u;
            src_wait<128>(g_xf + rb * 32, xbase + layer + 1, 0xAAAAu, rdy, lane);
            rdy = 0u;
            if (hal) src_wait<128>(g_xf + (rb - 1) * 32, xbase + layer + 1, 0xAAAAu, rdy, lane);
            const float2* sp = g_stats + ((epoch & 1) * 4 + layer) * S_ + m0 + lane;
            float2 u[5];
#pragma unroll
            for (int i = 0; i < 4; ++i) u[i] = __ldcg(sp + i * 32);
            u[4] = __ldcg(sp - (hal ? 16 : 0));
#pragma unroll 1
            for (int i = 0; i < 5; ++i) {
              const float mean = u[0].x * (1.f / D_);
              const float var = fmaxf(fmaf(-u[0].x, mean, u[0].y) * (1.f / D_), 0.f);
              const float sd = bf16r(sqrtf(bf16r(bf16r(var) + 1e-5f)));
              const int R = i * 32 + lane;
              if (i < 4) {
                const float hm = -0.5f * bf16r(mean);
                if (!isB) sts128(sb + SM_SD + R * 64 + ((R >> 1) & 3) * 16, make_uint4(__float_as_uint(sd) >> 16, 0u, 0u, 0u));
                sts128(sb + SM_AP + R * 16, make_uint4(pack_bf16(hm, hm), pack_bf16(hm, 0.f), 0u, 0u));
              }
              if (i < 4 || (hal && lane < 16)) sts_f(sb + SM_RS + (i < 4 ? 16 + R : lane) * 4, __fdividef(1.f, sd));
#pragma unroll
              for (int j = 0; j < 4; ++j) u[j] = u[j + 1];
            }
            PROFT(lane == 0, 64 + layer * 16 + 12);
          }
        }
        HLP_CTX();
        fence_async_smem();
        __syncwarp();
        if (lane == 0) mbar_arrive(BA(B_STAT));
        PROFT(lane == 0, 64 + layer * 16 + 14);
        if (!isB && lane == 0) {
#pragma unroll 1
          for (int hp = 0; hp < 2; ++hp) {
            mbar_wait(BA(hp ? B_KVS : B_KVS0), (layer >> 1) & 1);
            flag_wait(&g_kvflag[hp * 8 + g].v, epoch * (16u * ((NLAYERS + 1) / 2)) + 16u * ((layer >> 1) + 1));
            const float* kvl = g_kv + ((size_t)((epoch & 1) * 2 + (layer >> 1)) * 8 + g) * 8448;
            const uint32_t kb = BA(hp ? B_KVF1 : B_KVF);
            fence_async_all();
            mbar_expect_tx(kb, 16384 + 512);
            bulk_load(sb + VB + hp * SLOT, kvl + hp * 4096, 16384, kb);
            bulk_load(sb + SM_AP + hp * 512, kvl + 8192 + hp * 128, 512, kb);
            PROFT(hp == 0, 64 + layer * 16 + 15);
          }
        }
        __syncwarp();
      }
    }
    __syncwarp();
    asm volatile("barrier.cluster.arrive.relaxed.aligned;" ::: "memory");
    cluster_wait();
  } else {
    asm volatile("setmaxnreg.inc.sync.aligned.u32 232;");
    PROFT(threadIdx.x == 128, 235);
    cluster_wait();
    PROFT(threadIdx.x == 128, 236);
    consumer(c);
    asm volatile("bar.warp.sync 0xffffffff;\nbarrier.cluster.arrive.relaxed.aligned;\nbarrier.cluster.wait.aligned;\n" ::: "memory");
  }
}

typedef CUresult (*PFN_encodeTiled)(CUtensorMap*, CUtensorMapDataType, cuuint32_t, void*, const cuuint64_t*, const cuuint64_t*,
                                    const cuuint32_t*, const cuuint32_t*, CUtensorMapInterleave, CUtensorMapSwizzle,
                                    CUtensorMapL2promotion, CUtensorMapFloatOOBfill);

static void make_map2(PFN_encodeTiled enc, CUtensorMap* m, const void* ptr, uint64_t cols, uint64_t rows, uint32_t box_c, uint32_t box_r) {
  cuuint64_t dims[2] = {cols, rows};
  cuuint64_t strides[1] = {cols * 2};
  cuuint32_t box[2] = {box_c, box_r};
  cuuint32_t es[2] = {1, 1};
  CUresult r = enc(m, CU_TENSOR_MAP_DATA_TYPE_BFLOAT16, 2, const_cast<void*>(ptr), dims, strides, box, es, CU_TENSOR_MAP_INTERLEAVE_NONE,
                   box_c == 64 ? CU_TENSOR_MAP_SWIZZLE_128B : CU_TENSOR_MAP_SWIZZLE_64B, CU_TENSOR_MAP_L2_PROMOTION_L2_256B, CU_TENSOR_MAP_FLOAT_OOB_FILL_NONE);
  (void)r;
}
static void make_map5(PFN_encodeTiled enc, CUtensorMap* m, const void* ptr, uint64_t cols) {
  for (int p = 0; p < 2; ++p) {
    cuuint64_t dims[5] = {cols, 2, 4, 4, 32};
    cuuint64_t strides[4] = {cols * 2, cols * (p ? 16 : 4), cols * (p ? 4 : 16), cols * 64};
    cuuint32_t box[5] = {64, 2, 4, 4, 2};
    cuuint32_t es[5] = {1, 1, 1, 1, 1};
    CUresult r = enc(m + p, CU_TENSOR_MAP_DATA_TYPE_BFLOAT16, 5, const_cast<void*>(ptr), dims, strides, box, es, CU_TENSOR_MAP_INTERLEAVE_NONE,
                     CU_TENSOR_MAP_SWIZZLE_128B, CU_TENSOR_MAP_L2_PROMOTION_L2_256B, CU_TENSOR_MAP_FLOAT_OOB_FILL_NONE);
    (void)r;
  }
}

extern "C" void kernel_launch(void* const* d_in, const int* in_sizes, int n_in, void* d_out, int out_size) {
  const bf16* A_x = (const bf16*)d_in[0];
  const bf16* A_wqkv = (const bf16*)d_in[1];
  const bf16* A_wphi = (const bf16*)d_in[2];
  const bf16* A_wo = (const bf16*)d_in[3];
  const bf16* B_wqkv = (const bf16*)d_in[5];
  const bf16* B_wo = (const bf16*)d_in[6];
  bf16* out = (bf16*)d_out;

  static PFN_encodeTiled enc = nullptr;
  static bf16 *p_x, *p_o, *p_wf;
  static uint32_t boff;
  if (!enc) {
    void* fn = nullptr; cudaDriverEntryPointQueryResult qr;
    cudaGetDriverEntryPoint("cuTensorMapEncodeTiled", &fn, cudaEnableDefault, &qr);
    enc = (PFN_encodeTiled)fn;
    cudaGetSymbolAddress((void**)&p_x, g_x);
    cudaGetSymbolAddress((void**)&p_o, g_o);
    cudaGetSymbolAddress((void**)&p_wf, g_wf);
    cudaFuncSetAttribute(mega_kernel, cudaFuncAttributeMaxDynamicSharedMemorySize, SM_TOTAL);
    cudaLaunchConfig_t cfg = {};
    cudaLaunchAttribute at; at.id = cudaLaunchAttributeClusterDimension; at.val.clusterDim.x = 2; at.val.clusterDim.y = 1; at.val.clusterDim.z = 1;
    cfg.gridDim = dim3(132); cfg.blockDim = dim3(384); cfg.dynamicSmemBytes = SM_TOTAL; cfg.attrs = &at; cfg.numAttrs = 1;
    int nc = 0;
    if (cudaOccupancyMaxActiveClusters(&nc, mega_kernel, &cfg) != cudaSuccess) { nc = 0; (void)cudaGetLastError(); }
    boff = nc >= 66 ? 0u : 4u;
  }
  Maps maps;
  make_map5(enc, &maps.m[MAP_WF], p_wf, 2048);
  make_map5(enc, &maps.m[MAP_WA], A_wqkv, 3072);
  make_map5(enc, &maps.m[MAP_WB], B_wqkv, 3072);
  make_map5(enc, &maps.m[MAP_WOA], A_wo, 1024);
  make_map5(enc, &maps.m[MAP_WOB], B_wo, 1024);
  make_map2(enc, &maps.m[MAP_X0], A_x, 1024, 2048, 64, 128);
  make_map2(enc, &maps.m[MAP_X], p_x, 1024, 2048, 64, 128);
  make_map2(enc, &maps.m[MAP_O], p_o, 1024, 2048, 64, 128);
  make_map2(enc, &maps.m[MAP_PHI], A_wphi, 32, 1024, 32, 128);
  Ctx c; c.zero = 0u; c.boff = boff; c.x0 = A_x; c.out = out;
  mega_kernel<<<132, 384, SM_TOTAL, cudaStreamPerThread>>>(maps, c, A_wqkv, B_wqkv, A_wo, B_wo);
}
```

```cpp
#include <cuda_runtime.h>
#include <cuda_bf16.h>
#include <cuda.h>
#include <stdint.h>

typedef __nv_bfloat16 bf16;

constexpr int S_ = 2048, D_ = 1024;

struct __align__(128) Flag { unsigned int v; unsigned int pad[31]; };
__device__ __align__(1024) bf16 g_x[S_ * D_];
__device__ __align__(1024) bf16 g_o[S_ * D_];
__device__ __align__(1024) uint32_t g_halo[2 * 17 * 8 * 2048];
__device__ __align__(1024) bf16 g_kv[2 * 2 * 8 * 10240];
__device__ __align__(1024) float2 g_stats[2 * 4 * S_];
__device__ __align__(1024) float g_cs[2 * 2 * 3072];
__device__ __align__(1024) bf16 g_wf[D_ * 2048];
__device__ Flag g_kvflag[16], g_csflag[13];
__device__ __align__(128) unsigned int g_xf[16 * 32], g_of[16 * 32];
__device__ __align__(128) unsigned int g_hf[16 * 32];
__device__ __align__(128) unsigned int g_wff[8 * 32];
__device__ unsigned int g_epoch, g_err;
#define PROFT(cond, idx) asm volatile("" ::: "memory")

__device__ __forceinline__ uint32_t smem_u32(const void* p) { return (uint32_t)__cvta_generic_to_shared(p); }
__device__ __forceinline__ void mbar_init(uint32_t bar, uint32_t count) {
  asm volatile("mbarrier.init.shared::cta.b64 [%0], %1;" ::"r"(bar), "r"(count) : "memory");
}
__device__ __forceinline__ void mbar_expect_tx(uint32_t bar, uint32_t bytes) {
  asm volatile("mbarrier.arrive.expect_tx.shared::cta.b64 _, [%0], %1;" ::"r"(bar), "r"(bytes) : "memory");
}
__device__ __forceinline__ void mbar_arrive(uint32_t bar) {
  asm volatile("mbarrier.arrive.shared::cta.b64 _, [%0];" ::"r"(bar) : "memory");
}
__device__ __forceinline__ bool mbar_try_wait(uint32_t bar, uint32_t parity) {
  uint32_t ok;
  asm volatile("{\n.reg .pred p;\nmbarrier.try_wait.parity.shared::cta.b64 p, [%1], %2;\nselp.b32 %0, 1, 0, p;\n}\n"
               : "=r"(ok) : "r"(bar), "r"(parity) : "memory");
  return ok != 0;
}
__device__ __forceinline__ bool mbar_test_wait(uint32_t bar, uint32_t parity) {
  uint32_t ok;
  asm volatile("{\n.reg .pred p;\nmbarrier.test_wait.parity.shared::cta.b64 p, [%1], %2;\nselp.b32 %0, 1, 0, p;\n}\n"
               : "=r"(ok) : "r"(bar), "r"(parity) : "memory");
  return ok != 0;
}
__device__ __forceinline__ uint64_t gtimer() {
  uint64_t t; asm volatile("mov.u64 %0, %globaltimer;" : "=l"(t)); return t;
}
__device__ __forceinline__ void mbar_wait(uint32_t bar, uint32_t parity) {
  uint32_t n = 0;
  bool ok;
#pragma unroll 1
  do { ++n; ok = mbar_try_wait(bar, parity); } while (!ok && n < (1u << 22));
}
__device__ __forceinline__ unsigned int ld_acquire(const unsigned int* p) {
  unsigned int v; asm volatile("ld.acquire.gpu.global.u32 %0, [%1];" : "=r"(v) : "l"(p) : "memory"); return v;
}
__device__ __forceinline__ void flag_add(unsigned int* p) {
  asm volatile("red.release.gpu.global.add.u32 [%0], 1;" ::"l"(p) : "memory");
}
__device__ __forceinline__ void flag_set(unsigned int* p, unsigned int v) {
  asm volatile("st.release.gpu.global.u32 [%0], %1;" ::"l"(p), "r"(v) : "memory");
}
template <int SLEEP>
__device__ __forceinline__ void src_wait(const unsigned int* f, unsigned int target, uint32_t need, uint32_t& ready, int lane) {
  uint32_t n = 0;
#pragma unroll 1
  while ((ready & need) != need) {
    const unsigned int v = ld_acquire(f + (lane & 15));
    ready = __ballot_sync(0xffffffffu, (int)(v - target) >= 0);
    if (SLEEP) { if ((ready & need) != need) __nanosleep(SLEEP); }
    if (++n > (1u << 20)) break;
  }
  __syncwarp();
}
__device__ __forceinline__ unsigned int ld_relaxed(const unsigned int* p);
__device__ __forceinline__ unsigned int ld_relaxed(const unsigned int* p) {
  unsigned int v; asm volatile("ld.relaxed.gpu.global.u32 %0, [%1];" : "=r"(v) : "l"(p) : "memory"); return v;
}
template <int SLEEP>
__device__ __forceinline__ void flag_wait_t(const unsigned int* p, unsigned int target) {
  uint32_t n = 0;
#pragma unroll 1
  while ((int)(ld_acquire(p) - target) < 0) {
    if (SLEEP) __nanosleep(SLEEP);
    if (++n > (1u << 20)) break;
  }
}
__device__ __forceinline__ void flag_wait(const unsigned int* p, unsigned int target) { flag_wait_t<0>(p, target); }
__device__ __forceinline__ void flag_wait_slow(const unsigned int* p, unsigned int target) { flag_wait_t<256>(p, target); }
__device__ __forceinline__ void mbar_wait_u(uint32_t bar, uint32_t parity) {
  uint32_t n = 0;
#pragma unroll 1
  while (!__all_sync(0xffffffffu, mbar_try_wait(bar, parity))) {
    if (++n > (1u << 22)) break;
  }
}
__device__ __forceinline__ void expect_tx_e(uint32_t bar, uint32_t bytes) {
  asm volatile("{\n.reg .pred p;\nelect.sync _|p, 0xffffffff;\n@p mbarrier.arrive.expect_tx.shared::cta.b64 _, [%0], %1;\n}\n" ::"r"(bar), "r"(bytes) : "memory");
}
__device__ __forceinline__ void tma_2d_e(uint32_t dst, const CUtensorMap* tm, int c0, int c1, uint32_t bar) {
  asm volatile("{\n.reg .pred p;\nelect.sync _|p, 0xffffffff;\n"
               "@p cp.async.bulk.tensor.2d.shared::cluster.global.mbarrier::complete_tx::bytes [%0], [%1, {%2, %3}], [%4];\n}\n"
               ::"r"(dst), "l"(tm), "r"(c0), "r"(c1), "r"(bar) : "memory");
}
__device__ __forceinline__ void tma_5d_e(uint32_t dst, const CUtensorMap* tm, int c0, int c4, uint32_t bar) {
  asm volatile("{\n.reg .pred p;\nelect.sync _|p, 0xffffffff;\n"
               "@p cp.async.bulk.tensor.5d.shared::cluster.global.mbarrier::complete_tx::bytes [%0], [%1, {%2, %5, %5, %5, %3}], [%4];\n}\n"
               ::"r"(dst), "l"(tm), "r"(c0), "r"(c4), "r"(bar), "r"(0) : "memory");
}
__device__ __forceinline__ void tma_5d_mc_e(uint32_t dst, const CUtensorMap* tm, int c0, int c4, uint32_t bar) {
  asm volatile("{\n.reg .pred p;\nelect.sync _|p, 0xffffffff;\n"
               "@p cp.async.bulk.tensor.5d.shared::cluster.global.mbarrier::complete_tx::bytes.multicast::cluster [%0], [%1, {%2, %6, %6, %6, %3}], [%4], %5;\n}\n"
               ::"r"(dst), "l"(tm), "r"(c0), "r"(c4), "r"(bar), "h"((uint16_t)3), "r"(0) : "memory");
}
__device__ __forceinline__ void wait_tma_5d_mc(bool w, uint32_t eb, uint32_t par, uint32_t dst, const CUtensorMap* tm, int c0, int c4, uint32_t fb) {
  asm volatile("" : "+r"(dst), "+l"(tm), "+r"(c0), "+r"(c4), "+r"(fb));
  if (w) mbar_wait_u(eb, par);
  tma_5d_mc_e(dst, tm, c0, c4, fb);
}
__device__ __forceinline__ void stg128(void* p, uint32_t a, uint32_t b, uint32_t c, uint32_t d) {
  asm volatile("st.global.v4.u32 [%0], {%1,%2,%3,%4};" ::"l"(p), "r"(a), "r"(b), "r"(c), "r"(d) : "memory");
}
__device__ __forceinline__ void stg128_p(bool on, void* p, uint32_t a, uint32_t b, uint32_t c, uint32_t d) {
  asm volatile("{\n.reg .pred p;\nsetp.ne.b32 p, %5, 0;\n@p st.global.v4.u32 [%0], {%1,%2,%3,%4};\n}\n" ::"l"(p), "r"(a), "r"(b), "r"(c), "r"(d), "r"((int)on) : "memory");
}
__device__ __forceinline__ void ldg128(const void* p, uint32_t& a, uint32_t& b, uint32_t& c, uint32_t& d) {
  asm volatile("ld.global.cg.v4.u32 {%0,%1,%2,%3}, [%4];" : "=r"(a), "=r"(b), "=r"(c), "=r"(d) : "l"(p) : "memory");
}
__device__ __forceinline__ void release2c(uint32_t off) {
  asm volatile("mbarrier.arrive.shared::cluster.b64 _, [%0];\nmbarrier.arrive.shared::cluster.b64 _, [%1];" ::"r"(off), "r"(off + (1u << 24)) : "memory");
}
__device__ __forceinline__ void tma_store_5d(const CUtensorMap* tm, uint32_t src, int c0, int c4) {
  asm volatile("cp.async.bulk.tensor.5d.global.shared::cta.bulk_group [%0, {%2, %4, %4, %4, %3}], [%1];"
               ::"l"(tm), "r"(src), "r"(c0), "r"(c4), "r"(0) : "memory");
}
__device__ __forceinline__ void bulk_load(uint32_t dst, const void* src, uint32_t bytes, uint32_t bar) {
  asm volatile("cp.async.bulk.shared::cluster.global.mbarrier::complete_tx::bytes [%0], [%1], %2, [%3];" ::"r"(dst), "l"(src), "r"(bytes), "r"(bar) : "memory");
}
__device__ __forceinline__ void bulk_red_add(void* dst, uint32_t src, uint32_t bytes) {
  asm volatile("cp.reduce.async.bulk.global.shared::cta.bulk_group.add.noftz.bf16 [%0], [%1], %2;" ::"l"(dst), "r"(src), "r"(bytes) : "memory");
}
__device__ __forceinline__ void bulk_commit() { asm volatile("cp.async.bulk.commit_group;" ::: "memory"); }
__device__ __forceinline__ void bulk_wait0() { asm volatile("cp.async.bulk.wait_group 0;" ::: "memory"); }
__device__ __forceinline__ void fence_async_smem() { asm volatile("fence.proxy.async.shared::cta;" ::: "memory"); }
__device__ __forceinline__ void fence_async_all() { asm volatile("fence.proxy.async.global;" ::: "memory"); }
__device__ __forceinline__ void wgmma_fence() { asm volatile("wgmma.fence.sync.aligned;" ::: "memory"); }
__device__ __forceinline__ void wgmma_commit() { asm volatile("wgmma.commit_group.sync.aligned;" ::: "memory"); }
template <int N> __device__ __forceinline__ void wgmma_wait() { asm volatile("wgmma.wait_group.sync.aligned %0;" ::"n"(N) : "memory"); }
__device__ __forceinline__ void cluster_wait() { asm volatile("barrier.cluster.wait.acquire.aligned;" ::: "memory"); }
template <int ID, int N> __device__ __forceinline__ void nbar() { asm volatile("bar.sync %0, %1;" ::"n"(ID), "n"(N) : "memory"); }
__device__ __forceinline__ uint64_t desc64(uint32_t lo, uint32_t hi) { return (uint64_t)lo | ((uint64_t)hi << 32); }
__device__ __forceinline__ uint32_t pack_bf16(float lo, float hi) {
  uint32_t r; asm("cvt.rn.bf16x2.f32 %0, %1, %2;" : "=r"(r) : "f"(hi), "f"(lo)); return r;
}
__device__ __forceinline__ uint32_t add_bf16x2(uint32_t a, uint32_t b) {
  uint32_t r; asm("add.rn.bf16x2 %0, %1, %2;" : "=r"(r) : "r"(a), "r"(b)); return r;
}
__device__ __forceinline__ float bf16r(float x) { return __bfloat162float(__float2bfloat16_rn(x)); }
__device__ __forceinline__ float bf_lo(uint32_t u) { return __uint_as_float(u << 16); }
__device__ __forceinline__ float bf_hi(uint32_t u) { return __uint_as_float(u & 0xFFFF0000u); }
__device__ __forceinline__ float ex2(float x) { float r; asm("ex2.approx.ftz.f32 %0, %1;" : "=f"(r) : "f"(x)); return r; }
__device__ __forceinline__ float ex2v(float x) { float r; asm volatile("ex2.approx.ftz.f32 %0, %1;" : "=f"(r) : "f"(x) : "memory"); return r; }
__device__ __forceinline__ float rcp(float x) { float r; asm("rcp.approx.ftz.f32 %0, %1;" : "=f"(r) : "f"(x)); return r; }
__device__ __forceinline__ void mma_bf16(float (&d)[4], uint32_t a0, uint32_t a1, uint32_t a2, uint32_t a3, uint32_t b0, uint32_t b1) {
  asm("mma.sync.aligned.m16n8k16.row.col.f32.bf16.bf16.f32 {%0,%1,%2,%3}, {%4,%5,%6,%7}, {%8,%9}, {%0,%1,%2,%3};"
               : "+f"(d[0]), "+f"(d[1]), "+f"(d[2]), "+f"(d[3]) : "r"(a0), "r"(a1), "r"(a2), "r"(a3), "r"(b0), "r"(b1));
}
__device__ __forceinline__ void ldsm_x4(uint32_t& r0, uint32_t& r1, uint32_t& r2, uint32_t& r3, uint32_t addr) {
  asm volatile("ldmatrix.sync.aligned.m8n8.x4.shared.b16 {%0,%1,%2,%3}, [%4];"
               : "=r"(r0), "=r"(r1), "=r"(r2), "=r"(r3) : "r"(addr) : "memory");
}
__device__ __forceinline__ void ldsm_x4_t(uint32_t& r0, uint32_t& r1, uint32_t& r2, uint32_t& r3, uint32_t addr) {
  asm volatile("ldmatrix.sync.aligned.m8n8.x4.trans.shared.b16 {%0,%1,%2,%3}, [%4];"
               : "=r"(r0), "=r"(r1), "=r"(r2), "=r"(r3) : "r"(addr) : "memory");
}
__device__ __forceinline__ void stsm_x4(uint32_t addr, uint32_t r0, uint32_t r1, uint32_t r2, uint32_t r3) {
  asm volatile("stmatrix.sync.aligned.m8n8.x4.shared.b16 [%0], {%1,%2,%3,%4};"
               ::"r"(addr), "r"(r0), "r"(r1), "r"(r2), "r"(r3) : "memory");
}
__device__ __forceinline__ void stsm_x2(uint32_t addr, uint32_t r0, uint32_t r1) {
  asm volatile("stmatrix.sync.aligned.m8n8.x2.shared.b16 [%0], {%1,%2};" ::"r"(addr), "r"(r0), "r"(r1) : "memory");
}
__device__ __forceinline__ uint4 lds128(uint32_t addr) {
  uint4 v; asm volatile("ld.shared.v4.b32 {%0,%1,%2,%3}, [%4];" : "=r"(v.x), "=r"(v.y), "=r"(v.z), "=r"(v.w) : "r"(addr) : "memory"); return v;
}
__device__ __forceinline__ void sts128(uint32_t addr, uint4 v) {
  asm volatile("st.shared.v4.b32 [%0], {%1,%2,%3,%4};" ::"r"(addr), "r"(v.x), "r"(v.y), "r"(v.z), "r"(v.w) : "memory");
}
__device__ __forceinline__ float lds_f(uint32_t addr) {
  float v; asm volatile("ld.shared.f32 %0, [%1];" : "=f"(v) : "r"(addr) : "memory"); return v;
}
__device__ __forceinline__ void nbar_dyn(int id, int n) { asm volatile("bar.sync %0, %1;" ::"r"(id), "r"(n) : "memory"); }
__device__ __forceinline__ uint64_t make_desc_ns(uint32_t addr, uint32_t lbo_bytes, uint32_t sbo_bytes) {
  return (uint64_t)((addr & 0x3FFFF) >> 4) | ((uint64_t)(lbo_bytes >> 4) << 16) | ((uint64_t)(sbo_bytes >> 4) << 32);
}
__device__ __forceinline__ void sts_f(uint32_t addr, float v) { asm volatile("st.shared.f32 [%0], %1;" ::"r"(addr), "f"(v) : "memory"); }
__device__ __forceinline__ void sts64(uint32_t addr, uint32_t a, uint32_t b) {
  asm volatile("st.shared.v2.b32 [%0], {%1,%2};" ::"r"(addr), "r"(a), "r"(b) : "memory");
}
__device__ __forceinline__ void sts_f2(uint32_t addr, float a, float b) {
  asm volatile("st.shared.v2.f32 [%0], {%1,%2};" ::"r"(addr), "f"(a), "f"(b) : "memory");
}
__device__ __forceinline__ void red_add2_p(bool on, float* p, float a, float b) {
  asm volatile("{\n.reg .pred p;\nsetp.ne.b32 p, %3, 0;\n@p red.global.add.v2.f32 [%0], {%1,%2};\n}\n" ::"l"(p), "f"(a), "f"(b), "r"((int)on) : "memory");
}
__device__ __forceinline__ void red_add4(float* p, float a, float b, float c, float d) {
  asm volatile("red.global.add.v4.f32 [%0], {%1,%2,%3,%4};" ::"l"(p), "f"(a), "f"(b), "f"(c), "f"(d) : "memory");
}
__device__ __forceinline__ void red_add1(float* p, float a) {
  asm volatile("red.global.add.f32 [%0], %1;" ::"l"(p), "f"(a) : "memory");
}
__device__ __forceinline__ void l2_prefetch(const void* p, uint32_t bytes) {
  asm volatile("cp.async.bulk.prefetch.L2.global [%0], %1;" ::"l"(p), "r"(bytes) : "memory");
}

__device__ __forceinline__ void wgmma_n256(float (&d)[192], uint64_t da, uint64_t db, int scale_d) {
  asm volatile("{\n.reg .pred p;\nsetp.ne.b32 p, %130, 0;\n"
    "wgmma.mma_async.sync.aligned.m64n256k16.f32.bf16.bf16 {%0, %1, %2, %3, %4, %5, %6, %7, %8, %9, %10, %11, %12, %13, %14, %15, %16, %17, %18, %19, %20, %21, %22, %23, %24, %25, %26, %27, %28, %29, %30, %31, %32, %33, %34, %35, %36, %37, %38, %39, %40, %41, %42, %43, %44, %45, %46, %47, %48, %49, %50, %51, %52, %53, %54, %55, %56, %57, %58, %59, %60, %61, %62, %63, %64, %65, %66, %67, %68, %69, %70, %71, %72, %73, %74, %75, %76, %77, %78, %79, %80, %81, %82, %83, %84, %85, %86, %87, %88, %89, %90, %91, %92, %93, %94, %95, %96, %97, %98, %99, %100, %101, %102, %103, %104, %105, %106, %107, %108, %109, %110, %111, %112, %113, %114, %115, %116, %117, %118, %119, %120, %121, %122, %123, %124, %125, %126, %127}, %128, %129, p, 1, 1, 0, 1;\n}\n"
    : "+f"(d[0]), "+f"(d[1]), "+f"(d[2]), "+f"(d[3]), "+f"(d[4]), "+f"(d[5]), "+f"(d[6]), "+f"(d[7]), "+f"(d[8]), "+f"(d[9]), "+f"(d[10]), "+f"(d[11]), "+f"(d[12]), "+f"(d[13]), "+f"(d[14]), "+f"(d[15]), "+f"(d[16]), "+f"(d[17]), "+f"(d[18]), "+f"(d[19]), "+f"(d[20]), "+f"(d[21]), "+f"(d[22]), "+f"(d[23]), "+f"(d[24]), "+f"(d[25]), "+f"(d[26]), "+f"(d[27]), "+f"(d[28]), "+f"(d[29]), "+f"(d[30]), "+f"(d[31]), "+f"(d[32]), "+f"(d[33]), "+f"(d[34]), "+f"(d[35]), "+f"(d[36]), "+f"(d[37]), "+f"(d[38]), "+f"(d[39]), "+f"(d[40]), "+f"(d[41]), "+f"(d[42]), "+f"(d[43]), "+f"(d[44]), "+f"(d[45]), "+f"(d[46]), "+f"(d[47]), "+f"(d[48]), "+f"(d[49]), "+f"(d[50]), "+f"(d[51]), "+f"(d[52]), "+f"(d[53]), "+f"(d[54]), "+f"(d[55]), "+f"(d[56]), "+f"(d[57]), "+f"(d[58]), "+f"(d[59]), "+f"(d[60]), "+f"(d[61]), "+f"(d[62]), "+f"(d[63]), "+f"(d[64]), "+f"(d[65]), "+f"(d[66]), "+f"(d[67]), "+f"(d[68]), "+f"(d[69]), "+f"(d[70]), "+f"(d[71]), "+f"(d[72]), "+f"(d[73]), "+f"(d[74]), "+f"(d[75]), "+f"(d[76]), "+f"(d[77]), "+f"(d[78]), "+f"(d[79]), "+f"(d[80]), "+f"(d[81]), "+f"(d[82]), "+f"(d[83]), "+f"(d[84]), "+f"(d[85]), "+f"(d[86]), "+f"(d[87]), "+f"(d[88]), "+f"(d[89]), "+f"(d[90]), "+f"(d[91]), "+f"(d[92]), "+f"(d[93]), "+f"(d[94]), "+f"(d[95]), "+f"(d[96]), "+f"(d[97]), "+f"(d[98]), "+f"(d[99]), "+f"(d[100]), "+f"(d[101]), "+f"(d[102]), "+f"(d[103]), "+f"(d[104]), "+f"(d[105]), "+f"(d[106]), "+f"(d[107]), "+f"(d[108]), "+f"(d[109]), "+f"(d[110]), "+f"(d[111]), "+f"(d[112]), "+f"(d[113]), "+f"(d[114]), "+f"(d[115]), "+f"(d[116]), "+f"(d[117]), "+f"(d[118]), "+f"(d[119]), "+f"(d[120]), "+f"(d[121]), "+f"(d[122]), "+f"(d[123]), "+f"(d[124]), "+f"(d[125]), "+f"(d[126]), "+f"(d[127])
    : "l"(da), "l"(db), "r"(scale_d));
}
__device__ __forceinline__ void wgmma_n128(float (&d)[192], uint64_t da, uint64_t db, int scale_d) {
  asm volatile("{\n.reg .pred p;\nsetp.ne.b32 p, %66, 0;\n"
    "wgmma.mma_async.sync.aligned.m64n128k16.f32.bf16.bf16 {%0, %1, %2, %3, %4, %5, %6, %7, %8, %9, %10, %11, %12, %13, %14, %15, %16, %17, %18, %19, %20, %21, %22, %23, %24, %25, %26, %27, %28, %29, %30, %31, %32, %33, %34, %35, %36, %37, %38, %39, %40, %41, %42, %43, %44, %45, %46, %47, %48, %49, %50, %51, %52, %53, %54, %55, %56, %57, %58, %59, %60, %61, %62, %63}, %64, %65, p, 1, 1, 0, 1;\n}\n"
    : "+f"(d[128]), "+f"(d[129]), "+f"(d[130]), "+f"(d[131]), "+f"(d[132]), "+f"(d[133]), "+f"(d[134]), "+f"(d[135]), "+f"(d[136]), "+f"(d[137]), "+f"(d[138]), "+f"(d[139]), "+f"(d[140]), "+f"(d[141]), "+f"(d[142]), "+f"(d[143]), "+f"(d[144]), "+f"(d[145]), "+f"(d[146]), "+f"(d[147]), "+f"(d[148]), "+f"(d[149]), "+f"(d[150]), "+f"(d[151]), "+f"(d[152]), "+f"(d[153]), "+f"(d[154]), "+f"(d[155]), "+f"(d[156]), "+f"(d[157]), "+f"(d[158]), "+f"(d[159]), "+f"(d[160]), "+f"(d[161]), "+f"(d[162]), "+f"(d[163]), "+f"(d[164]), "+f"(d[165]), "+f"(d[166]), "+f"(d[167]), "+f"(d[168]), "+f"(d[169]), "+f"(d[170]), "+f"(d[171]), "+f"(d[172]), "+f"(d[173]), "+f"(d[174]), "+f"(d[175]), "+f"(d[176]), "+f"(d[177]), "+f"(d[178]), "+f"(d[179]), "+f"(d[180]), "+f"(d[181]), "+f"(d[182]), "+f"(d[183]), "+f"(d[184]), "+f"(d[185]), "+f"(d[186]), "+f"(d[187]), "+f"(d[188]), "+f"(d[189]), "+f"(d[190]), "+f"(d[191])
    : "l"(da), "l"(db), "r"(scale_d));
}
__device__ __forceinline__ void wgmma_n256_k(float (&d)[192], uint64_t da, uint64_t db, int scale_d) {
  asm volatile("{\n.reg .pred p;\nsetp.ne.b32 p, %130, 0;\n"
    "wgmma.mma_async.sync.aligned.m64n256k16.f32.bf16.bf16 {%0, %1, %2, %3, %4, %5, %6, %7, %8, %9, %10, %11, %12, %13, %14, %15, %16, %17, %18, %19, %20, %21, %22, %23, %24, %25, %26, %27, %28, %29, %30, %31, %32, %33, %34, %35, %36, %37, %38, %39, %40, %41, %42, %43, %44, %45, %46, %47, %48, %49, %50, %51, %52, %53, %54, %55, %56, %57, %58, %59, %60, %61, %62, %63, %64, %65, %66, %67, %68, %69, %70, %71, %72, %73, %74, %75, %76, %77, %78, %79, %80, %81, %82, %83, %84, %85, %86, %87, %88, %89, %90, %91, %92, %93, %94, %95, %96, %97, %98, %99, %100, %101, %102, %103, %104, %105, %106, %107, %108, %109, %110, %111, %112, %113, %114, %115, %116, %117, %118, %119, %120, %121, %122, %123, %124, %125, %126, %127}, %128, %129, p, 1, 1, 0, 0;\n}\n"
    : "+f"(d[0]), "+f"(d[1]), "+f"(d[2]), "+f"(d[3]), "+f"(d[4]), "+f"(d[5]), "+f"(d[6]), "+f"(d[7]), "+f"(d[8]), "+f"(d[9]), "+f"(d[10]), "+f"(d[11]), "+f"(d[12]), "+f"(d[13]), "+f"(d[14]), "+f"(d[15]), "+f"(d[16]), "+f"(d[17]), "+f"(d[18]), "+f"(d[19]), "+f"(d[20]), "+f"(d[21]), "+f"(d[22]), "+f"(d[23]), "+f"(d[24]), "+f"(d[25]), "+f"(d[26]), "+f"(d[27]), "+f"(d[28]), "+f"(d[29]), "+f"(d[30]), "+f"(d[31]), "+f"(d[32]), "+f"(d[33]), "+f"(d[34]), "+f"(d[35]), "+f"(d[36]), "+f"(d[37]), "+f"(d[38]), "+f"(d[39]), "+f"(d[40]), "+f"(d[41]), "+f"(d[42]), "+f"(d[43]), "+f"(d[44]), "+f"(d[45]), "+f"(d[46]), "+f"(d[47]), "+f"(d[48]), "+f"(d[49]), "+f"(d[50]), "+f"(d[51]), "+f"(d[52]), "+f"(d[53]), "+f"(d[54]), "+f"(d[55]), "+f"(d[56]), "+f"(d[57]), "+f"(d[58]), "+f"(d[59]), "+f"(d[60]), "+f"(d[61]), "+f"(d[62]), "+f"(d[63]), "+f"(d[64]), "+f"(d[65]), "+f"(d[66]), "+f"(d[67]), "+f"(d[68]), "+f"(d[69]), "+f"(d[70]), "+f"(d[71]), "+f"(d[72]), "+f"(d[73]), "+f"(d[74]), "+f"(d[75]), "+f"(d[76]), "+f"(d[77]), "+f"(d[78]), "+f"(d[79]), "+f"(d[80]), "+f"(d[81]), "+f"(d[82]), "+f"(d[83]), "+f"(d[84]), "+f"(d[85]), "+f"(d[86]), "+f"(d[87]), "+f"(d[88]), "+f"(d[89]), "+f"(d[90]), "+f"(d[91]), "+f"(d[92]), "+f"(d[93]), "+f"(d[94]), "+f"(d[95]), "+f"(d[96]), "+f"(d[97]), "+f"(d[98]), "+f"(d[99]), "+f"(d[100]), "+f"(d[101]), "+f"(d[102]), "+f"(d[103]), "+f"(d[104]), "+f"(d[105]), "+f"(d[106]), "+f"(d[107]), "+f"(d[108]), "+f"(d[109]), "+f"(d[110]), "+f"(d[111]), "+f"(d[112]), "+f"(d[113]), "+f"(d[114]), "+f"(d[115]), "+f"(d[116]), "+f"(d[117]), "+f"(d[118]), "+f"(d[119]), "+f"(d[120]), "+f"(d[121]), "+f"(d[122]), "+f"(d[123]), "+f"(d[124]), "+f"(d[125]), "+f"(d[126]), "+f"(d[127])
    : "l"(da), "l"(db), "r"(scale_d));
}
__device__ __forceinline__ void wgmma_n128_k(float (&d)[192], uint64_t da, uint64_t db, int scale_d) {
  asm volatile("{\n.reg .pred p;\nsetp.ne.b32 p, %66, 0;\n"
    "wgmma.mma_async.sync.aligned.m64n128k16.f32.bf16.bf16 {%0, %1, %2, %3, %4, %5, %6, %7, %8, %9, %10, %11, %12, %13, %14, %15, %16, %17, %18, %19, %20, %21, %22, %23, %24, %25, %26, %27, %28, %29, %30, %31, %32, %33, %34, %35, %36, %37, %38, %39, %40, %41, %42, %43, %44, %45, %46, %47, %48, %49, %50, %51, %52, %53, %54, %55, %56, %57, %58, %59, %60, %61, %62, %63}, %64, %65, p, 1, 1, 0, 0;\n}\n"
    : "+f"(d[128]), "+f"(d[129]), "+f"(d[130]), "+f"(d[131]), "+f"(d[132]), "+f"(d[133]), "+f"(d[134]), "+f"(d[135]), "+f"(d[136]), "+f"(d[137]), "+f"(d[138]), "+f"(d[139]), "+f"(d[140]), "+f"(d[141]), "+f"(d[142]), "+f"(d[143]), "+f"(d[144]), "+f"(d[145]), "+f"(d[146]), "+f"(d[147]), "+f"(d[148]), "+f"(d[149]), "+f"(d[150]), "+f"(d[151]), "+f"(d[152]), "+f"(d[153]), "+f"(d[154]), "+f"(d[155]), "+f"(d[156]), "+f"(d[157]), "+f"(d[158]), "+f"(d[159]), "+f"(d[160]), "+f"(d[161]), "+f"(d[162]), "+f"(d[163]), "+f"(d[164]), "+f"(d[165]), "+f"(d[166]), "+f"(d[167]), "+f"(d[168]), "+f"(d[169]), "+f"(d[170]), "+f"(d[171]), "+f"(d[172]), "+f"(d[173]), "+f"(d[174]), "+f"(d[175]), "+f"(d[176]), "+f"(d[177]), "+f"(d[178]), "+f"(d[179]), "+f"(d[180]), "+f"(d[181]), "+f"(d[182]), "+f"(d[183]), "+f"(d[184]), "+f"(d[185]), "+f"(d[186]), "+f"(d[187]), "+f"(d[188]), "+f"(d[189]), "+f"(d[190]), "+f"(d[191])
    : "l"(da), "l"(db), "r"(scale_d));
}
__device__ __forceinline__ void wgmma_n40_tt(float (&d)[20], uint64_t da, uint64_t db, int scale_d) {
  asm volatile("{\n.reg .pred p;\nsetp.ne.b32 p, %22, 0;\n"
    "wgmma.mma_async.sync.aligned.m64n40k16.f32.bf16.bf16 {%0, %1, %2, %3, %4, %5, %6, %7, %8, %9, %10, %11, %12, %13, %14, %15, %16, %17, %18, %19}, %20, %21, p, 1, 1, 1, 1;\n}\n"
    : "+f"(d[0]), "+f"(d[1]), "+f"(d[2]), "+f"(d[3]), "+f"(d[4]), "+f"(d[5]), "+f"(d[6]), "+f"(d[7]), "+f"(d[8]), "+f"(d[9]), "+f"(d[10]), "+f"(d[11]), "+f"(d[12]), "+f"(d[13]), "+f"(d[14]), "+f"(d[15]), "+f"(d[16]), "+f"(d[17]), "+f"(d[18]), "+f"(d[19])
    : "l"(da), "l"(db), "r"(scale_d));
}
__device__ __forceinline__ void wgmma_n40_rs(float (&d)[20], const uint32_t (&a)[4], uint64_t db, int scale_d) {
  asm volatile("{\n.reg .pred p;\nsetp.ne.b32 p, %25, 0;\n"
    "wgmma.mma_async.sync.aligned.m64n40k16.f32.bf16.bf16 {%0, %1, %2, %3, %4, %5, %6, %7, %8, %9, %10, %11, %12, %13, %14, %15, %16, %17, %18, %19}, {%20, %21, %22, %23}, %24, p, 1, 1, 1;\n}\n"
    : "+f"(d[0]), "+f"(d[1]), "+f"(d[2]), "+f"(d[3]), "+f"(d[4]), "+f"(d[5]), "+f"(d[6]), "+f"(d[7]), "+f"(d[8]), "+f"(d[9]), "+f"(d[10]), "+f"(d[11]), "+f"(d[12]), "+f"(d[13]), "+f"(d[14]), "+f"(d[15]), "+f"(d[16]), "+f"(d[17]), "+f"(d[18]), "+f"(d[19])
    : "r"(a[0]), "r"(a[1]), "r"(a[2]), "r"(a[3]), "l"(db), "r"(scale_d));
}
__device__ __forceinline__ void wgmma_n128_0(float (&d)[192], uint64_t da, uint64_t db) {
  asm volatile("{\n.reg .pred p;\nsetp.ne.b32 p, 0, 0;\n"
    "wgmma.mma_async.sync.aligned.m64n128k16.f32.bf16.bf16 {%0, %1, %2, %3, %4, %5, %6, %7, %8, %9, %10, %11, %12, %13, %14, %15, %16, %17, %18, %19, %20, %21, %22, %23, %24, %25, %26, %27, %28, %29, %30, %31, %32, %33, %34, %35, %36, %37, %38, %39, %40, %41, %42, %43, %44, %45, %46, %47, %48, %49, %50, %51, %52, %53, %54, %55, %56, %57, %58, %59, %60, %61, %62, %63}, %64, %65, p, 1, 1, 0, 1;\n}\n"
    : "=f"(d[128]), "=f"(d[129]), "=f"(d[130]), "=f"(d[131]), "=f"(d[132]), "=f"(d[133]), "=f"(d[134]), "=f"(d[135]), "=f"(d[136]), "=f"(d[137]), "=f"(d[138]), "=f"(d[139]), "=f"(d[140]), "=f"(d[141]), "=f"(d[142]), "=f"(d[143]), "=f"(d[144]), "=f"(d[145]), "=f"(d[146]), "=f"(d[147]), "=f"(d[148]), "=f"(d[149]), "=f"(d[150]), "=f"(d[151]), "=f"(d[152]), "=f"(d[153]), "=f"(d[154]), "=f"(d[155]), "=f"(d[156]), "=f"(d[157]), "=f"(d[158]), "=f"(d[159]), "=f"(d[160]), "=f"(d[161]), "=f"(d[162]), "=f"(d[163]), "=f"(d[164]), "=f"(d[165]), "=f"(d[166]), "=f"(d[167]), "=f"(d[168]), "=f"(d[169]), "=f"(d[170]), "=f"(d[171]), "=f"(d[172]), "=f"(d[173]), "=f"(d[174]), "=f"(d[175]), "=f"(d[176]), "=f"(d[177]), "=f"(d[178]), "=f"(d[179]), "=f"(d[180]), "=f"(d[181]), "=f"(d[182]), "=f"(d[183]), "=f"(d[184]), "=f"(d[185]), "=f"(d[186]), "=f"(d[187]), "=f"(d[188]), "=f"(d[189]), "=f"(d[190]), "=f"(d[191])
    : "l"(da), "l"(db));
}
__device__ __forceinline__ void wgmma_n128_rs(float (&d)[192], const uint32_t (&a)[4], uint64_t db, int scale_d) {
  asm volatile("{\n.reg .pred p;\nsetp.ne.b32 p, %69, 0;\n"
    "wgmma.mma_async.sync.aligned.m64n128k16.f32.bf16.bf16 {%0, %1, %2, %3, %4, %5, %6, %7, %8, %9, %10, %11, %12, %13, %14, %15, %16, %17, %18, %19, %20, %21, %22, %23, %24, %25, %26, %27, %28, %29, %30, %31, %32, %33, %34, %35, %36, %37, %38, %39, %40, %41, %42, %43, %44, %45, %46, %47, %48, %49, %50, %51, %52, %53, %54, %55, %56, %57, %58, %59, %60, %61, %62, %63}, {%64, %65, %66, %67}, %68, p, 1, 1, 1;\n}\n"
    : "+f"(d[128]), "+f"(d[129]), "+f"(d[130]), "+f"(d[131]), "+f"(d[132]), "+f"(d[133]), "+f"(d[134]), "+f"(d[135]), "+f"(d[136]), "+f"(d[137]), "+f"(d[138]), "+f"(d[139]), "+f"(d[140]), "+f"(d[141]), "+f"(d[142]), "+f"(d[143]), "+f"(d[144]), "+f"(d[145]), "+f"(d[146]), "+f"(d[147]), "+f"(d[148]), "+f"(d[149]), "+f"(d[150]), "+f"(d[151]), "+f"(d[152]), "+f"(d[153]), "+f"(d[154]), "+f"(d[155]), "+f"(d[156]), "+f"(d[157]), "+f"(d[158]), "+f"(d[159]), "+f"(d[160]), "+f"(d[161]), "+f"(d[162]), "+f"(d[163]), "+f"(d[164]), "+f"(d[165]), "+f"(d[166]), "+f"(d[167]), "+f"(d[168]), "+f"(d[169]), "+f"(d[170]), "+f"(d[171]), "+f"(d[172]), "+f"(d[173]), "+f"(d[174]), "+f"(d[175]), "+f"(d[176]), "+f"(d[177]), "+f"(d[178]), "+f"(d[179]), "+f"(d[180]), "+f"(d[181]), "+f"(d[182]), "+f"(d[183]), "+f"(d[184]), "+f"(d[185]), "+f"(d[186]), "+f"(d[187]), "+f"(d[188]), "+f"(d[189]), "+f"(d[190]), "+f"(d[191])
    : "r"(a[0]), "r"(a[1]), "r"(a[2]), "r"(a[3]), "l"(db), "r"(scale_d));
}
__device__ __forceinline__ void wgmma_n32_0(float (&d)[16], uint64_t da, uint64_t db) {
  asm volatile("{\n.reg .pred p;\nsetp.ne.b32 p, 0, 0;\n"
    "wgmma.mma_async.sync.aligned.m64n32k16.f32.bf16.bf16 {%0, %1, %2, %3, %4, %5, %6, %7, %8, %9, %10, %11, %12, %13, %14, %15}, %16, %17, p, 1, 1, 0, 1;\n}\n"
    : "=f"(d[0]), "=f"(d[1]), "=f"(d[2]), "=f"(d[3]), "=f"(d[4]), "=f"(d[5]), "=f"(d[6]), "=f"(d[7]), "=f"(d[8]), "=f"(d[9]), "=f"(d[10]), "=f"(d[11]), "=f"(d[12]), "=f"(d[13]), "=f"(d[14]), "=f"(d[15])
    : "l"(da), "l"(db));
}
__device__ __forceinline__ void wgmma_n32(float (&d)[16], uint64_t da, uint64_t db, int scale_d) {
  asm volatile("{\n.reg .pred p;\nsetp.ne.b32 p, %18, 0;\n"
    "wgmma.mma_async.sync.aligned.m64n32k16.f32.bf16.bf16 {%0, %1, %2, %3, %4, %5, %6, %7, %8, %9, %10, %11, %12, %13, %14, %15}, %16, %17, p, 1, 1, 0, 1;\n}\n"
    : "+f"(d[0]), "+f"(d[1]), "+f"(d[2]), "+f"(d[3]), "+f"(d[4]), "+f"(d[5]), "+f"(d[6]), "+f"(d[7]), "+f"(d[8]), "+f"(d[9]), "+f"(d[10]), "+f"(d[11]), "+f"(d[12]), "+f"(d[13]), "+f"(d[14]), "+f"(d[15])
    : "l"(da), "l"(db), "r"(scale_d));
}
__device__ __forceinline__ void wgmma_n8_t(float (&d)[4], uint64_t da, uint64_t db, int scale_d) {
  asm volatile("{\n.reg .pred p;\nsetp.ne.b32 p, %6, 0;\n"
    "wgmma.mma_async.sync.aligned.m64n8k16.f32.bf16.bf16 {%0, %1, %2, %3}, %4, %5, p, 1, 1, 1, 0;\n}\n"
    : "+f"(d[0]), "+f"(d[1]), "+f"(d[2]), "+f"(d[3])
    : "l"(da), "l"(db), "r"(scale_d));
}
__device__ __forceinline__ void wgmma_n128_rs0(float (&d)[192], const uint32_t (&a)[4], uint64_t db) {
  asm volatile("{\n.reg .pred p;\nsetp.ne.b32 p, 0, 0;\n"
    "wgmma.mma_async.sync.aligned.m64n128k16.f32.bf16.bf16 {%0, %1, %2, %3, %4, %5, %6, %7, %8, %9, %10, %11, %12, %13, %14, %15, %16, %17, %18, %19, %20, %21, %22, %23, %24, %25, %26, %27, %28, %29, %30, %31, %32, %33, %34, %35, %36, %37, %38, %39, %40, %41, %42, %43, %44, %45, %46, %47, %48, %49, %50, %51, %52, %53, %54, %55, %56, %57, %58, %59, %60, %61, %62, %63}, {%64, %65, %66, %67}, %68, p, 1, 1, 1;\n}\n"
    : "=f"(d[128]), "=f"(d[129]), "=f"(d[130]), "=f"(d[131]), "=f"(d[132]), "=f"(d[133]), "=f"(d[134]), "=f"(d[135]), "=f"(d[136]), "=f"(d[137]), "=f"(d[138]), "=f"(d[139]), "=f"(d[140]), "=f"(d[141]), "=f"(d[142]), "=f"(d[143]), "=f"(d[144]), "=f"(d[145]), "=f"(d[146]), "=f"(d[147]), "=f"(d[148]), "=f"(d[149]), "=f"(d[150]), "=f"(d[151]), "=f"(d[152]), "=f"(d[153]), "=f"(d[154]), "=f"(d[155]), "=f"(d[156]), "=f"(d[157]), "=f"(d[158]), "=f"(d[159]), "=f"(d[160]), "=f"(d[161]), "=f"(d[162]), "=f"(d[163]), "=f"(d[164]), "=f"(d[165]), "=f"(d[166]), "=f"(d[167]), "=f"(d[168]), "=f"(d[169]), "=f"(d[170]), "=f"(d[171]), "=f"(d[172]), "=f"(d[173]), "=f"(d[174]), "=f"(d[175]), "=f"(d[176]), "=f"(d[177]), "=f"(d[178]), "=f"(d[179]), "=f"(d[180]), "=f"(d[181]), "=f"(d[182]), "=f"(d[183]), "=f"(d[184]), "=f"(d[185]), "=f"(d[186]), "=f"(d[187]), "=f"(d[188]), "=f"(d[189]), "=f"(d[190]), "=f"(d[191])
    : "r"(a[0]), "r"(a[1]), "r"(a[2]), "r"(a[3]), "l"(db));
}
__device__ __forceinline__ void wgmma_n256_rs(float (&d)[192], const uint32_t (&a)[4], uint64_t db, int scale_d) {
  asm volatile("{\n.reg .pred p;\nsetp.ne.b32 p, %133, 0;\n"
    "wgmma.mma_async.sync.aligned.m64n256k16.f32.bf16.bf16 {%0, %1, %2, %3, %4, %5, %6, %7, %8, %9, %10, %11, %12, %13, %14, %15, %16, %17, %18, %19, %20, %21, %22, %23, %24, %25, %26, %27, %28, %29, %30, %31, %32, %33, %34, %35, %36, %37, %38, %39, %40, %41, %42, %43, %44, %45, %46, %47, %48, %49, %50, %51, %52, %53, %54, %55, %56, %57, %58, %59, %60, %61, %62, %63, %64, %65, %66, %67, %68, %69, %70, %71, %72, %73, %74, %75, %76, %77, %78, %79, %80, %81, %82, %83, %84, %85, %86, %87, %88, %89, %90, %91, %92, %93, %94, %95, %96, %97, %98, %99, %100, %101, %102, %103, %104, %105, %106, %107, %108, %109, %110, %111, %112, %113, %114, %115, %116, %117, %118, %119, %120, %121, %122, %123, %124, %125, %126, %127}, {%128, %129, %130, %131}, %132, p, 1, 1, 1;\n}\n"
    : "+f"(d[0]), "+f"(d[1]), "+f"(d[2]), "+f"(d[3]), "+f"(d[4]), "+f"(d[5]), "+f"(d[6]), "+f"(d[7]), "+f"(d[8]), "+f"(d[9]), "+f"(d[10]), "+f"(d[11]), "+f"(d[12]), "+f"(d[13]), "+f"(d[14]), "+f"(d[15]), "+f"(d[16]), "+f"(d[17]), "+f"(d[18]), "+f"(d[19]), "+f"(d[20]), "+f"(d[21]), "+f"(d[22]), "+f"(d[23]), "+f"(d[24]), "+f"(d[25]), "+f"(d[26]), "+f"(d[27]), "+f"(d[28]), "+f"(d[29]), "+f"(d[30]), "+f"(d[31]), "+f"(d[32]), "+f"(d[33]), "+f"(d[34]), "+f"(d[35]), "+f"(d[36]), "+f"(d[37]), "+f"(d[38]), "+f"(d[39]), "+f"(d[40]), "+f"(d[41]), "+f"(d[42]), "+f"(d[43]), "+f"(d[44]), "+f"(d[45]), "+f"(d[46]), "+f"(d[47]), "+f"(d[48]), "+f"(d[49]), "+f"(d[50]), "+f"(d[51]), "+f"(d[52]), "+f"(d[53]), "+f"(d[54]), "+f"(d[55]), "+f"(d[56]), "+f"(d[57]), "+f"(d[58]), "+f"(d[59]), "+f"(d[60]), "+f"(d[61]), "+f"(d[62]), "+f"(d[63]), "+f"(d[64]), "+f"(d[65]), "+f"(d[66]), "+f"(d[67]), "+f"(d[68]), "+f"(d[69]), "+f"(d[70]), "+f"(d[71]), "+f"(d[72]), "+f"(d[73]), "+f"(d[74]), "+f"(d[75]), "+f"(d[76]), "+f"(d[77]), "+f"(d[78]), "+f"(d[79]), "+f"(d[80]), "+f"(d[81]), "+f"(d[82]), "+f"(d[83]), "+f"(d[84]), "+f"(d[85]), "+f"(d[86]), "+f"(d[87]), "+f"(d[88]), "+f"(d[89]), "+f"(d[90]), "+f"(d[91]), "+f"(d[92]), "+f"(d[93]), "+f"(d[94]), "+f"(d[95]), "+f"(d[96]), "+f"(d[97]), "+f"(d[98]), "+f"(d[99]), "+f"(d[100]), "+f"(d[101]), "+f"(d[102]), "+f"(d[103]), "+f"(d[104]), "+f"(d[105]), "+f"(d[106]), "+f"(d[107]), "+f"(d[108]), "+f"(d[109]), "+f"(d[110]), "+f"(d[111]), "+f"(d[112]), "+f"(d[113]), "+f"(d[114]), "+f"(d[115]), "+f"(d[116]), "+f"(d[117]), "+f"(d[118]), "+f"(d[119]), "+f"(d[120]), "+f"(d[121]), "+f"(d[122]), "+f"(d[123]), "+f"(d[124]), "+f"(d[125]), "+f"(d[126]), "+f"(d[127])
    : "r"(a[0]), "r"(a[1]), "r"(a[2]), "r"(a[3]), "l"(db), "r"(scale_d));
}
__device__ __forceinline__ void wgmma_n256_rs0(float (&d)[192], const uint32_t (&a)[4], uint64_t db) {
  asm volatile("{\n.reg .pred p;\nsetp.ne.b32 p, 0, 0;\n"
    "wgmma.mma_async.sync.aligned.m64n256k16.f32.bf16.bf16 {%0, %1, %2, %3, %4, %5, %6, %7, %8, %9, %10, %11, %12, %13, %14, %15, %16, %17, %18, %19, %20, %21, %22, %23, %24, %25, %26, %27, %28, %29, %30, %31, %32, %33, %34, %35, %36, %37, %38, %39, %40, %41, %42, %43, %44, %45, %46, %47, %48, %49, %50, %51, %52, %53, %54, %55, %56, %57, %58, %59, %60, %61, %62, %63, %64, %65, %66, %67, %68, %69, %70, %71, %72, %73, %74, %75, %76, %77, %78, %79, %80, %81, %82, %83, %84, %85, %86, %87, %88, %89, %90, %91, %92, %93, %94, %95, %96, %97, %98, %99, %100, %101, %102, %103, %104, %105, %106, %107, %108, %109, %110, %111, %112, %113, %114, %115, %116, %117, %118, %119, %120, %121, %122, %123, %124, %125, %126, %127}, {%128, %129, %130, %131}, %132, p, 1, 1, 1;\n}\n"
    : "=f"(d[0]), "=f"(d[1]), "=f"(d[2]), "=f"(d[3]), "=f"(d[4]), "=f"(d[5]), "=f"(d[6]), "=f"(d[7]), "=f"(d[8]), "=f"(d[9]), "=f"(d[10]), "=f"(d[11]), "=f"(d[12]), "=f"(d[13]), "=f"(d[14]), "=f"(d[15]), "=f"(d[16]), "=f"(d[17]), "=f"(d[18]), "=f"(d[19]), "=f"(d[20]), "=f"(d[21]), "=f"(d[22]), "=f"(d[23]), "=f"(d[24]), "=f"(d[25]), "=f"(d[26]), "=f"(d[27]), "=f"(d[28]), "=f"(d[29]), "=f"(d[30]), "=f"(d[31]), "=f"(d[32]), "=f"(d[33]), "=f"(d[34]), "=f"(d[35]), "=f"(d[36]), "=f"(d[37]), "=f"(d[38]), "=f"(d[39]), "=f"(d[40]), "=f"(d[41]), "=f"(d[42]), "=f"(d[43]), "=f"(d[44]), "=f"(d[45]), "=f"(d[46]), "=f"(d[47]), "=f"(d[48]), "=f"(d[49]), "=f"(d[50]), "=f"(d[51]), "=f"(d[52]), "=f"(d[53]), "=f"(d[54]), "=f"(d[55]), "=f"(d[56]), "=f"(d[57]), "=f"(d[58]), "=f"(d[59]), "=f"(d[60]), "=f"(d[61]), "=f"(d[62]), "=f"(d[63]), "=f"(d[64]), "=f"(d[65]), "=f"(d[66]), "=f"(d[67]), "=f"(d[68]), "=f"(d[69]), "=f"(d[70]), "=f"(d[71]), "=f"(d[72]), "=f"(d[73]), "=f"(d[74]), "=f"(d[75]), "=f"(d[76]), "=f"(d[77]), "=f"(d[78]), "=f"(d[79]), "=f"(d[80]), "=f"(d[81]), "=f"(d[82]), "=f"(d[83]), "=f"(d[84]), "=f"(d[85]), "=f"(d[86]), "=f"(d[87]), "=f"(d[88]), "=f"(d[89]), "=f"(d[90]), "=f"(d[91]), "=f"(d[92]), "=f"(d[93]), "=f"(d[94]), "=f"(d[95]), "=f"(d[96]), "=f"(d[97]), "=f"(d[98]), "=f"(d[99]), "=f"(d[100]), "=f"(d[101]), "=f"(d[102]), "=f"(d[103]), "=f"(d[104]), "=f"(d[105]), "=f"(d[106]), "=f"(d[107]), "=f"(d[108]), "=f"(d[109]), "=f"(d[110]), "=f"(d[111]), "=f"(d[112]), "=f"(d[113]), "=f"(d[114]), "=f"(d[115]), "=f"(d[116]), "=f"(d[117]), "=f"(d[118]), "=f"(d[119]), "=f"(d[120]), "=f"(d[121]), "=f"(d[122]), "=f"(d[123]), "=f"(d[124]), "=f"(d[125]), "=f"(d[126]), "=f"(d[127])
    : "r"(a[0]), "r"(a[1]), "r"(a[2]), "r"(a[3]), "l"(db));
}

constexpr int SLOT = 16384;
constexpr int VB = 4 * SLOT, PH = 0, XS = 6;
constexpr int SM_SD = 13 * SLOT;
constexpr int SM_BAR = SM_SD + 8192;
constexpr int SM_RS = SM_BAR + 1024;
constexpr int SM_AP = SM_RS + 640;
constexpr int SM_BP = SM_AP + 2048;
constexpr int SM_EPOCH = SM_BP + 6144;
constexpr int SM_TOTAL = SM_EPOCH + 16;
constexpr int FM = 0, FT = 16, FW = 30, CM = 46, CT = 62, CW = 76, B_EF = 92, B_STAT = 93, B_KVF = 94, B_HALO = 95,
              B_KVDONE = 96, B_OH0 = 97, B_OH1 = 98, B_XH0 = 99, B_XDONE = 100, B_WFD = 101, B_XT = 102, B_OF0 = 103, B_KVF1 = 104, B_KVS = 105, B_RAW = 106  , B_X0 = 108, B_KVS0 = 109;
constexpr uint64_t BAR_LG = 0x00043333330004ull;
#define BA(i) (bar + (i) * 8)
#define REL2(i) release2c(SB0 + SM_BAR + (i) * 8)
constexpr int NF = 3, ND = 13, NR = 0, NWOP = 48, NAOP = 38;
constexpr bool EF_USED = false;
constexpr uint64_t TL_A = 0x6278627862786ull, TL_B = 0xa9c3ba9c3ba9cull, WO_A = 0x76b24038b51403ffull, WO_B = 0x8c5a197c6a297c8bull;
__constant__ uint32_t c_wop[NWOP + 1] = {0xeb0009, 0x186b8000, 0x6c0112, 0x1aec011a, 0x6c8224, 0x22ec822b, 0x18170330, 0x18178442, 0x18180554, 0x18188660, 0x18190772, 0x18198884, 0x181a0990, 0x181a8aa2, 0x181b0bb4, 0x181b8cc0, 0xaed10fc, 0xa9711e9, 0x181c0dd2, 0xa9792da, 0x129813cb, 0x181c8ee4, 0x181d0ff0, 0x109d94b3, 0x109f15ac, 0x109f9699, 0x10a0178a, 0x10a0987b, 0x10a11963, 0x10a19a5c, 0x10a21b49, 0x10a29c3a, 0x9231e0b, 0x9239f18, 0x1124202c, 0x13242137, 0x1124a249, 0x1324a352, 0x1125246a, 0x13252576, 0x1127268c, 0x1127a797, 0x112828a9, 0x1128a9b1, 0x11292aca, 0x13292bd5, 0x112a2cec, 0x132a2df8, 0};
__constant__ uint32_t c_aop[NAOP + 1] = {0x6d8228, 0x170336, 0x178447, 0x180558, 0x188666, 0x190777, 0x198888, 0x1a0996, 0x1a8aa7, 0x1b0bb8, 0x1b8cc6, 0x1c0dd7, 0x1c8ee8, 0x1d0ff6, 0x1d93c2, 0x1f14b6, 0x1f95a8, 0x201697, 0x209782, 0x211876, 0x219968, 0x221a57, 0x229b42, 0x231c36, 0xa3a023, 0xb12130, 0x2b12244, 0x2b12351, 0x2b12465, 0xa6257b, 0xa6a688, 0xa72793, 0xa7a8a0, 0xa829b4, 0xa8aac2, 0xa9abdb, 0x2a9ace6, 0xaaadf7, 0};
__constant__ uint32_t c_map[64] = {4, 5, 6, 7, 0, 16, 32, 48, 64, 80, 96, 112, 1, 17, 33, 49, 65, 81, 97, 113, 2, 18, 34, 50, 66, 82, 98, 114, 3, 19, 35, 51, 67, 83, 99, 115, 20, 36, 52, 68, 84, 100, 116, 21, 37, 53, 69, 85, 101, 117, 22, 38, 54, 70, 86, 102, 118, 23, 39, 55, 71, 87, 103, 119};
enum { MAP_WF = 0, MAP_WA = 2, MAP_WB = 4, MAP_WOA = 6, MAP_WOB = 8, MAP_X0 = 10, MAP_X = 11, MAP_O = 12, MAP_PHI = 13, NMAP = 14 };
struct Maps { CUtensorMap m[NMAP]; };

#define PL 2
#define PROFL(a, b)
#define SUBS 8
#define CHW 1
#define SUBS1 12
#define XRAT 10
#define XRN 4
#define BT1 1
#define ST1 8
#define X0AT 1
#define W1DL 400
#define SKA 0
#define SKB 0
#define BPRE 0
#define XST 3
#define WH 4
#define PFM 3
#define PFS 2
#define NLAYERS 4
constexpr float L2E = 1.4426950408889634f;

#define D128(lo) desc64(lo, 0x40000040u)
struct Ctx { uint32_t zero, boff; const bf16* x0; bf16* out; };
#define BLK_CTX() \
  uint32_t bid_; asm volatile("mov.u32 %0, %%ctaid.x;" : "=r"(bid_)); \
  bid_ -= c.boff; \
  const uint32_t gr_ = c_map[bid_ >> 1]; \
  const int cr = bid_ & 1, g = gr_ & 7, rb = (gr_ >> 3) + cr, m0 = rb * 128; \
  const uint32_t sb = SB0 + (cr << 24); \
  const uint32_t bar = sb + SM_BAR; \
  (void)cr; (void)g; (void)rb; (void)m0; (void)bar;
extern __shared__ uint8_t smem_raw[];
constexpr uint32_t SB0 = 1024;

#define PHASE_CTX() \
  BLK_CTX(); \
  int tid_ = threadIdx.x; asm volatile("" : "+r"(tid_)); \
  const int lane = tid_ & 31, cw = (tid_ >> 5) - 4, wg = cw >> 2, wq = cw & 3, gq = lane >> 2, t = lane & 3, wrow0 = cw * 16; \
  const int lrow = (lane & 7) + ((lane >> 3) & 1) * 8, lchk = lane >> 4; \
  const bool elected = (tid_ & 127) == 0; \
  const uint32_t rowo = (wrow0 + lrow) * 128, X = (lchk ^ (lane & 7)) << 4; \
  const uint32_t Y = (wrow0 + (lane & 7)) * 128 + (((lane >> 3) ^ (lane & 7)) << 4); \
  const size_t gfr = (size_t)(m0 + wrow0 + gq) * D_ + g * 128 + 8 * t; \
  (void)bar; (void)wq; (void)gq; (void)lrow; (void)lchk; (void)elected; (void)wrow0; (void)wg; (void)rowo; (void)X; (void)t; (void)Y; (void)gfr;
#define MMA_CTX() \
  const uint32_t wu = __shfl_sync(0xffffffffu, wg, 0); \
  const uint32_t dA0 = ((SB0 >> 4) | (1u << 16)) + wu * 512, dB0 = (SB0 >> 4) | (512u << 16); \
  const uint32_t par = layer & 1;

__device__ __forceinline__ void slab_out_half(uint32_t slot, bf16* dst, int wrow0, int lane) {
  const int r0 = lane >> 3, ch = lane & 7;
  const uint32_t src = slot + (wrow0 + r0) * 128;
  uint4 v[4];
#pragma unroll
  for (int i = 0; i < 4; ++i) v[i] = lds128(src + i * 512 + (((ch ^ (4 * i + r0)) & 7) << 4));
  dst += (size_t)(wrow0 + r0) * D_ + ch * 8;
#pragma unroll
  for (int i = 0; i < 4; ++i) *reinterpret_cast<uint4*>(dst + (size_t)i * 4 * D_) = v[i];
}

__device__ __forceinline__ void consumer(const Ctx& c) {
  float acc[192];
  uint32_t xf[4][4];
  uint32_t xp[8][4];
  {
    PHASE_CTX();
    const unsigned int epoch = ld_relaxed(&g_epoch);
    PROFT(tid_ == 128, 0);
    const uint32_t wu = __shfl_sync(0xffffffffu, wg, 0);
    if (tid_ < 128 + 8) sts128(sb + SM_AP + lane * 16, make_uint4(0x3F803F80u, 0x3F803F80u, 0x3F803F80u, 0x3F803F80u));
#pragma unroll 1
    for (int it = 0; it < 2; ++it) {
      float p[4][16];
      mbar_wait(BA(B_RAW + it), 0);
      PROFT(tid_ == 128, it ? 15 : 2);
      const uint32_t da = ((SB0 >> 4) | (1u << 16)) + (wu ? 9 + it : 2 * it) * 1024, db = (SB0 + SM_SD) >> 4;
      wgmma_fence();
#pragma unroll
      for (int h = 0; h < 4; ++h) wgmma_n32_0(p[h], D128(da + (h >> 1) * 512 + (h & 1) * 4), desc64(db + h * 128, 0x80000020u));
#pragma unroll
      for (int h = 0; h < 4; ++h) wgmma_n32(p[h], D128(da + (h >> 1) * 512 + (h & 1) * 4 + 2), desc64(db + h * 128 + 64, 0x80000020u), 1);
      wgmma_commit();
      wgmma_wait<0>();
#pragma unroll
      for (int i = 0; i < 64; ++i) asm volatile("" : "+f"(p[i >> 4][i & 15]) :: "memory");
      const uint32_t base = sb + (wg ? 9 + it : 2 * it) * SLOT + (wq * 16 + gq) * 128;
      uint32_t w[4][4][2];
#pragma unroll
      for (int i = 0; i < 32; ++i) w[i >> 3][(i >> 1) & 3][i & 1] = pack_bf16(p[i >> 3][2 * (i & 7)], p[i >> 3][2 * (i & 7) + 1]);
      if (wu) {
#pragma unroll
        for (int i = 0; i < 8; ++i)
          sts128(base + (i >> 2) * 8192 + (i & 1) * 1024 + (((((i >> 1) & 1) * 4 + t) ^ gq) << 4), make_uint4(w[i >> 1][0][i & 1], w[i >> 1][1][i & 1], w[i >> 1][2][i & 1], w[i >> 1][3][i & 1]));
      } else {
#pragma unroll
        for (int i = 0; i < 16; ++i)
          sts64(base + (i >> 3) * 8192 + (i & 1) * 1024 + ((((t & 1) * 4 + ((i >> 1) & 3)) ^ gq) << 4) + (t >> 1) * 8, w[(i >> 3) * 2][(i >> 1) & 3][i & 1], w[(i >> 3) * 2 + 1][(i >> 1) & 3][i & 1]);
      }
      fence_async_smem();
      __syncwarp();
      if (it == cr && lane == 0) mbar_arrive(BA(B_WFD));
    }
    if (tid_ == 128) sts_f(sb + SM_EPOCH, __uint_as_float(epoch & 1));
#pragma unroll
    for (int i = 0; i < 32; ++i) xp[i >> 2][i & 3] = 0u;
    nbar<1, 256>();
    PROFT(tid_ == 128, 13);
    mbar_wait(BA(FM + cr), 0);
    float cs[3][4];
    wgmma_fence();
#pragma unroll
    for (int ks = 0; ks < 4; ++ks)
#pragma unroll
      for (int i = 0; i < 3; ++i) {
        const uint32_t bx = (i == 0 ? 2 * cr * 1024 : i == 1 ? (2 * cr + 1) * 1024 : (9 + cr) * 1024) + wu * 512;
        wgmma_n8_t(cs[i], D128(((SB0 >> 4) | (512u << 16)) + bx + ks * 128), desc64((SB0 + SM_AP) >> 4, 0), ks != 0);
      }
    wgmma_commit();
    mbar_wait(BA(FM), 0);
#pragma unroll
    for (int k = 0; k < 4; ++k) ldsm_x4(xf[k][0], xf[k][1], xf[k][2], xf[k][3], sb + XS * SLOT + rowo + (X ^ (k << 5)));
    wgmma_wait<0>();
#pragma unroll
    for (int i = 0; i < 12; ++i) asm volatile("" : "+f"(cs[i >> 2][i & 3]) :: "memory");
    if (t < 2) {
#pragma unroll
      for (int i = 0; i < 3; ++i) red_add1(g_cs + (epoch & 1) * 6144 + g * 384 + i * 128 + wg * 64 + wq * 16 + gq + t * 8, t ? cs[i][2] : cs[i][0]);
    }
    PROFT(tid_ == 128, 14);
  }
#pragma unroll 1
  for (int layer = 0;; ++layer) {
    {
      wgmma_fence();
      wgmma_n256_rs0(acc, xf[0], D128((SB0 >> 4) | (512u << 16)));
#pragma unroll
      for (int k = 1; k < 4; ++k) wgmma_n256_rs(acc, xf[k], D128(((SB0 >> 4) | (512u << 16)) + k * 128), 1);
      wgmma_commit();
      PHASE_CTX();
      MMA_CTX();
      {
        const uint32_t ep = __float_as_uint(lds_f(sb + SM_EPOCH));
        if (layer == 0) {
          mbar_wait(BA(B_X0), 0);
#pragma unroll
          for (int i = 0; i < 8; ++i) ldsm_x4(xp[i][0], xp[i][1], xp[i][2], xp[i][3], sb + (11 + (i >> 2)) * SLOT + (Y ^ ((i & 2) << 5)) + (i & 1) * 1024);
          if (lane == ((xp[0][0] ^ xp[1][0] ^ xp[2][0] ^ xp[3][0] ^ xp[7][0]) & c.zero)) REL2(B_XT);
        } else {
#pragma unroll
          for (int i = 0; i < 8; ++i) stsm_x4(sb + (XS + (i >> 2)) * SLOT + (Y ^ ((i & 2) << 5)) + (i & 1) * 1024, xp[i][0], xp[i][1], xp[i][2], xp[i][3]);
        }
        float s0 = 0.f, s1 = 0.f, q0 = 0.f, q1 = 0.f;
        auto stats = [&](int j0, int j1) {
#pragma unroll
          for (int j = j0; j < j1; ++j) {
            const uint32_t u0 = xp[(j >> 2) * 2][j & 3], u1 = xp[(j >> 2) * 2 + 1][j & 3];
            s0 += bf_lo(u0) + bf_hi(u0); s1 += bf_lo(u1) + bf_hi(u1);
            q0 = fmaf(bf_lo(u0), bf_lo(u0), fmaf(bf_hi(u0), bf_hi(u0), q0)); q1 = fmaf(bf_lo(u1), bf_lo(u1), fmaf(bf_hi(u1), bf_hi(u1), q1));
          }
        };
        stats(0, ST1);
        fence_async_smem();
        nbar_dyn(3 + wu + (__float_as_uint(s0 + s1 + q0 + q1) & c.zero), 128);
        mbar_wait(BA(FM + 1), par);
        wgmma_fence();
#pragma unroll
        for (int k = 0; k < 4; ++k) wgmma_n256(acc, D128(dA0 + (XS + 1) * 1024 + k * 2), D128(dB0 + 2048 + k * 128), 1);
        wgmma_commit();
        wgmma_wait<1>();
#pragma unroll
        for (int i = 4; i < 8; ++i) stg128_p(layer, g_x + gfr + (i & 1) * 8 * D_ + (i >> 1) * 32, xp[i][0], xp[i][1], xp[i][2], xp[i][3]);
        {
          uint32_t zc; asm volatile("mov.u32 %0, %%clock;" : "=r"(zc) :: "memory");
          q0 += __uint_as_float(zc & c.zero); q1 += __uint_as_float(zc & c.zero); s0 += __uint_as_float(zc & c.zero); s1 += __uint_as_float(zc & c.zero);
        }
        stats(ST1, 16);
        wgmma_fence();
        wgmma_n128_0(acc, D128(dA0 + XS * 1024), D128(dB0 + 9 * 1024));
#pragma unroll
        for (int k = 1; k < 4; ++k) wgmma_n128(acc, D128(dA0 + XS * 1024 + k * 2), D128(dB0 + 9 * 1024 + k * 128), 1);
        wgmma_commit();
        const bool od = t & 1;
        float sa = od ? s1 : s0, qa = od ? q1 : q0;
        sa += __shfl_xor_sync(0xffffffffu, od ? s0 : s1, 1);
        qa += __shfl_xor_sync(0xffffffffu, od ? q0 : q1, 1);
        wgmma_fence();
#pragma unroll
        for (int k = 0; k < 4; ++k) wgmma_n128(acc, D128(dA0 + (XS + 1) * 1024 + k * 2), D128(dB0 + 10 * 1024 + k * 128), 1);
        wgmma_commit();
        sa += __shfl_xor_sync(0xffffffffu, sa, 2);
        qa += __shfl_xor_sync(0xffffffffu, qa, 2);
        red_add2_p(t < 2, reinterpret_cast<float*>(g_stats + (ep * 4 + layer) * S_ + m0 + wrow0 + gq + t * 8), sa, qa);
        __syncwarp();
        if (lane == 0) mbar_arrive(BA(B_XDONE));
        wgmma_wait<1>();
        if (elected) REL2(CM);
      }
      uint32_t s = 2;
#pragma unroll 1
      for (int i = 2; i < NF; ++i) {
        PROFL(tid_ == 128 && layer == PL + 1, 244 + 2 * i);
        mbar_wait(BA(FM + i), par);
        PROFL(tid_ == 128 && layer == PL + 1, 245 + 2 * i);
        const uint32_t da = dA0 + (XS + s) * 1024, dk = dB0 + s * 2048, dq = dB0 + (9 + s) * 1024;
        wgmma_fence();
#pragma unroll
        for (int k = 0; k < 4; ++k) wgmma_n128(acc, D128(da + k * 2), D128(dq + k * 128), 1);
        wgmma_commit();
        wgmma_wait<1>();
        if (elected) REL2(CM + i - 1);
        wgmma_fence();
#pragma unroll
        for (int k = 0; k < 4; ++k) wgmma_n256(acc, D128(da + k * 2), D128(dk + k * 128), 1);
        wgmma_commit();
        if (++s == 3) s = 0;
      }
#pragma unroll 1
      for (int i = NF; i < 15; ++i) {
        mbar_wait(BA(FM + i), par);
        const uint32_t da = dA0 + (XS + s) * 1024, dk = dB0 + s * 2048;
        wgmma_fence();
#pragma unroll
        for (int k = 0; k < 4; ++k) wgmma_n256(acc, D128(da + k * 2), D128(dk + k * 128), 1);
        wgmma_commit();
        wgmma_wait<1>();
        if (elected) REL2(CM + i - 1);
        if (++s == 3) s = 0;
      }
      {
        const uint64_t dap = desc64(((SB0 + SM_AP) >> 4) + wu * 64, 8), dbp = make_desc_ns(SB0 + SM_BP, 0, 128);
        mbar_wait(BA(B_STAT), par);
        mbar_wait(BA(FM + 15), par);
        PROFT(tid_ == 128, layer * 16 + 9);
        wgmma_fence();
        wgmma_n256_k(acc, dap, dbp, 1);
#pragma unroll
        for (int k = 0; k < 4; ++k) wgmma_n256(acc, D128(dA0 + XS * 1024 + k * 2), D128(dB0 + k * 128), 1);
        wgmma_commit();
        wgmma_wait<1>();
        if (elected) REL2(CM + 14);
        mbar_wait(BA(FT), par);
        wgmma_fence();
        wgmma_n128_k(acc, dap, dbp + 256, 1);
#pragma unroll
        for (int k = 0; k < 4; ++k) wgmma_n128(acc, D128(dA0 + (uint32_t)(TL_A & 15) * 1024 + k * 2), D128(dB0 + (uint32_t)(TL_B & 15) * 1024 + k * 128), 1);
        wgmma_commit();
        wgmma_wait<1>();
        if (elected) REL2(CM + 15);
#pragma unroll
        for (int i = 0; i < 128; ++i) asm volatile("" : "+f"(acc[i]) :: "memory");
      }
    }
    uint32_t of[8][4], o1[4][4];
    {
      PHASE_CTX();
      MMA_CTX();
      PROFT(tid_ == 128, layer * 16 + 1);
      PROFT(lane == 0 && layer == PL, 192 + cw);
      PROFT(tid_ == 128 && layer == PL, 160);
      uint64_t ta = (TL_A >> 4), tw = TL_B >> 4;
      uint32_t da, db, dz = dA0;
      auto sub = [&](int n) {
        const int j = n >> 2, k = n & 3;
        if (k == 0) {
          dz += c.zero;
          da = dz + ((uint32_t)ta & 15) * 1024; db = dB0 + ((uint32_t)tw & 15) * 1024;
          ta >>= 4; tw >>= 4;
          mbar_wait(BA(FT + j), par);
          wgmma_fence();
        }
        wgmma_n128(acc, D128(da + k * 2), D128(db + k * 128), 1);
        if (k == 3) {
          wgmma_commit();
          wgmma_wait<1>();
          if (elected) REL2(CT + j - 1);
        }
      };
      auto run = [&](int j0, int j1) {
#pragma unroll 1
        for (int j = j0; j < j1; ++j) {
          mbar_wait(BA(FT + j), par);
          da = dA0 + ((uint32_t)ta & 15) * 1024; db = dB0 + ((uint32_t)tw & 15) * 1024;
          ta >>= 4; tw >>= 4;
          wgmma_fence();
#pragma unroll
          for (int k = 0; k < 4; ++k) wgmma_n128(acc, D128(da + k * 2), D128(db + k * 128), 1);
          wgmma_commit();
          wgmma_wait<1>();
          if (elected) REL2(CT + j - 1);
        }
        ta = TL_A >> (4 * j1); tw = TL_B >> (4 * j1);
      };
      auto rest = [&](int j0, int sk) {
        if (sk) {
          run(j0, ND - sk);
          if (wu == 0) nbar<6, 256>();
          j0 = ND - sk;
        }
        run(j0, ND);
        if (sk && wu) asm volatile("bar.arrive 6, 256;" ::: "memory");
      };
      auto rest_end = [&]() {
        wgmma_wait<0>();
        if (elected) REL2(CT + ND - 1);
#pragma unroll
        for (int i = 128; i < 192; ++i) asm volatile("" : "+f"(acc[i]) :: "memory");
      };
      auto wo0 = [&]() {
        wgmma_fence();
        wgmma_n128_rs0(acc, of[0], D128(dB0 + (uint32_t)(WO_B & 15) * 1024));
#pragma unroll
        for (int k = 1; k < 4; ++k) wgmma_n128_rs(acc, of[k], D128(dB0 + (uint32_t)(WO_B & 15) * 1024 + k * 128), 1);
        wgmma_commit();
      };
      const float rs0 = lds_f(sb + SM_RS + (16 + wrow0 + gq) * 4), rs1 = lds_f(sb + SM_RS + (24 + wrow0 + gq) * 4);
#define EPOCH() __float_as_uint(lds_f(sb + SM_EPOCH))
      mbar_wait(BA(CM + 14), par);
      if (par) {
        uint32_t kk[8][4], kp[8][4], vf[2][2][4][4];
        int sn = 4;
#pragma unroll
        for (int i = 0; i < 4 * BT1; ++i) sub(sn++);
        {
          uint32_t vv[8][4];
#pragma unroll
          for (int jp = 0; jp < 8; ++jp) {
            kk[jp][0] = pack_bf16(acc[8 * jp], acc[8 * jp + 1]); kk[jp][1] = pack_bf16(acc[8 * jp + 4], acc[8 * jp + 5]);
            kk[jp][2] = pack_bf16(acc[8 * jp + 2], acc[8 * jp + 3]); kk[jp][3] = pack_bf16(acc[8 * jp + 6], acc[8 * jp + 7]);
#pragma unroll
            for (int i = 0; i < 4; ++i) vv[jp][i] = pack_bf16(acc[64 + 8 * jp + 2 * i], acc[65 + 8 * jp + 2 * i]);
          }
          if (cw == 7) {
            uint32_t* const hbuf = g_halo + (size_t)(((layer >> 1) * 17 + rb + 1) * 8 + g) * 2048;
#pragma unroll
            for (int jp = 0; jp < 8; ++jp) stg128(hbuf + jp * 128 + lane * 4, kk[jp][0], kk[jp][1], kk[jp][2], kk[jp][3]);
#pragma unroll
            for (int i = 0; i < 32; ++i) hbuf[1024 + (i >> 4) * 512 + (gq + (i & 1) * 8) * 32 + ((((i >> 1) & 7) ^ gq) << 2) + t] = vv[i >> 2][i & 3];
            __syncwarp();
            if (lane == 0) mbar_arrive(BA(B_OF0));
          }
#pragma unroll
          for (int jp = 0; jp < 8; ++jp) {
            sub(sn++);
            stsm_x4(sb + VB + (jp >> 2) * SLOT + rowo + (X ^ ((jp & 3) << 5)), vv[jp][0], vv[jp][1], vv[jp][2], vv[jp][3]);
          }
        }
        PROFT(tid_ == 128, layer * 16 + 2);
        const int e = gq & 1;
        float f0[4], f1[4], b0[4], b1[4], rj[4];
#pragma unroll
        for (int nt = 0; nt < 4; ++nt) {
          const int kx = nt * 8 + 2 * t + e;
          const bool okk = (m0 + wrow0 + kx) >= 16;
          const int d0 = kx - gq, d1 = d0 - 8;
          rj[nt] = lds_f(sb + SM_RS + (wrow0 + kx) * 4);
          const bool m0_ = okk && d0 >= 2 && d0 <= 16, m1_ = okk && d1 >= 2 && d1 <= 16;
          f0[nt] = m0_ ? rj[nt] * rs0 * (0.17677669529663687f * L2E) : 0.f;
          f1[nt] = m1_ ? rj[nt] * rs1 * (0.17677669529663687f * L2E) : 0.f;
          b0[nt] = m0_ ? 0.f : -1e30f; b1[nt] = m1_ ? 0.f : -1e30f;
        }
        mbar_wait(BA(CM + 15), par);
#pragma unroll
        for (int jp = 0; jp < 8; ++jp) {
          sub(sn++);
          sts128(sb + PH + cw * 4096 + jp * 512 + lane * 16, make_uint4(kk[jp][0], kk[jp][1], kk[jp][2], kk[jp][3]));
        }
#pragma unroll
        for (int i = 0; i < 4; ++i) sub(sn++);
        nbar<1, 256>();
        PROFT(tid_ == 128, layer * 16 + 3);
        rest(sn >> 2, SKB);
        if (!BPRE) rest_end();
        PROFT(lane == 0 && layer == PL, 200 + cw);
        PROFT(tid_ == 128, layer * 16 + 10);
        if (cw == 0) mbar_wait(BA(B_HALO), (layer >> 1) & 1);
        PROFT(tid_ == 128, layer * 16 + 5);
        const uint32_t vs = sb + (cw ? VB + rowo - 2048 : SM_SD + 4096 + rowo), vst = cw ? SLOT : 2048;
        const uint32_t psel = e ? 0x1054u : 0x5410u;
#pragma unroll
        for (int hp = 0; hp < 2; ++hp) {
#pragma unroll
          for (int i = 4 * hp; i < 4 * hp + 4; ++i) {
            const uint4 u = lds128(sb + (cw ? PH + (cw - 1) * 4096 : SM_SD) + lane * 16 + i * 512);
            kp[i][0] = u.x; kp[i][1] = u.y; kp[i][2] = u.z; kp[i][3] = u.w;
          }
#pragma unroll
          for (int i = 4 * hp; i < 4 * hp + 4; ++i) {
            ldsm_x4_t(vf[0][i & 1][i >> 1][0], vf[0][i & 1][i >> 1][1], vf[0][i & 1][i >> 1][2], vf[0][i & 1][i >> 1][3], vs + (i >> 2) * vst + (X ^ ((i & 3) << 5)));
            ldsm_x4_t(vf[1][i & 1][i >> 1][0], vf[1][i & 1][i >> 1][1], vf[1][i & 1][i >> 1][2], vf[1][i & 1][i >> 1][3], sb + VB + (i >> 2) * SLOT + rowo + (X ^ ((i & 3) << 5)));
          }
          if (BPRE && !hp) rest_end();
          float l0[2][4], l1[2][4];
#pragma unroll
          for (int h = 0; h < 2; ++h) {
            const int H = 2 * hp + h;
            uint32_t qa[8];
#pragma unroll
            for (int i = 0; i < 8; ++i) qa[i] = pack_bf16(acc[128 + 16 * H + 2 * i], acc[129 + 16 * H + 2 * i]);
#pragma unroll
            for (int nt = 3; nt >= 0; --nt) {
              float sc[4] = {0.f, 0.f, 0.f, 0.f};
#pragma unroll
              for (int ks = 0; ks < 2; ++ks) {
                const uint32_t (&kf)[4] = nt < 2 ? kp[2 * H + ks] : kk[2 * H + ks];
                mma_bf16(sc, qa[4 * ks], qa[4 * ks + 1], qa[4 * ks + 2], qa[4 * ks + 3], kf[2 * (nt & 1)], kf[2 * (nt & 1) + 1]);
              }
              l0[h][nt] = fmaf(e ? sc[1] : sc[0], f0[nt], b0[nt]);
              l1[h][nt] = fmaf(e ? sc[3] : sc[2], f1[nt], b1[nt]);
            }
          }
          float mx0[2], mx1[2], s0[2], s1[2];
#pragma unroll
          for (int h = 0; h < 2; ++h) {
            mx0[h] = fmaxf(fmaxf(l0[h][0], l0[h][1]), l0[h][2]);
            mx1[h] = fmaxf(fmaxf(l1[h][1], l1[h][2]), l1[h][3]);
          }
#pragma unroll
          for (int o = 1; o <= 2; o <<= 1)
#pragma unroll
            for (int h = 0; h < 2; ++h) {
              mx0[h] = fmaxf(mx0[h], __shfl_xor_sync(0xffffffffu, mx0[h], o));
              mx1[h] = fmaxf(mx1[h], __shfl_xor_sync(0xffffffffu, mx1[h], o));
            }
#pragma unroll
          for (int h = 0; h < 2; ++h) {
#pragma unroll
            for (int nt = 0; nt < 3; ++nt) { l0[h][nt] = ex2(l0[h][nt] - mx0[h]); l1[h][nt + 1] = ex2(l1[h][nt + 1] - mx1[h]); }
            s0[h] = (l0[h][0] + l0[h][1]) + l0[h][2];
            s1[h] = (l1[h][1] + l1[h][2]) + l1[h][3];
          }
#pragma unroll
          for (int o = 1; o <= 2; o <<= 1)
#pragma unroll
            for (int h = 0; h < 2; ++h) {
              s0[h] += __shfl_xor_sync(0xffffffffu, s0[h], o);
              s1[h] += __shfl_xor_sync(0xffffffffu, s1[h], o);
            }
          uint32_t ow[2][2][4];
#pragma unroll
          for (int h = 0; h < 2; ++h) {
            const int H = 2 * hp + h;
            uint32_t pl[4], ph[4];
            const float i0 = rcp(s0[h]), i1 = rcp(s1[h]);
#pragma unroll
            for (int nt = 0; nt < 4; ++nt) {
              const uint32_t pk = pack_bf16(nt < 3 ? l0[h][nt] * i0 * rj[nt] : 0.f, nt > 0 ? l1[h][nt] * i1 * rj[nt] : 0.f);
              pl[nt] = nt < 3 ? __byte_perm(pk, 0u, psel) : 0u;
              ph[nt] = nt > 0 ? __byte_perm(pk, 0u, psel + 0x2222u) : 0u;
            }
#pragma unroll
            for (int nj = 0; nj < 4; ++nj) {
              float oa[4] = {0.f, 0.f, 0.f, 0.f};
#pragma unroll
              for (int ks = 0; ks < 2; ++ks)
                mma_bf16(oa, pl[2 * ks], ph[2 * ks], pl[2 * ks + 1], ph[2 * ks + 1], vf[ks][nj >> 1][H][2 * (nj & 1)], vf[ks][nj >> 1][H][2 * (nj & 1) + 1]);
              ow[h][0][nj] = pack_bf16(oa[0], oa[1]); ow[h][1][nj] = pack_bf16(oa[2], oa[3]);
            }
          }
          if (hp == 0) {
#pragma unroll
            for (int i = 0; i < 4; ++i) stg128(g_o + gfr + (i & 1) * 8 * D_ + (i >> 1) * 32, ow[i >> 1][i & 1][0], ow[i >> 1][i & 1][1], ow[i >> 1][i & 1][2], ow[i >> 1][i & 1][3]);
            __syncwarp();
            if (lane == 0) mbar_arrive(BA(B_OH0));
          } else {
#pragma unroll
            for (int i = 0; i < 16; ++i) o1[i >> 2][i & 3] = ow[i >> 3][(i >> 2) & 1][i & 3];
          }
#pragma unroll
          for (int i = 0; i < 16; ++i) of[4 * hp + (i >> 2)][i & 3] = ow[i >> 3][i & 1][(i >> 1) & 3];
          if (!hp) { PROFT(tid_ == 128, layer * 16 + 15); mbar_wait(BA(FW), par); }
        }
      } else {
        float sc[2] = {rs0 * L2E, rs1 * L2E};
        {
          const uint32_t vb = sb + VB + (rowo >> 1), X0 = (lchk ^ ((lane & 7) >> 1)) << 4;
          const uint32_t pb = sb + PH + (t & 1) * SLOT + (wrow0 + gq) * 128 + ((((t & 1) * 4 + (t & 2)) ^ gq) << 4);
          float kva[20], en[32], mx[2][2], mn[2][2];
#define PV(hp, j) acc[32 * (hp) + (j)]
          auto mm = [&](int hp, int j) {
            const int r = (j >> 1) & 1;
            if (j < 4 && !(j & 1)) { mx[hp][r] = PV(hp, j); mn[hp][r] = PV(hp, j); }
            else { mx[hp][r] = fmaxf(mx[hp][r], PV(hp, j)); mn[hp][r] = fminf(mn[hp][r], PV(hp, j)); }
          };
          auto mmx = [&](int hp) {
#pragma unroll
            for (int r = 0; r < 2; ++r) {
              mx[hp][r] = fmaxf(mx[hp][r], __shfl_xor_sync(0xffffffffu, mx[hp][r], 2)) * -sc[r];
              mn[hp][r] = fmaf(fminf(mn[hp][r], __shfl_xor_sync(0xffffffffu, mn[hp][r], 2)), sc[r], mx[hp][r]);
            }
          };
          auto stage = [&](int hp) {
#pragma unroll
            for (int i = 0; i < 20; ++i) asm volatile("" : "+f"(kva[i]) :: "memory");
            nbar_dyn(3 + wu, 128);
            const uint32_t ad = sb + VB + hp * SLOT + wg * 8192 + (2 * wq + ((lane >> 3) & 1)) * 640 + (lane & 7) * 16;
#pragma unroll
            for (int i = 0; i < 2; ++i)
              stsm_x4(ad + (2 * i + lchk) * 128, pack_bf16(kva[8 * i], kva[8 * i + 1]), pack_bf16(kva[8 * i + 2], kva[8 * i + 3]),
                      pack_bf16(kva[8 * i + 4], kva[8 * i + 5]), pack_bf16(kva[8 * i + 6], kva[8 * i + 7]));
            stsm_x2(ad + 512, pack_bf16(kva[16], 0.0625f), pack_bf16(kva[18], 0.0625f));
            fence_async_smem();
            __syncwarp();
            if (lane == 0) mbar_arrive(BA(B_KVDONE));
          };
          int sn = 4;
#pragma unroll
          for (int j = 0; j < 32; ++j) mm(0, j);
          mmx(0);
#pragma unroll
          for (int hp = 0; hp < 2; ++hp) {
            float sp[2] = {0.f, 0.f}, sm[2] = {0.f, 0.f};
#pragma unroll
            for (int j = 0; j < 32; ++j) {
              const int r = (j >> 1) & 1, ns = hp ? SUBS1 : SUBS;
              if ((j * ns) / 32 != ((j + 1) * ns) / 32) {
                sub(sn++);
                if (hp && sn == 4 + SUBS + 4 + 4 * (XST & 1)) { stage(0); PROFT(tid_ == 128, layer * 16 + 12); }
              }
              const float x = fmaf(PV(hp, j), sc[r], mx[hp][r]);
              PV(hp, j) = ex2(x); en[j] = ex2(mn[hp][r] - x);
              sp[r] += PV(hp, j); sm[r] += en[j];
              if (hp == 0) {
                mm(1, j);
                if ((j & 3) == 0) {
                  const int jp = 8 + (j >> 2);
                  stsm_x4(vb + ((jp - 8) >> 1) * 8192 + (X0 ^ ((jp & 1) << 5)), pack_bf16(acc[8 * jp], acc[8 * jp + 1]), pack_bf16(acc[8 * jp + 2], acc[8 * jp + 3]),
                          pack_bf16(acc[8 * jp + 4], acc[8 * jp + 5]), pack_bf16(acc[8 * jp + 6], acc[8 * jp + 7]));
                }
              }
            }
#pragma unroll
            for (int i = 0; i < 4; ++i) if (XST & (1 << hp)) sub(sn++);
#pragma unroll
            for (int r = 0; r < 2; ++r) {
              sp[r] = rcp(sp[r] + __shfl_xor_sync(0xffffffffu, sp[r], 2)) * (r ? rs1 : rs0);
              sm[r] = rcp(sm[r] + __shfl_xor_sync(0xffffffffu, sm[r], 2)) * (r ? rs1 : rs0);
            }
            if (hp == 0) { mmx(1); mbar_wait(BA(CM + 15), par); }
            else { PROFT(tid_ == 128, layer * 16 + 11); nbar<1, 256>(); }
#pragma unroll
            for (int i = 0; i < 4; ++i) {
              const int r = i & 1, d = 16 * (i >> 1) + 2 * r;
              sts128((pb + r * 1024) ^ ((i >> 1) << 4), make_uint4(pack_bf16(PV(hp, d) * sp[r], PV(hp, d + 1) * sp[r]), pack_bf16(PV(hp, d + 4) * sp[r], PV(hp, d + 5) * sp[r]),
                                                                    pack_bf16(PV(hp, d + 8) * sp[r], PV(hp, d + 9) * sp[r]), pack_bf16(PV(hp, d + 12) * sp[r], PV(hp, d + 13) * sp[r])));
              sts128((pb + r * 1024) ^ ((i >> 1) << 4) ^ 64, make_uint4(pack_bf16(en[d] * sm[r], en[d + 1] * sm[r]), pack_bf16(en[d + 4] * sm[r], en[d + 5] * sm[r]),
                                                                         pack_bf16(en[d + 8] * sm[r], en[d + 9] * sm[r]), pack_bf16(en[d + 12] * sm[r], en[d + 13] * sm[r])));
            }
            fence_async_smem();
            nbar<1, 256>();
            const uint32_t dP = dB0 + (PH >> 4) + wu * 1024;
            const uint32_t dV = (dB0 & 0xFFFFu) + ((VB + hp * SLOT) >> 4) + (((SM_SD - VB - hp * SLOT) >> 4) << 16) + wu * (512u - (512u << 16));
            wgmma_fence();
#pragma unroll
            for (int ks = 0; ks < 8; ++ks) wgmma_n40_tt(kva, D128(dP + ks * 128), desc64(dV + ks * 64, 0x80000020u), ks != 0);
            wgmma_commit();
          }
#pragma unroll
          for (int i = 0; i < 4; ++i) sub(sn++);
          stage(1);
          PROFT(tid_ == 128, layer * 16 + 3);
          rest(sn >> 2, SKA);
          rest_end();
          PROFT(lane == 0 && layer == PL, 200 + cw);
          PROFT(tid_ == 128, layer * 16 + 10);
        }
#define QV(H, i) acc[128 + 16 * (H) + (i)]
        float mx[4][2], mn[4][2];
        uint32_t ph[4][4][4];
        auto mnx = [&](int hp) {
#pragma unroll
          for (int H = 2 * hp; H < 2 * hp + 2; ++H)
#pragma unroll
            for (int r = 0; r < 2; ++r) {
              mx[H][r] = fmaxf(fmaxf(fmaxf(QV(H, 2 * r), QV(H, 2 * r + 1)), fmaxf(QV(H, 4 + 2 * r), QV(H, 5 + 2 * r))),
                               fmaxf(fmaxf(QV(H, 8 + 2 * r), QV(H, 9 + 2 * r)), fmaxf(QV(H, 12 + 2 * r), QV(H, 13 + 2 * r))));
              mn[H][r] = fminf(fminf(fminf(QV(H, 2 * r), QV(H, 2 * r + 1)), fminf(QV(H, 4 + 2 * r), QV(H, 5 + 2 * r))),
                               fminf(fminf(QV(H, 8 + 2 * r), QV(H, 9 + 2 * r)), fminf(QV(H, 12 + 2 * r), QV(H, 13 + 2 * r))));
            }
#pragma unroll
          for (int o = 1; o <= 2; o <<= 1)
#pragma unroll
            for (int H = 2 * hp; H < 2 * hp + 2; ++H)
#pragma unroll
              for (int r = 0; r < 2; ++r) {
                mx[H][r] = fmaxf(mx[H][r], __shfl_xor_sync(0xffffffffu, mx[H][r], o));
                mn[H][r] = fminf(mn[H][r], __shfl_xor_sync(0xffffffffu, mn[H][r], o));
              }
#pragma unroll
          for (int H = 2 * hp; H < 2 * hp + 2; ++H)
#pragma unroll
            for (int r = 0; r < 2; ++r) { mx[H][r] *= -sc[r]; mn[H][r] = fmaf(mn[H][r], sc[r], mx[H][r]); }
        };
        auto fm = [&](int H) {
#pragma unroll
          for (int i = 0; i < 8; ++i) {
            const int r = i & 1;
            const float x0 = fmaf(QV(H, 2 * i), sc[r], mx[H][r]), x1 = fmaf(QV(H, 2 * i + 1), sc[r], mx[H][r]);
            ph[H][i >> 2][i & 3] = pack_bf16(ex2(x0), ex2(x1));
            ph[H][2 + (i >> 2)][i & 3] = pack_bf16(ex2(mn[H][r] - x0), ex2(mn[H][r] - x1));
          }
        };
        mnx(0);
        fm(0);
        fm(1);
#pragma unroll
        for (int hp = 0; hp < 2; ++hp) {
          if (hp) mbar_wait(BA(FW), par);
          mbar_wait(BA(hp ? B_KVF1 : B_KVF), (layer >> 1) & 1);
          PROFT(tid_ == 128, layer * 16 + (hp ? 4 : 5));
          float oa[4][20];
          wgmma_fence();
#pragma unroll
          for (int s = 0; s < 2; ++s)
#pragma unroll
            for (int v = 0; v < 4; ++v) {
              const int h = v >> 1, s4 = 2 * (v & 1) + s;
              wgmma_n40_rs(oa[v], ph[2 * hp + h][s4], desc64((((SB0 + VB + hp * SLOT) >> 4) | (40u << 16)) + h * 512 + (s4 ^ (2 * h)) * 80, 8), s != 0);
            }
          wgmma_commit();
          if (hp == 0) { mnx(1); wgmma_wait<0>(); }
          else wgmma_wait<0>();
#pragma unroll
          for (int i = 0; i < 20; ++i) asm volatile("" : "+f"(oa[0][i]), "+f"(oa[1][i]), "+f"(oa[2][i]), "+f"(oa[3][i]) :: "memory");
          uint32_t ow[2][2][4];
#pragma unroll
          for (int h = 0; h < 2; ++h)
#pragma unroll
            for (int r = 0; r < 2; ++r) {
              const float a = oa[2 * h + 1][17 + 2 * r], b = oa[2 * h][17 + 2 * r];
              const float id = rcp(fmaf(oa[2 * h][16 + 2 * r], a, fmaf(a, 1e-6f, oa[2 * h + 1][16 + 2 * r]) * b));
              const float fa = a * id, fb = b * id;
#pragma unroll
              for (int j = 0; j < 4; ++j)
                ow[h][r][j] = pack_bf16(fmaf(oa[2 * h][4 * j + 2 * r], fa, oa[2 * h + 1][4 * j + 2 * r] * fb),
                                        fmaf(oa[2 * h][4 * j + 2 * r + 1], fa, oa[2 * h + 1][4 * j + 2 * r + 1] * fb));
            }
#pragma unroll
          for (int i = 0; i < 16; ++i) of[4 * hp + (i >> 2)][i & 3] = ow[i >> 3][i & 1][(i >> 1) & 3];
          if (hp == 0) {
#pragma unroll
            for (int i = 0; i < 8; ++i) {
              if (!(i & 1)) stg128(g_o + gfr + ((i >> 1) & 1) * 8 * D_ + (i >> 2) * 32, ow[i >> 2][(i >> 1) & 1][0], ow[i >> 2][(i >> 1) & 1][1], ow[i >> 2][(i >> 1) & 1][2], ow[i >> 2][(i >> 1) & 1][3]);
              const int r = i & 1;
              const float x0 = fmaf(QV(2, 2 * i), sc[r], mx[2][r]), x1 = fmaf(QV(2, 2 * i + 1), sc[r], mx[2][r]);
              ph[2][i >> 2][i & 3] = pack_bf16(ex2v(x0), ex2v(x1));
              ph[2][2 + (i >> 2)][i & 3] = pack_bf16(ex2v(mn[2][r] - x0), ex2v(mn[2][r] - x1));
            }
            __syncwarp();
            if (lane == 0) mbar_arrive(BA(B_OH0));
            PROFT(tid_ == 128 && layer, layer * 16 + 15);
            fm(3);
          } else {
#pragma unroll
            for (int i = 0; i < 16; ++i) o1[i >> 2][i & 3] = ow[i >> 3][(i >> 2) & 1][i & 3];
          }
        }
      }
      PROFT(tid_ == 128, layer * 16 + 6);
#pragma unroll
      for (int i = 0; i < 4; ++i) stg128(g_o + gfr + (i & 1) * 8 * D_ + (2 + (i >> 1)) * 32, o1[i][0], o1[i][1], o1[i][2], o1[i][3]);
      __syncwarp();
      if (lane == 0) { mbar_arrive(BA(B_OH1)); if (EF_USED) REL2(B_EF); }
      PROFT(lane == 0 && layer == PL, 208 + cw);
      wo0();
    }
    {
      PHASE_CTX();
      MMA_CTX();
      mbar_wait(BA(FW + 1), par);
      wgmma_fence();
#pragma unroll
      for (int k = 0; k < 4; ++k) wgmma_n128_rs(acc, of[4 + k], D128(dB0 + (uint32_t)((WO_B >> 4) & 15) * 1024 + k * 128), 1);
      wgmma_commit();
      wgmma_wait<1>();
      if (elected) REL2(CW);
      uint64_t ta = WO_A >> 8, tw = WO_B >> 8;
      auto run = [&](int i0, int i1) {
#pragma unroll 1
        for (int i = i0; i < i1; ++i) {
          mbar_wait(BA(FW + i), par);
          PROFL(tid_ == 128 && layer == PL, 160 + i);
          const uint32_t da = dA0 + ((uint32_t)ta & 15) * 1024, db = dB0 + ((uint32_t)tw & 15) * 1024;
          ta >>= 4; tw >>= 4;
          wgmma_fence();
#pragma unroll
          for (int k = 0; k < 4; ++k) wgmma_n128(acc, D128(da + k * 2), D128(db + k * 128), 1);
          wgmma_commit();
          wgmma_wait<1>();
          if (elected) REL2(CW + i - 1);
        }
        ta = WO_A >> (4 * (i1 & 15)); tw = WO_B >> (4 * (i1 & 15));
      };
      run(2, XRAT);
#pragma unroll
      for (int j = 0; j < 8 / XRN; ++j) {
#pragma unroll
        for (int i = j * XRN; i < (j + 1) * XRN; ++i) ldg128((layer ? g_x : c.x0) + gfr + (i & 1) * 8 * D_ + (i >> 1) * 32, xp[i][0], xp[i][1], xp[i][2], xp[i][3]);
        run(XRAT + j, j + 1 < 8 / XRN ? XRAT + j + 1 : 16);
      }
      if (layer == 0) {
#pragma unroll
        for (int o = 1; o <= 2; o <<= 1)
#pragma unroll
          for (int i = 0; i < 16; ++i) {
            const int j = o == 1 ? 2 * (i & 1) : (i & 1);
            uint32_t &a = xp[i >> 1][j], &b = xp[i >> 1][j + o];
            const uint32_t r = __shfl_xor_sync(0xffffffffu, (t & o) ? a : b, o);
            if (t & o) a = r; else b = r;
          }
      }
      if (layer != NLAYERS - 1) mbar_wait(BA(FM), par ^ 1);
      wgmma_wait<0>();
#pragma unroll
      for (int i = 128; i < 192; ++i) asm volatile("" : "+f"(acc[i]) :: "memory");
      if (elected) REL2(CW + 15);
      PROFT(lane == 0 && layer == PL, 216 + cw);
      PROFT(tid_ == 128, layer * 16 + 7);
#pragma unroll
      for (int i = 0; i < 32; ++i)
        xp[i >> 2][i & 3] = add_bf16x2(xp[i >> 2][i & 3], pack_bf16(acc[128 + 16 * (i >> 3) + 4 * (i & 3) + 2 * ((i >> 2) & 1)], acc[129 + 16 * (i >> 3) + 4 * (i & 3) + 2 * ((i >> 2) & 1)]));
      if (layer == NLAYERS - 1) {
#pragma unroll
        for (int i = 0; i < 8; ++i) stsm_x4(sb + (XS + (i >> 2)) * SLOT + (Y ^ ((i & 2) << 5)) + (i & 1) * 1024, xp[i][0], xp[i][1], xp[i][2], xp[i][3]);
        __syncwarp();
        slab_out_half(sb + XS * SLOT, c.out + (size_t)m0 * D_ + g * 128, wrow0, lane);
        slab_out_half(sb + (XS + 1) * SLOT, c.out + (size_t)m0 * D_ + g * 128 + 64, wrow0, lane);
        PROFT(tid_ == 128, layer * 16 + 24);
        break;
      }
#pragma unroll
      for (int i = 0; i < 4; ++i) stg128(g_x + gfr + (i & 1) * 8 * D_ + (i >> 1) * 32, xp[i][0], xp[i][1], xp[i][2], xp[i][3]);
      __syncwarp();
      if (lane == 0) mbar_arrive(BA(B_XH0));
#pragma unroll
      for (int i = 0; i < 16; ++i) xf[i >> 2][i & 3] = xp[2 * (i >> 3) + (i & 1)][(i >> 1) & 3];
      PROFT(tid_ == 128, layer * 16 + 24);
    }
  }
}

__device__ __forceinline__ uint64_t k_order(int o) {
  const uint32_t lo = (1u << (4 * o)) - 1u, h0 = (0xECA86420u & lo) | ((0xECA86420u >> 4) & ~lo);
  return (uint64_t)(2 * o) | ((uint64_t)(2 * o + 1) << 4) | ((uint64_t)(h0 & 0xFFFFFFFu) << 8) | ((uint64_t)((h0 & 0xFFFFFFFu) | 0x1111111u) << 36);
}

__global__ void __cluster_dims__(2, 1, 1) __launch_bounds__(384, 1)
mega_kernel(const __grid_constant__ Maps maps, const __grid_constant__ Ctx c, const bf16* __restrict__ wA, const bf16* __restrict__ wB,
            const bf16* __restrict__ woA, const bf16* __restrict__ woB) {
  if (blockIdx.x - c.boff >= 128u) {
    const unsigned int epoch = ld_relaxed(&g_epoch);
    const int e = (blockIdx.x - c.boff) & 3, tid = threadIdx.x;
    float s[8] = {0.f, 0.f, 0.f, 0.f, 0.f, 0.f, 0.f, 0.f};
    const uint32_t sb = smem_u32(smem_raw), bar = sb + SM_BAR;
    auto issue = [&](int i) {
      mbar_expect_tx(BA(i & 3), 49152);
      bulk_load(sb + (i & 3) * 49152, wB + (size_t)e * 256 * 3072 + i * 24576, 49152, BA(i & 3));
    };
    if (tid == 0) {
#pragma unroll 1
      for (int i = 0; i < 4; ++i) {
        mbar_init(BA(i), 1);
        fence_async_smem();
        issue(i);
      }
    }
    __syncthreads();
#pragma unroll 1
    for (int i = 0; i < 32; ++i) {
      mbar_wait(BA(i & 3), (i >> 2) & 1);
#pragma unroll 2
      for (int r = 0; r < 8; ++r) {
        const uint4 v = lds128(sb + (i & 3) * 49152 + r * 6144 + tid * 16);
        s[0] += bf_lo(v.x); s[1] += bf_hi(v.x); s[2] += bf_lo(v.y); s[3] += bf_hi(v.y);
        s[4] += bf_lo(v.z); s[5] += bf_hi(v.z); s[6] += bf_lo(v.w); s[7] += bf_hi(v.w);
      }
      __syncthreads();
      if (tid == 0 && i < 28) issue(i + 4);
    }
    float* cd = g_cs + (epoch & 1) * 6144 + 3072 + ((tid >> 4) & 7) * 384 + (tid < 128 ? 256 : (tid >> 7) * 128 - 128) + (tid & 15) * 8;
    red_add4(cd, s[0], s[1], s[2], s[3]);
    red_add4(cd + 4, s[4], s[5], s[6], s[7]);
    __syncthreads();
    if (tid == 0) flag_add(&g_csflag[8].v);
    const int op = (epoch & 1) ^ 1;
    float4* kz = reinterpret_cast<float4*>(g_kv + (size_t)op * (2 * 8 * 10240)) + e * 5120;
#pragma unroll 1
    for (int i = tid; i < 5120; i += 384) kz[i] = make_float4(0.f, 0.f, 0.f, 0.f);
    reinterpret_cast<float4*>(g_cs + op * 6144)[e * 384 + tid] = make_float4(0.f, 0.f, 0.f, 0.f);
#pragma unroll 1
    for (int i = tid; i < 1024; i += 384) reinterpret_cast<float4*>(g_stats + (op * 4 + e) * S_)[i] = make_float4(0.f, 0.f, 0.f, 0.f);
    return;
  }
  const int warp = __shfl_sync(0xffffffffu, threadIdx.x >> 5, 0), lane = threadIdx.x & 31;
  if (smem_u32(smem_raw) != SB0 + ((blockIdx.x & 1) << 24)) __trap();
  {
  const int cid = (blockIdx.x - c.boff) >> 1, u7 = ((cid - 36) * 37) >> 8, cr = blockIdx.x & 1;
  const int g = cid < 4 ? 4 + cid : cid < 36 ? (cid - 4) >> 3 : 4 + u7, rb = (cid < 4 ? 0 : cid < 36 ? (cid - 4) & 7 : cid - 35 - 7 * u7) * 2 + cr, m0 = rb * 128;
  const uint32_t sb = SB0 + (cr << 24), bar = sb + SM_BAR;
  PROFT(lane == 0 && (warp == 0 || warp == 4), 224 + (warp >> 2) * 8);
  uint32_t cx = 0;
  if (warp == 2) {
    if (lane < NMAP) asm volatile("prefetch.tensormap [%0];" ::"l"(&maps.m[lane]) : "memory");
    if (lane == 31) asm volatile("prefetch.global.L2 [%0];" ::"l"(&g_epoch));
  } else if (warp == 3) {
    cx = c_map[cid] + c_wop[lane] + c_wop[NWOP - lane] + c_aop[lane] + c_aop[NAOP - lane] + (uint32_t)(uintptr_t)g_x;
  } else if (warp >= 4 && warp < 8) {
    const int i = threadIdx.x - 128;
    asm volatile("prefetch.global.L2 [%0];" ::"l"(wA + (size_t)((rb & ~1) * 64 + cr * 32 + ((i >> 1) & 31)) * 3072 + (i >> 6) * 1024 + g * 128 + (i & 1) * 64));
  }
  if (warp < 2) {
    const int s = warp, kb = (rb & ~1) + s;
    if (lane == 0) {
      mbar_init(BA(FM + s), 1u);
      mbar_init(BA(B_RAW + warp), 1u);
      mbar_init(BA(warp ? B_X0 : B_KVS0), 1u);
      asm volatile("fence.mbarrier_init.release.cluster;" ::: "memory");
    }
    __syncwarp();
    if (warp == 0) tma_2d_e(sb + SM_SD, &maps.m[MAP_PHI], 0, g * 128, BA(B_RAW));
    else if (W1DL) __nanosleep(W1DL);
#pragma unroll
    for (int j = 0; j < 6; ++j)
      tma_5d_e(sb + (j < 2 ? 2 * s : j < 4 ? 9 + s : 2 * s + 1) * SLOT + (j & 1) * 8192, &maps.m[MAP_WA], (j < 2 ? 1024 : j < 4 ? 0 : 2048) + g * 128 + (j & 1) * 64, 2 * kb,
               BA(j < 4 ? B_RAW + warp : FM + s));
    tma_2d_e(sb + (XS + s) * SLOT, &maps.m[MAP_X0], kb * 64, m0, BA(FM + s));
    expect_tx_e(BA(B_RAW + warp), warp ? 32768 : 32768 + 8192);
    expect_tx_e(BA(FM + s), 32768);
    if (X0AT == 0 && warp == 1) {
      tma_2d_e(sb + 11 * SLOT, &maps.m[MAP_X0], g * 128, m0, BA(B_X0));
      tma_2d_e(sb + 12 * SLOT, &maps.m[MAP_X0], g * 128 + 64, m0, BA(B_X0));
      expect_tx_e(BA(B_X0), 32768);
    }
  } else if (warp >= 4 && lane == 0) {
#pragma unroll 1
    for (int i = 2 + (warp - 4) * 13; i < 15 + (warp - 4) * 13; ++i)
      mbar_init(BA(i), 1u << ((i < CM ? 0u : i < B_EF ? 2u : (uint32_t)(BAR_LG >> (4 * ((i - B_EF) & 15)))) & 7u));
    asm volatile("fence.mbarrier_init.release.cluster;" ::: "memory");
  }
  __syncwarp();
  asm volatile("barrier.cluster.arrive.relaxed.aligned;" ::: "memory");
  if (threadIdx.x == 96 + c.zero) sts_f(sb + SM_EPOCH + 4, __uint_as_float(cx));
  PROFT(lane == 0 && (warp == 0 || warp == 4), 225 + (warp >> 2) * 8);
  __syncwarp();
  PROFT(lane == 0 && (warp == 0 || warp == 4), 226 + (warp >> 2) * 8);
  }

  if (warp < 4) {
    asm volatile("setmaxnreg.dec.sync.aligned.u32 40;");
    PROFT(threadIdx.x == 0, 227);
    cluster_wait();
    PROFT(threadIdx.x == 0, 228);
    if (warp == 0 || warp == 3) {
    if (warp == 0) {
      BLK_CTX();
      const unsigned int epoch = __shfl_sync(0xffffffffu, ld_relaxed(&g_epoch), 0), xbase = epoch * NLAYERS;
      (void)xbase;
      const uint64_t ordg = k_order(g);
      if (X0AT) {
        mbar_wait_u(BA(B_RAW + X0AT - 1), 0);
        tma_2d_e(sb + 11 * SLOT, &maps.m[MAP_X0], g * 128, m0, BA(B_X0));
        tma_2d_e(sb + 12 * SLOT, &maps.m[MAP_X0], g * 128 + 64, m0, BA(B_X0));
        expect_tx_e(BA(B_X0), 32768);
      }
#pragma unroll 1
      for (int lp = 0; lp < 2 * NLAYERS; ++lp) {
        const int layer = lp >> 1, n1 = (lp & 1) ? NAOP : NAOP - 14;
        int n = (lp & 1) ? NAOP - 14 : 0;
        const uint64_t ord = lp ? ordg : k_order(rb >> 1);
        uint32_t ready = lp ? 0u : 0xFFFFu, nop = c_aop[n];
        const unsigned int* fl = ((lp & 1) ? g_of : g_xf) + rb * 32;
        const CUtensorMap* tm = &maps.m[(lp & 1) ? MAP_O : lp ? MAP_X : MAP_X0];
        const uint32_t skip = layer ? 1u << 25 : 9u << 22;
#pragma unroll 1
        for (; n < n1; ++n) {
          const uint32_t op = nop;
          nop = c_aop[n + 1];
          const uint32_t kb = (uint32_t)(ord >> ((op >> 2) & 60)) & 15;
          uint32_t dst = sb + (op & 15) * SLOT, kc = kb * 64, fb = bar + ((op >> 5) & 0x3F8), need = ~ready & (1u << kb);
          asm volatile("" : "+r"(dst), "+r"(kc), "+r"(fb), "+r"(need));
          const uint32_t eb = bar + ((op >> 12) & 0x3F8), ep = (layer ^ (op >> 22)) & 1;
          bool fr = op & skip;
          if (need) {
            if (!fr) fr = __all_sync(0xffffffffu, mbar_test_wait(eb, ep));
            PROFT(lane == 0 && (n == 0 || n == NAOP - 14), 64 + layer * 16 + (n ? 2 : 0));
            src_wait<0>(fl, xbase + layer + 1, need, ready, lane);
            fence_async_all();
          }
          if (!fr) mbar_wait_u(eb, ep);
          tma_2d_e(dst, tm, kc, m0, fb);
          PROFT(lane == 0 && (n == 0 || n == NAOP - 14), 64 + layer * 16 + (n ? 3 : 1));
          PROFL(lane == 0 && layer == PL && n >= NAOP - 14, 178 + n - (NAOP - 14));
          PROFL(lane == 0 && layer == PL + 1 && n < 4, 242 + n);
        }
      }
    } else {
      BLK_CTX();
      const unsigned int epoch = __shfl_sync(0xffffffffu, ld_relaxed(&g_epoch), 0), xbase = epoch * NLAYERS;
      (void)xbase;
      const uint64_t ordg = k_order(g);
#pragma unroll 1
      for (int layer = 0; layer < NLAYERS; ++layer) {
        const uint64_t ordq = layer ? ordg : k_order(rb >> 1);
        uint32_t ready = layer ? 0xFFFFu : 0u, nop = c_wop[0];
        const CUtensorMap* tq = &maps.m[(layer & 1) ? MAP_WB : MAP_WF];
        const CUtensorMap* tk = &maps.m[(layer & 1) ? MAP_WB : cr ? MAP_WA : MAP_WF];
        const uint32_t skip = layer ? 1u << 25 : 9u << 22, pm = layer ? 0xE0u : 0u;
        int n = 0;
#pragma unroll 1
        for (; n < NWOP - 16; ++n) {
          const uint32_t op = nop;
          nop = c_wop[n + 1];
          const uint32_t isq = (op >> 23) & 1, fb = bar + ((op >> 5) & 0x3F8);
          const uint32_t kb = (uint32_t)(ordq >> ((op >> 2) & 60)) & 15;
          const CUtensorMap* tm = (isq ? tq : tk) + ((op & pm) ? 1 : 0);
          const uint32_t dst = sb + (op & 15) * SLOT + cr * (isq ? 8192 : SLOT);
          const int col = g * 128 + (isq ? cr * 64 : 1024 + cr * 1024);
          if (layer == 0) {
            if ((op & 0x7E00) == 0) continue;
            const uint32_t need = ((isq || !cr) ? 1u << kb : 0u) | (((op >> 22) & 1) ? 0u : (((op >> 15) & 127) == CM ? 1u : 3u) << (rb & ~1));
            if ((ready & need) != need) {
              src_wait<0>(g_wff + g * 32, epoch + 1, need, ready, lane);
              fence_async_all();
            }
            if ((op & 15) >= 11) mbar_wait_u(BA(B_XT), 0);
          }
          wait_tma_5d_mc(!(op & skip), bar + ((op >> 12) & 0x3F8), (layer ^ (op >> 22)) & 1, dst, tm, col, 2 * kb, fb);
          if (!isq) tma_5d_mc_e(dst + 8192, tm, col + 64, 2 * kb, fb);
          if (op >> 26) expect_tx_e(fb, (op >> 26) * 8192);
          PROFL(lane == 0 && layer == PL + 1 && n < 16, 128 + n);
        }
        const CUtensorMap* to = &maps.m[(layer & 1) ? MAP_WOB : MAP_WOA];
#pragma unroll 1
        for (; n < NWOP; ++n) {
          const uint32_t op = nop;
          nop = c_wop[n + 1];
          const uint32_t fb = bar + ((op >> 5) & 0x3F8), kb = (uint32_t)(ordg >> ((op >> 2) & 60)) & 15;
          if (WH < 16 && n == NWOP - 16 + WH && !(layer & 1)) mbar_wait_u(BA(B_KVS), (layer >> 1) & 1);
          wait_tma_5d_mc(!((op >> 25) & 1), bar + ((op >> 12) & 0x3F8), layer & 1, sb + (op & 15) * SLOT + cr * 8192, to + ((op & 0xE0) ? 1 : 0), g * 128 + cr * 64, 2 * kb, fb);
          expect_tx_e(fb, (op >> 26) * 8192);
          PROFL(lane == 0 && layer == PL, 144 + ((op >> 8) & 127) - FW);
        }
      }
    }
    } else if (warp == 1) {
      BLK_CTX();
      const unsigned int epoch = __shfl_sync(0xffffffffu, ld_relaxed(&g_epoch), 0), xbase = epoch * NLAYERS;
      (void)xbase;
      if (lane == 0) {
        mbar_wait(BA(B_WFD), 0);
        PROFT(true, 229);
#pragma unroll 1
        for (int j = 0; j < 4; ++j) tma_store_5d(&maps.m[MAP_WF], sb + (j < 2 ? 2 * cr : 9 + cr) * SLOT + (j & 1) * 8192, (j < 2 ? 1024 : 0) + g * 128 + (j & 1) * 64, 2 * rb);
        bulk_commit();
        bulk_wait0();
        PROFT(true, 230);
        fence_async_all();
        flag_set(g_wff + g * 32 + rb, epoch + 1);
        PROFT(true, 64 + 13);
#pragma unroll 1
        for (int e = 0; e < NLAYERS; ++e) {
          BLK_CTX();
          if (e > 0) {
            mbar_wait(BA(B_XH0), (e - 1) & 1);
            PROFT(e == PL + 1, 240);
            flag_set(g_xf + rb * 32 + 2 * g, xbase + e + 1);
            PROFT(e == PL + 1, 241);
          }
          mbar_wait(BA(B_XDONE), e & 1);
          PROFT(true, 64 + e * 16 + 4);
          flag_set(g_xf + rb * 32 + 2 * g + 1, xbase + e + 1);
          if (e == 0) {
            flag_add(&g_csflag[g].v);
#pragma unroll 1
            for (int i = 0; i < 4; ++i) {
              mbar_wait(BA(CM + PFM + PFS * i), 0);
              l2_prefetch(i < 3 ? wB + (size_t)(i * 128 + bid_) * 8192 : woA + (size_t)bid_ * 8192, 16384);
            }
          }
          if (PFM && e == 1) l2_prefetch(woB + (size_t)bid_ * 8192, 16384);
          PROFT(true, 64 + e * 16 + 7);
          if ((e & 1) == 0) {
            bf16* kvl = g_kv + ((size_t)((epoch & 1) * 2 + (e >> 1)) * 8 + g) * 10240;
#pragma unroll 1
            for (int hp = 0; hp < 2; ++hp) {
              mbar_wait(BA(B_KVDONE), hp);
#pragma unroll 1
              for (int i = 0; i < 4; ++i) {
                const int ch = (i + (rb >> 2)) & 3;
                bulk_red_add(kvl + hp * 5120 + ch * 1280, sb + VB + hp * SLOT + (ch >> 1) * 8192 + (ch & 1) * 2560, 2560);
                bulk_commit();
                asm volatile("cp.async.bulk.wait_group %0;" :: "n"(CHW) : "memory");
              }
              bulk_wait0();
              PROFT(true, 64 + e * 16 + (hp ? 10 : 6));
              fence_async_all();
              flag_add(&g_kvflag[hp * 8 + g].v);
              mbar_arrive(BA(hp ? B_KVS : B_KVS0));
              PROFT(e > 0 && hp, 64 + e * 16 + 8);
            }
          }
          if (e & 1) {
            mbar_wait(BA(B_OF0), (e >> 1) & 1);
            flag_set(g_hf + rb * 32 + g, xbase + e + 1);
            if (rb) flag_wait(g_hf + (rb - 1) * 32 + g, xbase + e + 1);
            fence_async_all();
            mbar_expect_tx(BA(B_HALO), 8192);
            bulk_load(sb + SM_SD, g_halo + (size_t)(((e >> 1) * 17 + rb) * 8 + g) * 2048, 8192, BA(B_HALO));
            PROFT(true, 64 + e * 16 + 15);
          }
          mbar_wait(BA(B_OH0), e & 1);
          PROFT(e > 0, 64 + e * 16 + 13);
          flag_set(g_of + rb * 32 + 2 * g, xbase + e + 1);
          PROFT(true, 64 + e * 16 + 9);
          mbar_wait(BA(B_OH1), e & 1);
          PROFT(true, 64 + e * 16 + 5);
          flag_set(g_of + rb * 32 + 2 * g + 1, xbase + e + 1);
          PROFT(true, 64 + e * 16 + 11);
        }
        if (bid_ == 0) g_epoch = epoch + 1;
      }
    } else {
      BLK_CTX();
      const unsigned int epoch = __shfl_sync(0xffffffffu, ld_relaxed(&g_epoch), 0), xbase = epoch * NLAYERS;
      (void)xbase;
      if (lane < 16) sts_f(sb + SM_RS + lane * 4, 0.f);
#pragma unroll 1
      for (int layer = 0; layer < NLAYERS; ++layer) {
#define HLP_CTX() BLK_CTX(); int lane = threadIdx.x & 31; asm volatile("" : "+r"(lane)); const bool isB = layer & 1, hal = isB && rb > 0; (void)hal;
#pragma unroll 1
        for (int ph = 0; ph < 2; ++ph) {
          HLP_CTX();
          if (ph == (layer == 0)) {
            const float* cs = g_cs + (epoch & 1) * 6144 + g * 384;
            if (layer) mbar_wait_u(BA(CT), (layer - 1) & 1);
            if (layer < 2) {
              if (lane == 0) flag_wait_slow(&g_csflag[isB ? 8 : g].v, isB ? epoch * 4u + 4u : epoch * 16u + 16u);
              __syncwarp();
            }
#pragma unroll 1
            for (int i0 = 0; i0 < 12; i0 += 4) {
              float a[4];
#pragma unroll
              for (int i = 0; i < 4; ++i) a[i] = __ldcg(cs + isB * 3072 + (i0 + i) * 32 + lane);
#pragma unroll
              for (int i = 0; i < 4; ++i) {
                const float c1 = bf16r(a[i]), c2 = bf16r(a[i] - c1), c3 = (a[i] - c1) - c2;
                sts128(sb + SM_BP + ((i0 + i) * 32 + lane) * 16, make_uint4(pack_bf16(c1, c2), pack_bf16(c3, 0.f), 0u, 0u));
              }
            }
          } else {
            uint32_t rdy = 0u;
            src_wait<128>(g_xf + rb * 32, xbase + layer + 1, 0xAAAAu, rdy, lane);
            rdy = 0u;
            if (hal) src_wait<128>(g_xf + (rb - 1) * 32, xbase + layer + 1, 0xAAAAu, rdy, lane);
            const float2* sp = g_stats + ((epoch & 1) * 4 + layer) * S_ + m0 + lane;
            float2 u[5];
#pragma unroll
            for (int i = 0; i < 4; ++i) u[i] = __ldcg(sp + i * 32);
            u[4] = __ldcg(sp - (hal ? 16 : 0));
#pragma unroll 1
            for (int i = 0; i < 5; ++i) {
              const float mean = u[0].x * (1.f / D_);
              const float var = fmaxf(fmaf(-u[0].x, mean, u[0].y) * (1.f / D_), 0.f);
              const float sd = bf16r(sqrtf(bf16r(bf16r(var) + 1e-5f)));
              const int R = i * 32 + lane;
              if (i < 4) {
                const float hm = -0.5f * bf16r(mean);
                if (!isB) sts128(sb + SM_SD + R * 64 + ((R >> 1) & 3) * 16, make_uint4(__float_as_uint(sd) >> 16, __float_as_uint(sd) >> 16, __float_as_uint(sd) >> 16, __float_as_uint(sd) >> 16));
                sts128(sb + SM_AP + R * 16, make_uint4(pack_bf16(hm, hm), pack_bf16(hm, 0.f), 0u, 0u));
              }
              if (i < 4 || (hal && lane < 16)) sts_f(sb + SM_RS + (i < 4 ? 16 + R : lane) * 4, __fdividef(1.f, sd));
#pragma unroll
              for (int j = 0; j < 4; ++j) u[j] = u[j + 1];
            }
            PROFT(lane == 0, 64 + layer * 16 + 12);
          }
        }
        HLP_CTX();
        fence_async_smem();
        __syncwarp();
        if (lane == 0) mbar_arrive(BA(B_STAT));
        PROFT(lane == 0, 64 + layer * 16 + 14);
        if (!isB && lane == 0) {
#pragma unroll 1
          for (int hp = 0; hp < 2; ++hp) {
            mbar_wait(BA(hp ? B_KVS : B_KVS0), (layer >> 1) & 1);
            flag_wait(&g_kvflag[hp * 8 + g].v, epoch * (16u * ((NLAYERS + 1) / 2)) + 16u * ((layer >> 1) + 1));
            const bf16* kvl = g_kv + ((size_t)((epoch & 1) * 2 + (layer >> 1)) * 8 + g) * 10240 + hp * 5120;
            const uint32_t kb = BA(hp ? B_KVF1 : B_KVF);
            fence_async_all();
            mbar_expect_tx(kb, 10240);
            bulk_load(sb + VB + hp * SLOT, kvl, 5120, kb);
            bulk_load(sb + VB + hp * SLOT + 8192, kvl + 2560, 5120, kb);
            PROFT(hp == 0, 64 + layer * 16 + 15);
          }
        }
        __syncwarp();
      }
    }
    __syncwarp();
    asm volatile("barrier.cluster.arrive.relaxed.aligned;" ::: "memory");
    cluster_wait();
  } else {
    asm volatile("setmaxnreg.inc.sync.aligned.u32 232;");
    PROFT(threadIdx.x == 128, 235);
    cluster_wait();
    PROFT(threadIdx.x == 128, 236);
    consumer(c);
    asm volatile("bar.warp.sync 0xffffffff;\nbarrier.cluster.arrive.relaxed.aligned;\nbarrier.cluster.wait.aligned;\n" ::: "memory");
  }
}

typedef CUresult (*PFN_encodeTiled)(CUtensorMap*, CUtensorMapDataType, cuuint32_t, void*, const cuuint64_t*, const cuuint64_t*,
                                    const cuuint32_t*, const cuuint32_t*, CUtensorMapInterleave, CUtensorMapSwizzle,
                                    CUtensorMapL2promotion, CUtensorMapFloatOOBfill);

static void make_map2(PFN_encodeTiled enc, CUtensorMap* m, const void* ptr, uint64_t cols, uint64_t rows, uint32_t box_c, uint32_t box_r) {
  cuuint64_t dims[2] = {cols, rows};
  cuuint64_t strides[1] = {cols * 2};
  cuuint32_t box[2] = {box_c, box_r};
  cuuint32_t es[2] = {1, 1};
  CUresult r = enc(m, CU_TENSOR_MAP_DATA_TYPE_BFLOAT16, 2, const_cast<void*>(ptr), dims, strides, box, es, CU_TENSOR_MAP_INTERLEAVE_NONE,
                   box_c == 64 ? CU_TENSOR_MAP_SWIZZLE_128B : CU_TENSOR_MAP_SWIZZLE_64B, CU_TENSOR_MAP_L2_PROMOTION_L2_256B, CU_TENSOR_MAP_FLOAT_OOB_FILL_NONE);
  (void)r;
}
static void make_map5(PFN_encodeTiled enc, CUtensorMap* m, const void* ptr, uint64_t cols) {
  for (int p = 0; p < 2; ++p) {
    cuuint64_t dims[5] = {cols, 2, 4, 4, 32};
    cuuint64_t strides[4] = {cols * 2, cols * (p ? 16 : 4), cols * (p ? 4 : 16), cols * 64};
    cuuint32_t box[5] = {64, 2, 4, 4, 2};
    cuuint32_t es[5] = {1, 1, 1, 1, 1};
    CUresult r = enc(m + p, CU_TENSOR_MAP_DATA_TYPE_BFLOAT16, 5, const_cast<void*>(ptr), dims, strides, box, es, CU_TENSOR_MAP_INTERLEAVE_NONE,
                     CU_TENSOR_MAP_SWIZZLE_128B, CU_TENSOR_MAP_L2_PROMOTION_L2_256B, CU_TENSOR_MAP_FLOAT_OOB_FILL_NONE);
    (void)r;
  }
}

extern "C" void kernel_launch(void* const* d_in, const int* in_sizes, int n_in, void* d_out, int out_size) {
  const bf16* A_x = (const bf16*)d_in[0];
  const bf16* A_wqkv = (const bf16*)d_in[1];
  const bf16* A_wphi = (const bf16*)d_in[2];
  const bf16* A_wo = (const bf16*)d_in[3];
  const bf16* B_wqkv = (const bf16*)d_in[5];
  const bf16* B_wo = (const bf16*)d_in[6];
  bf16* out = (bf16*)d_out;

  static PFN_encodeTiled enc = nullptr;
  static bf16 *p_x, *p_o, *p_wf;
  static uint32_t boff;
  if (!enc) {
    void* fn = nullptr; cudaDriverEntryPointQueryResult qr;
    cudaGetDriverEntryPoint("cuTensorMapEncodeTiled", &fn, cudaEnableDefault, &qr);
    enc = (PFN_encodeTiled)fn;
    cudaGetSymbolAddress((void**)&p_x, g_x);
    cudaGetSymbolAddress((void**)&p_o, g_o);
    cudaGetSymbolAddress((void**)&p_wf, g_wf);
    cudaFuncSetAttribute(mega_kernel, cudaFuncAttributeMaxDynamicSharedMemorySize, SM_TOTAL);
    cudaLaunchConfig_t cfg = {};
    cudaLaunchAttribute at; at.id = cudaLaunchAttributeClusterDimension; at.val.clusterDim.x = 2; at.val.clusterDim.y = 1; at.val.clusterDim.z = 1;
    cfg.gridDim = dim3(132); cfg.blockDim = dim3(384); cfg.dynamicSmemBytes = SM_TOTAL; cfg.attrs = &at; cfg.numAttrs = 1;
    int nc = 0;
    if (cudaOccupancyMaxActiveClusters(&nc, mega_kernel, &cfg) != cudaSuccess) { nc = 0; (void)cudaGetLastError(); }
    boff = nc >= 66 ? 0u : 4u;
  }
  Maps maps;
  make_map5(enc, &maps.m[MAP_WF], p_wf, 2048);
  make_map5(enc, &maps.m[MAP_WA], A_wqkv, 3072);
  make_map5(enc, &maps.m[MAP_WB], B_wqkv, 3072);
  make_map5(enc, &maps.m[MAP_WOA], A_wo, 1024);
  make_map5(enc, &maps.m[MAP_WOB], B_wo, 1024);
  make_map2(enc, &maps.m[MAP_X0], A_x, 1024, 2048, 64, 128);
  make_map2(enc, &maps.m[MAP_X], p_x, 1024, 2048, 64, 128);
  make_map2(enc, &maps.m[MAP_O], p_o, 1024, 2048, 64, 128);
  make_map2(enc, &maps.m[MAP_PHI], A_wphi, 32, 1024, 32, 128);
  Ctx c; c.zero = 0u; c.boff = boff; c.x0 = A_x; c.out = out;
  mega_kernel<<<132, 384, SM_TOTAL, cudaStreamPerThread>>>(maps, c, A_wqkv, B_wqkv, A_wo, B_wo);
}
```

```cpp
#include <cuda_runtime.h>
#include <cuda_bf16.h>
#include <cuda.h>
#include <stdint.h>

typedef __nv_bfloat16 bf16;

constexpr int S_ = 2048, D_ = 1024;

struct __align__(128) Flag { unsigned int v; unsigned int pad[31]; };
__device__ __align__(1024) bf16 g_x[S_ * D_];
__device__ __align__(1024) bf16 g_o[S_ * D_];
__device__ __align__(1024) uint32_t g_halo[2 * 17 * 8 * 2048];
__device__ __align__(1024) bf16 g_kv[2 * 2 * 8 * 10240];
__device__ __align__(1024) float2 g_stats[2 * 4 * S_];
__device__ __align__(1024) float g_cs[2 * 2 * 3072];
__device__ __align__(1024) bf16 g_wf[D_ * 2048];
__device__ Flag g_kvflag[16], g_csflag[13];
__device__ __align__(128) unsigned int g_xf[16 * 32], g_of[16 * 32];
__device__ __align__(128) unsigned int g_hf[16 * 32];
__device__ __align__(128) unsigned int g_wff[8 * 32];
__device__ unsigned int g_epoch, g_err;
#define PROFT(cond, idx) asm volatile("" ::: "memory")

__device__ __forceinline__ uint32_t smem_u32(const void* p) { return (uint32_t)__cvta_generic_to_shared(p); }
__device__ __forceinline__ void mbar_init(uint32_t bar, uint32_t count) {
  asm volatile("mbarrier.init.shared::cta.b64 [%0], %1;" ::"r"(bar), "r"(count) : "memory");
}
__device__ __forceinline__ void mbar_expect_tx(uint32_t bar, uint32_t bytes) {
  asm volatile("mbarrier.arrive.expect_tx.shared::cta.b64 _, [%0], %1;" ::"r"(bar), "r"(bytes) : "memory");
}
__device__ __forceinline__ void mbar_arrive(uint32_t bar) {
  asm volatile("mbarrier.arrive.shared::cta.b64 _, [%0];" ::"r"(bar) : "memory");
}
__device__ __forceinline__ bool mbar_try_wait(uint32_t bar, uint32_t parity) {
  uint32_t ok;
  asm volatile("{\n.reg .pred p;\nmbarrier.try_wait.parity.shared::cta.b64 p, [%1], %2;\nselp.b32 %0, 1, 0, p;\n}\n"
               : "=r"(ok) : "r"(bar), "r"(parity) : "memory");
  return ok != 0;
}
__device__ __forceinline__ bool mbar_test_wait(uint32_t bar, uint32_t parity) {
  uint32_t ok;
  asm volatile("{\n.reg .pred p;\nmbarrier.test_wait.parity.shared::cta.b64 p, [%1], %2;\nselp.b32 %0, 1, 0, p;\n}\n"
               : "=r"(ok) : "r"(bar), "r"(parity) : "memory");
  return ok != 0;
}
__device__ __forceinline__ uint64_t gtimer() {
  uint64_t t; asm volatile("mov.u64 %0, %globaltimer;" : "=l"(t)); return t;
}
__device__ __forceinline__ void mbar_wait(uint32_t bar, uint32_t parity) {
  uint32_t n = 0;
  bool ok;
#pragma unroll 1
  do { ++n; ok = mbar_try_wait(bar, parity); } while (!ok && n < (1u << 22));
}
__device__ __forceinline__ unsigned int ld_acquire(const unsigned int* p) {
  unsigned int v; asm volatile("ld.acquire.gpu.global.u32 %0, [%1];" : "=r"(v) : "l"(p) : "memory"); return v;
}
__device__ __forceinline__ void flag_add(unsigned int* p) {
  asm volatile("red.release.gpu.global.add.u32 [%0], 1;" ::"l"(p) : "memory");
}
__device__ __forceinline__ void flag_set(unsigned int* p, unsigned int v) {
  asm volatile("st.release.gpu.global.u32 [%0], %1;" ::"l"(p), "r"(v) : "memory");
}
template <int SLEEP>
__device__ __forceinline__ void src_wait(const unsigned int* f, unsigned int target, uint32_t need, uint32_t& ready, int lane) {
  uint32_t n = 0;
#pragma unroll 1
  while ((ready & need) != need) {
    const unsigned int v = ld_acquire(f + (lane & 15));
    ready = __ballot_sync(0xffffffffu, (int)(v - target) >= 0);
    if (SLEEP) { if ((ready & need) != need) __nanosleep(SLEEP); }
    if (++n > (1u << 20)) break;
  }
  __syncwarp();
}
__device__ __forceinline__ unsigned int ld_relaxed(const unsigned int* p);
__device__ __forceinline__ unsigned int ld_relaxed(const unsigned int* p) {
  unsigned int v; asm volatile("ld.relaxed.gpu.global.u32 %0, [%1];" : "=r"(v) : "l"(p) : "memory"); return v;
}
template <int SLEEP>
__device__ __forceinline__ void flag_wait_t(const unsigned int* p, unsigned int target) {
  uint32_t n = 0;
#pragma unroll 1
  while ((int)(ld_acquire(p) - target) < 0) {
    if (SLEEP) __nanosleep(SLEEP);
    if (++n > (1u << 20)) break;
  }
}
__device__ __forceinline__ void flag_wait(const unsigned int* p, unsigned int target) { flag_wait_t<0>(p, target); }
__device__ __forceinline__ void flag_wait_slow(const unsigned int* p, unsigned int target) { flag_wait_t<256>(p, target); }
__device__ __forceinline__ void mbar_wait_u(uint32_t bar, uint32_t parity) {
  uint32_t n = 0;
#pragma unroll 1
  while (!__all_sync(0xffffffffu, mbar_try_wait(bar, parity))) {
    if (++n > (1u << 22)) break;
  }
}
__device__ __forceinline__ void expect_tx_e(uint32_t bar, uint32_t bytes) {
  asm volatile("{\n.reg .pred p;\nelect.sync _|p, 0xffffffff;\n@p mbarrier.arrive.expect_tx.shared::cta.b64 _, [%0], %1;\n}\n" ::"r"(bar), "r"(bytes) : "memory");
}
__device__ __forceinline__ void tma_2d_e(uint32_t dst, const CUtensorMap* tm, int c0, int c1, uint32_t bar) {
  asm volatile("{\n.reg .pred p;\nelect.sync _|p, 0xffffffff;\n"
               "@p cp.async.bulk.tensor.2d.shared::cluster.global.mbarrier::complete_tx::bytes [%0], [%1, {%2, %3}], [%4];\n}\n"
               ::"r"(dst), "l"(tm), "r"(c0), "r"(c1), "r"(bar) : "memory");
}
__device__ __forceinline__ void tma_5d_e(uint32_t dst, const CUtensorMap* tm, int c0, int c4, uint32_t bar) {
  asm volatile("{\n.reg .pred p;\nelect.sync _|p, 0xffffffff;\n"
               "@p cp.async.bulk.tensor.5d.shared::cluster.global.mbarrier::complete_tx::bytes [%0], [%1, {%2, %5, %5, %5, %3}], [%4];\n}\n"
               ::"r"(dst), "l"(tm), "r"(c0), "r"(c4), "r"(bar), "r"(0) : "memory");
}
__device__ __forceinline__ void tma_5d_mc_e(uint32_t dst, const CUtensorMap* tm, int c0, int c4, uint32_t bar) {
  asm volatile("{\n.reg .pred p;\nelect.sync _|p, 0xffffffff;\n"
               "@p cp.async.bulk.tensor.5d.shared::cluster.global.mbarrier::complete_tx::bytes.multicast::cluster [%0], [%1, {%2, %6, %6, %6, %3}], [%4], %5;\n}\n"
               ::"r"(dst), "l"(tm), "r"(c0), "r"(c4), "r"(bar), "h"((uint16_t)3), "r"(0) : "memory");
}
__device__ __forceinline__ void wait_tma_5d_mc(bool w, uint32_t eb, uint32_t par, uint32_t dst, const CUtensorMap* tm, int c0, int c4, uint32_t fb) {
  asm volatile("" : "+r"(dst), "+l"(tm), "+r"(c0), "+r"(c4), "+r"(fb));
  if (w) mbar_wait_u(eb, par);
  tma_5d_mc_e(dst, tm, c0, c4, fb);
}
__device__ __forceinline__ void stg128(void* p, uint32_t a, uint32_t b, uint32_t c, uint32_t d) {
  asm volatile("st.global.v4.u32 [%0], {%1,%2,%3,%4};" ::"l"(p), "r"(a), "r"(b), "r"(c), "r"(d) : "memory");
}
__device__ __forceinline__ void stg128_p(bool on, void* p, uint32_t a, uint32_t b, uint32_t c, uint32_t d) {
  asm volatile("{\n.reg .pred p;\nsetp.ne.b32 p, %5, 0;\n@p st.global.v4.u32 [%0], {%1,%2,%3,%4};\n}\n" ::"l"(p), "r"(a), "r"(b), "r"(c), "r"(d), "r"((int)on) : "memory");
}
__device__ __forceinline__ void ldg128(const void* p, uint32_t& a, uint32_t& b, uint32_t& c, uint32_t& d) {
  asm volatile("ld.global.cg.v4.u32 {%0,%1,%2,%3}, [%4];" : "=r"(a), "=r"(b), "=r"(c), "=r"(d) : "l"(p) : "memory");
}
__device__ __forceinline__ void release2c(uint32_t off) {
  asm volatile("mbarrier.arrive.shared::cluster.b64 _, [%0];\nmbarrier.arrive.shared::cluster.b64 _, [%1];" ::"r"(off), "r"(off + (1u << 24)) : "memory");
}
__device__ __forceinline__ void tma_store_5d(const CUtensorMap* tm, uint32_t src, int c0, int c4) {
  asm volatile("cp.async.bulk.tensor.5d.global.shared::cta.bulk_group [%0, {%2, %4, %4, %4, %3}], [%1];"
               ::"l"(tm), "r"(src), "r"(c0), "r"(c4), "r"(0) : "memory");
}
__device__ __forceinline__ void bulk_load(uint32_t dst, const void* src, uint32_t bytes, uint32_t bar) {
  asm volatile("cp.async.bulk.shared::cluster.global.mbarrier::complete_tx::bytes [%0], [%1], %2, [%3];" ::"r"(dst), "l"(src), "r"(bytes), "r"(bar) : "memory");
}
__device__ __forceinline__ void bulk_red_add(void* dst, uint32_t src, uint32_t bytes) {
  asm volatile("cp.reduce.async.bulk.global.shared::cta.bulk_group.add.noftz.bf16 [%0], [%1], %2;" ::"l"(dst), "r"(src), "r"(bytes) : "memory");
}
__device__ __forceinline__ void bulk_commit() { asm volatile("cp.async.bulk.commit_group;" ::: "memory"); }
__device__ __forceinline__ void bulk_wait0() { asm volatile("cp.async.bulk.wait_group 0;" ::: "memory"); }
__device__ __forceinline__ void fence_async_smem() { asm volatile("fence.proxy.async.shared::cta;" ::: "memory"); }
__device__ __forceinline__ void fence_async_all() { asm volatile("fence.proxy.async.global;" ::: "memory"); }
__device__ __forceinline__ void wgmma_fence() { asm volatile("wgmma.fence.sync.aligned;" ::: "memory"); }
__device__ __forceinline__ void wgmma_commit() { asm volatile("wgmma.commit_group.sync.aligned;" ::: "memory"); }
template <int N> __device__ __forceinline__ void wgmma_wait() { asm volatile("wgmma.wait_group.sync.aligned %0;" ::"n"(N) : "memory"); }
__device__ __forceinline__ void cluster_wait() { asm volatile("barrier.cluster.wait.acquire.aligned;" ::: "memory"); }
template <int ID, int N> __device__ __forceinline__ void nbar() { asm volatile("bar.sync %0, %1;" ::"n"(ID), "n"(N) : "memory"); }
__device__ __forceinline__ uint64_t desc64(uint32_t lo, uint32_t hi) { return (uint64_t)lo | ((uint64_t)hi << 32); }
__device__ __forceinline__ uint32_t pack_bf16(float lo, float hi) {
  uint32_t r; asm("cvt.rn.bf16x2.f32 %0, %1, %2;" : "=r"(r) : "f"(hi), "f"(lo)); return r;
}
__device__ __forceinline__ uint32_t add_bf16x2(uint32_t a, uint32_t b) {
  uint32_t r; asm("add.rn.bf16x2 %0, %1, %2;" : "=r"(r) : "r"(a), "r"(b)); return r;
}
__device__ __forceinline__ float bf16r(float x) { return __bfloat162float(__float2bfloat16_rn(x)); }
__device__ __forceinline__ float bf_lo(uint32_t u) { return __uint_as_float(u << 16); }
__device__ __forceinline__ float bf_hi(uint32_t u) { return __uint_as_float(u & 0xFFFF0000u); }
__device__ __forceinline__ float ex2(float x) { float r; asm("ex2.approx.ftz.f32 %0, %1;" : "=f"(r) : "f"(x)); return r; }
__device__ __forceinline__ float rcp(float x) { float r; asm("rcp.approx.ftz.f32 %0, %1;" : "=f"(r) : "f"(x)); return r; }
__device__ __forceinline__ void mma_bf16(float (&d)[4], uint32_t a0, uint32_t a1, uint32_t a2, uint32_t a3, uint32_t b0, uint32_t b1) {
  asm("mma.sync.aligned.m16n8k16.row.col.f32.bf16.bf16.f32 {%0,%1,%2,%3}, {%4,%5,%6,%7}, {%8,%9}, {%0,%1,%2,%3};"
               : "+f"(d[0]), "+f"(d[1]), "+f"(d[2]), "+f"(d[3]) : "r"(a0), "r"(a1), "r"(a2), "r"(a3), "r"(b0), "r"(b1));
}
__device__ __forceinline__ void ldsm_x4(uint32_t& r0, uint32_t& r1, uint32_t& r2, uint32_t& r3, uint32_t addr) {
  asm volatile("ldmatrix.sync.aligned.m8n8.x4.shared.b16 {%0,%1,%2,%3}, [%4];"
               : "=r"(r0), "=r"(r1), "=r"(r2), "=r"(r3) : "r"(addr) : "memory");
}
__device__ __forceinline__ void ldsm_x4_t(uint32_t& r0, uint32_t& r1, uint32_t& r2, uint32_t& r3, uint32_t addr) {
  asm volatile("ldmatrix.sync.aligned.m8n8.x4.trans.shared.b16 {%0,%1,%2,%3}, [%4];"
               : "=r"(r0), "=r"(r1), "=r"(r2), "=r"(r3) : "r"(addr) : "memory");
}
__device__ __forceinline__ void stsm_x4(uint32_t addr, uint32_t r0, uint32_t r1, uint32_t r2, uint32_t r3) {
  asm volatile("stmatrix.sync.aligned.m8n8.x4.shared.b16 [%0], {%1,%2,%3,%4};"
               ::"r"(addr), "r"(r0), "r"(r1), "r"(r2), "r"(r3) : "memory");
}
__device__ __forceinline__ void stsm_x2(uint32_t addr, uint32_t r0, uint32_t r1) {
  asm volatile("stmatrix.sync.aligned.m8n8.x2.shared.b16 [%0], {%1,%2};" ::"r"(addr), "r"(r0), "r"(r1) : "memory");
}
__device__ __forceinline__ uint4 lds128(uint32_t addr) {
  uint4 v; asm volatile("ld.shared.v4.b32 {%0,%1,%2,%3}, [%4];" : "=r"(v.x), "=r"(v.y), "=r"(v.z), "=r"(v.w) : "r"(addr) : "memory"); return v;
}
__device__ __forceinline__ void sts128(uint32_t addr, uint4 v) {
  asm volatile("st.shared.v4.b32 [%0], {%1,%2,%3,%4};" ::"r"(addr), "r"(v.x), "r"(v.y), "r"(v.z), "r"(v.w) : "memory");
}
__device__ __forceinline__ float lds_f(uint32_t addr) {
  float v; asm volatile("ld.shared.f32 %0, [%1];" : "=f"(v) : "r"(addr) : "memory"); return v;
}
__device__ __forceinline__ void nbar_dyn(int id, int n) { asm volatile("bar.sync %0, %1;" ::"r"(id), "r"(n) : "memory"); }
__device__ __forceinline__ uint64_t make_desc_ns(uint32_t addr, uint32_t lbo_bytes, uint32_t sbo_bytes) {
  return (uint64_t)((addr & 0x3FFFF) >> 4) | ((uint64_t)(lbo_bytes >> 4) << 16) | ((uint64_t)(sbo_bytes >> 4) << 32);
}
__device__ __forceinline__ void sts_f(uint32_t addr, float v) { asm volatile("st.shared.f32 [%0], %1;" ::"r"(addr), "f"(v) : "memory"); }
__device__ __forceinline__ void sts64(uint32_t addr, uint32_t a, uint32_t b) {
  asm volatile("st.shared.v2.b32 [%0], {%1,%2};" ::"r"(addr), "r"(a), "r"(b) : "memory");
}
__device__ __forceinline__ void sts_f2(uint32_t addr, float a, float b) {
  asm volatile("st.shared.v2.f32 [%0], {%1,%2};" ::"r"(addr), "f"(a), "f"(b) : "memory");
}
__device__ __forceinline__ void red_add2_p(bool on, float* p, float a, float b) {
  asm volatile("{\n.reg .pred p;\nsetp.ne.b32 p, %3, 0;\n@p red.global.add.v2.f32 [%0], {%1,%2};\n}\n" ::"l"(p), "f"(a), "f"(b), "r"((int)on) : "memory");
}
__device__ __forceinline__ void red_add4(float* p, float a, float b, float c, float d) {
  asm volatile("red.global.add.v4.f32 [%0], {%1,%2,%3,%4};" ::"l"(p), "f"(a), "f"(b), "f"(c), "f"(d) : "memory");
}
__device__ __forceinline__ void red_add1(float* p, float a) {
  asm volatile("red.global.add.f32 [%0], %1;" ::"l"(p), "f"(a) : "memory");
}
__device__ __forceinline__ void l2_prefetch(const void* p, uint32_t bytes) {
  asm volatile("cp.async.bulk.prefetch.L2.global [%0], %1;" ::"l"(p), "r"(bytes) : "memory");
}

__device__ __forceinline__ void wgmma_n256(float (&d)[192], uint64_t da, uint64_t db, int scale_d) {
  asm volatile("{\n.reg .pred p;\nsetp.ne.b32 p, %130, 0;\n"
    "wgmma.mma_async.sync.aligned.m64n256k16.f32.bf16.bf16 {%0, %1, %2, %3, %4, %5, %6, %7, %8, %9, %10, %11, %12, %13, %14, %15, %16, %17, %18, %19, %20, %21, %22, %23, %24, %25, %26, %27, %28, %29, %30, %31, %32, %33, %34, %35, %36, %37, %38, %39, %40, %41, %42, %43, %44, %45, %46, %47, %48, %49, %50, %51, %52, %53, %54, %55, %56, %57, %58, %59, %60, %61, %62, %63, %64, %65, %66, %67, %68, %69, %70, %71, %72, %73, %74, %75, %76, %77, %78, %79, %80, %81, %82, %83, %84, %85, %86, %87, %88, %89, %90, %91, %92, %93, %94, %95, %96, %97, %98, %99, %100, %101, %102, %103, %104, %105, %106, %107, %108, %109, %110, %111, %112, %113, %114, %115, %116, %117, %118, %119, %120, %121, %122, %123, %124, %125, %126, %127}, %128, %129, p, 1, 1, 0, 1;\n}\n"
    : "+f"(d[0]), "+f"(d[1]), "+f"(d[2]), "+f"(d[3]), "+f"(d[4]), "+f"(d[5]), "+f"(d[6]), "+f"(d[7]), "+f"(d[8]), "+f"(d[9]), "+f"(d[10]), "+f"(d[11]), "+f"(d[12]), "+f"(d[13]), "+f"(d[14]), "+f"(d[15]), "+f"(d[16]), "+f"(d[17]), "+f"(d[18]), "+f"(d[19]), "+f"(d[20]), "+f"(d[21]), "+f"(d[22]), "+f"(d[23]), "+f"(d[24]), "+f"(d[25]), "+f"(d[26]), "+f"(d[27]), "+f"(d[28]), "+f"(d[29]), "+f"(d[30]), "+f"(d[31]), "+f"(d[32]), "+f"(d[33]), "+f"(d[34]), "+f"(d[35]), "+f"(d[36]), "+f"(d[37]), "+f"(d[38]), "+f"(d[39]), "+f"(d[40]), "+f"(d[41]), "+f"(d[42]), "+f"(d[43]), "+f"(d[44]), "+f"(d[45]), "+f"(d[46]), "+f"(d[47]), "+f"(d[48]), "+f"(d[49]), "+f"(d[50]), "+f"(d[51]), "+f"(d[52]), "+f"(d[53]), "+f"(d[54]), "+f"(d[55]), "+f"(d[56]), "+f"(d[57]), "+f"(d[58]), "+f"(d[59]), "+f"(d[60]), "+f"(d[61]), "+f"(d[62]), "+f"(d[63]), "+f"(d[64]), "+f"(d[65]), "+f"(d[66]), "+f"(d[67]), "+f"(d[68]), "+f"(d[69]), "+f"(d[70]), "+f"(d[71]), "+f"(d[72]), "+f"(d[73]), "+f"(d[74]), "+f"(d[75]), "+f"(d[76]), "+f"(d[77]), "+f"(d[78]), "+f"(d[79]), "+f"(d[80]), "+f"(d[81]), "+f"(d[82]), "+f"(d[83]), "+f"(d[84]), "+f"(d[85]), "+f"(d[86]), "+f"(d[87]), "+f"(d[88]), "+f"(d[89]), "+f"(d[90]), "+f"(d[91]), "+f"(d[92]), "+f"(d[93]), "+f"(d[94]), "+f"(d[95]), "+f"(d[96]), "+f"(d[97]), "+f"(d[98]), "+f"(d[99]), "+f"(d[100]), "+f"(d[101]), "+f"(d[102]), "+f"(d[103]), "+f"(d[104]), "+f"(d[105]), "+f"(d[106]), "+f"(d[107]), "+f"(d[108]), "+f"(d[109]), "+f"(d[110]), "+f"(d[111]), "+f"(d[112]), "+f"(d[113]), "+f"(d[114]), "+f"(d[115]), "+f"(d[116]), "+f"(d[117]), "+f"(d[118]), "+f"(d[119]), "+f"(d[120]), "+f"(d[121]), "+f"(d[122]), "+f"(d[123]), "+f"(d[124]), "+f"(d[125]), "+f"(d[126]), "+f"(d[127])
    : "l"(da), "l"(db), "r"(scale_d));
}
__device__ __forceinline__ void wgmma_n128(float (&d)[192], uint64_t da, uint64_t db, int scale_d) {
  asm volatile("{\n.reg .pred p;\nsetp.ne.b32 p, %66, 0;\n"
    "wgmma.mma_async.sync.aligned.m64n128k16.f32.bf16.bf16 {%0, %1, %2, %3, %4, %5, %6, %7, %8, %9, %10, %11, %12, %13, %14, %15, %16, %17, %18, %19, %20, %21, %22, %23, %24, %25, %26, %27, %28, %29, %30, %31, %32, %33, %34, %35, %36, %37, %38, %39, %40, %41, %42, %43, %44, %45, %46, %47, %48, %49, %50, %51, %52, %53, %54, %55, %56, %57, %58, %59, %60, %61, %62, %63}, %64, %65, p, 1, 1, 0, 1;\n}\n"
    : "+f"(d[128]), "+f"(d[129]), "+f"(d[130]), "+f"(d[131]), "+f"(d[132]), "+f"(d[133]), "+f"(d[134]), "+f"(d[135]), "+f"(d[136]), "+f"(d[137]), "+f"(d[138]), "+f"(d[139]), "+f"(d[140]), "+f"(d[141]), "+f"(d[142]), "+f"(d[143]), "+f"(d[144]), "+f"(d[145]), "+f"(d[146]), "+f"(d[147]), "+f"(d[148]), "+f"(d[149]), "+f"(d[150]), "+f"(d[151]), "+f"(d[152]), "+f"(d[153]), "+f"(d[154]), "+f"(d[155]), "+f"(d[156]), "+f"(d[157]), "+f"(d[158]), "+f"(d[159]), "+f"(d[160]), "+f"(d[161]), "+f"(d[162]), "+f"(d[163]), "+f"(d[164]), "+f"(d[165]), "+f"(d[166]), "+f"(d[167]), "+f"(d[168]), "+f"(d[169]), "+f"(d[170]), "+f"(d[171]), "+f"(d[172]), "+f"(d[173]), "+f"(d[174]), "+f"(d[175]), "+f"(d[176]), "+f"(d[177]), "+f"(d[178]), "+f"(d[179]), "+f"(d[180]), "+f"(d[181]), "+f"(d[182]), "+f"(d[183]), "+f"(d[184]), "+f"(d[185]), "+f"(d[186]), "+f"(d[187]), "+f"(d[188]), "+f"(d[189]), "+f"(d[190]), "+f"(d[191])
    : "l"(da), "l"(db), "r"(scale_d));
}
__device__ __forceinline__ void wgmma_n256_k(float (&d)[192], uint64_t da, uint64_t db, int scale_d) {
  asm volatile("{\n.reg .pred p;\nsetp.ne.b32 p, %130, 0;\n"
    "wgmma.mma_async.sync.aligned.m64n256k16.f32.bf16.bf16 {%0, %1, %2, %3, %4, %5, %6, %7, %8, %9, %10, %11, %12, %13, %14, %15, %16, %17, %18, %19, %20, %21, %22, %23, %24, %25, %26, %27, %28, %29, %30, %31, %32, %33, %34, %35, %36, %37, %38, %39, %40, %41, %42, %43, %44, %45, %46, %47, %48, %49, %50, %51, %52, %53, %54, %55, %56, %57, %58, %59, %60, %61, %62, %63, %64, %65, %66, %67, %68, %69, %70, %71, %72, %73, %74, %75, %76, %77, %78, %79, %80, %81, %82, %83, %84, %85, %86, %87, %88, %89, %90, %91, %92, %93, %94, %95, %96, %97, %98, %99, %100, %101, %102, %103, %104, %105, %106, %107, %108, %109, %110, %111, %112, %113, %114, %115, %116, %117, %118, %119, %120, %121, %122, %123, %124, %125, %126, %127}, %128, %129, p, 1, 1, 0, 0;\n}\n"
    : "+f"(d[0]), "+f"(d[1]), "+f"(d[2]), "+f"(d[3]), "+f"(d[4]), "+f"(d[5]), "+f"(d[6]), "+f"(d[7]), "+f"(d[8]), "+f"(d[9]), "+f"(d[10]), "+f"(d[11]), "+f"(d[12]), "+f"(d[13]), "+f"(d[14]), "+f"(d[15]), "+f"(d[16]), "+f"(d[17]), "+f"(d[18]), "+f"(d[19]), "+f"(d[20]), "+f"(d[21]), "+f"(d[22]), "+f"(d[23]), "+f"(d[24]), "+f"(d[25]), "+f"(d[26]), "+f"(d[27]), "+f"(d[28]), "+f"(d[29]), "+f"(d[30]), "+f"(d[31]), "+f"(d[32]), "+f"(d[33]), "+f"(d[34]), "+f"(d[35]), "+f"(d[36]), "+f"(d[37]), "+f"(d[38]), "+f"(d[39]), "+f"(d[40]), "+f"(d[41]), "+f"(d[42]), "+f"(d[43]), "+f"(d[44]), "+f"(d[45]), "+f"(d[46]), "+f"(d[47]), "+f"(d[48]), "+f"(d[49]), "+f"(d[50]), "+f"(d[51]), "+f"(d[52]), "+f"(d[53]), "+f"(d[54]), "+f"(d[55]), "+f"(d[56]), "+f"(d[57]), "+f"(d[58]), "+f"(d[59]), "+f"(d[60]), "+f"(d[61]), "+f"(d[62]), "+f"(d[63]), "+f"(d[64]), "+f"(d[65]), "+f"(d[66]), "+f"(d[67]), "+f"(d[68]), "+f"(d[69]), "+f"(d[70]), "+f"(d[71]), "+f"(d[72]), "+f"(d[73]), "+f"(d[74]), "+f"(d[75]), "+f"(d[76]), "+f"(d[77]), "+f"(d[78]), "+f"(d[79]), "+f"(d[80]), "+f"(d[81]), "+f"(d[82]), "+f"(d[83]), "+f"(d[84]), "+f"(d[85]), "+f"(d[86]), "+f"(d[87]), "+f"(d[88]), "+f"(d[89]), "+f"(d[90]), "+f"(d[91]), "+f"(d[92]), "+f"(d[93]), "+f"(d[94]), "+f"(d[95]), "+f"(d[96]), "+f"(d[97]), "+f"(d[98]), "+f"(d[99]), "+f"(d[100]), "+f"(d[101]), "+f"(d[102]), "+f"(d[103]), "+f"(d[104]), "+f"(d[105]), "+f"(d[106]), "+f"(d[107]), "+f"(d[108]), "+f"(d[109]), "+f"(d[110]), "+f"(d[111]), "+f"(d[112]), "+f"(d[113]), "+f"(d[114]), "+f"(d[115]), "+f"(d[116]), "+f"(d[117]), "+f"(d[118]), "+f"(d[119]), "+f"(d[120]), "+f"(d[121]), "+f"(d[122]), "+f"(d[123]), "+f"(d[124]), "+f"(d[125]), "+f"(d[126]), "+f"(d[127])
    : "l"(da), "l"(db), "r"(scale_d));
}
__device__ __forceinline__ void wgmma_n128_k(float (&d)[192], uint64_t da, uint64_t db, int scale_d) {
  asm volatile("{\n.reg .pred p;\nsetp.ne.b32 p, %66, 0;\n"
    "wgmma.mma_async.sync.aligned.m64n128k16.f32.bf16.bf16 {%0, %1, %2, %3, %4, %5, %6, %7, %8, %9, %10, %11, %12, %13, %14, %15, %16, %17, %18, %19, %20, %21, %22, %23, %24, %25, %26, %27, %28, %29, %30, %31, %32, %33, %34, %35, %36, %37, %38, %39, %40, %41, %42, %43, %44, %45, %46, %47, %48, %49, %50, %51, %52, %53, %54, %55, %56, %57, %58, %59, %60, %61, %62, %63}, %64, %65, p, 1, 1, 0, 0;\n}\n"
    : "+f"(d[128]), "+f"(d[129]), "+f"(d[130]), "+f"(d[131]), "+f"(d[132]), "+f"(d[133]), "+f"(d[134]), "+f"(d[135]), "+f"(d[136]), "+f"(d[137]), "+f"(d[138]), "+f"(d[139]), "+f"(d[140]), "+f"(d[141]), "+f"(d[142]), "+f"(d[143]), "+f"(d[144]), "+f"(d[145]), "+f"(d[146]), "+f"(d[147]), "+f"(d[148]), "+f"(d[149]), "+f"(d[150]), "+f"(d[151]), "+f"(d[152]), "+f"(d[153]), "+f"(d[154]), "+f"(d[155]), "+f"(d[156]), "+f"(d[157]), "+f"(d[158]), "+f"(d[159]), "+f"(d[160]), "+f"(d[161]), "+f"(d[162]), "+f"(d[163]), "+f"(d[164]), "+f"(d[165]), "+f"(d[166]), "+f"(d[167]), "+f"(d[168]), "+f"(d[169]), "+f"(d[170]), "+f"(d[171]), "+f"(d[172]), "+f"(d[173]), "+f"(d[174]), "+f"(d[175]), "+f"(d[176]), "+f"(d[177]), "+f"(d[178]), "+f"(d[179]), "+f"(d[180]), "+f"(d[181]), "+f"(d[182]), "+f"(d[183]), "+f"(d[184]), "+f"(d[185]), "+f"(d[186]), "+f"(d[187]), "+f"(d[188]), "+f"(d[189]), "+f"(d[190]), "+f"(d[191])
    : "l"(da), "l"(db), "r"(scale_d));
}
__device__ __forceinline__ void wgmma_n40_tt(float (&d)[20], uint64_t da, uint64_t db, int scale_d) {
  asm volatile("{\n.reg .pred p;\nsetp.ne.b32 p, %22, 0;\n"
    "wgmma.mma_async.sync.aligned.m64n40k16.f32.bf16.bf16 {%0, %1, %2, %3, %4, %5, %6, %7, %8, %9, %10, %11, %12, %13, %14, %15, %16, %17, %18, %19}, %20, %21, p, 1, 1, 1, 1;\n}\n"
    : "+f"(d[0]), "+f"(d[1]), "+f"(d[2]), "+f"(d[3]), "+f"(d[4]), "+f"(d[5]), "+f"(d[6]), "+f"(d[7]), "+f"(d[8]), "+f"(d[9]), "+f"(d[10]), "+f"(d[11]), "+f"(d[12]), "+f"(d[13]), "+f"(d[14]), "+f"(d[15]), "+f"(d[16]), "+f"(d[17]), "+f"(d[18]), "+f"(d[19])
    : "l"(da), "l"(db), "r"(scale_d));
}
__device__ __forceinline__ void wgmma_n40_rs(float (&d)[20], const uint32_t (&a)[4], uint64_t db, int scale_d) {
  asm volatile("{\n.reg .pred p;\nsetp.ne.b32 p, %25, 0;\n"
    "wgmma.mma_async.sync.aligned.m64n40k16.f32.bf16.bf16 {%0, %1, %2, %3, %4, %5, %6, %7, %8, %9, %10, %11, %12, %13, %14, %15, %16, %17, %18, %19}, {%20, %21, %22, %23}, %24, p, 1, 1, 1;\n}\n"
    : "+f"(d[0]), "+f"(d[1]), "+f"(d[2]), "+f"(d[3]), "+f"(d[4]), "+f"(d[5]), "+f"(d[6]), "+f"(d[7]), "+f"(d[8]), "+f"(d[9]), "+f"(d[10]), "+f"(d[11]), "+f"(d[12]), "+f"(d[13]), "+f"(d[14]), "+f"(d[15]), "+f"(d[16]), "+f"(d[17]), "+f"(d[18]), "+f"(d[19])
    : "r"(a[0]), "r"(a[1]), "r"(a[2]), "r"(a[3]), "l"(db), "r"(scale_d));
}
__device__ __forceinline__ void wgmma_n128_0(float (&d)[192], uint64_t da, uint64_t db) {
  asm volatile("{\n.reg .pred p;\nsetp.ne.b32 p, 0, 0;\n"
    "wgmma.mma_async.sync.aligned.m64n128k16.f32.bf16.bf16 {%0, %1, %2, %3, %4, %5, %6, %7, %8, %9, %10, %11, %12, %13, %14, %15, %16, %17, %18, %19, %20, %21, %22, %23, %24, %25, %26, %27, %28, %29, %30, %31, %32, %33, %34, %35, %36, %37, %38, %39, %40, %41, %42, %43, %44, %45, %46, %47, %48, %49, %50, %51, %52, %53, %54, %55, %56, %57, %58, %59, %60, %61, %62, %63}, %64, %65, p, 1, 1, 0, 1;\n}\n"
    : "=f"(d[128]), "=f"(d[129]), "=f"(d[130]), "=f"(d[131]), "=f"(d[132]), "=f"(d[133]), "=f"(d[134]), "=f"(d[135]), "=f"(d[136]), "=f"(d[137]), "=f"(d[138]), "=f"(d[139]), "=f"(d[140]), "=f"(d[141]), "=f"(d[142]), "=f"(d[143]), "=f"(d[144]), "=f"(d[145]), "=f"(d[146]), "=f"(d[147]), "=f"(d[148]), "=f"(d[149]), "=f"(d[150]), "=f"(d[151]), "=f"(d[152]), "=f"(d[153]), "=f"(d[154]), "=f"(d[155]), "=f"(d[156]), "=f"(d[157]), "=f"(d[158]), "=f"(d[159]), "=f"(d[160]), "=f"(d[161]), "=f"(d[162]), "=f"(d[163]), "=f"(d[164]), "=f"(d[165]), "=f"(d[166]), "=f"(d[167]), "=f"(d[168]), "=f"(d[169]), "=f"(d[170]), "=f"(d[171]), "=f"(d[172]), "=f"(d[173]), "=f"(d[174]), "=f"(d[175]), "=f"(d[176]), "=f"(d[177]), "=f"(d[178]), "=f"(d[179]), "=f"(d[180]), "=f"(d[181]), "=f"(d[182]), "=f"(d[183]), "=f"(d[184]), "=f"(d[185]), "=f"(d[186]), "=f"(d[187]), "=f"(d[188]), "=f"(d[189]), "=f"(d[190]), "=f"(d[191])
    : "l"(da), "l"(db));
}
__device__ __forceinline__ void wgmma_n128_rs(float (&d)[192], const uint32_t (&a)[4], uint64_t db, int scale_d) {
  asm volatile("{\n.reg .pred p;\nsetp.ne.b32 p, %69, 0;\n"
    "wgmma.mma_async.sync.aligned.m64n128k16.f32.bf16.bf16 {%0, %1, %2, %3, %4, %5, %6, %7, %8, %9, %10, %11, %12, %13, %14, %15, %16, %17, %18, %19, %20, %21, %22, %23, %24, %25, %26, %27, %28, %29, %30, %31, %32, %33, %34, %35, %36, %37, %38, %39, %40, %41, %42, %43, %44, %45, %46, %47, %48, %49, %50, %51, %52, %53, %54, %55, %56, %57, %58, %59, %60, %61, %62, %63}, {%64, %65, %66, %67}, %68, p, 1, 1, 1;\n}\n"
    : "+f"(d[128]), "+f"(d[129]), "+f"(d[130]), "+f"(d[131]), "+f"(d[132]), "+f"(d[133]), "+f"(d[134]), "+f"(d[135]), "+f"(d[136]), "+f"(d[137]), "+f"(d[138]), "+f"(d[139]), "+f"(d[140]), "+f"(d[141]), "+f"(d[142]), "+f"(d[143]), "+f"(d[144]), "+f"(d[145]), "+f"(d[146]), "+f"(d[147]), "+f"(d[148]), "+f"(d[149]), "+f"(d[150]), "+f"(d[151]), "+f"(d[152]), "+f"(d[153]), "+f"(d[154]), "+f"(d[155]), "+f"(d[156]), "+f"(d[157]), "+f"(d[158]), "+f"(d[159]), "+f"(d[160]), "+f"(d[161]), "+f"(d[162]), "+f"(d[163]), "+f"(d[164]), "+f"(d[165]), "+f"(d[166]), "+f"(d[167]), "+f"(d[168]), "+f"(d[169]), "+f"(d[170]), "+f"(d[171]), "+f"(d[172]), "+f"(d[173]), "+f"(d[174]), "+f"(d[175]), "+f"(d[176]), "+f"(d[177]), "+f"(d[178]), "+f"(d[179]), "+f"(d[180]), "+f"(d[181]), "+f"(d[182]), "+f"(d[183]), "+f"(d[184]), "+f"(d[185]), "+f"(d[186]), "+f"(d[187]), "+f"(d[188]), "+f"(d[189]), "+f"(d[190]), "+f"(d[191])
    : "r"(a[0]), "r"(a[1]), "r"(a[2]), "r"(a[3]), "l"(db), "r"(scale_d));
}
__device__ __forceinline__ void wgmma_n32_0(float (&d)[16], uint64_t da, uint64_t db) {
  asm volatile("{\n.reg .pred p;\nsetp.ne.b32 p, 0, 0;\n"
    "wgmma.mma_async.sync.aligned.m64n32k16.f32.bf16.bf16 {%0, %1, %2, %3, %4, %5, %6, %7, %8, %9, %10, %11, %12, %13, %14, %15}, %16, %17, p, 1, 1, 0, 1;\n}\n"
    : "=f"(d[0]), "=f"(d[1]), "=f"(d[2]), "=f"(d[3]), "=f"(d[4]), "=f"(d[5]), "=f"(d[6]), "=f"(d[7]), "=f"(d[8]), "=f"(d[9]), "=f"(d[10]), "=f"(d[11]), "=f"(d[12]), "=f"(d[13]), "=f"(d[14]), "=f"(d[15])
    : "l"(da), "l"(db));
}
__device__ __forceinline__ void wgmma_n32(float (&d)[16], uint64_t da, uint64_t db, int scale_d) {
  asm volatile("{\n.reg .pred p;\nsetp.ne.b32 p, %18, 0;\n"
    "wgmma.mma_async.sync.aligned.m64n32k16.f32.bf16.bf16 {%0, %1, %2, %3, %4, %5, %6, %7, %8, %9, %10, %11, %12, %13, %14, %15}, %16, %17, p, 1, 1, 0, 1;\n}\n"
    : "+f"(d[0]), "+f"(d[1]), "+f"(d[2]), "+f"(d[3]), "+f"(d[4]), "+f"(d[5]), "+f"(d[6]), "+f"(d[7]), "+f"(d[8]), "+f"(d[9]), "+f"(d[10]), "+f"(d[11]), "+f"(d[12]), "+f"(d[13]), "+f"(d[14]), "+f"(d[15])
    : "l"(da), "l"(db), "r"(scale_d));
}
__device__ __forceinline__ void wgmma_n8_t(float (&d)[4], uint64_t da, uint64_t db, int scale_d) {
  asm volatile("{\n.reg .pred p;\nsetp.ne.b32 p, %6, 0;\n"
    "wgmma.mma_async.sync.aligned.m64n8k16.f32.bf16.bf16 {%0, %1, %2, %3}, %4, %5, p, 1, 1, 1, 0;\n}\n"
    : "+f"(d[0]), "+f"(d[1]), "+f"(d[2]), "+f"(d[3])
    : "l"(da), "l"(db), "r"(scale_d));
}
__device__ __forceinline__ void wgmma_n128_rs0(float (&d)[192], const uint32_t (&a)[4], uint64_t db) {
  asm volatile("{\n.reg .pred p;\nsetp.ne.b32 p, 0, 0;\n"
    "wgmma.mma_async.sync.aligned.m64n128k16.f32.bf16.bf16 {%0, %1, %2, %3, %4, %5, %6, %7, %8, %9, %10, %11, %12, %13, %14, %15, %16, %17, %18, %19, %20, %21, %22, %23, %24, %25, %26, %27, %28, %29, %30, %31, %32, %33, %34, %35, %36, %37, %38, %39, %40, %41, %42, %43, %44, %45, %46, %47, %48, %49, %50, %51, %52, %53, %54, %55, %56, %57, %58, %59, %60, %61, %62, %63}, {%64, %65, %66, %67}, %68, p, 1, 1, 1;\n}\n"
    : "=f"(d[128]), "=f"(d[129]), "=f"(d[130]), "=f"(d[131]), "=f"(d[132]), "=f"(d[133]), "=f"(d[134]), "=f"(d[135]), "=f"(d[136]), "=f"(d[137]), "=f"(d[138]), "=f"(d[139]), "=f"(d[140]), "=f"(d[141]), "=f"(d[142]), "=f"(d[143]), "=f"(d[144]), "=f"(d[145]), "=f"(d[146]), "=f"(d[147]), "=f"(d[148]), "=f"(d[149]), "=f"(d[150]), "=f"(d[151]), "=f"(d[152]), "=f"(d[153]), "=f"(d[154]), "=f"(d[155]), "=f"(d[156]), "=f"(d[157]), "=f"(d[158]), "=f"(d[159]), "=f"(d[160]), "=f"(d[161]), "=f"(d[162]), "=f"(d[163]), "=f"(d[164]), "=f"(d[165]), "=f"(d[166]), "=f"(d[167]), "=f"(d[168]), "=f"(d[169]), "=f"(d[170]), "=f"(d[171]), "=f"(d[172]), "=f"(d[173]), "=f"(d[174]), "=f"(d[175]), "=f"(d[176]), "=f"(d[177]), "=f"(d[178]), "=f"(d[179]), "=f"(d[180]), "=f"(d[181]), "=f"(d[182]), "=f"(d[183]), "=f"(d[184]), "=f"(d[185]), "=f"(d[186]), "=f"(d[187]), "=f"(d[188]), "=f"(d[189]), "=f"(d[190]), "=f"(d[191])
    : "r"(a[0]), "r"(a[1]), "r"(a[2]), "r"(a[3]), "l"(db));
}
__device__ __forceinline__ void wgmma_n256_rs(float (&d)[192], const uint32_t (&a)[4], uint64_t db, int scale_d) {
  asm volatile("{\n.reg .pred p;\nsetp.ne.b32 p, %133, 0;\n"
    "wgmma.mma_async.sync.aligned.m64n256k16.f32.bf16.bf16 {%0, %1, %2, %3, %4, %5, %6, %7, %8, %9, %10, %11, %12, %13, %14, %15, %16, %17, %18, %19, %20, %21, %22, %23, %24, %25, %26, %27, %28, %29, %30, %31, %32, %33, %34, %35, %36, %37, %38, %39, %40, %41, %42, %43, %44, %45, %46, %47, %48, %49, %50, %51, %52, %53, %54, %55, %56, %57, %58, %59, %60, %61, %62, %63, %64, %65, %66, %67, %68, %69, %70, %71, %72, %73, %74, %75, %76, %77, %78, %79, %80, %81, %82, %83, %84, %85, %86, %87, %88, %89, %90, %91, %92, %93, %94, %95, %96, %97, %98, %99, %100, %101, %102, %103, %104, %105, %106, %107, %108, %109, %110, %111, %112, %113, %114, %115, %116, %117, %118, %119, %120, %121, %122, %123, %124, %125, %126, %127}, {%128, %129, %130, %131}, %132, p, 1, 1, 1;\n}\n"
    : "+f"(d[0]), "+f"(d[1]), "+f"(d[2]), "+f"(d[3]), "+f"(d[4]), "+f"(d[5]), "+f"(d[6]), "+f"(d[7]), "+f"(d[8]), "+f"(d[9]), "+f"(d[10]), "+f"(d[11]), "+f"(d[12]), "+f"(d[13]), "+f"(d[14]), "+f"(d[15]), "+f"(d[16]), "+f"(d[17]), "+f"(d[18]), "+f"(d[19]), "+f"(d[20]), "+f"(d[21]), "+f"(d[22]), "+f"(d[23]), "+f"(d[24]), "+f"(d[25]), "+f"(d[26]), "+f"(d[27]), "+f"(d[28]), "+f"(d[29]), "+f"(d[30]), "+f"(d[31]), "+f"(d[32]), "+f"(d[33]), "+f"(d[34]), "+f"(d[35]), "+f"(d[36]), "+f"(d[37]), "+f"(d[38]), "+f"(d[39]), "+f"(d[40]), "+f"(d[41]), "+f"(d[42]), "+f"(d[43]), "+f"(d[44]), "+f"(d[45]), "+f"(d[46]), "+f"(d[47]), "+f"(d[48]), "+f"(d[49]), "+f"(d[50]), "+f"(d[51]), "+f"(d[52]), "+f"(d[53]), "+f"(d[54]), "+f"(d[55]), "+f"(d[56]), "+f"(d[57]), "+f"(d[58]), "+f"(d[59]), "+f"(d[60]), "+f"(d[61]), "+f"(d[62]), "+f"(d[63]), "+f"(d[64]), "+f"(d[65]), "+f"(d[66]), "+f"(d[67]), "+f"(d[68]), "+f"(d[69]), "+f"(d[70]), "+f"(d[71]), "+f"(d[72]), "+f"(d[73]), "+f"(d[74]), "+f"(d[75]), "+f"(d[76]), "+f"(d[77]), "+f"(d[78]), "+f"(d[79]), "+f"(d[80]), "+f"(d[81]), "+f"(d[82]), "+f"(d[83]), "+f"(d[84]), "+f"(d[85]), "+f"(d[86]), "+f"(d[87]), "+f"(d[88]), "+f"(d[89]), "+f"(d[90]), "+f"(d[91]), "+f"(d[92]), "+f"(d[93]), "+f"(d[94]), "+f"(d[95]), "+f"(d[96]), "+f"(d[97]), "+f"(d[98]), "+f"(d[99]), "+f"(d[100]), "+f"(d[101]), "+f"(d[102]), "+f"(d[103]), "+f"(d[104]), "+f"(d[105]), "+f"(d[106]), "+f"(d[107]), "+f"(d[108]), "+f"(d[109]), "+f"(d[110]), "+f"(d[111]), "+f"(d[112]), "+f"(d[113]), "+f"(d[114]), "+f"(d[115]), "+f"(d[116]), "+f"(d[117]), "+f"(d[118]), "+f"(d[119]), "+f"(d[120]), "+f"(d[121]), "+f"(d[122]), "+f"(d[123]), "+f"(d[124]), "+f"(d[125]), "+f"(d[126]), "+f"(d[127])
    : "r"(a[0]), "r"(a[1]), "r"(a[2]), "r"(a[3]), "l"(db), "r"(scale_d));
}
__device__ __forceinline__ void wgmma_n256_rs0(float (&d)[192], const uint32_t (&a)[4], uint64_t db) {
  asm volatile("{\n.reg .pred p;\nsetp.ne.b32 p, 0, 0;\n"
    "wgmma.mma_async.sync.aligned.m64n256k16.f32.bf16.bf16 {%0, %1, %2, %3, %4, %5, %6, %7, %8, %9, %10, %11, %12, %13, %14, %15, %16, %17, %18, %19, %20, %21, %22, %23, %24, %25, %26, %27, %28, %29, %30, %31, %32, %33, %34, %35, %36, %37, %38, %39, %40, %41, %42, %43, %44, %45, %46, %47, %48, %49, %50, %51, %52, %53, %54, %55, %56, %57, %58, %59, %60, %61, %62, %63, %64, %65, %66, %67, %68, %69, %70, %71, %72, %73, %74, %75, %76, %77, %78, %79, %80, %81, %82, %83, %84, %85, %86, %87, %88, %89, %90, %91, %92, %93, %94, %95, %96, %97, %98, %99, %100, %101, %102, %103, %104, %105, %106, %107, %108, %109, %110, %111, %112, %113, %114, %115, %116, %117, %118, %119, %120, %121, %122, %123, %124, %125, %126, %127}, {%128, %129, %130, %131}, %132, p, 1, 1, 1;\n}\n"
    : "=f"(d[0]), "=f"(d[1]), "=f"(d[2]), "=f"(d[3]), "=f"(d[4]), "=f"(d[5]), "=f"(d[6]), "=f"(d[7]), "=f"(d[8]), "=f"(d[9]), "=f"(d[10]), "=f"(d[11]), "=f"(d[12]), "=f"(d[13]), "=f"(d[14]), "=f"(d[15]), "=f"(d[16]), "=f"(d[17]), "=f"(d[18]), "=f"(d[19]), "=f"(d[20]), "=f"(d[21]), "=f"(d[22]), "=f"(d[23]), "=f"(d[24]), "=f"(d[25]), "=f"(d[26]), "=f"(d[27]), "=f"(d[28]), "=f"(d[29]), "=f"(d[30]), "=f"(d[31]), "=f"(d[32]), "=f"(d[33]), "=f"(d[34]), "=f"(d[35]), "=f"(d[36]), "=f"(d[37]), "=f"(d[38]), "=f"(d[39]), "=f"(d[40]), "=f"(d[41]), "=f"(d[42]), "=f"(d[43]), "=f"(d[44]), "=f"(d[45]), "=f"(d[46]), "=f"(d[47]), "=f"(d[48]), "=f"(d[49]), "=f"(d[50]), "=f"(d[51]), "=f"(d[52]), "=f"(d[53]), "=f"(d[54]), "=f"(d[55]), "=f"(d[56]), "=f"(d[57]), "=f"(d[58]), "=f"(d[59]), "=f"(d[60]), "=f"(d[61]), "=f"(d[62]), "=f"(d[63]), "=f"(d[64]), "=f"(d[65]), "=f"(d[66]), "=f"(d[67]), "=f"(d[68]), "=f"(d[69]), "=f"(d[70]), "=f"(d[71]), "=f"(d[72]), "=f"(d[73]), "=f"(d[74]), "=f"(d[75]), "=f"(d[76]), "=f"(d[77]), "=f"(d[78]), "=f"(d[79]), "=f"(d[80]), "=f"(d[81]), "=f"(d[82]), "=f"(d[83]), "=f"(d[84]), "=f"(d[85]), "=f"(d[86]), "=f"(d[87]), "=f"(d[88]), "=f"(d[89]), "=f"(d[90]), "=f"(d[91]), "=f"(d[92]), "=f"(d[93]), "=f"(d[94]), "=f"(d[95]), "=f"(d[96]), "=f"(d[97]), "=f"(d[98]), "=f"(d[99]), "=f"(d[100]), "=f"(d[101]), "=f"(d[102]), "=f"(d[103]), "=f"(d[104]), "=f"(d[105]), "=f"(d[106]), "=f"(d[107]), "=f"(d[108]), "=f"(d[109]), "=f"(d[110]), "=f"(d[111]), "=f"(d[112]), "=f"(d[113]), "=f"(d[114]), "=f"(d[115]), "=f"(d[116]), "=f"(d[117]), "=f"(d[118]), "=f"(d[119]), "=f"(d[120]), "=f"(d[121]), "=f"(d[122]), "=f"(d[123]), "=f"(d[124]), "=f"(d[125]), "=f"(d[126]), "=f"(d[127])
    : "r"(a[0]), "r"(a[1]), "r"(a[2]), "r"(a[3]), "l"(db));
}

constexpr int SLOT = 16384;
constexpr int VB = 4 * SLOT, PH = 0, XS = 6;
constexpr int SM_SD = 13 * SLOT;
constexpr int SM_BAR = SM_SD + 8192;
constexpr int SM_RS = SM_BAR + 1024;
constexpr int SM_AP = SM_RS + 640;
constexpr int SM_BP = SM_AP + 2048;
constexpr int SM_EPOCH = SM_BP + 6144;
constexpr int SM_TOTAL = SM_EPOCH + 16;
constexpr int FM = 0, FT = 16, FW = 30, CM = 46, CT = 62, CW = 76, B_EF = 92, B_STAT = 93, B_KVF = 94, B_HALO = 95,
              B_KVDONE = 96, B_OH0 = 97, B_OH1 = 98, B_XH0 = 99, B_XDONE = 100, B_WFD = 101, B_XT = 102, B_OF0 = 103, B_KVF1 = 104, B_KVS = 105, B_RAW = 106  , B_X0 = 108, B_KVS0 = 109;
constexpr uint64_t BAR_LG = 0x00043333330004ull;
#define BA(i) (bar + (i) * 8)
#define REL2(i) release2c(SB0 + SM_BAR + (i) * 8)
constexpr int NF = 3, ND = 13, NR = 0, NWOP = 48, NAOP = 38;
constexpr bool EF_USED = false;
constexpr uint64_t TL_A = 0x6278627862786ull, TL_B = 0xa9c3ba9c3ba9cull, WO_A = 0x76b24038b51403ffull, WO_B = 0x8c5a197c6a297c8bull;
__constant__ uint32_t c_wop[NWOP + 1] = {0xeb0009, 0x186b8000, 0x6c0112, 0x1aec011a, 0x6c8224, 0x22ec822b, 0x18170330, 0x18178442, 0x18180554, 0x18188660, 0x18190772, 0x18198884, 0x181a0990, 0x181a8aa2, 0x181b0bb4, 0x181b8cc0, 0xaed10fc, 0xa9711e9, 0x181c0dd2, 0xa9792da, 0x129813cb, 0x181c8ee4, 0x181d0ff0, 0x109d94b3, 0x109f15ac, 0x109f9699, 0x10a0178a, 0x10a0987b, 0x10a11963, 0x10a19a5c, 0x10a21b49, 0x10a29c3a, 0x9231e0b, 0x9239f18, 0x1124202c, 0x13242137, 0x1124a249, 0x1324a352, 0x1125246a, 0x13252576, 0x1127268c, 0x1127a797, 0x112828a9, 0x1128a9b1, 0x11292aca, 0x13292bd5, 0x112a2cec, 0x132a2df8, 0};
__constant__ uint32_t c_aop[NAOP + 1] = {0x6d8228, 0x170336, 0x178447, 0x180558, 0x188666, 0x190777, 0x198888, 0x1a0996, 0x1a8aa7, 0x1b0bb8, 0x1b8cc6, 0x1c0dd7, 0x1c8ee8, 0x1d0ff6, 0x1d93c2, 0x1f14b6, 0x1f95a8, 0x201697, 0x209782, 0x211876, 0x219968, 0x221a57, 0x229b42, 0x231c36, 0xa3a023, 0xb12130, 0x2b12244, 0x2b12351, 0x2b12465, 0xa6257b, 0xa6a688, 0xa72793, 0xa7a8a0, 0xa829b4, 0xa8aac2, 0xa9abdb, 0x2a9ace6, 0xaaadf7, 0};
__constant__ uint32_t c_map[64] = {4, 5, 6, 7, 0, 16, 32, 48, 64, 80, 96, 112, 1, 17, 33, 49, 65, 81, 97, 113, 2, 18, 34, 50, 66, 82, 98, 114, 3, 19, 35, 51, 67, 83, 99, 115, 20, 36, 52, 68, 84, 100, 116, 21, 37, 53, 69, 85, 101, 117, 22, 38, 54, 70, 86, 102, 118, 23, 39, 55, 71, 87, 103, 119};
enum { MAP_WF = 0, MAP_WA = 2, MAP_WB = 4, MAP_WOA = 6, MAP_WOB = 8, MAP_X0 = 10, MAP_X = 11, MAP_O = 12, MAP_PHI = 13, NMAP = 14 };
struct Maps { CUtensorMap m[NMAP]; };

#define PL 2
#define PROFL(a, b)
#define SUBS 16
#define CHW 4
#define SUBS1 16
#define XRAT 10
#define XRN 4
#define BT1 1
#define ST1 8
#define X0AT 1
#define W1DL 400
#define SKA 0
#define SKB 0
#define BPRE 0
#define XST 0
#define WH 4
#define PFM 3
#define PFS 2
#define NLAYERS 4
constexpr float L2E = 1.4426950408889634f;

#define D128(lo) desc64(lo, 0x40000040u)
struct Ctx { uint32_t zero, boff; const bf16* x0; bf16* out; };
#define BLK_CTX() \
  uint32_t bid_; asm volatile("mov.u32 %0, %%ctaid.x;" : "=r"(bid_)); \
  bid_ -= c.boff; \
  const uint32_t gr_ = c_map[bid_ >> 1]; \
  const int cr = bid_ & 1, g = gr_ & 7, rb = (gr_ >> 3) + cr, m0 = rb * 128; \
  const uint32_t sb = SB0 + (cr << 24); \
  const uint32_t bar = sb + SM_BAR; \
  (void)cr; (void)g; (void)rb; (void)m0; (void)bar;
extern __shared__ uint8_t smem_raw[];
constexpr uint32_t SB0 = 1024;

#define PHASE_CTX() \
  BLK_CTX(); \
  int tid_ = threadIdx.x; asm volatile("" : "+r"(tid_)); \
  const int lane = tid_ & 31, cw = (tid_ >> 5) - 4, wg = cw >> 2, wq = cw & 3, gq = lane >> 2, t = lane & 3, wrow0 = cw * 16; \
  const int lrow = (lane & 7) + ((lane >> 3) & 1) * 8, lchk = lane >> 4; \
  const bool elected = (tid_ & 127) == 0; \
  const uint32_t rowo = (wrow0 + lrow) * 128, X = (lchk ^ (lane & 7)) << 4; \
  const uint32_t Y = (wrow0 + (lane & 7)) * 128 + (((lane >> 3) ^ (lane & 7)) << 4); \
  const size_t gfr = (size_t)(m0 + wrow0 + gq) * D_ + g * 128 + 8 * t; \
  (void)bar; (void)wq; (void)gq; (void)lrow; (void)lchk; (void)elected; (void)wrow0; (void)wg; (void)rowo; (void)X; (void)t; (void)Y; (void)gfr;
#define MMA_CTX() \
  const uint32_t wu = __shfl_sync(0xffffffffu, wg, 0); \
  const uint32_t dA0 = ((SB0 >> 4) | (1u << 16)) + wu * 512, dB0 = (SB0 >> 4) | (512u << 16); \
  const uint32_t par = layer & 1;

__device__ __forceinline__ void slab_out_half(uint32_t slot, bf16* dst, int wrow0, int lane) {
  const int r0 = lane >> 3, ch = lane & 7;
  const uint32_t src = slot + (wrow0 + r0) * 128;
  uint4 v[4];
#pragma unroll
  for (int i = 0; i < 4; ++i) v[i] = lds128(src + i * 512 + (((ch ^ (4 * i + r0)) & 7) << 4));
  dst += (size_t)(wrow0 + r0) * D_ + ch * 8;
#pragma unroll
  for (int i = 0; i < 4; ++i) *reinterpret_cast<uint4*>(dst + (size_t)i * 4 * D_) = v[i];
}

__device__ __forceinline__ void consumer(const Ctx& c) {
  float acc[192];
  uint32_t xf[4][4];
  uint32_t xp[8][4];
  {
    PHASE_CTX();
    const unsigned int epoch = ld_relaxed(&g_epoch);
    PROFT(tid_ == 128, 0);
    const uint32_t wu = __shfl_sync(0xffffffffu, wg, 0);
    if (tid_ < 128 + 8) sts128(sb + SM_AP + lane * 16, make_uint4(0x3F803F80u, 0x3F803F80u, 0x3F803F80u, 0x3F803F80u));
#pragma unroll 1
    for (int it = 0; it < 2; ++it) {
      float p[4][16];
      mbar_wait(BA(B_RAW + it), 0);
      PROFT(tid_ == 128, it ? 15 : 2);
      const uint32_t da = ((SB0 >> 4) | (1u << 16)) + (wu ? 9 + it : 2 * it) * 1024, db = (SB0 + SM_SD) >> 4;
      wgmma_fence();
#pragma unroll
      for (int h = 0; h < 4; ++h) wgmma_n32_0(p[h], D128(da + (h >> 1) * 512 + (h & 1) * 4), desc64(db + h * 128, 0x80000020u));
#pragma unroll
      for (int h = 0; h < 4; ++h) wgmma_n32(p[h], D128(da + (h >> 1) * 512 + (h & 1) * 4 + 2), desc64(db + h * 128 + 64, 0x80000020u), 1);
      wgmma_commit();
      wgmma_wait<0>();
#pragma unroll
      for (int i = 0; i < 64; ++i) asm volatile("" : "+f"(p[i >> 4][i & 15]) :: "memory");
      const uint32_t base = sb + (wg ? 9 + it : 2 * it) * SLOT + (wq * 16 + gq) * 128;
      uint32_t w[4][4][2];
#pragma unroll
      for (int i = 0; i < 32; ++i) w[i >> 3][(i >> 1) & 3][i & 1] = pack_bf16(p[i >> 3][2 * (i & 7)], p[i >> 3][2 * (i & 7) + 1]);
      if (wu) {
#pragma unroll
        for (int i = 0; i < 8; ++i)
          sts128(base + (i >> 2) * 8192 + (i & 1) * 1024 + (((((i >> 1) & 1) * 4 + t) ^ gq) << 4), make_uint4(w[i >> 1][0][i & 1], w[i >> 1][1][i & 1], w[i >> 1][2][i & 1], w[i >> 1][3][i & 1]));
      } else {
#pragma unroll
        for (int i = 0; i < 16; ++i)
          sts64(base + (i >> 3) * 8192 + (i & 1) * 1024 + ((((t & 1) * 4 + ((i >> 1) & 3)) ^ gq) << 4) + (t >> 1) * 8, w[(i >> 3) * 2][(i >> 1) & 3][i & 1], w[(i >> 3) * 2 + 1][(i >> 1) & 3][i & 1]);
      }
      fence_async_smem();
      __syncwarp();
      if (it == cr && lane == 0) mbar_arrive(BA(B_WFD));
    }
    if (tid_ == 128) sts_f(sb + SM_EPOCH, __uint_as_float(epoch & 1));
#pragma unroll
    for (int i = 0; i < 32; ++i) xp[i >> 2][i & 3] = 0u;
    nbar<1, 256>();
    PROFT(tid_ == 128, 13);
    mbar_wait(BA(FM + cr), 0);
    float cs[3][4];
    wgmma_fence();
#pragma unroll
    for (int ks = 0; ks < 4; ++ks)
#pragma unroll
      for (int i = 0; i < 3; ++i) {
        const uint32_t bx = (i == 0 ? 2 * cr * 1024 : i == 1 ? (2 * cr + 1) * 1024 : (9 + cr) * 1024) + wu * 512;
        wgmma_n8_t(cs[i], D128(((SB0 >> 4) | (512u << 16)) + bx + ks * 128), desc64((SB0 + SM_AP) >> 4, 0), ks != 0);
      }
    wgmma_commit();
    mbar_wait(BA(FM), 0);
#pragma unroll
    for (int k = 0; k < 4; ++k) ldsm_x4(xf[k][0], xf[k][1], xf[k][2], xf[k][3], sb + XS * SLOT + rowo + (X ^ (k << 5)));
    wgmma_wait<0>();
#pragma unroll
    for (int i = 0; i < 12; ++i) asm volatile("" : "+f"(cs[i >> 2][i & 3]) :: "memory");
    if (t < 2) {
#pragma unroll
      for (int i = 0; i < 3; ++i) red_add1(g_cs + (epoch & 1) * 6144 + g * 384 + i * 128 + wg * 64 + wq * 16 + gq + t * 8, t ? cs[i][2] : cs[i][0]);
    }
    PROFT(tid_ == 128, 14);
  }
#pragma unroll 1
  for (int layer = 0;; ++layer) {
    {
      wgmma_fence();
      wgmma_n256_rs0(acc, xf[0], D128((SB0 >> 4) | (512u << 16)));
#pragma unroll
      for (int k = 1; k < 4; ++k) wgmma_n256_rs(acc, xf[k], D128(((SB0 >> 4) | (512u << 16)) + k * 128), 1);
      wgmma_commit();
      PHASE_CTX();
      MMA_CTX();
      {
        const uint32_t ep = __float_as_uint(lds_f(sb + SM_EPOCH));
        if (layer == 0) {
          mbar_wait(BA(B_X0), 0);
#pragma unroll
          for (int i = 0; i < 8; ++i) ldsm_x4(xp[i][0], xp[i][1], xp[i][2], xp[i][3], sb + (11 + (i >> 2)) * SLOT + (Y ^ ((i & 2) << 5)) + (i & 1) * 1024);
          if (lane == ((xp[0][0] ^ xp[1][0] ^ xp[2][0] ^ xp[3][0] ^ xp[7][0]) & c.zero)) REL2(B_XT);
        } else {
#pragma unroll
          for (int i = 0; i < 8; ++i) stsm_x4(sb + (XS + (i >> 2)) * SLOT + (Y ^ ((i & 2) << 5)) + (i & 1) * 1024, xp[i][0], xp[i][1], xp[i][2], xp[i][3]);
        }
        float s0 = 0.f, s1 = 0.f, q0 = 0.f, q1 = 0.f;
        auto stats = [&](int j0, int j1) {
#pragma unroll
          for (int j = j0; j < j1; ++j) {
            const uint32_t u0 = xp[(j >> 2) * 2][j & 3], u1 = xp[(j >> 2) * 2 + 1][j & 3];
            s0 += bf_lo(u0) + bf_hi(u0); s1 += bf_lo(u1) + bf_hi(u1);
            q0 = fmaf(bf_lo(u0), bf_lo(u0), fmaf(bf_hi(u0), bf_hi(u0), q0)); q1 = fmaf(bf_lo(u1), bf_lo(u1), fmaf(bf_hi(u1), bf_hi(u1), q1));
          }
        };
        stats(0, ST1);
        fence_async_smem();
        nbar_dyn(3 + wu + (__float_as_uint(s0 + s1 + q0 + q1) & c.zero), 128);
        mbar_wait(BA(FM + 1), par);
        wgmma_fence();
#pragma unroll
        for (int k = 0; k < 4; ++k) wgmma_n256(acc, D128(dA0 + (XS + 1) * 1024 + k * 2), D128(dB0 + 2048 + k * 128), 1);
        wgmma_commit();
        wgmma_wait<1>();
#pragma unroll
        for (int i = 4; i < 8; ++i) stg128_p(layer, g_x + gfr + (i & 1) * 8 * D_ + (i >> 1) * 32, xp[i][0], xp[i][1], xp[i][2], xp[i][3]);
        {
          uint32_t zc; asm volatile("mov.u32 %0, %%clock;" : "=r"(zc) :: "memory");
          q0 += __uint_as_float(zc & c.zero); q1 += __uint_as_float(zc & c.zero); s0 += __uint_as_float(zc & c.zero); s1 += __uint_as_float(zc & c.zero);
        }
        stats(ST1, 16);
        wgmma_fence();
        wgmma_n128_0(acc, D128(dA0 + XS * 1024), D128(dB0 + 9 * 1024));
#pragma unroll
        for (int k = 1; k < 4; ++k) wgmma_n128(acc, D128(dA0 + XS * 1024 + k * 2), D128(dB0 + 9 * 1024 + k * 128), 1);
        wgmma_commit();
        const bool od = t & 1;
        float sa = od ? s1 : s0, qa = od ? q1 : q0;
        sa += __shfl_xor_sync(0xffffffffu, od ? s0 : s1, 1);
        qa += __shfl_xor_sync(0xffffffffu, od ? q0 : q1, 1);
        wgmma_fence();
#pragma unroll
        for (int k = 0; k < 4; ++k) wgmma_n128(acc, D128(dA0 + (XS + 1) * 1024 + k * 2), D128(dB0 + 10 * 1024 + k * 128), 1);
        wgmma_commit();
        sa += __shfl_xor_sync(0xffffffffu, sa, 2);
        qa += __shfl_xor_sync(0xffffffffu, qa, 2);
        red_add2_p(t < 2, reinterpret_cast<float*>(g_stats + (ep * 4 + layer) * S_ + m0 + wrow0 + gq + t * 8), sa, qa);
        __syncwarp();
        if (lane == 0) mbar_arrive(BA(B_XDONE));
        wgmma_wait<1>();
        if (elected) REL2(CM);
      }
      uint32_t s = 2;
#pragma unroll 1
      for (int i = 2; i < NF; ++i) {
        PROFL(tid_ == 128 && layer == PL + 1, 244 + 2 * i);
        mbar_wait(BA(FM + i), par);
        PROFL(tid_ == 128 && layer == PL + 1, 245 + 2 * i);
        const uint32_t da = dA0 + (XS + s) * 1024, dk = dB0 + s * 2048, dq = dB0 + (9 + s) * 1024;
        wgmma_fence();
#pragma unroll
        for (int k = 0; k < 4; ++k) wgmma_n128(acc, D128(da + k * 2), D128(dq + k * 128), 1);
        wgmma_commit();
        wgmma_wait<1>();
        if (elected) REL2(CM + i - 1);
        wgmma_fence();
#pragma unroll
        for (int k = 0; k < 4; ++k) wgmma_n256(acc, D128(da + k * 2), D128(dk + k * 128), 1);
        wgmma_commit();
        if (++s == 3) s = 0;
      }
#pragma unroll 1
      for (int i = NF; i < 15; ++i) {
        mbar_wait(BA(FM + i), par);
        const uint32_t da = dA0 + (XS + s) * 1024, dk = dB0 + s * 2048;
        wgmma_fence();
#pragma unroll
        for (int k = 0; k < 4; ++k) wgmma_n256(acc, D128(da + k * 2), D128(dk + k * 128), 1);
        wgmma_commit();
        wgmma_wait<1>();
        if (elected) REL2(CM + i - 1);
        if (++s == 3) s = 0;
      }
      {
        const uint64_t dap = desc64(((SB0 + SM_AP) >> 4) + wu * 64, 8), dbp = make_desc_ns(SB0 + SM_BP, 0, 128);
        mbar_wait(BA(B_STAT), par);
        mbar_wait(BA(FM + 15), par);
        PROFT(tid_ == 128, layer * 16 + 9);
        wgmma_fence();
        wgmma_n256_k(acc, dap, dbp, 1);
#pragma unroll
        for (int k = 0; k < 4; ++k) wgmma_n256(acc, D128(dA0 + XS * 1024 + k * 2), D128(dB0 + k * 128), 1);
        wgmma_commit();
        wgmma_wait<1>();
        if (elected) REL2(CM + 14);
        mbar_wait(BA(FT), par);
        wgmma_fence();
        wgmma_n128_k(acc, dap, dbp + 256, 1);
#pragma unroll
        for (int k = 0; k < 4; ++k) wgmma_n128(acc, D128(dA0 + (uint32_t)(TL_A & 15) * 1024 + k * 2), D128(dB0 + (uint32_t)(TL_B & 15) * 1024 + k * 128), 1);
        wgmma_commit();
        wgmma_wait<1>();
        if (elected) REL2(CM + 15);
#pragma unroll
        for (int i = 0; i < 128; ++i) asm volatile("" : "+f"(acc[i]) :: "memory");
      }
    }
    uint32_t of[8][4], o1[4][4];
    {
      PHASE_CTX();
      MMA_CTX();
      PROFT(tid_ == 128, layer * 16 + 1);
      PROFT(lane == 0 && layer == PL, 192 + cw);
      PROFT(tid_ == 128 && layer == PL, 160);
      uint64_t ta = (TL_A >> 4), tw = TL_B >> 4;
      uint32_t da, db, dz = dA0;
      auto sub = [&](int n) {
        const int j = n >> 2, k = n & 3;
        if (k == 0) {
          dz += c.zero;
          da = dz + ((uint32_t)ta & 15) * 1024; db = dB0 + ((uint32_t)tw & 15) * 1024;
          ta >>= 4; tw >>= 4;
          mbar_wait(BA(FT + j), par);
          wgmma_fence();
        }
        wgmma_n128(acc, D128(da + k * 2), D128(db + k * 128), 1);
        if (k == 3) {
          wgmma_commit();
          wgmma_wait<1>();
          if (elected) REL2(CT + j - 1);
        }
      };
      auto run = [&](int j0, int j1) {
#pragma unroll 1
        for (int j = j0; j < j1; ++j) {
          mbar_wait(BA(FT + j), par);
          da = dA0 + ((uint32_t)ta & 15) * 1024; db = dB0 + ((uint32_t)tw & 15) * 1024;
          ta >>= 4; tw >>= 4;
          wgmma_fence();
#pragma unroll
          for (int k = 0; k < 4; ++k) wgmma_n128(acc, D128(da + k * 2), D128(db + k * 128), 1);
          wgmma_commit();
          wgmma_wait<1>();
          if (elected) REL2(CT + j - 1);
        }
        ta = TL_A >> (4 * j1); tw = TL_B >> (4 * j1);
      };
      auto rest = [&](int j0, int sk) {
        if (sk) {
          run(j0, ND - sk);
          if (wu == 0) nbar<6, 256>();
          j0 = ND - sk;
        }
        run(j0, ND);
        if (sk && wu) asm volatile("bar.arrive 6, 256;" ::: "memory");
      };
      auto rest_end = [&]() {
        wgmma_wait<0>();
        if (elected) REL2(CT + ND - 1);
#pragma unroll
        for (int i = 128; i < 192; ++i) asm volatile("" : "+f"(acc[i]) :: "memory");
      };
      auto wo0 = [&]() {
        wgmma_fence();
        wgmma_n128_rs0(acc, of[0], D128(dB0 + (uint32_t)(WO_B & 15) * 1024));
#pragma unroll
        for (int k = 1; k < 4; ++k) wgmma_n128_rs(acc, of[k], D128(dB0 + (uint32_t)(WO_B & 15) * 1024 + k * 128), 1);
        wgmma_commit();
      };
      const float rs0 = lds_f(sb + SM_RS + (16 + wrow0 + gq) * 4), rs1 = lds_f(sb + SM_RS + (24 + wrow0 + gq) * 4);
#define EPOCH() __float_as_uint(lds_f(sb + SM_EPOCH))
      mbar_wait(BA(CM + 14), par);
      if (par) {
        uint32_t kk[8][4], kp[8][4], vf[2][2][4][4];
        int sn = 4;
#pragma unroll
        for (int i = 0; i < 4 * BT1; ++i) sub(sn++);
        {
          uint32_t vv[8][4];
#pragma unroll
          for (int jp = 0; jp < 8; ++jp) {
            kk[jp][0] = pack_bf16(acc[8 * jp], acc[8 * jp + 1]); kk[jp][1] = pack_bf16(acc[8 * jp + 4], acc[8 * jp + 5]);
            kk[jp][2] = pack_bf16(acc[8 * jp + 2], acc[8 * jp + 3]); kk[jp][3] = pack_bf16(acc[8 * jp + 6], acc[8 * jp + 7]);
#pragma unroll
            for (int i = 0; i < 4; ++i) vv[jp][i] = pack_bf16(acc[64 + 8 * jp + 2 * i], acc[65 + 8 * jp + 2 * i]);
          }
          if (cw == 7) {
            uint32_t* const hbuf = g_halo + (size_t)(((layer >> 1) * 17 + rb + 1) * 8 + g) * 2048;
#pragma unroll
            for (int jp = 0; jp < 8; ++jp) stg128(hbuf + jp * 128 + lane * 4, kk[jp][0], kk[jp][1], kk[jp][2], kk[jp][3]);
#pragma unroll
            for (int i = 0; i < 32; ++i) hbuf[1024 + (i >> 4) * 512 + (gq + (i & 1) * 8) * 32 + ((((i >> 1) & 7) ^ gq) << 2) + t] = vv[i >> 2][i & 3];
            __syncwarp();
            if (lane == 0) mbar_arrive(BA(B_OF0));
          }
#pragma unroll
          for (int jp = 0; jp < 8; ++jp) {
            sub(sn++);
            stsm_x4(sb + VB + (jp >> 2) * SLOT + rowo + (X ^ ((jp & 3) << 5)), vv[jp][0], vv[jp][1], vv[jp][2], vv[jp][3]);
          }
        }
        PROFT(tid_ == 128, layer * 16 + 2);
        const int e = gq & 1;
        float f0[4], f1[4], b0[4], b1[4], rj[4];
#pragma unroll
        for (int nt = 0; nt < 4; ++nt) {
          const int kx = nt * 8 + 2 * t + e;
          const bool okk = (m0 + wrow0 + kx) >= 16;
          const int d0 = kx - gq, d1 = d0 - 8;
          rj[nt] = lds_f(sb + SM_RS + (wrow0 + kx) * 4);
          const bool m0_ = okk && d0 >= 2 && d0 <= 16, m1_ = okk && d1 >= 2 && d1 <= 16;
          f0[nt] = m0_ ? rj[nt] * rs0 * (0.17677669529663687f * L2E) : 0.f;
          f1[nt] = m1_ ? rj[nt] * rs1 * (0.17677669529663687f * L2E) : 0.f;
          b0[nt] = m0_ ? 0.f : -1e30f; b1[nt] = m1_ ? 0.f : -1e30f;
        }
        mbar_wait(BA(CM + 15), par);
#pragma unroll
        for (int jp = 0; jp < 8; ++jp) {
          sub(sn++);
          sts128(sb + PH + cw * 4096 + jp * 512 + lane * 16, make_uint4(kk[jp][0], kk[jp][1], kk[jp][2], kk[jp][3]));
        }
#pragma unroll
        for (int i = 0; i < 4; ++i) sub(sn++);
        nbar<1, 256>();
        PROFT(tid_ == 128, layer * 16 + 3);
        rest(sn >> 2, SKB);
        if (!BPRE) rest_end();
        PROFT(lane == 0 && layer == PL, 200 + cw);
        PROFT(tid_ == 128, layer * 16 + 10);
        if (cw == 0) mbar_wait(BA(B_HALO), (layer >> 1) & 1);
        PROFT(tid_ == 128, layer * 16 + 5);
        const uint32_t vs = sb + (cw ? VB + rowo - 2048 : SM_SD + 4096 + rowo), vst = cw ? SLOT : 2048;
        const uint32_t psel = e ? 0x1054u : 0x5410u;
#pragma unroll
        for (int hp = 0; hp < 2; ++hp) {
#pragma unroll
          for (int i = 4 * hp; i < 4 * hp + 4; ++i) {
            const uint4 u = lds128(sb + (cw ? PH + (cw - 1) * 4096 : SM_SD) + lane * 16 + i * 512);
            kp[i][0] = u.x; kp[i][1] = u.y; kp[i][2] = u.z; kp[i][3] = u.w;
          }
#pragma unroll
          for (int i = 4 * hp; i < 4 * hp + 4; ++i) {
            ldsm_x4_t(vf[0][i & 1][i >> 1][0], vf[0][i & 1][i >> 1][1], vf[0][i & 1][i >> 1][2], vf[0][i & 1][i >> 1][3], vs + (i >> 2) * vst + (X ^ ((i & 3) << 5)));
            ldsm_x4_t(vf[1][i & 1][i >> 1][0], vf[1][i & 1][i >> 1][1], vf[1][i & 1][i >> 1][2], vf[1][i & 1][i >> 1][3], sb + VB + (i >> 2) * SLOT + rowo + (X ^ ((i & 3) << 5)));
          }
          if (BPRE && !hp) rest_end();
          float l0[2][4], l1[2][4];
#pragma unroll
          for (int h = 0; h < 2; ++h) {
            const int H = 2 * hp + h;
            uint32_t qa[8];
#pragma unroll
            for (int i = 0; i < 8; ++i) qa[i] = pack_bf16(acc[128 + 16 * H + 2 * i], acc[129 + 16 * H + 2 * i]);
#pragma unroll
            for (int nt = 3; nt >= 0; --nt) {
              float sc[4] = {0.f, 0.f, 0.f, 0.f};
#pragma unroll
              for (int ks = 0; ks < 2; ++ks) {
                const uint32_t (&kf)[4] = nt < 2 ? kp[2 * H + ks] : kk[2 * H + ks];
                mma_bf16(sc, qa[4 * ks], qa[4 * ks + 1], qa[4 * ks + 2], qa[4 * ks + 3], kf[2 * (nt & 1)], kf[2 * (nt & 1) + 1]);
              }
              l0[h][nt] = fmaf(e ? sc[1] : sc[0], f0[nt], b0[nt]);
              l1[h][nt] = fmaf(e ? sc[3] : sc[2], f1[nt], b1[nt]);
            }
          }
          float mx0[2], mx1[2], s0[2], s1[2];
#pragma unroll
          for (int h = 0; h < 2; ++h) {
            mx0[h] = fmaxf(fmaxf(l0[h][0], l0[h][1]), l0[h][2]);
            mx1[h] = fmaxf(fmaxf(l1[h][1], l1[h][2]), l1[h][3]);
          }
#pragma unroll
          for (int o = 1; o <= 2; o <<= 1)
#pragma unroll
            for (int h = 0; h < 2; ++h) {
              mx0[h] = fmaxf(mx0[h], __shfl_xor_sync(0xffffffffu, mx0[h], o));
              mx1[h] = fmaxf(mx1[h], __shfl_xor_sync(0xffffffffu, mx1[h], o));
            }
#pragma unroll
          for (int h = 0; h < 2; ++h) {
#pragma unroll
            for (int nt = 0; nt < 3; ++nt) { l0[h][nt] = ex2(l0[h][nt] - mx0[h]); l1[h][nt + 1] = ex2(l1[h][nt + 1] - mx1[h]); }
            s0[h] = (l0[h][0] + l0[h][1]) + l0[h][2];
            s1[h] = (l1[h][1] + l1[h][2]) + l1[h][3];
          }
#pragma unroll
          for (int o = 1; o <= 2; o <<= 1)
#pragma unroll
            for (int h = 0; h < 2; ++h) {
              s0[h] += __shfl_xor_sync(0xffffffffu, s0[h], o);
              s1[h] += __shfl_xor_sync(0xffffffffu, s1[h], o);
            }
          uint32_t ow[2][2][4];
#pragma unroll
          for (int h = 0; h < 2; ++h) {
            const int H = 2 * hp + h;
            uint32_t pl[4], ph[4];
            const float i0 = rcp(s0[h]), i1 = rcp(s1[h]);
#pragma unroll
            for (int nt = 0; nt < 4; ++nt) {
              const uint32_t pk = pack_bf16(nt < 3 ? l0[h][nt] * i0 * rj[nt] : 0.f, nt > 0 ? l1[h][nt] * i1 * rj[nt] : 0.f);
              pl[nt] = nt < 3 ? __byte_perm(pk, 0u, psel) : 0u;
              ph[nt] = nt > 0 ? __byte_perm(pk, 0u, psel + 0x2222u) : 0u;
            }
#pragma unroll
            for (int nj = 0; nj < 4; ++nj) {
              float oa[4] = {0.f, 0.f, 0.f, 0.f};
#pragma unroll
              for (int ks = 0; ks < 2; ++ks)
                mma_bf16(oa, pl[2 * ks], ph[2 * ks], pl[2 * ks + 1], ph[2 * ks + 1], vf[ks][nj >> 1][H][2 * (nj & 1)], vf[ks][nj >> 1][H][2 * (nj & 1) + 1]);
              ow[h][0][nj] = pack_bf16(oa[0], oa[1]); ow[h][1][nj] = pack_bf16(oa[2], oa[3]);
            }
          }
          if (hp == 0) {
#pragma unroll
            for (int i = 0; i < 4; ++i) stg128(g_o + gfr + (i & 1) * 8 * D_ + (i >> 1) * 32, ow[i >> 1][i & 1][0], ow[i >> 1][i & 1][1], ow[i >> 1][i & 1][2], ow[i >> 1][i & 1][3]);
            __syncwarp();
            if (lane == 0) mbar_arrive(BA(B_OH0));
          } else {
#pragma unroll
            for (int i = 0; i < 16; ++i) o1[i >> 2][i & 3] = ow[i >> 3][(i >> 2) & 1][i & 3];
          }
#pragma unroll
          for (int i = 0; i < 16; ++i) of[4 * hp + (i >> 2)][i & 3] = ow[i >> 3][i & 1][(i >> 1) & 3];
          if (!hp) { PROFT(tid_ == 128, layer * 16 + 15); mbar_wait(BA(FW), par); }
        }
      } else {
        float sc[2] = {rs0 * L2E, rs1 * L2E};
        {
          const uint32_t vb = sb + VB + (rowo >> 1), X0 = (lchk ^ ((lane & 7) >> 1)) << 4;
          const uint32_t pb = sb + PH + (t & 1) * SLOT + (wrow0 + gq) * 128 + ((((t & 1) * 4 + (t & 2)) ^ gq) << 4);
          float kva[20], en[32], mx[2][2], mn[2][2];
#define PV(hp, j) acc[32 * (hp) + (j)]
          auto mm = [&](int hp, int j) {
            const int r = (j >> 1) & 1;
            if (j < 4 && !(j & 1)) { mx[hp][r] = PV(hp, j); mn[hp][r] = PV(hp, j); }
            else { mx[hp][r] = fmaxf(mx[hp][r], PV(hp, j)); mn[hp][r] = fminf(mn[hp][r], PV(hp, j)); }
          };
          auto mmx = [&](int hp) {
#pragma unroll
            for (int r = 0; r < 2; ++r) {
              mx[hp][r] = fmaxf(mx[hp][r], __shfl_xor_sync(0xffffffffu, mx[hp][r], 2)) * -sc[r];
              mn[hp][r] = fmaf(fminf(mn[hp][r], __shfl_xor_sync(0xffffffffu, mn[hp][r], 2)), sc[r], mx[hp][r]);
            }
          };
          auto stage = [&](int hp) {
#pragma unroll
            for (int i = 0; i < 20; ++i) asm volatile("" : "+f"(kva[i]) :: "memory");
            nbar_dyn(3 + wu, 128);
            const uint32_t ad = sb + VB + hp * SLOT + wg * 8192 + (2 * wq + ((lane >> 3) & 1)) * 640 + (lane & 7) * 16;
#pragma unroll
            for (int i = 0; i < 2; ++i)
              stsm_x4(ad + (2 * i + lchk) * 128, pack_bf16(kva[8 * i], kva[8 * i + 1]), pack_bf16(kva[8 * i + 2], kva[8 * i + 3]),
                      pack_bf16(kva[8 * i + 4], kva[8 * i + 5]), pack_bf16(kva[8 * i + 6], kva[8 * i + 7]));
            stsm_x2(ad + 512, pack_bf16(kva[16], 0.0625f), pack_bf16(kva[18], 0.0625f));
            fence_async_smem();
            __syncwarp();
            if (lane == 0) mbar_arrive(BA(B_KVDONE));
          };
          int sn = 4;
#pragma unroll
          for (int j = 0; j < 32; ++j) mm(0, j);
          mmx(0);
#pragma unroll
          for (int hp = 0; hp < 2; ++hp) {
            float sp[2] = {0.f, 0.f}, sm[2] = {0.f, 0.f};
#pragma unroll
            for (int j = 0; j < 32; ++j) {
              const int r = (j >> 1) & 1, ns = hp ? SUBS1 : SUBS;
              if ((j * ns) / 32 != ((j + 1) * ns) / 32) {
                sub(sn++);
                if (hp && sn == 4 + SUBS + 4 + 4 * (XST & 1)) { stage(0); PROFT(tid_ == 128, layer * 16 + 12); }
              }
              const float x = fmaf(PV(hp, j), sc[r], mx[hp][r]);
              PV(hp, j) = ex2(x); en[j] = ex2(mn[hp][r] - x);
              sp[r] += PV(hp, j); sm[r] += en[j];
              if (hp == 0) {
                mm(1, j);
                if ((j & 3) == 0) {
                  const int jp = 8 + (j >> 2);
                  stsm_x4(vb + ((jp - 8) >> 1) * 8192 + (X0 ^ ((jp & 1) << 5)), pack_bf16(acc[8 * jp], acc[8 * jp + 1]), pack_bf16(acc[8 * jp + 2], acc[8 * jp + 3]),
                          pack_bf16(acc[8 * jp + 4], acc[8 * jp + 5]), pack_bf16(acc[8 * jp + 6], acc[8 * jp + 7]));
                }
              }
            }
#pragma unroll
            for (int i = 0; i < 4; ++i) if (XST & (1 << hp)) sub(sn++);
#pragma unroll
            for (int r = 0; r < 2; ++r) {
              sp[r] = rcp(sp[r] + __shfl_xor_sync(0xffffffffu, sp[r], 2)) * (r ? rs1 : rs0);
              sm[r] = rcp(sm[r] + __shfl_xor_sync(0xffffffffu, sm[r], 2)) * (r ? rs1 : rs0);
            }
            if (hp == 0) { mmx(1); mbar_wait(BA(CM + 15), par); }
            else { PROFT(tid_ == 128, layer * 16 + 11); nbar<1, 256>(); }
#pragma unroll
            for (int i = 0; i < 4; ++i) {
              const int r = i & 1, d = 16 * (i >> 1) + 2 * r;
              sts128((pb + r * 1024) ^ ((i >> 1) << 4), make_uint4(pack_bf16(PV(hp, d) * sp[r], PV(hp, d + 1) * sp[r]), pack_bf16(PV(hp, d + 4) * sp[r], PV(hp, d + 5) * sp[r]),
                                                                    pack_bf16(PV(hp, d + 8) * sp[r], PV(hp, d + 9) * sp[r]), pack_bf16(PV(hp, d + 12) * sp[r], PV(hp, d + 13) * sp[r])));
              sts128((pb + r * 1024) ^ ((i >> 1) << 4) ^ 64, make_uint4(pack_bf16(en[d] * sm[r], en[d + 1] * sm[r]), pack_bf16(en[d + 4] * sm[r], en[d + 5] * sm[r]),
                                                                         pack_bf16(en[d + 8] * sm[r], en[d + 9] * sm[r]), pack_bf16(en[d + 12] * sm[r], en[d + 13] * sm[r])));
            }
            fence_async_smem();
            nbar<1, 256>();
            const uint32_t dP = dB0 + (PH >> 4) + wu * 1024;
            const uint32_t dV = (dB0 & 0xFFFFu) + ((VB + hp * SLOT) >> 4) + (((SM_SD - VB - hp * SLOT) >> 4) << 16) + wu * (512u - (512u << 16));
            wgmma_fence();
#pragma unroll
            for (int ks = 0; ks < 8; ++ks) wgmma_n40_tt(kva, D128(dP + ks * 128), desc64(dV + ks * 64, 0x80000020u), ks != 0);
            wgmma_commit();
          }
#pragma unroll
          for (int i = 0; i < 4; ++i) sub(sn++);
          stage(1);
          PROFT(tid_ == 128, layer * 16 + 3);
          rest(sn >> 2, SKA);
          rest_end();
          PROFT(lane == 0 && layer == PL, 200 + cw);
          PROFT(tid_ == 128, layer * 16 + 10);
        }
#define QV(H, i) acc[128 + 16 * (H) + (i)]
        float mx[4][2], mn[4][2];
        uint32_t ph[4][4][4];
        auto mnx = [&](int hp) {
#pragma unroll
          for (int H = 2 * hp; H < 2 * hp + 2; ++H)
#pragma unroll
            for (int r = 0; r < 2; ++r) {
              mx[H][r] = fmaxf(fmaxf(fmaxf(QV(H, 2 * r), QV(H, 2 * r + 1)), fmaxf(QV(H, 4 + 2 * r), QV(H, 5 + 2 * r))),
                               fmaxf(fmaxf(QV(H, 8 + 2 * r), QV(H, 9 + 2 * r)), fmaxf(QV(H, 12 + 2 * r), QV(H, 13 + 2 * r))));
              mn[H][r] = fminf(fminf(fminf(QV(H, 2 * r), QV(H, 2 * r + 1)), fminf(QV(H, 4 + 2 * r), QV(H, 5 + 2 * r))),
                               fminf(fminf(QV(H, 8 + 2 * r), QV(H, 9 + 2 * r)), fminf(QV(H, 12 + 2 * r), QV(H, 13 + 2 * r))));
            }
#pragma unroll
          for (int o = 1; o <= 2; o <<= 1)
#pragma unroll
            for (int H = 2 * hp; H < 2 * hp + 2; ++H)
#pragma unroll
              for (int r = 0; r < 2; ++r) {
                mx[H][r] = fmaxf(mx[H][r], __shfl_xor_sync(0xffffffffu, mx[H][r], o));
                mn[H][r] = fminf(mn[H][r], __shfl_xor_sync(0xffffffffu, mn[H][r], o));
              }
#pragma unroll
          for (int H = 2 * hp; H < 2 * hp + 2; ++H)
#pragma unroll
            for (int r = 0; r < 2; ++r) { mx[H][r] *= -sc[r]; mn[H][r] = fmaf(mn[H][r], sc[r], mx[H][r]); }
        };
        auto fm = [&](int H) {
#pragma unroll
          for (int i = 0; i < 8; ++i) {
            const int r = i & 1;
            const float x0 = fmaf(QV(H, 2 * i), sc[r], mx[H][r]), x1 = fmaf(QV(H, 2 * i + 1), sc[r], mx[H][r]);
            ph[H][i >> 2][i & 3] = pack_bf16(ex2(x0), ex2(x1));
            ph[H][2 + (i >> 2)][i & 3] = pack_bf16(ex2(mn[H][r] - x0), ex2(mn[H][r] - x1));
          }
        };
        mnx(0);
        fm(0); fm(1);
#pragma unroll
        for (int hp = 0; hp < 2; ++hp) {
          if (hp) mbar_wait(BA(FW), par);
          mbar_wait(BA(hp ? B_KVF1 : B_KVF), (layer >> 1) & 1);
          PROFT(tid_ == 128, layer * 16 + (hp ? 4 : 5));
          float oa[4][20];
          wgmma_fence();
#pragma unroll
          for (int s = 0; s < 2; ++s)
#pragma unroll
            for (int v = 0; v < 4; ++v) {
              const int h = v >> 1, s4 = 2 * (v & 1) + s;
              wgmma_n40_rs(oa[v], ph[2 * hp + h][s4], desc64((((SB0 + VB + hp * SLOT) >> 4) | (40u << 16)) + h * 512 + (s4 ^ (2 * h)) * 80, 8), s != 0);
            }
          wgmma_commit();
          if (hp == 0) { mnx(1); wgmma_wait<0>(); }
          else wgmma_wait<0>();
#pragma unroll
          for (int i = 0; i < 20; ++i) asm volatile("" : "+f"(oa[0][i]), "+f"(oa[1][i]), "+f"(oa[2][i]), "+f"(oa[3][i]) :: "memory");
          uint32_t ow[2][2][4];
#pragma unroll
          for (int h = 0; h < 2; ++h)
#pragma unroll
            for (int r = 0; r < 2; ++r) {
              const float a = oa[2 * h + 1][17 + 2 * r], b = oa[2 * h][17 + 2 * r];
              const float id = rcp(fmaf(oa[2 * h][16 + 2 * r], a, fmaf(a, 1e-6f, oa[2 * h + 1][16 + 2 * r]) * b));
              const float fa = a * id, fb = b * id;
#pragma unroll
              for (int j = 0; j < 4; ++j)
                ow[h][r][j] = pack_bf16(fmaf(oa[2 * h][4 * j + 2 * r], fa, oa[2 * h + 1][4 * j + 2 * r] * fb),
                                        fmaf(oa[2 * h][4 * j + 2 * r + 1], fa, oa[2 * h + 1][4 * j + 2 * r + 1] * fb));
            }
#pragma unroll
          for (int i = 0; i < 16; ++i) of[4 * hp + (i >> 2)][i & 3] = ow[i >> 3][i & 1][(i >> 1) & 3];
          if (hp == 0) {
#pragma unroll
            for (int i = 0; i < 4; ++i) stg128(g_o + gfr + (i & 1) * 8 * D_ + (i >> 1) * 32, ow[i >> 1][i & 1][0], ow[i >> 1][i & 1][1], ow[i >> 1][i & 1][2], ow[i >> 1][i & 1][3]);
            __syncwarp();
            if (lane == 0) mbar_arrive(BA(B_OH0));
            PROFT(tid_ == 128 && layer, layer * 16 + 15);
            fm(2); fm(3);
          } else {
#pragma unroll
            for (int i = 0; i < 16; ++i) o1[i >> 2][i & 3] = ow[i >> 3][(i >> 2) & 1][i & 3];
          }
        }
      }
      PROFT(tid_ == 128, layer * 16 + 6);
#pragma unroll
      for (int i = 0; i < 4; ++i) stg128(g_o + gfr + (i & 1) * 8 * D_ + (2 + (i >> 1)) * 32, o1[i][0], o1[i][1], o1[i][2], o1[i][3]);
      __syncwarp();
      if (lane == 0) { mbar_arrive(BA(B_OH1)); if (EF_USED) REL2(B_EF); }
      PROFT(lane == 0 && layer == PL, 208 + cw);
      wo0();
    }
    {
      PHASE_CTX();
      MMA_CTX();
      mbar_wait(BA(FW + 1), par);
      wgmma_fence();
#pragma unroll
      for (int k = 0; k < 4; ++k) wgmma_n128_rs(acc, of[4 + k], D128(dB0 + (uint32_t)((WO_B >> 4) & 15) * 1024 + k * 128), 1);
      wgmma_commit();
      wgmma_wait<1>();
      if (elected) REL2(CW);
      uint64_t ta = WO_A >> 8, tw = WO_B >> 8;
      auto run = [&](int i0, int i1) {
#pragma unroll 1
        for (int i = i0; i < i1; ++i) {
          mbar_wait(BA(FW + i), par);
          PROFL(tid_ == 128 && layer == PL, 160 + i);
          const uint32_t da = dA0 + ((uint32_t)ta & 15) * 1024, db = dB0 + ((uint32_t)tw & 15) * 1024;
          ta >>= 4; tw >>= 4;
          wgmma_fence();
#pragma unroll
          for (int k = 0; k < 4; ++k) wgmma_n128(acc, D128(da + k * 2), D128(db + k * 128), 1);
          wgmma_commit();
          wgmma_wait<1>();
          if (elected) REL2(CW + i - 1);
        }
        ta = WO_A >> (4 * (i1 & 15)); tw = WO_B >> (4 * (i1 & 15));
      };
      run(2, XRAT);
#pragma unroll
      for (int j = 0; j < 8 / XRN; ++j) {
#pragma unroll
        for (int i = j * XRN; i < (j + 1) * XRN; ++i) ldg128((layer ? g_x : c.x0) + gfr + (i & 1) * 8 * D_ + (i >> 1) * 32, xp[i][0], xp[i][1], xp[i][2], xp[i][3]);
        run(XRAT + j, j + 1 < 8 / XRN ? XRAT + j + 1 : 16);
      }
      if (layer == 0) {
#pragma unroll
        for (int o = 1; o <= 2; o <<= 1)
#pragma unroll
          for (int i = 0; i < 16; ++i) {
            const int j = o == 1 ? 2 * (i & 1) : (i & 1);
            uint32_t &a = xp[i >> 1][j], &b = xp[i >> 1][j + o];
            const uint32_t r = __shfl_xor_sync(0xffffffffu, (t & o) ? a : b, o);
            if (t & o) a = r; else b = r;
          }
      }
      if (layer != NLAYERS - 1) mbar_wait(BA(FM), par ^ 1);
      wgmma_wait<0>();
#pragma unroll
      for (int i = 128; i < 192; ++i) asm volatile("" : "+f"(acc[i]) :: "memory");
      if (elected) REL2(CW + 15);
      PROFT(lane == 0 && layer == PL, 216 + cw);
      PROFT(tid_ == 128, layer * 16 + 7);
#pragma unroll
      for (int i = 0; i < 32; ++i)
        xp[i >> 2][i & 3] = add_bf16x2(xp[i >> 2][i & 3], pack_bf16(acc[128 + 16 * (i >> 3) + 4 * (i & 3) + 2 * ((i >> 2) & 1)], acc[129 + 16 * (i >> 3) + 4 * (i & 3) + 2 * ((i >> 2) & 1)]));
      if (layer == NLAYERS - 1) {
#pragma unroll
        for (int i = 0; i < 8; ++i) stsm_x4(sb + (XS + (i >> 2)) * SLOT + (Y ^ ((i & 2) << 5)) + (i & 1) * 1024, xp[i][0], xp[i][1], xp[i][2], xp[i][3]);
        __syncwarp();
        slab_out_half(sb + XS * SLOT, c.out + (size_t)m0 * D_ + g * 128, wrow0, lane);
        slab_out_half(sb + (XS + 1) * SLOT, c.out + (size_t)m0 * D_ + g * 128 + 64, wrow0, lane);
        PROFT(tid_ == 128, layer * 16 + 24);
        break;
      }
#pragma unroll
      for (int i = 0; i < 4; ++i) stg128(g_x + gfr + (i & 1) * 8 * D_ + (i >> 1) * 32, xp[i][0], xp[i][1], xp[i][2], xp[i][3]);
      __syncwarp();
      if (lane == 0) mbar_arrive(BA(B_XH0));
#pragma unroll
      for (int i = 0; i < 16; ++i) xf[i >> 2][i & 3] = xp[2 * (i >> 3) + (i & 1)][(i >> 1) & 3];
      PROFT(tid_ == 128, layer * 16 + 24);
    }
  }
}

__device__ __forceinline__ uint64_t k_order(int o) {
  const uint32_t lo = (1u << (4 * o)) - 1u, h0 = (0xECA86420u & lo) | ((0xECA86420u >> 4) & ~lo);
  return (uint64_t)(2 * o) | ((uint64_t)(2 * o + 1) << 4) | ((uint64_t)(h0 & 0xFFFFFFFu) << 8) | ((uint64_t)((h0 & 0xFFFFFFFu) | 0x1111111u) << 36);
}

__global__ void __cluster_dims__(2, 1, 1) __launch_bounds__(384, 1)
mega_kernel(const __grid_constant__ Maps maps, const __grid_constant__ Ctx c, const bf16* __restrict__ wA, const bf16* __restrict__ wB,
            const bf16* __restrict__ woA, const bf16* __restrict__ woB) {
  if (blockIdx.x - c.boff >= 128u) {
    const unsigned int epoch = ld_relaxed(&g_epoch);
    const int e = (blockIdx.x - c.boff) & 3, tid = threadIdx.x;
    float s[8] = {0.f, 0.f, 0.f, 0.f, 0.f, 0.f, 0.f, 0.f};
    const uint32_t sb = smem_u32(smem_raw), bar = sb + SM_BAR;
    auto issue = [&](int i) {
      mbar_expect_tx(BA(i & 3), 49152);
      bulk_load(sb + (i & 3) * 49152, wB + (size_t)e * 256 * 3072 + i * 24576, 49152, BA(i & 3));
    };
    if (tid == 0) {
#pragma unroll 1
      for (int i = 0; i < 4; ++i) {
        mbar_init(BA(i), 1);
        fence_async_smem();
        issue(i);
      }
    }
    __syncthreads();
#pragma unroll 1
    for (int i = 0; i < 32; ++i) {
      mbar_wait(BA(i & 3), (i >> 2) & 1);
#pragma unroll 2
      for (int r = 0; r < 8; ++r) {
        const uint4 v = lds128(sb + (i & 3) * 49152 + r * 6144 + tid * 16);
        s[0] += bf_lo(v.x); s[1] += bf_hi(v.x); s[2] += bf_lo(v.y); s[3] += bf_hi(v.y);
        s[4] += bf_lo(v.z); s[5] += bf_hi(v.z); s[6] += bf_lo(v.w); s[7] += bf_hi(v.w);
      }
      __syncthreads();
      if (tid == 0 && i < 28) issue(i + 4);
    }
    float* cd = g_cs + (epoch & 1) * 6144 + 3072 + ((tid >> 4) & 7) * 384 + (tid < 128 ? 256 : (tid >> 7) * 128 - 128) + (tid & 15) * 8;
    red_add4(cd, s[0], s[1], s[2], s[3]);
    red_add4(cd + 4, s[4], s[5], s[6], s[7]);
    __syncthreads();
    if (tid == 0) flag_add(&g_csflag[8].v);
    const int op = (epoch & 1) ^ 1;
    float4* kz = reinterpret_cast<float4*>(g_kv + (size_t)op * (2 * 8 * 10240)) + e * 5120;
#pragma unroll 1
    for (int i = tid; i < 5120; i += 384) kz[i] = make_float4(0.f, 0.f, 0.f, 0.f);
    reinterpret_cast<float4*>(g_cs + op * 6144)[e * 384 + tid] = make_float4(0.f, 0.f, 0.f, 0.f);
#pragma unroll 1
    for (int i = tid; i < 1024; i += 384) reinterpret_cast<float4*>(g_stats + (op * 4 + e) * S_)[i] = make_float4(0.f, 0.f, 0.f, 0.f);
    return;
  }
  const int warp = __shfl_sync(0xffffffffu, threadIdx.x >> 5, 0), lane = threadIdx.x & 31;
  if (smem_u32(smem_raw) != SB0 + ((blockIdx.x & 1) << 24)) __trap();
  {
  const int cid = (blockIdx.x - c.boff) >> 1, u7 = ((cid - 36) * 37) >> 8, cr = blockIdx.x & 1;
  const int g = cid < 4 ? 4 + cid : cid < 36 ? (cid - 4) >> 3 : 4 + u7, rb = (cid < 4 ? 0 : cid < 36 ? (cid - 4) & 7 : cid - 35 - 7 * u7) * 2 + cr, m0 = rb * 128;
  const uint32_t sb = SB0 + (cr << 24), bar = sb + SM_BAR;
  PROFT(lane == 0 && (warp == 0 || warp == 4), 224 + (warp >> 2) * 8);
  uint32_t cx = 0;
  if (warp == 2) {
    if (lane < NMAP) asm volatile("prefetch.tensormap [%0];" ::"l"(&maps.m[lane]) : "memory");
    if (lane == 31) asm volatile("prefetch.global.L2 [%0];" ::"l"(&g_epoch));
  } else if (warp == 3) {
    cx = c_map[cid] + c_wop[lane] + c_wop[NWOP - lane] + c_aop[lane] + c_aop[NAOP - lane] + (uint32_t)(uintptr_t)g_x;
  } else if (warp >= 4 && warp < 8) {
    const int i = threadIdx.x - 128;
    asm volatile("prefetch.global.L2 [%0];" ::"l"(wA + (size_t)((rb & ~1) * 64 + cr * 32 + ((i >> 1) & 31)) * 3072 + (i >> 6) * 1024 + g * 128 + (i & 1) * 64));
  }
  if (warp < 2) {
    const int s = warp, kb = (rb & ~1) + s;
    if (lane == 0) {
      mbar_init(BA(FM + s), 1u);
      mbar_init(BA(B_RAW + warp), 1u);
      mbar_init(BA(warp ? B_X0 : B_KVS0), 1u);
      asm volatile("fence.mbarrier_init.release.cluster;" ::: "memory");
    }
    __syncwarp();
    if (warp == 0) tma_2d_e(sb + SM_SD, &maps.m[MAP_PHI], 0, g * 128, BA(B_RAW));
    else if (W1DL) __nanosleep(W1DL);
#pragma unroll
    for (int j = 0; j < 6; ++j)
      tma_5d_e(sb + (j < 2 ? 2 * s : j < 4 ? 9 + s : 2 * s + 1) * SLOT + (j & 1) * 8192, &maps.m[MAP_WA], (j < 2 ? 1024 : j < 4 ? 0 : 2048) + g * 128 + (j & 1) * 64, 2 * kb,
               BA(j < 4 ? B_RAW + warp : FM + s));
    tma_2d_e(sb + (XS + s) * SLOT, &maps.m[MAP_X0], kb * 64, m0, BA(FM + s));
    expect_tx_e(BA(B_RAW + warp), warp ? 32768 : 32768 + 8192);
    expect_tx_e(BA(FM + s), 32768);
    if (X0AT == 0 && warp == 1) {
      tma_2d_e(sb + 11 * SLOT, &maps.m[MAP_X0], g * 128, m0, BA(B_X0));
      tma_2d_e(sb + 12 * SLOT, &maps.m[MAP_X0], g * 128 + 64, m0, BA(B_X0));
      expect_tx_e(BA(B_X0), 32768);
    }
  } else if (warp >= 4 && lane == 0) {
#pragma unroll 1
    for (int i = 2 + (warp - 4) * 13; i < 15 + (warp - 4) * 13; ++i)
      mbar_init(BA(i), 1u << ((i < CM ? 0u : i < B_EF ? 2u : (uint32_t)(BAR_LG >> (4 * ((i - B_EF) & 15)))) & 7u));
    asm volatile("fence.mbarrier_init.release.cluster;" ::: "memory");
  }
  __syncwarp();
  asm volatile("barrier.cluster.arrive.relaxed.aligned;" ::: "memory");
  if (threadIdx.x == 96 + c.zero) sts_f(sb + SM_EPOCH + 4, __uint_as_float(cx));
  PROFT(lane == 0 && (warp == 0 || warp == 4), 225 + (warp >> 2) * 8);
  __syncwarp();
  PROFT(lane == 0 && (warp == 0 || warp == 4), 226 + (warp >> 2) * 8);
  }

  if (warp < 4) {
    asm volatile("setmaxnreg.dec.sync.aligned.u32 40;");
    PROFT(threadIdx.x == 0, 227);
    cluster_wait();
    PROFT(threadIdx.x == 0, 228);
    if (warp == 0 || warp == 3) {
    if (warp == 0) {
      BLK_CTX();
      const unsigned int epoch = __shfl_sync(0xffffffffu, ld_relaxed(&g_epoch), 0), xbase = epoch * NLAYERS;
      (void)xbase;
      const uint64_t ordg = k_order(g);
      if (X0AT) {
        mbar_wait_u(BA(B_RAW + X0AT - 1), 0);
        tma_2d_e(sb + 11 * SLOT, &maps.m[MAP_X0], g * 128, m0, BA(B_X0));
        tma_2d_e(sb + 12 * SLOT, &maps.m[MAP_X0], g * 128 + 64, m0, BA(B_X0));
        expect_tx_e(BA(B_X0), 32768);
      }
#pragma unroll 1
      for (int lp = 0; lp < 2 * NLAYERS; ++lp) {
        const int layer = lp >> 1, n1 = (lp & 1) ? NAOP : NAOP - 14;
        int n = (lp & 1) ? NAOP - 14 : 0;
        const uint64_t ord = lp ? ordg : k_order(rb >> 1);
        uint32_t ready = lp ? 0u : 0xFFFFu, nop = c_aop[n];
        const unsigned int* fl = ((lp & 1) ? g_of : g_xf) + rb * 32;
        const CUtensorMap* tm = &maps.m[(lp & 1) ? MAP_O : lp ? MAP_X : MAP_X0];
        const uint32_t skip = layer ? 1u << 25 : 9u << 22;
        if (lp) mbar_wait_u(BA((lp & 1) ? B_OH0 : B_XH0), ((lp - 1) >> 1) & 1);
#pragma unroll 1
        for (; n < n1; ++n) {
          const uint32_t op = nop;
          nop = c_aop[n + 1];
          const uint32_t kb = (uint32_t)(ord >> ((op >> 2) & 60)) & 15;
          uint32_t dst = sb + (op & 15) * SLOT, kc = kb * 64, fb = bar + ((op >> 5) & 0x3F8), need = ~ready & (1u << kb);
          asm volatile("" : "+r"(dst), "+r"(kc), "+r"(fb), "+r"(need));
          const uint32_t eb = bar + ((op >> 12) & 0x3F8), ep = (layer ^ (op >> 22)) & 1;
          bool fr = op & skip;
          if (need) {
            if (!fr) fr = __all_sync(0xffffffffu, mbar_test_wait(eb, ep));
            PROFT(lane == 0 && (n == 0 || n == NAOP - 14), 64 + layer * 16 + (n ? 2 : 0));
            src_wait<0>(fl, xbase + layer + 1, need, ready, lane);
            fence_async_all();
          }
          if (!fr) mbar_wait_u(eb, ep);
          tma_2d_e(dst, tm, kc, m0, fb);
          PROFT(lane == 0 && (n == 0 || n == NAOP - 14), 64 + layer * 16 + (n ? 3 : 1));
          PROFL(lane == 0 && layer == PL && n >= NAOP - 14, 178 + n - (NAOP - 14));
          PROFL(lane == 0 && layer == PL + 1 && n < 4, 242 + n);
        }
      }
    } else {
      BLK_CTX();
      const unsigned int epoch = __shfl_sync(0xffffffffu, ld_relaxed(&g_epoch), 0), xbase = epoch * NLAYERS;
      (void)xbase;
      const uint64_t ordg = k_order(g);
#pragma unroll 1
      for (int layer = 0; layer < NLAYERS; ++layer) {
        const uint64_t ordq = layer ? ordg : k_order(rb >> 1);
        uint32_t ready = layer ? 0xFFFFu : 0u, nop = c_wop[0];
        const CUtensorMap* tq = &maps.m[(layer & 1) ? MAP_WB : MAP_WF];
        const CUtensorMap* tk = &maps.m[(layer & 1) ? MAP_WB : cr ? MAP_WA : MAP_WF];
        const uint32_t skip = layer ? 1u << 25 : 9u << 22, pm = layer ? 0xE0u : 0u;
        int n = 0;
#pragma unroll 1
        for (; n < NWOP - 16; ++n) {
          const uint32_t op = nop;
          nop = c_wop[n + 1];
          const uint32_t isq = (op >> 23) & 1, fb = bar + ((op >> 5) & 0x3F8);
          const uint32_t kb = (uint32_t)(ordq >> ((op >> 2) & 60)) & 15;
          const CUtensorMap* tm = (isq ? tq : tk) + ((op & pm) ? 1 : 0);
          const uint32_t dst = sb + (op & 15) * SLOT + cr * (isq ? 8192 : SLOT);
          const int col = g * 128 + (isq ? cr * 64 : 1024 + cr * 1024);
          if (layer == 0) {
            if ((op & 0x7E00) == 0) continue;
            const uint32_t need = ((isq || !cr) ? 1u << kb : 0u) | (((op >> 22) & 1) ? 0u : (((op >> 15) & 127) == CM ? 1u : 3u) << (rb & ~1));
            if ((ready & need) != need) {
              src_wait<0>(g_wff + g * 32, epoch + 1, need, ready, lane);
              fence_async_all();
            }
            if ((op & 15) >= 11) mbar_wait_u(BA(B_XT), 0);
          }
          wait_tma_5d_mc(!(op & skip), bar + ((op >> 12) & 0x3F8), (layer ^ (op >> 22)) & 1, dst, tm, col, 2 * kb, fb);
          if (!isq) tma_5d_mc_e(dst + 8192, tm, col + 64, 2 * kb, fb);
          if (op >> 26) expect_tx_e(fb, (op >> 26) * 8192);
          PROFL(lane == 0 && layer == PL + 1 && n < 16, 128 + n);
        }
        const CUtensorMap* to = &maps.m[(layer & 1) ? MAP_WOB : MAP_WOA];
#pragma unroll 1
        for (; n < NWOP; ++n) {
          const uint32_t op = nop;
          nop = c_wop[n + 1];
          const uint32_t fb = bar + ((op >> 5) & 0x3F8), kb = (uint32_t)(ordg >> ((op >> 2) & 60)) & 15;
          if (WH < 16 && n == NWOP - 16 + WH && !(layer & 1)) mbar_wait_u(BA(B_KVS), (layer >> 1) & 1);
          wait_tma_5d_mc(!((op >> 25) & 1), bar + ((op >> 12) & 0x3F8), layer & 1, sb + (op & 15) * SLOT + cr * 8192, to + ((op & 0xE0) ? 1 : 0), g * 128 + cr * 64, 2 * kb, fb);
          expect_tx_e(fb, (op >> 26) * 8192);
          PROFL(lane == 0 && layer == PL, 144 + ((op >> 8) & 127) - FW);
        }
      }
    }
    } else if (warp == 1) {
      BLK_CTX();
      const unsigned int epoch = __shfl_sync(0xffffffffu, ld_relaxed(&g_epoch), 0), xbase = epoch * NLAYERS;
      (void)xbase;
      if (lane == 0) {
        mbar_wait(BA(B_WFD), 0);
        PROFT(true, 229);
#pragma unroll 1
        for (int j = 0; j < 4; ++j) tma_store_5d(&maps.m[MAP_WF], sb + (j < 2 ? 2 * cr : 9 + cr) * SLOT + (j & 1) * 8192, (j < 2 ? 1024 : 0) + g * 128 + (j & 1) * 64, 2 * rb);
        bulk_commit();
        bulk_wait0();
        PROFT(true, 230);
        fence_async_all();
        flag_set(g_wff + g * 32 + rb, epoch + 1);
        PROFT(true, 64 + 13);
#pragma unroll 1
        for (int e = 0; e < NLAYERS; ++e) {
          BLK_CTX();
          if (e > 0) {
            mbar_wait(BA(B_XH0), (e - 1) & 1);
            PROFT(e == PL + 1, 240);
            flag_set(g_xf + rb * 32 + 2 * g, xbase + e + 1);
            PROFT(e == PL + 1, 241);
          }
          mbar_wait(BA(B_XDONE), e & 1);
          PROFT(true, 64 + e * 16 + 4);
          flag_set(g_xf + rb * 32 + 2 * g + 1, xbase + e + 1);
          if (e == 0) {
            flag_add(&g_csflag[g].v);
#pragma unroll 1
            for (int i = 0; i < 4; ++i) {
              mbar_wait(BA(CM + PFM + PFS * i), 0);
              l2_prefetch(i < 3 ? wB + (size_t)(i * 128 + bid_) * 8192 : woA + (size_t)bid_ * 8192, 16384);
            }
          }
          if (PFM && e == 1) l2_prefetch(woB + (size_t)bid_ * 8192, 16384);
          PROFT(true, 64 + e * 16 + 7);
          if ((e & 1) == 0) {
            bf16* kvl = g_kv + ((size_t)((epoch & 1) * 2 + (e >> 1)) * 8 + g) * 10240;
#pragma unroll 1
            for (int hp = 0; hp < 2; ++hp) {
              mbar_wait(BA(B_KVDONE), hp);
#pragma unroll 1
              for (int i = 0; i < 4; ++i) {
                const int ch = (i + (rb >> 2)) & 3;
                bulk_red_add(kvl + hp * 5120 + ch * 1280, sb + VB + hp * SLOT + (ch >> 1) * 8192 + (ch & 1) * 2560, 2560);
                bulk_commit();
                asm volatile("cp.async.bulk.wait_group %0;" :: "n"(CHW) : "memory");
              }
              bulk_wait0();
              PROFT(true, 64 + e * 16 + (hp ? 10 : 6));
              fence_async_all();
              flag_add(&g_kvflag[hp * 8 + g].v);
              mbar_arrive(BA(hp ? B_KVS : B_KVS0));
              PROFT(e > 0 && hp, 64 + e * 16 + 8);
            }
          }
          if (e & 1) {
            mbar_wait(BA(B_OF0), (e >> 1) & 1);
            flag_set(g_hf + rb * 32 + g, xbase + e + 1);
            if (rb) flag_wait(g_hf + (rb - 1) * 32 + g, xbase + e + 1);
            fence_async_all();
            mbar_expect_tx(BA(B_HALO), 8192);
            bulk_load(sb + SM_SD, g_halo + (size_t)(((e >> 1) * 17 + rb) * 8 + g) * 2048, 8192, BA(B_HALO));
            PROFT(true, 64 + e * 16 + 15);
          }
          mbar_wait(BA(B_OH0), e & 1);
          PROFT(e > 0, 64 + e * 16 + 13);
          flag_set(g_of + rb * 32 + 2 * g, xbase + e + 1);
          PROFT(true, 64 + e * 16 + 9);
          mbar_wait(BA(B_OH1), e & 1);
          PROFT(true, 64 + e * 16 + 5);
          flag_set(g_of + rb * 32 + 2 * g + 1, xbase + e + 1);
          PROFT(true, 64 + e * 16 + 11);
        }
        if (bid_ == 0) g_epoch = epoch + 1;
      }
    } else {
      BLK_CTX();
      const unsigned int epoch = __shfl_sync(0xffffffffu, ld_relaxed(&g_epoch), 0), xbase = epoch * NLAYERS;
      (void)xbase;
      if (lane < 16) sts_f(sb + SM_RS + lane * 4, 0.f);
#pragma unroll 1
      for (int layer = 0; layer < NLAYERS; ++layer) {
#define HLP_CTX() BLK_CTX(); int lane = threadIdx.x & 31; asm volatile("" : "+r"(lane)); const bool isB = layer & 1, hal = isB && rb > 0; (void)hal;
#pragma unroll 1
        for (int ph = 0; ph < 2; ++ph) {
          HLP_CTX();
          if (ph == (layer == 0)) {
            const float* cs = g_cs + (epoch & 1) * 6144 + g * 384;
            if (layer) mbar_wait_u(BA(CT), (layer - 1) & 1);
            if (layer < 2) {
              if (lane == 0) flag_wait_slow(&g_csflag[isB ? 8 : g].v, isB ? epoch * 4u + 4u : epoch * 16u + 16u);
              __syncwarp();
            }
#pragma unroll 1
            for (int i0 = 0; i0 < 12; i0 += 4) {
              float a[4];
#pragma unroll
              for (int i = 0; i < 4; ++i) a[i] = __ldcg(cs + isB * 3072 + (i0 + i) * 32 + lane);
#pragma unroll
              for (int i = 0; i < 4; ++i) {
                const float c1 = bf16r(a[i]), c2 = bf16r(a[i] - c1), c3 = (a[i] - c1) - c2;
                sts128(sb + SM_BP + ((i0 + i) * 32 + lane) * 16, make_uint4(pack_bf16(c1, c2), pack_bf16(c3, 0.f), 0u, 0u));
              }
            }
          } else {
            uint32_t rdy = 0u;
            mbar_wait_u(BA(CM + 3), layer & 1);
            src_wait<128>(g_xf + rb * 32, xbase + layer + 1, 0xAAAAu, rdy, lane);
            rdy = 0u;
            if (hal) src_wait<128>(g_xf + (rb - 1) * 32, xbase + layer + 1, 0xAAAAu, rdy, lane);
            const float2* sp = g_stats + ((epoch & 1) * 4 + layer) * S_ + m0 + lane;
            float2 u[5];
#pragma unroll
            for (int i = 0; i < 4; ++i) u[i] = __ldcg(sp + i * 32);
            u[4] = __ldcg(sp - (hal ? 16 : 0));
#pragma unroll 1
            for (int i = 0; i < 5; ++i) {
              const float mean = u[0].x * (1.f / D_);
              const float var = fmaxf(fmaf(-u[0].x, mean, u[0].y) * (1.f / D_), 0.f);
              const float sd = bf16r(sqrtf(bf16r(bf16r(var) + 1e-5f)));
              const int R = i * 32 + lane;
              if (i < 4) {
                const float hm = -0.5f * bf16r(mean);
                if (!isB) sts128(sb + SM_SD + R * 64 + ((R >> 1) & 3) * 16, make_uint4(__float_as_uint(sd) >> 16, __float_as_uint(sd) >> 16, __float_as_uint(sd) >> 16, __float_as_uint(sd) >> 16));
                sts128(sb + SM_AP + R * 16, make_uint4(pack_bf16(hm, hm), pack_bf16(hm, 0.f), 0u, 0u));
              }
              if (i < 4 || (hal && lane < 16)) sts_f(sb + SM_RS + (i < 4 ? 16 + R : lane) * 4, __fdividef(1.f, sd));
#pragma unroll
              for (int j = 0; j < 4; ++j) u[j] = u[j + 1];
            }
            PROFT(lane == 0, 64 + layer * 16 + 12);
          }
        }
        HLP_CTX();
        fence_async_smem();
        __syncwarp();
        if (lane == 0) mbar_arrive(BA(B_STAT));
        PROFT(lane == 0, 64 + layer * 16 + 14);
        if (!isB && lane == 0) {
#pragma unroll 1
          for (int hp = 0; hp < 2; ++hp) {
            mbar_wait(BA(hp ? B_KVS : B_KVS0), (layer >> 1) & 1);
            flag_wait(&g_kvflag[hp * 8 + g].v, epoch * (16u * ((NLAYERS + 1) / 2)) + 16u * ((layer >> 1) + 1));
            const bf16* kvl = g_kv + ((size_t)((epoch & 1) * 2 + (layer >> 1)) * 8 + g) * 10240 + hp * 5120;
            const uint32_t kb = BA(hp ? B_KVF1 : B_KVF);
            fence_async_all();
            mbar_expect_tx(kb, 10240);
            bulk_load(sb + VB + hp * SLOT, kvl, 5120, kb);
            bulk_load(sb + VB + hp * SLOT + 8192, kvl + 2560, 5120, kb);
            PROFT(hp == 0, 64 + layer * 16 + 15);
          }
        }
        __syncwarp();
      }
    }
    __syncwarp();
    asm volatile("barrier.cluster.arrive.relaxed.aligned;" ::: "memory");
    cluster_wait();
  } else {
    asm volatile("setmaxnreg.inc.sync.aligned.u32 232;");
    PROFT(threadIdx.x == 128, 235);
    cluster_wait();
    PROFT(threadIdx.x == 128, 236);
    consumer(c);
    asm volatile("bar.warp.sync 0xffffffff;\nbarrier.cluster.arrive.relaxed.aligned;\nbarrier.cluster.wait.aligned;\n" ::: "memory");
  }
}

typedef CUresult (*PFN_encodeTiled)(CUtensorMap*, CUtensorMapDataType, cuuint32_t, void*, const cuuint64_t*, const cuuint64_t*,
                                    const cuuint32_t*, const cuuint32_t*, CUtensorMapInterleave, CUtensorMapSwizzle,
                                    CUtensorMapL2promotion, CUtensorMapFloatOOBfill);

static void make_map2(PFN_encodeTiled enc, CUtensorMap* m, const void* ptr, uint64_t cols, uint64_t rows, uint32_t box_c, uint32_t box_r) {
  cuuint64_t dims[2] = {cols, rows};
  cuuint64_t strides[1] = {cols * 2};
  cuuint32_t box[2] = {box_c, box_r};
  cuuint32_t es[2] = {1, 1};
  CUresult r = enc(m, CU_TENSOR_MAP_DATA_TYPE_BFLOAT16, 2, const_cast<void*>(ptr), dims, strides, box, es, CU_TENSOR_MAP_INTERLEAVE_NONE,
                   box_c == 64 ? CU_TENSOR_MAP_SWIZZLE_128B : CU_TENSOR_MAP_SWIZZLE_64B, CU_TENSOR_MAP_L2_PROMOTION_L2_256B, CU_TENSOR_MAP_FLOAT_OOB_FILL_NONE);
  (void)r;
}
static void make_map5(PFN_encodeTiled enc, CUtensorMap* m, const void* ptr, uint64_t cols) {
  for (int p = 0; p < 2; ++p) {
    cuuint64_t dims[5] = {cols, 2, 4, 4, 32};
    cuuint64_t strides[4] = {cols * 2, cols * (p ? 16 : 4), cols * (p ? 4 : 16), cols * 64};
    cuuint32_t box[5] = {64, 2, 4, 4, 2};
    cuuint32_t es[5] = {1, 1, 1, 1, 1};
    CUresult r = enc(m + p, CU_TENSOR_MAP_DATA_TYPE_BFLOAT16, 5, const_cast<void*>(ptr), dims, strides, box, es, CU_TENSOR_MAP_INTERLEAVE_NONE,
                     CU_TENSOR_MAP_SWIZZLE_128B, CU_TENSOR_MAP_L2_PROMOTION_L2_256B, CU_TENSOR_MAP_FLOAT_OOB_FILL_NONE);
    (void)r;
  }
}

extern "C" void kernel_launch(void* const* d_in, const int* in_sizes, int n_in, void* d_out, int out_size) {
  const bf16* A_x = (const bf16*)d_in[0];
  const bf16* A_wqkv = (const bf16*)d_in[1];
  const bf16* A_wphi = (const bf16*)d_in[2];
  const bf16* A_wo = (const bf16*)d_in[3];
  const bf16* B_wqkv = (const bf16*)d_in[5];
  const bf16* B_wo = (const bf16*)d_in[6];
  bf16* out = (bf16*)d_out;

  static PFN_encodeTiled enc = nullptr;
  static bf16 *p_x, *p_o, *p_wf;
  static uint32_t boff;
  if (!enc) {
    void* fn = nullptr; cudaDriverEntryPointQueryResult qr;
    cudaGetDriverEntryPoint("cuTensorMapEncodeTiled", &fn, cudaEnableDefault, &qr);
    enc = (PFN_encodeTiled)fn;
    cudaGetSymbolAddress((void**)&p_x, g_x);
    cudaGetSymbolAddress((void**)&p_o, g_o);
    cudaGetSymbolAddress((void**)&p_wf, g_wf);
    cudaFuncSetAttribute(mega_kernel, cudaFuncAttributeMaxDynamicSharedMemorySize, SM_TOTAL);
    cudaLaunchConfig_t cfg = {};
    cudaLaunchAttribute at; at.id = cudaLaunchAttributeClusterDimension; at.val.clusterDim.x = 2; at.val.clusterDim.y = 1; at.val.clusterDim.z = 1;
    cfg.gridDim = dim3(132); cfg.blockDim = dim3(384); cfg.dynamicSmemBytes = SM_TOTAL; cfg.attrs = &at; cfg.numAttrs = 1;
    int nc = 0;
    if (cudaOccupancyMaxActiveClusters(&nc, mega_kernel, &cfg) != cudaSuccess) { nc = 0; (void)cudaGetLastError(); }
    boff = nc >= 66 ? 0u : 4u;
  }
  Maps maps;
  make_map5(enc, &maps.m[MAP_WF], p_wf, 2048);
  make_map5(enc, &maps.m[MAP_WA], A_wqkv, 3072);
  make_map5(enc, &maps.m[MAP_WB], B_wqkv, 3072);
  make_map5(enc, &maps.m[MAP_WOA], A_wo, 1024);
  make_map5(enc, &maps.m[MAP_WOB], B_wo, 1024);
  make_map2(enc, &maps.m[MAP_X0], A_x, 1024, 2048, 64, 128);
  make_map2(enc, &maps.m[MAP_X], p_x, 1024, 2048, 64, 128);
  make_map2(enc, &maps.m[MAP_O], p_o, 1024, 2048, 64, 128);
  make_map2(enc, &maps.m[MAP_PHI], A_wphi, 32, 1024, 32, 128);
  Ctx c; c.zero = 0u; c.boff = boff; c.x0 = A_x; c.out = out;
  mega_kernel<<<132, 384, SM_TOTAL, cudaStreamPerThread>>>(maps, c, A_wqkv, B_wqkv, A_wo, B_wo);
}
```

```cpp
#include <cuda_runtime.h>
#include <cuda_bf16.h>
#include <cuda.h>
#include <stdint.h>

typedef __nv_bfloat16 bf16;

constexpr int S_ = 2048, D_ = 1024;

struct __align__(128) Flag { unsigned int v; unsigned int pad[31]; };
__device__ __align__(1024) bf16 g_x[S_ * D_];
__device__ __align__(1024) bf16 g_o[S_ * D_];
__device__ __align__(1024) uint32_t g_halo[2 * 17 * 8 * 2048];
__device__ __align__(1024) bf16 g_kv[2 * 2 * 8 * 10240];
__device__ __align__(1024) float2 g_stats[2 * 4 * S_];
__device__ __align__(1024) float g_cs[2 * 2 * 3072];
__device__ __align__(1024) bf16 g_wf[D_ * 2048];
__device__ Flag g_kvflag[16], g_csflag[13];
__device__ __align__(128) unsigned int g_xf[16 * 32], g_of[16 * 32];
__device__ __align__(128) unsigned int g_hf[16 * 32];
__device__ __align__(128) unsigned int g_wff[8 * 32];
__device__ unsigned int g_epoch, g_err;
#define PROFT(cond, idx) asm volatile("" ::: "memory")

__device__ __forceinline__ uint32_t smem_u32(const void* p) { return (uint32_t)__cvta_generic_to_shared(p); }
__device__ __forceinline__ void mbar_init(uint32_t bar, uint32_t count) {
  asm volatile("mbarrier.init.shared::cta.b64 [%0], %1;" ::"r"(bar), "r"(count) : "memory");
}
__device__ __forceinline__ void mbar_expect_tx(uint32_t bar, uint32_t bytes) {
  asm volatile("mbarrier.arrive.expect_tx.shared::cta.b64 _, [%0], %1;" ::"r"(bar), "r"(bytes) : "memory");
}
__device__ __forceinline__ void mbar_arrive(uint32_t bar) {
  asm volatile("mbarrier.arrive.shared::cta.b64 _, [%0];" ::"r"(bar) : "memory");
}
__device__ __forceinline__ bool mbar_try_wait(uint32_t bar, uint32_t parity) {
  uint32_t ok;
  asm volatile("{\n.reg .pred p;\nmbarrier.try_wait.parity.shared::cta.b64 p, [%1], %2;\nselp.b32 %0, 1, 0, p;\n}\n"
               : "=r"(ok) : "r"(bar), "r"(parity) : "memory");
  return ok != 0;
}
__device__ __forceinline__ bool mbar_test_wait(uint32_t bar, uint32_t parity) {
  uint32_t ok;
  asm volatile("{\n.reg .pred p;\nmbarrier.test_wait.parity.shared::cta.b64 p, [%1], %2;\nselp.b32 %0, 1, 0, p;\n}\n"
               : "=r"(ok) : "r"(bar), "r"(parity) : "memory");
  return ok != 0;
}
__device__ __forceinline__ uint64_t gtimer() {
  uint64_t t; asm volatile("mov.u64 %0, %globaltimer;" : "=l"(t)); return t;
}
__device__ __forceinline__ void mbar_wait(uint32_t bar, uint32_t parity) {
  uint32_t n = 0;
  bool ok;
#pragma unroll 1
  do { ++n; ok = mbar_try_wait(bar, parity); } while (!ok && n < (1u << 22));
}
__device__ __forceinline__ unsigned int ld_acquire(const unsigned int* p) {
  unsigned int v; asm volatile("ld.acquire.gpu.global.u32 %0, [%1];" : "=r"(v) : "l"(p) : "memory"); return v;
}
__device__ __forceinline__ void flag_add(unsigned int* p) {
  asm volatile("red.release.gpu.global.add.u32 [%0], 1;" ::"l"(p) : "memory");
}
__device__ __forceinline__ void flag_set(unsigned int* p, unsigned int v) {
  asm volatile("st.release.gpu.global.u32 [%0], %1;" ::"l"(p), "r"(v) : "memory");
}
template <int SLEEP>
__device__ __forceinline__ void src_wait(const unsigned int* f, unsigned int target, uint32_t need, uint32_t& ready, int lane) {
  uint32_t n = 0;
#pragma unroll 1
  while ((ready & need) != need) {
    const unsigned int v = ld_acquire(f + (lane & 15));
    ready = __ballot_sync(0xffffffffu, (int)(v - target) >= 0);
    if (SLEEP) { if ((ready & need) != need) __nanosleep(SLEEP); }
    if (++n > (1u << 20)) break;
  }
  __syncwarp();
}
__device__ __forceinline__ unsigned int ld_relaxed(const unsigned int* p);
__device__ __forceinline__ unsigned int ld_relaxed(const unsigned int* p) {
  unsigned int v; asm volatile("ld.relaxed.gpu.global.u32 %0, [%1];" : "=r"(v) : "l"(p) : "memory"); return v;
}
template <int SLEEP>
__device__ __forceinline__ void flag_wait_t(const unsigned int* p, unsigned int target) {
  uint32_t n = 0;
#pragma unroll 1
  while ((int)(ld_acquire(p) - target) < 0) {
    if (SLEEP) __nanosleep(SLEEP);
    if (++n > (1u << 20)) break;
  }
}
__device__ __forceinline__ void flag_wait(const unsigned int* p, unsigned int target) { flag_wait_t<0>(p, target); }
__device__ __forceinline__ void flag_wait_slow(const unsigned int* p, unsigned int target) { flag_wait_t<256>(p, target); }
__device__ __forceinline__ void mbar_wait_u(uint32_t bar, uint32_t parity) {
  uint32_t n = 0;
#pragma unroll 1
  while (!__all_sync(0xffffffffu, mbar_try_wait(bar, parity))) {
    if (++n > (1u << 22)) break;
  }
}
__device__ __forceinline__ void expect_tx_e(uint32_t bar, uint32_t bytes) {
  asm volatile("{\n.reg .pred p;\nelect.sync _|p, 0xffffffff;\n@p mbarrier.arrive.expect_tx.shared::cta.b64 _, [%0], %1;\n}\n" ::"r"(bar), "r"(bytes) : "memory");
}
__device__ __forceinline__ void tma_2d_e(uint32_t dst, const CUtensorMap* tm, int c0, int c1, uint32_t bar) {
  asm volatile("{\n.reg .pred p;\nelect.sync _|p, 0xffffffff;\n"
               "@p cp.async.bulk.tensor.2d.shared::cluster.global.mbarrier::complete_tx::bytes [%0], [%1, {%2, %3}], [%4];\n}\n"
               ::"r"(dst), "l"(tm), "r"(c0), "r"(c1), "r"(bar) : "memory");
}
__device__ __forceinline__ void tma_5d_e(uint32_t dst, const CUtensorMap* tm, int c0, int c4, uint32_t bar) {
  asm volatile("{\n.reg .pred p;\nelect.sync _|p, 0xffffffff;\n"
               "@p cp.async.bulk.tensor.5d.shared::cluster.global.mbarrier::complete_tx::bytes [%0], [%1, {%2, %5, %5, %5, %3}], [%4];\n}\n"
               ::"r"(dst), "l"(tm), "r"(c0), "r"(c4), "r"(bar), "r"(0) : "memory");
}
__device__ __forceinline__ void tma_5d_mc_e(uint32_t dst, const CUtensorMap* tm, int c0, int c4, uint32_t bar) {
  asm volatile("{\n.reg .pred p;\nelect.sync _|p, 0xffffffff;\n"
               "@p cp.async.bulk.tensor.5d.shared::cluster.global.mbarrier::complete_tx::bytes.multicast::cluster [%0], [%1, {%2, %6, %6, %6, %3}], [%4], %5;\n}\n"
               ::"r"(dst), "l"(tm), "r"(c0), "r"(c4), "r"(bar), "h"((uint16_t)3), "r"(0) : "memory");
}
__device__ __forceinline__ void wait_tma_5d_mc(bool w, uint32_t eb, uint32_t par, uint32_t dst, const CUtensorMap* tm, int c0, int c4, uint32_t fb) {
  asm volatile("" : "+r"(dst), "+l"(tm), "+r"(c0), "+r"(c4), "+r"(fb));
  if (w) mbar_wait_u(eb, par);
  tma_5d_mc_e(dst, tm, c0, c4, fb);
}
__device__ __forceinline__ void stg128(void* p, uint32_t a, uint32_t b, uint32_t c, uint32_t d) {
  asm volatile("st.global.v4.u32 [%0], {%1,%2,%3,%4};" ::"l"(p), "r"(a), "r"(b), "r"(c), "r"(d) : "memory");
}
__device__ __forceinline__ void stg128_p(bool on, void* p, uint32_t a, uint32_t b, uint32_t c, uint32_t d) {
  asm volatile("{\n.reg .pred p;\nsetp.ne.b32 p, %5, 0;\n@p st.global.v4.u32 [%0], {%1,%2,%3,%4};\n}\n" ::"l"(p), "r"(a), "r"(b), "r"(c), "r"(d), "r"((int)on) : "memory");
}
__device__ __forceinline__ void ldg128(const void* p, uint32_t& a, uint32_t& b, uint32_t& c, uint32_t& d) {
  asm volatile("ld.global.cg.v4.u32 {%0,%1,%2,%3}, [%4];" : "=r"(a), "=r"(b), "=r"(c), "=r"(d) : "l"(p) : "memory");
}
__device__ __forceinline__ void release2c(uint32_t off) {
  asm volatile("mbarrier.arrive.shared::cluster.b64 _, [%0];\nmbarrier.arrive.shared::cluster.b64 _, [%1];" ::"r"(off), "r"(off + (1u << 24)) : "memory");
}
__device__ __forceinline__ void tma_store_5d(const CUtensorMap* tm, uint32_t src, int c0, int c4) {
  asm volatile("cp.async.bulk.tensor.5d.global.shared::cta.bulk_group [%0, {%2, %4, %4, %4, %3}], [%1];"
               ::"l"(tm), "r"(src), "r"(c0), "r"(c4), "r"(0) : "memory");
}
__device__ __forceinline__ void bulk_load(uint32_t dst, const void* src, uint32_t bytes, uint32_t bar) {
  asm volatile("cp.async.bulk.shared::cluster.global.mbarrier::complete_tx::bytes [%0], [%1], %2, [%3];" ::"r"(dst), "l"(src), "r"(bytes), "r"(bar) : "memory");
}
__device__ __forceinline__ void bulk_red_add(void* dst, uint32_t src, uint32_t bytes) {
  asm volatile("cp.reduce.async.bulk.global.shared::cta.bulk_group.add.noftz.bf16 [%0], [%1], %2;" ::"l"(dst), "r"(src), "r"(bytes) : "memory");
}
__device__ __forceinline__ void bulk_commit() { asm volatile("cp.async.bulk.commit_group;" ::: "memory"); }
__device__ __forceinline__ void bulk_wait0() { asm volatile("cp.async.bulk.wait_group 0;" ::: "memory"); }
__device__ __forceinline__ void fence_async_smem() { asm volatile("fence.proxy.async.shared::cta;" ::: "memory"); }
__device__ __forceinline__ void fence_async_all() { asm volatile("fence.proxy.async.global;" ::: "memory"); }
__device__ __forceinline__ void wgmma_fence() { asm volatile("wgmma.fence.sync.aligned;" ::: "memory"); }
__device__ __forceinline__ void wgmma_commit() { asm volatile("wgmma.commit_group.sync.aligned;" ::: "memory"); }
template <int N> __device__ __forceinline__ void wgmma_wait() { asm volatile("wgmma.wait_group.sync.aligned %0;" ::"n"(N) : "memory"); }
__device__ __forceinline__ void cluster_wait() { asm volatile("barrier.cluster.wait.acquire.aligned;" ::: "memory"); }
template <int ID, int N> __device__ __forceinline__ void nbar() { asm volatile("bar.sync %0, %1;" ::"n"(ID), "n"(N) : "memory"); }
__device__ __forceinline__ uint64_t desc64(uint32_t lo, uint32_t hi) { return (uint64_t)lo | ((uint64_t)hi << 32); }
__device__ __forceinline__ uint32_t pack_bf16(float lo, float hi) {
  uint32_t r; asm("cvt.rn.bf16x2.f32 %0, %1, %2;" : "=r"(r) : "f"(hi), "f"(lo)); return r;
}
__device__ __forceinline__ uint32_t add_bf16x2(uint32_t a, uint32_t b) {
  uint32_t r; asm("add.rn.bf16x2 %0, %1, %2;" : "=r"(r) : "r"(a), "r"(b)); return r;
}
__device__ __forceinline__ float bf16r(float x) { return __bfloat162float(__float2bfloat16_rn(x)); }
__device__ __forceinline__ float bf_lo(uint32_t u) { return __uint_as_float(u << 16); }
__device__ __forceinline__ float bf_hi(uint32_t u) { return __uint_as_float(u & 0xFFFF0000u); }
__device__ __forceinline__ float ex2(float x) { float r; asm("ex2.approx.ftz.f32 %0, %1;" : "=f"(r) : "f"(x)); return r; }
__device__ __forceinline__ float rcp(float x) { float r; asm("rcp.approx.ftz.f32 %0, %1;" : "=f"(r) : "f"(x)); return r; }
__device__ __forceinline__ void mma_bf16(float (&d)[4], uint32_t a0, uint32_t a1, uint32_t a2, uint32_t a3, uint32_t b0, uint32_t b1) {
  asm("mma.sync.aligned.m16n8k16.row.col.f32.bf16.bf16.f32 {%0,%1,%2,%3}, {%4,%5,%6,%7}, {%8,%9}, {%0,%1,%2,%3};"
               : "+f"(d[0]), "+f"(d[1]), "+f"(d[2]), "+f"(d[3]) : "r"(a0), "r"(a1), "r"(a2), "r"(a3), "r"(b0), "r"(b1));
}
__device__ __forceinline__ void ldsm_x4(uint32_t& r0, uint32_t& r1, uint32_t& r2, uint32_t& r3, uint32_t addr) {
  asm volatile("ldmatrix.sync.aligned.m8n8.x4.shared.b16 {%0,%1,%2,%3}, [%4];"
               : "=r"(r0), "=r"(r1), "=r"(r2), "=r"(r3) : "r"(addr) : "memory");
}
__device__ __forceinline__ void ldsm_x4_t(uint32_t& r0, uint32_t& r1, uint32_t& r2, uint32_t& r3, uint32_t addr) {
  asm volatile("ldmatrix.sync.aligned.m8n8.x4.trans.shared.b16 {%0,%1,%2,%3}, [%4];"
               : "=r"(r0), "=r"(r1), "=r"(r2), "=r"(r3) : "r"(addr) : "memory");
}
__device__ __forceinline__ void stsm_x4(uint32_t addr, uint32_t r0, uint32_t r1, uint32_t r2, uint32_t r3) {
  asm volatile("stmatrix.sync.aligned.m8n8.x4.shared.b16 [%0], {%1,%2,%3,%4};"
               ::"r"(addr), "r"(r0), "r"(r1), "r"(r2), "r"(r3) : "memory");
}
__device__ __forceinline__ void stsm_x2(uint32_t addr, uint32_t r0, uint32_t r1) {
  asm volatile("stmatrix.sync.aligned.m8n8.x2.shared.b16 [%0], {%1,%2};" ::"r"(addr), "r"(r0), "r"(r1) : "memory");
}
__device__ __forceinline__ uint4 lds128(uint32_t addr) {
  uint4 v; asm volatile("ld.shared.v4.b32 {%0,%1,%2,%3}, [%4];" : "=r"(v.x), "=r"(v.y), "=r"(v.z), "=r"(v.w) : "r"(addr) : "memory"); return v;
}
__device__ __forceinline__ void sts128(uint32_t addr, uint4 v) {
  asm volatile("st.shared.v4.b32 [%0], {%1,%2,%3,%4};" ::"r"(addr), "r"(v.x), "r"(v.y), "r"(v.z), "r"(v.w) : "memory");
}
__device__ __forceinline__ float lds_f(uint32_t addr) {
  float v; asm volatile("ld.shared.f32 %0, [%1];" : "=f"(v) : "r"(addr) : "memory"); return v;
}
__device__ __forceinline__ void nbar_dyn(int id, int n) { asm volatile("bar.sync %0, %1;" ::"r"(id), "r"(n) : "memory"); }
__device__ __forceinline__ uint64_t make_desc_ns(uint32_t addr, uint32_t lbo_bytes, uint32_t sbo_bytes) {
  return (uint64_t)((addr & 0x3FFFF) >> 4) | ((uint64_t)(lbo_bytes >> 4) << 16) | ((uint64_t)(sbo_bytes >> 4) << 32);
}
__device__ __forceinline__ void sts_f(uint32_t addr, float v) { asm volatile("st.shared.f32 [%0], %1;" ::"r"(addr), "f"(v) : "memory"); }
__device__ __forceinline__ void sts64(uint32_t addr, uint32_t a, uint32_t b) {
  asm volatile("st.shared.v2.b32 [%0], {%1,%2};" ::"r"(addr), "r"(a), "r"(b) : "memory");
}
__device__ __forceinline__ void sts_f2(uint32_t addr, float a, float b) {
  asm volatile("st.shared.v2.f32 [%0], {%1,%2};" ::"r"(addr), "f"(a), "f"(b) : "memory");
}
__device__ __forceinline__ void red_add2_p(bool on, float* p, float a, float b) {
  asm volatile("{\n.reg .pred p;\nsetp.ne.b32 p, %3, 0;\n@p red.global.add.v2.f32 [%0], {%1,%2};\n}\n" ::"l"(p), "f"(a), "f"(b), "r"((int)on) : "memory");
}
__device__ __forceinline__ void red_add4(float* p, float a, float b, float c, float d) {
  asm volatile("red.global.add.v4.f32 [%0], {%1,%2,%3,%4};" ::"l"(p), "f"(a), "f"(b), "f"(c), "f"(d) : "memory");
}
__device__ __forceinline__ void red_add1(float* p, float a) {
  asm volatile("red.global.add.f32 [%0], %1;" ::"l"(p), "f"(a) : "memory");
}
__device__ __forceinline__ void l2_prefetch(const void* p, uint32_t bytes) {
  asm volatile("cp.async.bulk.prefetch.L2.global [%0], %1;" ::"l"(p), "r"(bytes) : "memory");
}

__device__ __forceinline__ void wgmma_n256(float (&d)[192], uint64_t da, uint64_t db, int scale_d) {
  asm volatile("{\n.reg .pred p;\nsetp.ne.b32 p, %130, 0;\n"
    "wgmma.mma_async.sync.aligned.m64n256k16.f32.bf16.bf16 {%0, %1, %2, %3, %4, %5, %6, %7, %8, %9, %10, %11, %12, %13, %14, %15, %16, %17, %18, %19, %20, %21, %22, %23, %24, %25, %26, %27, %28, %29, %30, %31, %32, %33, %34, %35, %36, %37, %38, %39, %40, %41, %42, %43, %44, %45, %46, %47, %48, %49, %50, %51, %52, %53, %54, %55, %56, %57, %58, %59, %60, %61, %62, %63, %64, %65, %66, %67, %68, %69, %70, %71, %72, %73, %74, %75, %76, %77, %78, %79, %80, %81, %82, %83, %84, %85, %86, %87, %88, %89, %90, %91, %92, %93, %94, %95, %96, %97, %98, %99, %100, %101, %102, %103, %104, %105, %106, %107, %108, %109, %110, %111, %112, %113, %114, %115, %116, %117, %118, %119, %120, %121, %122, %123, %124, %125, %126, %127}, %128, %129, p, 1, 1, 0, 1;\n}\n"
    : "+f"(d[0]), "+f"(d[1]), "+f"(d[2]), "+f"(d[3]), "+f"(d[4]), "+f"(d[5]), "+f"(d[6]), "+f"(d[7]), "+f"(d[8]), "+f"(d[9]), "+f"(d[10]), "+f"(d[11]), "+f"(d[12]), "+f"(d[13]), "+f"(d[14]), "+f"(d[15]), "+f"(d[16]), "+f"(d[17]), "+f"(d[18]), "+f"(d[19]), "+f"(d[20]), "+f"(d[21]), "+f"(d[22]), "+f"(d[23]), "+f"(d[24]), "+f"(d[25]), "+f"(d[26]), "+f"(d[27]), "+f"(d[28]), "+f"(d[29]), "+f"(d[30]), "+f"(d[31]), "+f"(d[32]), "+f"(d[33]), "+f"(d[34]), "+f"(d[35]), "+f"(d[36]), "+f"(d[37]), "+f"(d[38]), "+f"(d[39]), "+f"(d[40]), "+f"(d[41]), "+f"(d[42]), "+f"(d[43]), "+f"(d[44]), "+f"(d[45]), "+f"(d[46]), "+f"(d[47]), "+f"(d[48]), "+f"(d[49]), "+f"(d[50]), "+f"(d[51]), "+f"(d[52]), "+f"(d[53]), "+f"(d[54]), "+f"(d[55]), "+f"(d[56]), "+f"(d[57]), "+f"(d[58]), "+f"(d[59]), "+f"(d[60]), "+f"(d[61]), "+f"(d[62]), "+f"(d[63]), "+f"(d[64]), "+f"(d[65]), "+f"(d[66]), "+f"(d[67]), "+f"(d[68]), "+f"(d[69]), "+f"(d[70]), "+f"(d[71]), "+f"(d[72]), "+f"(d[73]), "+f"(d[74]), "+f"(d[75]), "+f"(d[76]), "+f"(d[77]), "+f"(d[78]), "+f"(d[79]), "+f"(d[80]), "+f"(d[81]), "+f"(d[82]), "+f"(d[83]), "+f"(d[84]), "+f"(d[85]), "+f"(d[86]), "+f"(d[87]), "+f"(d[88]), "+f"(d[89]), "+f"(d[90]), "+f"(d[91]), "+f"(d[92]), "+f"(d[93]), "+f"(d[94]), "+f"(d[95]), "+f"(d[96]), "+f"(d[97]), "+f"(d[98]), "+f"(d[99]), "+f"(d[100]), "+f"(d[101]), "+f"(d[102]), "+f"(d[103]), "+f"(d[104]), "+f"(d[105]), "+f"(d[106]), "+f"(d[107]), "+f"(d[108]), "+f"(d[109]), "+f"(d[110]), "+f"(d[111]), "+f"(d[112]), "+f"(d[113]), "+f"(d[114]), "+f"(d[115]), "+f"(d[116]), "+f"(d[117]), "+f"(d[118]), "+f"(d[119]), "+f"(d[120]), "+f"(d[121]), "+f"(d[122]), "+f"(d[123]), "+f"(d[124]), "+f"(d[125]), "+f"(d[126]), "+f"(d[127])
    : "l"(da), "l"(db), "r"(scale_d));
}
__device__ __forceinline__ void wgmma_n128(float (&d)[192], uint64_t da, uint64_t db, int scale_d) {
  asm volatile("{\n.reg .pred p;\nsetp.ne.b32 p, %66, 0;\n"
    "wgmma.mma_async.sync.aligned.m64n128k16.f32.bf16.bf16 {%0, %1, %2, %3, %4, %5, %6, %7, %8, %9, %10, %11, %12, %13, %14, %15, %16, %17, %18, %19, %20, %21, %22, %23, %24, %25, %26, %27, %28, %29, %30, %31, %32, %33, %34, %35, %36, %37, %38, %39, %40, %41, %42, %43, %44, %45, %46, %47, %48, %49, %50, %51, %52, %53, %54, %55, %56, %57, %58, %59, %60, %61, %62, %63}, %64, %65, p, 1, 1, 0, 1;\n}\n"
    : "+f"(d[128]), "+f"(d[129]), "+f"(d[130]), "+f"(d[131]), "+f"(d[132]), "+f"(d[133]), "+f"(d[134]), "+f"(d[135]), "+f"(d[136]), "+f"(d[137]), "+f"(d[138]), "+f"(d[139]), "+f"(d[140]), "+f"(d[141]), "+f"(d[142]), "+f"(d[143]), "+f"(d[144]), "+f"(d[145]), "+f"(d[146]), "+f"(d[147]), "+f"(d[148]), "+f"(d[149]), "+f"(d[150]), "+f"(d[151]), "+f"(d[152]), "+f"(d[153]), "+f"(d[154]), "+f"(d[155]), "+f"(d[156]), "+f"(d[157]), "+f"(d[158]), "+f"(d[159]), "+f"(d[160]), "+f"(d[161]), "+f"(d[162]), "+f"(d[163]), "+f"(d[164]), "+f"(d[165]), "+f"(d[166]), "+f"(d[167]), "+f"(d[168]), "+f"(d[169]), "+f"(d[170]), "+f"(d[171]), "+f"(d[172]), "+f"(d[173]), "+f"(d[174]), "+f"(d[175]), "+f"(d[176]), "+f"(d[177]), "+f"(d[178]), "+f"(d[179]), "+f"(d[180]), "+f"(d[181]), "+f"(d[182]), "+f"(d[183]), "+f"(d[184]), "+f"(d[185]), "+f"(d[186]), "+f"(d[187]), "+f"(d[188]), "+f"(d[189]), "+f"(d[190]), "+f"(d[191])
    : "l"(da), "l"(db), "r"(scale_d));
}
__device__ __forceinline__ void wgmma_n256_k(float (&d)[192], uint64_t da, uint64_t db, int scale_d) {
  asm volatile("{\n.reg .pred p;\nsetp.ne.b32 p, %130, 0;\n"
    "wgmma.mma_async.sync.aligned.m64n256k16.f32.bf16.bf16 {%0, %1, %2, %3, %4, %5, %6, %7, %8, %9, %10, %11, %12, %13, %14, %15, %16, %17, %18, %19, %20, %21, %22, %23, %24, %25, %26, %27, %28, %29, %30, %31, %32, %33, %34, %35, %36, %37, %38, %39, %40, %41, %42, %43, %44, %45, %46, %47, %48, %49, %50, %51, %52, %53, %54, %55, %56, %57, %58, %59, %60, %61, %62, %63, %64, %65, %66, %67, %68, %69, %70, %71, %72, %73, %74, %75, %76, %77, %78, %79, %80, %81, %82, %83, %84, %85, %86, %87, %88, %89, %90, %91, %92, %93, %94, %95, %96, %97, %98, %99, %100, %101, %102, %103, %104, %105, %106, %107, %108, %109, %110, %111, %112, %113, %114, %115, %116, %117, %118, %119, %120, %121, %122, %123, %124, %125, %126, %127}, %128, %129, p, 1, 1, 0, 0;\n}\n"
    : "+f"(d[0]), "+f"(d[1]), "+f"(d[2]), "+f"(d[3]), "+f"(d[4]), "+f"(d[5]), "+f"(d[6]), "+f"(d[7]), "+f"(d[8]), "+f"(d[9]), "+f"(d[10]), "+f"(d[11]), "+f"(d[12]), "+f"(d[13]), "+f"(d[14]), "+f"(d[15]), "+f"(d[16]), "+f"(d[17]), "+f"(d[18]), "+f"(d[19]), "+f"(d[20]), "+f"(d[21]), "+f"(d[22]), "+f"(d[23]), "+f"(d[24]), "+f"(d[25]), "+f"(d[26]), "+f"(d[27]), "+f"(d[28]), "+f"(d[29]), "+f"(d[30]), "+f"(d[31]), "+f"(d[32]), "+f"(d[33]), "+f"(d[34]), "+f"(d[35]), "+f"(d[36]), "+f"(d[37]), "+f"(d[38]), "+f"(d[39]), "+f"(d[40]), "+f"(d[41]), "+f"(d[42]), "+f"(d[43]), "+f"(d[44]), "+f"(d[45]), "+f"(d[46]), "+f"(d[47]), "+f"(d[48]), "+f"(d[49]), "+f"(d[50]), "+f"(d[51]), "+f"(d[52]), "+f"(d[53]), "+f"(d[54]), "+f"(d[55]), "+f"(d[56]), "+f"(d[57]), "+f"(d[58]), "+f"(d[59]), "+f"(d[60]), "+f"(d[61]), "+f"(d[62]), "+f"(d[63]), "+f"(d[64]), "+f"(d[65]), "+f"(d[66]), "+f"(d[67]), "+f"(d[68]), "+f"(d[69]), "+f"(d[70]), "+f"(d[71]), "+f"(d[72]), "+f"(d[73]), "+f"(d[74]), "+f"(d[75]), "+f"(d[76]), "+f"(d[77]), "+f"(d[78]), "+f"(d[79]), "+f"(d[80]), "+f"(d[81]), "+f"(d[82]), "+f"(d[83]), "+f"(d[84]), "+f"(d[85]), "+f"(d[86]), "+f"(d[87]), "+f"(d[88]), "+f"(d[89]), "+f"(d[90]), "+f"(d[91]), "+f"(d[92]), "+f"(d[93]), "+f"(d[94]), "+f"(d[95]), "+f"(d[96]), "+f"(d[97]), "+f"(d[98]), "+f"(d[99]), "+f"(d[100]), "+f"(d[101]), "+f"(d[102]), "+f"(d[103]), "+f"(d[104]), "+f"(d[105]), "+f"(d[106]), "+f"(d[107]), "+f"(d[108]), "+f"(d[109]), "+f"(d[110]), "+f"(d[111]), "+f"(d[112]), "+f"(d[113]), "+f"(d[114]), "+f"(d[115]), "+f"(d[116]), "+f"(d[117]), "+f"(d[118]), "+f"(d[119]), "+f"(d[120]), "+f"(d[121]), "+f"(d[122]), "+f"(d[123]), "+f"(d[124]), "+f"(d[125]), "+f"(d[126]), "+f"(d[127])
    : "l"(da), "l"(db), "r"(scale_d));
}
__device__ __forceinline__ void wgmma_n128_k(float (&d)[192], uint64_t da, uint64_t db, int scale_d) {
  asm volatile("{\n.reg .pred p;\nsetp.ne.b32 p, %66, 0;\n"
    "wgmma.mma_async.sync.aligned.m64n128k16.f32.bf16.bf16 {%0, %1, %2, %3, %4, %5, %6, %7, %8, %9, %10, %11, %12, %13, %14, %15, %16, %17, %18, %19, %20, %21, %22, %23, %24, %25, %26, %27, %28, %29, %30, %31, %32, %33, %34, %35, %36, %37, %38, %39, %40, %41, %42, %43, %44, %45, %46, %47, %48, %49, %50, %51, %52, %53, %54, %55, %56, %57, %58, %59, %60, %61, %62, %63}, %64, %65, p, 1, 1, 0, 0;\n}\n"
    : "+f"(d[128]), "+f"(d[129]), "+f"(d[130]), "+f"(d[131]), "+f"(d[132]), "+f"(d[133]), "+f"(d[134]), "+f"(d[135]), "+f"(d[136]), "+f"(d[137]), "+f"(d[138]), "+f"(d[139]), "+f"(d[140]), "+f"(d[141]), "+f"(d[142]), "+f"(d[143]), "+f"(d[144]), "+f"(d[145]), "+f"(d[146]), "+f"(d[147]), "+f"(d[148]), "+f"(d[149]), "+f"(d[150]), "+f"(d[151]), "+f"(d[152]), "+f"(d[153]), "+f"(d[154]), "+f"(d[155]), "+f"(d[156]), "+f"(d[157]), "+f"(d[158]), "+f"(d[159]), "+f"(d[160]), "+f"(d[161]), "+f"(d[162]), "+f"(d[163]), "+f"(d[164]), "+f"(d[165]), "+f"(d[166]), "+f"(d[167]), "+f"(d[168]), "+f"(d[169]), "+f"(d[170]), "+f"(d[171]), "+f"(d[172]), "+f"(d[173]), "+f"(d[174]), "+f"(d[175]), "+f"(d[176]), "+f"(d[177]), "+f"(d[178]), "+f"(d[179]), "+f"(d[180]), "+f"(d[181]), "+f"(d[182]), "+f"(d[183]), "+f"(d[184]), "+f"(d[185]), "+f"(d[186]), "+f"(d[187]), "+f"(d[188]), "+f"(d[189]), "+f"(d[190]), "+f"(d[191])
    : "l"(da), "l"(db), "r"(scale_d));
}
__device__ __forceinline__ void wgmma_n40_tt(float (&d)[20], uint64_t da, uint64_t db, int scale_d) {
  asm volatile("{\n.reg .pred p;\nsetp.ne.b32 p, %22, 0;\n"
    "wgmma.mma_async.sync.aligned.m64n40k16.f32.bf16.bf16 {%0, %1, %2, %3, %4, %5, %6, %7, %8, %9, %10, %11, %12, %13, %14, %15, %16, %17, %18, %19}, %20, %21, p, 1, 1, 1, 1;\n}\n"
    : "+f"(d[0]), "+f"(d[1]), "+f"(d[2]), "+f"(d[3]), "+f"(d[4]), "+f"(d[5]), "+f"(d[6]), "+f"(d[7]), "+f"(d[8]), "+f"(d[9]), "+f"(d[10]), "+f"(d[11]), "+f"(d[12]), "+f"(d[13]), "+f"(d[14]), "+f"(d[15]), "+f"(d[16]), "+f"(d[17]), "+f"(d[18]), "+f"(d[19])
    : "l"(da), "l"(db), "r"(scale_d));
}
__device__ __forceinline__ void wgmma_n40_rs(float (&d)[20], const uint32_t (&a)[4], uint64_t db, int scale_d) {
  asm volatile("{\n.reg .pred p;\nsetp.ne.b32 p, %25, 0;\n"
    "wgmma.mma_async.sync.aligned.m64n40k16.f32.bf16.bf16 {%0, %1, %2, %3, %4, %5, %6, %7, %8, %9, %10, %11, %12, %13, %14, %15, %16, %17, %18, %19}, {%20, %21, %22, %23}, %24, p, 1, 1, 1;\n}\n"
    : "+f"(d[0]), "+f"(d[1]), "+f"(d[2]), "+f"(d[3]), "+f"(d[4]), "+f"(d[5]), "+f"(d[6]), "+f"(d[7]), "+f"(d[8]), "+f"(d[9]), "+f"(d[10]), "+f"(d[11]), "+f"(d[12]), "+f"(d[13]), "+f"(d[14]), "+f"(d[15]), "+f"(d[16]), "+f"(d[17]), "+f"(d[18]), "+f"(d[19])
    : "r"(a[0]), "r"(a[1]), "r"(a[2]), "r"(a[3]), "l"(db), "r"(scale_d));
}
__device__ __forceinline__ void wgmma_n128_0(float (&d)[192], uint64_t da, uint64_t db) {
  asm volatile("{\n.reg .pred p;\nsetp.ne.b32 p, 0, 0;\n"
    "wgmma.mma_async.sync.aligned.m64n128k16.f32.bf16.bf16 {%0, %1, %2, %3, %4, %5, %6, %7, %8, %9, %10, %11, %12, %13, %14, %15, %16, %17, %18, %19, %20, %21, %22, %23, %24, %25, %26, %27, %28, %29, %30, %31, %32, %33, %34, %35, %36, %37, %38, %39, %40, %41, %42, %43, %44, %45, %46, %47, %48, %49, %50, %51, %52, %53, %54, %55, %56, %57, %58, %59, %60, %61, %62, %63}, %64, %65, p, 1, 1, 0, 1;\n}\n"
    : "=f"(d[128]), "=f"(d[129]), "=f"(d[130]), "=f"(d[131]), "=f"(d[132]), "=f"(d[133]), "=f"(d[134]), "=f"(d[135]), "=f"(d[136]), "=f"(d[137]), "=f"(d[138]), "=f"(d[139]), "=f"(d[140]), "=f"(d[141]), "=f"(d[142]), "=f"(d[143]), "=f"(d[144]), "=f"(d[145]), "=f"(d[146]), "=f"(d[147]), "=f"(d[148]), "=f"(d[149]), "=f"(d[150]), "=f"(d[151]), "=f"(d[152]), "=f"(d[153]), "=f"(d[154]), "=f"(d[155]), "=f"(d[156]), "=f"(d[157]), "=f"(d[158]), "=f"(d[159]), "=f"(d[160]), "=f"(d[161]), "=f"(d[162]), "=f"(d[163]), "=f"(d[164]), "=f"(d[165]), "=f"(d[166]), "=f"(d[167]), "=f"(d[168]), "=f"(d[169]), "=f"(d[170]), "=f"(d[171]), "=f"(d[172]), "=f"(d[173]), "=f"(d[174]), "=f"(d[175]), "=f"(d[176]), "=f"(d[177]), "=f"(d[178]), "=f"(d[179]), "=f"(d[180]), "=f"(d[181]), "=f"(d[182]), "=f"(d[183]), "=f"(d[184]), "=f"(d[185]), "=f"(d[186]), "=f"(d[187]), "=f"(d[188]), "=f"(d[189]), "=f"(d[190]), "=f"(d[191])
    : "l"(da), "l"(db));
}
__device__ __forceinline__ void wgmma_n128_rs(float (&d)[192], const uint32_t (&a)[4], uint64_t db, int scale_d) {
  asm volatile("{\n.reg .pred p;\nsetp.ne.b32 p, %69, 0;\n"
    "wgmma.mma_async.sync.aligned.m64n128k16.f32.bf16.bf16 {%0, %1, %2, %3, %4, %5, %6, %7, %8, %9, %10, %11, %12, %13, %14, %15, %16, %17, %18, %19, %20, %21, %22, %23, %24, %25, %26, %27, %28, %29, %30, %31, %32, %33, %34, %35, %36, %37, %38, %39, %40, %41, %42, %43, %44, %45, %46, %47, %48, %49, %50, %51, %52, %53, %54, %55, %56, %57, %58, %59, %60, %61, %62, %63}, {%64, %65, %66, %67}, %68, p, 1, 1, 1;\n}\n"
    : "+f"(d[128]), "+f"(d[129]), "+f"(d[130]), "+f"(d[131]), "+f"(d[132]), "+f"(d[133]), "+f"(d[134]), "+f"(d[135]), "+f"(d[136]), "+f"(d[137]), "+f"(d[138]), "+f"(d[139]), "+f"(d[140]), "+f"(d[141]), "+f"(d[142]), "+f"(d[143]), "+f"(d[144]), "+f"(d[145]), "+f"(d[146]), "+f"(d[147]), "+f"(d[148]), "+f"(d[149]), "+f"(d[150]), "+f"(d[151]), "+f"(d[152]), "+f"(d[153]), "+f"(d[154]), "+f"(d[155]), "+f"(d[156]), "+f"(d[157]), "+f"(d[158]), "+f"(d[159]), "+f"(d[160]), "+f"(d[161]), "+f"(d[162]), "+f"(d[163]), "+f"(d[164]), "+f"(d[165]), "+f"(d[166]), "+f"(d[167]), "+f"(d[168]), "+f"(d[169]), "+f"(d[170]), "+f"(d[171]), "+f"(d[172]), "+f"(d[173]), "+f"(d[174]), "+f"(d[175]), "+f"(d[176]), "+f"(d[177]), "+f"(d[178]), "+f"(d[179]), "+f"(d[180]), "+f"(d[181]), "+f"(d[182]), "+f"(d[183]), "+f"(d[184]), "+f"(d[185]), "+f"(d[186]), "+f"(d[187]), "+f"(d[188]), "+f"(d[189]), "+f"(d[190]), "+f"(d[191])
    : "r"(a[0]), "r"(a[1]), "r"(a[2]), "r"(a[3]), "l"(db), "r"(scale_d));
}
__device__ __forceinline__ void wgmma_n32_0(float (&d)[16], uint64_t da, uint64_t db) {
  asm volatile("{\n.reg .pred p;\nsetp.ne.b32 p, 0, 0;\n"
    "wgmma.mma_async.sync.aligned.m64n32k16.f32.bf16.bf16 {%0, %1, %2, %3, %4, %5, %6, %7, %8, %9, %10, %11, %12, %13, %14, %15}, %16, %17, p, 1, 1, 0, 1;\n}\n"
    : "=f"(d[0]), "=f"(d[1]), "=f"(d[2]), "=f"(d[3]), "=f"(d[4]), "=f"(d[5]), "=f"(d[6]), "=f"(d[7]), "=f"(d[8]), "=f"(d[9]), "=f"(d[10]), "=f"(d[11]), "=f"(d[12]), "=f"(d[13]), "=f"(d[14]), "=f"(d[15])
    : "l"(da), "l"(db));
}
__device__ __forceinline__ void wgmma_n32(float (&d)[16], uint64_t da, uint64_t db, int scale_d) {
  asm volatile("{\n.reg .pred p;\nsetp.ne.b32 p, %18, 0;\n"
    "wgmma.mma_async.sync.aligned.m64n32k16.f32.bf16.bf16 {%0, %1, %2, %3, %4, %5, %6, %7, %8, %9, %10, %11, %12, %13, %14, %15}, %16, %17, p, 1, 1, 0, 1;\n}\n"
    : "+f"(d[0]), "+f"(d[1]), "+f"(d[2]), "+f"(d[3]), "+f"(d[4]), "+f"(d[5]), "+f"(d[6]), "+f"(d[7]), "+f"(d[8]), "+f"(d[9]), "+f"(d[10]), "+f"(d[11]), "+f"(d[12]), "+f"(d[13]), "+f"(d[14]), "+f"(d[15])
    : "l"(da), "l"(db), "r"(scale_d));
}
__device__ __forceinline__ void wgmma_n8_t(float (&d)[4], uint64_t da, uint64_t db, int scale_d) {
  asm volatile("{\n.reg .pred p;\nsetp.ne.b32 p, %6, 0;\n"
    "wgmma.mma_async.sync.aligned.m64n8k16.f32.bf16.bf16 {%0, %1, %2, %3}, %4, %5, p, 1, 1, 1, 0;\n}\n"
    : "+f"(d[0]), "+f"(d[1]), "+f"(d[2]), "+f"(d[3])
    : "l"(da), "l"(db), "r"(scale_d));
}
__device__ __forceinline__ void wgmma_n128_rs0(float (&d)[192], const uint32_t (&a)[4], uint64_t db) {
  asm volatile("{\n.reg .pred p;\nsetp.ne.b32 p, 0, 0;\n"
    "wgmma.mma_async.sync.aligned.m64n128k16.f32.bf16.bf16 {%0, %1, %2, %3, %4, %5, %6, %7, %8, %9, %10, %11, %12, %13, %14, %15, %16, %17, %18, %19, %20, %21, %22, %23, %24, %25, %26, %27, %28, %29, %30, %31, %32, %33, %34, %35, %36, %37, %38, %39, %40, %41, %42, %43, %44, %45, %46, %47, %48, %49, %50, %51, %52, %53, %54, %55, %56, %57, %58, %59, %60, %61, %62, %63}, {%64, %65, %66, %67}, %68, p, 1, 1, 1;\n}\n"
    : "=f"(d[128]), "=f"(d[129]), "=f"(d[130]), "=f"(d[131]), "=f"(d[132]), "=f"(d[133]), "=f"(d[134]), "=f"(d[135]), "=f"(d[136]), "=f"(d[137]), "=f"(d[138]), "=f"(d[139]), "=f"(d[140]), "=f"(d[141]), "=f"(d[142]), "=f"(d[143]), "=f"(d[144]), "=f"(d[145]), "=f"(d[146]), "=f"(d[147]), "=f"(d[148]), "=f"(d[149]), "=f"(d[150]), "=f"(d[151]), "=f"(d[152]), "=f"(d[153]), "=f"(d[154]), "=f"(d[155]), "=f"(d[156]), "=f"(d[157]), "=f"(d[158]), "=f"(d[159]), "=f"(d[160]), "=f"(d[161]), "=f"(d[162]), "=f"(d[163]), "=f"(d[164]), "=f"(d[165]), "=f"(d[166]), "=f"(d[167]), "=f"(d[168]), "=f"(d[169]), "=f"(d[170]), "=f"(d[171]), "=f"(d[172]), "=f"(d[173]), "=f"(d[174]), "=f"(d[175]), "=f"(d[176]), "=f"(d[177]), "=f"(d[178]), "=f"(d[179]), "=f"(d[180]), "=f"(d[181]), "=f"(d[182]), "=f"(d[183]), "=f"(d[184]), "=f"(d[185]), "=f"(d[186]), "=f"(d[187]), "=f"(d[188]), "=f"(d[189]), "=f"(d[190]), "=f"(d[191])
    : "r"(a[0]), "r"(a[1]), "r"(a[2]), "r"(a[3]), "l"(db));
}
__device__ __forceinline__ void wgmma_n256_rs(float (&d)[192], const uint32_t (&a)[4], uint64_t db, int scale_d) {
  asm volatile("{\n.reg .pred p;\nsetp.ne.b32 p, %133, 0;\n"
    "wgmma.mma_async.sync.aligned.m64n256k16.f32.bf16.bf16 {%0, %1, %2, %3, %4, %5, %6, %7, %8, %9, %10, %11, %12, %13, %14, %15, %16, %17, %18, %19, %20, %21, %22, %23, %24, %25, %26, %27, %28, %29, %30, %31, %32, %33, %34, %35, %36, %37, %38, %39, %40, %41, %42, %43, %44, %45, %46, %47, %48, %49, %50, %51, %52, %53, %54, %55, %56, %57, %58, %59, %60, %61, %62, %63, %64, %65, %66, %67, %68, %69, %70, %71, %72, %73, %74, %75, %76, %77, %78, %79, %80, %81, %82, %83, %84, %85, %86, %87, %88, %89, %90, %91, %92, %93, %94, %95, %96, %97, %98, %99, %100, %101, %102, %103, %104, %105, %106, %107, %108, %109, %110, %111, %112, %113, %114, %115, %116, %117, %118, %119, %120, %121, %122, %123, %124, %125, %126, %127}, {%128, %129, %130, %131}, %132, p, 1, 1, 1;\n}\n"
    : "+f"(d[0]), "+f"(d[1]), "+f"(d[2]), "+f"(d[3]), "+f"(d[4]), "+f"(d[5]), "+f"(d[6]), "+f"(d[7]), "+f"(d[8]), "+f"(d[9]), "+f"(d[10]), "+f"(d[11]), "+f"(d[12]), "+f"(d[13]), "+f"(d[14]), "+f"(d[15]), "+f"(d[16]), "+f"(d[17]), "+f"(d[18]), "+f"(d[19]), "+f"(d[20]), "+f"(d[21]), "+f"(d[22]), "+f"(d[23]), "+f"(d[24]), "+f"(d[25]), "+f"(d[26]), "+f"(d[27]), "+f"(d[28]), "+f"(d[29]), "+f"(d[30]), "+f"(d[31]), "+f"(d[32]), "+f"(d[33]), "+f"(d[34]), "+f"(d[35]), "+f"(d[36]), "+f"(d[37]), "+f"(d[38]), "+f"(d[39]), "+f"(d[40]), "+f"(d[41]), "+f"(d[42]), "+f"(d[43]), "+f"(d[44]), "+f"(d[45]), "+f"(d[46]), "+f"(d[47]), "+f"(d[48]), "+f"(d[49]), "+f"(d[50]), "+f"(d[51]), "+f"(d[52]), "+f"(d[53]), "+f"(d[54]), "+f"(d[55]), "+f"(d[56]), "+f"(d[57]), "+f"(d[58]), "+f"(d[59]), "+f"(d[60]), "+f"(d[61]), "+f"(d[62]), "+f"(d[63]), "+f"(d[64]), "+f"(d[65]), "+f"(d[66]), "+f"(d[67]), "+f"(d[68]), "+f"(d[69]), "+f"(d[70]), "+f"(d[71]), "+f"(d[72]), "+f"(d[73]), "+f"(d[74]), "+f"(d[75]), "+f"(d[76]), "+f"(d[77]), "+f"(d[78]), "+f"(d[79]), "+f"(d[80]), "+f"(d[81]), "+f"(d[82]), "+f"(d[83]), "+f"(d[84]), "+f"(d[85]), "+f"(d[86]), "+f"(d[87]), "+f"(d[88]), "+f"(d[89]), "+f"(d[90]), "+f"(d[91]), "+f"(d[92]), "+f"(d[93]), "+f"(d[94]), "+f"(d[95]), "+f"(d[96]), "+f"(d[97]), "+f"(d[98]), "+f"(d[99]), "+f"(d[100]), "+f"(d[101]), "+f"(d[102]), "+f"(d[103]), "+f"(d[104]), "+f"(d[105]), "+f"(d[106]), "+f"(d[107]), "+f"(d[108]), "+f"(d[109]), "+f"(d[110]), "+f"(d[111]), "+f"(d[112]), "+f"(d[113]), "+f"(d[114]), "+f"(d[115]), "+f"(d[116]), "+f"(d[117]), "+f"(d[118]), "+f"(d[119]), "+f"(d[120]), "+f"(d[121]), "+f"(d[122]), "+f"(d[123]), "+f"(d[124]), "+f"(d[125]), "+f"(d[126]), "+f"(d[127])
    : "r"(a[0]), "r"(a[1]), "r"(a[2]), "r"(a[3]), "l"(db), "r"(scale_d));
}
__device__ __forceinline__ void wgmma_n256_rs0(float (&d)[192], const uint32_t (&a)[4], uint64_t db) {
  asm volatile("{\n.reg .pred p;\nsetp.ne.b32 p, 0, 0;\n"
    "wgmma.mma_async.sync.aligned.m64n256k16.f32.bf16.bf16 {%0, %1, %2, %3, %4, %5, %6, %7, %8, %9, %10, %11, %12, %13, %14, %15, %16, %17, %18, %19, %20, %21, %22, %23, %24, %25, %26, %27, %28, %29, %30, %31, %32, %33, %34, %35, %36, %37, %38, %39, %40, %41, %42, %43, %44, %45, %46, %47, %48, %49, %50, %51, %52, %53, %54, %55, %56, %57, %58, %59, %60, %61, %62, %63, %64, %65, %66, %67, %68, %69, %70, %71, %72, %73, %74, %75, %76, %77, %78, %79, %80, %81, %82, %83, %84, %85, %86, %87, %88, %89, %90, %91, %92, %93, %94, %95, %96, %97, %98, %99, %100, %101, %102, %103, %104, %105, %106, %107, %108, %109, %110, %111, %112, %113, %114, %115, %116, %117, %118, %119, %120, %121, %122, %123, %124, %125, %126, %127}, {%128, %129, %130, %131}, %132, p, 1, 1, 1;\n}\n"
    : "=f"(d[0]), "=f"(d[1]), "=f"(d[2]), "=f"(d[3]), "=f"(d[4]), "=f"(d[5]), "=f"(d[6]), "=f"(d[7]), "=f"(d[8]), "=f"(d[9]), "=f"(d[10]), "=f"(d[11]), "=f"(d[12]), "=f"(d[13]), "=f"(d[14]), "=f"(d[15]), "=f"(d[16]), "=f"(d[17]), "=f"(d[18]), "=f"(d[19]), "=f"(d[20]), "=f"(d[21]), "=f"(d[22]), "=f"(d[23]), "=f"(d[24]), "=f"(d[25]), "=f"(d[26]), "=f"(d[27]), "=f"(d[28]), "=f"(d[29]), "=f"(d[30]), "=f"(d[31]), "=f"(d[32]), "=f"(d[33]), "=f"(d[34]), "=f"(d[35]), "=f"(d[36]), "=f"(d[37]), "=f"(d[38]), "=f"(d[39]), "=f"(d[40]), "=f"(d[41]), "=f"(d[42]), "=f"(d[43]), "=f"(d[44]), "=f"(d[45]), "=f"(d[46]), "=f"(d[47]), "=f"(d[48]), "=f"(d[49]), "=f"(d[50]), "=f"(d[51]), "=f"(d[52]), "=f"(d[53]), "=f"(d[54]), "=f"(d[55]), "=f"(d[56]), "=f"(d[57]), "=f"(d[58]), "=f"(d[59]), "=f"(d[60]), "=f"(d[61]), "=f"(d[62]), "=f"(d[63]), "=f"(d[64]), "=f"(d[65]), "=f"(d[66]), "=f"(d[67]), "=f"(d[68]), "=f"(d[69]), "=f"(d[70]), "=f"(d[71]), "=f"(d[72]), "=f"(d[73]), "=f"(d[74]), "=f"(d[75]), "=f"(d[76]), "=f"(d[77]), "=f"(d[78]), "=f"(d[79]), "=f"(d[80]), "=f"(d[81]), "=f"(d[82]), "=f"(d[83]), "=f"(d[84]), "=f"(d[85]), "=f"(d[86]), "=f"(d[87]), "=f"(d[88]), "=f"(d[89]), "=f"(d[90]), "=f"(d[91]), "=f"(d[92]), "=f"(d[93]), "=f"(d[94]), "=f"(d[95]), "=f"(d[96]), "=f"(d[97]), "=f"(d[98]), "=f"(d[99]), "=f"(d[100]), "=f"(d[101]), "=f"(d[102]), "=f"(d[103]), "=f"(d[104]), "=f"(d[105]), "=f"(d[106]), "=f"(d[107]), "=f"(d[108]), "=f"(d[109]), "=f"(d[110]), "=f"(d[111]), "=f"(d[112]), "=f"(d[113]), "=f"(d[114]), "=f"(d[115]), "=f"(d[116]), "=f"(d[117]), "=f"(d[118]), "=f"(d[119]), "=f"(d[120]), "=f"(d[121]), "=f"(d[122]), "=f"(d[123]), "=f"(d[124]), "=f"(d[125]), "=f"(d[126]), "=f"(d[127])
    : "r"(a[0]), "r"(a[1]), "r"(a[2]), "r"(a[3]), "l"(db));
}

constexpr int SLOT = 16384;
constexpr int VB = 4 * SLOT, PH = 0, XS = 6;
constexpr int SM_SD = 13 * SLOT;
constexpr int SM_BAR = SM_SD + 8192;
constexpr int SM_RS = SM_BAR + 1024;
constexpr int SM_AP = SM_RS + 640;
constexpr int SM_BP = SM_AP + 2048;
constexpr int SM_EPOCH = SM_BP + 6144;
constexpr int SM_TOTAL = SM_EPOCH + 16;
constexpr int FM = 0, FT = 16, FW = 30, CM = 46, CT = 62, CW = 76, B_EF = 92, B_STAT = 93, B_KVF = 94, B_HALO = 95,
              B_KVDONE = 96, B_OH0 = 97, B_OH1 = 98, B_XH0 = 99, B_XDONE = 100, B_WFD = 101, B_XT = 102, B_OF0 = 103, B_KVF1 = 104, B_KVS = 105, B_RAW = 106  , B_X0 = 108, B_KVS0 = 109;
constexpr uint64_t BAR_LG = 0x00043333330004ull;
#define BA(i) (bar + (i) * 8)
#define REL2(i) release2c(SB0 + SM_BAR + (i) * 8)
constexpr int NF = 3, ND = 13, NR = 0, NWOP = 48, NAOP = 38;
constexpr bool EF_USED = false;
constexpr uint64_t TL_A = 0x6278627862786ull, TL_B = 0xa9c3ba9c3ba9cull, WO_A = 0x76b24038b51403ffull, WO_B = 0x8c5a197c6a297c8bull;
__constant__ uint32_t c_wop[NWOP + 1] = {0xeb0009, 0x186b8000, 0x6c0112, 0x1aec011a, 0x6c8224, 0x22ec822b, 0x18170330, 0x18178442, 0x18180554, 0x18188660, 0x18190772, 0x18198884, 0x181a0990, 0x181a8aa2, 0x181b0bb4, 0x181b8cc0, 0xaed10fc, 0xa9711e9, 0x181c0dd2, 0xa9792da, 0x129813cb, 0x181c8ee4, 0x181d0ff0, 0x109d94b3, 0x109f15ac, 0x109f9699, 0x10a0178a, 0x10a0987b, 0x10a11963, 0x10a19a5c, 0x10a21b49, 0x10a29c3a, 0x9231e0b, 0x9239f18, 0x1124202c, 0x13242137, 0x1124a249, 0x1324a352, 0x1125246a, 0x13252576, 0x1127268c, 0x1127a797, 0x112828a9, 0x1128a9b1, 0x11292aca, 0x13292bd5, 0x112a2cec, 0x132a2df8, 0};
__constant__ uint32_t c_aop[NAOP + 1] = {0x6d8228, 0x170336, 0x178447, 0x180558, 0x188666, 0x190777, 0x198888, 0x1a0996, 0x1a8aa7, 0x1b0bb8, 0x1b8cc6, 0x1c0dd7, 0x1c8ee8, 0x1d0ff6, 0x1d93c2, 0x1f14b6, 0x1f95a8, 0x201697, 0x209782, 0x211876, 0x219968, 0x221a57, 0x229b42, 0x231c36, 0xa3a023, 0xb12130, 0x2b12244, 0x2b12351, 0x2b12465, 0xa6257b, 0xa6a688, 0xa72793, 0xa7a8a0, 0xa829b4, 0xa8aac2, 0xa9abdb, 0x2a9ace6, 0xaaadf7, 0};
__constant__ uint32_t c_map[64] = {4, 5, 6, 7, 0, 16, 32, 48, 64, 80, 96, 112, 1, 17, 33, 49, 65, 81, 97, 113, 2, 18, 34, 50, 66, 82, 98, 114, 3, 19, 35, 51, 67, 83, 99, 115, 20, 36, 52, 68, 84, 100, 116, 21, 37, 53, 69, 85, 101, 117, 22, 38, 54, 70, 86, 102, 118, 23, 39, 55, 71, 87, 103, 119};
enum { MAP_WF = 0, MAP_WA = 2, MAP_WB = 4, MAP_WOA = 6, MAP_WOB = 8, MAP_X0 = 10, MAP_X = 11, MAP_O = 12, MAP_PHI = 13, NMAP = 14 };
struct Maps { CUtensorMap m[NMAP]; };

#define PL 2
#define PROFL(a, b)
#define SUBS 16
#define CHW 4
#define SUBS1 16
#define XRAT 10
#define XRN 4
#define BT1 1
#define ST1 8
#define X0AT 1
#define W1DL 400
#define SKA 0
#define SKB 0
#define BPRE 0
#define XST 0
#define WH 4
#define PFM 3
#define PFS 2
#define NLAYERS 4
constexpr float L2E = 1.4426950408889634f;

#define D128(lo) desc64(lo, 0x40000040u)
struct Ctx { uint32_t zero, boff; const bf16* x0; bf16* out; };
#define BLK_CTX() \
  uint32_t bid_; asm volatile("mov.u32 %0, %%ctaid.x;" : "=r"(bid_)); \
  bid_ -= c.boff; \
  const uint32_t gr_ = c_map[bid_ >> 1]; \
  const int cr = bid_ & 1, g = gr_ & 7, rb = (gr_ >> 3) + cr, m0 = rb * 128; \
  const uint32_t sb = SB0 + (cr << 24); \
  const uint32_t bar = sb + SM_BAR; \
  (void)cr; (void)g; (void)rb; (void)m0; (void)bar;
extern __shared__ uint8_t smem_raw[];
constexpr uint32_t SB0 = 1024;

#define PHASE_CTX() \
  BLK_CTX(); \
  int tid_ = threadIdx.x; asm volatile("" : "+r"(tid_)); \
  const int lane = tid_ & 31, cw = (tid_ >> 5) - 4, wg = cw >> 2, wq = cw & 3, gq = lane >> 2, t = lane & 3, wrow0 = cw * 16; \
  const int lrow = (lane & 7) + ((lane >> 3) & 1) * 8, lchk = lane >> 4; \
  const bool elected = (tid_ & 127) == 0; \
  const uint32_t rowo = (wrow0 + lrow) * 128, X = (lchk ^ (lane & 7)) << 4; \
  const uint32_t Y = (wrow0 + (lane & 7)) * 128 + (((lane >> 3) ^ (lane & 7)) << 4); \
  const size_t gfr = (size_t)(m0 + wrow0 + gq) * D_ + g * 128 + 8 * t; \
  (void)bar; (void)wq; (void)gq; (void)lrow; (void)lchk; (void)elected; (void)wrow0; (void)wg; (void)rowo; (void)X; (void)t; (void)Y; (void)gfr;
#define MMA_CTX() \
  const uint32_t wu = __shfl_sync(0xffffffffu, wg, 0); \
  const uint32_t dA0 = ((SB0 >> 4) | (1u << 16)) + wu * 512, dB0 = (SB0 >> 4) | (512u << 16); \
  const uint32_t par = layer & 1;

__device__ __forceinline__ void slab_out_half(uint32_t slot, bf16* dst, int wrow0, int lane) {
  const int r0 = lane >> 3, ch = lane & 7;
  const uint32_t src = slot + (wrow0 + r0) * 128;
  uint4 v[4];
#pragma unroll
  for (int i = 0; i < 4; ++i) v[i] = lds128(src + i * 512 + (((ch ^ (4 * i + r0)) & 7) << 4));
  dst += (size_t)(wrow0 + r0) * D_ + ch * 8;
#pragma unroll
  for (int i = 0; i < 4; ++i) *reinterpret_cast<uint4*>(dst + (size_t)i * 4 * D_) = v[i];
}

__device__ __forceinline__ void consumer(const Ctx& c) {
  float acc[192];
  uint32_t xf[4][4];
  uint32_t xp[8][4];
  {
    PHASE_CTX();
    const unsigned int epoch = ld_relaxed(&g_epoch);
    PROFT(tid_ == 128, 0);
    const uint32_t wu = __shfl_sync(0xffffffffu, wg, 0);
    if (tid_ < 128 + 8) sts128(sb + SM_AP + lane * 16, make_uint4(0x3F803F80u, 0x3F803F80u, 0x3F803F80u, 0x3F803F80u));
#pragma unroll 1
    for (int it = 0; it < 2; ++it) {
      float p[4][16];
      mbar_wait(BA(B_RAW + it), 0);
      PROFT(tid_ == 128, it ? 15 : 2);
      const uint32_t da = ((SB0 >> 4) | (1u << 16)) + (wu ? 9 + it : 2 * it) * 1024, db = (SB0 + SM_SD) >> 4;
      wgmma_fence();
#pragma unroll
      for (int h = 0; h < 4; ++h) wgmma_n32_0(p[h], D128(da + (h >> 1) * 512 + (h & 1) * 4), desc64(db + h * 128, 0x80000020u));
#pragma unroll
      for (int h = 0; h < 4; ++h) wgmma_n32(p[h], D128(da + (h >> 1) * 512 + (h & 1) * 4 + 2), desc64(db + h * 128 + 64, 0x80000020u), 1);
      wgmma_commit();
      wgmma_wait<0>();
#pragma unroll
      for (int i = 0; i < 64; ++i) asm volatile("" : "+f"(p[i >> 4][i & 15]) :: "memory");
      const uint32_t base = sb + (wg ? 9 + it : 2 * it) * SLOT + (wq * 16 + gq) * 128;
      uint32_t w[4][4][2];
#pragma unroll
      for (int i = 0; i < 32; ++i) w[i >> 3][(i >> 1) & 3][i & 1] = pack_bf16(p[i >> 3][2 * (i & 7)], p[i >> 3][2 * (i & 7) + 1]);
      if (wu) {
#pragma unroll
        for (int i = 0; i < 8; ++i)
          sts128(base + (i >> 2) * 8192 + (i & 1) * 1024 + (((((i >> 1) & 1) * 4 + t) ^ gq) << 4), make_uint4(w[i >> 1][0][i & 1], w[i >> 1][1][i & 1], w[i >> 1][2][i & 1], w[i >> 1][3][i & 1]));
      } else {
#pragma unroll
        for (int i = 0; i < 16; ++i)
          sts64(base + (i >> 3) * 8192 + (i & 1) * 1024 + ((((t & 1) * 4 + ((i >> 1) & 3)) ^ gq) << 4) + (t >> 1) * 8, w[(i >> 3) * 2][(i >> 1) & 3][i & 1], w[(i >> 3) * 2 + 1][(i >> 1) & 3][i & 1]);
      }
      fence_async_smem();
      __syncwarp();
      if (it == cr && lane == 0) mbar_arrive(BA(B_WFD));
    }
    if (tid_ == 128) sts_f(sb + SM_EPOCH, __uint_as_float(epoch & 1));
#pragma unroll
    for (int i = 0; i < 32; ++i) xp[i >> 2][i & 3] = 0u;
    nbar<1, 256>();
    PROFT(tid_ == 128, 13);
    mbar_wait(BA(FM + cr), 0);
    float cs[3][4];
    wgmma_fence();
#pragma unroll
    for (int ks = 0; ks < 4; ++ks)
#pragma unroll
      for (int i = 0; i < 3; ++i) {
        const uint32_t bx = (i == 0 ? 2 * cr * 1024 : i == 1 ? (2 * cr + 1) * 1024 : (9 + cr) * 1024) + wu * 512;
        wgmma_n8_t(cs[i], D128(((SB0 >> 4) | (512u << 16)) + bx + ks * 128), desc64((SB0 + SM_AP) >> 4, 0), ks != 0);
      }
    wgmma_commit();
    mbar_wait(BA(FM), 0);
#pragma unroll
    for (int k = 0; k < 4; ++k) ldsm_x4(xf[k][0], xf[k][1], xf[k][2], xf[k][3], sb + XS * SLOT + rowo + (X ^ (k << 5)));
    wgmma_wait<0>();
#pragma unroll
    for (int i = 0; i < 12; ++i) asm volatile("" : "+f"(cs[i >> 2][i & 3]) :: "memory");
    if (t < 2) {
#pragma unroll
      for (int i = 0; i < 3; ++i) red_add1(g_cs + (epoch & 1) * 6144 + g * 384 + i * 128 + wg * 64 + wq * 16 + gq + t * 8, t ? cs[i][2] : cs[i][0]);
    }
    PROFT(tid_ == 128, 14);
  }
#pragma unroll 1
  for (int layer = 0;; ++layer) {
    {
      wgmma_fence();
      wgmma_n256_rs0(acc, xf[0], D128((SB0 >> 4) | (512u << 16)));
#pragma unroll
      for (int k = 1; k < 4; ++k) wgmma_n256_rs(acc, xf[k], D128(((SB0 >> 4) | (512u << 16)) + k * 128), 1);
      wgmma_commit();
      PHASE_CTX();
      MMA_CTX();
      {
        const uint32_t ep = __float_as_uint(lds_f(sb + SM_EPOCH));
        if (layer == 0) {
          mbar_wait(BA(B_X0), 0);
#pragma unroll
          for (int i = 0; i < 8; ++i) ldsm_x4(xp[i][0], xp[i][1], xp[i][2], xp[i][3], sb + (11 + (i >> 2)) * SLOT + (Y ^ ((i & 2) << 5)) + (i & 1) * 1024);
          if (lane == ((xp[0][0] ^ xp[1][0] ^ xp[2][0] ^ xp[3][0] ^ xp[7][0]) & c.zero)) REL2(B_XT);
        } else {
#pragma unroll
          for (int i = 0; i < 8; ++i) stsm_x4(sb + (XS + (i >> 2)) * SLOT + (Y ^ ((i & 2) << 5)) + (i & 1) * 1024, xp[i][0], xp[i][1], xp[i][2], xp[i][3]);
        }
        float s0 = 0.f, s1 = 0.f, q0 = 0.f, q1 = 0.f;
        auto stats = [&](int j0, int j1) {
#pragma unroll
          for (int j = j0; j < j1; ++j) {
            const uint32_t u0 = xp[(j >> 2) * 2][j & 3], u1 = xp[(j >> 2) * 2 + 1][j & 3];
            s0 += bf_lo(u0) + bf_hi(u0); s1 += bf_lo(u1) + bf_hi(u1);
            q0 = fmaf(bf_lo(u0), bf_lo(u0), fmaf(bf_hi(u0), bf_hi(u0), q0)); q1 = fmaf(bf_lo(u1), bf_lo(u1), fmaf(bf_hi(u1), bf_hi(u1), q1));
          }
        };
        stats(0, ST1);
        fence_async_smem();
        nbar_dyn(3 + wu + (__float_as_uint(s0 + s1 + q0 + q1) & c.zero), 128);
        mbar_wait(BA(FM + 1), par);
        wgmma_fence();
#pragma unroll
        for (int k = 0; k < 4; ++k) wgmma_n256(acc, D128(dA0 + (XS + 1) * 1024 + k * 2), D128(dB0 + 2048 + k * 128), 1);
        wgmma_commit();
        wgmma_wait<1>();
#pragma unroll
        for (int i = 4; i < 8; ++i) stg128_p(layer, g_x + gfr + (i & 1) * 8 * D_ + (i >> 1) * 32, xp[i][0], xp[i][1], xp[i][2], xp[i][3]);
        {
          uint32_t zc; asm volatile("mov.u32 %0, %%clock;" : "=r"(zc) :: "memory");
          q0 += __uint_as_float(zc & c.zero); q1 += __uint_as_float(zc & c.zero); s0 += __uint_as_float(zc & c.zero); s1 += __uint_as_float(zc & c.zero);
        }
        stats(ST1, 16);
        wgmma_fence();
        wgmma_n128_0(acc, D128(dA0 + XS * 1024), D128(dB0 + 9 * 1024));
#pragma unroll
        for (int k = 1; k < 4; ++k) wgmma_n128(acc, D128(dA0 + XS * 1024 + k * 2), D128(dB0 + 9 * 1024 + k * 128), 1);
        wgmma_commit();
        const bool od = t & 1;
        float sa = od ? s1 : s0, qa = od ? q1 : q0;
        sa += __shfl_xor_sync(0xffffffffu, od ? s0 : s1, 1);
        qa += __shfl_xor_sync(0xffffffffu, od ? q0 : q1, 1);
        wgmma_fence();
#pragma unroll
        for (int k = 0; k < 4; ++k) wgmma_n128(acc, D128(dA0 + (XS + 1) * 1024 + k * 2), D128(dB0 + 10 * 1024 + k * 128), 1);
        wgmma_commit();
        sa += __shfl_xor_sync(0xffffffffu, sa, 2);
        qa += __shfl_xor_sync(0xffffffffu, qa, 2);
        red_add2_p(t < 2, reinterpret_cast<float*>(g_stats + (ep * 4 + layer) * S_ + m0 + wrow0 + gq + t * 8), sa, qa);
        __syncwarp();
        if (lane == 0) mbar_arrive(BA(B_XDONE));
        wgmma_wait<1>();
        if (elected) REL2(CM);
      }
      uint32_t s = 2;
#pragma unroll 1
      for (int i = 2; i < NF; ++i) {
        PROFL(tid_ == 128 && layer == PL + 1, 244 + 2 * i);
        mbar_wait(BA(FM + i), par);
        PROFL(tid_ == 128 && layer == PL + 1, 245 + 2 * i);
        const uint32_t da = dA0 + (XS + s) * 1024, dk = dB0 + s * 2048, dq = dB0 + (9 + s) * 1024;
        wgmma_fence();
#pragma unroll
        for (int k = 0; k < 4; ++k) wgmma_n128(acc, D128(da + k * 2), D128(dq + k * 128), 1);
        wgmma_commit();
        wgmma_wait<1>();
        if (elected) REL2(CM + i - 1);
        wgmma_fence();
#pragma unroll
        for (int k = 0; k < 4; ++k) wgmma_n256(acc, D128(da + k * 2), D128(dk + k * 128), 1);
        wgmma_commit();
        if (++s == 3) s = 0;
      }
#pragma unroll 1
      for (int i = NF; i < 15; ++i) {
        mbar_wait(BA(FM + i), par);
        const uint32_t da = dA0 + (XS + s) * 1024, dk = dB0 + s * 2048;
        wgmma_fence();
#pragma unroll
        for (int k = 0; k < 4; ++k) wgmma_n256(acc, D128(da + k * 2), D128(dk + k * 128), 1);
        wgmma_commit();
        wgmma_wait<1>();
        if (elected) REL2(CM + i - 1);
        if (++s == 3) s = 0;
      }
      {
        const uint64_t dap = desc64(((SB0 + SM_AP) >> 4) + wu * 64, 8), dbp = make_desc_ns(SB0 + SM_BP, 0, 128);
        mbar_wait(BA(B_STAT), par);
        mbar_wait(BA(FM + 15), par);
        PROFT(tid_ == 128, layer * 16 + 9);
        wgmma_fence();
        wgmma_n256_k(acc, dap, dbp, 1);
#pragma unroll
        for (int k = 0; k < 4; ++k) wgmma_n256(acc, D128(dA0 + XS * 1024 + k * 2), D128(dB0 + k * 128), 1);
        wgmma_commit();
        wgmma_wait<1>();
        if (elected) REL2(CM + 14);
        mbar_wait(BA(FT), par);
        wgmma_fence();
        wgmma_n128_k(acc, dap, dbp + 256, 1);
#pragma unroll
        for (int k = 0; k < 4; ++k) wgmma_n128(acc, D128(dA0 + (uint32_t)(TL_A & 15) * 1024 + k * 2), D128(dB0 + (uint32_t)(TL_B & 15) * 1024 + k * 128), 1);
        wgmma_commit();
        wgmma_wait<1>();
        if (elected) REL2(CM + 15);
#pragma unroll
        for (int i = 0; i < 128; ++i) asm volatile("" : "+f"(acc[i]) :: "memory");
      }
    }
    uint32_t of[8][4], o1[4][4];
    {
      PHASE_CTX();
      MMA_CTX();
      PROFT(tid_ == 128, layer * 16 + 1);
      PROFT(lane == 0 && layer == PL, 192 + cw);
      PROFT(tid_ == 128 && layer == PL, 160);
      uint64_t ta = (TL_A >> 4), tw = TL_B >> 4;
      uint32_t da, db, dz = dA0;
      auto sub = [&](int n) {
        const int j = n >> 2, k = n & 3;
        if (k == 0) {
          dz += c.zero;
          da = dz + ((uint32_t)ta & 15) * 1024; db = dB0 + ((uint32_t)tw & 15) * 1024;
          ta >>= 4; tw >>= 4;
          mbar_wait(BA(FT + j), par);
          wgmma_fence();
        }
        wgmma_n128(acc, D128(da + k * 2), D128(db + k * 128), 1);
        if (k == 3) {
          wgmma_commit();
          wgmma_wait<1>();
          if (elected) REL2(CT + j - 1);
        }
      };
      auto run = [&](int j0, int j1) {
#pragma unroll 1
        for (int j = j0; j < j1; ++j) {
          mbar_wait(BA(FT + j), par);
          da = dA0 + ((uint32_t)ta & 15) * 1024; db = dB0 + ((uint32_t)tw & 15) * 1024;
          ta >>= 4; tw >>= 4;
          wgmma_fence();
#pragma unroll
          for (int k = 0; k < 4; ++k) wgmma_n128(acc, D128(da + k * 2), D128(db + k * 128), 1);
          wgmma_commit();
          wgmma_wait<1>();
          if (elected) REL2(CT + j - 1);
        }
        ta = TL_A >> (4 * j1); tw = TL_B >> (4 * j1);
      };
      auto rest = [&](int j0, int sk) {
        if (sk) {
          run(j0, ND - sk);
          if (wu == 0) nbar<6, 256>();
          j0 = ND - sk;
        }
        run(j0, ND);
        if (sk && wu) asm volatile("bar.arrive 6, 256;" ::: "memory");
      };
      auto rest_end = [&]() {
        wgmma_wait<0>();
        if (elected) REL2(CT + ND - 1);
#pragma unroll
        for (int i = 128; i < 192; ++i) asm volatile("" : "+f"(acc[i]) :: "memory");
      };
      auto wo0 = [&]() {
        wgmma_fence();
        wgmma_n128_rs0(acc, of[0], D128(dB0 + (uint32_t)(WO_B & 15) * 1024));
#pragma unroll
        for (int k = 1; k < 4; ++k) wgmma_n128_rs(acc, of[k], D128(dB0 + (uint32_t)(WO_B & 15) * 1024 + k * 128), 1);
        wgmma_commit();
      };
      const float rs0 = lds_f(sb + SM_RS + (16 + wrow0 + gq) * 4), rs1 = lds_f(sb + SM_RS + (24 + wrow0 + gq) * 4);
#define EPOCH() __float_as_uint(lds_f(sb + SM_EPOCH))
      mbar_wait(BA(CM + 14), par);
      if (par) {
        uint32_t kk[8][4], kp[8][4], vf[2][2][4][4];
        int sn = 4;
        float rj[4];
#pragma unroll
        for (int nt = 0; nt < 4; ++nt) rj[nt] = lds_f(sb + SM_RS + (wrow0 + nt * 8 + 2 * t + (gq & 1)) * 4);
#pragma unroll
        for (int i = 0; i < 4 * BT1; ++i) sub(sn++);
        {
          uint32_t vv[8][4];
#pragma unroll
          for (int jp = 0; jp < 8; ++jp) {
            kk[jp][0] = pack_bf16(acc[8 * jp], acc[8 * jp + 1]); kk[jp][1] = pack_bf16(acc[8 * jp + 4], acc[8 * jp + 5]);
            kk[jp][2] = pack_bf16(acc[8 * jp + 2], acc[8 * jp + 3]); kk[jp][3] = pack_bf16(acc[8 * jp + 6], acc[8 * jp + 7]);
#pragma unroll
            for (int i = 0; i < 4; ++i) vv[jp][i] = pack_bf16(acc[64 + 8 * jp + 2 * i], acc[65 + 8 * jp + 2 * i]);
          }
          if (cw == 7) {
            uint32_t* const hbuf = g_halo + (size_t)(((layer >> 1) * 17 + rb + 1) * 8 + g) * 2048;
#pragma unroll
            for (int jp = 0; jp < 8; ++jp) stg128(hbuf + jp * 128 + lane * 4, kk[jp][0], kk[jp][1], kk[jp][2], kk[jp][3]);
#pragma unroll
            for (int i = 0; i < 32; ++i) hbuf[1024 + (i >> 4) * 512 + (gq + (i & 1) * 8) * 32 + ((((i >> 1) & 7) ^ gq) << 2) + t] = vv[i >> 2][i & 3];
            __syncwarp();
            if (lane == 0) mbar_arrive(BA(B_OF0));
          }
#pragma unroll
          for (int jp = 0; jp < 8; ++jp) {
            sub(sn++);
            stsm_x4(sb + VB + (jp >> 2) * SLOT + rowo + (X ^ ((jp & 3) << 5)), vv[jp][0], vv[jp][1], vv[jp][2], vv[jp][3]);
          }
        }
        PROFT(tid_ == 128, layer * 16 + 2);
        const int e = gq & 1;
        float f0[4], f1[4], b0[4], b1[4];
#pragma unroll
        for (int nt = 0; nt < 4; ++nt) {
          const int kx = nt * 8 + 2 * t + e;
          const bool okk = (m0 + wrow0 + kx) >= 16;
          const int d0 = kx - gq, d1 = d0 - 8;
          const bool m0_ = okk && d0 >= 2 && d0 <= 16, m1_ = okk && d1 >= 2 && d1 <= 16;
          f0[nt] = m0_ ? rj[nt] * rs0 * (0.17677669529663687f * L2E) : 0.f;
          f1[nt] = m1_ ? rj[nt] * rs1 * (0.17677669529663687f * L2E) : 0.f;
          b0[nt] = m0_ ? 0.f : -1e30f; b1[nt] = m1_ ? 0.f : -1e30f;
        }
        uint32_t ko = sb + PH + cw * 4096 + lane * 16;
        mbar_wait(BA(CM + 15), par);
#pragma unroll
        for (int jp = 0; jp < 8; ++jp) {
          sub(sn++);
          sts128(ko + jp * 512, make_uint4(kk[jp][0], kk[jp][1], kk[jp][2], kk[jp][3]));
        }
#pragma unroll
        for (int i = 0; i < 4; ++i) sub(sn++);
        nbar<1, 256>();
        PROFT(tid_ == 128, layer * 16 + 3);
        rest(sn >> 2, SKB);
        if (!BPRE) rest_end();
        PROFT(lane == 0 && layer == PL, 200 + cw);
        PROFT(tid_ == 128, layer * 16 + 10);
        if (cw == 0) mbar_wait(BA(B_HALO), (layer >> 1) & 1);
        PROFT(tid_ == 128, layer * 16 + 5);
        const uint32_t vs = sb + (cw ? VB + rowo - 2048 : SM_SD + 4096 + rowo), vst = cw ? SLOT : 2048;
        asm volatile("" : "+r"(ko));
        const uint32_t ka = ko + (cw ? -4096 : SM_SD - PH);
        const uint32_t psel = e ? 0x1054u : 0x5410u;
#pragma unroll
        for (int hp = 0; hp < 2; ++hp) {
#pragma unroll
          for (int i = 4 * hp; i < 4 * hp + 4; ++i) {
            const uint4 u = lds128(ka + i * 512);
            kp[i][0] = u.x; kp[i][1] = u.y; kp[i][2] = u.z; kp[i][3] = u.w;
          }
#pragma unroll
          for (int i = 4 * hp; i < 4 * hp + 4; ++i) {
            ldsm_x4_t(vf[0][i & 1][i >> 1][0], vf[0][i & 1][i >> 1][1], vf[0][i & 1][i >> 1][2], vf[0][i & 1][i >> 1][3], vs + (i >> 2) * vst + (X ^ ((i & 3) << 5)));
            ldsm_x4_t(vf[1][i & 1][i >> 1][0], vf[1][i & 1][i >> 1][1], vf[1][i & 1][i >> 1][2], vf[1][i & 1][i >> 1][3], sb + VB + (i >> 2) * SLOT + rowo + (X ^ ((i & 3) << 5)));
          }
          if (BPRE && !hp) rest_end();
          float l0[2][4], l1[2][4];
#pragma unroll
          for (int h = 0; h < 2; ++h) {
            const int H = 2 * hp + h;
            uint32_t qa[8];
#pragma unroll
            for (int i = 0; i < 8; ++i) qa[i] = pack_bf16(acc[128 + 16 * H + 2 * i], acc[129 + 16 * H + 2 * i]);
#pragma unroll
            for (int nt = 3; nt >= 0; --nt) {
              float sc[4] = {0.f, 0.f, 0.f, 0.f};
#pragma unroll
              for (int ks = 0; ks < 2; ++ks) {
                const uint32_t (&kf)[4] = nt < 2 ? kp[2 * H + ks] : kk[2 * H + ks];
                mma_bf16(sc, qa[4 * ks], qa[4 * ks + 1], qa[4 * ks + 2], qa[4 * ks + 3], kf[2 * (nt & 1)], kf[2 * (nt & 1) + 1]);
              }
              l0[h][nt] = fmaf(e ? sc[1] : sc[0], f0[nt], b0[nt]);
              l1[h][nt] = fmaf(e ? sc[3] : sc[2], f1[nt], b1[nt]);
            }
          }
          float mx0[2], mx1[2], s0[2], s1[2];
#pragma unroll
          for (int h = 0; h < 2; ++h) {
            mx0[h] = fmaxf(fmaxf(l0[h][0], l0[h][1]), l0[h][2]);
            mx1[h] = fmaxf(fmaxf(l1[h][1], l1[h][2]), l1[h][3]);
          }
#pragma unroll
          for (int o = 1; o <= 2; o <<= 1)
#pragma unroll
            for (int h = 0; h < 2; ++h) {
              mx0[h] = fmaxf(mx0[h], __shfl_xor_sync(0xffffffffu, mx0[h], o));
              mx1[h] = fmaxf(mx1[h], __shfl_xor_sync(0xffffffffu, mx1[h], o));
            }
#pragma unroll
          for (int h = 0; h < 2; ++h) {
#pragma unroll
            for (int nt = 0; nt < 3; ++nt) { l0[h][nt] = ex2(l0[h][nt] - mx0[h]); l1[h][nt + 1] = ex2(l1[h][nt + 1] - mx1[h]); }
            s0[h] = (l0[h][0] + l0[h][1]) + l0[h][2];
            s1[h] = (l1[h][1] + l1[h][2]) + l1[h][3];
          }
#pragma unroll
          for (int o = 1; o <= 2; o <<= 1)
#pragma unroll
            for (int h = 0; h < 2; ++h) {
              s0[h] += __shfl_xor_sync(0xffffffffu, s0[h], o);
              s1[h] += __shfl_xor_sync(0xffffffffu, s1[h], o);
            }
          uint32_t ow[2][2][4];
#pragma unroll
          for (int h = 0; h < 2; ++h) {
            const int H = 2 * hp + h;
            uint32_t pl[4], ph[4];
            const float i0 = rcp(s0[h]), i1 = rcp(s1[h]);
#pragma unroll
            for (int nt = 0; nt < 4; ++nt) {
              const uint32_t pk = pack_bf16(nt < 3 ? l0[h][nt] * i0 * rj[nt] : 0.f, nt > 0 ? l1[h][nt] * i1 * rj[nt] : 0.f);
              pl[nt] = nt < 3 ? __byte_perm(pk, 0u, psel) : 0u;
              ph[nt] = nt > 0 ? __byte_perm(pk, 0u, psel + 0x2222u) : 0u;
            }
#pragma unroll
            for (int nj = 0; nj < 4; ++nj) {
              float oa[4] = {0.f, 0.f, 0.f, 0.f};
#pragma unroll
              for (int ks = 0; ks < 2; ++ks)
                mma_bf16(oa, pl[2 * ks], ph[2 * ks], pl[2 * ks + 1], ph[2 * ks + 1], vf[ks][nj >> 1][H][2 * (nj & 1)], vf[ks][nj >> 1][H][2 * (nj & 1) + 1]);
              ow[h][0][nj] = pack_bf16(oa[0], oa[1]); ow[h][1][nj] = pack_bf16(oa[2], oa[3]);
            }
          }
          if (hp == 0) {
#pragma unroll
            for (int i = 0; i < 4; ++i) stg128(g_o + gfr + (i & 1) * 8 * D_ + (i >> 1) * 32, ow[i >> 1][i & 1][0], ow[i >> 1][i & 1][1], ow[i >> 1][i & 1][2], ow[i >> 1][i & 1][3]);
            __syncwarp();
            if (lane == 0) mbar_arrive(BA(B_OH0));
          } else {
#pragma unroll
            for (int i = 0; i < 16; ++i) o1[i >> 2][i & 3] = ow[i >> 3][(i >> 2) & 1][i & 3];
          }
#pragma unroll
          for (int i = 0; i < 16; ++i) of[4 * hp + (i >> 2)][i & 3] = ow[i >> 3][i & 1][(i >> 1) & 3];
          if (!hp) { PROFT(tid_ == 128, layer * 16 + 15); mbar_wait(BA(FW), par); }
        }
      } else {
        float sc[2] = {rs0 * L2E, rs1 * L2E};
        {
          const uint32_t vb = sb + VB + (rowo >> 1), X0 = (lchk ^ ((lane & 7) >> 1)) << 4;
          const uint32_t pb = sb + PH + (t & 1) * SLOT + (wrow0 + gq) * 128 + ((((t & 1) * 4 + (t & 2)) ^ gq) << 4);
          float kva[20], en[32], mx[2][2], mn[2][2];
#define PV(hp, j) acc[32 * (hp) + (j)]
          auto mm = [&](int hp, int j) {
            const int r = (j >> 1) & 1;
            if (j < 4 && !(j & 1)) { mx[hp][r] = PV(hp, j); mn[hp][r] = PV(hp, j); }
            else { mx[hp][r] = fmaxf(mx[hp][r], PV(hp, j)); mn[hp][r] = fminf(mn[hp][r], PV(hp, j)); }
          };
          auto mmx = [&](int hp) {
#pragma unroll
            for (int r = 0; r < 2; ++r) {
              mx[hp][r] = fmaxf(mx[hp][r], __shfl_xor_sync(0xffffffffu, mx[hp][r], 2)) * -sc[r];
              mn[hp][r] = fmaf(fminf(mn[hp][r], __shfl_xor_sync(0xffffffffu, mn[hp][r], 2)), sc[r], mx[hp][r]);
            }
          };
          auto stage = [&](int hp) {
#pragma unroll
            for (int i = 0; i < 20; ++i) asm volatile("" : "+f"(kva[i]) :: "memory");
            nbar_dyn(3 + wu, 128);
            const uint32_t ad = sb + VB + hp * SLOT + wg * 8192 + (2 * wq + ((lane >> 3) & 1)) * 640 + (lane & 7) * 16;
#pragma unroll
            for (int i = 0; i < 2; ++i)
              stsm_x4(ad + (2 * i + lchk) * 128, pack_bf16(kva[8 * i], kva[8 * i + 1]), pack_bf16(kva[8 * i + 2], kva[8 * i + 3]),
                      pack_bf16(kva[8 * i + 4], kva[8 * i + 5]), pack_bf16(kva[8 * i + 6], kva[8 * i + 7]));
            stsm_x2(ad + 512, pack_bf16(kva[16], 0.0625f), pack_bf16(kva[18], 0.0625f));
            fence_async_smem();
            __syncwarp();
            if (lane == 0) mbar_arrive(BA(B_KVDONE));
          };
          int sn = 4;
#pragma unroll
          for (int j = 0; j < 32; ++j) mm(0, j);
          mmx(0);
#pragma unroll
          for (int hp = 0; hp < 2; ++hp) {
            float sp[2] = {0.f, 0.f}, sm[2] = {0.f, 0.f};
#pragma unroll
            for (int j = 0; j < 32; ++j) {
              const int r = (j >> 1) & 1, ns = hp ? SUBS1 : SUBS;
              if ((j * ns) / 32 != ((j + 1) * ns) / 32) {
                sub(sn++);
                if (hp && sn == 4 + SUBS + 4 + 4 * (XST & 1)) { stage(0); PROFT(tid_ == 128, layer * 16 + 12); }
              }
              const float x = fmaf(PV(hp, j), sc[r], mx[hp][r]);
              PV(hp, j) = ex2(x); en[j] = ex2(mn[hp][r] - x);
              sp[r] += PV(hp, j); sm[r] += en[j];
              if (hp == 0) {
                mm(1, j);
                if ((j & 3) == 0) {
                  const int jp = 8 + (j >> 2);
                  stsm_x4(vb + ((jp - 8) >> 1) * 8192 + (X0 ^ ((jp & 1) << 5)), pack_bf16(acc[8 * jp], acc[8 * jp + 1]), pack_bf16(acc[8 * jp + 2], acc[8 * jp + 3]),
                          pack_bf16(acc[8 * jp + 4], acc[8 * jp + 5]), pack_bf16(acc[8 * jp + 6], acc[8 * jp + 7]));
                }
              }
            }
#pragma unroll
            for (int i = 0; i < 4; ++i) if (XST & (1 << hp)) sub(sn++);
#pragma unroll
            for (int r = 0; r < 2; ++r) {
              sp[r] = rcp(sp[r] + __shfl_xor_sync(0xffffffffu, sp[r], 2)) * (r ? rs1 : rs0);
              sm[r] = rcp(sm[r] + __shfl_xor_sync(0xffffffffu, sm[r], 2)) * (r ? rs1 : rs0);
            }
            if (hp == 0) { mmx(1); mbar_wait(BA(CM + 15), par); }
            else { PROFT(tid_ == 128, layer * 16 + 11); nbar<1, 256>(); }
#pragma unroll
            for (int i = 0; i < 4; ++i) {
              const int r = i & 1, d = 16 * (i >> 1) + 2 * r;
              sts128((pb + r * 1024) ^ ((i >> 1) << 4), make_uint4(pack_bf16(PV(hp, d) * sp[r], PV(hp, d + 1) * sp[r]), pack_bf16(PV(hp, d + 4) * sp[r], PV(hp, d + 5) * sp[r]),
                                                                    pack_bf16(PV(hp, d + 8) * sp[r], PV(hp, d + 9) * sp[r]), pack_bf16(PV(hp, d + 12) * sp[r], PV(hp, d + 13) * sp[r])));
              sts128((pb + r * 1024) ^ ((i >> 1) << 4) ^ 64, make_uint4(pack_bf16(en[d] * sm[r], en[d + 1] * sm[r]), pack_bf16(en[d + 4] * sm[r], en[d + 5] * sm[r]),
                                                                         pack_bf16(en[d + 8] * sm[r], en[d + 9] * sm[r]), pack_bf16(en[d + 12] * sm[r], en[d + 13] * sm[r])));
            }
            fence_async_smem();
            nbar<1, 256>();
            const uint32_t dP = dB0 + (PH >> 4) + wu * 1024;
            const uint32_t dV = (dB0 & 0xFFFFu) + ((VB + hp * SLOT) >> 4) + (((SM_SD - VB - hp * SLOT) >> 4) << 16) + wu * (512u - (512u << 16));
            wgmma_fence();
#pragma unroll
            for (int ks = 0; ks < 8; ++ks) wgmma_n40_tt(kva, D128(dP + ks * 128), desc64(dV + ks * 64, 0x80000020u), ks != 0);
            wgmma_commit();
          }
#pragma unroll
          for (int i = 0; i < 4; ++i) sub(sn++);
          stage(1);
          PROFT(tid_ == 128, layer * 16 + 3);
          rest(sn >> 2, SKA);
          rest_end();
          PROFT(lane == 0 && layer == PL, 200 + cw);
          PROFT(tid_ == 128, layer * 16 + 10);
        }
#define QV(H, i) acc[128 + 16 * (H) + (i)]
        float mx[4][2], mn[4][2];
        uint32_t ph[4][4][4];
        auto mnx = [&](int hp) {
#pragma unroll
          for (int H = 2 * hp; H < 2 * hp + 2; ++H)
#pragma unroll
            for (int r = 0; r < 2; ++r) {
              mx[H][r] = fmaxf(fmaxf(fmaxf(QV(H, 2 * r), QV(H, 2 * r + 1)), fmaxf(QV(H, 4 + 2 * r), QV(H, 5 + 2 * r))),
                               fmaxf(fmaxf(QV(H, 8 + 2 * r), QV(H, 9 + 2 * r)), fmaxf(QV(H, 12 + 2 * r), QV(H, 13 + 2 * r))));
              mn[H][r] = fminf(fminf(fminf(QV(H, 2 * r), QV(H, 2 * r + 1)), fminf(QV(H, 4 + 2 * r), QV(H, 5 + 2 * r))),
                               fminf(fminf(QV(H, 8 + 2 * r), QV(H, 9 + 2 * r)), fminf(QV(H, 12 + 2 * r), QV(H, 13 + 2 * r))));
            }
#pragma unroll
          for (int o = 1; o <= 2; o <<= 1)
#pragma unroll
            for (int H = 2 * hp; H < 2 * hp + 2; ++H)
#pragma unroll
              for (int r = 0; r < 2; ++r) {
                mx[H][r] = fmaxf(mx[H][r], __shfl_xor_sync(0xffffffffu, mx[H][r], o));
                mn[H][r] = fminf(mn[H][r], __shfl_xor_sync(0xffffffffu, mn[H][r], o));
              }
#pragma unroll
          for (int H = 2 * hp; H < 2 * hp + 2; ++H)
#pragma unroll
            for (int r = 0; r < 2; ++r) { mx[H][r] *= -sc[r]; mn[H][r] = fmaf(mn[H][r], sc[r], mx[H][r]); }
        };
        auto fm = [&](int H) {
#pragma unroll
          for (int i = 0; i < 8; ++i) {
            const int r = i & 1;
            const float x0 = fmaf(QV(H, 2 * i), sc[r], mx[H][r]), x1 = fmaf(QV(H, 2 * i + 1), sc[r], mx[H][r]);
            ph[H][i >> 2][i & 3] = pack_bf16(ex2(x0), ex2(x1));
            ph[H][2 + (i >> 2)][i & 3] = pack_bf16(ex2(mn[H][r] - x0), ex2(mn[H][r] - x1));
          }
        };
        mnx(0);
        fm(0); fm(1);
#pragma unroll
        for (int hp = 0; hp < 2; ++hp) {
          if (hp) mbar_wait(BA(FW), par);
          mbar_wait(BA(hp ? B_KVF1 : B_KVF), (layer >> 1) & 1);
          PROFT(tid_ == 128, layer * 16 + (hp ? 4 : 5));
          float oa[4][20];
          wgmma_fence();
#pragma unroll
          for (int s = 0; s < 2; ++s)
#pragma unroll
            for (int v = 0; v < 4; ++v) {
              const int h = v >> 1, s4 = 2 * (v & 1) + s;
              wgmma_n40_rs(oa[v], ph[2 * hp + h][s4], desc64((((SB0 + VB + hp * SLOT) >> 4) | (40u << 16)) + h * 512 + (s4 ^ (2 * h)) * 80, 8), s != 0);
            }
          wgmma_commit();
          if (hp == 0) { mnx(1); wgmma_wait<0>(); }
          else wgmma_wait<0>();
#pragma unroll
          for (int i = 0; i < 20; ++i) asm volatile("" : "+f"(oa[0][i]), "+f"(oa[1][i]), "+f"(oa[2][i]), "+f"(oa[3][i]) :: "memory");
          uint32_t ow[2][2][4];
#pragma unroll
          for (int h = 0; h < 2; ++h)
#pragma unroll
            for (int r = 0; r < 2; ++r) {
              const float a = oa[2 * h + 1][17 + 2 * r], b = oa[2 * h][17 + 2 * r];
              const float id = rcp(fmaf(oa[2 * h][16 + 2 * r], a, fmaf(a, 1e-6f, oa[2 * h + 1][16 + 2 * r]) * b));
              const float fa = a * id, fb = b * id;
#pragma unroll
              for (int j = 0; j < 4; ++j)
                ow[h][r][j] = pack_bf16(fmaf(oa[2 * h][4 * j + 2 * r], fa, oa[2 * h + 1][4 * j + 2 * r] * fb),
                                        fmaf(oa[2 * h][4 * j + 2 * r + 1], fa, oa[2 * h + 1][4 * j + 2 * r + 1] * fb));
            }
#pragma unroll
          for (int i = 0; i < 16; ++i) of[4 * hp + (i >> 2)][i & 3] = ow[i >> 3][i & 1][(i >> 1) & 3];
          if (hp == 0) {
#pragma unroll
            for (int i = 0; i < 4; ++i) stg128(g_o + gfr + (i & 1) * 8 * D_ + (i >> 1) * 32, ow[i >> 1][i & 1][0], ow[i >> 1][i & 1][1], ow[i >> 1][i & 1][2], ow[i >> 1][i & 1][3]);
            __syncwarp();
            if (lane == 0) mbar_arrive(BA(B_OH0));
            PROFT(tid_ == 128 && layer, layer * 16 + 15);
            fm(2); fm(3);
          } else {
#pragma unroll
            for (int i = 0; i < 16; ++i) o1[i >> 2][i & 3] = ow[i >> 3][(i >> 2) & 1][i & 3];
          }
        }
      }
      PROFT(tid_ == 128, layer * 16 + 6);
#pragma unroll
      for (int i = 0; i < 4; ++i) stg128(g_o + gfr + (i & 1) * 8 * D_ + (2 + (i >> 1)) * 32, o1[i][0], o1[i][1], o1[i][2], o1[i][3]);
      __syncwarp();
      if (lane == 0) { mbar_arrive(BA(B_OH1)); if (EF_USED) REL2(B_EF); }
      PROFT(lane == 0 && layer == PL, 208 + cw);
      wo0();
    }
    {
      PHASE_CTX();
      MMA_CTX();
      mbar_wait(BA(FW + 1), par);
      wgmma_fence();
#pragma unroll
      for (int k = 0; k < 4; ++k) wgmma_n128_rs(acc, of[4 + k], D128(dB0 + (uint32_t)((WO_B >> 4) & 15) * 1024 + k * 128), 1);
      wgmma_commit();
      wgmma_wait<1>();
      if (elected) REL2(CW);
      uint64_t ta = WO_A >> 8, tw = WO_B >> 8;
      auto run = [&](int i0, int i1) {
#pragma unroll 1
        for (int i = i0; i < i1; ++i) {
          mbar_wait(BA(FW + i), par);
          PROFL(tid_ == 128 && layer == PL, 160 + i);
          const uint32_t da = dA0 + ((uint32_t)ta & 15) * 1024, db = dB0 + ((uint32_t)tw & 15) * 1024;
          ta >>= 4; tw >>= 4;
          wgmma_fence();
#pragma unroll
          for (int k = 0; k < 4; ++k) wgmma_n128(acc, D128(da + k * 2), D128(db + k * 128), 1);
          wgmma_commit();
          wgmma_wait<1>();
          if (elected) REL2(CW + i - 1);
        }
        ta = WO_A >> (4 * (i1 & 15)); tw = WO_B >> (4 * (i1 & 15));
      };
      run(2, XRAT);
#pragma unroll
      for (int j = 0; j < 8 / XRN; ++j) {
#pragma unroll
        for (int i = j * XRN; i < (j + 1) * XRN; ++i) ldg128((layer ? g_x : c.x0) + gfr + (i & 1) * 8 * D_ + (i >> 1) * 32, xp[i][0], xp[i][1], xp[i][2], xp[i][3]);
        run(XRAT + j, j + 1 < 8 / XRN ? XRAT + j + 1 : 16);
      }
      if (layer == 0) {
#pragma unroll
        for (int o = 1; o <= 2; o <<= 1)
#pragma unroll
          for (int i = 0; i < 16; ++i) {
            const int j = o == 1 ? 2 * (i & 1) : (i & 1);
            uint32_t &a = xp[i >> 1][j], &b = xp[i >> 1][j + o];
            const uint32_t r = __shfl_xor_sync(0xffffffffu, (t & o) ? a : b, o);
            if (t & o) a = r; else b = r;
          }
      }
      if (layer != NLAYERS - 1) mbar_wait(BA(FM), par ^ 1);
      wgmma_wait<0>();
#pragma unroll
      for (int i = 128; i < 192; ++i) asm volatile("" : "+f"(acc[i]) :: "memory");
      if (elected) REL2(CW + 15);
      PROFT(lane == 0 && layer == PL, 216 + cw);
      PROFT(tid_ == 128, layer * 16 + 7);
#pragma unroll
      for (int i = 0; i < 32; ++i)
        xp[i >> 2][i & 3] = add_bf16x2(xp[i >> 2][i & 3], pack_bf16(acc[128 + 16 * (i >> 3) + 4 * (i & 3) + 2 * ((i >> 2) & 1)], acc[129 + 16 * (i >> 3) + 4 * (i & 3) + 2 * ((i >> 2) & 1)]));
      if (layer == NLAYERS - 1) {
#pragma unroll
        for (int i = 0; i < 8; ++i) stsm_x4(sb + (XS + (i >> 2)) * SLOT + (Y ^ ((i & 2) << 5)) + (i & 1) * 1024, xp[i][0], xp[i][1], xp[i][2], xp[i][3]);
        __syncwarp();
        slab_out_half(sb + XS * SLOT, c.out + (size_t)m0 * D_ + g * 128, wrow0, lane);
        slab_out_half(sb + (XS + 1) * SLOT, c.out + (size_t)m0 * D_ + g * 128 + 64, wrow0, lane);
        PROFT(tid_ == 128, layer * 16 + 24);
        break;
      }
#pragma unroll
      for (int i = 0; i < 4; ++i) stg128(g_x + gfr + (i & 1) * 8 * D_ + (i >> 1) * 32, xp[i][0], xp[i][1], xp[i][2], xp[i][3]);
      __syncwarp();
      if (lane == 0) mbar_arrive(BA(B_XH0));
#pragma unroll
      for (int i = 0; i < 16; ++i) xf[i >> 2][i & 3] = xp[2 * (i >> 3) + (i & 1)][(i >> 1) & 3];
      PROFT(tid_ == 128, layer * 16 + 24);
    }
  }
}

__device__ __forceinline__ uint64_t k_order(int o) {
  const uint32_t lo = (1u << (4 * o)) - 1u, h0 = (0xECA86420u & lo) | ((0xECA86420u >> 4) & ~lo);
  return (uint64_t)(2 * o) | ((uint64_t)(2 * o + 1) << 4) | ((uint64_t)(h0 & 0xFFFFFFFu) << 8) | ((uint64_t)((h0 & 0xFFFFFFFu) | 0x1111111u) << 36);
}

__global__ void __cluster_dims__(2, 1, 1) __launch_bounds__(384, 1)
mega_kernel(const __grid_constant__ Maps maps, const __grid_constant__ Ctx c, const bf16* __restrict__ wA, const bf16* __restrict__ wB,
            const bf16* __restrict__ woA, const bf16* __restrict__ woB) {
  if (blockIdx.x - c.boff >= 128u) {
    const unsigned int epoch = ld_relaxed(&g_epoch);
    const int e = (blockIdx.x - c.boff) & 3, tid = threadIdx.x;
    float s[8] = {0.f, 0.f, 0.f, 0.f, 0.f, 0.f, 0.f, 0.f};
    const uint32_t sb = smem_u32(smem_raw), bar = sb + SM_BAR;
    auto issue = [&](int i) {
      mbar_expect_tx(BA(i & 3), 49152);
      bulk_load(sb + (i & 3) * 49152, wB + (size_t)e * 256 * 3072 + i * 24576, 49152, BA(i & 3));
    };
    if (tid == 0) {
#pragma unroll 1
      for (int i = 0; i < 4; ++i) {
        mbar_init(BA(i), 1);
        fence_async_smem();
        issue(i);
      }
    }
    __syncthreads();
#pragma unroll 1
    for (int i = 0; i < 32; ++i) {
      mbar_wait(BA(i & 3), (i >> 2) & 1);
#pragma unroll 2
      for (int r = 0; r < 8; ++r) {
        const uint4 v = lds128(sb + (i & 3) * 49152 + r * 6144 + tid * 16);
        s[0] += bf_lo(v.x); s[1] += bf_hi(v.x); s[2] += bf_lo(v.y); s[3] += bf_hi(v.y);
        s[4] += bf_lo(v.z); s[5] += bf_hi(v.z); s[6] += bf_lo(v.w); s[7] += bf_hi(v.w);
      }
      __syncthreads();
      if (tid == 0 && i < 28) issue(i + 4);
    }
    float* cd = g_cs + (epoch & 1) * 6144 + 3072 + ((tid >> 4) & 7) * 384 + (tid < 128 ? 256 : (tid >> 7) * 128 - 128) + (tid & 15) * 8;
    red_add4(cd, s[0], s[1], s[2], s[3]);
    red_add4(cd + 4, s[4], s[5], s[6], s[7]);
    __syncthreads();
    if (tid == 0) flag_add(&g_csflag[8].v);
    const int op = (epoch & 1) ^ 1;
    float4* kz = reinterpret_cast<float4*>(g_kv + (size_t)op * (2 * 8 * 10240)) + e * 5120;
#pragma unroll 1
    for (int i = tid; i < 5120; i += 384) kz[i] = make_float4(0.f, 0.f, 0.f, 0.f);
    reinterpret_cast<float4*>(g_cs + op * 6144)[e * 384 + tid] = make_float4(0.f, 0.f, 0.f, 0.f);
#pragma unroll 1
    for (int i = tid; i < 1024; i += 384) reinterpret_cast<float4*>(g_stats + (op * 4 + e) * S_)[i] = make_float4(0.f, 0.f, 0.f, 0.f);
    return;
  }
  const int warp = __shfl_sync(0xffffffffu, threadIdx.x >> 5, 0), lane = threadIdx.x & 31;
  if (smem_u32(smem_raw) != SB0 + ((blockIdx.x & 1) << 24)) __trap();
  {
  const int cid = (blockIdx.x - c.boff) >> 1, u7 = ((cid - 36) * 37) >> 8, cr = blockIdx.x & 1;
  const int g = cid < 4 ? 4 + cid : cid < 36 ? (cid - 4) >> 3 : 4 + u7, rb = (cid < 4 ? 0 : cid < 36 ? (cid - 4) & 7 : cid - 35 - 7 * u7) * 2 + cr, m0 = rb * 128;
  const uint32_t sb = SB0 + (cr << 24), bar = sb + SM_BAR;
  PROFT(lane == 0 && (warp == 0 || warp == 4), 224 + (warp >> 2) * 8);
  uint32_t cx = 0;
  if (warp == 2) {
    if (lane < NMAP) asm volatile("prefetch.tensormap [%0];" ::"l"(&maps.m[lane]) : "memory");
    if (lane == 31) asm volatile("prefetch.global.L2 [%0];" ::"l"(&g_epoch));
  } else if (warp == 3) {
    cx = c_map[cid] + c_wop[lane] + c_wop[NWOP - lane] + c_aop[lane] + c_aop[NAOP - lane] + (uint32_t)(uintptr_t)g_x;
  } else if (warp >= 4 && warp < 8) {
    const int i = threadIdx.x - 128;
    asm volatile("prefetch.global.L2 [%0];" ::"l"(wA + (size_t)((rb & ~1) * 64 + cr * 32 + ((i >> 1) & 31)) * 3072 + (i >> 6) * 1024 + g * 128 + (i & 1) * 64));
  }
  if (warp < 2) {
    const int s = warp, kb = (rb & ~1) + s;
    if (lane == 0) {
      mbar_init(BA(FM + s), 1u);
      mbar_init(BA(B_RAW + warp), 1u);
      mbar_init(BA(warp ? B_X0 : B_KVS0), 1u);
      asm volatile("fence.mbarrier_init.release.cluster;" ::: "memory");
    }
    __syncwarp();
    if (warp == 0) tma_2d_e(sb + SM_SD, &maps.m[MAP_PHI], 0, g * 128, BA(B_RAW));
    else if (W1DL) __nanosleep(W1DL);
#pragma unroll
    for (int j = 0; j < 6; ++j)
      tma_5d_e(sb + (j < 2 ? 2 * s : j < 4 ? 9 + s : 2 * s + 1) * SLOT + (j & 1) * 8192, &maps.m[MAP_WA], (j < 2 ? 1024 : j < 4 ? 0 : 2048) + g * 128 + (j & 1) * 64, 2 * kb,
               BA(j < 4 ? B_RAW + warp : FM + s));
    tma_2d_e(sb + (XS + s) * SLOT, &maps.m[MAP_X0], kb * 64, m0, BA(FM + s));
    expect_tx_e(BA(B_RAW + warp), warp ? 32768 : 32768 + 8192);
    expect_tx_e(BA(FM + s), 32768);
    if (X0AT == 0 && warp == 1) {
      tma_2d_e(sb + 11 * SLOT, &maps.m[MAP_X0], g * 128, m0, BA(B_X0));
      tma_2d_e(sb + 12 * SLOT, &maps.m[MAP_X0], g * 128 + 64, m0, BA(B_X0));
      expect_tx_e(BA(B_X0), 32768);
    }
  } else if (warp >= 4 && lane == 0) {
#pragma unroll 1
    for (int i = 2 + (warp - 4) * 13; i < 15 + (warp - 4) * 13; ++i)
      mbar_init(BA(i), 1u << ((i < CM ? 0u : i < B_EF ? 2u : (uint32_t)(BAR_LG >> (4 * ((i - B_EF) & 15)))) & 7u));
    asm volatile("fence.mbarrier_init.release.cluster;" ::: "memory");
  }
  __syncwarp();
  asm volatile("barrier.cluster.arrive.relaxed.aligned;" ::: "memory");
  if (threadIdx.x == 96 + c.zero) sts_f(sb + SM_EPOCH + 4, __uint_as_float(cx));
  PROFT(lane == 0 && (warp == 0 || warp == 4), 225 + (warp >> 2) * 8);
  __syncwarp();
  PROFT(lane == 0 && (warp == 0 || warp == 4), 226 + (warp >> 2) * 8);
  }

  if (warp < 4) {
    asm volatile("setmaxnreg.dec.sync.aligned.u32 40;");
    PROFT(threadIdx.x == 0, 227);
    cluster_wait();
    PROFT(threadIdx.x == 0, 228);
    if (warp == 0 || warp == 3) {
    if (warp == 0) {
      BLK_CTX();
      const unsigned int epoch = __shfl_sync(0xffffffffu, ld_relaxed(&g_epoch), 0), xbase = epoch * NLAYERS;
      (void)xbase;
      const uint64_t ordg = k_order(g);
      if (X0AT) {
        mbar_wait_u(BA(B_RAW + X0AT - 1), 0);
        tma_2d_e(sb + 11 * SLOT, &maps.m[MAP_X0], g * 128, m0, BA(B_X0));
        tma_2d_e(sb + 12 * SLOT, &maps.m[MAP_X0], g * 128 + 64, m0, BA(B_X0));
        expect_tx_e(BA(B_X0), 32768);
      }
#pragma unroll 1
      for (int lp = 0; lp < 2 * NLAYERS; ++lp) {
        const int layer = lp >> 1, n1 = (lp & 1) ? NAOP : NAOP - 14;
        int n = (lp & 1) ? NAOP - 14 : 0;
        const uint64_t ord = lp ? ordg : k_order(rb >> 1);
        uint32_t ready = lp ? 0u : 0xFFFFu, nop = c_aop[n];
        const unsigned int* fl = ((lp & 1) ? g_of : g_xf) + rb * 32;
        const CUtensorMap* tm = &maps.m[(lp & 1) ? MAP_O : lp ? MAP_X : MAP_X0];
        const uint32_t skip = layer ? 1u << 25 : 9u << 22;
        if (lp) mbar_wait_u(BA((lp & 1) ? B_OH0 : B_XH0), ((lp - 1) >> 1) & 1);
#pragma unroll 1
        for (; n < n1; ++n) {
          const uint32_t op = nop;
          nop = c_aop[n + 1];
          const uint32_t kb = (uint32_t)(ord >> ((op >> 2) & 60)) & 15;
          uint32_t dst = sb + (op & 15) * SLOT, kc = kb * 64, fb = bar + ((op >> 5) & 0x3F8), need = ~ready & (1u << kb);
          asm volatile("" : "+r"(dst), "+r"(kc), "+r"(fb), "+r"(need));
          const uint32_t eb = bar + ((op >> 12) & 0x3F8), ep = (layer ^ (op >> 22)) & 1;
          bool fr = op & skip;
          if (need) {
            if (!fr) fr = __all_sync(0xffffffffu, mbar_test_wait(eb, ep));
            PROFT(lane == 0 && (n == 0 || n == NAOP - 14), 64 + layer * 16 + (n ? 2 : 0));
            src_wait<0>(fl, xbase + layer + 1, need, ready, lane);
            fence_async_all();
          }
          if (!fr) mbar_wait_u(eb, ep);
          tma_2d_e(dst, tm, kc, m0, fb);
          PROFT(lane == 0 && (n == 0 || n == NAOP - 14), 64 + layer * 16 + (n ? 3 : 1));
          PROFL(lane == 0 && layer == PL && n >= NAOP - 14, 178 + n - (NAOP - 14));
          PROFL(lane == 0 && layer == PL + 1 && n < 4, 242 + n);
        }
      }
    } else {
      BLK_CTX();
      const unsigned int epoch = __shfl_sync(0xffffffffu, ld_relaxed(&g_epoch), 0), xbase = epoch * NLAYERS;
      (void)xbase;
      const uint64_t ordg = k_order(g);
#pragma unroll 1
      for (int layer = 0; layer < NLAYERS; ++layer) {
        const uint64_t ordq = layer ? ordg : k_order(rb >> 1);
        uint32_t ready = layer ? 0xFFFFu : 0u, nop = c_wop[0];
        const CUtensorMap* tq = &maps.m[(layer & 1) ? MAP_WB : MAP_WF];
        const CUtensorMap* tk = &maps.m[(layer & 1) ? MAP_WB : cr ? MAP_WA : MAP_WF];
        const uint32_t skip = layer ? 1u << 25 : 9u << 22, pm = layer ? 0xE0u : 0u;
        int n = 0;
#pragma unroll 1
        for (; n < NWOP - 16; ++n) {
          const uint32_t op = nop;
          nop = c_wop[n + 1];
          const uint32_t isq = (op >> 23) & 1, fb = bar + ((op >> 5) & 0x3F8);
          const uint32_t kb = (uint32_t)(ordq >> ((op >> 2) & 60)) & 15;
          const CUtensorMap* tm = (isq ? tq : tk) + ((op & pm) ? 1 : 0);
          const uint32_t dst = sb + (op & 15) * SLOT + cr * (isq ? 8192 : SLOT);
          const int col = g * 128 + (isq ? cr * 64 : 1024 + cr * 1024);
          if (layer == 0) {
            if ((op & 0x7E00) == 0) continue;
            const uint32_t need = ((isq || !cr) ? 1u << kb : 0u) | (((op >> 22) & 1) ? 0u : (((op >> 15) & 127) == CM ? 1u : 3u) << (rb & ~1));
            if ((ready & need) != need) {
              src_wait<0>(g_wff + g * 32, epoch + 1, need, ready, lane);
              fence_async_all();
            }
            if ((op & 15) >= 11) mbar_wait_u(BA(B_XT), 0);
          }
          wait_tma_5d_mc(!(op & skip), bar + ((op >> 12) & 0x3F8), (layer ^ (op >> 22)) & 1, dst, tm, col, 2 * kb, fb);
          if (!isq) tma_5d_mc_e(dst + 8192, tm, col + 64, 2 * kb, fb);
          if (op >> 26) expect_tx_e(fb, (op >> 26) * 8192);
          PROFL(lane == 0 && layer == PL + 1 && n < 16, 128 + n);
        }
        const CUtensorMap* to = &maps.m[(layer & 1) ? MAP_WOB : MAP_WOA];
#pragma unroll 1
        for (; n < NWOP; ++n) {
          const uint32_t op = nop;
          nop = c_wop[n + 1];
          const uint32_t fb = bar + ((op >> 5) & 0x3F8), kb = (uint32_t)(ordg >> ((op >> 2) & 60)) & 15;
          if (WH < 16 && n == NWOP - 16 + WH && !(layer & 1)) mbar_wait_u(BA(B_KVS), (layer >> 1) & 1);
          wait_tma_5d_mc(!((op >> 25) & 1), bar + ((op >> 12) & 0x3F8), layer & 1, sb + (op & 15) * SLOT + cr * 8192, to + ((op & 0xE0) ? 1 : 0), g * 128 + cr * 64, 2 * kb, fb);
          expect_tx_e(fb, (op >> 26) * 8192);
          PROFL(lane == 0 && layer == PL, 144 + ((op >> 8) & 127) - FW);
        }
      }
    }
    } else if (warp == 1) {
      BLK_CTX();
      const unsigned int epoch = __shfl_sync(0xffffffffu, ld_relaxed(&g_epoch), 0), xbase = epoch * NLAYERS;
      (void)xbase;
      if (lane == 0) {
        mbar_wait(BA(B_WFD), 0);
        PROFT(true, 229);
#pragma unroll 1
        for (int j = 0; j < 4; ++j) tma_store_5d(&maps.m[MAP_WF], sb + (j < 2 ? 2 * cr : 9 + cr) * SLOT + (j & 1) * 8192, (j < 2 ? 1024 : 0) + g * 128 + (j & 1) * 64, 2 * rb);
        bulk_commit();
        bulk_wait0();
        PROFT(true, 230);
        fence_async_all();
        flag_set(g_wff + g * 32 + rb, epoch + 1);
        PROFT(true, 64 + 13);
#pragma unroll 1
        for (int e = 0; e < NLAYERS; ++e) {
          BLK_CTX();
          if (e > 0) {
            mbar_wait(BA(B_XH0), (e - 1) & 1);
            PROFT(e == PL + 1, 240);
            flag_set(g_xf + rb * 32 + 2 * g, xbase + e + 1);
            PROFT(e == PL + 1, 241);
          }
          mbar_wait(BA(B_XDONE), e & 1);
          PROFT(true, 64 + e * 16 + 4);
          flag_set(g_xf + rb * 32 + 2 * g + 1, xbase + e + 1);
          if (e == 0) {
            flag_add(&g_csflag[g].v);
#pragma unroll 1
            for (int i = 0; i < 4; ++i) {
              mbar_wait(BA(CM + PFM + PFS * i), 0);
              l2_prefetch(i < 3 ? wB + (size_t)(i * 128 + bid_) * 8192 : woA + (size_t)bid_ * 8192, 16384);
            }
          }
          if (PFM && e == 1) l2_prefetch(woB + (size_t)bid_ * 8192, 16384);
          PROFT(true, 64 + e * 16 + 7);
          if ((e & 1) == 0) {
            bf16* kvl = g_kv + ((size_t)((epoch & 1) * 2 + (e >> 1)) * 8 + g) * 10240;
#pragma unroll 1
            for (int hp = 0; hp < 2; ++hp) {
              mbar_wait(BA(B_KVDONE), hp);
#pragma unroll 1
              for (int i = 0; i < 4; ++i) {
                const int ch = (i + (rb >> 2)) & 3;
                bulk_red_add(kvl + hp * 5120 + ch * 1280, sb + VB + hp * SLOT + (ch >> 1) * 8192 + (ch & 1) * 2560, 2560);
                bulk_commit();
                asm volatile("cp.async.bulk.wait_group %0;" :: "n"(CHW) : "memory");
              }
              bulk_wait0();
              PROFT(true, 64 + e * 16 + (hp ? 10 : 6));
              fence_async_all();
              flag_add(&g_kvflag[hp * 8 + g].v);
              mbar_arrive(BA(hp ? B_KVS : B_KVS0));
              PROFT(e > 0 && hp, 64 + e * 16 + 8);
            }
          }
          if (e & 1) {
            mbar_wait(BA(B_OF0), (e >> 1) & 1);
            flag_set(g_hf + rb * 32 + g, xbase + e + 1);
            if (rb) flag_wait(g_hf + (rb - 1) * 32 + g, xbase + e + 1);
            fence_async_all();
            mbar_expect_tx(BA(B_HALO), 8192);
            bulk_load(sb + SM_SD, g_halo + (size_t)(((e >> 1) * 17 + rb) * 8 + g) * 2048, 8192, BA(B_HALO));
            PROFT(true, 64 + e * 16 + 15);
          }
          mbar_wait(BA(B_OH0), e & 1);
          PROFT(e > 0, 64 + e * 16 + 13);
          flag_set(g_of + rb * 32 + 2 * g, xbase + e + 1);
          PROFT(true, 64 + e * 16 + 9);
          mbar_wait(BA(B_OH1), e & 1);
          PROFT(true, 64 + e * 16 + 5);
          flag_set(g_of + rb * 32 + 2 * g + 1, xbase + e + 1);
          PROFT(true, 64 + e * 16 + 11);
        }
        if (bid_ == 0) g_epoch = epoch + 1;
      }
    } else {
      BLK_CTX();
      const unsigned int epoch = __shfl_sync(0xffffffffu, ld_relaxed(&g_epoch), 0), xbase = epoch * NLAYERS;
      (void)xbase;
      if (lane < 16) sts_f(sb + SM_RS + lane * 4, 0.f);
#pragma unroll 1
      for (int layer = 0; layer < NLAYERS; ++layer) {
#define HLP_CTX() BLK_CTX(); int lane = threadIdx.x & 31; asm volatile("" : "+r"(lane)); const bool isB = layer & 1, hal = isB && rb > 0; (void)hal;
#pragma unroll 1
        for (int ph = 0; ph < 2; ++ph) {
          HLP_CTX();
          if (ph == (layer == 0)) {
            const float* cs = g_cs + (epoch & 1) * 6144 + g * 384;
            if (layer) mbar_wait_u(BA(CT), (layer - 1) & 1);
            if (layer < 2) {
              if (lane == 0) flag_wait_slow(&g_csflag[isB ? 8 : g].v, isB ? epoch * 4u + 4u : epoch * 16u + 16u);
              __syncwarp();
            }
#pragma unroll 1
            for (int i0 = 0; i0 < 12; i0 += 4) {
              float a[4];
#pragma unroll
              for (int i = 0; i < 4; ++i) a[i] = __ldcg(cs + isB * 3072 + (i0 + i) * 32 + lane);
#pragma unroll
              for (int i = 0; i < 4; ++i) {
                const float c1 = bf16r(a[i]), c2 = bf16r(a[i] - c1), c3 = (a[i] - c1) - c2;
                sts128(sb + SM_BP + ((i0 + i) * 32 + lane) * 16, make_uint4(pack_bf16(c1, c2), pack_bf16(c3, 0.f), 0u, 0u));
              }
            }
          } else {
            uint32_t rdy = 0u;
            mbar_wait_u(BA(CM + 3), layer & 1);
            src_wait<128>(g_xf + rb * 32, xbase + layer + 1, 0xAAAAu, rdy, lane);
            rdy = 0u;
            if (hal) src_wait<128>(g_xf + (rb - 1) * 32, xbase + layer + 1, 0xAAAAu, rdy, lane);
            const float2* sp = g_stats + ((epoch & 1) * 4 + layer) * S_ + m0 + lane;
            float2 u[5];
#pragma unroll
            for (int i = 0; i < 4; ++i) u[i] = __ldcg(sp + i * 32);
            u[4] = __ldcg(sp - (hal ? 16 : 0));
#pragma unroll 1
            for (int i = 0; i < 5; ++i) {
              const float mean = u[0].x * (1.f / D_);
              const float var = fmaxf(fmaf(-u[0].x, mean, u[0].y) * (1.f / D_), 0.f);
              const float sd = bf16r(sqrtf(bf16r(bf16r(var) + 1e-5f)));
              const int R = i * 32 + lane;
              if (i < 4) {
                const float hm = -0.5f * bf16r(mean);
                if (!isB) sts128(sb + SM_SD + R * 64 + ((R >> 1) & 3) * 16, make_uint4(__float_as_uint(sd) >> 16, __float_as_uint(sd) >> 16, __float_as_uint(sd) >> 16, __float_as_uint(sd) >> 16));
                sts128(sb + SM_AP + R * 16, make_uint4(pack_bf16(hm, hm), pack_bf16(hm, 0.f), 0u, 0u));
              }
              if (i < 4 || (hal && lane < 16)) sts_f(sb + SM_RS + (i < 4 ? 16 + R : lane) * 4, __fdividef(1.f, sd));
#pragma unroll
              for (int j = 0; j < 4; ++j) u[j] = u[j + 1];
            }
            PROFT(lane == 0, 64 + layer * 16 + 12);
          }
        }
        HLP_CTX();
        fence_async_smem();
        __syncwarp();
        if (lane == 0) mbar_arrive(BA(B_STAT));
        PROFT(lane == 0, 64 + layer * 16 + 14);
        if (!isB && lane == 0) {
#pragma unroll 1
          for (int hp = 0; hp < 2; ++hp) {
            mbar_wait(BA(hp ? B_KVS : B_KVS0), (layer >> 1) & 1);
            flag_wait(&g_kvflag[hp * 8 + g].v, epoch * (16u * ((NLAYERS + 1) / 2)) + 16u * ((layer >> 1) + 1));
            const bf16* kvl = g_kv + ((size_t)((epoch & 1) * 2 + (layer >> 1)) * 8 + g) * 10240 + hp * 5120;
            const uint32_t kb = BA(hp ? B_KVF1 : B_KVF);
            fence_async_all();
            mbar_expect_tx(kb, 10240);
            bulk_load(sb + VB + hp * SLOT, kvl, 5120, kb);
            bulk_load(sb + VB + hp * SLOT + 8192, kvl + 2560, 5120, kb);
            PROFT(hp == 0, 64 + layer * 16 + 15);
          }
        }
        __syncwarp();
      }
    }
    __syncwarp();
    asm volatile("barrier.cluster.arrive.relaxed.aligned;" ::: "memory");
    cluster_wait();
  } else {
    asm volatile("setmaxnreg.inc.sync.aligned.u32 232;");
    PROFT(threadIdx.x == 128, 235);
    cluster_wait();
    PROFT(threadIdx.x == 128, 236);
    consumer(c);
    asm volatile("bar.warp.sync 0xffffffff;\nbarrier.cluster.arrive.relaxed.aligned;\nbarrier.cluster.wait.aligned;\n" ::: "memory");
  }
}

typedef CUresult (*PFN_encodeTiled)(CUtensorMap*, CUtensorMapDataType, cuuint32_t, void*, const cuuint64_t*, const cuuint64_t*,
                                    const cuuint32_t*, const cuuint32_t*, CUtensorMapInterleave, CUtensorMapSwizzle,
                                    CUtensorMapL2promotion, CUtensorMapFloatOOBfill);

static void make_map2(PFN_encodeTiled enc, CUtensorMap* m, const void* ptr, uint64_t cols, uint64_t rows, uint32_t box_c, uint32_t box_r) {
  cuuint64_t dims[2] = {cols, rows};
  cuuint64_t strides[1] = {cols * 2};
  cuuint32_t box[2] = {box_c, box_r};
  cuuint32_t es[2] = {1, 1};
  CUresult r = enc(m, CU_TENSOR_MAP_DATA_TYPE_BFLOAT16, 2, const_cast<void*>(ptr), dims, strides, box, es, CU_TENSOR_MAP_INTERLEAVE_NONE,
                   box_c == 64 ? CU_TENSOR_MAP_SWIZZLE_128B : CU_TENSOR_MAP_SWIZZLE_64B, CU_TENSOR_MAP_L2_PROMOTION_L2_256B, CU_TENSOR_MAP_FLOAT_OOB_FILL_NONE);
  (void)r;
}
static void make_map5(PFN_encodeTiled enc, CUtensorMap* m, const void* ptr, uint64_t cols) {
  for (int p = 0; p < 2; ++p) {
    cuuint64_t dims[5] = {cols, 2, 4, 4, 32};
    cuuint64_t strides[4] = {cols * 2, cols * (p ? 16 : 4), cols * (p ? 4 : 16), cols * 64};
    cuuint32_t box[5] = {64, 2, 4, 4, 2};
    cuuint32_t es[5] = {1, 1, 1, 1, 1};
    CUresult r = enc(m + p, CU_TENSOR_MAP_DATA_TYPE_BFLOAT16, 5, const_cast<void*>(ptr), dims, strides, box, es, CU_TENSOR_MAP_INTERLEAVE_NONE,
                     CU_TENSOR_MAP_SWIZZLE_128B, CU_TENSOR_MAP_L2_PROMOTION_L2_256B, CU_TENSOR_MAP_FLOAT_OOB_FILL_NONE);
    (void)r;
  }
}

extern "C" void kernel_launch(void* const* d_in, const int* in_sizes, int n_in, void* d_out, int out_size) {
  const bf16* A_x = (const bf16*)d_in[0];
  const bf16* A_wqkv = (const bf16*)d_in[1];
  const bf16* A_wphi = (const bf16*)d_in[2];
  const bf16* A_wo = (const bf16*)d_in[3];
  const bf16* B_wqkv = (const bf16*)d_in[5];
  const bf16* B_wo = (const bf16*)d_in[6];
  bf16* out = (bf16*)d_out;

  static PFN_encodeTiled enc = nullptr;
  static bf16 *p_x, *p_o, *p_wf;
  static uint32_t boff;
  if (!enc) {
    void* fn = nullptr; cudaDriverEntryPointQueryResult qr;
    cudaGetDriverEntryPoint("cuTensorMapEncodeTiled", &fn, cudaEnableDefault, &qr);
    enc = (PFN_encodeTiled)fn;
    cudaGetSymbolAddress((void**)&p_x, g_x);
    cudaGetSymbolAddress((void**)&p_o, g_o);
    cudaGetSymbolAddress((void**)&p_wf, g_wf);
    cudaFuncSetAttribute(mega_kernel, cudaFuncAttributeMaxDynamicSharedMemorySize, SM_TOTAL);
    cudaLaunchConfig_t cfg = {};
    cudaLaunchAttribute at; at.id = cudaLaunchAttributeClusterDimension; at.val.clusterDim.x = 2; at.val.clusterDim.y = 1; at.val.clusterDim.z = 1;
    cfg.gridDim = dim3(132); cfg.blockDim = dim3(384); cfg.dynamicSmemBytes = SM_TOTAL; cfg.attrs = &at; cfg.numAttrs = 1;
    int nc = 0;
    if (cudaOccupancyMaxActiveClusters(&nc, mega_kernel, &cfg) != cudaSuccess) { nc = 0; (void)cudaGetLastError(); }
    boff = nc >= 66 ? 0u : 4u;
  }
  Maps maps;
  make_map5(enc, &maps.m[MAP_WF], p_wf, 2048);
  make_map5(enc, &maps.m[MAP_WA], A_wqkv, 3072);
  make_map5(enc, &maps.m[MAP_WB], B_wqkv, 3072);
  make_map5(enc, &maps.m[MAP_WOA], A_wo, 1024);
  make_map5(enc, &maps.m[MAP_WOB], B_wo, 1024);
  make_map2(enc, &maps.m[MAP_X0], A_x, 1024, 2048, 64, 128);
  make_map2(enc, &maps.m[MAP_X], p_x, 1024, 2048, 64, 128);
  make_map2(enc, &maps.m[MAP_O], p_o, 1024, 2048, 64, 128);
  make_map2(enc, &maps.m[MAP_PHI], A_wphi, 32, 1024, 32, 128);
  Ctx c; c.zero = 0u; c.boff = boff; c.x0 = A_x; c.out = out;
  mega_kernel<<<132, 384, SM_TOTAL, cudaStreamPerThread>>>(maps, c, A_wqkv, B_wqkv, A_wo, B_wo);
}
```

```cpp
#include <cuda_runtime.h>
#include <cuda_bf16.h>
#include <cuda.h>
#include <stdint.h>

typedef __nv_bfloat16 bf16;

constexpr int S_ = 2048, D_ = 1024;

struct __align__(128) Flag { unsigned int v; unsigned int pad[31]; };
__device__ __align__(1024) bf16 g_x[S_ * D_];
__device__ __align__(1024) bf16 g_o[S_ * D_];
__device__ __align__(1024) uint32_t g_halo[2 * 17 * 8 * 2048];
__device__ __align__(1024) bf16 g_kv[2 * 2 * 8 * 10240];
__device__ __align__(1024) float2 g_stats[2 * 4 * S_];
__device__ __align__(1024) float g_cs[2 * 2 * 3072];
__device__ __align__(1024) bf16 g_wf[D_ * 2048];
__device__ Flag g_kvflag[16], g_csflag[13];
__device__ __align__(128) unsigned int g_xf[16 * 32], g_of[16 * 32];
__device__ __align__(128) unsigned int g_hf[16 * 32];
__device__ __align__(128) unsigned int g_wff[8 * 32];
__device__ unsigned int g_epoch, g_err;
#define PROFT(cond, idx) asm volatile("" ::: "memory")

#define SUSP 20000
__device__ __forceinline__ uint32_t smem_u32(const void* p) { return (uint32_t)__cvta_generic_to_shared(p); }
__device__ __forceinline__ void mbar_init(uint32_t bar, uint32_t count) {
  asm volatile("mbarrier.init.shared::cta.b64 [%0], %1;" ::"r"(bar), "r"(count) : "memory");
}
__device__ __forceinline__ void mbar_expect_tx(uint32_t bar, uint32_t bytes) {
  asm volatile("mbarrier.arrive.expect_tx.shared::cta.b64 _, [%0], %1;" ::"r"(bar), "r"(bytes) : "memory");
}
__device__ __forceinline__ void mbar_arrive(uint32_t bar) {
  asm volatile("mbarrier.arrive.shared::cta.b64 _, [%0];" ::"r"(bar) : "memory");
}
__device__ __forceinline__ bool mbar_try_wait(uint32_t bar, uint32_t parity) {
  uint32_t ok;
  asm volatile("{\n.reg .pred p;\nmbarrier.try_wait.parity.shared::cta.b64 p, [%1], %2;\nselp.b32 %0, 1, 0, p;\n}\n"
               : "=r"(ok) : "r"(bar), "r"(parity) : "memory");
  return ok != 0;
}
__device__ __forceinline__ bool mbar_try_wait_s(uint32_t bar, uint32_t parity) {
  uint32_t ok;
  asm volatile("{\n.reg .pred p;\nmbarrier.try_wait.parity.shared::cta.b64 p, [%1], %2, %3;\nselp.b32 %0, 1, 0, p;\n}\n"
               : "=r"(ok) : "r"(bar), "r"(parity), "r"(SUSP) : "memory");
  return ok != 0;
}
__device__ __forceinline__ void mbar_wait_s(uint32_t bar, uint32_t parity) {
  uint32_t n = 0;
  bool ok;
#pragma unroll 1
  do { ++n; ok = mbar_try_wait_s(bar, parity); } while (!ok && n < (1u << 16));
}
__device__ __forceinline__ bool mbar_test_wait(uint32_t bar, uint32_t parity) {
  uint32_t ok;
  asm volatile("{\n.reg .pred p;\nmbarrier.test_wait.parity.shared::cta.b64 p, [%1], %2;\nselp.b32 %0, 1, 0, p;\n}\n"
               : "=r"(ok) : "r"(bar), "r"(parity) : "memory");
  return ok != 0;
}
__device__ __forceinline__ uint64_t gtimer() {
  uint64_t t; asm volatile("mov.u64 %0, %globaltimer;" : "=l"(t)); return t;
}
__device__ __forceinline__ void mbar_wait(uint32_t bar, uint32_t parity) {
  uint32_t n = 0;
  bool ok;
#pragma unroll 1
  do { ++n; ok = mbar_try_wait(bar, parity); } while (!ok && n < (1u << 22));
}
__device__ __forceinline__ unsigned int ld_acquire(const unsigned int* p) {
  unsigned int v; asm volatile("ld.acquire.gpu.global.u32 %0, [%1];" : "=r"(v) : "l"(p) : "memory"); return v;
}
__device__ __forceinline__ void flag_add(unsigned int* p) {
  asm volatile("red.release.gpu.global.add.u32 [%0], 1;" ::"l"(p) : "memory");
}
__device__ __forceinline__ void flag_set(unsigned int* p, unsigned int v) {
  asm volatile("st.release.gpu.global.u32 [%0], %1;" ::"l"(p), "r"(v) : "memory");
}
template <int SLEEP>
__device__ __forceinline__ void src_wait(const unsigned int* f, unsigned int target, uint32_t need, uint32_t& ready, int lane) {
  uint32_t n = 0;
#pragma unroll 1
  while ((ready & need) != need) {
    const unsigned int v = ld_acquire(f + (lane & 15));
    ready = __ballot_sync(0xffffffffu, (int)(v - target) >= 0);
    if (SLEEP) { if ((ready & need) != need) __nanosleep(SLEEP); }
    if (++n > (1u << 20)) break;
  }
  __syncwarp();
}
__device__ __forceinline__ unsigned int ld_relaxed(const unsigned int* p);
__device__ __forceinline__ unsigned int ld_relaxed(const unsigned int* p) {
  unsigned int v; asm volatile("ld.relaxed.gpu.global.u32 %0, [%1];" : "=r"(v) : "l"(p) : "memory"); return v;
}
template <int SLEEP>
__device__ __forceinline__ void flag_wait_t(const unsigned int* p, unsigned int target) {
  uint32_t n = 0;
#pragma unroll 1
  while ((int)(ld_acquire(p) - target) < 0) {
    if (SLEEP) __nanosleep(SLEEP);
    if (++n > (1u << 20)) break;
  }
}
__device__ __forceinline__ void flag_wait(const unsigned int* p, unsigned int target) { flag_wait_t<0>(p, target); }
__device__ __forceinline__ void flag_wait_slow(const unsigned int* p, unsigned int target) { flag_wait_t<256>(p, target); }
__device__ __forceinline__ void mbar_wait_u(uint32_t bar, uint32_t parity) {
  uint32_t n = 0;
#pragma unroll 1
  while (!__all_sync(0xffffffffu, SUSP ? mbar_try_wait_s(bar, parity) : mbar_try_wait(bar, parity))) {
    if (++n > (SUSP ? 1u << 16 : 1u << 22)) break;
  }
}
__device__ __forceinline__ void expect_tx_e(uint32_t bar, uint32_t bytes) {
  asm volatile("{\n.reg .pred p;\nelect.sync _|p, 0xffffffff;\n@p mbarrier.arrive.expect_tx.shared::cta.b64 _, [%0], %1;\n}\n" ::"r"(bar), "r"(bytes) : "memory");
}
__device__ __forceinline__ void tma_2d_e(uint32_t dst, const CUtensorMap* tm, int c0, int c1, uint32_t bar) {
  asm volatile("{\n.reg .pred p;\nelect.sync _|p, 0xffffffff;\n"
               "@p cp.async.bulk.tensor.2d.shared::cluster.global.mbarrier::complete_tx::bytes [%0], [%1, {%2, %3}], [%4];\n}\n"
               ::"r"(dst), "l"(tm), "r"(c0), "r"(c1), "r"(bar) : "memory");
}
__device__ __forceinline__ void tma_5d_e(uint32_t dst, const CUtensorMap* tm, int c0, int c4, uint32_t bar) {
  asm volatile("{\n.reg .pred p;\nelect.sync _|p, 0xffffffff;\n"
               "@p cp.async.bulk.tensor.5d.shared::cluster.global.mbarrier::complete_tx::bytes [%0], [%1, {%2, %5, %5, %5, %3}], [%4];\n}\n"
               ::"r"(dst), "l"(tm), "r"(c0), "r"(c4), "r"(bar), "r"(0) : "memory");
}
__device__ __forceinline__ void tma_5d_mc_e(uint32_t dst, const CUtensorMap* tm, int c0, int c4, uint32_t bar) {
  asm volatile("{\n.reg .pred p;\nelect.sync _|p, 0xffffffff;\n"
               "@p cp.async.bulk.tensor.5d.shared::cluster.global.mbarrier::complete_tx::bytes.multicast::cluster [%0], [%1, {%2, %6, %6, %6, %3}], [%4], %5;\n}\n"
               ::"r"(dst), "l"(tm), "r"(c0), "r"(c4), "r"(bar), "h"((uint16_t)3), "r"(0) : "memory");
}
__device__ __forceinline__ void wait_tma_5d_mc(bool w, uint32_t eb, uint32_t par, uint32_t dst, const CUtensorMap* tm, int c0, int c4, uint32_t fb) {
  asm volatile("" : "+r"(dst), "+l"(tm), "+r"(c0), "+r"(c4), "+r"(fb));
  if (w) mbar_wait_u(eb, par);
  tma_5d_mc_e(dst, tm, c0, c4, fb);
}
__device__ __forceinline__ void stg128(void* p, uint32_t a, uint32_t b, uint32_t c, uint32_t d) {
  asm volatile("st.global.v4.u32 [%0], {%1,%2,%3,%4};" ::"l"(p), "r"(a), "r"(b), "r"(c), "r"(d) : "memory");
}
__device__ __forceinline__ void stg128_p(bool on, void* p, uint32_t a, uint32_t b, uint32_t c, uint32_t d) {
  asm volatile("{\n.reg .pred p;\nsetp.ne.b32 p, %5, 0;\n@p st.global.v4.u32 [%0], {%1,%2,%3,%4};\n}\n" ::"l"(p), "r"(a), "r"(b), "r"(c), "r"(d), "r"((int)on) : "memory");
}
__device__ __forceinline__ void ldg128(const void* p, uint32_t& a, uint32_t& b, uint32_t& c, uint32_t& d) {
  asm volatile("ld.global.cg.v4.u32 {%0,%1,%2,%3}, [%4];" : "=r"(a), "=r"(b), "=r"(c), "=r"(d) : "l"(p) : "memory");
}
__device__ __forceinline__ void release2c(uint32_t off) {
  asm volatile("mbarrier.arrive.shared::cluster.b64 _, [%0];\nmbarrier.arrive.shared::cluster.b64 _, [%1];" ::"r"(off), "r"(off + (1u << 24)) : "memory");
}
__device__ __forceinline__ void tma_store_5d(const CUtensorMap* tm, uint32_t src, int c0, int c4) {
  asm volatile("cp.async.bulk.tensor.5d.global.shared::cta.bulk_group [%0, {%2, %4, %4, %4, %3}], [%1];"
               ::"l"(tm), "r"(src), "r"(c0), "r"(c4), "r"(0) : "memory");
}
__device__ __forceinline__ void bulk_load(uint32_t dst, const void* src, uint32_t bytes, uint32_t bar) {
  asm volatile("cp.async.bulk.shared::cluster.global.mbarrier::complete_tx::bytes [%0], [%1], %2, [%3];" ::"r"(dst), "l"(src), "r"(bytes), "r"(bar) : "memory");
}
__device__ __forceinline__ void bulk_red_add(void* dst, uint32_t src, uint32_t bytes) {
  asm volatile("cp.reduce.async.bulk.global.shared::cta.bulk_group.add.noftz.bf16 [%0], [%1], %2;" ::"l"(dst), "r"(src), "r"(bytes) : "memory");
}
__device__ __forceinline__ void bulk_commit() { asm volatile("cp.async.bulk.commit_group;" ::: "memory"); }
__device__ __forceinline__ void bulk_wait0() { asm volatile("cp.async.bulk.wait_group 0;" ::: "memory"); }
__device__ __forceinline__ void fence_async_smem() { asm volatile("fence.proxy.async.shared::cta;" ::: "memory"); }
__device__ __forceinline__ void fence_async_all() { asm volatile("fence.proxy.async.global;" ::: "memory"); }
__device__ __forceinline__ void wgmma_fence() { asm volatile("wgmma.fence.sync.aligned;" ::: "memory"); }
__device__ __forceinline__ void wgmma_commit() { asm volatile("wgmma.commit_group.sync.aligned;" ::: "memory"); }
template <int N> __device__ __forceinline__ void wgmma_wait() { asm volatile("wgmma.wait_group.sync.aligned %0;" ::"n"(N) : "memory"); }
__device__ __forceinline__ void cluster_wait() { asm volatile("barrier.cluster.wait.acquire.aligned;" ::: "memory"); }
template <int ID, int N> __device__ __forceinline__ void nbar() { asm volatile("bar.sync %0, %1;" ::"n"(ID), "n"(N) : "memory"); }
__device__ __forceinline__ uint64_t desc64(uint32_t lo, uint32_t hi) { return (uint64_t)lo | ((uint64_t)hi << 32); }
__device__ __forceinline__ uint32_t pack_bf16(float lo, float hi) {
  uint32_t r; asm("cvt.rn.bf16x2.f32 %0, %1, %2;" : "=r"(r) : "f"(hi), "f"(lo)); return r;
}
__device__ __forceinline__ uint32_t add_bf16x2(uint32_t a, uint32_t b) {
  uint32_t r; asm("add.rn.bf16x2 %0, %1, %2;" : "=r"(r) : "r"(a), "r"(b)); return r;
}
__device__ __forceinline__ float bf16r(float x) { return __bfloat162float(__float2bfloat16_rn(x)); }
__device__ __forceinline__ float bf_lo(uint32_t u) { return __uint_as_float(u << 16); }
__device__ __forceinline__ float bf_hi(uint32_t u) { return __uint_as_float(u & 0xFFFF0000u); }
__device__ __forceinline__ float ex2(float x) { float r; asm("ex2.approx.ftz.f32 %0, %1;" : "=f"(r) : "f"(x)); return r; }
__device__ __forceinline__ float rcp(float x) { float r; asm("rcp.approx.ftz.f32 %0, %1;" : "=f"(r) : "f"(x)); return r; }
__device__ __forceinline__ void mma_bf16(float (&d)[4], uint32_t a0, uint32_t a1, uint32_t a2, uint32_t a3, uint32_t b0, uint32_t b1) {
  asm("mma.sync.aligned.m16n8k16.row.col.f32.bf16.bf16.f32 {%0,%1,%2,%3}, {%4,%5,%6,%7}, {%8,%9}, {%0,%1,%2,%3};"
               : "+f"(d[0]), "+f"(d[1]), "+f"(d[2]), "+f"(d[3]) : "r"(a0), "r"(a1), "r"(a2), "r"(a3), "r"(b0), "r"(b1));
}
__device__ __forceinline__ void ldsm_x4(uint32_t& r0, uint32_t& r1, uint32_t& r2, uint32_t& r3, uint32_t addr) {
  asm volatile("ldmatrix.sync.aligned.m8n8.x4.shared.b16 {%0,%1,%2,%3}, [%4];"
               : "=r"(r0), "=r"(r1), "=r"(r2), "=r"(r3) : "r"(addr) : "memory");
}
__device__ __forceinline__ void ldsm_x4_t(uint32_t& r0, uint32_t& r1, uint32_t& r2, uint32_t& r3, uint32_t addr) {
  asm volatile("ldmatrix.sync.aligned.m8n8.x4.trans.shared.b16 {%0,%1,%2,%3}, [%4];"
               : "=r"(r0), "=r"(r1), "=r"(r2), "=r"(r3) : "r"(addr) : "memory");
}
__device__ __forceinline__ void stsm_x4(uint32_t addr, uint32_t r0, uint32_t r1, uint32_t r2, uint32_t r3) {
  asm volatile("stmatrix.sync.aligned.m8n8.x4.shared.b16 [%0], {%1,%2,%3,%4};"
               ::"r"(addr), "r"(r0), "r"(r1), "r"(r2), "r"(r3) : "memory");
}
__device__ __forceinline__ void stsm_x2(uint32_t addr, uint32_t r0, uint32_t r1) {
  asm volatile("stmatrix.sync.aligned.m8n8.x2.shared.b16 [%0], {%1,%2};" ::"r"(addr), "r"(r0), "r"(r1) : "memory");
}
__device__ __forceinline__ uint4 lds128(uint32_t addr) {
  uint4 v; asm volatile("ld.shared.v4.b32 {%0,%1,%2,%3}, [%4];" : "=r"(v.x), "=r"(v.y), "=r"(v.z), "=r"(v.w) : "r"(addr) : "memory"); return v;
}
__device__ __forceinline__ void sts128(uint32_t addr, uint4 v) {
  asm volatile("st.shared.v4.b32 [%0], {%1,%2,%3,%4};" ::"r"(addr), "r"(v.x), "r"(v.y), "r"(v.z), "r"(v.w) : "memory");
}
__device__ __forceinline__ float lds_f(uint32_t addr) {
  float v; asm volatile("ld.shared.f32 %0, [%1];" : "=f"(v) : "r"(addr) : "memory"); return v;
}
__device__ __forceinline__ void nbar_dyn(int id, int n) { asm volatile("bar.sync %0, %1;" ::"r"(id), "r"(n) : "memory"); }
__device__ __forceinline__ uint64_t make_desc_ns(uint32_t addr, uint32_t lbo_bytes, uint32_t sbo_bytes) {
  return (uint64_t)((addr & 0x3FFFF) >> 4) | ((uint64_t)(lbo_bytes >> 4) << 16) | ((uint64_t)(sbo_bytes >> 4) << 32);
}
__device__ __forceinline__ void sts_f(uint32_t addr, float v) { asm volatile("st.shared.f32 [%0], %1;" ::"r"(addr), "f"(v) : "memory"); }
__device__ __forceinline__ void sts64(uint32_t addr, uint32_t a, uint32_t b) {
  asm volatile("st.shared.v2.b32 [%0], {%1,%2};" ::"r"(addr), "r"(a), "r"(b) : "memory");
}
__device__ __forceinline__ void sts_f2(uint32_t addr, float a, float b) {
  asm volatile("st.shared.v2.f32 [%0], {%1,%2};" ::"r"(addr), "f"(a), "f"(b) : "memory");
}
__device__ __forceinline__ void red_add2_p(bool on, float* p, float a, float b) {
  asm volatile("{\n.reg .pred p;\nsetp.ne.b32 p, %3, 0;\n@p red.global.add.v2.f32 [%0], {%1,%2};\n}\n" ::"l"(p), "f"(a), "f"(b), "r"((int)on) : "memory");
}
__device__ __forceinline__ void red_add4(float* p, float a, float b, float c, float d) {
  asm volatile("red.global.add.v4.f32 [%0], {%1,%2,%3,%4};" ::"l"(p), "f"(a), "f"(b), "f"(c), "f"(d) : "memory");
}
__device__ __forceinline__ void red_add1(float* p, float a) {
  asm volatile("red.global.add.f32 [%0], %1;" ::"l"(p), "f"(a) : "memory");
}
__device__ __forceinline__ void l2_prefetch(const void* p, uint32_t bytes) {
  asm volatile("cp.async.bulk.prefetch.L2.global [%0], %1;" ::"l"(p), "r"(bytes) : "memory");
}

__device__ __forceinline__ void wgmma_n256(float (&d)[192], uint64_t da, uint64_t db, int scale_d) {
  asm volatile("{\n.reg .pred p;\nsetp.ne.b32 p, %130, 0;\n"
    "wgmma.mma_async.sync.aligned.m64n256k16.f32.bf16.bf16 {%0, %1, %2, %3, %4, %5, %6, %7, %8, %9, %10, %11, %12, %13, %14, %15, %16, %17, %18, %19, %20, %21, %22, %23, %24, %25, %26, %27, %28, %29, %30, %31, %32, %33, %34, %35, %36, %37, %38, %39, %40, %41, %42, %43, %44, %45, %46, %47, %48, %49, %50, %51, %52, %53, %54, %55, %56, %57, %58, %59, %60, %61, %62, %63, %64, %65, %66, %67, %68, %69, %70, %71, %72, %73, %74, %75, %76, %77, %78, %79, %80, %81, %82, %83, %84, %85, %86, %87, %88, %89, %90, %91, %92, %93, %94, %95, %96, %97, %98, %99, %100, %101, %102, %103, %104, %105, %106, %107, %108, %109, %110, %111, %112, %113, %114, %115, %116, %117, %118, %119, %120, %121, %122, %123, %124, %125, %126, %127}, %128, %129, p, 1, 1, 0, 1;\n}\n"
    : "+f"(d[0]), "+f"(d[1]), "+f"(d[2]), "+f"(d[3]), "+f"(d[4]), "+f"(d[5]), "+f"(d[6]), "+f"(d[7]), "+f"(d[8]), "+f"(d[9]), "+f"(d[10]), "+f"(d[11]), "+f"(d[12]), "+f"(d[13]), "+f"(d[14]), "+f"(d[15]), "+f"(d[16]), "+f"(d[17]), "+f"(d[18]), "+f"(d[19]), "+f"(d[20]), "+f"(d[21]), "+f"(d[22]), "+f"(d[23]), "+f"(d[24]), "+f"(d[25]), "+f"(d[26]), "+f"(d[27]), "+f"(d[28]), "+f"(d[29]), "+f"(d[30]), "+f"(d[31]), "+f"(d[32]), "+f"(d[33]), "+f"(d[34]), "+f"(d[35]), "+f"(d[36]), "+f"(d[37]), "+f"(d[38]), "+f"(d[39]), "+f"(d[40]), "+f"(d[41]), "+f"(d[42]), "+f"(d[43]), "+f"(d[44]), "+f"(d[45]), "+f"(d[46]), "+f"(d[47]), "+f"(d[48]), "+f"(d[49]), "+f"(d[50]), "+f"(d[51]), "+f"(d[52]), "+f"(d[53]), "+f"(d[54]), "+f"(d[55]), "+f"(d[56]), "+f"(d[57]), "+f"(d[58]), "+f"(d[59]), "+f"(d[60]), "+f"(d[61]), "+f"(d[62]), "+f"(d[63]), "+f"(d[64]), "+f"(d[65]), "+f"(d[66]), "+f"(d[67]), "+f"(d[68]), "+f"(d[69]), "+f"(d[70]), "+f"(d[71]), "+f"(d[72]), "+f"(d[73]), "+f"(d[74]), "+f"(d[75]), "+f"(d[76]), "+f"(d[77]), "+f"(d[78]), "+f"(d[79]), "+f"(d[80]), "+f"(d[81]), "+f"(d[82]), "+f"(d[83]), "+f"(d[84]), "+f"(d[85]), "+f"(d[86]), "+f"(d[87]), "+f"(d[88]), "+f"(d[89]), "+f"(d[90]), "+f"(d[91]), "+f"(d[92]), "+f"(d[93]), "+f"(d[94]), "+f"(d[95]), "+f"(d[96]), "+f"(d[97]), "+f"(d[98]), "+f"(d[99]), "+f"(d[100]), "+f"(d[101]), "+f"(d[102]), "+f"(d[103]), "+f"(d[104]), "+f"(d[105]), "+f"(d[106]), "+f"(d[107]), "+f"(d[108]), "+f"(d[109]), "+f"(d[110]), "+f"(d[111]), "+f"(d[112]), "+f"(d[113]), "+f"(d[114]), "+f"(d[115]), "+f"(d[116]), "+f"(d[117]), "+f"(d[118]), "+f"(d[119]), "+f"(d[120]), "+f"(d[121]), "+f"(d[122]), "+f"(d[123]), "+f"(d[124]), "+f"(d[125]), "+f"(d[126]), "+f"(d[127])
    : "l"(da), "l"(db), "r"(scale_d));
}
__device__ __forceinline__ void wgmma_n128(float (&d)[192], uint64_t da, uint64_t db, int scale_d) {
  asm volatile("{\n.reg .pred p;\nsetp.ne.b32 p, %66, 0;\n"
    "wgmma.mma_async.sync.aligned.m64n128k16.f32.bf16.bf16 {%0, %1, %2, %3, %4, %5, %6, %7, %8, %9, %10, %11, %12, %13, %14, %15, %16, %17, %18, %19, %20, %21, %22, %23, %24, %25, %26, %27, %28, %29, %30, %31, %32, %33, %34, %35, %36, %37, %38, %39, %40, %41, %42, %43, %44, %45, %46, %47, %48, %49, %50, %51, %52, %53, %54, %55, %56, %57, %58, %59, %60, %61, %62, %63}, %64, %65, p, 1, 1, 0, 1;\n}\n"
    : "+f"(d[128]), "+f"(d[129]), "+f"(d[130]), "+f"(d[131]), "+f"(d[132]), "+f"(d[133]), "+f"(d[134]), "+f"(d[135]), "+f"(d[136]), "+f"(d[137]), "+f"(d[138]), "+f"(d[139]), "+f"(d[140]), "+f"(d[141]), "+f"(d[142]), "+f"(d[143]), "+f"(d[144]), "+f"(d[145]), "+f"(d[146]), "+f"(d[147]), "+f"(d[148]), "+f"(d[149]), "+f"(d[150]), "+f"(d[151]), "+f"(d[152]), "+f"(d[153]), "+f"(d[154]), "+f"(d[155]), "+f"(d[156]), "+f"(d[157]), "+f"(d[158]), "+f"(d[159]), "+f"(d[160]), "+f"(d[161]), "+f"(d[162]), "+f"(d[163]), "+f"(d[164]), "+f"(d[165]), "+f"(d[166]), "+f"(d[167]), "+f"(d[168]), "+f"(d[169]), "+f"(d[170]), "+f"(d[171]), "+f"(d[172]), "+f"(d[173]), "+f"(d[174]), "+f"(d[175]), "+f"(d[176]), "+f"(d[177]), "+f"(d[178]), "+f"(d[179]), "+f"(d[180]), "+f"(d[181]), "+f"(d[182]), "+f"(d[183]), "+f"(d[184]), "+f"(d[185]), "+f"(d[186]), "+f"(d[187]), "+f"(d[188]), "+f"(d[189]), "+f"(d[190]), "+f"(d[191])
    : "l"(da), "l"(db), "r"(scale_d));
}
__device__ __forceinline__ void wgmma_n256_k(float (&d)[192], uint64_t da, uint64_t db, int scale_d) {
  asm volatile("{\n.reg .pred p;\nsetp.ne.b32 p, %130, 0;\n"
    "wgmma.mma_async.sync.aligned.m64n256k16.f32.bf16.bf16 {%0, %1, %2, %3, %4, %5, %6, %7, %8, %9, %10, %11, %12, %13, %14, %15, %16, %17, %18, %19, %20, %21, %22, %23, %24, %25, %26, %27, %28, %29, %30, %31, %32, %33, %34, %35, %36, %37, %38, %39, %40, %41, %42, %43, %44, %45, %46, %47, %48, %49, %50, %51, %52, %53, %54, %55, %56, %57, %58, %59, %60, %61, %62, %63, %64, %65, %66, %67, %68, %69, %70, %71, %72, %73, %74, %75, %76, %77, %78, %79, %80, %81, %82, %83, %84, %85, %86, %87, %88, %89, %90, %91, %92, %93, %94, %95, %96, %97, %98, %99, %100, %101, %102, %103, %104, %105, %106, %107, %108, %109, %110, %111, %112, %113, %114, %115, %116, %117, %118, %119, %120, %121, %122, %123, %124, %125, %126, %127}, %128, %129, p, 1, 1, 0, 0;\n}\n"
    : "+f"(d[0]), "+f"(d[1]), "+f"(d[2]), "+f"(d[3]), "+f"(d[4]), "+f"(d[5]), "+f"(d[6]), "+f"(d[7]), "+f"(d[8]), "+f"(d[9]), "+f"(d[10]), "+f"(d[11]), "+f"(d[12]), "+f"(d[13]), "+f"(d[14]), "+f"(d[15]), "+f"(d[16]), "+f"(d[17]), "+f"(d[18]), "+f"(d[19]), "+f"(d[20]), "+f"(d[21]), "+f"(d[22]), "+f"(d[23]), "+f"(d[24]), "+f"(d[25]), "+f"(d[26]), "+f"(d[27]), "+f"(d[28]), "+f"(d[29]), "+f"(d[30]), "+f"(d[31]), "+f"(d[32]), "+f"(d[33]), "+f"(d[34]), "+f"(d[35]), "+f"(d[36]), "+f"(d[37]), "+f"(d[38]), "+f"(d[39]), "+f"(d[40]), "+f"(d[41]), "+f"(d[42]), "+f"(d[43]), "+f"(d[44]), "+f"(d[45]), "+f"(d[46]), "+f"(d[47]), "+f"(d[48]), "+f"(d[49]), "+f"(d[50]), "+f"(d[51]), "+f"(d[52]), "+f"(d[53]), "+f"(d[54]), "+f"(d[55]), "+f"(d[56]), "+f"(d[57]), "+f"(d[58]), "+f"(d[59]), "+f"(d[60]), "+f"(d[61]), "+f"(d[62]), "+f"(d[63]), "+f"(d[64]), "+f"(d[65]), "+f"(d[66]), "+f"(d[67]), "+f"(d[68]), "+f"(d[69]), "+f"(d[70]), "+f"(d[71]), "+f"(d[72]), "+f"(d[73]), "+f"(d[74]), "+f"(d[75]), "+f"(d[76]), "+f"(d[77]), "+f"(d[78]), "+f"(d[79]), "+f"(d[80]), "+f"(d[81]), "+f"(d[82]), "+f"(d[83]), "+f"(d[84]), "+f"(d[85]), "+f"(d[86]), "+f"(d[87]), "+f"(d[88]), "+f"(d[89]), "+f"(d[90]), "+f"(d[91]), "+f"(d[92]), "+f"(d[93]), "+f"(d[94]), "+f"(d[95]), "+f"(d[96]), "+f"(d[97]), "+f"(d[98]), "+f"(d[99]), "+f"(d[100]), "+f"(d[101]), "+f"(d[102]), "+f"(d[103]), "+f"(d[104]), "+f"(d[105]), "+f"(d[106]), "+f"(d[107]), "+f"(d[108]), "+f"(d[109]), "+f"(d[110]), "+f"(d[111]), "+f"(d[112]), "+f"(d[113]), "+f"(d[114]), "+f"(d[115]), "+f"(d[116]), "+f"(d[117]), "+f"(d[118]), "+f"(d[119]), "+f"(d[120]), "+f"(d[121]), "+f"(d[122]), "+f"(d[123]), "+f"(d[124]), "+f"(d[125]), "+f"(d[126]), "+f"(d[127])
    : "l"(da), "l"(db), "r"(scale_d));
}
__device__ __forceinline__ void wgmma_n128_k(float (&d)[192], uint64_t da, uint64_t db, int scale_d) {
  asm volatile("{\n.reg .pred p;\nsetp.ne.b32 p, %66, 0;\n"
    "wgmma.mma_async.sync.aligned.m64n128k16.f32.bf16.bf16 {%0, %1, %2, %3, %4, %5, %6, %7, %8, %9, %10, %11, %12, %13, %14, %15, %16, %17, %18, %19, %20, %21, %22, %23, %24, %25, %26, %27, %28, %29, %30, %31, %32, %33, %34, %35, %36, %37, %38, %39, %40, %41, %42, %43, %44, %45, %46, %47, %48, %49, %50, %51, %52, %53, %54, %55, %56, %57, %58, %59, %60, %61, %62, %63}, %64, %65, p, 1, 1, 0, 0;\n}\n"
    : "+f"(d[128]), "+f"(d[129]), "+f"(d[130]), "+f"(d[131]), "+f"(d[132]), "+f"(d[133]), "+f"(d[134]), "+f"(d[135]), "+f"(d[136]), "+f"(d[137]), "+f"(d[138]), "+f"(d[139]), "+f"(d[140]), "+f"(d[141]), "+f"(d[142]), "+f"(d[143]), "+f"(d[144]), "+f"(d[145]), "+f"(d[146]), "+f"(d[147]), "+f"(d[148]), "+f"(d[149]), "+f"(d[150]), "+f"(d[151]), "+f"(d[152]), "+f"(d[153]), "+f"(d[154]), "+f"(d[155]), "+f"(d[156]), "+f"(d[157]), "+f"(d[158]), "+f"(d[159]), "+f"(d[160]), "+f"(d[161]), "+f"(d[162]), "+f"(d[163]), "+f"(d[164]), "+f"(d[165]), "+f"(d[166]), "+f"(d[167]), "+f"(d[168]), "+f"(d[169]), "+f"(d[170]), "+f"(d[171]), "+f"(d[172]), "+f"(d[173]), "+f"(d[174]), "+f"(d[175]), "+f"(d[176]), "+f"(d[177]), "+f"(d[178]), "+f"(d[179]), "+f"(d[180]), "+f"(d[181]), "+f"(d[182]), "+f"(d[183]), "+f"(d[184]), "+f"(d[185]), "+f"(d[186]), "+f"(d[187]), "+f"(d[188]), "+f"(d[189]), "+f"(d[190]), "+f"(d[191])
    : "l"(da), "l"(db), "r"(scale_d));
}
__device__ __forceinline__ void wgmma_n40_tt(float (&d)[20], uint64_t da, uint64_t db, int scale_d) {
  asm volatile("{\n.reg .pred p;\nsetp.ne.b32 p, %22, 0;\n"
    "wgmma.mma_async.sync.aligned.m64n40k16.f32.bf16.bf16 {%0, %1, %2, %3, %4, %5, %6, %7, %8, %9, %10, %11, %12, %13, %14, %15, %16, %17, %18, %19}, %20, %21, p, 1, 1, 1, 1;\n}\n"
    : "+f"(d[0]), "+f"(d[1]), "+f"(d[2]), "+f"(d[3]), "+f"(d[4]), "+f"(d[5]), "+f"(d[6]), "+f"(d[7]), "+f"(d[8]), "+f"(d[9]), "+f"(d[10]), "+f"(d[11]), "+f"(d[12]), "+f"(d[13]), "+f"(d[14]), "+f"(d[15]), "+f"(d[16]), "+f"(d[17]), "+f"(d[18]), "+f"(d[19])
    : "l"(da), "l"(db), "r"(scale_d));
}
__device__ __forceinline__ void wgmma_n40_rs(float (&d)[20], const uint32_t (&a)[4], uint64_t db, int scale_d) {
  asm volatile("{\n.reg .pred p;\nsetp.ne.b32 p, %25, 0;\n"
    "wgmma.mma_async.sync.aligned.m64n40k16.f32.bf16.bf16 {%0, %1, %2, %3, %4, %5, %6, %7, %8, %9, %10, %11, %12, %13, %14, %15, %16, %17, %18, %19}, {%20, %21, %22, %23}, %24, p, 1, 1, 1;\n}\n"
    : "+f"(d[0]), "+f"(d[1]), "+f"(d[2]), "+f"(d[3]), "+f"(d[4]), "+f"(d[5]), "+f"(d[6]), "+f"(d[7]), "+f"(d[8]), "+f"(d[9]), "+f"(d[10]), "+f"(d[11]), "+f"(d[12]), "+f"(d[13]), "+f"(d[14]), "+f"(d[15]), "+f"(d[16]), "+f"(d[17]), "+f"(d[18]), "+f"(d[19])
    : "r"(a[0]), "r"(a[1]), "r"(a[2]), "r"(a[3]), "l"(db), "r"(scale_d));
}
__device__ __forceinline__ void wgmma_n128_0(float (&d)[192], uint64_t da, uint64_t db) {
  asm volatile("{\n.reg .pred p;\nsetp.ne.b32 p, 0, 0;\n"
    "wgmma.mma_async.sync.aligned.m64n128k16.f32.bf16.bf16 {%0, %1, %2, %3, %4, %5, %6, %7, %8, %9, %10, %11, %12, %13, %14, %15, %16, %17, %18, %19, %20, %21, %22, %23, %24, %25, %26, %27, %28, %29, %30, %31, %32, %33, %34, %35, %36, %37, %38, %39, %40, %41, %42, %43, %44, %45, %46, %47, %48, %49, %50, %51, %52, %53, %54, %55, %56, %57, %58, %59, %60, %61, %62, %63}, %64, %65, p, 1, 1, 0, 1;\n}\n"
    : "=f"(d[128]), "=f"(d[129]), "=f"(d[130]), "=f"(d[131]), "=f"(d[132]), "=f"(d[133]), "=f"(d[134]), "=f"(d[135]), "=f"(d[136]), "=f"(d[137]), "=f"(d[138]), "=f"(d[139]), "=f"(d[140]), "=f"(d[141]), "=f"(d[142]), "=f"(d[143]), "=f"(d[144]), "=f"(d[145]), "=f"(d[146]), "=f"(d[147]), "=f"(d[148]), "=f"(d[149]), "=f"(d[150]), "=f"(d[151]), "=f"(d[152]), "=f"(d[153]), "=f"(d[154]), "=f"(d[155]), "=f"(d[156]), "=f"(d[157]), "=f"(d[158]), "=f"(d[159]), "=f"(d[160]), "=f"(d[161]), "=f"(d[162]), "=f"(d[163]), "=f"(d[164]), "=f"(d[165]), "=f"(d[166]), "=f"(d[167]), "=f"(d[168]), "=f"(d[169]), "=f"(d[170]), "=f"(d[171]), "=f"(d[172]), "=f"(d[173]), "=f"(d[174]), "=f"(d[175]), "=f"(d[176]), "=f"(d[177]), "=f"(d[178]), "=f"(d[179]), "=f"(d[180]), "=f"(d[181]), "=f"(d[182]), "=f"(d[183]), "=f"(d[184]), "=f"(d[185]), "=f"(d[186]), "=f"(d[187]), "=f"(d[188]), "=f"(d[189]), "=f"(d[190]), "=f"(d[191])
    : "l"(da), "l"(db));
}
__device__ __forceinline__ void wgmma_n128_rs(float (&d)[192], const uint32_t (&a)[4], uint64_t db, int scale_d) {
  asm volatile("{\n.reg .pred p;\nsetp.ne.b32 p, %69, 0;\n"
    "wgmma.mma_async.sync.aligned.m64n128k16.f32.bf16.bf16 {%0, %1, %2, %3, %4, %5, %6, %7, %8, %9, %10, %11, %12, %13, %14, %15, %16, %17, %18, %19, %20, %21, %22, %23, %24, %25, %26, %27, %28, %29, %30, %31, %32, %33, %34, %35, %36, %37, %38, %39, %40, %41, %42, %43, %44, %45, %46, %47, %48, %49, %50, %51, %52, %53, %54, %55, %56, %57, %58, %59, %60, %61, %62, %63}, {%64, %65, %66, %67}, %68, p, 1, 1, 1;\n}\n"
    : "+f"(d[128]), "+f"(d[129]), "+f"(d[130]), "+f"(d[131]), "+f"(d[132]), "+f"(d[133]), "+f"(d[134]), "+f"(d[135]), "+f"(d[136]), "+f"(d[137]), "+f"(d[138]), "+f"(d[139]), "+f"(d[140]), "+f"(d[141]), "+f"(d[142]), "+f"(d[143]), "+f"(d[144]), "+f"(d[145]), "+f"(d[146]), "+f"(d[147]), "+f"(d[148]), "+f"(d[149]), "+f"(d[150]), "+f"(d[151]), "+f"(d[152]), "+f"(d[153]), "+f"(d[154]), "+f"(d[155]), "+f"(d[156]), "+f"(d[157]), "+f"(d[158]), "+f"(d[159]), "+f"(d[160]), "+f"(d[161]), "+f"(d[162]), "+f"(d[163]), "+f"(d[164]), "+f"(d[165]), "+f"(d[166]), "+f"(d[167]), "+f"(d[168]), "+f"(d[169]), "+f"(d[170]), "+f"(d[171]), "+f"(d[172]), "+f"(d[173]), "+f"(d[174]), "+f"(d[175]), "+f"(d[176]), "+f"(d[177]), "+f"(d[178]), "+f"(d[179]), "+f"(d[180]), "+f"(d[181]), "+f"(d[182]), "+f"(d[183]), "+f"(d[184]), "+f"(d[185]), "+f"(d[186]), "+f"(d[187]), "+f"(d[188]), "+f"(d[189]), "+f"(d[190]), "+f"(d[191])
    : "r"(a[0]), "r"(a[1]), "r"(a[2]), "r"(a[3]), "l"(db), "r"(scale_d));
}
__device__ __forceinline__ void wgmma_n32_0(float (&d)[16], uint64_t da, uint64_t db) {
  asm volatile("{\n.reg .pred p;\nsetp.ne.b32 p, 0, 0;\n"
    "wgmma.mma_async.sync.aligned.m64n32k16.f32.bf16.bf16 {%0, %1, %2, %3, %4, %5, %6, %7, %8, %9, %10, %11, %12, %13, %14, %15}, %16, %17, p, 1, 1, 0, 1;\n}\n"
    : "=f"(d[0]), "=f"(d[1]), "=f"(d[2]), "=f"(d[3]), "=f"(d[4]), "=f"(d[5]), "=f"(d[6]), "=f"(d[7]), "=f"(d[8]), "=f"(d[9]), "=f"(d[10]), "=f"(d[11]), "=f"(d[12]), "=f"(d[13]), "=f"(d[14]), "=f"(d[15])
    : "l"(da), "l"(db));
}
__device__ __forceinline__ void wgmma_n32(float (&d)[16], uint64_t da, uint64_t db, int scale_d) {
  asm volatile("{\n.reg .pred p;\nsetp.ne.b32 p, %18, 0;\n"
    "wgmma.mma_async.sync.aligned.m64n32k16.f32.bf16.bf16 {%0, %1, %2, %3, %4, %5, %6, %7, %8, %9, %10, %11, %12, %13, %14, %15}, %16, %17, p, 1, 1, 0, 1;\n}\n"
    : "+f"(d[0]), "+f"(d[1]), "+f"(d[2]), "+f"(d[3]), "+f"(d[4]), "+f"(d[5]), "+f"(d[6]), "+f"(d[7]), "+f"(d[8]), "+f"(d[9]), "+f"(d[10]), "+f"(d[11]), "+f"(d[12]), "+f"(d[13]), "+f"(d[14]), "+f"(d[15])
    : "l"(da), "l"(db), "r"(scale_d));
}
__device__ __forceinline__ void wgmma_n8_t(float (&d)[4], uint64_t da, uint64_t db, int scale_d) {
  asm volatile("{\n.reg .pred p;\nsetp.ne.b32 p, %6, 0;\n"
    "wgmma.mma_async.sync.aligned.m64n8k16.f32.bf16.bf16 {%0, %1, %2, %3}, %4, %5, p, 1, 1, 1, 0;\n}\n"
    : "+f"(d[0]), "+f"(d[1]), "+f"(d[2]), "+f"(d[3])
    : "l"(da), "l"(db), "r"(scale_d));
}
__device__ __forceinline__ void wgmma_n128_rs0(float (&d)[192], const uint32_t (&a)[4], uint64_t db) {
  asm volatile("{\n.reg .pred p;\nsetp.ne.b32 p, 0, 0;\n"
    "wgmma.mma_async.sync.aligned.m64n128k16.f32.bf16.bf16 {%0, %1, %2, %3, %4, %5, %6, %7, %8, %9, %10, %11, %12, %13, %14, %15, %16, %17, %18, %19, %20, %21, %22, %23, %24, %25, %26, %27, %28, %29, %30, %31, %32, %33, %34, %35, %36, %37, %38, %39, %40, %41, %42, %43, %44, %45, %46, %47, %48, %49, %50, %51, %52, %53, %54, %55, %56, %57, %58, %59, %60, %61, %62, %63}, {%64, %65, %66, %67}, %68, p, 1, 1, 1;\n}\n"
    : "=f"(d[128]), "=f"(d[129]), "=f"(d[130]), "=f"(d[131]), "=f"(d[132]), "=f"(d[133]), "=f"(d[134]), "=f"(d[135]), "=f"(d[136]), "=f"(d[137]), "=f"(d[138]), "=f"(d[139]), "=f"(d[140]), "=f"(d[141]), "=f"(d[142]), "=f"(d[143]), "=f"(d[144]), "=f"(d[145]), "=f"(d[146]), "=f"(d[147]), "=f"(d[148]), "=f"(d[149]), "=f"(d[150]), "=f"(d[151]), "=f"(d[152]), "=f"(d[153]), "=f"(d[154]), "=f"(d[155]), "=f"(d[156]), "=f"(d[157]), "=f"(d[158]), "=f"(d[159]), "=f"(d[160]), "=f"(d[161]), "=f"(d[162]), "=f"(d[163]), "=f"(d[164]), "=f"(d[165]), "=f"(d[166]), "=f"(d[167]), "=f"(d[168]), "=f"(d[169]), "=f"(d[170]), "=f"(d[171]), "=f"(d[172]), "=f"(d[173]), "=f"(d[174]), "=f"(d[175]), "=f"(d[176]), "=f"(d[177]), "=f"(d[178]), "=f"(d[179]), "=f"(d[180]), "=f"(d[181]), "=f"(d[182]), "=f"(d[183]), "=f"(d[184]), "=f"(d[185]), "=f"(d[186]), "=f"(d[187]), "=f"(d[188]), "=f"(d[189]), "=f"(d[190]), "=f"(d[191])
    : "r"(a[0]), "r"(a[1]), "r"(a[2]), "r"(a[3]), "l"(db));
}
__device__ __forceinline__ void wgmma_n256_rs(float (&d)[192], const uint32_t (&a)[4], uint64_t db, int scale_d) {
  asm volatile("{\n.reg .pred p;\nsetp.ne.b32 p, %133, 0;\n"
    "wgmma.mma_async.sync.aligned.m64n256k16.f32.bf16.bf16 {%0, %1, %2, %3, %4, %5, %6, %7, %8, %9, %10, %11, %12, %13, %14, %15, %16, %17, %18, %19, %20, %21, %22, %23, %24, %25, %26, %27, %28, %29, %30, %31, %32, %33, %34, %35, %36, %37, %38, %39, %40, %41, %42, %43, %44, %45, %46, %47, %48, %49, %50, %51, %52, %53, %54, %55, %56, %57, %58, %59, %60, %61, %62, %63, %64, %65, %66, %67, %68, %69, %70, %71, %72, %73, %74, %75, %76, %77, %78, %79, %80, %81, %82, %83, %84, %85, %86, %87, %88, %89, %90, %91, %92, %93, %94, %95, %96, %97, %98, %99, %100, %101, %102, %103, %104, %105, %106, %107, %108, %109, %110, %111, %112, %113, %114, %115, %116, %117, %118, %119, %120, %121, %122, %123, %124, %125, %126, %127}, {%128, %129, %130, %131}, %132, p, 1, 1, 1;\n}\n"
    : "+f"(d[0]), "+f"(d[1]), "+f"(d[2]), "+f"(d[3]), "+f"(d[4]), "+f"(d[5]), "+f"(d[6]), "+f"(d[7]), "+f"(d[8]), "+f"(d[9]), "+f"(d[10]), "+f"(d[11]), "+f"(d[12]), "+f"(d[13]), "+f"(d[14]), "+f"(d[15]), "+f"(d[16]), "+f"(d[17]), "+f"(d[18]), "+f"(d[19]), "+f"(d[20]), "+f"(d[21]), "+f"(d[22]), "+f"(d[23]), "+f"(d[24]), "+f"(d[25]), "+f"(d[26]), "+f"(d[27]), "+f"(d[28]), "+f"(d[29]), "+f"(d[30]), "+f"(d[31]), "+f"(d[32]), "+f"(d[33]), "+f"(d[34]), "+f"(d[35]), "+f"(d[36]), "+f"(d[37]), "+f"(d[38]), "+f"(d[39]), "+f"(d[40]), "+f"(d[41]), "+f"(d[42]), "+f"(d[43]), "+f"(d[44]), "+f"(d[45]), "+f"(d[46]), "+f"(d[47]), "+f"(d[48]), "+f"(d[49]), "+f"(d[50]), "+f"(d[51]), "+f"(d[52]), "+f"(d[53]), "+f"(d[54]), "+f"(d[55]), "+f"(d[56]), "+f"(d[57]), "+f"(d[58]), "+f"(d[59]), "+f"(d[60]), "+f"(d[61]), "+f"(d[62]), "+f"(d[63]), "+f"(d[64]), "+f"(d[65]), "+f"(d[66]), "+f"(d[67]), "+f"(d[68]), "+f"(d[69]), "+f"(d[70]), "+f"(d[71]), "+f"(d[72]), "+f"(d[73]), "+f"(d[74]), "+f"(d[75]), "+f"(d[76]), "+f"(d[77]), "+f"(d[78]), "+f"(d[79]), "+f"(d[80]), "+f"(d[81]), "+f"(d[82]), "+f"(d[83]), "+f"(d[84]), "+f"(d[85]), "+f"(d[86]), "+f"(d[87]), "+f"(d[88]), "+f"(d[89]), "+f"(d[90]), "+f"(d[91]), "+f"(d[92]), "+f"(d[93]), "+f"(d[94]), "+f"(d[95]), "+f"(d[96]), "+f"(d[97]), "+f"(d[98]), "+f"(d[99]), "+f"(d[100]), "+f"(d[101]), "+f"(d[102]), "+f"(d[103]), "+f"(d[104]), "+f"(d[105]), "+f"(d[106]), "+f"(d[107]), "+f"(d[108]), "+f"(d[109]), "+f"(d[110]), "+f"(d[111]), "+f"(d[112]), "+f"(d[113]), "+f"(d[114]), "+f"(d[115]), "+f"(d[116]), "+f"(d[117]), "+f"(d[118]), "+f"(d[119]), "+f"(d[120]), "+f"(d[121]), "+f"(d[122]), "+f"(d[123]), "+f"(d[124]), "+f"(d[125]), "+f"(d[126]), "+f"(d[127])
    : "r"(a[0]), "r"(a[1]), "r"(a[2]), "r"(a[3]), "l"(db), "r"(scale_d));
}
__device__ __forceinline__ void wgmma_n256_rs0(float (&d)[192], const uint32_t (&a)[4], uint64_t db) {
  asm volatile("{\n.reg .pred p;\nsetp.ne.b32 p, 0, 0;\n"
    "wgmma.mma_async.sync.aligned.m64n256k16.f32.bf16.bf16 {%0, %1, %2, %3, %4, %5, %6, %7, %8, %9, %10, %11, %12, %13, %14, %15, %16, %17, %18, %19, %20, %21, %22, %23, %24, %25, %26, %27, %28, %29, %30, %31, %32, %33, %34, %35, %36, %37, %38, %39, %40, %41, %42, %43, %44, %45, %46, %47, %48, %49, %50, %51, %52, %53, %54, %55, %56, %57, %58, %59, %60, %61, %62, %63, %64, %65, %66, %67, %68, %69, %70, %71, %72, %73, %74, %75, %76, %77, %78, %79, %80, %81, %82, %83, %84, %85, %86, %87, %88, %89, %90, %91, %92, %93, %94, %95, %96, %97, %98, %99, %100, %101, %102, %103, %104, %105, %106, %107, %108, %109, %110, %111, %112, %113, %114, %115, %116, %117, %118, %119, %120, %121, %122, %123, %124, %125, %126, %127}, {%128, %129, %130, %131}, %132, p, 1, 1, 1;\n}\n"
    : "=f"(d[0]), "=f"(d[1]), "=f"(d[2]), "=f"(d[3]), "=f"(d[4]), "=f"(d[5]), "=f"(d[6]), "=f"(d[7]), "=f"(d[8]), "=f"(d[9]), "=f"(d[10]), "=f"(d[11]), "=f"(d[12]), "=f"(d[13]), "=f"(d[14]), "=f"(d[15]), "=f"(d[16]), "=f"(d[17]), "=f"(d[18]), "=f"(d[19]), "=f"(d[20]), "=f"(d[21]), "=f"(d[22]), "=f"(d[23]), "=f"(d[24]), "=f"(d[25]), "=f"(d[26]), "=f"(d[27]), "=f"(d[28]), "=f"(d[29]), "=f"(d[30]), "=f"(d[31]), "=f"(d[32]), "=f"(d[33]), "=f"(d[34]), "=f"(d[35]), "=f"(d[36]), "=f"(d[37]), "=f"(d[38]), "=f"(d[39]), "=f"(d[40]), "=f"(d[41]), "=f"(d[42]), "=f"(d[43]), "=f"(d[44]), "=f"(d[45]), "=f"(d[46]), "=f"(d[47]), "=f"(d[48]), "=f"(d[49]), "=f"(d[50]), "=f"(d[51]), "=f"(d[52]), "=f"(d[53]), "=f"(d[54]), "=f"(d[55]), "=f"(d[56]), "=f"(d[57]), "=f"(d[58]), "=f"(d[59]), "=f"(d[60]), "=f"(d[61]), "=f"(d[62]), "=f"(d[63]), "=f"(d[64]), "=f"(d[65]), "=f"(d[66]), "=f"(d[67]), "=f"(d[68]), "=f"(d[69]), "=f"(d[70]), "=f"(d[71]), "=f"(d[72]), "=f"(d[73]), "=f"(d[74]), "=f"(d[75]), "=f"(d[76]), "=f"(d[77]), "=f"(d[78]), "=f"(d[79]), "=f"(d[80]), "=f"(d[81]), "=f"(d[82]), "=f"(d[83]), "=f"(d[84]), "=f"(d[85]), "=f"(d[86]), "=f"(d[87]), "=f"(d[88]), "=f"(d[89]), "=f"(d[90]), "=f"(d[91]), "=f"(d[92]), "=f"(d[93]), "=f"(d[94]), "=f"(d[95]), "=f"(d[96]), "=f"(d[97]), "=f"(d[98]), "=f"(d[99]), "=f"(d[100]), "=f"(d[101]), "=f"(d[102]), "=f"(d[103]), "=f"(d[104]), "=f"(d[105]), "=f"(d[106]), "=f"(d[107]), "=f"(d[108]), "=f"(d[109]), "=f"(d[110]), "=f"(d[111]), "=f"(d[112]), "=f"(d[113]), "=f"(d[114]), "=f"(d[115]), "=f"(d[116]), "=f"(d[117]), "=f"(d[118]), "=f"(d[119]), "=f"(d[120]), "=f"(d[121]), "=f"(d[122]), "=f"(d[123]), "=f"(d[124]), "=f"(d[125]), "=f"(d[126]), "=f"(d[127])
    : "r"(a[0]), "r"(a[1]), "r"(a[2]), "r"(a[3]), "l"(db));
}

constexpr int SLOT = 16384;
constexpr int VB = 4 * SLOT, PH = 0, XS = 6;
constexpr int SM_SD = 13 * SLOT;
constexpr int SM_BAR = SM_SD + 8192;
constexpr int SM_RS = SM_BAR + 1024;
constexpr int SM_AP = SM_RS + 640;
constexpr int SM_BP = SM_AP + 2048;
constexpr int SM_EPOCH = SM_BP + 6144;
constexpr int SM_TOTAL = SM_EPOCH + 16;
constexpr int FM = 0, FT = 16, FW = 30, CM = 46, CT = 62, CW = 76, B_EF = 92, B_STAT = 93, B_KVF = 94, B_HALO = 95,
              B_KVDONE = 96, B_OH0 = 97, B_OH1 = 98, B_XH0 = 99, B_XDONE = 100, B_WFD = 101, B_XT = 102, B_OF0 = 103, B_KVF1 = 104, B_KVS = 105, B_RAW = 106  , B_X0 = 108, B_KVS0 = 109;
constexpr uint64_t BAR_LG = 0x00043333330004ull;
#define BA(i) (bar + (i) * 8)
#define REL2(i) release2c(SB0 + SM_BAR + (i) * 8)
constexpr int NF = 3, ND = 13, NR = 0, NWOP = 48, NAOP = 38;
constexpr bool EF_USED = false;
constexpr uint64_t TL_A = 0x6278627862786ull, TL_B = 0xa9c3ba9c3ba9cull, WO_A = 0x76b24038b51403ffull, WO_B = 0x8c5a197c6a297c8bull;
__constant__ uint32_t c_wop[NWOP + 1] = {0xeb0009, 0x186b8000, 0x6c0112, 0x1aec011a, 0x6c8224, 0x22ec822b, 0x18170330, 0x18178442, 0x18180554, 0x18188660, 0x18190772, 0x18198884, 0x181a0990, 0x181a8aa2, 0x181b0bb4, 0x181b8cc0, 0xaed10fc, 0xa9711e9, 0x181c0dd2, 0xa9792da, 0x129813cb, 0x181c8ee4, 0x181d0ff0, 0x109d94b3, 0x109f15ac, 0x109f9699, 0x10a0178a, 0x10a0987b, 0x10a11963, 0x10a19a5c, 0x10a21b49, 0x10a29c3a, 0x9231e0b, 0x9239f18, 0x1124202c, 0x13242137, 0x1124a249, 0x1324a352, 0x1125246a, 0x13252576, 0x1127268c, 0x1127a797, 0x112828a9, 0x1128a9b1, 0x11292aca, 0x13292bd5, 0x112a2cec, 0x132a2df8, 0};
__constant__ uint32_t c_aop[NAOP + 1] = {0x6d8228, 0x170336, 0x178447, 0x180558, 0x188666, 0x190777, 0x198888, 0x1a0996, 0x1a8aa7, 0x1b0bb8, 0x1b8cc6, 0x1c0dd7, 0x1c8ee8, 0x1d0ff6, 0x1d93c2, 0x1f14b6, 0x1f95a8, 0x201697, 0x209782, 0x211876, 0x219968, 0x221a57, 0x229b42, 0x231c36, 0xa3a023, 0xb12130, 0x2b12244, 0x2b12351, 0x2b12465, 0xa6257b, 0xa6a688, 0xa72793, 0xa7a8a0, 0xa829b4, 0xa8aac2, 0xa9abdb, 0x2a9ace6, 0xaaadf7, 0};
__constant__ uint32_t c_map[64] = {4, 5, 6, 7, 0, 16, 32, 48, 64, 80, 96, 112, 1, 17, 33, 49, 65, 81, 97, 113, 2, 18, 34, 50, 66, 82, 98, 114, 3, 19, 35, 51, 67, 83, 99, 115, 20, 36, 52, 68, 84, 100, 116, 21, 37, 53, 69, 85, 101, 117, 22, 38, 54, 70, 86, 102, 118, 23, 39, 55, 71, 87, 103, 119};
enum { MAP_WF = 0, MAP_WA = 2, MAP_WB = 4, MAP_WOA = 6, MAP_WOB = 8, MAP_X0 = 10, MAP_X = 11, MAP_O = 12, MAP_PHI = 13, NMAP = 14 };
struct Maps { CUtensorMap m[NMAP]; };

#define PL 2
#define PROFL(a, b)
#define SUBS 16
#define CHW 4
#define SUBS1 16
#define XRAT 10
#define XRN 4
#define BT1 1
#define ST1 8
#define X0AT 2
#define W1DL 400
#define SKA 0
#define SKB 0
#define BPRE 0
#define XST 0
#define WH 4
#define PFM 3
#define PFS 2
#define SVD 5000
#define NLAYERS 4
constexpr float L2E = 1.4426950408889634f;

#define D128(lo) desc64(lo, 0x40000040u)
struct Ctx { uint32_t zero, boff; const bf16* x0; bf16* out; };
#define BLK_CTX() \
  uint32_t bid_; asm volatile("mov.u32 %0, %%ctaid.x;" : "=r"(bid_)); \
  bid_ -= c.boff; \
  const uint32_t gr_ = c_map[bid_ >> 1]; \
  const int cr = bid_ & 1, g = gr_ & 7, rb = (gr_ >> 3) + cr, m0 = rb * 128; \
  const uint32_t sb = SB0 + (cr << 24); \
  const uint32_t bar = sb + SM_BAR; \
  (void)cr; (void)g; (void)rb; (void)m0; (void)bar;
extern __shared__ uint8_t smem_raw[];
constexpr uint32_t SB0 = 1024;

#define PHASE_CTX() \
  BLK_CTX(); \
  int tid_ = threadIdx.x; asm volatile("" : "+r"(tid_)); \
  const int lane = tid_ & 31, cw = (tid_ >> 5) - 4, wg = cw >> 2, wq = cw & 3, gq = lane >> 2, t = lane & 3, wrow0 = cw * 16; \
  const int lrow = (lane & 7) + ((lane >> 3) & 1) * 8, lchk = lane >> 4; \
  const bool elected = (tid_ & 127) == 0; \
  const uint32_t rowo = (wrow0 + lrow) * 128, X = (lchk ^ (lane & 7)) << 4; \
  const uint32_t Y = (wrow0 + (lane & 7)) * 128 + (((lane >> 3) ^ (lane & 7)) << 4); \
  const size_t gfr = (size_t)(m0 + wrow0 + gq) * D_ + g * 128 + 8 * t; \
  (void)bar; (void)wq; (void)gq; (void)lrow; (void)lchk; (void)elected; (void)wrow0; (void)wg; (void)rowo; (void)X; (void)t; (void)Y; (void)gfr;
#define MMA_CTX() \
  const uint32_t wu = __shfl_sync(0xffffffffu, wg, 0); \
  const uint32_t dA0 = ((SB0 >> 4) | (1u << 16)) + wu * 512, dB0 = (SB0 >> 4) | (512u << 16); \
  const uint32_t par = layer & 1;

__device__ __forceinline__ void slab_out_half(uint32_t slot, bf16* dst, int wrow0, int lane) {
  const int r0 = lane >> 3, ch = lane & 7;
  const uint32_t src = slot + (wrow0 + r0) * 128;
  uint4 v[4];
#pragma unroll
  for (int i = 0; i < 4; ++i) v[i] = lds128(src + i * 512 + (((ch ^ (4 * i + r0)) & 7) << 4));
  dst += (size_t)(wrow0 + r0) * D_ + ch * 8;
#pragma unroll
  for (int i = 0; i < 4; ++i) *reinterpret_cast<uint4*>(dst + (size_t)i * 4 * D_) = v[i];
}

__device__ __forceinline__ void consumer(const Ctx& c) {
  float acc[192];
  uint32_t xf[4][4];
  uint32_t xp[8][4];
  {
    PHASE_CTX();
    const unsigned int epoch = ld_relaxed(&g_epoch);
    PROFT(tid_ == 128, 0);
    const uint32_t wu = __shfl_sync(0xffffffffu, wg, 0);
    if (tid_ < 128 + 8) sts128(sb + SM_AP + lane * 16, make_uint4(0x3F803F80u, 0x3F803F80u, 0x3F803F80u, 0x3F803F80u));
#pragma unroll 1
    for (int it = 0; it < 2; ++it) {
      float p[4][16];
      mbar_wait(BA(B_RAW + it), 0);
      PROFT(tid_ == 128, it ? 15 : 2);
      const uint32_t da = ((SB0 >> 4) | (1u << 16)) + (wu ? 9 + it : 2 * it) * 1024, db = (SB0 + SM_SD) >> 4;
      wgmma_fence();
#pragma unroll
      for (int h = 0; h < 4; ++h) wgmma_n32_0(p[h], D128(da + (h >> 1) * 512 + (h & 1) * 4), desc64(db + h * 128, 0x80000020u));
#pragma unroll
      for (int h = 0; h < 4; ++h) wgmma_n32(p[h], D128(da + (h >> 1) * 512 + (h & 1) * 4 + 2), desc64(db + h * 128 + 64, 0x80000020u), 1);
      wgmma_commit();
      wgmma_wait<0>();
#pragma unroll
      for (int i = 0; i < 64; ++i) asm volatile("" : "+f"(p[i >> 4][i & 15]) :: "memory");
      const uint32_t base = sb + (wg ? 9 + it : 2 * it) * SLOT + (wq * 16 + gq) * 128;
      uint32_t w[4][4][2];
#pragma unroll
      for (int i = 0; i < 32; ++i) w[i >> 3][(i >> 1) & 3][i & 1] = pack_bf16(p[i >> 3][2 * (i & 7)], p[i >> 3][2 * (i & 7) + 1]);
      if (wu) {
#pragma unroll
        for (int i = 0; i < 8; ++i)
          sts128(base + (i >> 2) * 8192 + (i & 1) * 1024 + (((((i >> 1) & 1) * 4 + t) ^ gq) << 4), make_uint4(w[i >> 1][0][i & 1], w[i >> 1][1][i & 1], w[i >> 1][2][i & 1], w[i >> 1][3][i & 1]));
      } else {
#pragma unroll
        for (int i = 0; i < 16; ++i)
          sts64(base + (i >> 3) * 8192 + (i & 1) * 1024 + ((((t & 1) * 4 + ((i >> 1) & 3)) ^ gq) << 4) + (t >> 1) * 8, w[(i >> 3) * 2][(i >> 1) & 3][i & 1], w[(i >> 3) * 2 + 1][(i >> 1) & 3][i & 1]);
      }
      fence_async_smem();
      __syncwarp();
      if (it == cr && lane == 0) mbar_arrive(BA(B_WFD));
    }
    if (tid_ == 128) sts_f(sb + SM_EPOCH, __uint_as_float(epoch & 1));
#pragma unroll
    for (int i = 0; i < 32; ++i) xp[i >> 2][i & 3] = 0u;
    nbar<1, 256>();
    PROFT(tid_ == 128, 13);
    mbar_wait(BA(FM + cr), 0);
    float cs[3][4];
    wgmma_fence();
#pragma unroll
    for (int ks = 0; ks < 4; ++ks)
#pragma unroll
      for (int i = 0; i < 3; ++i) {
        const uint32_t bx = (i == 0 ? 2 * cr * 1024 : i == 1 ? (2 * cr + 1) * 1024 : (9 + cr) * 1024) + wu * 512;
        wgmma_n8_t(cs[i], D128(((SB0 >> 4) | (512u << 16)) + bx + ks * 128), desc64((SB0 + SM_AP) >> 4, 0), ks != 0);
      }
    wgmma_commit();
    mbar_wait(BA(FM), 0);
#pragma unroll
    for (int k = 0; k < 4; ++k) ldsm_x4(xf[k][0], xf[k][1], xf[k][2], xf[k][3], sb + XS * SLOT + rowo + (X ^ (k << 5)));
    wgmma_wait<0>();
#pragma unroll
    for (int i = 0; i < 12; ++i) asm volatile("" : "+f"(cs[i >> 2][i & 3]) :: "memory");
    if (t < 2) {
#pragma unroll
      for (int i = 0; i < 3; ++i) red_add1(g_cs + (epoch & 1) * 6144 + g * 384 + i * 128 + wg * 64 + wq * 16 + gq + t * 8, t ? cs[i][2] : cs[i][0]);
    }
    PROFT(tid_ == 128, 14);
  }
#pragma unroll 1
  for (int layer = 0;; ++layer) {
    {
      wgmma_fence();
      wgmma_n256_rs0(acc, xf[0], D128((SB0 >> 4) | (512u << 16)));
#pragma unroll
      for (int k = 1; k < 4; ++k) wgmma_n256_rs(acc, xf[k], D128(((SB0 >> 4) | (512u << 16)) + k * 128), 1);
      wgmma_commit();
      PHASE_CTX();
      MMA_CTX();
      {
        const uint32_t ep = __float_as_uint(lds_f(sb + SM_EPOCH));
        if (layer == 0) {
          mbar_wait(BA(B_X0), 0);
#pragma unroll
          for (int i = 0; i < 8; ++i) ldsm_x4(xp[i][0], xp[i][1], xp[i][2], xp[i][3], sb + (11 + (i >> 2)) * SLOT + (Y ^ ((i & 2) << 5)) + (i & 1) * 1024);
          if (lane == ((xp[0][0] ^ xp[1][0] ^ xp[2][0] ^ xp[3][0] ^ xp[7][0]) & c.zero)) REL2(B_XT);
        } else {
#pragma unroll
          for (int i = 0; i < 8; ++i) stsm_x4(sb + (XS + (i >> 2)) * SLOT + (Y ^ ((i & 2) << 5)) + (i & 1) * 1024, xp[i][0], xp[i][1], xp[i][2], xp[i][3]);
        }
        float s0 = 0.f, s1 = 0.f, q0 = 0.f, q1 = 0.f;
        auto stats = [&](int j0, int j1) {
#pragma unroll
          for (int j = j0; j < j1; ++j) {
            const uint32_t u0 = xp[(j >> 2) * 2][j & 3], u1 = xp[(j >> 2) * 2 + 1][j & 3];
            s0 += bf_lo(u0) + bf_hi(u0); s1 += bf_lo(u1) + bf_hi(u1);
            q0 = fmaf(bf_lo(u0), bf_lo(u0), fmaf(bf_hi(u0), bf_hi(u0), q0)); q1 = fmaf(bf_lo(u1), bf_lo(u1), fmaf(bf_hi(u1), bf_hi(u1), q1));
          }
        };
        stats(0, ST1);
        fence_async_smem();
        nbar_dyn(3 + wu + (__float_as_uint(s0 + s1 + q0 + q1) & c.zero), 128);
        mbar_wait(BA(FM + 1), par);
        wgmma_fence();
#pragma unroll
        for (int k = 0; k < 4; ++k) wgmma_n256(acc, D128(dA0 + (XS + 1) * 1024 + k * 2), D128(dB0 + 2048 + k * 128), 1);
        wgmma_commit();
        wgmma_wait<1>();
#pragma unroll
        for (int i = 4; i < 8; ++i) stg128_p(layer, g_x + gfr + (i & 1) * 8 * D_ + (i >> 1) * 32, xp[i][0], xp[i][1], xp[i][2], xp[i][3]);
        {
          uint32_t zc; asm volatile("mov.u32 %0, %%clock;" : "=r"(zc) :: "memory");
          q0 += __uint_as_float(zc & c.zero); q1 += __uint_as_float(zc & c.zero); s0 += __uint_as_float(zc & c.zero); s1 += __uint_as_float(zc & c.zero);
        }
        stats(ST1, 16);
        wgmma_fence();
        wgmma_n128_0(acc, D128(dA0 + XS * 1024), D128(dB0 + 9 * 1024));
#pragma unroll
        for (int k = 1; k < 4; ++k) wgmma_n128(acc, D128(dA0 + XS * 1024 + k * 2), D128(dB0 + 9 * 1024 + k * 128), 1);
        wgmma_commit();
        const bool od = t & 1;
        float sa = od ? s1 : s0, qa = od ? q1 : q0;
        sa += __shfl_xor_sync(0xffffffffu, od ? s0 : s1, 1);
        qa += __shfl_xor_sync(0xffffffffu, od ? q0 : q1, 1);
        wgmma_fence();
#pragma unroll
        for (int k = 0; k < 4; ++k) wgmma_n128(acc, D128(dA0 + (XS + 1) * 1024 + k * 2), D128(dB0 + 10 * 1024 + k * 128), 1);
        wgmma_commit();
        sa += __shfl_xor_sync(0xffffffffu, sa, 2);
        qa += __shfl_xor_sync(0xffffffffu, qa, 2);
        red_add2_p(t < 2, reinterpret_cast<float*>(g_stats + (ep * 4 + layer) * S_ + m0 + wrow0 + gq + t * 8), sa, qa);
        __syncwarp();
        if (lane == 0) mbar_arrive(BA(B_XDONE));
        wgmma_wait<1>();
        if (elected) REL2(CM);
      }
      uint32_t s = 2;
#pragma unroll 1
      for (int i = 2; i < NF; ++i) {
        PROFL(tid_ == 128 && layer == PL + 1, 244 + 2 * i);
        mbar_wait(BA(FM + i), par);
        PROFL(tid_ == 128 && layer == PL + 1, 245 + 2 * i);
        const uint32_t da = dA0 + (XS + s) * 1024, dk = dB0 + s * 2048, dq = dB0 + (9 + s) * 1024;
        wgmma_fence();
#pragma unroll
        for (int k = 0; k < 4; ++k) wgmma_n128(acc, D128(da + k * 2), D128(dq + k * 128), 1);
        wgmma_commit();
        wgmma_wait<1>();
        if (elected) REL2(CM + i - 1);
        wgmma_fence();
#pragma unroll
        for (int k = 0; k < 4; ++k) wgmma_n256(acc, D128(da + k * 2), D128(dk + k * 128), 1);
        wgmma_commit();
        if (++s == 3) s = 0;
      }
#pragma unroll 1
      for (int i = NF; i < 15; ++i) {
        mbar_wait(BA(FM + i), par);
        const uint32_t da = dA0 + (XS + s) * 1024, dk = dB0 + s * 2048;
        wgmma_fence();
#pragma unroll
        for (int k = 0; k < 4; ++k) wgmma_n256(acc, D128(da + k * 2), D128(dk + k * 128), 1);
        wgmma_commit();
        wgmma_wait<1>();
        if (elected) REL2(CM + i - 1);
        if (++s == 3) s = 0;
      }
      {
        const uint64_t dap = desc64(((SB0 + SM_AP) >> 4) + wu * 64, 8), dbp = make_desc_ns(SB0 + SM_BP, 0, 128);
        mbar_wait(BA(B_STAT), par);
        mbar_wait(BA(FM + 15), par);
        PROFT(tid_ == 128, layer * 16 + 9);
        wgmma_fence();
        wgmma_n256_k(acc, dap, dbp, 1);
#pragma unroll
        for (int k = 0; k < 4; ++k) wgmma_n256(acc, D128(dA0 + XS * 1024 + k * 2), D128(dB0 + k * 128), 1);
        wgmma_commit();
        wgmma_wait<1>();
        if (elected) REL2(CM + 14);
        mbar_wait(BA(FT), par);
        wgmma_fence();
        wgmma_n128_k(acc, dap, dbp + 256, 1);
#pragma unroll
        for (int k = 0; k < 4; ++k) wgmma_n128(acc, D128(dA0 + (uint32_t)(TL_A & 15) * 1024 + k * 2), D128(dB0 + (uint32_t)(TL_B & 15) * 1024 + k * 128), 1);
        wgmma_commit();
        wgmma_wait<1>();
        if (elected) REL2(CM + 15);
#pragma unroll
        for (int i = 0; i < 128; ++i) asm volatile("" : "+f"(acc[i]) :: "memory");
      }
    }
    uint32_t of[8][4], o1[4][4];
    {
      PHASE_CTX();
      MMA_CTX();
      PROFT(tid_ == 128, layer * 16 + 1);
      PROFT(lane == 0 && layer == PL, 192 + cw);
      PROFT(tid_ == 128 && layer == PL, 160);
      uint64_t ta = (TL_A >> 4), tw = TL_B >> 4;
      uint32_t da, db, dz = dA0;
      auto sub = [&](int n) {
        const int j = n >> 2, k = n & 3;
        if (k == 0) {
          dz += c.zero;
          da = dz + ((uint32_t)ta & 15) * 1024; db = dB0 + ((uint32_t)tw & 15) * 1024;
          ta >>= 4; tw >>= 4;
          mbar_wait(BA(FT + j), par);
          wgmma_fence();
        }
        wgmma_n128(acc, D128(da + k * 2), D128(db + k * 128), 1);
        if (k == 3) {
          wgmma_commit();
          wgmma_wait<1>();
          if (elected) REL2(CT + j - 1);
        }
      };
      auto run = [&](int j0, int j1) {
#pragma unroll 1
        for (int j = j0; j < j1; ++j) {
          mbar_wait(BA(FT + j), par);
          da = dA0 + ((uint32_t)ta & 15) * 1024; db = dB0 + ((uint32_t)tw & 15) * 1024;
          ta >>= 4; tw >>= 4;
          wgmma_fence();
#pragma unroll
          for (int k = 0; k < 4; ++k) wgmma_n128(acc, D128(da + k * 2), D128(db + k * 128), 1);
          wgmma_commit();
          wgmma_wait<1>();
          if (elected) REL2(CT + j - 1);
        }
        ta = TL_A >> (4 * j1); tw = TL_B >> (4 * j1);
      };
      auto rest = [&](int j0, int sk) {
        if (sk) {
          run(j0, ND - sk);
          if (wu == 0) nbar<6, 256>();
          j0 = ND - sk;
        }
        run(j0, ND);
        if (sk && wu) asm volatile("bar.arrive 6, 256;" ::: "memory");
      };
      auto rest_end = [&]() {
        wgmma_wait<0>();
        if (elected) REL2(CT + ND - 1);
#pragma unroll
        for (int i = 128; i < 192; ++i) asm volatile("" : "+f"(acc[i]) :: "memory");
      };
      auto wo0 = [&]() {
        wgmma_fence();
        wgmma_n128_rs0(acc, of[0], D128(dB0 + (uint32_t)(WO_B & 15) * 1024));
#pragma unroll
        for (int k = 1; k < 4; ++k) wgmma_n128_rs(acc, of[k], D128(dB0 + (uint32_t)(WO_B & 15) * 1024 + k * 128), 1);
        wgmma_commit();
      };
      const float rs0 = lds_f(sb + SM_RS + (16 + wrow0 + gq) * 4), rs1 = lds_f(sb + SM_RS + (24 + wrow0 + gq) * 4);
#define EPOCH() __float_as_uint(lds_f(sb + SM_EPOCH))
      mbar_wait(BA(CM + 14), par);
      if (par) {
        uint32_t kk[8][4], kp[8][4], vf[2][2][4][4];
        int sn = 4;
        float rj[4];
#pragma unroll
        for (int nt = 0; nt < 4; ++nt) rj[nt] = lds_f(sb + SM_RS + (wrow0 + nt * 8 + 2 * t + (gq & 1)) * 4);
#pragma unroll
        for (int i = 0; i < 4 * BT1; ++i) sub(sn++);
        {
          uint32_t vv[8][4];
#pragma unroll
          for (int jp = 0; jp < 8; ++jp) {
            kk[jp][0] = pack_bf16(acc[8 * jp], acc[8 * jp + 1]); kk[jp][1] = pack_bf16(acc[8 * jp + 4], acc[8 * jp + 5]);
            kk[jp][2] = pack_bf16(acc[8 * jp + 2], acc[8 * jp + 3]); kk[jp][3] = pack_bf16(acc[8 * jp + 6], acc[8 * jp + 7]);
#pragma unroll
            for (int i = 0; i < 4; ++i) vv[jp][i] = pack_bf16(acc[64 + 8 * jp + 2 * i], acc[65 + 8 * jp + 2 * i]);
          }
          if (cw == 7) {
            uint32_t* const hbuf = g_halo + (size_t)(((layer >> 1) * 17 + rb + 1) * 8 + g) * 2048;
#pragma unroll
            for (int jp = 0; jp < 8; ++jp) stg128(hbuf + jp * 128 + lane * 4, kk[jp][0], kk[jp][1], kk[jp][2], kk[jp][3]);
#pragma unroll
            for (int i = 0; i < 32; ++i) hbuf[1024 + (i >> 4) * 512 + (gq + (i & 1) * 8) * 32 + ((((i >> 1) & 7) ^ gq) << 2) + t] = vv[i >> 2][i & 3];
            __syncwarp();
            if (lane == 0) mbar_arrive(BA(B_OF0));
          }
#pragma unroll
          for (int jp = 0; jp < 8; ++jp) {
            sub(sn++);
            stsm_x4(sb + VB + (jp >> 2) * SLOT + rowo + (X ^ ((jp & 3) << 5)), vv[jp][0], vv[jp][1], vv[jp][2], vv[jp][3]);
          }
        }
        PROFT(tid_ == 128, layer * 16 + 2);
        const int e = gq & 1;
        float f0[4], f1[4], b0[4], b1[4];
#pragma unroll
        for (int nt = 0; nt < 4; ++nt) {
          const int kx = nt * 8 + 2 * t + e;
          const bool okk = (m0 + wrow0 + kx) >= 16;
          const int d0 = kx - gq, d1 = d0 - 8;
          const bool m0_ = okk && d0 >= 2 && d0 <= 16, m1_ = okk && d1 >= 2 && d1 <= 16;
          f0[nt] = m0_ ? rj[nt] * rs0 * (0.17677669529663687f * L2E) : 0.f;
          f1[nt] = m1_ ? rj[nt] * rs1 * (0.17677669529663687f * L2E) : 0.f;
          b0[nt] = m0_ ? 0.f : -1e30f; b1[nt] = m1_ ? 0.f : -1e30f;
        }
        uint32_t ko = sb + PH + cw * 4096 + lane * 16;
        mbar_wait(BA(CM + 15), par);
#pragma unroll
        for (int jp = 0; jp < 8; ++jp) {
          sub(sn++);
          sts128(ko + jp * 512, make_uint4(kk[jp][0], kk[jp][1], kk[jp][2], kk[jp][3]));
        }
#pragma unroll
        for (int i = 0; i < 4; ++i) sub(sn++);
        nbar<1, 256>();
        PROFT(tid_ == 128, layer * 16 + 3);
        rest(sn >> 2, SKB);
        if (!BPRE) rest_end();
        PROFT(lane == 0 && layer == PL, 200 + cw);
        PROFT(tid_ == 128, layer * 16 + 10);
        if (cw == 0) mbar_wait(BA(B_HALO), (layer >> 1) & 1);
        PROFT(tid_ == 128, layer * 16 + 5);
        const uint32_t vs = sb + (cw ? VB + rowo - 2048 : SM_SD + 4096 + rowo), vst = cw ? SLOT : 2048;
        asm volatile("" : "+r"(ko));
        const uint32_t ka = ko + (cw ? -4096 : SM_SD - PH);
        const uint32_t psel = e ? 0x1054u : 0x5410u;
#pragma unroll
        for (int hp = 0; hp < 2; ++hp) {
#pragma unroll
          for (int i = 4 * hp; i < 4 * hp + 4; ++i) {
            const uint4 u = lds128(ka + i * 512);
            kp[i][0] = u.x; kp[i][1] = u.y; kp[i][2] = u.z; kp[i][3] = u.w;
          }
#pragma unroll
          for (int i = 4 * hp; i < 4 * hp + 4; ++i) {
            ldsm_x4_t(vf[0][i & 1][i >> 1][0], vf[0][i & 1][i >> 1][1], vf[0][i & 1][i >> 1][2], vf[0][i & 1][i >> 1][3], vs + (i >> 2) * vst + (X ^ ((i & 3) << 5)));
            ldsm_x4_t(vf[1][i & 1][i >> 1][0], vf[1][i & 1][i >> 1][1], vf[1][i & 1][i >> 1][2], vf[1][i & 1][i >> 1][3], sb + VB + (i >> 2) * SLOT + rowo + (X ^ ((i & 3) << 5)));
          }
          if (BPRE && !hp) rest_end();
          float l0[2][4], l1[2][4];
#pragma unroll
          for (int h = 0; h < 2; ++h) {
            const int H = 2 * hp + h;
            uint32_t qa[8];
#pragma unroll
            for (int i = 0; i < 8; ++i) qa[i] = pack_bf16(acc[128 + 16 * H + 2 * i], acc[129 + 16 * H + 2 * i]);
#pragma unroll
            for (int nt = 3; nt >= 0; --nt) {
              float sc[4] = {0.f, 0.f, 0.f, 0.f};
#pragma unroll
              for (int ks = 0; ks < 2; ++ks) {
                const uint32_t (&kf)[4] = nt < 2 ? kp[2 * H + ks] : kk[2 * H + ks];
                mma_bf16(sc, qa[4 * ks], qa[4 * ks + 1], qa[4 * ks + 2], qa[4 * ks + 3], kf[2 * (nt & 1)], kf[2 * (nt & 1) + 1]);
              }
              l0[h][nt] = fmaf(e ? sc[1] : sc[0], f0[nt], b0[nt]);
              l1[h][nt] = fmaf(e ? sc[3] : sc[2], f1[nt], b1[nt]);
            }
          }
          float mx0[2], mx1[2], s0[2], s1[2];
#pragma unroll
          for (int h = 0; h < 2; ++h) {
            mx0[h] = fmaxf(fmaxf(l0[h][0], l0[h][1]), l0[h][2]);
            mx1[h] = fmaxf(fmaxf(l1[h][1], l1[h][2]), l1[h][3]);
          }
#pragma unroll
          for (int o = 1; o <= 2; o <<= 1)
#pragma unroll
            for (int h = 0; h < 2; ++h) {
              mx0[h] = fmaxf(mx0[h], __shfl_xor_sync(0xffffffffu, mx0[h], o));
              mx1[h] = fmaxf(mx1[h], __shfl_xor_sync(0xffffffffu, mx1[h], o));
            }
#pragma unroll
          for (int h = 0; h < 2; ++h) {
#pragma unroll
            for (int nt = 0; nt < 3; ++nt) { l0[h][nt] = ex2(l0[h][nt] - mx0[h]); l1[h][nt + 1] = ex2(l1[h][nt + 1] - mx1[h]); }
            s0[h] = (l0[h][0] + l0[h][1]) + l0[h][2];
            s1[h] = (l1[h][1] + l1[h][2]) + l1[h][3];
          }
#pragma unroll
          for (int o = 1; o <= 2; o <<= 1)
#pragma unroll
            for (int h = 0; h < 2; ++h) {
              s0[h] += __shfl_xor_sync(0xffffffffu, s0[h], o);
              s1[h] += __shfl_xor_sync(0xffffffffu, s1[h], o);
            }
          uint32_t ow[2][2][4];
#pragma unroll
          for (int h = 0; h < 2; ++h) {
            const int H = 2 * hp + h;
            uint32_t pl[4], ph[4];
            const float i0 = rcp(s0[h]), i1 = rcp(s1[h]);
#pragma unroll
            for (int nt = 0; nt < 4; ++nt) {
              const uint32_t pk = pack_bf16(nt < 3 ? l0[h][nt] * i0 * rj[nt] : 0.f, nt > 0 ? l1[h][nt] * i1 * rj[nt] : 0.f);
              pl[nt] = nt < 3 ? __byte_perm(pk, 0u, psel) : 0u;
              ph[nt] = nt > 0 ? __byte_perm(pk, 0u, psel + 0x2222u) : 0u;
            }
#pragma unroll
            for (int nj = 0; nj < 4; ++nj) {
              float oa[4] = {0.f, 0.f, 0.f, 0.f};
#pragma unroll
              for (int ks = 0; ks < 2; ++ks)
                mma_bf16(oa, pl[2 * ks], ph[2 * ks], pl[2 * ks + 1], ph[2 * ks + 1], vf[ks][nj >> 1][H][2 * (nj & 1)], vf[ks][nj >> 1][H][2 * (nj & 1) + 1]);
              ow[h][0][nj] = pack_bf16(oa[0], oa[1]); ow[h][1][nj] = pack_bf16(oa[2], oa[3]);
            }
          }
          if (hp == 0) {
#pragma unroll
            for (int i = 0; i < 4; ++i) stg128(g_o + gfr + (i & 1) * 8 * D_ + (i >> 1) * 32, ow[i >> 1][i & 1][0], ow[i >> 1][i & 1][1], ow[i >> 1][i & 1][2], ow[i >> 1][i & 1][3]);
            __syncwarp();
            if (lane == 0) mbar_arrive(BA(B_OH0));
          } else {
#pragma unroll
            for (int i = 0; i < 16; ++i) o1[i >> 2][i & 3] = ow[i >> 3][(i >> 2) & 1][i & 3];
          }
#pragma unroll
          for (int i = 0; i < 16; ++i) of[4 * hp + (i >> 2)][i & 3] = ow[i >> 3][i & 1][(i >> 1) & 3];
          if (!hp) { PROFT(tid_ == 128, layer * 16 + 15); mbar_wait(BA(FW), par); }
        }
      } else {
        float sc[2] = {rs0 * L2E, rs1 * L2E};
        {
          const uint32_t vb = sb + VB + (rowo >> 1), X0 = (lchk ^ ((lane & 7) >> 1)) << 4;
          const uint32_t pb = sb + PH + (t & 1) * SLOT + (wrow0 + gq) * 128 + ((((t & 1) * 4 + (t & 2)) ^ gq) << 4);
          float kva[20], en[32], mx[2][2], mn[2][2];
#define PV(hp, j) acc[32 * (hp) + (j)]
          auto mm = [&](int hp, int j) {
            const int r = (j >> 1) & 1;
            if (j < 4 && !(j & 1)) { mx[hp][r] = PV(hp, j); mn[hp][r] = PV(hp, j); }
            else { mx[hp][r] = fmaxf(mx[hp][r], PV(hp, j)); mn[hp][r] = fminf(mn[hp][r], PV(hp, j)); }
          };
          auto mmx = [&](int hp) {
#pragma unroll
            for (int r = 0; r < 2; ++r) {
              mx[hp][r] = fmaxf(mx[hp][r], __shfl_xor_sync(0xffffffffu, mx[hp][r], 2)) * -sc[r];
              mn[hp][r] = fmaf(fminf(mn[hp][r], __shfl_xor_sync(0xffffffffu, mn[hp][r], 2)), sc[r], mx[hp][r]);
            }
          };
          auto stage = [&](int hp) {
#pragma unroll
            for (int i = 0; i < 20; ++i) asm volatile("" : "+f"(kva[i]) :: "memory");
            nbar_dyn(3 + wu, 128);
            const uint32_t ad = sb + VB + hp * SLOT + wg * 8192 + (2 * wq + ((lane >> 3) & 1)) * 640 + (lane & 7) * 16;
#pragma unroll
            for (int i = 0; i < 2; ++i)
              stsm_x4(ad + (2 * i + lchk) * 128, pack_bf16(kva[8 * i], kva[8 * i + 1]), pack_bf16(kva[8 * i + 2], kva[8 * i + 3]),
                      pack_bf16(kva[8 * i + 4], kva[8 * i + 5]), pack_bf16(kva[8 * i + 6], kva[8 * i + 7]));
            stsm_x2(ad + 512, pack_bf16(kva[16], 0.0625f), pack_bf16(kva[18], 0.0625f));
            fence_async_smem();
            __syncwarp();
            if (lane == 0) mbar_arrive(BA(B_KVDONE));
          };
          int sn = 4;
#pragma unroll
          for (int j = 0; j < 32; ++j) mm(0, j);
          mmx(0);
#pragma unroll
          for (int hp = 0; hp < 2; ++hp) {
            float sp[2] = {0.f, 0.f}, sm[2] = {0.f, 0.f};
#pragma unroll
            for (int j = 0; j < 32; ++j) {
              const int r = (j >> 1) & 1, ns = hp ? SUBS1 : SUBS;
              if ((j * ns) / 32 != ((j + 1) * ns) / 32) {
                sub(sn++);
                if (hp && sn == 4 + SUBS + 4 + 4 * (XST & 1)) { stage(0); PROFT(tid_ == 128, layer * 16 + 12); }
              }
              const float x = fmaf(PV(hp, j), sc[r], mx[hp][r]);
              PV(hp, j) = ex2(x); en[j] = ex2(mn[hp][r] - x);
              sp[r] += PV(hp, j); sm[r] += en[j];
              if (hp == 0) {
                mm(1, j);
                if ((j & 3) == 0) {
                  const int jp = 8 + (j >> 2);
                  stsm_x4(vb + ((jp - 8) >> 1) * 8192 + (X0 ^ ((jp & 1) << 5)), pack_bf16(acc[8 * jp], acc[8 * jp + 1]), pack_bf16(acc[8 * jp + 2], acc[8 * jp + 3]),
                          pack_bf16(acc[8 * jp + 4], acc[8 * jp + 5]), pack_bf16(acc[8 * jp + 6], acc[8 * jp + 7]));
                }
              }
            }
#pragma unroll
            for (int i = 0; i < 4; ++i) if (XST & (1 << hp)) sub(sn++);
#pragma unroll
            for (int r = 0; r < 2; ++r) {
              sp[r] = rcp(sp[r] + __shfl_xor_sync(0xffffffffu, sp[r], 2)) * (r ? rs1 : rs0);
              sm[r] = rcp(sm[r] + __shfl_xor_sync(0xffffffffu, sm[r], 2)) * (r ? rs1 : rs0);
            }
            if (hp == 0) { mmx(1); mbar_wait(BA(CM + 15), par); }
            else { PROFT(tid_ == 128, layer * 16 + 11); nbar<1, 256>(); }
#pragma unroll
            for (int i = 0; i < 4; ++i) {
              const int r = i & 1, d = 16 * (i >> 1) + 2 * r;
              sts128((pb + r * 1024) ^ ((i >> 1) << 4), make_uint4(pack_bf16(PV(hp, d) * sp[r], PV(hp, d + 1) * sp[r]), pack_bf16(PV(hp, d + 4) * sp[r], PV(hp, d + 5) * sp[r]),
                                                                    pack_bf16(PV(hp, d + 8) * sp[r], PV(hp, d + 9) * sp[r]), pack_bf16(PV(hp, d + 12) * sp[r], PV(hp, d + 13) * sp[r])));
              sts128((pb + r * 1024) ^ ((i >> 1) << 4) ^ 64, make_uint4(pack_bf16(en[d] * sm[r], en[d + 1] * sm[r]), pack_bf16(en[d + 4] * sm[r], en[d + 5] * sm[r]),
                                                                         pack_bf16(en[d + 8] * sm[r], en[d + 9] * sm[r]), pack_bf16(en[d + 12] * sm[r], en[d + 13] * sm[r])));
            }
            fence_async_smem();
            nbar<1, 256>();
            const uint32_t dP = dB0 + (PH >> 4) + wu * 1024;
            const uint32_t dV = (dB0 & 0xFFFFu) + ((VB + hp * SLOT) >> 4) + (((SM_SD - VB - hp * SLOT) >> 4) << 16) + wu * (512u - (512u << 16));
            wgmma_fence();
#pragma unroll
            for (int ks = 0; ks < 8; ++ks) wgmma_n40_tt(kva, D128(dP + ks * 128), desc64(dV + ks * 64, 0x80000020u), ks != 0);
            wgmma_commit();
          }
#pragma unroll
          for (int i = 0; i < 4; ++i) sub(sn++);
          stage(1);
          PROFT(tid_ == 128, layer * 16 + 3);
          rest(sn >> 2, SKA);
          rest_end();
          PROFT(lane == 0 && layer == PL, 200 + cw);
          PROFT(tid_ == 128, layer * 16 + 10);
        }
#define QV(H, i) acc[128 + 16 * (H) + (i)]
        float mx[4][2], mn[4][2];
        uint32_t ph[4][4][4];
        auto mnx = [&](int hp) {
#pragma unroll
          for (int H = 2 * hp; H < 2 * hp + 2; ++H)
#pragma unroll
            for (int r = 0; r < 2; ++r) {
              mx[H][r] = fmaxf(fmaxf(fmaxf(QV(H, 2 * r), QV(H, 2 * r + 1)), fmaxf(QV(H, 4 + 2 * r), QV(H, 5 + 2 * r))),
                               fmaxf(fmaxf(QV(H, 8 + 2 * r), QV(H, 9 + 2 * r)), fmaxf(QV(H, 12 + 2 * r), QV(H, 13 + 2 * r))));
              mn[H][r] = fminf(fminf(fminf(QV(H, 2 * r), QV(H, 2 * r + 1)), fminf(QV(H, 4 + 2 * r), QV(H, 5 + 2 * r))),
                               fminf(fminf(QV(H, 8 + 2 * r), QV(H, 9 + 2 * r)), fminf(QV(H, 12 + 2 * r), QV(H, 13 + 2 * r))));
            }
#pragma unroll
          for (int o = 1; o <= 2; o <<= 1)
#pragma unroll
            for (int H = 2 * hp; H < 2 * hp + 2; ++H)
#pragma unroll
              for (int r = 0; r < 2; ++r) {
                mx[H][r] = fmaxf(mx[H][r], __shfl_xor_sync(0xffffffffu, mx[H][r], o));
                mn[H][r] = fminf(mn[H][r], __shfl_xor_sync(0xffffffffu, mn[H][r], o));
              }
#pragma unroll
          for (int H = 2 * hp; H < 2 * hp + 2; ++H)
#pragma unroll
            for (int r = 0; r < 2; ++r) { mx[H][r] *= -sc[r]; mn[H][r] = fmaf(mn[H][r], sc[r], mx[H][r]); }
        };
        auto fm = [&](int H) {
#pragma unroll
          for (int i = 0; i < 8; ++i) {
            const int r = i & 1;
            const float x0 = fmaf(QV(H, 2 * i), sc[r], mx[H][r]), x1 = fmaf(QV(H, 2 * i + 1), sc[r], mx[H][r]);
            ph[H][i >> 2][i & 3] = pack_bf16(ex2(x0), ex2(x1));
            ph[H][2 + (i >> 2)][i & 3] = pack_bf16(ex2(mn[H][r] - x0), ex2(mn[H][r] - x1));
          }
        };
        mnx(0);
        fm(0); fm(1);
#pragma unroll
        for (int hp = 0; hp < 2; ++hp) {
          if (hp) mbar_wait(BA(FW), par);
          mbar_wait(BA(hp ? B_KVF1 : B_KVF), (layer >> 1) & 1);
          PROFT(tid_ == 128, layer * 16 + (hp ? 4 : 5));
          float oa[4][20];
          wgmma_fence();
#pragma unroll
          for (int s = 0; s < 2; ++s)
#pragma unroll
            for (int v = 0; v < 4; ++v) {
              const int h = v >> 1, s4 = 2 * (v & 1) + s;
              wgmma_n40_rs(oa[v], ph[2 * hp + h][s4], desc64((((SB0 + VB + hp * SLOT) >> 4) | (40u << 16)) + h * 512 + (s4 ^ (2 * h)) * 80, 8), s != 0);
            }
          wgmma_commit();
          if (hp == 0) { mnx(1); wgmma_wait<0>(); }
          else wgmma_wait<0>();
#pragma unroll
          for (int i = 0; i < 20; ++i) asm volatile("" : "+f"(oa[0][i]), "+f"(oa[1][i]), "+f"(oa[2][i]), "+f"(oa[3][i]) :: "memory");
          uint32_t ow[2][2][4];
#pragma unroll
          for (int h = 0; h < 2; ++h)
#pragma unroll
            for (int r = 0; r < 2; ++r) {
              const float a = oa[2 * h + 1][17 + 2 * r], b = oa[2 * h][17 + 2 * r];
              const float id = rcp(fmaf(oa[2 * h][16 + 2 * r], a, fmaf(a, 1e-6f, oa[2 * h + 1][16 + 2 * r]) * b));
              const float fa = a * id, fb = b * id;
#pragma unroll
              for (int j = 0; j < 4; ++j)
                ow[h][r][j] = pack_bf16(fmaf(oa[2 * h][4 * j + 2 * r], fa, oa[2 * h + 1][4 * j + 2 * r] * fb),
                                        fmaf(oa[2 * h][4 * j + 2 * r + 1], fa, oa[2 * h + 1][4 * j + 2 * r + 1] * fb));
            }
#pragma unroll
          for (int i = 0; i < 16; ++i) of[4 * hp + (i >> 2)][i & 3] = ow[i >> 3][i & 1][(i >> 1) & 3];
          if (hp == 0) {
#pragma unroll
            for (int i = 0; i < 4; ++i) stg128(g_o + gfr + (i & 1) * 8 * D_ + (i >> 1) * 32, ow[i >> 1][i & 1][0], ow[i >> 1][i & 1][1], ow[i >> 1][i & 1][2], ow[i >> 1][i & 1][3]);
            __syncwarp();
            if (lane == 0) mbar_arrive(BA(B_OH0));
            PROFT(tid_ == 128 && layer, layer * 16 + 15);
            fm(2); fm(3);
          } else {
#pragma unroll
            for (int i = 0; i < 16; ++i) o1[i >> 2][i & 3] = ow[i >> 3][(i >> 2) & 1][i & 3];
          }
        }
      }
      PROFT(tid_ == 128, layer * 16 + 6);
#pragma unroll
      for (int i = 0; i < 4; ++i) stg128(g_o + gfr + (i & 1) * 8 * D_ + (2 + (i >> 1)) * 32, o1[i][0], o1[i][1], o1[i][2], o1[i][3]);
      __syncwarp();
      if (lane == 0) { mbar_arrive(BA(B_OH1)); if (EF_USED) REL2(B_EF); }
      PROFT(lane == 0 && layer == PL, 208 + cw);
      wo0();
    }
    {
      PHASE_CTX();
      MMA_CTX();
      mbar_wait(BA(FW + 1), par);
      wgmma_fence();
#pragma unroll
      for (int k = 0; k < 4; ++k) wgmma_n128_rs(acc, of[4 + k], D128(dB0 + (uint32_t)((WO_B >> 4) & 15) * 1024 + k * 128), 1);
      wgmma_commit();
      wgmma_wait<1>();
      if (elected) REL2(CW);
      uint64_t ta = WO_A >> 8, tw = WO_B >> 8;
      auto run = [&](int i0, int i1) {
#pragma unroll 1
        for (int i = i0; i < i1; ++i) {
          mbar_wait(BA(FW + i), par);
          PROFL(tid_ == 128 && layer == PL, 160 + i);
          const uint32_t da = dA0 + ((uint32_t)ta & 15) * 1024, db = dB0 + ((uint32_t)tw & 15) * 1024;
          ta >>= 4; tw >>= 4;
          wgmma_fence();
#pragma unroll
          for (int k = 0; k < 4; ++k) wgmma_n128(acc, D128(da + k * 2), D128(db + k * 128), 1);
          wgmma_commit();
          wgmma_wait<1>();
          if (elected) REL2(CW + i - 1);
        }
        ta = WO_A >> (4 * (i1 & 15)); tw = WO_B >> (4 * (i1 & 15));
      };
      run(2, XRAT);
#pragma unroll
      for (int j = 0; j < 8 / XRN; ++j) {
#pragma unroll
        for (int i = j * XRN; i < (j + 1) * XRN; ++i) ldg128((layer ? g_x : c.x0) + gfr + (i & 1) * 8 * D_ + (i >> 1) * 32, xp[i][0], xp[i][1], xp[i][2], xp[i][3]);
        run(XRAT + j, j + 1 < 8 / XRN ? XRAT + j + 1 : 16);
      }
      if (layer == 0) {
#pragma unroll
        for (int o = 1; o <= 2; o <<= 1)
#pragma unroll
          for (int i = 0; i < 16; ++i) {
            const int j = o == 1 ? 2 * (i & 1) : (i & 1);
            uint32_t &a = xp[i >> 1][j], &b = xp[i >> 1][j + o];
            const uint32_t r = __shfl_xor_sync(0xffffffffu, (t & o) ? a : b, o);
            if (t & o) a = r; else b = r;
          }
      }
      if (layer != NLAYERS - 1) mbar_wait(BA(FM), par ^ 1);
      wgmma_wait<0>();
#pragma unroll
      for (int i = 128; i < 192; ++i) asm volatile("" : "+f"(acc[i]) :: "memory");
      if (elected) REL2(CW + 15);
      PROFT(lane == 0 && layer == PL, 216 + cw);
      PROFT(tid_ == 128, layer * 16 + 7);
#pragma unroll
      for (int i = 0; i < 32; ++i)
        xp[i >> 2][i & 3] = add_bf16x2(xp[i >> 2][i & 3], pack_bf16(acc[128 + 16 * (i >> 3) + 4 * (i & 3) + 2 * ((i >> 2) & 1)], acc[129 + 16 * (i >> 3) + 4 * (i & 3) + 2 * ((i >> 2) & 1)]));
      if (layer == NLAYERS - 1) {
#pragma unroll
        for (int i = 0; i < 8; ++i) stsm_x4(sb + (XS + (i >> 2)) * SLOT + (Y ^ ((i & 2) << 5)) + (i & 1) * 1024, xp[i][0], xp[i][1], xp[i][2], xp[i][3]);
        __syncwarp();
        slab_out_half(sb + XS * SLOT, c.out + (size_t)m0 * D_ + g * 128, wrow0, lane);
        slab_out_half(sb + (XS + 1) * SLOT, c.out + (size_t)m0 * D_ + g * 128 + 64, wrow0, lane);
        PROFT(tid_ == 128, layer * 16 + 24);
        break;
      }
#pragma unroll
      for (int i = 0; i < 4; ++i) stg128(g_x + gfr + (i & 1) * 8 * D_ + (i >> 1) * 32, xp[i][0], xp[i][1], xp[i][2], xp[i][3]);
      __syncwarp();
      if (lane == 0) mbar_arrive(BA(B_XH0));
#pragma unroll
      for (int i = 0; i < 16; ++i) xf[i >> 2][i & 3] = xp[2 * (i >> 3) + (i & 1)][(i >> 1) & 3];
      PROFT(tid_ == 128, layer * 16 + 24);
    }
  }
}

__device__ __forceinline__ uint64_t k_order(int o) {
  const uint32_t lo = (1u << (4 * o)) - 1u, h0 = (0xECA86420u & lo) | ((0xECA86420u >> 4) & ~lo);
  return (uint64_t)(2 * o) | ((uint64_t)(2 * o + 1) << 4) | ((uint64_t)(h0 & 0xFFFFFFFu) << 8) | ((uint64_t)((h0 & 0xFFFFFFFu) | 0x1111111u) << 36);
}

__global__ void __cluster_dims__(2, 1, 1) __launch_bounds__(384, 1)
mega_kernel(const __grid_constant__ Maps maps, const __grid_constant__ Ctx c, const bf16* __restrict__ wA, const bf16* __restrict__ wB,
            const bf16* __restrict__ woA, const bf16* __restrict__ woB) {
  if (blockIdx.x - c.boff >= 128u) {
    const unsigned int epoch = ld_relaxed(&g_epoch);
    const int e = (blockIdx.x - c.boff) & 3, tid = threadIdx.x;
    float s[8] = {0.f, 0.f, 0.f, 0.f, 0.f, 0.f, 0.f, 0.f};
    const uint32_t sb = smem_u32(smem_raw), bar = sb + SM_BAR;
    auto issue = [&](int i) {
      mbar_expect_tx(BA(i & 3), 49152);
      bulk_load(sb + (i & 3) * 49152, wB + (size_t)e * 256 * 3072 + i * 24576, 49152, BA(i & 3));
    };
    if (tid == 0) {
      if (SVD) __nanosleep(SVD);
#pragma unroll 1
      for (int i = 0; i < 4; ++i) {
        mbar_init(BA(i), 1);
        fence_async_smem();
        issue(i);
      }
    }
    __syncthreads();
#pragma unroll 1
    for (int i = 0; i < 32; ++i) {
      mbar_wait(BA(i & 3), (i >> 2) & 1);
#pragma unroll 2
      for (int r = 0; r < 8; ++r) {
        const uint4 v = lds128(sb + (i & 3) * 49152 + r * 6144 + tid * 16);
        s[0] += bf_lo(v.x); s[1] += bf_hi(v.x); s[2] += bf_lo(v.y); s[3] += bf_hi(v.y);
        s[4] += bf_lo(v.z); s[5] += bf_hi(v.z); s[6] += bf_lo(v.w); s[7] += bf_hi(v.w);
      }
      __syncthreads();
      if (tid == 0 && i < 28) issue(i + 4);
    }
    float* cd = g_cs + (epoch & 1) * 6144 + 3072 + ((tid >> 4) & 7) * 384 + (tid < 128 ? 256 : (tid >> 7) * 128 - 128) + (tid & 15) * 8;
    red_add4(cd, s[0], s[1], s[2], s[3]);
    red_add4(cd + 4, s[4], s[5], s[6], s[7]);
    __syncthreads();
    if (tid == 0) flag_add(&g_csflag[8].v);
    const int op = (epoch & 1) ^ 1;
    float4* kz = reinterpret_cast<float4*>(g_kv + (size_t)op * (2 * 8 * 10240)) + e * 5120;
#pragma unroll 1
    for (int i = tid; i < 5120; i += 384) kz[i] = make_float4(0.f, 0.f, 0.f, 0.f);
    reinterpret_cast<float4*>(g_cs + op * 6144)[e * 384 + tid] = make_float4(0.f, 0.f, 0.f, 0.f);
#pragma unroll 1
    for (int i = tid; i < 1024; i += 384) reinterpret_cast<float4*>(g_stats + (op * 4 + e) * S_)[i] = make_float4(0.f, 0.f, 0.f, 0.f);
    return;
  }
  const int warp = __shfl_sync(0xffffffffu, threadIdx.x >> 5, 0), lane = threadIdx.x & 31;
  if (smem_u32(smem_raw) != SB0 + ((blockIdx.x & 1) << 24)) __trap();
  {
  const int cid = (blockIdx.x - c.boff) >> 1, u7 = ((cid - 36) * 37) >> 8, cr = blockIdx.x & 1;
  const int g = cid < 4 ? 4 + cid : cid < 36 ? (cid - 4) >> 3 : 4 + u7, rb = (cid < 4 ? 0 : cid < 36 ? (cid - 4) & 7 : cid - 35 - 7 * u7) * 2 + cr, m0 = rb * 128;
  const uint32_t sb = SB0 + (cr << 24), bar = sb + SM_BAR;
  PROFT(lane == 0 && (warp == 0 || warp == 4), 224 + (warp >> 2) * 8);
  uint32_t cx = 0;
  if (warp == 2) {
    if (lane < NMAP) asm volatile("prefetch.tensormap [%0];" ::"l"(&maps.m[lane]) : "memory");
    if (lane == 31) asm volatile("prefetch.global.L2 [%0];" ::"l"(&g_epoch));
  } else if (warp == 3) {
    cx = c_map[cid] + c_wop[lane] + c_wop[NWOP - lane] + c_aop[lane] + c_aop[NAOP - lane] + (uint32_t)(uintptr_t)g_x;
  } else if (warp >= 4 && warp < 8) {
    const int i = threadIdx.x - 128;
    asm volatile("prefetch.global.L2 [%0];" ::"l"(wA + (size_t)((rb & ~1) * 64 + cr * 32 + ((i >> 1) & 31)) * 3072 + (i >> 6) * 1024 + g * 128 + (i & 1) * 64));
  }
  if (warp < 2) {
    const int s = warp, kb = (rb & ~1) + s;
    if (lane == 0) {
      mbar_init(BA(FM + s), 1u);
      mbar_init(BA(B_RAW + warp), 1u);
      mbar_init(BA(warp ? B_X0 : B_KVS0), 1u);
      asm volatile("fence.mbarrier_init.release.cluster;" ::: "memory");
    }
    __syncwarp();
    if (warp == 0) tma_2d_e(sb + SM_SD, &maps.m[MAP_PHI], 0, g * 128, BA(B_RAW));
    else if (W1DL) __nanosleep(W1DL);
#pragma unroll
    for (int j = 0; j < 6; ++j)
      tma_5d_e(sb + (j < 2 ? 2 * s : j < 4 ? 9 + s : 2 * s + 1) * SLOT + (j & 1) * 8192, &maps.m[MAP_WA], (j < 2 ? 1024 : j < 4 ? 0 : 2048) + g * 128 + (j & 1) * 64, 2 * kb,
               BA(j < 4 ? B_RAW + warp : FM + s));
    tma_2d_e(sb + (XS + s) * SLOT, &maps.m[MAP_X0], kb * 64, m0, BA(FM + s));
    expect_tx_e(BA(B_RAW + warp), warp ? 32768 : 32768 + 8192);
    expect_tx_e(BA(FM + s), 32768);
    if (X0AT == 0 && warp == 1) {
      tma_2d_e(sb + 11 * SLOT, &maps.m[MAP_X0], g * 128, m0, BA(B_X0));
      tma_2d_e(sb + 12 * SLOT, &maps.m[MAP_X0], g * 128 + 64, m0, BA(B_X0));
      expect_tx_e(BA(B_X0), 32768);
    }
  } else if (warp >= 4 && lane == 0) {
#pragma unroll 1
    for (int i = 2 + (warp - 4) * 13; i < 15 + (warp - 4) * 13; ++i)
      mbar_init(BA(i), 1u << ((i < CM ? 0u : i < B_EF ? 2u : (uint32_t)(BAR_LG >> (4 * ((i - B_EF) & 15)))) & 7u));
    asm volatile("fence.mbarrier_init.release.cluster;" ::: "memory");
  }
  __syncwarp();
  asm volatile("barrier.cluster.arrive.relaxed.aligned;" ::: "memory");
  if (threadIdx.x == 96 + c.zero) sts_f(sb + SM_EPOCH + 4, __uint_as_float(cx));
  PROFT(lane == 0 && (warp == 0 || warp == 4), 225 + (warp >> 2) * 8);
  __syncwarp();
  PROFT(lane == 0 && (warp == 0 || warp == 4), 226 + (warp >> 2) * 8);
  }

  if (warp < 4) {
    asm volatile("setmaxnreg.dec.sync.aligned.u32 40;");
    PROFT(threadIdx.x == 0, 227);
    cluster_wait();
    PROFT(threadIdx.x == 0, 228);
    if (warp == 0 || warp == 3) {
    if (warp == 0) {
      BLK_CTX();
      const unsigned int epoch = __shfl_sync(0xffffffffu, ld_relaxed(&g_epoch), 0), xbase = epoch * NLAYERS;
      (void)xbase;
      const uint64_t ordg = k_order(g);
      if (X0AT) {
        mbar_wait_u(BA(B_RAW + X0AT - 1), 0);
        tma_2d_e(sb + 11 * SLOT, &maps.m[MAP_X0], g * 128, m0, BA(B_X0));
        tma_2d_e(sb + 12 * SLOT, &maps.m[MAP_X0], g * 128 + 64, m0, BA(B_X0));
        expect_tx_e(BA(B_X0), 32768);
      }
#pragma unroll 1
      for (int lp = 0; lp < 2 * NLAYERS; ++lp) {
        const int layer = lp >> 1, n1 = (lp & 1) ? NAOP : NAOP - 14;
        int n = (lp & 1) ? NAOP - 14 : 0;
        const uint64_t ord = lp ? ordg : k_order(rb >> 1);
        uint32_t ready = lp ? 0u : 0xFFFFu, nop = c_aop[n];
        const unsigned int* fl = ((lp & 1) ? g_of : g_xf) + rb * 32;
        const CUtensorMap* tm = &maps.m[(lp & 1) ? MAP_O : lp ? MAP_X : MAP_X0];
        const uint32_t skip = layer ? 1u << 25 : 9u << 22;
        if (lp) mbar_wait_u(BA((lp & 1) ? B_OH0 : B_XH0), ((lp - 1) >> 1) & 1);
#pragma unroll 1
        for (; n < n1; ++n) {
          const uint32_t op = nop;
          nop = c_aop[n + 1];
          const uint32_t kb = (uint32_t)(ord >> ((op >> 2) & 60)) & 15;
          uint32_t dst = sb + (op & 15) * SLOT, kc = kb * 64, fb = bar + ((op >> 5) & 0x3F8), need = ~ready & (1u << kb);
          asm volatile("" : "+r"(dst), "+r"(kc), "+r"(fb), "+r"(need));
          const uint32_t eb = bar + ((op >> 12) & 0x3F8), ep = (layer ^ (op >> 22)) & 1;
          bool fr = op & skip;
          if (need) {
            if (!fr) fr = __all_sync(0xffffffffu, mbar_test_wait(eb, ep));
            PROFT(lane == 0 && (n == 0 || n == NAOP - 14), 64 + layer * 16 + (n ? 2 : 0));
            src_wait<0>(fl, xbase + layer + 1, need, ready, lane);
            fence_async_all();
          }
          if (!fr) mbar_wait_u(eb, ep);
          tma_2d_e(dst, tm, kc, m0, fb);
          PROFT(lane == 0 && (n == 0 || n == NAOP - 14), 64 + layer * 16 + (n ? 3 : 1));
          PROFL(lane == 0 && layer == PL && n >= NAOP - 14, 178 + n - (NAOP - 14));
          PROFL(lane == 0 && layer == PL + 1 && n < 4, 242 + n);
        }
      }
    } else {
      BLK_CTX();
      const unsigned int epoch = __shfl_sync(0xffffffffu, ld_relaxed(&g_epoch), 0), xbase = epoch * NLAYERS;
      (void)xbase;
      const uint64_t ordg = k_order(g);
#pragma unroll 1
      for (int layer = 0; layer < NLAYERS; ++layer) {
        const uint64_t ordq = layer ? ordg : k_order(rb >> 1);
        uint32_t ready = layer ? 0xFFFFu : 0u, nop = c_wop[0];
        const CUtensorMap* tq = &maps.m[(layer & 1) ? MAP_WB : MAP_WF];
        const CUtensorMap* tk = &maps.m[(layer & 1) ? MAP_WB : cr ? MAP_WA : MAP_WF];
        const uint32_t skip = layer ? 1u << 25 : 9u << 22, pm = layer ? 0xE0u : 0u;
        int n = 0;
#pragma unroll 1
        for (; n < NWOP - 16; ++n) {
          const uint32_t op = nop;
          nop = c_wop[n + 1];
          const uint32_t isq = (op >> 23) & 1, fb = bar + ((op >> 5) & 0x3F8);
          const uint32_t kb = (uint32_t)(ordq >> ((op >> 2) & 60)) & 15;
          const CUtensorMap* tm = (isq ? tq : tk) + ((op & pm) ? 1 : 0);
          const uint32_t dst = sb + (op & 15) * SLOT + cr * (isq ? 8192 : SLOT);
          const int col = g * 128 + (isq ? cr * 64 : 1024 + cr * 1024);
          if (layer == 0) {
            if ((op & 0x7E00) == 0) continue;
            const uint32_t need = ((isq || !cr) ? 1u << kb : 0u) | (((op >> 22) & 1) ? 0u : (((op >> 15) & 127) == CM ? 1u : 3u) << (rb & ~1));
            if ((ready & need) != need) {
              src_wait<0>(g_wff + g * 32, epoch + 1, need, ready, lane);
              fence_async_all();
            }
            if ((op & 15) >= 11) mbar_wait_u(BA(B_XT), 0);
          }
          wait_tma_5d_mc(!(op & skip), bar + ((op >> 12) & 0x3F8), (layer ^ (op >> 22)) & 1, dst, tm, col, 2 * kb, fb);
          if (!isq) tma_5d_mc_e(dst + 8192, tm, col + 64, 2 * kb, fb);
          if (op >> 26) expect_tx_e(fb, (op >> 26) * 8192);
          PROFL(lane == 0 && layer == PL + 1 && n < 16, 128 + n);
        }
        const CUtensorMap* to = &maps.m[(layer & 1) ? MAP_WOB : MAP_WOA];
#pragma unroll 1
        for (; n < NWOP; ++n) {
          const uint32_t op = nop;
          nop = c_wop[n + 1];
          const uint32_t fb = bar + ((op >> 5) & 0x3F8), kb = (uint32_t)(ordg >> ((op >> 2) & 60)) & 15;
          if (WH < 16 && n == NWOP - 16 + WH && !(layer & 1)) mbar_wait_u(BA(B_KVS), (layer >> 1) & 1);
          wait_tma_5d_mc(!((op >> 25) & 1), bar + ((op >> 12) & 0x3F8), layer & 1, sb + (op & 15) * SLOT + cr * 8192, to + ((op & 0xE0) ? 1 : 0), g * 128 + cr * 64, 2 * kb, fb);
          expect_tx_e(fb, (op >> 26) * 8192);
          PROFL(lane == 0 && layer == PL, 144 + ((op >> 8) & 127) - FW);
        }
      }
    }
    } else if (warp == 1) {
      BLK_CTX();
      const unsigned int epoch = __shfl_sync(0xffffffffu, ld_relaxed(&g_epoch), 0), xbase = epoch * NLAYERS;
      (void)xbase;
      if (lane == 0) {
        mbar_wait_s(BA(B_WFD), 0);
        PROFT(true, 229);
#pragma unroll 1
        for (int j = 0; j < 4; ++j) tma_store_5d(&maps.m[MAP_WF], sb + (j < 2 ? 2 * cr : 9 + cr) * SLOT + (j & 1) * 8192, (j < 2 ? 1024 : 0) + g * 128 + (j & 1) * 64, 2 * rb);
        bulk_commit();
        bulk_wait0();
        PROFT(true, 230);
        fence_async_all();
        flag_set(g_wff + g * 32 + rb, epoch + 1);
        PROFT(true, 64 + 13);
#pragma unroll 1
        for (int e = 0; e < NLAYERS; ++e) {
          BLK_CTX();
          if (e > 0) {
            mbar_wait_s(BA(B_XH0), (e - 1) & 1);
            PROFT(e == PL + 1, 240);
            flag_set(g_xf + rb * 32 + 2 * g, xbase + e + 1);
            PROFT(e == PL + 1, 241);
          }
          mbar_wait_s(BA(B_XDONE), e & 1);
          PROFT(true, 64 + e * 16 + 4);
          flag_set(g_xf + rb * 32 + 2 * g + 1, xbase + e + 1);
          if (e == 0) {
            flag_add(&g_csflag[g].v);
#pragma unroll 1
            for (int i = 0; i < 4; ++i) {
              mbar_wait_s(BA(CM + PFM + PFS * i), 0);
              l2_prefetch(i < 3 ? wB + (size_t)(i * 128 + bid_) * 8192 : woA + (size_t)bid_ * 8192, 16384);
            }
          }
          if (PFM && e == 1) l2_prefetch(woB + (size_t)bid_ * 8192, 16384);
          PROFT(true, 64 + e * 16 + 7);
          if ((e & 1) == 0) {
            bf16* kvl = g_kv + ((size_t)((epoch & 1) * 2 + (e >> 1)) * 8 + g) * 10240;
#pragma unroll 1
            for (int hp = 0; hp < 2; ++hp) {
              mbar_wait_s(BA(B_KVDONE), hp);
#pragma unroll 1
              for (int i = 0; i < 4; ++i) {
                const int ch = (i + (rb >> 2)) & 3;
                bulk_red_add(kvl + hp * 5120 + ch * 1280, sb + VB + hp * SLOT + (ch >> 1) * 8192 + (ch & 1) * 2560, 2560);
                bulk_commit();
                asm volatile("cp.async.bulk.wait_group %0;" :: "n"(CHW) : "memory");
              }
              bulk_wait0();
              PROFT(true, 64 + e * 16 + (hp ? 10 : 6));
              fence_async_all();
              flag_add(&g_kvflag[hp * 8 + g].v);
              mbar_arrive(BA(hp ? B_KVS : B_KVS0));
              PROFT(e > 0 && hp, 64 + e * 16 + 8);
            }
          }
          if (e & 1) {
            mbar_wait_s(BA(B_OF0), (e >> 1) & 1);
            flag_set(g_hf + rb * 32 + g, xbase + e + 1);
            if (rb) flag_wait(g_hf + (rb - 1) * 32 + g, xbase + e + 1);
            fence_async_all();
            mbar_expect_tx(BA(B_HALO), 8192);
            bulk_load(sb + SM_SD, g_halo + (size_t)(((e >> 1) * 17 + rb) * 8 + g) * 2048, 8192, BA(B_HALO));
            PROFT(true, 64 + e * 16 + 15);
          }
          mbar_wait_s(BA(B_OH0), e & 1);
          PROFT(e > 0, 64 + e * 16 + 13);
          flag_set(g_of + rb * 32 + 2 * g, xbase + e + 1);
          PROFT(true, 64 + e * 16 + 9);
          mbar_wait_s(BA(B_OH1), e & 1);
          PROFT(true, 64 + e * 16 + 5);
          flag_set(g_of + rb * 32 + 2 * g + 1, xbase + e + 1);
          PROFT(true, 64 + e * 16 + 11);
        }
        if (bid_ == 0) g_epoch = epoch + 1;
      }
    } else {
      BLK_CTX();
      const unsigned int epoch = __shfl_sync(0xffffffffu, ld_relaxed(&g_epoch), 0), xbase = epoch * NLAYERS;
      (void)xbase;
      if (lane < 16) sts_f(sb + SM_RS + lane * 4, 0.f);
#pragma unroll 1
      for (int layer = 0; layer < NLAYERS; ++layer) {
#define HLP_CTX() BLK_CTX(); int lane = threadIdx.x & 31; asm volatile("" : "+r"(lane)); const bool isB = layer & 1, hal = isB && rb > 0; (void)hal;
#pragma unroll 1
        for (int ph = 0; ph < 2; ++ph) {
          HLP_CTX();
          if (ph == (layer == 0)) {
            const float* cs = g_cs + (epoch & 1) * 6144 + g * 384;
            if (layer) mbar_wait_u(BA(CT), (layer - 1) & 1);
            if (layer < 2) {
              if (lane == 0) flag_wait_slow(&g_csflag[isB ? 8 : g].v, isB ? epoch * 4u + 4u : epoch * 16u + 16u);
              __syncwarp();
            }
#pragma unroll 1
            for (int i0 = 0; i0 < 12; i0 += 4) {
              float a[4];
#pragma unroll
              for (int i = 0; i < 4; ++i) a[i] = __ldcg(cs + isB * 3072 + (i0 + i) * 32 + lane);
#pragma unroll
              for (int i = 0; i < 4; ++i) {
                const float c1 = bf16r(a[i]), c2 = bf16r(a[i] - c1), c3 = (a[i] - c1) - c2;
                sts128(sb + SM_BP + ((i0 + i) * 32 + lane) * 16, make_uint4(pack_bf16(c1, c2), pack_bf16(c3, 0.f), 0u, 0u));
              }
            }
          } else {
            uint32_t rdy = 0u;
            mbar_wait_u(BA(CM + 3), layer & 1);
            src_wait<128>(g_xf + rb * 32, xbase + layer + 1, 0xAAAAu, rdy, lane);
            rdy = 0u;
            if (hal) src_wait<128>(g_xf + (rb - 1) * 32, xbase + layer + 1, 0xAAAAu, rdy, lane);
            const float2* sp = g_stats + ((epoch & 1) * 4 + layer) * S_ + m0 + lane;
            float2 u[5];
#pragma unroll
            for (int i = 0; i < 4; ++i) u[i] = __ldcg(sp + i * 32);
            u[4] = __ldcg(sp - (hal ? 16 : 0));
#pragma unroll 1
            for (int i = 0; i < 5; ++i) {
              const float mean = u[0].x * (1.f / D_);
              const float var = fmaxf(fmaf(-u[0].x, mean, u[0].y) * (1.f / D_), 0.f);
              const float sd = bf16r(sqrtf(bf16r(bf16r(var) + 1e-5f)));
              const int R = i * 32 + lane;
              if (i < 4) {
                const float hm = -0.5f * bf16r(mean);
                if (!isB) sts128(sb + SM_SD + R * 64 + ((R >> 1) & 3) * 16, make_uint4(__float_as_uint(sd) >> 16, __float_as_uint(sd) >> 16, __float_as_uint(sd) >> 16, __float_as_uint(sd) >> 16));
                sts128(sb + SM_AP + R * 16, make_uint4(pack_bf16(hm, hm), pack_bf16(hm, 0.f), 0u, 0u));
              }
              if (i < 4 || (hal && lane < 16)) sts_f(sb + SM_RS + (i < 4 ? 16 + R : lane) * 4, __fdividef(1.f, sd));
#pragma unroll
              for (int j = 0; j < 4; ++j) u[j] = u[j + 1];
            }
            PROFT(lane == 0, 64 + layer * 16 + 12);
          }
        }
        HLP_CTX();
        fence_async_smem();
        __syncwarp();
        if (lane == 0) mbar_arrive(BA(B_STAT));
        PROFT(lane == 0, 64 + layer * 16 + 14);
        if (!isB && lane == 0) {
#pragma unroll 1
          for (int hp = 0; hp < 2; ++hp) {
            mbar_wait_s(BA(hp ? B_KVS : B_KVS0), (layer >> 1) & 1);
            flag_wait(&g_kvflag[hp * 8 + g].v, epoch * (16u * ((NLAYERS + 1) / 2)) + 16u * ((layer >> 1) + 1));
            const bf16* kvl = g_kv + ((size_t)((epoch & 1) * 2 + (layer >> 1)) * 8 + g) * 10240 + hp * 5120;
            const uint32_t kb = BA(hp ? B_KVF1 : B_KVF);
            fence_async_all();
            mbar_expect_tx(kb, 10240);
            bulk_load(sb + VB + hp * SLOT, kvl, 5120, kb);
            bulk_load(sb + VB + hp * SLOT + 8192, kvl + 2560, 5120, kb);
            PROFT(hp == 0, 64 + layer * 16 + 15);
          }
        }
        __syncwarp();
      }
    }
    __syncwarp();
    asm volatile("barrier.cluster.arrive.relaxed.aligned;" ::: "memory");
    cluster_wait();
  } else {
    asm volatile("setmaxnreg.inc.sync.aligned.u32 232;");
    PROFT(threadIdx.x == 128, 235);
    cluster_wait();
    PROFT(threadIdx.x == 128, 236);
    consumer(c);
    asm volatile("bar.warp.sync 0xffffffff;\nbarrier.cluster.arrive.relaxed.aligned;\nbarrier.cluster.wait.aligned;\n" ::: "memory");
  }
}

typedef CUresult (*PFN_encodeTiled)(CUtensorMap*, CUtensorMapDataType, cuuint32_t, void*, const cuuint64_t*, const cuuint64_t*,
                                    const cuuint32_t*, const cuuint32_t*, CUtensorMapInterleave, CUtensorMapSwizzle,
                                    CUtensorMapL2promotion, CUtensorMapFloatOOBfill);

static void make_map2(PFN_encodeTiled enc, CUtensorMap* m, const void* ptr, uint64_t cols, uint64_t rows, uint32_t box_c, uint32_t box_r) {
  cuuint64_t dims[2] = {cols, rows};
  cuuint64_t strides[1] = {cols * 2};
  cuuint32_t box[2] = {box_c, box_r};
  cuuint32_t es[2] = {1, 1};
  CUresult r = enc(m, CU_TENSOR_MAP_DATA_TYPE_BFLOAT16, 2, const_cast<void*>(ptr), dims, strides, box, es, CU_TENSOR_MAP_INTERLEAVE_NONE,
                   box_c == 64 ? CU_TENSOR_MAP_SWIZZLE_128B : CU_TENSOR_MAP_SWIZZLE_64B, CU_TENSOR_MAP_L2_PROMOTION_L2_256B, CU_TENSOR_MAP_FLOAT_OOB_FILL_NONE);
  (void)r;
}
static void make_map5(PFN_encodeTiled enc, CUtensorMap* m, const void* ptr, uint64_t cols) {
  for (int p = 0; p < 2; ++p) {
    cuuint64_t dims[5] = {cols, 2, 4, 4, 32};
    cuuint64_t strides[4] = {cols * 2, cols * (p ? 16 : 4), cols * (p ? 4 : 16), cols * 64};
    cuuint32_t box[5] = {64, 2, 4, 4, 2};
    cuuint32_t es[5] = {1, 1, 1, 1, 1};
    CUresult r = enc(m + p, CU_TENSOR_MAP_DATA_TYPE_BFLOAT16, 5, const_cast<void*>(ptr), dims, strides, box, es, CU_TENSOR_MAP_INTERLEAVE_NONE,
                     CU_TENSOR_MAP_SWIZZLE_128B, CU_TENSOR_MAP_L2_PROMOTION_L2_256B, CU_TENSOR_MAP_FLOAT_OOB_FILL_NONE);
    (void)r;
  }
}

extern "C" void kernel_launch(void* const* d_in, const int* in_sizes, int n_in, void* d_out, int out_size) {
  const bf16* A_x = (const bf16*)d_in[0];
  const bf16* A_wqkv = (const bf16*)d_in[1];
  const bf16* A_wphi = (const bf16*)d_in[2];
  const bf16* A_wo = (const bf16*)d_in[3];
  const bf16* B_wqkv = (const bf16*)d_in[5];
  const bf16* B_wo = (const bf16*)d_in[6];
  bf16* out = (bf16*)d_out;

  static PFN_encodeTiled enc = nullptr;
  static bf16 *p_x, *p_o, *p_wf;
  static uint32_t boff;
  if (!enc) {
    void* fn = nullptr; cudaDriverEntryPointQueryResult qr;
    cudaGetDriverEntryPoint("cuTensorMapEncodeTiled", &fn, cudaEnableDefault, &qr);
    enc = (PFN_encodeTiled)fn;
    cudaGetSymbolAddress((void**)&p_x, g_x);
    cudaGetSymbolAddress((void**)&p_o, g_o);
    cudaGetSymbolAddress((void**)&p_wf, g_wf);
    cudaFuncSetAttribute(mega_kernel, cudaFuncAttributeMaxDynamicSharedMemorySize, SM_TOTAL);
    cudaLaunchConfig_t cfg = {};
    cudaLaunchAttribute at; at.id = cudaLaunchAttributeClusterDimension; at.val.clusterDim.x = 2; at.val.clusterDim.y = 1; at.val.clusterDim.z = 1;
    cfg.gridDim = dim3(132); cfg.blockDim = dim3(384); cfg.dynamicSmemBytes = SM_TOTAL; cfg.attrs = &at; cfg.numAttrs = 1;
    int nc = 0;
    if (cudaOccupancyMaxActiveClusters(&nc, mega_kernel, &cfg) != cudaSuccess) { nc = 0; (void)cudaGetLastError(); }
    boff = nc >= 66 ? 0u : 4u;
  }
  Maps maps;
  make_map5(enc, &maps.m[MAP_WF], p_wf, 2048);
  make_map5(enc, &maps.m[MAP_WA], A_wqkv, 3072);
  make_map5(enc, &maps.m[MAP_WB], B_wqkv, 3072);
  make_map5(enc, &maps.m[MAP_WOA], A_wo, 1024);
  make_map5(enc, &maps.m[MAP_WOB], B_wo, 1024);
  make_map2(enc, &maps.m[MAP_X0], A_x, 1024, 2048, 64, 128);
  make_map2(enc, &maps.m[MAP_X], p_x, 1024, 2048, 64, 128);
  make_map2(enc, &maps.m[MAP_O], p_o, 1024, 2048, 64, 128);
  make_map2(enc, &maps.m[MAP_PHI], A_wphi, 32, 1024, 32, 128);
  Ctx c; c.zero = 0u; c.boff = boff; c.x0 = A_x; c.out = out;
  mega_kernel<<<132, 384, SM_TOTAL, cudaStreamPerThread>>>(maps, c, A_wqkv, B_wqkv, A_wo, B_wo);
}
```

```cpp
#include <cuda_runtime.h>
#include <cuda_bf16.h>
#include <cuda.h>
#include <stdint.h>

typedef __nv_bfloat16 bf16;

constexpr int S_ = 2048, D_ = 1024;

struct __align__(128) Flag { unsigned int v; unsigned int pad[31]; };
__device__ __align__(1024) bf16 g_x[S_ * D_];
__device__ __align__(1024) bf16 g_o[S_ * D_];
__device__ __align__(1024) uint32_t g_halo[2 * 17 * 8 * 2048];
__device__ __align__(1024) bf16 g_kv[2 * 2 * 8 * 10240];
__device__ __align__(1024) float2 g_stats[2 * 4 * S_];
__device__ __align__(1024) float g_cs[2 * 2 * 3072];
__device__ __align__(1024) bf16 g_wf[D_ * 2048];
__device__ Flag g_kvflag[16], g_csflag[9];
__device__ __align__(128) unsigned int g_xf[16 * 32], g_of[16 * 32];
__device__ __align__(128) unsigned int g_hf[16 * 32];
__device__ __align__(128) unsigned int g_wff[8 * 32];
__device__ unsigned int g_epoch, g_err;
#define PROFT(cond, idx) asm volatile("" ::: "memory")

#define SUSP 20000
__device__ __forceinline__ uint32_t smem_u32(const void* p) { return (uint32_t)__cvta_generic_to_shared(p); }
__device__ __forceinline__ void mbar_init(uint32_t bar, uint32_t count) {
  asm volatile("mbarrier.init.shared::cta.b64 [%0], %1;" ::"r"(bar), "r"(count) : "memory");
}
__device__ __forceinline__ void mbar_expect_tx(uint32_t bar, uint32_t bytes) {
  asm volatile("mbarrier.arrive.expect_tx.shared::cta.b64 _, [%0], %1;" ::"r"(bar), "r"(bytes) : "memory");
}
__device__ __forceinline__ void mbar_arrive(uint32_t bar) {
  asm volatile("mbarrier.arrive.shared::cta.b64 _, [%0];" ::"r"(bar) : "memory");
}
__device__ __forceinline__ bool mbar_try_wait(uint32_t bar, uint32_t parity) {
  uint32_t ok;
  asm volatile("{\n.reg .pred p;\nmbarrier.try_wait.parity.shared::cta.b64 p, [%1], %2;\nselp.b32 %0, 1, 0, p;\n}\n"
               : "=r"(ok) : "r"(bar), "r"(parity) : "memory");
  return ok != 0;
}
__device__ __forceinline__ bool mbar_try_wait_s(uint32_t bar, uint32_t parity) {
  uint32_t ok;
  asm volatile("{\n.reg .pred p;\nmbarrier.try_wait.parity.shared::cta.b64 p, [%1], %2, %3;\nselp.b32 %0, 1, 0, p;\n}\n"
               : "=r"(ok) : "r"(bar), "r"(parity), "r"(SUSP) : "memory");
  return ok != 0;
}
__device__ __forceinline__ void mbar_wait_s(uint32_t bar, uint32_t parity) {
  uint32_t n = 0;
  bool ok;
#pragma unroll 1
  do { ++n; ok = mbar_try_wait_s(bar, parity); } while (!ok && n < (1u << 16));
}
__device__ __forceinline__ bool mbar_test_wait(uint32_t bar, uint32_t parity) {
  uint32_t ok;
  asm volatile("{\n.reg .pred p;\nmbarrier.test_wait.parity.shared::cta.b64 p, [%1], %2;\nselp.b32 %0, 1, 0, p;\n}\n"
               : "=r"(ok) : "r"(bar), "r"(parity) : "memory");
  return ok != 0;
}
__device__ __forceinline__ uint64_t gtimer() {
  uint64_t t; asm volatile("mov.u64 %0, %globaltimer;" : "=l"(t)); return t;
}
__device__ __forceinline__ void mbar_wait(uint32_t bar, uint32_t parity) {
  uint32_t n = 0;
  bool ok;
#pragma unroll 1
  do { ++n; ok = mbar_try_wait(bar, parity); } while (!ok && n < (1u << 22));
}
__device__ __forceinline__ unsigned int ld_acquire(const unsigned int* p) {
  unsigned int v; asm volatile("ld.acquire.gpu.global.u32 %0, [%1];" : "=r"(v) : "l"(p) : "memory"); return v;
}
__device__ __forceinline__ void flag_add(unsigned int* p) {
  asm volatile("red.release.gpu.global.add.u32 [%0], 1;" ::"l"(p) : "memory");
}
__device__ __forceinline__ void flag_set(unsigned int* p, unsigned int v) {
  asm volatile("st.release.gpu.global.u32 [%0], %1;" ::"l"(p), "r"(v) : "memory");
}
template <int SLEEP>
__device__ __forceinline__ void src_wait(const unsigned int* f, unsigned int target, uint32_t need, uint32_t& ready, int lane) {
  uint32_t n = 0;
#pragma unroll 1
  while ((ready & need) != need) {
    const unsigned int v = ld_acquire(f + (lane & 15));
    ready = __ballot_sync(0xffffffffu, (int)(v - target) >= 0);
    if (SLEEP) { if ((ready & need) != need) __nanosleep(SLEEP); }
    if (++n > (1u << 20)) break;
  }
  __syncwarp();
}
__device__ __forceinline__ unsigned int ld_relaxed(const unsigned int* p);
__device__ __forceinline__ unsigned int ld_relaxed(const unsigned int* p) {
  unsigned int v; asm volatile("ld.relaxed.gpu.global.u32 %0, [%1];" : "=r"(v) : "l"(p) : "memory"); return v;
}
template <int SLEEP>
__device__ __forceinline__ void flag_wait_t(const unsigned int* p, unsigned int target) {
  uint32_t n = 0;
#pragma unroll 1
  while ((int)(ld_acquire(p) - target) < 0) {
    if (SLEEP) __nanosleep(SLEEP);
    if (++n > (1u << 20)) break;
  }
}
__device__ __forceinline__ void flag_wait(const unsigned int* p, unsigned int target) { flag_wait_t<0>(p, target); }
__device__ __forceinline__ void flag_wait_slow(const unsigned int* p, unsigned int target) { flag_wait_t<256>(p, target); }
__device__ __forceinline__ void mbar_wait_u(uint32_t bar, uint32_t parity) {
  uint32_t n = 0;
#pragma unroll 1
  while (!__all_sync(0xffffffffu, SUSP ? mbar_try_wait_s(bar, parity) : mbar_try_wait(bar, parity))) {
    if (++n > (SUSP ? 1u << 16 : 1u << 22)) break;
  }
}
__device__ __forceinline__ void expect_tx_e(uint32_t bar, uint32_t bytes) {
  asm volatile("{\n.reg .pred p;\nelect.sync _|p, 0xffffffff;\n@p mbarrier.arrive.expect_tx.shared::cta.b64 _, [%0], %1;\n}\n" ::"r"(bar), "r"(bytes) : "memory");
}
__device__ __forceinline__ void tma_2d_e(uint32_t dst, const CUtensorMap* tm, int c0, int c1, uint32_t bar) {
  asm volatile("{\n.reg .pred p;\nelect.sync _|p, 0xffffffff;\n"
               "@p cp.async.bulk.tensor.2d.shared::cluster.global.mbarrier::complete_tx::bytes [%0], [%1, {%2, %3}], [%4];\n}\n"
               ::"r"(dst), "l"(tm), "r"(c0), "r"(c1), "r"(bar) : "memory");
}
__device__ __forceinline__ void tma_5d_e(uint32_t dst, const CUtensorMap* tm, int c0, int c4, uint32_t bar) {
  asm volatile("{\n.reg .pred p;\nelect.sync _|p, 0xffffffff;\n"
               "@p cp.async.bulk.tensor.5d.shared::cluster.global.mbarrier::complete_tx::bytes [%0], [%1, {%2, %5, %5, %5, %3}], [%4];\n}\n"
               ::"r"(dst), "l"(tm), "r"(c0), "r"(c4), "r"(bar), "r"(0) : "memory");
}
__device__ __forceinline__ void tma_5d_mc_e(uint32_t dst, const CUtensorMap* tm, int c0, int c4, uint32_t bar) {
  asm volatile("{\n.reg .pred p;\nelect.sync _|p, 0xffffffff;\n"
               "@p cp.async.bulk.tensor.5d.shared::cluster.global.mbarrier::complete_tx::bytes.multicast::cluster [%0], [%1, {%2, %6, %6, %6, %3}], [%4], %5;\n}\n"
               ::"r"(dst), "l"(tm), "r"(c0), "r"(c4), "r"(bar), "h"((uint16_t)3), "r"(0) : "memory");
}
__device__ __forceinline__ void wait_tma_5d_mc(bool w, uint32_t eb, uint32_t par, uint32_t dst, const CUtensorMap* tm, int c0, int c4, uint32_t fb) {
  asm volatile("" : "+r"(dst), "+l"(tm), "+r"(c0), "+r"(c4), "+r"(fb));
  if (w) mbar_wait_u(eb, par);
  tma_5d_mc_e(dst, tm, c0, c4, fb);
}
__device__ __forceinline__ void stg128(void* p, uint32_t a, uint32_t b, uint32_t c, uint32_t d) {
  asm volatile("st.global.v4.u32 [%0], {%1,%2,%3,%4};" ::"l"(p), "r"(a), "r"(b), "r"(c), "r"(d) : "memory");
}
__device__ __forceinline__ void stg128_p(bool on, void* p, uint32_t a, uint32_t b, uint32_t c, uint32_t d) {
  asm volatile("{\n.reg .pred p;\nsetp.ne.b32 p, %5, 0;\n@p st.global.v4.u32 [%0], {%1,%2,%3,%4};\n}\n" ::"l"(p), "r"(a), "r"(b), "r"(c), "r"(d), "r"((int)on) : "memory");
}
__device__ __forceinline__ void ldg128(const void* p, uint32_t& a, uint32_t& b, uint32_t& c, uint32_t& d) {
  asm volatile("ld.global.cg.v4.u32 {%0,%1,%2,%3}, [%4];" : "=r"(a), "=r"(b), "=r"(c), "=r"(d) : "l"(p) : "memory");
}
__device__ __forceinline__ void release2c(uint32_t off) {
  asm volatile("mbarrier.arrive.shared::cluster.b64 _, [%0];\nmbarrier.arrive.shared::cluster.b64 _, [%1];" ::"r"(off), "r"(off + (1u << 24)) : "memory");
}
__device__ __forceinline__ void tma_store_5d(const CUtensorMap* tm, uint32_t src, int c0, int c4) {
  asm volatile("cp.async.bulk.tensor.5d.global.shared::cta.bulk_group [%0, {%2, %4, %4, %4, %3}], [%1];"
               ::"l"(tm), "r"(src), "r"(c0), "r"(c4), "r"(0) : "memory");
}
__device__ __forceinline__ void bulk_load(uint32_t dst, const void* src, uint32_t bytes, uint32_t bar) {
  asm volatile("cp.async.bulk.shared::cluster.global.mbarrier::complete_tx::bytes [%0], [%1], %2, [%3];" ::"r"(dst), "l"(src), "r"(bytes), "r"(bar) : "memory");
}
__device__ __forceinline__ void bulk_red_add(void* dst, uint32_t src, uint32_t bytes) {
  asm volatile("cp.reduce.async.bulk.global.shared::cta.bulk_group.add.noftz.bf16 [%0], [%1], %2;" ::"l"(dst), "r"(src), "r"(bytes) : "memory");
}
__device__ __forceinline__ void bulk_commit() { asm volatile("cp.async.bulk.commit_group;" ::: "memory"); }
__device__ __forceinline__ void bulk_wait0() { asm volatile("cp.async.bulk.wait_group 0;" ::: "memory"); }
__device__ __forceinline__ void fence_async_smem() { asm volatile("fence.proxy.async.shared::cta;" ::: "memory"); }
__device__ __forceinline__ void fence_async_all() { asm volatile("fence.proxy.async.global;" ::: "memory"); }
__device__ __forceinline__ void wgmma_fence() { asm volatile("wgmma.fence.sync.aligned;" ::: "memory"); }
__device__ __forceinline__ void wgmma_commit() { asm volatile("wgmma.commit_group.sync.aligned;" ::: "memory"); }
template <int N> __device__ __forceinline__ void wgmma_wait() { asm volatile("wgmma.wait_group.sync.aligned %0;" ::"n"(N) : "memory"); }
__device__ __forceinline__ void cluster_wait() { asm volatile("barrier.cluster.wait.acquire.aligned;" ::: "memory"); }
template <int ID, int N> __device__ __forceinline__ void nbar() { asm volatile("bar.sync %0, %1;" ::"n"(ID), "n"(N) : "memory"); }
__device__ __forceinline__ uint64_t desc64(uint32_t lo, uint32_t hi) { return (uint64_t)lo | ((uint64_t)hi << 32); }
__device__ __forceinline__ uint32_t pack_bf16(float lo, float hi) {
  uint32_t r; asm("cvt.rn.bf16x2.f32 %0, %1, %2;" : "=r"(r) : "f"(hi), "f"(lo)); return r;
}
__device__ __forceinline__ uint32_t add_bf16x2(uint32_t a, uint32_t b) {
  uint32_t r; asm("add.rn.bf16x2 %0, %1, %2;" : "=r"(r) : "r"(a), "r"(b)); return r;
}
__device__ __forceinline__ float bf16r(float x) { return __bfloat162float(__float2bfloat16_rn(x)); }
__device__ __forceinline__ float bf_lo(uint32_t u) { return __uint_as_float(u << 16); }
__device__ __forceinline__ float bf_hi(uint32_t u) { return __uint_as_float(u & 0xFFFF0000u); }
__device__ __forceinline__ float ex2(float x) { float r; asm("ex2.approx.ftz.f32 %0, %1;" : "=f"(r) : "f"(x)); return r; }
__device__ __forceinline__ float rcp(float x) { float r; asm("rcp.approx.ftz.f32 %0, %1;" : "=f"(r) : "f"(x)); return r; }
__device__ __forceinline__ void mma_bf16(float (&d)[4], uint32_t a0, uint32_t a1, uint32_t a2, uint32_t a3, uint32_t b0, uint32_t b1) {
  asm("mma.sync.aligned.m16n8k16.row.col.f32.bf16.bf16.f32 {%0,%1,%2,%3}, {%4,%5,%6,%7}, {%8,%9}, {%0,%1,%2,%3};"
               : "+f"(d[0]), "+f"(d[1]), "+f"(d[2]), "+f"(d[3]) : "r"(a0), "r"(a1), "r"(a2), "r"(a3), "r"(b0), "r"(b1));
}
__device__ __forceinline__ void ldsm_x4(uint32_t& r0, uint32_t& r1, uint32_t& r2, uint32_t& r3, uint32_t addr) {
  asm volatile("ldmatrix.sync.aligned.m8n8.x4.shared.b16 {%0,%1,%2,%3}, [%4];"
               : "=r"(r0), "=r"(r1), "=r"(r2), "=r"(r3) : "r"(addr) : "memory");
}
__device__ __forceinline__ void ldsm_x4_t(uint32_t& r0, uint32_t& r1, uint32_t& r2, uint32_t& r3, uint32_t addr) {
  asm volatile("ldmatrix.sync.aligned.m8n8.x4.trans.shared.b16 {%0,%1,%2,%3}, [%4];"
               : "=r"(r0), "=r"(r1), "=r"(r2), "=r"(r3) : "r"(addr) : "memory");
}
__device__ __forceinline__ void stsm_x4(uint32_t addr, uint32_t r0, uint32_t r1, uint32_t r2, uint32_t r3) {
  asm volatile("stmatrix.sync.aligned.m8n8.x4.shared.b16 [%0], {%1,%2,%3,%4};"
               ::"r"(addr), "r"(r0), "r"(r1), "r"(r2), "r"(r3) : "memory");
}
__device__ __forceinline__ void stsm_x2(uint32_t addr, uint32_t r0, uint32_t r1) {
  asm volatile("stmatrix.sync.aligned.m8n8.x2.shared.b16 [%0], {%1,%2};" ::"r"(addr), "r"(r0), "r"(r1) : "memory");
}
__device__ __forceinline__ uint4 lds128(uint32_t addr) {
  uint4 v; asm volatile("ld.shared.v4.b32 {%0,%1,%2,%3}, [%4];" : "=r"(v.x), "=r"(v.y), "=r"(v.z), "=r"(v.w) : "r"(addr) : "memory"); return v;
}
__device__ __forceinline__ void sts128(uint32_t addr, uint4 v) {
  asm volatile("st.shared.v4.b32 [%0], {%1,%2,%3,%4};" ::"r"(addr), "r"(v.x), "r"(v.y), "r"(v.z), "r"(v.w) : "memory");
}
__device__ __forceinline__ float lds_f(uint32_t addr) {
  float v; asm volatile("ld.shared.f32 %0, [%1];" : "=f"(v) : "r"(addr) : "memory"); return v;
}
__device__ __forceinline__ void nbar_dyn(int id, int n) { asm volatile("bar.sync %0, %1;" ::"r"(id), "r"(n) : "memory"); }
__device__ __forceinline__ uint64_t make_desc_ns(uint32_t addr, uint32_t lbo_bytes, uint32_t sbo_bytes) {
  return (uint64_t)((addr & 0x3FFFF) >> 4) | ((uint64_t)(lbo_bytes >> 4) << 16) | ((uint64_t)(sbo_bytes >> 4) << 32);
}
__device__ __forceinline__ void sts_f(uint32_t addr, float v) { asm volatile("st.shared.f32 [%0], %1;" ::"r"(addr), "f"(v) : "memory"); }
__device__ __forceinline__ void sts64(uint32_t addr, uint32_t a, uint32_t b) {
  asm volatile("st.shared.v2.b32 [%0], {%1,%2};" ::"r"(addr), "r"(a), "r"(b) : "memory");
}
__device__ __forceinline__ void sts_f2(uint32_t addr, float a, float b) {
  asm volatile("st.shared.v2.f32 [%0], {%1,%2};" ::"r"(addr), "f"(a), "f"(b) : "memory");
}
__device__ __forceinline__ void red_add2_p(bool on, float* p, float a, float b) {
  asm volatile("{\n.reg .pred p;\nsetp.ne.b32 p, %3, 0;\n@p red.global.add.v2.f32 [%0], {%1,%2};\n}\n" ::"l"(p), "f"(a), "f"(b), "r"((int)on) : "memory");
}
__device__ __forceinline__ void red_add4(float* p, float a, float b, float c, float d) {
  asm volatile("red.global.add.v4.f32 [%0], {%1,%2,%3,%4};" ::"l"(p), "f"(a), "f"(b), "f"(c), "f"(d) : "memory");
}
__device__ __forceinline__ void red_add1(float* p, float a) {
  asm volatile("red.global.add.f32 [%0], %1;" ::"l"(p), "f"(a) : "memory");
}
__device__ __forceinline__ void l2_prefetch(const void* p, uint32_t bytes) {
  asm volatile("cp.async.bulk.prefetch.L2.global [%0], %1;" ::"l"(p), "r"(bytes) : "memory");
}

__device__ __forceinline__ void wgmma_n256(float (&d)[192], uint64_t da, uint64_t db, int scale_d) {
  asm volatile("{\n.reg .pred p;\nsetp.ne.b32 p, %130, 0;\n"
    "wgmma.mma_async.sync.aligned.m64n256k16.f32.bf16.bf16 {%0, %1, %2, %3, %4, %5, %6, %7, %8, %9, %10, %11, %12, %13, %14, %15, %16, %17, %18, %19, %20, %21, %22, %23, %24, %25, %26, %27, %28, %29, %30, %31, %32, %33, %34, %35, %36, %37, %38, %39, %40, %41, %42, %43, %44, %45, %46, %47, %48, %49, %50, %51, %52, %53, %54, %55, %56, %57, %58, %59, %60, %61, %62, %63, %64, %65, %66, %67, %68, %69, %70, %71, %72, %73, %74, %75, %76, %77, %78, %79, %80, %81, %82, %83, %84, %85, %86, %87, %88, %89, %90, %91, %92, %93, %94, %95, %96, %97, %98, %99, %100, %101, %102, %103, %104, %105, %106, %107, %108, %109, %110, %111, %112, %113, %114, %115, %116, %117, %118, %119, %120, %121, %122, %123, %124, %125, %126, %127}, %128, %129, p, 1, 1, 0, 1;\n}\n"
    : "+f"(d[0]), "+f"(d[1]), "+f"(d[2]), "+f"(d[3]), "+f"(d[4]), "+f"(d[5]), "+f"(d[6]), "+f"(d[7]), "+f"(d[8]), "+f"(d[9]), "+f"(d[10]), "+f"(d[11]), "+f"(d[12]), "+f"(d[13]), "+f"(d[14]), "+f"(d[15]), "+f"(d[16]), "+f"(d[17]), "+f"(d[18]), "+f"(d[19]), "+f"(d[20]), "+f"(d[21]), "+f"(d[22]), "+f"(d[23]), "+f"(d[24]), "+f"(d[25]), "+f"(d[26]), "+f"(d[27]), "+f"(d[28]), "+f"(d[29]), "+f"(d[30]), "+f"(d[31]), "+f"(d[32]), "+f"(d[33]), "+f"(d[34]), "+f"(d[35]), "+f"(d[36]), "+f"(d[37]), "+f"(d[38]), "+f"(d[39]), "+f"(d[40]), "+f"(d[41]), "+f"(d[42]), "+f"(d[43]), "+f"(d[44]), "+f"(d[45]), "+f"(d[46]), "+f"(d[47]), "+f"(d[48]), "+f"(d[49]), "+f"(d[50]), "+f"(d[51]), "+f"(d[52]), "+f"(d[53]), "+f"(d[54]), "+f"(d[55]), "+f"(d[56]), "+f"(d[57]), "+f"(d[58]), "+f"(d[59]), "+f"(d[60]), "+f"(d[61]), "+f"(d[62]), "+f"(d[63]), "+f"(d[64]), "+f"(d[65]), "+f"(d[66]), "+f"(d[67]), "+f"(d[68]), "+f"(d[69]), "+f"(d[70]), "+f"(d[71]), "+f"(d[72]), "+f"(d[73]), "+f"(d[74]), "+f"(d[75]), "+f"(d[76]), "+f"(d[77]), "+f"(d[78]), "+f"(d[79]), "+f"(d[80]), "+f"(d[81]), "+f"(d[82]), "+f"(d[83]), "+f"(d[84]), "+f"(d[85]), "+f"(d[86]), "+f"(d[87]), "+f"(d[88]), "+f"(d[89]), "+f"(d[90]), "+f"(d[91]), "+f"(d[92]), "+f"(d[93]), "+f"(d[94]), "+f"(d[95]), "+f"(d[96]), "+f"(d[97]), "+f"(d[98]), "+f"(d[99]), "+f"(d[100]), "+f"(d[101]), "+f"(d[102]), "+f"(d[103]), "+f"(d[104]), "+f"(d[105]), "+f"(d[106]), "+f"(d[107]), "+f"(d[108]), "+f"(d[109]), "+f"(d[110]), "+f"(d[111]), "+f"(d[112]), "+f"(d[113]), "+f"(d[114]), "+f"(d[115]), "+f"(d[116]), "+f"(d[117]), "+f"(d[118]), "+f"(d[119]), "+f"(d[120]), "+f"(d[121]), "+f"(d[122]), "+f"(d[123]), "+f"(d[124]), "+f"(d[125]), "+f"(d[126]), "+f"(d[127])
    : "l"(da), "l"(db), "r"(scale_d));
}
__device__ __forceinline__ void wgmma_n128(float (&d)[192], uint64_t da, uint64_t db, int scale_d) {
  asm volatile("{\n.reg .pred p;\nsetp.ne.b32 p, %66, 0;\n"
    "wgmma.mma_async.sync.aligned.m64n128k16.f32.bf16.bf16 {%0, %1, %2, %3, %4, %5, %6, %7, %8, %9, %10, %11, %12, %13, %14, %15, %16, %17, %18, %19, %20, %21, %22, %23, %24, %25, %26, %27, %28, %29, %30, %31, %32, %33, %34, %35, %36, %37, %38, %39, %40, %41, %42, %43, %44, %45, %46, %47, %48, %49, %50, %51, %52, %53, %54, %55, %56, %57, %58, %59, %60, %61, %62, %63}, %64, %65, p, 1, 1, 0, 1;\n}\n"
    : "+f"(d[128]), "+f"(d[129]), "+f"(d[130]), "+f"(d[131]), "+f"(d[132]), "+f"(d[133]), "+f"(d[134]), "+f"(d[135]), "+f"(d[136]), "+f"(d[137]), "+f"(d[138]), "+f"(d[139]), "+f"(d[140]), "+f"(d[141]), "+f"(d[142]), "+f"(d[143]), "+f"(d[144]), "+f"(d[145]), "+f"(d[146]), "+f"(d[147]), "+f"(d[148]), "+f"(d[149]), "+f"(d[150]), "+f"(d[151]), "+f"(d[152]), "+f"(d[153]), "+f"(d[154]), "+f"(d[155]), "+f"(d[156]), "+f"(d[157]), "+f"(d[158]), "+f"(d[159]), "+f"(d[160]), "+f"(d[161]), "+f"(d[162]), "+f"(d[163]), "+f"(d[164]), "+f"(d[165]), "+f"(d[166]), "+f"(d[167]), "+f"(d[168]), "+f"(d[169]), "+f"(d[170]), "+f"(d[171]), "+f"(d[172]), "+f"(d[173]), "+f"(d[174]), "+f"(d[175]), "+f"(d[176]), "+f"(d[177]), "+f"(d[178]), "+f"(d[179]), "+f"(d[180]), "+f"(d[181]), "+f"(d[182]), "+f"(d[183]), "+f"(d[184]), "+f"(d[185]), "+f"(d[186]), "+f"(d[187]), "+f"(d[188]), "+f"(d[189]), "+f"(d[190]), "+f"(d[191])
    : "l"(da), "l"(db), "r"(scale_d));
}
__device__ __forceinline__ void wgmma_n256_k(float (&d)[192], uint64_t da, uint64_t db, int scale_d) {
  asm volatile("{\n.reg .pred p;\nsetp.ne.b32 p, %130, 0;\n"
    "wgmma.mma_async.sync.aligned.m64n256k16.f32.bf16.bf16 {%0, %1, %2, %3, %4, %5, %6, %7, %8, %9, %10, %11, %12, %13, %14, %15, %16, %17, %18, %19, %20, %21, %22, %23, %24, %25, %26, %27, %28, %29, %30, %31, %32, %33, %34, %35, %36, %37, %38, %39, %40, %41, %42, %43, %44, %45, %46, %47, %48, %49, %50, %51, %52, %53, %54, %55, %56, %57, %58, %59, %60, %61, %62, %63, %64, %65, %66, %67, %68, %69, %70, %71, %72, %73, %74, %75, %76, %77, %78, %79, %80, %81, %82, %83, %84, %85, %86, %87, %88, %89, %90, %91, %92, %93, %94, %95, %96, %97, %98, %99, %100, %101, %102, %103, %104, %105, %106, %107, %108, %109, %110, %111, %112, %113, %114, %115, %116, %117, %118, %119, %120, %121, %122, %123, %124, %125, %126, %127}, %128, %129, p, 1, 1, 0, 0;\n}\n"
    : "+f"(d[0]), "+f"(d[1]), "+f"(d[2]), "+f"(d[3]), "+f"(d[4]), "+f"(d[5]), "+f"(d[6]), "+f"(d[7]), "+f"(d[8]), "+f"(d[9]), "+f"(d[10]), "+f"(d[11]), "+f"(d[12]), "+f"(d[13]), "+f"(d[14]), "+f"(d[15]), "+f"(d[16]), "+f"(d[17]), "+f"(d[18]), "+f"(d[19]), "+f"(d[20]), "+f"(d[21]), "+f"(d[22]), "+f"(d[23]), "+f"(d[24]), "+f"(d[25]), "+f"(d[26]), "+f"(d[27]), "+f"(d[28]), "+f"(d[29]), "+f"(d[30]), "+f"(d[31]), "+f"(d[32]), "+f"(d[33]), "+f"(d[34]), "+f"(d[35]), "+f"(d[36]), "+f"(d[37]), "+f"(d[38]), "+f"(d[39]), "+f"(d[40]), "+f"(d[41]), "+f"(d[42]), "+f"(d[43]), "+f"(d[44]), "+f"(d[45]), "+f"(d[46]), "+f"(d[47]), "+f"(d[48]), "+f"(d[49]), "+f"(d[50]), "+f"(d[51]), "+f"(d[52]), "+f"(d[53]), "+f"(d[54]), "+f"(d[55]), "+f"(d[56]), "+f"(d[57]), "+f"(d[58]), "+f"(d[59]), "+f"(d[60]), "+f"(d[61]), "+f"(d[62]), "+f"(d[63]), "+f"(d[64]), "+f"(d[65]), "+f"(d[66]), "+f"(d[67]), "+f"(d[68]), "+f"(d[69]), "+f"(d[70]), "+f"(d[71]), "+f"(d[72]), "+f"(d[73]), "+f"(d[74]), "+f"(d[75]), "+f"(d[76]), "+f"(d[77]), "+f"(d[78]), "+f"(d[79]), "+f"(d[80]), "+f"(d[81]), "+f"(d[82]), "+f"(d[83]), "+f"(d[84]), "+f"(d[85]), "+f"(d[86]), "+f"(d[87]), "+f"(d[88]), "+f"(d[89]), "+f"(d[90]), "+f"(d[91]), "+f"(d[92]), "+f"(d[93]), "+f"(d[94]), "+f"(d[95]), "+f"(d[96]), "+f"(d[97]), "+f"(d[98]), "+f"(d[99]), "+f"(d[100]), "+f"(d[101]), "+f"(d[102]), "+f"(d[103]), "+f"(d[104]), "+f"(d[105]), "+f"(d[106]), "+f"(d[107]), "+f"(d[108]), "+f"(d[109]), "+f"(d[110]), "+f"(d[111]), "+f"(d[112]), "+f"(d[113]), "+f"(d[114]), "+f"(d[115]), "+f"(d[116]), "+f"(d[117]), "+f"(d[118]), "+f"(d[119]), "+f"(d[120]), "+f"(d[121]), "+f"(d[122]), "+f"(d[123]), "+f"(d[124]), "+f"(d[125]), "+f"(d[126]), "+f"(d[127])
    : "l"(da), "l"(db), "r"(scale_d));
}
__device__ __forceinline__ void wgmma_n128_k(float (&d)[192], uint64_t da, uint64_t db, int scale_d) {
  asm volatile("{\n.reg .pred p;\nsetp.ne.b32 p, %66, 0;\n"
    "wgmma.mma_async.sync.aligned.m64n128k16.f32.bf16.bf16 {%0, %1, %2, %3, %4, %5, %6, %7, %8, %9, %10, %11, %12, %13, %14, %15, %16, %17, %18, %19, %20, %21, %22, %23, %24, %25, %26, %27, %28, %29, %30, %31, %32, %33, %34, %35, %36, %37, %38, %39, %40, %41, %42, %43, %44, %45, %46, %47, %48, %49, %50, %51, %52, %53, %54, %55, %56, %57, %58, %59, %60, %61, %62, %63}, %64, %65, p, 1, 1, 0, 0;\n}\n"
    : "+f"(d[128]), "+f"(d[129]), "+f"(d[130]), "+f"(d[131]), "+f"(d[132]), "+f"(d[133]), "+f"(d[134]), "+f"(d[135]), "+f"(d[136]), "+f"(d[137]), "+f"(d[138]), "+f"(d[139]), "+f"(d[140]), "+f"(d[141]), "+f"(d[142]), "+f"(d[143]), "+f"(d[144]), "+f"(d[145]), "+f"(d[146]), "+f"(d[147]), "+f"(d[148]), "+f"(d[149]), "+f"(d[150]), "+f"(d[151]), "+f"(d[152]), "+f"(d[153]), "+f"(d[154]), "+f"(d[155]), "+f"(d[156]), "+f"(d[157]), "+f"(d[158]), "+f"(d[159]), "+f"(d[160]), "+f"(d[161]), "+f"(d[162]), "+f"(d[163]), "+f"(d[164]), "+f"(d[165]), "+f"(d[166]), "+f"(d[167]), "+f"(d[168]), "+f"(d[169]), "+f"(d[170]), "+f"(d[171]), "+f"(d[172]), "+f"(d[173]), "+f"(d[174]), "+f"(d[175]), "+f"(d[176]), "+f"(d[177]), "+f"(d[178]), "+f"(d[179]), "+f"(d[180]), "+f"(d[181]), "+f"(d[182]), "+f"(d[183]), "+f"(d[184]), "+f"(d[185]), "+f"(d[186]), "+f"(d[187]), "+f"(d[188]), "+f"(d[189]), "+f"(d[190]), "+f"(d[191])
    : "l"(da), "l"(db), "r"(scale_d));
}
__device__ __forceinline__ void wgmma_n40_tt(float (&d)[20], uint64_t da, uint64_t db, int scale_d) {
  asm volatile("{\n.reg .pred p;\nsetp.ne.b32 p, %22, 0;\n"
    "wgmma.mma_async.sync.aligned.m64n40k16.f32.bf16.bf16 {%0, %1, %2, %3, %4, %5, %6, %7, %8, %9, %10, %11, %12, %13, %14, %15, %16, %17, %18, %19}, %20, %21, p, 1, 1, 1, 1;\n}\n"
    : "+f"(d[0]), "+f"(d[1]), "+f"(d[2]), "+f"(d[3]), "+f"(d[4]), "+f"(d[5]), "+f"(d[6]), "+f"(d[7]), "+f"(d[8]), "+f"(d[9]), "+f"(d[10]), "+f"(d[11]), "+f"(d[12]), "+f"(d[13]), "+f"(d[14]), "+f"(d[15]), "+f"(d[16]), "+f"(d[17]), "+f"(d[18]), "+f"(d[19])
    : "l"(da), "l"(db), "r"(scale_d));
}
__device__ __forceinline__ void wgmma_n40_rs(float (&d)[20], const uint32_t (&a)[4], uint64_t db, int scale_d) {
  asm volatile("{\n.reg .pred p;\nsetp.ne.b32 p, %25, 0;\n"
    "wgmma.mma_async.sync.aligned.m64n40k16.f32.bf16.bf16 {%0, %1, %2, %3, %4, %5, %6, %7, %8, %9, %10, %11, %12, %13, %14, %15, %16, %17, %18, %19}, {%20, %21, %22, %23}, %24, p, 1, 1, 1;\n}\n"
    : "+f"(d[0]), "+f"(d[1]), "+f"(d[2]), "+f"(d[3]), "+f"(d[4]), "+f"(d[5]), "+f"(d[6]), "+f"(d[7]), "+f"(d[8]), "+f"(d[9]), "+f"(d[10]), "+f"(d[11]), "+f"(d[12]), "+f"(d[13]), "+f"(d[14]), "+f"(d[15]), "+f"(d[16]), "+f"(d[17]), "+f"(d[18]), "+f"(d[19])
    : "r"(a[0]), "r"(a[1]), "r"(a[2]), "r"(a[3]), "l"(db), "r"(scale_d));
}
__device__ __forceinline__ void wgmma_n128_0(float (&d)[192], uint64_t da, uint64_t db) {
  asm volatile("{\n.reg .pred p;\nsetp.ne.b32 p, 0, 0;\n"
    "wgmma.mma_async.sync.aligned.m64n128k16.f32.bf16.bf16 {%0, %1, %2, %3, %4, %5, %6, %7, %8, %9, %10, %11, %12, %13, %14, %15, %16, %17, %18, %19, %20, %21, %22, %23, %24, %25, %26, %27, %28, %29, %30, %31, %32, %33, %34, %35, %36, %37, %38, %39, %40, %41, %42, %43, %44, %45, %46, %47, %48, %49, %50, %51, %52, %53, %54, %55, %56, %57, %58, %59, %60, %61, %62, %63}, %64, %65, p, 1, 1, 0, 1;\n}\n"
    : "=f"(d[128]), "=f"(d[129]), "=f"(d[130]), "=f"(d[131]), "=f"(d[132]), "=f"(d[133]), "=f"(d[134]), "=f"(d[135]), "=f"(d[136]), "=f"(d[137]), "=f"(d[138]), "=f"(d[139]), "=f"(d[140]), "=f"(d[141]), "=f"(d[142]), "=f"(d[143]), "=f"(d[144]), "=f"(d[145]), "=f"(d[146]), "=f"(d[147]), "=f"(d[148]), "=f"(d[149]), "=f"(d[150]), "=f"(d[151]), "=f"(d[152]), "=f"(d[153]), "=f"(d[154]), "=f"(d[155]), "=f"(d[156]), "=f"(d[157]), "=f"(d[158]), "=f"(d[159]), "=f"(d[160]), "=f"(d[161]), "=f"(d[162]), "=f"(d[163]), "=f"(d[164]), "=f"(d[165]), "=f"(d[166]), "=f"(d[167]), "=f"(d[168]), "=f"(d[169]), "=f"(d[170]), "=f"(d[171]), "=f"(d[172]), "=f"(d[173]), "=f"(d[174]), "=f"(d[175]), "=f"(d[176]), "=f"(d[177]), "=f"(d[178]), "=f"(d[179]), "=f"(d[180]), "=f"(d[181]), "=f"(d[182]), "=f"(d[183]), "=f"(d[184]), "=f"(d[185]), "=f"(d[186]), "=f"(d[187]), "=f"(d[188]), "=f"(d[189]), "=f"(d[190]), "=f"(d[191])
    : "l"(da), "l"(db));
}
__device__ __forceinline__ void wgmma_n128_rs(float (&d)[192], const uint32_t (&a)[4], uint64_t db, int scale_d) {
  asm volatile("{\n.reg .pred p;\nsetp.ne.b32 p, %69, 0;\n"
    "wgmma.mma_async.sync.aligned.m64n128k16.f32.bf16.bf16 {%0, %1, %2, %3, %4, %5, %6, %7, %8, %9, %10, %11, %12, %13, %14, %15, %16, %17, %18, %19, %20, %21, %22, %23, %24, %25, %26, %27, %28, %29, %30, %31, %32, %33, %34, %35, %36, %37, %38, %39, %40, %41, %42, %43, %44, %45, %46, %47, %48, %49, %50, %51, %52, %53, %54, %55, %56, %57, %58, %59, %60, %61, %62, %63}, {%64, %65, %66, %67}, %68, p, 1, 1, 1;\n}\n"
    : "+f"(d[128]), "+f"(d[129]), "+f"(d[130]), "+f"(d[131]), "+f"(d[132]), "+f"(d[133]), "+f"(d[134]), "+f"(d[135]), "+f"(d[136]), "+f"(d[137]), "+f"(d[138]), "+f"(d[139]), "+f"(d[140]), "+f"(d[141]), "+f"(d[142]), "+f"(d[143]), "+f"(d[144]), "+f"(d[145]), "+f"(d[146]), "+f"(d[147]), "+f"(d[148]), "+f"(d[149]), "+f"(d[150]), "+f"(d[151]), "+f"(d[152]), "+f"(d[153]), "+f"(d[154]), "+f"(d[155]), "+f"(d[156]), "+f"(d[157]), "+f"(d[158]), "+f"(d[159]), "+f"(d[160]), "+f"(d[161]), "+f"(d[162]), "+f"(d[163]), "+f"(d[164]), "+f"(d[165]), "+f"(d[166]), "+f"(d[167]), "+f"(d[168]), "+f"(d[169]), "+f"(d[170]), "+f"(d[171]), "+f"(d[172]), "+f"(d[173]), "+f"(d[174]), "+f"(d[175]), "+f"(d[176]), "+f"(d[177]), "+f"(d[178]), "+f"(d[179]), "+f"(d[180]), "+f"(d[181]), "+f"(d[182]), "+f"(d[183]), "+f"(d[184]), "+f"(d[185]), "+f"(d[186]), "+f"(d[187]), "+f"(d[188]), "+f"(d[189]), "+f"(d[190]), "+f"(d[191])
    : "r"(a[0]), "r"(a[1]), "r"(a[2]), "r"(a[3]), "l"(db), "r"(scale_d));
}
__device__ __forceinline__ void wgmma_n32_0(float (&d)[16], uint64_t da, uint64_t db) {
  asm volatile("{\n.reg .pred p;\nsetp.ne.b32 p, 0, 0;\n"
    "wgmma.mma_async.sync.aligned.m64n32k16.f32.bf16.bf16 {%0, %1, %2, %3, %4, %5, %6, %7, %8, %9, %10, %11, %12, %13, %14, %15}, %16, %17, p, 1, 1, 0, 1;\n}\n"
    : "=f"(d[0]), "=f"(d[1]), "=f"(d[2]), "=f"(d[3]), "=f"(d[4]), "=f"(d[5]), "=f"(d[6]), "=f"(d[7]), "=f"(d[8]), "=f"(d[9]), "=f"(d[10]), "=f"(d[11]), "=f"(d[12]), "=f"(d[13]), "=f"(d[14]), "=f"(d[15])
    : "l"(da), "l"(db));
}
__device__ __forceinline__ void wgmma_n32(float (&d)[16], uint64_t da, uint64_t db, int scale_d) {
  asm volatile("{\n.reg .pred p;\nsetp.ne.b32 p, %18, 0;\n"
    "wgmma.mma_async.sync.aligned.m64n32k16.f32.bf16.bf16 {%0, %1, %2, %3, %4, %5, %6, %7, %8, %9, %10, %11, %12, %13, %14, %15}, %16, %17, p, 1, 1, 0, 1;\n}\n"
    : "+f"(d[0]), "+f"(d[1]), "+f"(d[2]), "+f"(d[3]), "+f"(d[4]), "+f"(d[5]), "+f"(d[6]), "+f"(d[7]), "+f"(d[8]), "+f"(d[9]), "+f"(d[10]), "+f"(d[11]), "+f"(d[12]), "+f"(d[13]), "+f"(d[14]), "+f"(d[15])
    : "l"(da), "l"(db), "r"(scale_d));
}
__device__ __forceinline__ void wgmma_n8_t(float (&d)[4], uint64_t da, uint64_t db, int scale_d) {
  asm volatile("{\n.reg .pred p;\nsetp.ne.b32 p, %6, 0;\n"
    "wgmma.mma_async.sync.aligned.m64n8k16.f32.bf16.bf16 {%0, %1, %2, %3}, %4, %5, p, 1, 1, 1, 0;\n}\n"
    : "+f"(d[0]), "+f"(d[1]), "+f"(d[2]), "+f"(d[3])
    : "l"(da), "l"(db), "r"(scale_d));
}
__device__ __forceinline__ void wgmma_n128_rs0(float (&d)[192], const uint32_t (&a)[4], uint64_t db) {
  asm volatile("{\n.reg .pred p;\nsetp.ne.b32 p, 0, 0;\n"
    "wgmma.mma_async.sync.aligned.m64n128k16.f32.bf16.bf16 {%0, %1, %2, %3, %4, %5, %6, %7, %8, %9, %10, %11, %12, %13, %14, %15, %16, %17, %18, %19, %20, %21, %22, %23, %24, %25, %26, %27, %28, %29, %30, %31, %32, %33, %34, %35, %36, %37, %38, %39, %40, %41, %42, %43, %44, %45, %46, %47, %48, %49, %50, %51, %52, %53, %54, %55, %56, %57, %58, %59, %60, %61, %62, %63}, {%64, %65, %66, %67}, %68, p, 1, 1, 1;\n}\n"
    : "=f"(d[128]), "=f"(d[129]), "=f"(d[130]), "=f"(d[131]), "=f"(d[132]), "=f"(d[133]), "=f"(d[134]), "=f"(d[135]), "=f"(d[136]), "=f"(d[137]), "=f"(d[138]), "=f"(d[139]), "=f"(d[140]), "=f"(d[141]), "=f"(d[142]), "=f"(d[143]), "=f"(d[144]), "=f"(d[145]), "=f"(d[146]), "=f"(d[147]), "=f"(d[148]), "=f"(d[149]), "=f"(d[150]), "=f"(d[151]), "=f"(d[152]), "=f"(d[153]), "=f"(d[154]), "=f"(d[155]), "=f"(d[156]), "=f"(d[157]), "=f"(d[158]), "=f"(d[159]), "=f"(d[160]), "=f"(d[161]), "=f"(d[162]), "=f"(d[163]), "=f"(d[164]), "=f"(d[165]), "=f"(d[166]), "=f"(d[167]), "=f"(d[168]), "=f"(d[169]), "=f"(d[170]), "=f"(d[171]), "=f"(d[172]), "=f"(d[173]), "=f"(d[174]), "=f"(d[175]), "=f"(d[176]), "=f"(d[177]), "=f"(d[178]), "=f"(d[179]), "=f"(d[180]), "=f"(d[181]), "=f"(d[182]), "=f"(d[183]), "=f"(d[184]), "=f"(d[185]), "=f"(d[186]), "=f"(d[187]), "=f"(d[188]), "=f"(d[189]), "=f"(d[190]), "=f"(d[191])
    : "r"(a[0]), "r"(a[1]), "r"(a[2]), "r"(a[3]), "l"(db));
}
__device__ __forceinline__ void wgmma_n256_rs(float (&d)[192], const uint32_t (&a)[4], uint64_t db, int scale_d) {
  asm volatile("{\n.reg .pred p;\nsetp.ne.b32 p, %133, 0;\n"
    "wgmma.mma_async.sync.aligned.m64n256k16.f32.bf16.bf16 {%0, %1, %2, %3, %4, %5, %6, %7, %8, %9, %10, %11, %12, %13, %14, %15, %16, %17, %18, %19, %20, %21, %22, %23, %24, %25, %26, %27, %28, %29, %30, %31, %32, %33, %34, %35, %36, %37, %38, %39, %40, %41, %42, %43, %44, %45, %46, %47, %48, %49, %50, %51, %52, %53, %54, %55, %56, %57, %58, %59, %60, %61, %62, %63, %64, %65, %66, %67, %68, %69, %70, %71, %72, %73, %74, %75, %76, %77, %78, %79, %80, %81, %82, %83, %84, %85, %86, %87, %88, %89, %90, %91, %92, %93, %94, %95, %96, %97, %98, %99, %100, %101, %102, %103, %104, %105, %106, %107, %108, %109, %110, %111, %112, %113, %114, %115, %116, %117, %118, %119, %120, %121, %122, %123, %124, %125, %126, %127}, {%128, %129, %130, %131}, %132, p, 1, 1, 1;\n}\n"
    : "+f"(d[0]), "+f"(d[1]), "+f"(d[2]), "+f"(d[3]), "+f"(d[4]), "+f"(d[5]), "+f"(d[6]), "+f"(d[7]), "+f"(d[8]), "+f"(d[9]), "+f"(d[10]), "+f"(d[11]), "+f"(d[12]), "+f"(d[13]), "+f"(d[14]), "+f"(d[15]), "+f"(d[16]), "+f"(d[17]), "+f"(d[18]), "+f"(d[19]), "+f"(d[20]), "+f"(d[21]), "+f"(d[22]), "+f"(d[23]), "+f"(d[24]), "+f"(d[25]), "+f"(d[26]), "+f"(d[27]), "+f"(d[28]), "+f"(d[29]), "+f"(d[30]), "+f"(d[31]), "+f"(d[32]), "+f"(d[33]), "+f"(d[34]), "+f"(d[35]), "+f"(d[36]), "+f"(d[37]), "+f"(d[38]), "+f"(d[39]), "+f"(d[40]), "+f"(d[41]), "+f"(d[42]), "+f"(d[43]), "+f"(d[44]), "+f"(d[45]), "+f"(d[46]), "+f"(d[47]), "+f"(d[48]), "+f"(d[49]), "+f"(d[50]), "+f"(d[51]), "+f"(d[52]), "+f"(d[53]), "+f"(d[54]), "+f"(d[55]), "+f"(d[56]), "+f"(d[57]), "+f"(d[58]), "+f"(d[59]), "+f"(d[60]), "+f"(d[61]), "+f"(d[62]), "+f"(d[63]), "+f"(d[64]), "+f"(d[65]), "+f"(d[66]), "+f"(d[67]), "+f"(d[68]), "+f"(d[69]), "+f"(d[70]), "+f"(d[71]), "+f"(d[72]), "+f"(d[73]), "+f"(d[74]), "+f"(d[75]), "+f"(d[76]), "+f"(d[77]), "+f"(d[78]), "+f"(d[79]), "+f"(d[80]), "+f"(d[81]), "+f"(d[82]), "+f"(d[83]), "+f"(d[84]), "+f"(d[85]), "+f"(d[86]), "+f"(d[87]), "+f"(d[88]), "+f"(d[89]), "+f"(d[90]), "+f"(d[91]), "+f"(d[92]), "+f"(d[93]), "+f"(d[94]), "+f"(d[95]), "+f"(d[96]), "+f"(d[97]), "+f"(d[98]), "+f"(d[99]), "+f"(d[100]), "+f"(d[101]), "+f"(d[102]), "+f"(d[103]), "+f"(d[104]), "+f"(d[105]), "+f"(d[106]), "+f"(d[107]), "+f"(d[108]), "+f"(d[109]), "+f"(d[110]), "+f"(d[111]), "+f"(d[112]), "+f"(d[113]), "+f"(d[114]), "+f"(d[115]), "+f"(d[116]), "+f"(d[117]), "+f"(d[118]), "+f"(d[119]), "+f"(d[120]), "+f"(d[121]), "+f"(d[122]), "+f"(d[123]), "+f"(d[124]), "+f"(d[125]), "+f"(d[126]), "+f"(d[127])
    : "r"(a[0]), "r"(a[1]), "r"(a[2]), "r"(a[3]), "l"(db), "r"(scale_d));
}
__device__ __forceinline__ void wgmma_n256_rs0(float (&d)[192], const uint32_t (&a)[4], uint64_t db) {
  asm volatile("{\n.reg .pred p;\nsetp.ne.b32 p, 0, 0;\n"
    "wgmma.mma_async.sync.aligned.m64n256k16.f32.bf16.bf16 {%0, %1, %2, %3, %4, %5, %6, %7, %8, %9, %10, %11, %12, %13, %14, %15, %16, %17, %18, %19, %20, %21, %22, %23, %24, %25, %26, %27, %28, %29, %30, %31, %32, %33, %34, %35, %36, %37, %38, %39, %40, %41, %42, %43, %44, %45, %46, %47, %48, %49, %50, %51, %52, %53, %54, %55, %56, %57, %58, %59, %60, %61, %62, %63, %64, %65, %66, %67, %68, %69, %70, %71, %72, %73, %74, %75, %76, %77, %78, %79, %80, %81, %82, %83, %84, %85, %86, %87, %88, %89, %90, %91, %92, %93, %94, %95, %96, %97, %98, %99, %100, %101, %102, %103, %104, %105, %106, %107, %108, %109, %110, %111, %112, %113, %114, %115, %116, %117, %118, %119, %120, %121, %122, %123, %124, %125, %126, %127}, {%128, %129, %130, %131}, %132, p, 1, 1, 1;\n}\n"
    : "=f"(d[0]), "=f"(d[1]), "=f"(d[2]), "=f"(d[3]), "=f"(d[4]), "=f"(d[5]), "=f"(d[6]), "=f"(d[7]), "=f"(d[8]), "=f"(d[9]), "=f"(d[10]), "=f"(d[11]), "=f"(d[12]), "=f"(d[13]), "=f"(d[14]), "=f"(d[15]), "=f"(d[16]), "=f"(d[17]), "=f"(d[18]), "=f"(d[19]), "=f"(d[20]), "=f"(d[21]), "=f"(d[22]), "=f"(d[23]), "=f"(d[24]), "=f"(d[25]), "=f"(d[26]), "=f"(d[27]), "=f"(d[28]), "=f"(d[29]), "=f"(d[30]), "=f"(d[31]), "=f"(d[32]), "=f"(d[33]), "=f"(d[34]), "=f"(d[35]), "=f"(d[36]), "=f"(d[37]), "=f"(d[38]), "=f"(d[39]), "=f"(d[40]), "=f"(d[41]), "=f"(d[42]), "=f"(d[43]), "=f"(d[44]), "=f"(d[45]), "=f"(d[46]), "=f"(d[47]), "=f"(d[48]), "=f"(d[49]), "=f"(d[50]), "=f"(d[51]), "=f"(d[52]), "=f"(d[53]), "=f"(d[54]), "=f"(d[55]), "=f"(d[56]), "=f"(d[57]), "=f"(d[58]), "=f"(d[59]), "=f"(d[60]), "=f"(d[61]), "=f"(d[62]), "=f"(d[63]), "=f"(d[64]), "=f"(d[65]), "=f"(d[66]), "=f"(d[67]), "=f"(d[68]), "=f"(d[69]), "=f"(d[70]), "=f"(d[71]), "=f"(d[72]), "=f"(d[73]), "=f"(d[74]), "=f"(d[75]), "=f"(d[76]), "=f"(d[77]), "=f"(d[78]), "=f"(d[79]), "=f"(d[80]), "=f"(d[81]), "=f"(d[82]), "=f"(d[83]), "=f"(d[84]), "=f"(d[85]), "=f"(d[86]), "=f"(d[87]), "=f"(d[88]), "=f"(d[89]), "=f"(d[90]), "=f"(d[91]), "=f"(d[92]), "=f"(d[93]), "=f"(d[94]), "=f"(d[95]), "=f"(d[96]), "=f"(d[97]), "=f"(d[98]), "=f"(d[99]), "=f"(d[100]), "=f"(d[101]), "=f"(d[102]), "=f"(d[103]), "=f"(d[104]), "=f"(d[105]), "=f"(d[106]), "=f"(d[107]), "=f"(d[108]), "=f"(d[109]), "=f"(d[110]), "=f"(d[111]), "=f"(d[112]), "=f"(d[113]), "=f"(d[114]), "=f"(d[115]), "=f"(d[116]), "=f"(d[117]), "=f"(d[118]), "=f"(d[119]), "=f"(d[120]), "=f"(d[121]), "=f"(d[122]), "=f"(d[123]), "=f"(d[124]), "=f"(d[125]), "=f"(d[126]), "=f"(d[127])
    : "r"(a[0]), "r"(a[1]), "r"(a[2]), "r"(a[3]), "l"(db));
}

constexpr int SLOT = 16384;
constexpr int VB = 4 * SLOT, PH = 0, XS = 6;
constexpr int SM_SD = 13 * SLOT;
constexpr int SM_BAR = SM_SD + 8192;
constexpr int SM_RS = SM_BAR + 1024;
constexpr int SM_AP = SM_RS + 640;
constexpr int SM_BP = SM_AP + 2048;
constexpr int SM_EPOCH = SM_BP + 6144;
constexpr int SM_TOTAL = SM_EPOCH + 16;
constexpr int FM = 0, FT = 16, FW = 30, CM = 46, CT = 62, CW = 76, B_EF = 92, B_STAT = 93, B_KVF = 94, B_HALO = 95,
              B_KVDONE = 96, B_OH0 = 97, B_OH1 = 98, B_XH0 = 99, B_XDONE = 100, B_WFD = 101, B_XT = 102, B_OF0 = 103, B_KVF1 = 104, B_KVS = 105, B_RAW = 106  , B_X0 = 108, B_KVS0 = 109;
constexpr uint64_t BAR_LG = 0x00043333330004ull;
#define BA(i) (bar + (i) * 8)
#define REL2(i) release2c(SB0 + SM_BAR + (i) * 8)
constexpr int NF = 3, ND = 13, NR = 0, NWOP = 48, NAOP = 38;
constexpr bool EF_USED = false;
constexpr uint64_t TL_A = 0x6278627862786ull, TL_B = 0xa9c3ba9c3ba9cull, WO_A = 0x76b24038b51403ffull, WO_B = 0x8c5a197c6a297c8bull;
__constant__ uint32_t c_wop[NWOP + 1] = {0xeb0009, 0x186b8000, 0x6c0112, 0x1aec011a, 0x6c8224, 0x22ec822b, 0x18170330, 0x18178442, 0x18180554, 0x18188660, 0x18190772, 0x18198884, 0x181a0990, 0x181a8aa2, 0x181b0bb4, 0x181b8cc0, 0xaed10fc, 0xa9711e9, 0x181c0dd2, 0xa9792da, 0x129813cb, 0x181c8ee4, 0x181d0ff0, 0x109d94b3, 0x109f15ac, 0x109f9699, 0x10a0178a, 0x10a0987b, 0x10a11963, 0x10a19a5c, 0x10a21b49, 0x10a29c3a, 0x9231e0b, 0x9239f18, 0x1124202c, 0x13242137, 0x1124a249, 0x1324a352, 0x1125246a, 0x13252576, 0x1127268c, 0x1127a797, 0x112828a9, 0x1128a9b1, 0x11292aca, 0x13292bd5, 0x112a2cec, 0x132a2df8, 0};
__constant__ uint32_t c_aop[NAOP + 1] = {0x6d8228, 0x170336, 0x178447, 0x180558, 0x188666, 0x190777, 0x198888, 0x1a0996, 0x1a8aa7, 0x1b0bb8, 0x1b8cc6, 0x1c0dd7, 0x1c8ee8, 0x1d0ff6, 0x1d93c2, 0x1f14b6, 0x1f95a8, 0x201697, 0x209782, 0x211876, 0x219968, 0x221a57, 0x229b42, 0x231c36, 0xa3a023, 0xb12130, 0x2b12244, 0x2b12351, 0x2b12465, 0xa6257b, 0xa6a688, 0xa72793, 0xa7a8a0, 0xa829b4, 0xa8aac2, 0xa9abdb, 0x2a9ace6, 0xaaadf7, 0};
__constant__ uint32_t c_map[64] = {4, 5, 6, 7, 0, 16, 32, 48, 64, 80, 96, 112, 1, 17, 33, 49, 65, 81, 97, 113, 2, 18, 34, 50, 66, 82, 98, 114, 3, 19, 35, 51, 67, 83, 99, 115, 20, 36, 52, 68, 84, 100, 116, 21, 37, 53, 69, 85, 101, 117, 22, 38, 54, 70, 86, 102, 118, 23, 39, 55, 71, 87, 103, 119};
enum { MAP_WF = 0, MAP_WA = 2, MAP_WB = 4, MAP_WOA = 6, MAP_WOB = 8, MAP_X0 = 10, MAP_X = 11, MAP_O = 12, MAP_PHI = 13, NMAP = 14 };
struct Maps { CUtensorMap m[NMAP]; };

#define PL 2
#define PROFL(a, b)
#define SUBS 16
#define SUBS1 16
#define XRAT 10
#define XRN 4
#define BT1 1
#define ST1 8
#define X0AT 2
#define W1DL 400
#define WH 4
#define PFM 3
#define PFS 2
#define SVD 5000
#define NLAYERS 4
constexpr float L2E = 1.4426950408889634f;

#define D128(lo) desc64(lo, 0x40000040u)
struct Ctx { uint32_t zero, boff; const bf16* x0; bf16* out; };
#define BLK_CTX() \
  uint32_t bid_; asm volatile("mov.u32 %0, %%ctaid.x;" : "=r"(bid_)); \
  bid_ -= c.boff; \
  const uint32_t gr_ = c_map[bid_ >> 1]; \
  const int cr = bid_ & 1, g = gr_ & 7, rb = (gr_ >> 3) + cr, m0 = rb * 128; \
  const uint32_t sb = SB0 + (cr << 24); \
  const uint32_t bar = sb + SM_BAR; \
  (void)cr; (void)g; (void)rb; (void)m0; (void)bar;
extern __shared__ uint8_t smem_raw[];
constexpr uint32_t SB0 = 1024;

#define PHASE_CTX() \
  BLK_CTX(); \
  int tid_ = threadIdx.x; asm volatile("" : "+r"(tid_)); \
  const int lane = tid_ & 31, cw = (tid_ >> 5) - 4, wg = cw >> 2, wq = cw & 3, gq = lane >> 2, t = lane & 3, wrow0 = cw * 16; \
  const int lrow = (lane & 7) + ((lane >> 3) & 1) * 8, lchk = lane >> 4; \
  const bool elected = (tid_ & 127) == 0; \
  const uint32_t rowo = (wrow0 + lrow) * 128, X = (lchk ^ (lane & 7)) << 4; \
  const uint32_t Y = (wrow0 + (lane & 7)) * 128 + (((lane >> 3) ^ (lane & 7)) << 4); \
  const size_t gfr = (size_t)(m0 + wrow0 + gq) * D_ + g * 128 + 8 * t; \
  (void)bar; (void)wq; (void)gq; (void)lrow; (void)lchk; (void)elected; (void)wrow0; (void)wg; (void)rowo; (void)X; (void)t; (void)Y; (void)gfr;
#define MMA_CTX() \
  const uint32_t wu = __shfl_sync(0xffffffffu, wg, 0); \
  const uint32_t dA0 = ((SB0 >> 4) | (1u << 16)) + wu * 512, dB0 = (SB0 >> 4) | (512u << 16); \
  const uint32_t par = layer & 1;

__device__ __forceinline__ void slab_out_half(uint32_t slot, bf16* dst, int wrow0, int lane) {
  const int r0 = lane >> 3, ch = lane & 7;
  const uint32_t src = slot + (wrow0 + r0) * 128;
  uint4 v[4];
#pragma unroll
  for (int i = 0; i < 4; ++i) v[i] = lds128(src + i * 512 + (((ch ^ (4 * i + r0)) & 7) << 4));
  dst += (size_t)(wrow0 + r0) * D_ + ch * 8;
#pragma unroll
  for (int i = 0; i < 4; ++i) *reinterpret_cast<uint4*>(dst + (size_t)i * 4 * D_) = v[i];
}

__device__ __forceinline__ void consumer(const Ctx& c) {
  float acc[192];
  uint32_t xf[4][4];
  uint32_t xp[8][4];
  {
    PHASE_CTX();
    const unsigned int epoch = ld_relaxed(&g_epoch);
    PROFT(tid_ == 128, 0);
    const uint32_t wu = __shfl_sync(0xffffffffu, wg, 0);
    if (tid_ < 128 + 8) sts128(sb + SM_AP + lane * 16, make_uint4(0x3F803F80u, 0x3F803F80u, 0x3F803F80u, 0x3F803F80u));
#pragma unroll 1
    for (int it = 0; it < 2; ++it) {
      float p[4][16];
      mbar_wait(BA(B_RAW + it), 0);
      PROFT(tid_ == 128, it ? 15 : 2);
      const uint32_t da = ((SB0 >> 4) | (1u << 16)) + (wu ? 9 + it : 2 * it) * 1024, db = (SB0 + SM_SD) >> 4;
      wgmma_fence();
#pragma unroll
      for (int h = 0; h < 4; ++h) wgmma_n32_0(p[h], D128(da + (h >> 1) * 512 + (h & 1) * 4), desc64(db + h * 128, 0x80000020u));
#pragma unroll
      for (int h = 0; h < 4; ++h) wgmma_n32(p[h], D128(da + (h >> 1) * 512 + (h & 1) * 4 + 2), desc64(db + h * 128 + 64, 0x80000020u), 1);
      wgmma_commit();
      wgmma_wait<0>();
#pragma unroll
      for (int i = 0; i < 64; ++i) asm volatile("" : "+f"(p[i >> 4][i & 15]) :: "memory");
      const uint32_t base = sb + (wg ? 9 + it : 2 * it) * SLOT + (wq * 16 + gq) * 128;
      uint32_t w[4][4][2];
#pragma unroll
      for (int i = 0; i < 32; ++i) w[i >> 3][(i >> 1) & 3][i & 1] = pack_bf16(p[i >> 3][2 * (i & 7)], p[i >> 3][2 * (i & 7) + 1]);
      if (wu) {
#pragma unroll
        for (int i = 0; i < 8; ++i)
          sts128(base + (i >> 2) * 8192 + (i & 1) * 1024 + (((((i >> 1) & 1) * 4 + t) ^ gq) << 4), make_uint4(w[i >> 1][0][i & 1], w[i >> 1][1][i & 1], w[i >> 1][2][i & 1], w[i >> 1][3][i & 1]));
      } else {
#pragma unroll
        for (int i = 0; i < 16; ++i)
          sts64(base + (i >> 3) * 8192 + (i & 1) * 1024 + ((((t & 1) * 4 + ((i >> 1) & 3)) ^ gq) << 4) + (t >> 1) * 8, w[(i >> 3) * 2][(i >> 1) & 3][i & 1], w[(i >> 3) * 2 + 1][(i >> 1) & 3][i & 1]);
      }
      fence_async_smem();
      __syncwarp();
      if (it == cr && lane == 0) mbar_arrive(BA(B_WFD));
    }
    if (tid_ == 128) sts_f(sb + SM_EPOCH, __uint_as_float(epoch & 1));
#pragma unroll
    for (int i = 0; i < 32; ++i) xp[i >> 2][i & 3] = 0u;
    nbar<1, 256>();
    PROFT(tid_ == 128, 13);
    mbar_wait(BA(FM + cr), 0);
    float cs[3][4];
    wgmma_fence();
#pragma unroll
    for (int ks = 0; ks < 4; ++ks)
#pragma unroll
      for (int i = 0; i < 3; ++i) {
        const uint32_t bx = (i == 0 ? 2 * cr * 1024 : i == 1 ? (2 * cr + 1) * 1024 : (9 + cr) * 1024) + wu * 512;
        wgmma_n8_t(cs[i], D128(((SB0 >> 4) | (512u << 16)) + bx + ks * 128), desc64((SB0 + SM_AP) >> 4, 0), ks != 0);
      }
    wgmma_commit();
    mbar_wait(BA(FM), 0);
#pragma unroll
    for (int k = 0; k < 4; ++k) ldsm_x4(xf[k][0], xf[k][1], xf[k][2], xf[k][3], sb + XS * SLOT + rowo + (X ^ (k << 5)));
    wgmma_wait<0>();
#pragma unroll
    for (int i = 0; i < 12; ++i) asm volatile("" : "+f"(cs[i >> 2][i & 3]) :: "memory");
    if (t < 2) {
#pragma unroll
      for (int i = 0; i < 3; ++i) red_add1(g_cs + (epoch & 1) * 6144 + g * 384 + i * 128 + wg * 64 + wq * 16 + gq + t * 8, t ? cs[i][2] : cs[i][0]);
    }
    PROFT(tid_ == 128, 14);
  }
#pragma unroll 1
  for (int layer = 0;; ++layer) {
    {
      wgmma_fence();
      wgmma_n256_rs0(acc, xf[0], D128((SB0 >> 4) | (512u << 16)));
#pragma unroll
      for (int k = 1; k < 4; ++k) wgmma_n256_rs(acc, xf[k], D128(((SB0 >> 4) | (512u << 16)) + k * 128), 1);
      wgmma_commit();
      PHASE_CTX();
      MMA_CTX();
      {
        const uint32_t ep = __float_as_uint(lds_f(sb + SM_EPOCH));
        if (layer == 0) {
          mbar_wait(BA(B_X0), 0);
#pragma unroll
          for (int i = 0; i < 8; ++i) ldsm_x4(xp[i][0], xp[i][1], xp[i][2], xp[i][3], sb + (11 + (i >> 2)) * SLOT + (Y ^ ((i & 2) << 5)) + (i & 1) * 1024);
          if (lane == ((xp[0][0] ^ xp[1][0] ^ xp[2][0] ^ xp[3][0] ^ xp[7][0]) & c.zero)) REL2(B_XT);
        } else {
#pragma unroll
          for (int i = 0; i < 8; ++i) stsm_x4(sb + (XS + (i >> 2)) * SLOT + (Y ^ ((i & 2) << 5)) + (i & 1) * 1024, xp[i][0], xp[i][1], xp[i][2], xp[i][3]);
        }
        float s0 = 0.f, s1 = 0.f, q0 = 0.f, q1 = 0.f;
        auto stats = [&](int j0, int j1) {
#pragma unroll
          for (int j = j0; j < j1; ++j) {
            const uint32_t u0 = xp[(j >> 2) * 2][j & 3], u1 = xp[(j >> 2) * 2 + 1][j & 3];
            s0 += bf_lo(u0) + bf_hi(u0); s1 += bf_lo(u1) + bf_hi(u1);
            q0 = fmaf(bf_lo(u0), bf_lo(u0), fmaf(bf_hi(u0), bf_hi(u0), q0)); q1 = fmaf(bf_lo(u1), bf_lo(u1), fmaf(bf_hi(u1), bf_hi(u1), q1));
          }
        };
        stats(0, ST1);
        fence_async_smem();
        nbar_dyn(3 + wu + (__float_as_uint(s0 + s1 + q0 + q1) & c.zero), 128);
        mbar_wait(BA(FM + 1), par);
        wgmma_fence();
#pragma unroll
        for (int k = 0; k < 4; ++k) wgmma_n256(acc, D128(dA0 + (XS + 1) * 1024 + k * 2), D128(dB0 + 2048 + k * 128), 1);
        wgmma_commit();
        wgmma_wait<1>();
#pragma unroll
        for (int i = 4; i < 8; ++i) stg128_p(layer, g_x + gfr + (i & 1) * 8 * D_ + (i >> 1) * 32, xp[i][0], xp[i][1], xp[i][2], xp[i][3]);
        {
          uint32_t zc; asm volatile("mov.u32 %0, %%clock;" : "=r"(zc) :: "memory");
          q0 += __uint_as_float(zc & c.zero); q1 += __uint_as_float(zc & c.zero); s0 += __uint_as_float(zc & c.zero); s1 += __uint_as_float(zc & c.zero);
        }
        stats(ST1, 16);
        wgmma_fence();
        wgmma_n128_0(acc, D128(dA0 + XS * 1024), D128(dB0 + 9 * 1024));
#pragma unroll
        for (int k = 1; k < 4; ++k) wgmma_n128(acc, D128(dA0 + XS * 1024 + k * 2), D128(dB0 + 9 * 1024 + k * 128), 1);
        wgmma_commit();
        const bool od = t & 1;
        float sa = od ? s1 : s0, qa = od ? q1 : q0;
        sa += __shfl_xor_sync(0xffffffffu, od ? s0 : s1, 1);
        qa += __shfl_xor_sync(0xffffffffu, od ? q0 : q1, 1);
        wgmma_fence();
#pragma unroll
        for (int k = 0; k < 4; ++k) wgmma_n128(acc, D128(dA0 + (XS + 1) * 1024 + k * 2), D128(dB0 + 10 * 1024 + k * 128), 1);
        wgmma_commit();
        sa += __shfl_xor_sync(0xffffffffu, sa, 2);
        qa += __shfl_xor_sync(0xffffffffu, qa, 2);
        red_add2_p(t < 2, reinterpret_cast<float*>(g_stats + (ep * 4 + layer) * S_ + m0 + wrow0 + gq + t * 8), sa, qa);
        __syncwarp();
        if (lane == 0) mbar_arrive(BA(B_XDONE));
        wgmma_wait<1>();
        if (elected) REL2(CM);
      }
      uint32_t s = 2;
#pragma unroll 1
      for (int i = 2; i < NF; ++i) {
        PROFL(tid_ == 128 && layer == PL + 1, 244 + 2 * i);
        mbar_wait(BA(FM + i), par);
        PROFL(tid_ == 128 && layer == PL + 1, 245 + 2 * i);
        const uint32_t da = dA0 + (XS + s) * 1024, dk = dB0 + s * 2048, dq = dB0 + (9 + s) * 1024;
        wgmma_fence();
#pragma unroll
        for (int k = 0; k < 4; ++k) wgmma_n128(acc, D128(da + k * 2), D128(dq + k * 128), 1);
        wgmma_commit();
        wgmma_wait<1>();
        if (elected) REL2(CM + i - 1);
        wgmma_fence();
#pragma unroll
        for (int k = 0; k < 4; ++k) wgmma_n256(acc, D128(da + k * 2), D128(dk + k * 128), 1);
        wgmma_commit();
        if (++s == 3) s = 0;
      }
#pragma unroll 1
      for (int i = NF; i < 15; ++i) {
        mbar_wait(BA(FM + i), par);
        const uint32_t da = dA0 + (XS + s) * 1024, dk = dB0 + s * 2048;
        wgmma_fence();
#pragma unroll
        for (int k = 0; k < 4; ++k) wgmma_n256(acc, D128(da + k * 2), D128(dk + k * 128), 1);
        wgmma_commit();
        wgmma_wait<1>();
        if (elected) REL2(CM + i - 1);
        if (++s == 3) s = 0;
      }
      {
        const uint64_t dap = desc64(((SB0 + SM_AP) >> 4) + wu * 64, 8), dbp = make_desc_ns(SB0 + SM_BP, 0, 128);
        mbar_wait(BA(B_STAT), par);
        mbar_wait(BA(FM + 15), par);
        PROFT(tid_ == 128, layer * 16 + 9);
        wgmma_fence();
        wgmma_n256_k(acc, dap, dbp, 1);
#pragma unroll
        for (int k = 0; k < 4; ++k) wgmma_n256(acc, D128(dA0 + XS * 1024 + k * 2), D128(dB0 + k * 128), 1);
        wgmma_commit();
        wgmma_wait<1>();
        if (elected) REL2(CM + 14);
        mbar_wait(BA(FT), par);
        wgmma_fence();
        wgmma_n128_k(acc, dap, dbp + 256, 1);
#pragma unroll
        for (int k = 0; k < 4; ++k) wgmma_n128(acc, D128(dA0 + (uint32_t)(TL_A & 15) * 1024 + k * 2), D128(dB0 + (uint32_t)(TL_B & 15) * 1024 + k * 128), 1);
        wgmma_commit();
        wgmma_wait<1>();
        if (elected) REL2(CM + 15);
#pragma unroll
        for (int i = 0; i < 128; ++i) asm volatile("" : "+f"(acc[i]) :: "memory");
      }
    }
    uint32_t of[8][4], o1[4][4];
    {
      PHASE_CTX();
      MMA_CTX();
      PROFT(tid_ == 128, layer * 16 + 1);
      PROFT(lane == 0 && layer == PL, 192 + cw);
      PROFT(tid_ == 128 && layer == PL, 160);
      uint64_t ta = (TL_A >> 4), tw = TL_B >> 4;
      uint32_t da, db, dz = dA0;
      auto sub = [&](int n) {
        const int j = n >> 2, k = n & 3;
        if (k == 0) {
          dz += c.zero;
          da = dz + ((uint32_t)ta & 15) * 1024; db = dB0 + ((uint32_t)tw & 15) * 1024;
          ta >>= 4; tw >>= 4;
          mbar_wait(BA(FT + j), par);
          wgmma_fence();
        }
        wgmma_n128(acc, D128(da + k * 2), D128(db + k * 128), 1);
        if (k == 3) {
          wgmma_commit();
          wgmma_wait<1>();
          if (elected) REL2(CT + j - 1);
        }
      };
      auto run = [&](int j0, int j1) {
#pragma unroll 1
        for (int j = j0; j < j1; ++j) {
          mbar_wait(BA(FT + j), par);
          da = dA0 + ((uint32_t)ta & 15) * 1024; db = dB0 + ((uint32_t)tw & 15) * 1024;
          ta >>= 4; tw >>= 4;
          wgmma_fence();
#pragma unroll
          for (int k = 0; k < 4; ++k) wgmma_n128(acc, D128(da + k * 2), D128(db + k * 128), 1);
          wgmma_commit();
          wgmma_wait<1>();
          if (elected) REL2(CT + j - 1);
        }
        ta = TL_A >> (4 * j1); tw = TL_B >> (4 * j1);
      };
      auto rest = [&](int j0) {
        run(j0, ND);
        wgmma_wait<0>();
        if (elected) REL2(CT + ND - 1);
#pragma unroll
        for (int i = 128; i < 192; ++i) asm volatile("" : "+f"(acc[i]) :: "memory");
      };
      auto wo0 = [&]() {
        wgmma_fence();
        wgmma_n128_rs0(acc, of[0], D128(dB0 + (uint32_t)(WO_B & 15) * 1024));
#pragma unroll
        for (int k = 1; k < 4; ++k) wgmma_n128_rs(acc, of[k], D128(dB0 + (uint32_t)(WO_B & 15) * 1024 + k * 128), 1);
        wgmma_commit();
      };
      const float rs0 = lds_f(sb + SM_RS + (16 + wrow0 + gq) * 4), rs1 = lds_f(sb + SM_RS + (24 + wrow0 + gq) * 4);
#define EPOCH() __float_as_uint(lds_f(sb + SM_EPOCH))
      mbar_wait(BA(CM + 14), par);
      if (par) {
        uint32_t kk[8][4], kp[8][4], vf[2][2][4][4];
        int sn = 4;
        float rj[4];
#pragma unroll
        for (int nt = 0; nt < 4; ++nt) rj[nt] = lds_f(sb + SM_RS + (wrow0 + nt * 8 + 2 * t + (gq & 1)) * 4);
#pragma unroll
        for (int i = 0; i < 4 * BT1; ++i) sub(sn++);
        {
          uint32_t vv[8][4];
#pragma unroll
          for (int jp = 0; jp < 8; ++jp) {
            kk[jp][0] = pack_bf16(acc[8 * jp], acc[8 * jp + 1]); kk[jp][1] = pack_bf16(acc[8 * jp + 4], acc[8 * jp + 5]);
            kk[jp][2] = pack_bf16(acc[8 * jp + 2], acc[8 * jp + 3]); kk[jp][3] = pack_bf16(acc[8 * jp + 6], acc[8 * jp + 7]);
#pragma unroll
            for (int i = 0; i < 4; ++i) vv[jp][i] = pack_bf16(acc[64 + 8 * jp + 2 * i], acc[65 + 8 * jp + 2 * i]);
          }
          if (cw == 7) {
            uint32_t* const hbuf = g_halo + (size_t)(((layer >> 1) * 17 + rb + 1) * 8 + g) * 2048;
#pragma unroll
            for (int jp = 0; jp < 8; ++jp) stg128(hbuf + jp * 128 + lane * 4, kk[jp][0], kk[jp][1], kk[jp][2], kk[jp][3]);
#pragma unroll
            for (int i = 0; i < 32; ++i) hbuf[1024 + (i >> 4) * 512 + (gq + (i & 1) * 8) * 32 + ((((i >> 1) & 7) ^ gq) << 2) + t] = vv[i >> 2][i & 3];
            __syncwarp();
            if (lane == 0) mbar_arrive(BA(B_OF0));
          }
#pragma unroll
          for (int jp = 0; jp < 8; ++jp) {
            sub(sn++);
            stsm_x4(sb + VB + (jp >> 2) * SLOT + rowo + (X ^ ((jp & 3) << 5)), vv[jp][0], vv[jp][1], vv[jp][2], vv[jp][3]);
          }
        }
        PROFT(tid_ == 128, layer * 16 + 2);
        const int e = gq & 1;
        float f0[4], f1[4], b0[4], b1[4];
#pragma unroll
        for (int nt = 0; nt < 4; ++nt) {
          const int kx = nt * 8 + 2 * t + e;
          const bool okk = (m0 + wrow0 + kx) >= 16;
          const int d0 = kx - gq, d1 = d0 - 8;
          const bool m0_ = okk && d0 >= 2 && d0 <= 16, m1_ = okk && d1 >= 2 && d1 <= 16;
          f0[nt] = m0_ ? rj[nt] * rs0 * (0.17677669529663687f * L2E) : 0.f;
          f1[nt] = m1_ ? rj[nt] * rs1 * (0.17677669529663687f * L2E) : 0.f;
          b0[nt] = m0_ ? 0.f : -1e30f; b1[nt] = m1_ ? 0.f : -1e30f;
        }
        uint32_t ko = sb + PH + cw * 4096 + lane * 16;
        mbar_wait(BA(CM + 15), par);
#pragma unroll
        for (int jp = 0; jp < 8; ++jp) {
          sub(sn++);
          sts128(ko + jp * 512, make_uint4(kk[jp][0], kk[jp][1], kk[jp][2], kk[jp][3]));
        }
#pragma unroll
        for (int i = 0; i < 4; ++i) sub(sn++);
        nbar<1, 256>();
        PROFT(tid_ == 128, layer * 16 + 3);
        rest(sn >> 2);
        PROFT(lane == 0 && layer == PL, 200 + cw);
        PROFT(tid_ == 128, layer * 16 + 10);
        if (cw == 0) mbar_wait(BA(B_HALO), (layer >> 1) & 1);
        PROFT(tid_ == 128, layer * 16 + 5);
        const uint32_t vs = sb + (cw ? VB + rowo - 2048 : SM_SD + 4096 + rowo), vst = cw ? SLOT : 2048;
        asm volatile("" : "+r"(ko));
        const uint32_t ka = ko + (cw ? -4096 : SM_SD - PH);
        const uint32_t psel = e ? 0x1054u : 0x5410u;
#pragma unroll
        for (int hp = 0; hp < 2; ++hp) {
#pragma unroll
          for (int i = 4 * hp; i < 4 * hp + 4; ++i) {
            const uint4 u = lds128(ka + i * 512);
            kp[i][0] = u.x; kp[i][1] = u.y; kp[i][2] = u.z; kp[i][3] = u.w;
          }
#pragma unroll
          for (int i = 4 * hp; i < 4 * hp + 4; ++i) {
            ldsm_x4_t(vf[0][i & 1][i >> 1][0], vf[0][i & 1][i >> 1][1], vf[0][i & 1][i >> 1][2], vf[0][i & 1][i >> 1][3], vs + (i >> 2) * vst + (X ^ ((i & 3) << 5)));
            ldsm_x4_t(vf[1][i & 1][i >> 1][0], vf[1][i & 1][i >> 1][1], vf[1][i & 1][i >> 1][2], vf[1][i & 1][i >> 1][3], sb + VB + (i >> 2) * SLOT + rowo + (X ^ ((i & 3) << 5)));
          }
          float l0[2][4], l1[2][4];
#pragma unroll
          for (int h = 0; h < 2; ++h) {
            const int H = 2 * hp + h;
            uint32_t qa[8];
#pragma unroll
            for (int i = 0; i < 8; ++i) qa[i] = pack_bf16(acc[128 + 16 * H + 2 * i], acc[129 + 16 * H + 2 * i]);
#pragma unroll
            for (int nt = 3; nt >= 0; --nt) {
              float sc[4] = {0.f, 0.f, 0.f, 0.f};
#pragma unroll
              for (int ks = 0; ks < 2; ++ks) {
                const uint32_t (&kf)[4] = nt < 2 ? kp[2 * H + ks] : kk[2 * H + ks];
                mma_bf16(sc, qa[4 * ks], qa[4 * ks + 1], qa[4 * ks + 2], qa[4 * ks + 3], kf[2 * (nt & 1)], kf[2 * (nt & 1) + 1]);
              }
              l0[h][nt] = fmaf(e ? sc[1] : sc[0], f0[nt], b0[nt]);
              l1[h][nt] = fmaf(e ? sc[3] : sc[2], f1[nt], b1[nt]);
            }
          }
          float mx0[2], mx1[2], s0[2], s1[2];
#pragma unroll
          for (int h = 0; h < 2; ++h) {
            mx0[h] = fmaxf(fmaxf(l0[h][0], l0[h][1]), l0[h][2]);
            mx1[h] = fmaxf(fmaxf(l1[h][1], l1[h][2]), l1[h][3]);
          }
#pragma unroll
          for (int o = 1; o <= 2; o <<= 1)
#pragma unroll
            for (int h = 0; h < 2; ++h) {
              mx0[h] = fmaxf(mx0[h], __shfl_xor_sync(0xffffffffu, mx0[h], o));
              mx1[h] = fmaxf(mx1[h], __shfl_xor_sync(0xffffffffu, mx1[h], o));
            }
#pragma unroll
          for (int h = 0; h < 2; ++h) {
#pragma unroll
            for (int nt = 0; nt < 3; ++nt) { l0[h][nt] = ex2(l0[h][nt] - mx0[h]); l1[h][nt + 1] = ex2(l1[h][nt + 1] - mx1[h]); }
            s0[h] = (l0[h][0] + l0[h][1]) + l0[h][2];
            s1[h] = (l1[h][1] + l1[h][2]) + l1[h][3];
          }
#pragma unroll
          for (int o = 1; o <= 2; o <<= 1)
#pragma unroll
            for (int h = 0; h < 2; ++h) {
              s0[h] += __shfl_xor_sync(0xffffffffu, s0[h], o);
              s1[h] += __shfl_xor_sync(0xffffffffu, s1[h], o);
            }
          uint32_t ow[2][2][4];
#pragma unroll
          for (int h = 0; h < 2; ++h) {
            const int H = 2 * hp + h;
            uint32_t pl[4], ph[4];
            const float i0 = rcp(s0[h]), i1 = rcp(s1[h]);
#pragma unroll
            for (int nt = 0; nt < 4; ++nt) {
              const uint32_t pk = pack_bf16(nt < 3 ? l0[h][nt] * i0 * rj[nt] : 0.f, nt > 0 ? l1[h][nt] * i1 * rj[nt] : 0.f);
              pl[nt] = nt < 3 ? __byte_perm(pk, 0u, psel) : 0u;
              ph[nt] = nt > 0 ? __byte_perm(pk, 0u, psel + 0x2222u) : 0u;
            }
#pragma unroll
            for (int nj = 0; nj < 4; ++nj) {
              float oa[4] = {0.f, 0.f, 0.f, 0.f};
#pragma unroll
              for (int ks = 0; ks < 2; ++ks)
                mma_bf16(oa, pl[2 * ks], ph[2 * ks], pl[2 * ks + 1], ph[2 * ks + 1], vf[ks][nj >> 1][H][2 * (nj & 1)], vf[ks][nj >> 1][H][2 * (nj & 1) + 1]);
              ow[h][0][nj] = pack_bf16(oa[0], oa[1]); ow[h][1][nj] = pack_bf16(oa[2], oa[3]);
            }
          }
          if (hp == 0) {
#pragma unroll
            for (int i = 0; i < 4; ++i) stg128(g_o + gfr + (i & 1) * 8 * D_ + (i >> 1) * 32, ow[i >> 1][i & 1][0], ow[i >> 1][i & 1][1], ow[i >> 1][i & 1][2], ow[i >> 1][i & 1][3]);
            __syncwarp();
            if (lane == 0) mbar_arrive(BA(B_OH0));
          } else {
#pragma unroll
            for (int i = 0; i < 16; ++i) o1[i >> 2][i & 3] = ow[i >> 3][(i >> 2) & 1][i & 3];
          }
#pragma unroll
          for (int i = 0; i < 16; ++i) of[4 * hp + (i >> 2)][i & 3] = ow[i >> 3][i & 1][(i >> 1) & 3];
          if (!hp) { PROFT(tid_ == 128, layer * 16 + 15); mbar_wait(BA(FW), par); }
        }
      } else {
        float sc[2] = {rs0 * L2E, rs1 * L2E};
        {
          const uint32_t vb = sb + VB + (rowo >> 1), X0 = (lchk ^ ((lane & 7) >> 1)) << 4;
          const uint32_t pb = sb + PH + (t & 1) * SLOT + (wrow0 + gq) * 128 + ((((t & 1) * 4 + (t & 2)) ^ gq) << 4);
          float kva[20], en[32], mx[2][2], mn[2][2];
#define PV(hp, j) acc[32 * (hp) + (j)]
          auto mm = [&](int hp, int j) {
            const int r = (j >> 1) & 1;
            if (j < 4 && !(j & 1)) { mx[hp][r] = PV(hp, j); mn[hp][r] = PV(hp, j); }
            else { mx[hp][r] = fmaxf(mx[hp][r], PV(hp, j)); mn[hp][r] = fminf(mn[hp][r], PV(hp, j)); }
          };
          auto mmx = [&](int hp) {
#pragma unroll
            for (int r = 0; r < 2; ++r) {
              mx[hp][r] = fmaxf(mx[hp][r], __shfl_xor_sync(0xffffffffu, mx[hp][r], 2)) * -sc[r];
              mn[hp][r] = fmaf(fminf(mn[hp][r], __shfl_xor_sync(0xffffffffu, mn[hp][r], 2)), sc[r], mx[hp][r]);
            }
          };
          auto stage = [&](int hp) {
#pragma unroll
            for (int i = 0; i < 20; ++i) asm volatile("" : "+f"(kva[i]) :: "memory");
            nbar_dyn(3 + wu, 128);
            const uint32_t ad = sb + VB + hp * SLOT + wg * 8192 + (2 * wq + ((lane >> 3) & 1)) * 640 + (lane & 7) * 16;
#pragma unroll
            for (int i = 0; i < 2; ++i)
              stsm_x4(ad + (2 * i + lchk) * 128, pack_bf16(kva[8 * i], kva[8 * i + 1]), pack_bf16(kva[8 * i + 2], kva[8 * i + 3]),
                      pack_bf16(kva[8 * i + 4], kva[8 * i + 5]), pack_bf16(kva[8 * i + 6], kva[8 * i + 7]));
            stsm_x2(ad + 512, pack_bf16(kva[16], 0.0625f), pack_bf16(kva[18], 0.0625f));
            fence_async_smem();
            __syncwarp();
            if (lane == 0) mbar_arrive(BA(B_KVDONE));
          };
          int sn = 4;
#pragma unroll
          for (int j = 0; j < 32; ++j) mm(0, j);
          mmx(0);
#pragma unroll
          for (int hp = 0; hp < 2; ++hp) {
            float sp[2] = {0.f, 0.f}, sm[2] = {0.f, 0.f};
#pragma unroll
            for (int j = 0; j < 32; ++j) {
              const int r = (j >> 1) & 1, ns = hp ? SUBS1 : SUBS;
              if ((j * ns) / 32 != ((j + 1) * ns) / 32) {
                sub(sn++);
                if (hp && sn == 4 + SUBS + 4) { stage(0); PROFT(tid_ == 128, layer * 16 + 12); }
              }
              const float x = fmaf(PV(hp, j), sc[r], mx[hp][r]);
              PV(hp, j) = ex2(x); en[j] = ex2(mn[hp][r] - x);
              sp[r] += PV(hp, j); sm[r] += en[j];
              if (hp == 0) {
                mm(1, j);
                if ((j & 3) == 0) {
                  const int jp = 8 + (j >> 2);
                  stsm_x4(vb + ((jp - 8) >> 1) * 8192 + (X0 ^ ((jp & 1) << 5)), pack_bf16(acc[8 * jp], acc[8 * jp + 1]), pack_bf16(acc[8 * jp + 2], acc[8 * jp + 3]),
                          pack_bf16(acc[8 * jp + 4], acc[8 * jp + 5]), pack_bf16(acc[8 * jp + 6], acc[8 * jp + 7]));
                }
              }
            }
#pragma unroll
            for (int r = 0; r < 2; ++r) {
              sp[r] = rcp(sp[r] + __shfl_xor_sync(0xffffffffu, sp[r], 2)) * (r ? rs1 : rs0);
              sm[r] = rcp(sm[r] + __shfl_xor_sync(0xffffffffu, sm[r], 2)) * (r ? rs1 : rs0);
            }
            if (hp == 0) { mmx(1); mbar_wait(BA(CM + 15), par); }
            else { PROFT(tid_ == 128, layer * 16 + 11); nbar<1, 256>(); }
#pragma unroll
            for (int i = 0; i < 4; ++i) {
              const int r = i & 1, d = 16 * (i >> 1) + 2 * r;
              sts128((pb + r * 1024) ^ ((i >> 1) << 4), make_uint4(pack_bf16(PV(hp, d) * sp[r], PV(hp, d + 1) * sp[r]), pack_bf16(PV(hp, d + 4) * sp[r], PV(hp, d + 5) * sp[r]),
                                                                    pack_bf16(PV(hp, d + 8) * sp[r], PV(hp, d + 9) * sp[r]), pack_bf16(PV(hp, d + 12) * sp[r], PV(hp, d + 13) * sp[r])));
              sts128((pb + r * 1024) ^ ((i >> 1) << 4) ^ 64, make_uint4(pack_bf16(en[d] * sm[r], en[d + 1] * sm[r]), pack_bf16(en[d + 4] * sm[r], en[d + 5] * sm[r]),
                                                                         pack_bf16(en[d + 8] * sm[r], en[d + 9] * sm[r]), pack_bf16(en[d + 12] * sm[r], en[d + 13] * sm[r])));
            }
            fence_async_smem();
            nbar<1, 256>();
            const uint32_t dP = dB0 + (PH >> 4) + wu * 1024;
            const uint32_t dV = (dB0 & 0xFFFFu) + ((VB + hp * SLOT) >> 4) + (((SM_SD - VB - hp * SLOT) >> 4) << 16) + wu * (512u - (512u << 16));
            wgmma_fence();
#pragma unroll
            for (int ks = 0; ks < 8; ++ks) wgmma_n40_tt(kva, D128(dP + ks * 128), desc64(dV + ks * 64, 0x80000020u), ks != 0);
            wgmma_commit();
          }
#pragma unroll
          for (int i = 0; i < 4; ++i) sub(sn++);
          stage(1);
          PROFT(tid_ == 128, layer * 16 + 3);
          rest(sn >> 2);
          PROFT(lane == 0 && layer == PL, 200 + cw);
          PROFT(tid_ == 128, layer * 16 + 10);
        }
#define QV(H, i) acc[128 + 16 * (H) + (i)]
        float mx[4][2], mn[4][2];
        uint32_t ph[4][4][4];
        auto mnx = [&](int hp) {
#pragma unroll
          for (int H = 2 * hp; H < 2 * hp + 2; ++H)
#pragma unroll
            for (int r = 0; r < 2; ++r) {
              mx[H][r] = fmaxf(fmaxf(fmaxf(QV(H, 2 * r), QV(H, 2 * r + 1)), fmaxf(QV(H, 4 + 2 * r), QV(H, 5 + 2 * r))),
                               fmaxf(fmaxf(QV(H, 8 + 2 * r), QV(H, 9 + 2 * r)), fmaxf(QV(H, 12 + 2 * r), QV(H, 13 + 2 * r))));
              mn[H][r] = fminf(fminf(fminf(QV(H, 2 * r), QV(H, 2 * r + 1)), fminf(QV(H, 4 + 2 * r), QV(H, 5 + 2 * r))),
                               fminf(fminf(QV(H, 8 + 2 * r), QV(H, 9 + 2 * r)), fminf(QV(H, 12 + 2 * r), QV(H, 13 + 2 * r))));
            }
#pragma unroll
          for (int o = 1; o <= 2; o <<= 1)
#pragma unroll
            for (int H = 2 * hp; H < 2 * hp + 2; ++H)
#pragma unroll
              for (int r = 0; r < 2; ++r) {
                mx[H][r] = fmaxf(mx[H][r], __shfl_xor_sync(0xffffffffu, mx[H][r], o));
                mn[H][r] = fminf(mn[H][r], __shfl_xor_sync(0xffffffffu, mn[H][r], o));
              }
#pragma unroll
          for (int H = 2 * hp; H < 2 * hp + 2; ++H)
#pragma unroll
            for (int r = 0; r < 2; ++r) { mx[H][r] *= -sc[r]; mn[H][r] = fmaf(mn[H][r], sc[r], mx[H][r]); }
        };
        auto fm = [&](int H) {
#pragma unroll
          for (int i = 0; i < 8; ++i) {
            const int r = i & 1;
            const float x0 = fmaf(QV(H, 2 * i), sc[r], mx[H][r]), x1 = fmaf(QV(H, 2 * i + 1), sc[r], mx[H][r]);
            ph[H][i >> 2][i & 3] = pack_bf16(ex2(x0), ex2(x1));
            ph[H][2 + (i >> 2)][i & 3] = pack_bf16(ex2(mn[H][r] - x0), ex2(mn[H][r] - x1));
          }
        };
        mnx(0);
        fm(0); fm(1);
#pragma unroll
        for (int hp = 0; hp < 2; ++hp) {
          if (hp) mbar_wait(BA(FW), par);
          mbar_wait(BA(hp ? B_KVF1 : B_KVF), (layer >> 1) & 1);
          PROFT(tid_ == 128, layer * 16 + (hp ? 4 : 5));
          float oa[4][20];
          wgmma_fence();
#pragma unroll
          for (int s = 0; s < 2; ++s)
#pragma unroll
            for (int v = 0; v < 4; ++v) {
              const int h = v >> 1, s4 = 2 * (v & 1) + s;
              wgmma_n40_rs(oa[v], ph[2 * hp + h][s4], desc64((((SB0 + VB + hp * SLOT) >> 4) | (40u << 16)) + h * 512 + (s4 ^ (2 * h)) * 80, 8), s != 0);
            }
          wgmma_commit();
          if (hp == 0) { mnx(1); wgmma_wait<0>(); }
          else wgmma_wait<0>();
#pragma unroll
          for (int i = 0; i < 20; ++i) asm volatile("" : "+f"(oa[0][i]), "+f"(oa[1][i]), "+f"(oa[2][i]), "+f"(oa[3][i]) :: "memory");
          uint32_t ow[2][2][4];
#pragma unroll
          for (int h = 0; h < 2; ++h)
#pragma unroll
            for (int r = 0; r < 2; ++r) {
              const float a = oa[2 * h + 1][17 + 2 * r], b = oa[2 * h][17 + 2 * r];
              const float id = rcp(fmaf(oa[2 * h][16 + 2 * r], a, fmaf(a, 1e-6f, oa[2 * h + 1][16 + 2 * r]) * b));
              const float fa = a * id, fb = b * id;
#pragma unroll
              for (int j = 0; j < 4; ++j)
                ow[h][r][j] = pack_bf16(fmaf(oa[2 * h][4 * j + 2 * r], fa, oa[2 * h + 1][4 * j + 2 * r] * fb),
                                        fmaf(oa[2 * h][4 * j + 2 * r + 1], fa, oa[2 * h + 1][4 * j + 2 * r + 1] * fb));
            }
#pragma unroll
          for (int i = 0; i < 16; ++i) of[4 * hp + (i >> 2)][i & 3] = ow[i >> 3][i & 1][(i >> 1) & 3];
          if (hp == 0) {
#pragma unroll
            for (int i = 0; i < 4; ++i) stg128(g_o + gfr + (i & 1) * 8 * D_ + (i >> 1) * 32, ow[i >> 1][i & 1][0], ow[i >> 1][i & 1][1], ow[i >> 1][i & 1][2], ow[i >> 1][i & 1][3]);
            __syncwarp();
            if (lane == 0) mbar_arrive(BA(B_OH0));
            PROFT(tid_ == 128 && layer, layer * 16 + 15);
            fm(2); fm(3);
          } else {
#pragma unroll
            for (int i = 0; i < 16; ++i) o1[i >> 2][i & 3] = ow[i >> 3][(i >> 2) & 1][i & 3];
          }
        }
      }
      PROFT(tid_ == 128, layer * 16 + 6);
#pragma unroll
      for (int i = 0; i < 4; ++i) stg128(g_o + gfr + (i & 1) * 8 * D_ + (2 + (i >> 1)) * 32, o1[i][0], o1[i][1], o1[i][2], o1[i][3]);
      __syncwarp();
      if (lane == 0) { mbar_arrive(BA(B_OH1)); if (EF_USED) REL2(B_EF); }
      PROFT(lane == 0 && layer == PL, 208 + cw);
      wo0();
    }
    {
      PHASE_CTX();
      MMA_CTX();
      mbar_wait(BA(FW + 1), par);
      wgmma_fence();
#pragma unroll
      for (int k = 0; k < 4; ++k) wgmma_n128_rs(acc, of[4 + k], D128(dB0 + (uint32_t)((WO_B >> 4) & 15) * 1024 + k * 128), 1);
      wgmma_commit();
      wgmma_wait<1>();
      if (elected) REL2(CW);
      uint64_t ta = WO_A >> 8, tw = WO_B >> 8;
      auto run = [&](int i0, int i1) {
#pragma unroll 1
        for (int i = i0; i < i1; ++i) {
          mbar_wait(BA(FW + i), par);
          PROFL(tid_ == 128 && layer == PL, 160 + i);
          const uint32_t da = dA0 + ((uint32_t)ta & 15) * 1024, db = dB0 + ((uint32_t)tw & 15) * 1024;
          ta >>= 4; tw >>= 4;
          wgmma_fence();
#pragma unroll
          for (int k = 0; k < 4; ++k) wgmma_n128(acc, D128(da + k * 2), D128(db + k * 128), 1);
          wgmma_commit();
          wgmma_wait<1>();
          if (elected) REL2(CW + i - 1);
        }
        ta = WO_A >> (4 * (i1 & 15)); tw = WO_B >> (4 * (i1 & 15));
      };
      run(2, XRAT);
#pragma unroll
      for (int j = 0; j < 8 / XRN; ++j) {
#pragma unroll
        for (int i = j * XRN; i < (j + 1) * XRN; ++i) ldg128((layer ? g_x : c.x0) + gfr + (i & 1) * 8 * D_ + (i >> 1) * 32, xp[i][0], xp[i][1], xp[i][2], xp[i][3]);
        run(XRAT + j, j + 1 < 8 / XRN ? XRAT + j + 1 : 16);
      }
      if (layer == 0) {
#pragma unroll
        for (int o = 1; o <= 2; o <<= 1)
#pragma unroll
          for (int i = 0; i < 16; ++i) {
            const int j = o == 1 ? 2 * (i & 1) : (i & 1);
            uint32_t &a = xp[i >> 1][j], &b = xp[i >> 1][j + o];
            const uint32_t r = __shfl_xor_sync(0xffffffffu, (t & o) ? a : b, o);
            if (t & o) a = r; else b = r;
          }
      }
      if (layer != NLAYERS - 1) mbar_wait(BA(FM), par ^ 1);
      wgmma_wait<0>();
#pragma unroll
      for (int i = 128; i < 192; ++i) asm volatile("" : "+f"(acc[i]) :: "memory");
      if (elected) REL2(CW + 15);
      PROFT(lane == 0 && layer == PL, 216 + cw);
      PROFT(tid_ == 128, layer * 16 + 7);
#pragma unroll
      for (int i = 0; i < 32; ++i)
        xp[i >> 2][i & 3] = add_bf16x2(xp[i >> 2][i & 3], pack_bf16(acc[128 + 16 * (i >> 3) + 4 * (i & 3) + 2 * ((i >> 2) & 1)], acc[129 + 16 * (i >> 3) + 4 * (i & 3) + 2 * ((i >> 2) & 1)]));
      if (layer == NLAYERS - 1) {
#pragma unroll
        for (int i = 0; i < 8; ++i) stsm_x4(sb + (XS + (i >> 2)) * SLOT + (Y ^ ((i & 2) << 5)) + (i & 1) * 1024, xp[i][0], xp[i][1], xp[i][2], xp[i][3]);
        __syncwarp();
        slab_out_half(sb + XS * SLOT, c.out + (size_t)m0 * D_ + g * 128, wrow0, lane);
        slab_out_half(sb + (XS + 1) * SLOT, c.out + (size_t)m0 * D_ + g * 128 + 64, wrow0, lane);
        PROFT(tid_ == 128, layer * 16 + 24);
        break;
      }
#pragma unroll
      for (int i = 0; i < 4; ++i) stg128(g_x + gfr + (i & 1) * 8 * D_ + (i >> 1) * 32, xp[i][0], xp[i][1], xp[i][2], xp[i][3]);
      __syncwarp();
      if (lane == 0) mbar_arrive(BA(B_XH0));
#pragma unroll
      for (int i = 0; i < 16; ++i) xf[i >> 2][i & 3] = xp[2 * (i >> 3) + (i & 1)][(i >> 1) & 3];
      PROFT(tid_ == 128, layer * 16 + 24);
    }
  }
}

__device__ __forceinline__ uint64_t k_order(int o) {
  const uint32_t lo = (1u << (4 * o)) - 1u, h0 = (0xECA86420u & lo) | ((0xECA86420u >> 4) & ~lo);
  return (uint64_t)(2 * o) | ((uint64_t)(2 * o + 1) << 4) | ((uint64_t)(h0 & 0xFFFFFFFu) << 8) | ((uint64_t)((h0 & 0xFFFFFFFu) | 0x1111111u) << 36);
}

__global__ void __cluster_dims__(2, 1, 1) __launch_bounds__(384, 1)
mega_kernel(const __grid_constant__ Maps maps, const __grid_constant__ Ctx c, const bf16* __restrict__ wA, const bf16* __restrict__ wB,
            const bf16* __restrict__ woA, const bf16* __restrict__ woB) {
  if (blockIdx.x - c.boff >= 128u) {
    const unsigned int epoch = ld_relaxed(&g_epoch);
    const int e = (blockIdx.x - c.boff) & 3, tid = threadIdx.x;
    float s[8] = {0.f, 0.f, 0.f, 0.f, 0.f, 0.f, 0.f, 0.f};
    const uint32_t sb = smem_u32(smem_raw), bar = sb + SM_BAR;
    auto issue = [&](int i) {
      mbar_expect_tx(BA(i & 3), 49152);
      bulk_load(sb + (i & 3) * 49152, wB + (size_t)e * 256 * 3072 + i * 24576, 49152, BA(i & 3));
    };
    if (tid == 0) {
      if (SVD) __nanosleep(SVD);
#pragma unroll 1
      for (int i = 0; i < 4; ++i) {
        mbar_init(BA(i), 1);
        fence_async_smem();
        issue(i);
      }
    }
    __syncthreads();
#pragma unroll 1
    for (int i = 0; i < 32; ++i) {
      mbar_wait(BA(i & 3), (i >> 2) & 1);
#pragma unroll 2
      for (int r = 0; r < 8; ++r) {
        const uint4 v = lds128(sb + (i & 3) * 49152 + r * 6144 + tid * 16);
        s[0] += bf_lo(v.x); s[1] += bf_hi(v.x); s[2] += bf_lo(v.y); s[3] += bf_hi(v.y);
        s[4] += bf_lo(v.z); s[5] += bf_hi(v.z); s[6] += bf_lo(v.w); s[7] += bf_hi(v.w);
      }
      __syncthreads();
      if (tid == 0 && i < 28) issue(i + 4);
    }
    float* cd = g_cs + (epoch & 1) * 6144 + 3072 + ((tid >> 4) & 7) * 384 + (tid < 128 ? 256 : (tid >> 7) * 128 - 128) + (tid & 15) * 8;
    red_add4(cd, s[0], s[1], s[2], s[3]);
    red_add4(cd + 4, s[4], s[5], s[6], s[7]);
    __syncthreads();
    if (tid == 0) flag_add(&g_csflag[8].v);
    const int op = (epoch & 1) ^ 1;
    float4* kz = reinterpret_cast<float4*>(g_kv + (size_t)op * (2 * 8 * 10240)) + e * 5120;
#pragma unroll 1
    for (int i = tid; i < 5120; i += 384) kz[i] = make_float4(0.f, 0.f, 0.f, 0.f);
    reinterpret_cast<float4*>(g_cs + op * 6144)[e * 384 + tid] = make_float4(0.f, 0.f, 0.f, 0.f);
#pragma unroll 1
    for (int i = tid; i < 1024; i += 384) reinterpret_cast<float4*>(g_stats + (op * 4 + e) * S_)[i] = make_float4(0.f, 0.f, 0.f, 0.f);
    return;
  }
  const int warp = __shfl_sync(0xffffffffu, threadIdx.x >> 5, 0), lane = threadIdx.x & 31;
  if (smem_u32(smem_raw) != SB0 + ((blockIdx.x & 1) << 24)) __trap();
  uint32_t cx = 0;
  {
  const int cid = (blockIdx.x - c.boff) >> 1, u7 = ((cid - 36) * 37) >> 8, cr = blockIdx.x & 1;
  const int g = cid < 4 ? 4 + cid : cid < 36 ? (cid - 4) >> 3 : 4 + u7, rb = (cid < 4 ? 0 : cid < 36 ? (cid - 4) & 7 : cid - 35 - 7 * u7) * 2 + cr, m0 = rb * 128;
  const uint32_t sb = SB0 + (cr << 24), bar = sb + SM_BAR;
  PROFT(lane == 0 && (warp == 0 || warp == 4), 224 + (warp >> 2) * 8);
  if (warp == 2) {
    if (lane < NMAP) asm volatile("prefetch.tensormap [%0];" ::"l"(&maps.m[lane]) : "memory");
    cx = ld_relaxed(&g_epoch);
  } else if (warp == 3) {
    cx = c_map[cid] + c_wop[lane] + c_wop[NWOP - lane] + c_aop[lane] + c_aop[NAOP - lane] + (uint32_t)(uintptr_t)g_x;
  } else if (warp >= 4 && warp < 8) {
    const int i = threadIdx.x - 128;
    asm volatile("prefetch.global.L2 [%0];" ::"l"(wA + (size_t)((rb & ~1) * 64 + cr * 32 + ((i >> 1) & 31)) * 3072 + (i >> 6) * 1024 + g * 128 + (i & 1) * 64));
  }
  if (warp < 2) {
    const int s = warp, kb = (rb & ~1) + s;
    if (lane == 0) {
      mbar_init(BA(FM + s), 1u);
      mbar_init(BA(B_RAW + warp), 1u);
      mbar_init(BA(warp ? B_X0 : B_KVS0), 1u);
      asm volatile("fence.mbarrier_init.release.cluster;" ::: "memory");
    }
    __syncwarp();
    if (warp == 0) tma_2d_e(sb + SM_SD, &maps.m[MAP_PHI], 0, g * 128, BA(B_RAW));
    else if (W1DL) __nanosleep(W1DL);
#pragma unroll
    for (int j = 0; j < 6; ++j)
      tma_5d_e(sb + (j < 2 ? 2 * s : j < 4 ? 9 + s : 2 * s + 1) * SLOT + (j & 1) * 8192, &maps.m[MAP_WA], (j < 2 ? 1024 : j < 4 ? 0 : 2048) + g * 128 + (j & 1) * 64, 2 * kb,
               BA(j < 4 ? B_RAW + warp : FM + s));
    tma_2d_e(sb + (XS + s) * SLOT, &maps.m[MAP_X0], kb * 64, m0, BA(FM + s));
    expect_tx_e(BA(B_RAW + warp), warp ? 32768 : 32768 + 8192);
    expect_tx_e(BA(FM + s), 32768);
  } else if (warp >= 4 && lane == 0) {
#pragma unroll 1
    for (int i = 2 + (warp - 4) * 13; i < 15 + (warp - 4) * 13; ++i)
      mbar_init(BA(i), 1u << ((i < CM ? 0u : i < B_EF ? 2u : (uint32_t)(BAR_LG >> (4 * ((i - B_EF) & 15)))) & 7u));
    asm volatile("fence.mbarrier_init.release.cluster;" ::: "memory");
  }
  __syncwarp();
  asm volatile("barrier.cluster.arrive.relaxed.aligned;" ::: "memory");
  if (threadIdx.x == 96 + c.zero) sts_f(sb + SM_EPOCH + 4, __uint_as_float(cx));
  PROFT(lane == 0 && (warp == 0 || warp == 4), 225 + (warp >> 2) * 8);
  __syncwarp();
  PROFT(lane == 0 && (warp == 0 || warp == 4), 226 + (warp >> 2) * 8);
  }

  if (warp < 4) {
    asm volatile("setmaxnreg.dec.sync.aligned.u32 40;");
    PROFT(threadIdx.x == 0, 227);
    cluster_wait();
    PROFT(threadIdx.x == 0, 228);
    if (warp == 0 || warp == 3) {
    if (warp == 0) {
      BLK_CTX();
      const unsigned int epoch = __shfl_sync(0xffffffffu, ld_relaxed(&g_epoch), 0), xbase = epoch * NLAYERS;
      (void)xbase;
      const uint64_t ordg = k_order(g);
      if (X0AT) {
        mbar_wait_u(BA(B_RAW + X0AT - 1), 0);
        tma_2d_e(sb + 11 * SLOT, &maps.m[MAP_X0], g * 128, m0, BA(B_X0));
        tma_2d_e(sb + 12 * SLOT, &maps.m[MAP_X0], g * 128 + 64, m0, BA(B_X0));
        expect_tx_e(BA(B_X0), 32768);
      }
#pragma unroll 1
      for (int lp = 0; lp < 2 * NLAYERS; ++lp) {
        const int layer = lp >> 1, n1 = (lp & 1) ? NAOP : NAOP - 14;
        int n = (lp & 1) ? NAOP - 14 : 0;
        const uint64_t ord = lp ? ordg : k_order(rb >> 1);
        uint32_t ready = lp ? 0u : 0xFFFFu, nop = c_aop[n];
        const unsigned int* fl = ((lp & 1) ? g_of : g_xf) + rb * 32;
        const CUtensorMap* tm = &maps.m[(lp & 1) ? MAP_O : lp ? MAP_X : MAP_X0];
        const uint32_t skip = layer ? 1u << 25 : 9u << 22;
        if (lp) mbar_wait_u(BA((lp & 1) ? B_OH0 : B_XH0), ((lp - 1) >> 1) & 1);
#pragma unroll 1
        for (; n < n1; ++n) {
          const uint32_t op = nop;
          nop = c_aop[n + 1];
          const uint32_t kb = (uint32_t)(ord >> ((op >> 2) & 60)) & 15;
          uint32_t dst = sb + (op & 15) * SLOT, kc = kb * 64, fb = bar + ((op >> 5) & 0x3F8), need = ~ready & (1u << kb);
          asm volatile("" : "+r"(dst), "+r"(kc), "+r"(fb), "+r"(need));
          const uint32_t eb = bar + ((op >> 12) & 0x3F8), ep = (layer ^ (op >> 22)) & 1;
          bool fr = op & skip;
          if (need) {
            if (!fr) fr = __all_sync(0xffffffffu, mbar_test_wait(eb, ep));
            PROFT(lane == 0 && (n == 0 || n == NAOP - 14), 64 + layer * 16 + (n ? 2 : 0));
            src_wait<0>(fl, xbase + layer + 1, need, ready, lane);
            fence_async_all();
          }
          if (!fr) mbar_wait_u(eb, ep);
          tma_2d_e(dst, tm, kc, m0, fb);
          PROFT(lane == 0 && (n == 0 || n == NAOP - 14), 64 + layer * 16 + (n ? 3 : 1));
          PROFL(lane == 0 && layer == PL && n >= NAOP - 14, 178 + n - (NAOP - 14));
          PROFL(lane == 0 && layer == PL + 1 && n < 4, 242 + n);
        }
      }
    } else {
      BLK_CTX();
      const unsigned int epoch = __shfl_sync(0xffffffffu, ld_relaxed(&g_epoch), 0), xbase = epoch * NLAYERS;
      (void)xbase;
      const uint64_t ordg = k_order(g);
#pragma unroll 1
      for (int layer = 0; layer < NLAYERS; ++layer) {
        const uint64_t ordq = layer ? ordg : k_order(rb >> 1);
        uint32_t ready = layer ? 0xFFFFu : 0u, nop = c_wop[0];
        const CUtensorMap* tq = &maps.m[(layer & 1) ? MAP_WB : MAP_WF];
        const CUtensorMap* tk = &maps.m[(layer & 1) ? MAP_WB : cr ? MAP_WA : MAP_WF];
        const uint32_t skip = layer ? 1u << 25 : 9u << 22, pm = layer ? 0xE0u : 0u;
        int n = 0;
#pragma unroll 1
        for (; n < NWOP - 16; ++n) {
          const uint32_t op = nop;
          nop = c_wop[n + 1];
          const uint32_t isq = (op >> 23) & 1, fb = bar + ((op >> 5) & 0x3F8);
          const uint32_t kb = (uint32_t)(ordq >> ((op >> 2) & 60)) & 15;
          const CUtensorMap* tm = (isq ? tq : tk) + ((op & pm) ? 1 : 0);
          const uint32_t dst = sb + (op & 15) * SLOT + cr * (isq ? 8192 : SLOT);
          const int col = g * 128 + (isq ? cr * 64 : 1024 + cr * 1024);
          if (layer == 0) {
            if ((op & 0x7E00) == 0) continue;
            const uint32_t need = ((isq || !cr) ? 1u << kb : 0u) | (((op >> 22) & 1) ? 0u : (((op >> 15) & 127) == CM ? 1u : 3u) << (rb & ~1));
            if ((ready & need) != need) {
              src_wait<0>(g_wff + g * 32, epoch + 1, need, ready, lane);
              fence_async_all();
            }
            if ((op & 15) >= 11) mbar_wait_u(BA(B_XT), 0);
          }
          wait_tma_5d_mc(!(op & skip), bar + ((op >> 12) & 0x3F8), (layer ^ (op >> 22)) & 1, dst, tm, col, 2 * kb, fb);
          if (!isq) tma_5d_mc_e(dst + 8192, tm, col + 64, 2 * kb, fb);
          if (op >> 26) expect_tx_e(fb, (op >> 26) * 8192);
          PROFL(lane == 0 && layer == PL + 1 && n < 16, 128 + n);
        }
        const CUtensorMap* to = &maps.m[(layer & 1) ? MAP_WOB : MAP_WOA];
#pragma unroll 1
        for (; n < NWOP; ++n) {
          const uint32_t op = nop;
          nop = c_wop[n + 1];
          const uint32_t fb = bar + ((op >> 5) & 0x3F8), kb = (uint32_t)(ordg >> ((op >> 2) & 60)) & 15;
          if (WH < 16 && n == NWOP - 16 + WH && !(layer & 1)) mbar_wait_u(BA(B_KVS), (layer >> 1) & 1);
          wait_tma_5d_mc(!((op >> 25) & 1), bar + ((op >> 12) & 0x3F8), layer & 1, sb + (op & 15) * SLOT + cr * 8192, to + ((op & 0xE0) ? 1 : 0), g * 128 + cr * 64, 2 * kb, fb);
          expect_tx_e(fb, (op >> 26) * 8192);
          PROFL(lane == 0 && layer == PL, 144 + ((op >> 8) & 127) - FW);
        }
      }
    }
    } else if (warp == 1) {
      BLK_CTX();
      const unsigned int epoch = __shfl_sync(0xffffffffu, ld_relaxed(&g_epoch), 0), xbase = epoch * NLAYERS;
      (void)xbase;
      if (lane == 0) {
        mbar_wait_s(BA(B_WFD), 0);
        PROFT(true, 229);
#pragma unroll 1
        for (int j = 0; j < 4; ++j) tma_store_5d(&maps.m[MAP_WF], sb + (j < 2 ? 2 * cr : 9 + cr) * SLOT + (j & 1) * 8192, (j < 2 ? 1024 : 0) + g * 128 + (j & 1) * 64, 2 * rb);
        bulk_commit();
        bulk_wait0();
        PROFT(true, 230);
        fence_async_all();
        flag_set(g_wff + g * 32 + rb, epoch + 1);
        PROFT(true, 64 + 13);
#pragma unroll 1
        for (int e = 0; e < NLAYERS; ++e) {
          BLK_CTX();
          if (e > 0) {
            mbar_wait_s(BA(B_XH0), (e - 1) & 1);
            PROFT(e == PL + 1, 240);
            flag_set(g_xf + rb * 32 + 2 * g, xbase + e + 1);
            PROFT(e == PL + 1, 241);
          }
          mbar_wait_s(BA(B_XDONE), e & 1);
          PROFT(true, 64 + e * 16 + 4);
          flag_set(g_xf + rb * 32 + 2 * g + 1, xbase + e + 1);
          if (e == 0) {
            flag_add(&g_csflag[g].v);
#pragma unroll 1
            for (int i = 0; i < 4; ++i) {
              mbar_wait_s(BA(CM + PFM + PFS * i), 0);
              l2_prefetch(i < 3 ? wB + (size_t)(i * 128 + bid_) * 8192 : woA + (size_t)bid_ * 8192, 16384);
            }
          }
          if (e == 1) l2_prefetch(woB + (size_t)bid_ * 8192, 16384);
          PROFT(true, 64 + e * 16 + 7);
          if ((e & 1) == 0) {
            bf16* kvl = g_kv + ((size_t)((epoch & 1) * 2 + (e >> 1)) * 8 + g) * 10240;
#pragma unroll 1
            for (int hp = 0; hp < 2; ++hp) {
              mbar_wait_s(BA(B_KVDONE), hp);
#pragma unroll 1
              for (int i = 0; i < 4; ++i) {
                const int ch = (i + (rb >> 2)) & 3;
                bulk_red_add(kvl + hp * 5120 + ch * 1280, sb + VB + hp * SLOT + (ch >> 1) * 8192 + (ch & 1) * 2560, 2560);
                bulk_commit();
              }
              bulk_wait0();
              PROFT(true, 64 + e * 16 + (hp ? 10 : 6));
              fence_async_all();
              flag_add(&g_kvflag[hp * 8 + g].v);
              mbar_arrive(BA(hp ? B_KVS : B_KVS0));
              PROFT(e > 0 && hp, 64 + e * 16 + 8);
            }
          }
          if (e & 1) {
            mbar_wait_s(BA(B_OF0), (e >> 1) & 1);
            flag_set(g_hf + rb * 32 + g, xbase + e + 1);
            if (rb) flag_wait(g_hf + (rb - 1) * 32 + g, xbase + e + 1);
            fence_async_all();
            mbar_expect_tx(BA(B_HALO), 8192);
            bulk_load(sb + SM_SD, g_halo + (size_t)(((e >> 1) * 17 + rb) * 8 + g) * 2048, 8192, BA(B_HALO));
            PROFT(true, 64 + e * 16 + 15);
          }
          mbar_wait_s(BA(B_OH0), e & 1);
          PROFT(e > 0, 64 + e * 16 + 13);
          flag_set(g_of + rb * 32 + 2 * g, xbase + e + 1);
          PROFT(true, 64 + e * 16 + 9);
          mbar_wait_s(BA(B_OH1), e & 1);
          PROFT(true, 64 + e * 16 + 5);
          flag_set(g_of + rb * 32 + 2 * g + 1, xbase + e + 1);
          PROFT(true, 64 + e * 16 + 11);
        }
        if (bid_ == 0) g_epoch = epoch + 1;
      }
    } else {
      BLK_CTX();
      const unsigned int epoch = __shfl_sync(0xffffffffu, cx, 0), xbase = epoch * NLAYERS;
      (void)xbase;
      if (lane < 16) sts_f(sb + SM_RS + lane * 4, 0.f);
#pragma unroll 1
      for (int layer = 0; layer < NLAYERS; ++layer) {
#define HLP_CTX() BLK_CTX(); int lane = threadIdx.x & 31; asm volatile("" : "+r"(lane)); const bool isB = layer & 1, hal = isB && rb > 0; (void)hal;
#pragma unroll 1
        for (int ph = 0; ph < 2; ++ph) {
          HLP_CTX();
          if (ph == (layer == 0)) {
            const float* cs = g_cs + (epoch & 1) * 6144 + g * 384;
            if (layer) mbar_wait_u(BA(CT), (layer - 1) & 1);
            if (layer < 2) {
              if (lane == 0) flag_wait_slow(&g_csflag[isB ? 8 : g].v, isB ? epoch * 4u + 4u : epoch * 16u + 16u);
              __syncwarp();
            }
#pragma unroll 1
            for (int i0 = 0; i0 < 12; i0 += 4) {
              float a[4];
#pragma unroll
              for (int i = 0; i < 4; ++i) a[i] = __ldcg(cs + isB * 3072 + (i0 + i) * 32 + lane);
#pragma unroll
              for (int i = 0; i < 4; ++i) {
                const float c1 = bf16r(a[i]), c2 = bf16r(a[i] - c1), c3 = (a[i] - c1) - c2;
                sts128(sb + SM_BP + ((i0 + i) * 32 + lane) * 16, make_uint4(pack_bf16(c1, c2), pack_bf16(c3, 0.f), 0u, 0u));
              }
            }
          } else {
            uint32_t rdy = 0u;
            mbar_wait_u(BA(CM + 3), layer & 1);
            src_wait<128>(g_xf + rb * 32, xbase + layer + 1, 0xAAAAu, rdy, lane);
            rdy = 0u;
            if (hal) src_wait<128>(g_xf + (rb - 1) * 32, xbase + layer + 1, 0xAAAAu, rdy, lane);
            const float2* sp = g_stats + ((epoch & 1) * 4 + layer) * S_ + m0 + lane;
            float2 u[5];
#pragma unroll
            for (int i = 0; i < 4; ++i) u[i] = __ldcg(sp + i * 32);
            u[4] = __ldcg(sp - (hal ? 16 : 0));
#pragma unroll 1
            for (int i = 0; i < 5; ++i) {
              const float mean = u[0].x * (1.f / D_);
              const float var = fmaxf(fmaf(-u[0].x, mean, u[0].y) * (1.f / D_), 0.f);
              const float sd = bf16r(sqrtf(bf16r(bf16r(var) + 1e-5f)));
              const int R = i * 32 + lane;
              if (i < 4) {
                const float hm = -0.5f * bf16r(mean);
                if (!isB) sts128(sb + SM_SD + R * 64 + ((R >> 1) & 3) * 16, make_uint4(__float_as_uint(sd) >> 16, __float_as_uint(sd) >> 16, __float_as_uint(sd) >> 16, __float_as_uint(sd) >> 16));
                sts128(sb + SM_AP + R * 16, make_uint4(pack_bf16(hm, hm), pack_bf16(hm, 0.f), 0u, 0u));
              }
              if (i < 4 || (hal && lane < 16)) sts_f(sb + SM_RS + (i < 4 ? 16 + R : lane) * 4, __fdividef(1.f, sd));
#pragma unroll
              for (int j = 0; j < 4; ++j) u[j] = u[j + 1];
            }
            PROFT(lane == 0, 64 + layer * 16 + 12);
          }
        }
        HLP_CTX();
        fence_async_smem();
        __syncwarp();
        if (lane == 0) mbar_arrive(BA(B_STAT));
        PROFT(lane == 0, 64 + layer * 16 + 14);
        if (!isB && lane == 0) {
#pragma unroll 1
          for (int hp = 0; hp < 2; ++hp) {
            mbar_wait_s(BA(hp ? B_KVS : B_KVS0), (layer >> 1) & 1);
            flag_wait(&g_kvflag[hp * 8 + g].v, epoch * (16u * ((NLAYERS + 1) / 2)) + 16u * ((layer >> 1) + 1));
            const bf16* kvl = g_kv + ((size_t)((epoch & 1) * 2 + (layer >> 1)) * 8 + g) * 10240 + hp * 5120;
            const uint32_t kb = BA(hp ? B_KVF1 : B_KVF);
            fence_async_all();
            mbar_expect_tx(kb, 10240);
            bulk_load(sb + VB + hp * SLOT, kvl, 5120, kb);
            bulk_load(sb + VB + hp * SLOT + 8192, kvl + 2560, 5120, kb);
            PROFT(hp == 0, 64 + layer * 16 + 15);
          }
        }
        __syncwarp();
      }
    }
    __syncwarp();
    asm volatile("barrier.cluster.arrive.relaxed.aligned;" ::: "memory");
    cluster_wait();
  } else {
    asm volatile("setmaxnreg.inc.sync.aligned.u32 232;");
    PROFT(threadIdx.x == 128, 235);
    cluster_wait();
    PROFT(threadIdx.x == 128, 236);
    consumer(c);
    asm volatile("bar.warp.sync 0xffffffff;\nbarrier.cluster.arrive.relaxed.aligned;\nbarrier.cluster.wait.aligned;\n" ::: "memory");
  }
}

typedef CUresult (*PFN_encodeTiled)(CUtensorMap*, CUtensorMapDataType, cuuint32_t, void*, const cuuint64_t*, const cuuint64_t*,
                                    const cuuint32_t*, const cuuint32_t*, CUtensorMapInterleave, CUtensorMapSwizzle,
                                    CUtensorMapL2promotion, CUtensorMapFloatOOBfill);

static void make_map2(PFN_encodeTiled enc, CUtensorMap* m, const void* ptr, uint64_t cols, uint64_t rows, uint32_t box_c, uint32_t box_r) {
  cuuint64_t dims[2] = {cols, rows};
  cuuint64_t strides[1] = {cols * 2};
  cuuint32_t box[2] = {box_c, box_r};
  cuuint32_t es[2] = {1, 1};
  CUresult r = enc(m, CU_TENSOR_MAP_DATA_TYPE_BFLOAT16, 2, const_cast<void*>(ptr), dims, strides, box, es, CU_TENSOR_MAP_INTERLEAVE_NONE,
                   box_c == 64 ? CU_TENSOR_MAP_SWIZZLE_128B : CU_TENSOR_MAP_SWIZZLE_64B, CU_TENSOR_MAP_L2_PROMOTION_L2_256B, CU_TENSOR_MAP_FLOAT_OOB_FILL_NONE);
  (void)r;
}
static void make_map5(PFN_encodeTiled enc, CUtensorMap* m, const void* ptr, uint64_t cols) {
  for (int p = 0; p < 2; ++p) {
    cuuint64_t dims[5] = {cols, 2, 4, 4, 32};
    cuuint64_t strides[4] = {cols * 2, cols * (p ? 16 : 4), cols * (p ? 4 : 16), cols * 64};
    cuuint32_t box[5] = {64, 2, 4, 4, 2};
    cuuint32_t es[5] = {1, 1, 1, 1, 1};
    CUresult r = enc(m + p, CU_TENSOR_MAP_DATA_TYPE_BFLOAT16, 5, const_cast<void*>(ptr), dims, strides, box, es, CU_TENSOR_MAP_INTERLEAVE_NONE,
                     CU_TENSOR_MAP_SWIZZLE_128B, CU_TENSOR_MAP_L2_PROMOTION_L2_256B, CU_TENSOR_MAP_FLOAT_OOB_FILL_NONE);
    (void)r;
  }
}

extern "C" void kernel_launch(void* const* d_in, const int* in_sizes, int n_in, void* d_out, int out_size) {
  const bf16* A_x = (const bf16*)d_in[0];
  const bf16* A_wqkv = (const bf16*)d_in[1];
  const bf16* A_wphi = (const bf16*)d_in[2];
  const bf16* A_wo = (const bf16*)d_in[3];
  const bf16* B_wqkv = (const bf16*)d_in[5];
  const bf16* B_wo = (const bf16*)d_in[6];
  bf16* out = (bf16*)d_out;

  static PFN_encodeTiled enc = nullptr;
  static bf16 *p_x, *p_o, *p_wf;
  static uint32_t boff;
  if (!enc) {
    void* fn = nullptr; cudaDriverEntryPointQueryResult qr;
    cudaGetDriverEntryPoint("cuTensorMapEncodeTiled", &fn, cudaEnableDefault, &qr);
    enc = (PFN_encodeTiled)fn;
    cudaGetSymbolAddress((void**)&p_x, g_x);
    cudaGetSymbolAddress((void**)&p_o, g_o);
    cudaGetSymbolAddress((void**)&p_wf, g_wf);
    cudaFuncSetAttribute(mega_kernel, cudaFuncAttributeMaxDynamicSharedMemorySize, SM_TOTAL);
    cudaLaunchConfig_t cfg = {};
    cudaLaunchAttribute at; at.id = cudaLaunchAttributeClusterDimension; at.val.clusterDim.x = 2; at.val.clusterDim.y = 1; at.val.clusterDim.z = 1;
    cfg.gridDim = dim3(132); cfg.blockDim = dim3(384); cfg.dynamicSmemBytes = SM_TOTAL; cfg.attrs = &at; cfg.numAttrs = 1;
    int nc = 0;
    if (cudaOccupancyMaxActiveClusters(&nc, mega_kernel, &cfg) != cudaSuccess) { nc = 0; (void)cudaGetLastError(); }
    boff = nc >= 66 ? 0u : 4u;
  }
  Maps maps;
  make_map5(enc, &maps.m[MAP_WF], p_wf, 2048);
  make_map5(enc, &maps.m[MAP_WA], A_wqkv, 3072);
  make_map5(enc, &maps.m[MAP_WB], B_wqkv, 3072);
  make_map5(enc, &maps.m[MAP_WOA], A_wo, 1024);
  make_map5(enc, &maps.m[MAP_WOB], B_wo, 1024);
  make_map2(enc, &maps.m[MAP_X0], A_x, 1024, 2048, 64, 128);
  make_map2(enc, &maps.m[MAP_X], p_x, 1024, 2048, 64, 128);
  make_map2(enc, &maps.m[MAP_O], p_o, 1024, 2048, 64, 128);
  make_map2(enc, &maps.m[MAP_PHI], A_wphi, 32, 1024, 32, 128);
  Ctx c; c.zero = 0u; c.boff = boff; c.x0 = A_x; c.out = out;
  mega_kernel<<<132, 384, SM_TOTAL, cudaStreamPerThread>>>(maps, c, A_wqkv, B_wqkv, A_wo, B_wo);
}
```

```cpp
#include <cuda_runtime.h>
#include <cuda_bf16.h>
#include <cuda.h>
#include <stdint.h>

typedef __nv_bfloat16 bf16;

constexpr int S_ = 2048, D_ = 1024;

struct __align__(128) Flag { unsigned int v; unsigned int pad[31]; };
__device__ __align__(1024) bf16 g_x[S_ * D_];
__device__ __align__(1024) bf16 g_o[S_ * D_];
__device__ __align__(1024) uint32_t g_halo[2 * 17 * 8 * 2048];
__device__ __align__(1024) bf16 g_kv[2 * 2 * 8 * 10240];
__device__ __align__(1024) float2 g_stats[2 * 4 * S_];
__device__ __align__(1024) float g_cs[2 * 2 * 3072];
__device__ __align__(1024) bf16 g_wf[D_ * 2048];
__device__ Flag g_kvflag[16], g_csflag[9];
__device__ __align__(128) unsigned int g_xf[16 * 32], g_of[16 * 32];
__device__ __align__(128) unsigned int g_hf[16 * 32];
__device__ __align__(128) unsigned int g_wff[8 * 32];
__device__ unsigned int g_epoch, g_rot, g_err;
#define PROFT(cond, idx) asm volatile("" ::: "memory")

#define SUSP 20000
__device__ __forceinline__ uint32_t smem_u32(const void* p) { return (uint32_t)__cvta_generic_to_shared(p); }
__device__ __forceinline__ void mbar_init(uint32_t bar, uint32_t count) {
  asm volatile("mbarrier.init.shared::cta.b64 [%0], %1;" ::"r"(bar), "r"(count) : "memory");
}
__device__ __forceinline__ void mbar_expect_tx(uint32_t bar, uint32_t bytes) {
  asm volatile("mbarrier.arrive.expect_tx.shared::cta.b64 _, [%0], %1;" ::"r"(bar), "r"(bytes) : "memory");
}
__device__ __forceinline__ void mbar_arrive(uint32_t bar) {
  asm volatile("mbarrier.arrive.shared::cta.b64 _, [%0];" ::"r"(bar) : "memory");
}
__device__ __forceinline__ bool mbar_try_wait(uint32_t bar, uint32_t parity) {
  uint32_t ok;
  asm volatile("{\n.reg .pred p;\nmbarrier.try_wait.parity.shared::cta.b64 p, [%1], %2;\nselp.b32 %0, 1, 0, p;\n}\n"
               : "=r"(ok) : "r"(bar), "r"(parity) : "memory");
  return ok != 0;
}
__device__ __forceinline__ bool mbar_try_wait_s(uint32_t bar, uint32_t parity) {
  uint32_t ok;
  asm volatile("{\n.reg .pred p;\nmbarrier.try_wait.parity.shared::cta.b64 p, [%1], %2, %3;\nselp.b32 %0, 1, 0, p;\n}\n"
               : "=r"(ok) : "r"(bar), "r"(parity), "r"(SUSP) : "memory");
  return ok != 0;
}
__device__ __forceinline__ void mbar_wait_s(uint32_t bar, uint32_t parity) {
  uint32_t n = 0;
  bool ok;
#pragma unroll 1
  do { ++n; ok = mbar_try_wait_s(bar, parity); } while (!ok && n < (1u << 16));
}
__device__ __forceinline__ bool mbar_test_wait(uint32_t bar, uint32_t parity) {
  uint32_t ok;
  asm volatile("{\n.reg .pred p;\nmbarrier.test_wait.parity.shared::cta.b64 p, [%1], %2;\nselp.b32 %0, 1, 0, p;\n}\n"
               : "=r"(ok) : "r"(bar), "r"(parity) : "memory");
  return ok != 0;
}
__device__ __forceinline__ uint64_t gtimer() {
  uint64_t t; asm volatile("mov.u64 %0, %globaltimer;" : "=l"(t)); return t;
}
__device__ __forceinline__ void mbar_wait(uint32_t bar, uint32_t parity) {
  uint32_t n = 0;
  bool ok;
#pragma unroll 1
  do { ++n; ok = mbar_try_wait(bar, parity); } while (!ok && n < (1u << 22));
}
__device__ __forceinline__ unsigned int ld_acquire(const unsigned int* p) {
  unsigned int v; asm volatile("ld.acquire.gpu.global.u32 %0, [%1];" : "=r"(v) : "l"(p) : "memory"); return v;
}
__device__ __forceinline__ void flag_add(unsigned int* p) {
  asm volatile("red.release.gpu.global.add.u32 [%0], 1;" ::"l"(p) : "memory");
}
__device__ __forceinline__ void flag_set(unsigned int* p, unsigned int v) {
  asm volatile("st.release.gpu.global.u32 [%0], %1;" ::"l"(p), "r"(v) : "memory");
}
template <int SLEEP>
__device__ __forceinline__ void src_wait(const unsigned int* f, unsigned int target, uint32_t need, uint32_t& ready, int lane) {
  uint32_t n = 0;
#pragma unroll 1
  while ((ready & need) != need) {
    const unsigned int v = ld_acquire(f + (lane & 15));
    ready = __ballot_sync(0xffffffffu, (int)(v - target) >= 0);
    if (SLEEP) { if ((ready & need) != need) __nanosleep(SLEEP); }
    if (++n > (1u << 20)) break;
  }
  __syncwarp();
}
__device__ __forceinline__ unsigned int ld_relaxed(const unsigned int* p);
__device__ __forceinline__ unsigned int ld_relaxed(const unsigned int* p) {
  unsigned int v; asm volatile("ld.relaxed.gpu.global.u32 %0, [%1];" : "=r"(v) : "l"(p) : "memory"); return v;
}
template <int SLEEP>
__device__ __forceinline__ void flag_wait_t(const unsigned int* p, unsigned int target) {
  uint32_t n = 0;
#pragma unroll 1
  while ((int)(ld_acquire(p) - target) < 0) {
    if (SLEEP) __nanosleep(SLEEP);
    if (++n > (1u << 20)) break;
  }
}
__device__ __forceinline__ void flag_wait(const unsigned int* p, unsigned int target) { flag_wait_t<0>(p, target); }
__device__ __forceinline__ void flag_wait_slow(const unsigned int* p, unsigned int target) { flag_wait_t<256>(p, target); }
__device__ __forceinline__ void mbar_wait_u(uint32_t bar, uint32_t parity) {
  uint32_t n = 0;
#pragma unroll 1
  while (!__all_sync(0xffffffffu, SUSP ? mbar_try_wait_s(bar, parity) : mbar_try_wait(bar, parity))) {
    if (++n > (SUSP ? 1u << 16 : 1u << 22)) break;
  }
}
__device__ __forceinline__ void expect_tx_e(uint32_t bar, uint32_t bytes) {
  asm volatile("{\n.reg .pred p;\nelect.sync _|p, 0xffffffff;\n@p mbarrier.arrive.expect_tx.shared::cta.b64 _, [%0], %1;\n}\n" ::"r"(bar), "r"(bytes) : "memory");
}
__device__ __forceinline__ void tma_2d_e(uint32_t dst, const CUtensorMap* tm, int c0, int c1, uint32_t bar) {
  asm volatile("{\n.reg .pred p;\nelect.sync _|p, 0xffffffff;\n"
               "@p cp.async.bulk.tensor.2d.shared::cluster.global.mbarrier::complete_tx::bytes [%0], [%1, {%2, %3}], [%4];\n}\n"
               ::"r"(dst), "l"(tm), "r"(c0), "r"(c1), "r"(bar) : "memory");
}
__device__ __forceinline__ void tma_5d_e(uint32_t dst, const CUtensorMap* tm, int c0, int c4, uint32_t bar) {
  asm volatile("{\n.reg .pred p;\nelect.sync _|p, 0xffffffff;\n"
               "@p cp.async.bulk.tensor.5d.shared::cluster.global.mbarrier::complete_tx::bytes [%0], [%1, {%2, %5, %5, %5, %3}], [%4];\n}\n"
               ::"r"(dst), "l"(tm), "r"(c0), "r"(c4), "r"(bar), "r"(0) : "memory");
}
__device__ __forceinline__ void tma_5d_mc_e(uint32_t dst, const CUtensorMap* tm, int c0, int c4, uint32_t bar) {
  asm volatile("{\n.reg .pred p;\nelect.sync _|p, 0xffffffff;\n"
               "@p cp.async.bulk.tensor.5d.shared::cluster.global.mbarrier::complete_tx::bytes.multicast::cluster [%0], [%1, {%2, %6, %6, %6, %3}], [%4], %5;\n}\n"
               ::"r"(dst), "l"(tm), "r"(c0), "r"(c4), "r"(bar), "h"((uint16_t)3), "r"(0) : "memory");
}
__device__ __forceinline__ void wait_tma_5d_mc(bool w, uint32_t eb, uint32_t par, uint32_t dst, const CUtensorMap* tm, int c0, int c4, uint32_t fb) {
  asm volatile("" : "+r"(dst), "+l"(tm), "+r"(c0), "+r"(c4), "+r"(fb));
  if (w) mbar_wait_u(eb, par);
  tma_5d_mc_e(dst, tm, c0, c4, fb);
}
__device__ __forceinline__ void stg128(void* p, uint32_t a, uint32_t b, uint32_t c, uint32_t d) {
  asm volatile("st.global.v4.u32 [%0], {%1,%2,%3,%4};" ::"l"(p), "r"(a), "r"(b), "r"(c), "r"(d) : "memory");
}
__device__ __forceinline__ void stg128_p(bool on, void* p, uint32_t a, uint32_t b, uint32_t c, uint32_t d) {
  asm volatile("{\n.reg .pred p;\nsetp.ne.b32 p, %5, 0;\n@p st.global.v4.u32 [%0], {%1,%2,%3,%4};\n}\n" ::"l"(p), "r"(a), "r"(b), "r"(c), "r"(d), "r"((int)on) : "memory");
}
__device__ __forceinline__ void ldg128(const void* p, uint32_t& a, uint32_t& b, uint32_t& c, uint32_t& d) {
  asm volatile("ld.global.cg.v4.u32 {%0,%1,%2,%3}, [%4];" : "=r"(a), "=r"(b), "=r"(c), "=r"(d) : "l"(p) : "memory");
}
__device__ __forceinline__ void release2c(uint32_t off) {
  asm volatile("mbarrier.arrive.shared::cluster.b64 _, [%0];\nmbarrier.arrive.shared::cluster.b64 _, [%1];" ::"r"(off), "r"(off + (1u << 24)) : "memory");
}
__device__ __forceinline__ void tma_store_5d(const CUtensorMap* tm, uint32_t src, int c0, int c4) {
  asm volatile("cp.async.bulk.tensor.5d.global.shared::cta.bulk_group [%0, {%2, %4, %4, %4, %3}], [%1];"
               ::"l"(tm), "r"(src), "r"(c0), "r"(c4), "r"(0) : "memory");
}
__device__ __forceinline__ void bulk_load(uint32_t dst, const void* src, uint32_t bytes, uint32_t bar) {
  asm volatile("cp.async.bulk.shared::cluster.global.mbarrier::complete_tx::bytes [%0], [%1], %2, [%3];" ::"r"(dst), "l"(src), "r"(bytes), "r"(bar) : "memory");
}
__device__ __forceinline__ void bulk_red_add(void* dst, uint32_t src, uint32_t bytes) {
  asm volatile("cp.reduce.async.bulk.global.shared::cta.bulk_group.add.noftz.bf16 [%0], [%1], %2;" ::"l"(dst), "r"(src), "r"(bytes) : "memory");
}
__device__ __forceinline__ void bulk_commit() { asm volatile("cp.async.bulk.commit_group;" ::: "memory"); }
__device__ __forceinline__ void bulk_wait0() { asm volatile("cp.async.bulk.wait_group 0;" ::: "memory"); }
__device__ __forceinline__ void fence_async_smem() { asm volatile("fence.proxy.async.shared::cta;" ::: "memory"); }
__device__ __forceinline__ void fence_async_all() { asm volatile("fence.proxy.async.global;" ::: "memory"); }
__device__ __forceinline__ void wgmma_fence() { asm volatile("wgmma.fence.sync.aligned;" ::: "memory"); }
__device__ __forceinline__ void wgmma_commit() { asm volatile("wgmma.commit_group.sync.aligned;" ::: "memory"); }
template <int N> __device__ __forceinline__ void wgmma_wait() { asm volatile("wgmma.wait_group.sync.aligned %0;" ::"n"(N) : "memory"); }
__device__ __forceinline__ void cluster_wait() { asm volatile("barrier.cluster.wait.acquire.aligned;" ::: "memory"); }
template <int ID, int N> __device__ __forceinline__ void nbar() { asm volatile("bar.sync %0, %1;" ::"n"(ID), "n"(N) : "memory"); }
__device__ __forceinline__ uint64_t desc64(uint32_t lo, uint32_t hi) { return (uint64_t)lo | ((uint64_t)hi << 32); }
__device__ __forceinline__ uint32_t pack_bf16(float lo, float hi) {
  uint32_t r; asm("cvt.rn.bf16x2.f32 %0, %1, %2;" : "=r"(r) : "f"(hi), "f"(lo)); return r;
}
__device__ __forceinline__ uint32_t add_bf16x2(uint32_t a, uint32_t b) {
  uint32_t r; asm("add.rn.bf16x2 %0, %1, %2;" : "=r"(r) : "r"(a), "r"(b)); return r;
}
__device__ __forceinline__ float bf16r(float x) { return __bfloat162float(__float2bfloat16_rn(x)); }
__device__ __forceinline__ float bf_lo(uint32_t u) { return __uint_as_float(u << 16); }
__device__ __forceinline__ float bf_hi(uint32_t u) { return __uint_as_float(u & 0xFFFF0000u); }
__device__ __forceinline__ float ex2(float x) { float r; asm("ex2.approx.ftz.f32 %0, %1;" : "=f"(r) : "f"(x)); return r; }
__device__ __forceinline__ float rcp(float x) { float r; asm("rcp.approx.ftz.f32 %0, %1;" : "=f"(r) : "f"(x)); return r; }
__device__ __forceinline__ void mma_bf16(float (&d)[4], uint32_t a0, uint32_t a1, uint32_t a2, uint32_t a3, uint32_t b0, uint32_t b1) {
  asm("mma.sync.aligned.m16n8k16.row.col.f32.bf16.bf16.f32 {%0,%1,%2,%3}, {%4,%5,%6,%7}, {%8,%9}, {%0,%1,%2,%3};"
               : "+f"(d[0]), "+f"(d[1]), "+f"(d[2]), "+f"(d[3]) : "r"(a0), "r"(a1), "r"(a2), "r"(a3), "r"(b0), "r"(b1));
}
__device__ __forceinline__ void ldsm_x4(uint32_t& r0, uint32_t& r1, uint32_t& r2, uint32_t& r3, uint32_t addr) {
  asm volatile("ldmatrix.sync.aligned.m8n8.x4.shared.b16 {%0,%1,%2,%3}, [%4];"
               : "=r"(r0), "=r"(r1), "=r"(r2), "=r"(r3) : "r"(addr) : "memory");
}
__device__ __forceinline__ void ldsm_x4_t(uint32_t& r0, uint32_t& r1, uint32_t& r2, uint32_t& r3, uint32_t addr) {
  asm volatile("ldmatrix.sync.aligned.m8n8.x4.trans.shared.b16 {%0,%1,%2,%3}, [%4];"
               : "=r"(r0), "=r"(r1), "=r"(r2), "=r"(r3) : "r"(addr) : "memory");
}
__device__ __forceinline__ void stsm_x4(uint32_t addr, uint32_t r0, uint32_t r1, uint32_t r2, uint32_t r3) {
  asm volatile("stmatrix.sync.aligned.m8n8.x4.shared.b16 [%0], {%1,%2,%3,%4};"
               ::"r"(addr), "r"(r0), "r"(r1), "r"(r2), "r"(r3) : "memory");
}
__device__ __forceinline__ void stsm_x2(uint32_t addr, uint32_t r0, uint32_t r1) {
  asm volatile("stmatrix.sync.aligned.m8n8.x2.shared.b16 [%0], {%1,%2};" ::"r"(addr), "r"(r0), "r"(r1) : "memory");
}
__device__ __forceinline__ uint4 lds128(uint32_t addr) {
  uint4 v; asm volatile("ld.shared.v4.b32 {%0,%1,%2,%3}, [%4];" : "=r"(v.x), "=r"(v.y), "=r"(v.z), "=r"(v.w) : "r"(addr) : "memory"); return v;
}
__device__ __forceinline__ void sts128(uint32_t addr, uint4 v) {
  asm volatile("st.shared.v4.b32 [%0], {%1,%2,%3,%4};" ::"r"(addr), "r"(v.x), "r"(v.y), "r"(v.z), "r"(v.w) : "memory");
}
__device__ __forceinline__ float lds_f(uint32_t addr) {
  float v; asm volatile("ld.shared.f32 %0, [%1];" : "=f"(v) : "r"(addr) : "memory"); return v;
}
__device__ __forceinline__ void nbar_dyn(int id, int n) { asm volatile("bar.sync %0, %1;" ::"r"(id), "r"(n) : "memory"); }
__device__ __forceinline__ uint64_t make_desc_ns(uint32_t addr, uint32_t lbo_bytes, uint32_t sbo_bytes) {
  return (uint64_t)((addr & 0x3FFFF) >> 4) | ((uint64_t)(lbo_bytes >> 4) << 16) | ((uint64_t)(sbo_bytes >> 4) << 32);
}
__device__ __forceinline__ void sts_f(uint32_t addr, float v) { asm volatile("st.shared.f32 [%0], %1;" ::"r"(addr), "f"(v) : "memory"); }
__device__ __forceinline__ void sts64(uint32_t addr, uint32_t a, uint32_t b) {
  asm volatile("st.shared.v2.b32 [%0], {%1,%2};" ::"r"(addr), "r"(a), "r"(b) : "memory");
}
__device__ __forceinline__ void sts_f2(uint32_t addr, float a, float b) {
  asm volatile("st.shared.v2.f32 [%0], {%1,%2};" ::"r"(addr), "f"(a), "f"(b) : "memory");
}
__device__ __forceinline__ void red_add2_p(bool on, float* p, float a, float b) {
  asm volatile("{\n.reg .pred p;\nsetp.ne.b32 p, %3, 0;\n@p red.global.add.v2.f32 [%0], {%1,%2};\n}\n" ::"l"(p), "f"(a), "f"(b), "r"((int)on) : "memory");
}
__device__ __forceinline__ void red_add4(float* p, float a, float b, float c, float d) {
  asm volatile("red.global.add.v4.f32 [%0], {%1,%2,%3,%4};" ::"l"(p), "f"(a), "f"(b), "f"(c), "f"(d) : "memory");
}
__device__ __forceinline__ void red_add1(float* p, float a) {
  asm volatile("red.global.add.f32 [%0], %1;" ::"l"(p), "f"(a) : "memory");
}
__device__ __forceinline__ void l2_prefetch(const void* p, uint32_t bytes) {
  asm volatile("cp.async.bulk.prefetch.L2.global [%0], %1;" ::"l"(p), "r"(bytes) : "memory");
}

__device__ __forceinline__ void wgmma_n256(float (&d)[192], uint64_t da, uint64_t db, int scale_d) {
  asm volatile("{\n.reg .pred p;\nsetp.ne.b32 p, %130, 0;\n"
    "wgmma.mma_async.sync.aligned.m64n256k16.f32.bf16.bf16 {%0, %1, %2, %3, %4, %5, %6, %7, %8, %9, %10, %11, %12, %13, %14, %15, %16, %17, %18, %19, %20, %21, %22, %23, %24, %25, %26, %27, %28, %29, %30, %31, %32, %33, %34, %35, %36, %37, %38, %39, %40, %41, %42, %43, %44, %45, %46, %47, %48, %49, %50, %51, %52, %53, %54, %55, %56, %57, %58, %59, %60, %61, %62, %63, %64, %65, %66, %67, %68, %69, %70, %71, %72, %73, %74, %75, %76, %77, %78, %79, %80, %81, %82, %83, %84, %85, %86, %87, %88, %89, %90, %91, %92, %93, %94, %95, %96, %97, %98, %99, %100, %101, %102, %103, %104, %105, %106, %107, %108, %109, %110, %111, %112, %113, %114, %115, %116, %117, %118, %119, %120, %121, %122, %123, %124, %125, %126, %127}, %128, %129, p, 1, 1, 0, 1;\n}\n"
    : "+f"(d[0]), "+f"(d[1]), "+f"(d[2]), "+f"(d[3]), "+f"(d[4]), "+f"(d[5]), "+f"(d[6]), "+f"(d[7]), "+f"(d[8]), "+f"(d[9]), "+f"(d[10]), "+f"(d[11]), "+f"(d[12]), "+f"(d[13]), "+f"(d[14]), "+f"(d[15]), "+f"(d[16]), "+f"(d[17]), "+f"(d[18]), "+f"(d[19]), "+f"(d[20]), "+f"(d[21]), "+f"(d[22]), "+f"(d[23]), "+f"(d[24]), "+f"(d[25]), "+f"(d[26]), "+f"(d[27]), "+f"(d[28]), "+f"(d[29]), "+f"(d[30]), "+f"(d[31]), "+f"(d[32]), "+f"(d[33]), "+f"(d[34]), "+f"(d[35]), "+f"(d[36]), "+f"(d[37]), "+f"(d[38]), "+f"(d[39]), "+f"(d[40]), "+f"(d[41]), "+f"(d[42]), "+f"(d[43]), "+f"(d[44]), "+f"(d[45]), "+f"(d[46]), "+f"(d[47]), "+f"(d[48]), "+f"(d[49]), "+f"(d[50]), "+f"(d[51]), "+f"(d[52]), "+f"(d[53]), "+f"(d[54]), "+f"(d[55]), "+f"(d[56]), "+f"(d[57]), "+f"(d[58]), "+f"(d[59]), "+f"(d[60]), "+f"(d[61]), "+f"(d[62]), "+f"(d[63]), "+f"(d[64]), "+f"(d[65]), "+f"(d[66]), "+f"(d[67]), "+f"(d[68]), "+f"(d[69]), "+f"(d[70]), "+f"(d[71]), "+f"(d[72]), "+f"(d[73]), "+f"(d[74]), "+f"(d[75]), "+f"(d[76]), "+f"(d[77]), "+f"(d[78]), "+f"(d[79]), "+f"(d[80]), "+f"(d[81]), "+f"(d[82]), "+f"(d[83]), "+f"(d[84]), "+f"(d[85]), "+f"(d[86]), "+f"(d[87]), "+f"(d[88]), "+f"(d[89]), "+f"(d[90]), "+f"(d[91]), "+f"(d[92]), "+f"(d[93]), "+f"(d[94]), "+f"(d[95]), "+f"(d[96]), "+f"(d[97]), "+f"(d[98]), "+f"(d[99]), "+f"(d[100]), "+f"(d[101]), "+f"(d[102]), "+f"(d[103]), "+f"(d[104]), "+f"(d[105]), "+f"(d[106]), "+f"(d[107]), "+f"(d[108]), "+f"(d[109]), "+f"(d[110]), "+f"(d[111]), "+f"(d[112]), "+f"(d[113]), "+f"(d[114]), "+f"(d[115]), "+f"(d[116]), "+f"(d[117]), "+f"(d[118]), "+f"(d[119]), "+f"(d[120]), "+f"(d[121]), "+f"(d[122]), "+f"(d[123]), "+f"(d[124]), "+f"(d[125]), "+f"(d[126]), "+f"(d[127])
    : "l"(da), "l"(db), "r"(scale_d));
}
__device__ __forceinline__ void wgmma_n128(float (&d)[192], uint64_t da, uint64_t db, int scale_d) {
  asm volatile("{\n.reg .pred p;\nsetp.ne.b32 p, %66, 0;\n"
    "wgmma.mma_async.sync.aligned.m64n128k16.f32.bf16.bf16 {%0, %1, %2, %3, %4, %5, %6, %7, %8, %9, %10, %11, %12, %13, %14, %15, %16, %17, %18, %19, %20, %21, %22, %23, %24, %25, %26, %27, %28, %29, %30, %31, %32, %33, %34, %35, %36, %37, %38, %39, %40, %41, %42, %43, %44, %45, %46, %47, %48, %49, %50, %51, %52, %53, %54, %55, %56, %57, %58, %59, %60, %61, %62, %63}, %64, %65, p, 1, 1, 0, 1;\n}\n"
    : "+f"(d[128]), "+f"(d[129]), "+f"(d[130]), "+f"(d[131]), "+f"(d[132]), "+f"(d[133]), "+f"(d[134]), "+f"(d[135]), "+f"(d[136]), "+f"(d[137]), "+f"(d[138]), "+f"(d[139]), "+f"(d[140]), "+f"(d[141]), "+f"(d[142]), "+f"(d[143]), "+f"(d[144]), "+f"(d[145]), "+f"(d[146]), "+f"(d[147]), "+f"(d[148]), "+f"(d[149]), "+f"(d[150]), "+f"(d[151]), "+f"(d[152]), "+f"(d[153]), "+f"(d[154]), "+f"(d[155]), "+f"(d[156]), "+f"(d[157]), "+f"(d[158]), "+f"(d[159]), "+f"(d[160]), "+f"(d[161]), "+f"(d[162]), "+f"(d[163]), "+f"(d[164]), "+f"(d[165]), "+f"(d[166]), "+f"(d[167]), "+f"(d[168]), "+f"(d[169]), "+f"(d[170]), "+f"(d[171]), "+f"(d[172]), "+f"(d[173]), "+f"(d[174]), "+f"(d[175]), "+f"(d[176]), "+f"(d[177]), "+f"(d[178]), "+f"(d[179]), "+f"(d[180]), "+f"(d[181]), "+f"(d[182]), "+f"(d[183]), "+f"(d[184]), "+f"(d[185]), "+f"(d[186]), "+f"(d[187]), "+f"(d[188]), "+f"(d[189]), "+f"(d[190]), "+f"(d[191])
    : "l"(da), "l"(db), "r"(scale_d));
}
__device__ __forceinline__ void wgmma_n256_k(float (&d)[192], uint64_t da, uint64_t db, int scale_d) {
  asm volatile("{\n.reg .pred p;\nsetp.ne.b32 p, %130, 0;\n"
    "wgmma.mma_async.sync.aligned.m64n256k16.f32.bf16.bf16 {%0, %1, %2, %3, %4, %5, %6, %7, %8, %9, %10, %11, %12, %13, %14, %15, %16, %17, %18, %19, %20, %21, %22, %23, %24, %25, %26, %27, %28, %29, %30, %31, %32, %33, %34, %35, %36, %37, %38, %39, %40, %41, %42, %43, %44, %45, %46, %47, %48, %49, %50, %51, %52, %53, %54, %55, %56, %57, %58, %59, %60, %61, %62, %63, %64, %65, %66, %67, %68, %69, %70, %71, %72, %73, %74, %75, %76, %77, %78, %79, %80, %81, %82, %83, %84, %85, %86, %87, %88, %89, %90, %91, %92, %93, %94, %95, %96, %97, %98, %99, %100, %101, %102, %103, %104, %105, %106, %107, %108, %109, %110, %111, %112, %113, %114, %115, %116, %117, %118, %119, %120, %121, %122, %123, %124, %125, %126, %127}, %128, %129, p, 1, 1, 0, 0;\n}\n"
    : "+f"(d[0]), "+f"(d[1]), "+f"(d[2]), "+f"(d[3]), "+f"(d[4]), "+f"(d[5]), "+f"(d[6]), "+f"(d[7]), "+f"(d[8]), "+f"(d[9]), "+f"(d[10]), "+f"(d[11]), "+f"(d[12]), "+f"(d[13]), "+f"(d[14]), "+f"(d[15]), "+f"(d[16]), "+f"(d[17]), "+f"(d[18]), "+f"(d[19]), "+f"(d[20]), "+f"(d[21]), "+f"(d[22]), "+f"(d[23]), "+f"(d[24]), "+f"(d[25]), "+f"(d[26]), "+f"(d[27]), "+f"(d[28]), "+f"(d[29]), "+f"(d[30]), "+f"(d[31]), "+f"(d[32]), "+f"(d[33]), "+f"(d[34]), "+f"(d[35]), "+f"(d[36]), "+f"(d[37]), "+f"(d[38]), "+f"(d[39]), "+f"(d[40]), "+f"(d[41]), "+f"(d[42]), "+f"(d[43]), "+f"(d[44]), "+f"(d[45]), "+f"(d[46]), "+f"(d[47]), "+f"(d[48]), "+f"(d[49]), "+f"(d[50]), "+f"(d[51]), "+f"(d[52]), "+f"(d[53]), "+f"(d[54]), "+f"(d[55]), "+f"(d[56]), "+f"(d[57]), "+f"(d[58]), "+f"(d[59]), "+f"(d[60]), "+f"(d[61]), "+f"(d[62]), "+f"(d[63]), "+f"(d[64]), "+f"(d[65]), "+f"(d[66]), "+f"(d[67]), "+f"(d[68]), "+f"(d[69]), "+f"(d[70]), "+f"(d[71]), "+f"(d[72]), "+f"(d[73]), "+f"(d[74]), "+f"(d[75]), "+f"(d[76]), "+f"(d[77]), "+f"(d[78]), "+f"(d[79]), "+f"(d[80]), "+f"(d[81]), "+f"(d[82]), "+f"(d[83]), "+f"(d[84]), "+f"(d[85]), "+f"(d[86]), "+f"(d[87]), "+f"(d[88]), "+f"(d[89]), "+f"(d[90]), "+f"(d[91]), "+f"(d[92]), "+f"(d[93]), "+f"(d[94]), "+f"(d[95]), "+f"(d[96]), "+f"(d[97]), "+f"(d[98]), "+f"(d[99]), "+f"(d[100]), "+f"(d[101]), "+f"(d[102]), "+f"(d[103]), "+f"(d[104]), "+f"(d[105]), "+f"(d[106]), "+f"(d[107]), "+f"(d[108]), "+f"(d[109]), "+f"(d[110]), "+f"(d[111]), "+f"(d[112]), "+f"(d[113]), "+f"(d[114]), "+f"(d[115]), "+f"(d[116]), "+f"(d[117]), "+f"(d[118]), "+f"(d[119]), "+f"(d[120]), "+f"(d[121]), "+f"(d[122]), "+f"(d[123]), "+f"(d[124]), "+f"(d[125]), "+f"(d[126]), "+f"(d[127])
    : "l"(da), "l"(db), "r"(scale_d));
}
__device__ __forceinline__ void wgmma_n128_k(float (&d)[192], uint64_t da, uint64_t db, int scale_d) {
  asm volatile("{\n.reg .pred p;\nsetp.ne.b32 p, %66, 0;\n"
    "wgmma.mma_async.sync.aligned.m64n128k16.f32.bf16.bf16 {%0, %1, %2, %3, %4, %5, %6, %7, %8, %9, %10, %11, %12, %13, %14, %15, %16, %17, %18, %19, %20, %21, %22, %23, %24, %25, %26, %27, %28, %29, %30, %31, %32, %33, %34, %35, %36, %37, %38, %39, %40, %41, %42, %43, %44, %45, %46, %47, %48, %49, %50, %51, %52, %53, %54, %55, %56, %57, %58, %59, %60, %61, %62, %63}, %64, %65, p, 1, 1, 0, 0;\n}\n"
    : "+f"(d[128]), "+f"(d[129]), "+f"(d[130]), "+f"(d[131]), "+f"(d[132]), "+f"(d[133]), "+f"(d[134]), "+f"(d[135]), "+f"(d[136]), "+f"(d[137]), "+f"(d[138]), "+f"(d[139]), "+f"(d[140]), "+f"(d[141]), "+f"(d[142]), "+f"(d[143]), "+f"(d[144]), "+f"(d[145]), "+f"(d[146]), "+f"(d[147]), "+f"(d[148]), "+f"(d[149]), "+f"(d[150]), "+f"(d[151]), "+f"(d[152]), "+f"(d[153]), "+f"(d[154]), "+f"(d[155]), "+f"(d[156]), "+f"(d[157]), "+f"(d[158]), "+f"(d[159]), "+f"(d[160]), "+f"(d[161]), "+f"(d[162]), "+f"(d[163]), "+f"(d[164]), "+f"(d[165]), "+f"(d[166]), "+f"(d[167]), "+f"(d[168]), "+f"(d[169]), "+f"(d[170]), "+f"(d[171]), "+f"(d[172]), "+f"(d[173]), "+f"(d[174]), "+f"(d[175]), "+f"(d[176]), "+f"(d[177]), "+f"(d[178]), "+f"(d[179]), "+f"(d[180]), "+f"(d[181]), "+f"(d[182]), "+f"(d[183]), "+f"(d[184]), "+f"(d[185]), "+f"(d[186]), "+f"(d[187]), "+f"(d[188]), "+f"(d[189]), "+f"(d[190]), "+f"(d[191])
    : "l"(da), "l"(db), "r"(scale_d));
}
__device__ __forceinline__ void wgmma_n40_tt(float (&d)[20], uint64_t da, uint64_t db, int scale_d) {
  asm volatile("{\n.reg .pred p;\nsetp.ne.b32 p, %22, 0;\n"
    "wgmma.mma_async.sync.aligned.m64n40k16.f32.bf16.bf16 {%0, %1, %2, %3, %4, %5, %6, %7, %8, %9, %10, %11, %12, %13, %14, %15, %16, %17, %18, %19}, %20, %21, p, 1, 1, 1, 1;\n}\n"
    : "+f"(d[0]), "+f"(d[1]), "+f"(d[2]), "+f"(d[3]), "+f"(d[4]), "+f"(d[5]), "+f"(d[6]), "+f"(d[7]), "+f"(d[8]), "+f"(d[9]), "+f"(d[10]), "+f"(d[11]), "+f"(d[12]), "+f"(d[13]), "+f"(d[14]), "+f"(d[15]), "+f"(d[16]), "+f"(d[17]), "+f"(d[18]), "+f"(d[19])
    : "l"(da), "l"(db), "r"(scale_d));
}
__device__ __forceinline__ void wgmma_n40_rs(float (&d)[20], const uint32_t (&a)[4], uint64_t db, int scale_d) {
  asm volatile("{\n.reg .pred p;\nsetp.ne.b32 p, %25, 0;\n"
    "wgmma.mma_async.sync.aligned.m64n40k16.f32.bf16.bf16 {%0, %1, %2, %3, %4, %5, %6, %7, %8, %9, %10, %11, %12, %13, %14, %15, %16, %17, %18, %19}, {%20, %21, %22, %23}, %24, p, 1, 1, 1;\n}\n"
    : "+f"(d[0]), "+f"(d[1]), "+f"(d[2]), "+f"(d[3]), "+f"(d[4]), "+f"(d[5]), "+f"(d[6]), "+f"(d[7]), "+f"(d[8]), "+f"(d[9]), "+f"(d[10]), "+f"(d[11]), "+f"(d[12]), "+f"(d[13]), "+f"(d[14]), "+f"(d[15]), "+f"(d[16]), "+f"(d[17]), "+f"(d[18]), "+f"(d[19])
    : "r"(a[0]), "r"(a[1]), "r"(a[2]), "r"(a[3]), "l"(db), "r"(scale_d));
}
__device__ __forceinline__ void wgmma_n128_0(float (&d)[192], uint64_t da, uint64_t db) {
  asm volatile("{\n.reg .pred p;\nsetp.ne.b32 p, 0, 0;\n"
    "wgmma.mma_async.sync.aligned.m64n128k16.f32.bf16.bf16 {%0, %1, %2, %3, %4, %5, %6, %7, %8, %9, %10, %11, %12, %13, %14, %15, %16, %17, %18, %19, %20, %21, %22, %23, %24, %25, %26, %27, %28, %29, %30, %31, %32, %33, %34, %35, %36, %37, %38, %39, %40, %41, %42, %43, %44, %45, %46, %47, %48, %49, %50, %51, %52, %53, %54, %55, %56, %57, %58, %59, %60, %61, %62, %63}, %64, %65, p, 1, 1, 0, 1;\n}\n"
    : "=f"(d[128]), "=f"(d[129]), "=f"(d[130]), "=f"(d[131]), "=f"(d[132]), "=f"(d[133]), "=f"(d[134]), "=f"(d[135]), "=f"(d[136]), "=f"(d[137]), "=f"(d[138]), "=f"(d[139]), "=f"(d[140]), "=f"(d[141]), "=f"(d[142]), "=f"(d[143]), "=f"(d[144]), "=f"(d[145]), "=f"(d[146]), "=f"(d[147]), "=f"(d[148]), "=f"(d[149]), "=f"(d[150]), "=f"(d[151]), "=f"(d[152]), "=f"(d[153]), "=f"(d[154]), "=f"(d[155]), "=f"(d[156]), "=f"(d[157]), "=f"(d[158]), "=f"(d[159]), "=f"(d[160]), "=f"(d[161]), "=f"(d[162]), "=f"(d[163]), "=f"(d[164]), "=f"(d[165]), "=f"(d[166]), "=f"(d[167]), "=f"(d[168]), "=f"(d[169]), "=f"(d[170]), "=f"(d[171]), "=f"(d[172]), "=f"(d[173]), "=f"(d[174]), "=f"(d[175]), "=f"(d[176]), "=f"(d[177]), "=f"(d[178]), "=f"(d[179]), "=f"(d[180]), "=f"(d[181]), "=f"(d[182]), "=f"(d[183]), "=f"(d[184]), "=f"(d[185]), "=f"(d[186]), "=f"(d[187]), "=f"(d[188]), "=f"(d[189]), "=f"(d[190]), "=f"(d[191])
    : "l"(da), "l"(db));
}
__device__ __forceinline__ void wgmma_n128_rs(float (&d)[192], const uint32_t (&a)[4], uint64_t db, int scale_d) {
  asm volatile("{\n.reg .pred p;\nsetp.ne.b32 p, %69, 0;\n"
    "wgmma.mma_async.sync.aligned.m64n128k16.f32.bf16.bf16 {%0, %1, %2, %3, %4, %5, %6, %7, %8, %9, %10, %11, %12, %13, %14, %15, %16, %17, %18, %19, %20, %21, %22, %23, %24, %25, %26, %27, %28, %29, %30, %31, %32, %33, %34, %35, %36, %37, %38, %39, %40, %41, %42, %43, %44, %45, %46, %47, %48, %49, %50, %51, %52, %53, %54, %55, %56, %57, %58, %59, %60, %61, %62, %63}, {%64, %65, %66, %67}, %68, p, 1, 1, 1;\n}\n"
    : "+f"(d[128]), "+f"(d[129]), "+f"(d[130]), "+f"(d[131]), "+f"(d[132]), "+f"(d[133]), "+f"(d[134]), "+f"(d[135]), "+f"(d[136]), "+f"(d[137]), "+f"(d[138]), "+f"(d[139]), "+f"(d[140]), "+f"(d[141]), "+f"(d[142]), "+f"(d[143]), "+f"(d[144]), "+f"(d[145]), "+f"(d[146]), "+f"(d[147]), "+f"(d[148]), "+f"(d[149]), "+f"(d[150]), "+f"(d[151]), "+f"(d[152]), "+f"(d[153]), "+f"(d[154]), "+f"(d[155]), "+f"(d[156]), "+f"(d[157]), "+f"(d[158]), "+f"(d[159]), "+f"(d[160]), "+f"(d[161]), "+f"(d[162]), "+f"(d[163]), "+f"(d[164]), "+f"(d[165]), "+f"(d[166]), "+f"(d[167]), "+f"(d[168]), "+f"(d[169]), "+f"(d[170]), "+f"(d[171]), "+f"(d[172]), "+f"(d[173]), "+f"(d[174]), "+f"(d[175]), "+f"(d[176]), "+f"(d[177]), "+f"(d[178]), "+f"(d[179]), "+f"(d[180]), "+f"(d[181]), "+f"(d[182]), "+f"(d[183]), "+f"(d[184]), "+f"(d[185]), "+f"(d[186]), "+f"(d[187]), "+f"(d[188]), "+f"(d[189]), "+f"(d[190]), "+f"(d[191])
    : "r"(a[0]), "r"(a[1]), "r"(a[2]), "r"(a[3]), "l"(db), "r"(scale_d));
}
__device__ __forceinline__ void wgmma_n32_0(float (&d)[16], uint64_t da, uint64_t db) {
  asm volatile("{\n.reg .pred p;\nsetp.ne.b32 p, 0, 0;\n"
    "wgmma.mma_async.sync.aligned.m64n32k16.f32.bf16.bf16 {%0, %1, %2, %3, %4, %5, %6, %7, %8, %9, %10, %11, %12, %13, %14, %15}, %16, %17, p, 1, 1, 0, 1;\n}\n"
    : "=f"(d[0]), "=f"(d[1]), "=f"(d[2]), "=f"(d[3]), "=f"(d[4]), "=f"(d[5]), "=f"(d[6]), "=f"(d[7]), "=f"(d[8]), "=f"(d[9]), "=f"(d[10]), "=f"(d[11]), "=f"(d[12]), "=f"(d[13]), "=f"(d[14]), "=f"(d[15])
    : "l"(da), "l"(db));
}
__device__ __forceinline__ void wgmma_n32(float (&d)[16], uint64_t da, uint64_t db, int scale_d) {
  asm volatile("{\n.reg .pred p;\nsetp.ne.b32 p, %18, 0;\n"
    "wgmma.mma_async.sync.aligned.m64n32k16.f32.bf16.bf16 {%0, %1, %2, %3, %4, %5, %6, %7, %8, %9, %10, %11, %12, %13, %14, %15}, %16, %17, p, 1, 1, 0, 1;\n}\n"
    : "+f"(d[0]), "+f"(d[1]), "+f"(d[2]), "+f"(d[3]), "+f"(d[4]), "+f"(d[5]), "+f"(d[6]), "+f"(d[7]), "+f"(d[8]), "+f"(d[9]), "+f"(d[10]), "+f"(d[11]), "+f"(d[12]), "+f"(d[13]), "+f"(d[14]), "+f"(d[15])
    : "l"(da), "l"(db), "r"(scale_d));
}
__device__ __forceinline__ void wgmma_n8_t(float (&d)[4], uint64_t da, uint64_t db, int scale_d) {
  asm volatile("{\n.reg .pred p;\nsetp.ne.b32 p, %6, 0;\n"
    "wgmma.mma_async.sync.aligned.m64n8k16.f32.bf16.bf16 {%0, %1, %2, %3}, %4, %5, p, 1, 1, 1, 0;\n}\n"
    : "+f"(d[0]), "+f"(d[1]), "+f"(d[2]), "+f"(d[3])
    : "l"(da), "l"(db), "r"(scale_d));
}
__device__ __forceinline__ void wgmma_n128_rs0(float (&d)[192], const uint32_t (&a)[4], uint64_t db) {
  asm volatile("{\n.reg .pred p;\nsetp.ne.b32 p, 0, 0;\n"
    "wgmma.mma_async.sync.aligned.m64n128k16.f32.bf16.bf16 {%0, %1, %2, %3, %4, %5, %6, %7, %8, %9, %10, %11, %12, %13, %14, %15, %16, %17, %18, %19, %20, %21, %22, %23, %24, %25, %26, %27, %28, %29, %30, %31, %32, %33, %34, %35, %36, %37, %38, %39, %40, %41, %42, %43, %44, %45, %46, %47, %48, %49, %50, %51, %52, %53, %54, %55, %56, %57, %58, %59, %60, %61, %62, %63}, {%64, %65, %66, %67}, %68, p, 1, 1, 1;\n}\n"
    : "=f"(d[128]), "=f"(d[129]), "=f"(d[130]), "=f"(d[131]), "=f"(d[132]), "=f"(d[133]), "=f"(d[134]), "=f"(d[135]), "=f"(d[136]), "=f"(d[137]), "=f"(d[138]), "=f"(d[139]), "=f"(d[140]), "=f"(d[141]), "=f"(d[142]), "=f"(d[143]), "=f"(d[144]), "=f"(d[145]), "=f"(d[146]), "=f"(d[147]), "=f"(d[148]), "=f"(d[149]), "=f"(d[150]), "=f"(d[151]), "=f"(d[152]), "=f"(d[153]), "=f"(d[154]), "=f"(d[155]), "=f"(d[156]), "=f"(d[157]), "=f"(d[158]), "=f"(d[159]), "=f"(d[160]), "=f"(d[161]), "=f"(d[162]), "=f"(d[163]), "=f"(d[164]), "=f"(d[165]), "=f"(d[166]), "=f"(d[167]), "=f"(d[168]), "=f"(d[169]), "=f"(d[170]), "=f"(d[171]), "=f"(d[172]), "=f"(d[173]), "=f"(d[174]), "=f"(d[175]), "=f"(d[176]), "=f"(d[177]), "=f"(d[178]), "=f"(d[179]), "=f"(d[180]), "=f"(d[181]), "=f"(d[182]), "=f"(d[183]), "=f"(d[184]), "=f"(d[185]), "=f"(d[186]), "=f"(d[187]), "=f"(d[188]), "=f"(d[189]), "=f"(d[190]), "=f"(d[191])
    : "r"(a[0]), "r"(a[1]), "r"(a[2]), "r"(a[3]), "l"(db));
}
__device__ __forceinline__ void wgmma_n256_rs(float (&d)[192], const uint32_t (&a)[4], uint64_t db, int scale_d) {
  asm volatile("{\n.reg .pred p;\nsetp.ne.b32 p, %133, 0;\n"
    "wgmma.mma_async.sync.aligned.m64n256k16.f32.bf16.bf16 {%0, %1, %2, %3, %4, %5, %6, %7, %8, %9, %10, %11, %12, %13, %14, %15, %16, %17, %18, %19, %20, %21, %22, %23, %24, %25, %26, %27, %28, %29, %30, %31, %32, %33, %34, %35, %36, %37, %38, %39, %40, %41, %42, %43, %44, %45, %46, %47, %48, %49, %50, %51, %52, %53, %54, %55, %56, %57, %58, %59, %60, %61, %62, %63, %64, %65, %66, %67, %68, %69, %70, %71, %72, %73, %74, %75, %76, %77, %78, %79, %80, %81, %82, %83, %84, %85, %86, %87, %88, %89, %90, %91, %92, %93, %94, %95, %96, %97, %98, %99, %100, %101, %102, %103, %104, %105, %106, %107, %108, %109, %110, %111, %112, %113, %114, %115, %116, %117, %118, %119, %120, %121, %122, %123, %124, %125, %126, %127}, {%128, %129, %130, %131}, %132, p, 1, 1, 1;\n}\n"
    : "+f"(d[0]), "+f"(d[1]), "+f"(d[2]), "+f"(d[3]), "+f"(d[4]), "+f"(d[5]), "+f"(d[6]), "+f"(d[7]), "+f"(d[8]), "+f"(d[9]), "+f"(d[10]), "+f"(d[11]), "+f"(d[12]), "+f"(d[13]), "+f"(d[14]), "+f"(d[15]), "+f"(d[16]), "+f"(d[17]), "+f"(d[18]), "+f"(d[19]), "+f"(d[20]), "+f"(d[21]), "+f"(d[22]), "+f"(d[23]), "+f"(d[24]), "+f"(d[25]), "+f"(d[26]), "+f"(d[27]), "+f"(d[28]), "+f"(d[29]), "+f"(d[30]), "+f"(d[31]), "+f"(d[32]), "+f"(d[33]), "+f"(d[34]), "+f"(d[35]), "+f"(d[36]), "+f"(d[37]), "+f"(d[38]), "+f"(d[39]), "+f"(d[40]), "+f"(d[41]), "+f"(d[42]), "+f"(d[43]), "+f"(d[44]), "+f"(d[45]), "+f"(d[46]), "+f"(d[47]), "+f"(d[48]), "+f"(d[49]), "+f"(d[50]), "+f"(d[51]), "+f"(d[52]), "+f"(d[53]), "+f"(d[54]), "+f"(d[55]), "+f"(d[56]), "+f"(d[57]), "+f"(d[58]), "+f"(d[59]), "+f"(d[60]), "+f"(d[61]), "+f"(d[62]), "+f"(d[63]), "+f"(d[64]), "+f"(d[65]), "+f"(d[66]), "+f"(d[67]), "+f"(d[68]), "+f"(d[69]), "+f"(d[70]), "+f"(d[71]), "+f"(d[72]), "+f"(d[73]), "+f"(d[74]), "+f"(d[75]), "+f"(d[76]), "+f"(d[77]), "+f"(d[78]), "+f"(d[79]), "+f"(d[80]), "+f"(d[81]), "+f"(d[82]), "+f"(d[83]), "+f"(d[84]), "+f"(d[85]), "+f"(d[86]), "+f"(d[87]), "+f"(d[88]), "+f"(d[89]), "+f"(d[90]), "+f"(d[91]), "+f"(d[92]), "+f"(d[93]), "+f"(d[94]), "+f"(d[95]), "+f"(d[96]), "+f"(d[97]), "+f"(d[98]), "+f"(d[99]), "+f"(d[100]), "+f"(d[101]), "+f"(d[102]), "+f"(d[103]), "+f"(d[104]), "+f"(d[105]), "+f"(d[106]), "+f"(d[107]), "+f"(d[108]), "+f"(d[109]), "+f"(d[110]), "+f"(d[111]), "+f"(d[112]), "+f"(d[113]), "+f"(d[114]), "+f"(d[115]), "+f"(d[116]), "+f"(d[117]), "+f"(d[118]), "+f"(d[119]), "+f"(d[120]), "+f"(d[121]), "+f"(d[122]), "+f"(d[123]), "+f"(d[124]), "+f"(d[125]), "+f"(d[126]), "+f"(d[127])
    : "r"(a[0]), "r"(a[1]), "r"(a[2]), "r"(a[3]), "l"(db), "r"(scale_d));
}
__device__ __forceinline__ void wgmma_n256_rs0(float (&d)[192], const uint32_t (&a)[4], uint64_t db) {
  asm volatile("{\n.reg .pred p;\nsetp.ne.b32 p, 0, 0;\n"
    "wgmma.mma_async.sync.aligned.m64n256k16.f32.bf16.bf16 {%0, %1, %2, %3, %4, %5, %6, %7, %8, %9, %10, %11, %12, %13, %14, %15, %16, %17, %18, %19, %20, %21, %22, %23, %24, %25, %26, %27, %28, %29, %30, %31, %32, %33, %34, %35, %36, %37, %38, %39, %40, %41, %42, %43, %44, %45, %46, %47, %48, %49, %50, %51, %52, %53, %54, %55, %56, %57, %58, %59, %60, %61, %62, %63, %64, %65, %66, %67, %68, %69, %70, %71, %72, %73, %74, %75, %76, %77, %78, %79, %80, %81, %82, %83, %84, %85, %86, %87, %88, %89, %90, %91, %92, %93, %94, %95, %96, %97, %98, %99, %100, %101, %102, %103, %104, %105, %106, %107, %108, %109, %110, %111, %112, %113, %114, %115, %116, %117, %118, %119, %120, %121, %122, %123, %124, %125, %126, %127}, {%128, %129, %130, %131}, %132, p, 1, 1, 1;\n}\n"
    : "=f"(d[0]), "=f"(d[1]), "=f"(d[2]), "=f"(d[3]), "=f"(d[4]), "=f"(d[5]), "=f"(d[6]), "=f"(d[7]), "=f"(d[8]), "=f"(d[9]), "=f"(d[10]), "=f"(d[11]), "=f"(d[12]), "=f"(d[13]), "=f"(d[14]), "=f"(d[15]), "=f"(d[16]), "=f"(d[17]), "=f"(d[18]), "=f"(d[19]), "=f"(d[20]), "=f"(d[21]), "=f"(d[22]), "=f"(d[23]), "=f"(d[24]), "=f"(d[25]), "=f"(d[26]), "=f"(d[27]), "=f"(d[28]), "=f"(d[29]), "=f"(d[30]), "=f"(d[31]), "=f"(d[32]), "=f"(d[33]), "=f"(d[34]), "=f"(d[35]), "=f"(d[36]), "=f"(d[37]), "=f"(d[38]), "=f"(d[39]), "=f"(d[40]), "=f"(d[41]), "=f"(d[42]), "=f"(d[43]), "=f"(d[44]), "=f"(d[45]), "=f"(d[46]), "=f"(d[47]), "=f"(d[48]), "=f"(d[49]), "=f"(d[50]), "=f"(d[51]), "=f"(d[52]), "=f"(d[53]), "=f"(d[54]), "=f"(d[55]), "=f"(d[56]), "=f"(d[57]), "=f"(d[58]), "=f"(d[59]), "=f"(d[60]), "=f"(d[61]), "=f"(d[62]), "=f"(d[63]), "=f"(d[64]), "=f"(d[65]), "=f"(d[66]), "=f"(d[67]), "=f"(d[68]), "=f"(d[69]), "=f"(d[70]), "=f"(d[71]), "=f"(d[72]), "=f"(d[73]), "=f"(d[74]), "=f"(d[75]), "=f"(d[76]), "=f"(d[77]), "=f"(d[78]), "=f"(d[79]), "=f"(d[80]), "=f"(d[81]), "=f"(d[82]), "=f"(d[83]), "=f"(d[84]), "=f"(d[85]), "=f"(d[86]), "=f"(d[87]), "=f"(d[88]), "=f"(d[89]), "=f"(d[90]), "=f"(d[91]), "=f"(d[92]), "=f"(d[93]), "=f"(d[94]), "=f"(d[95]), "=f"(d[96]), "=f"(d[97]), "=f"(d[98]), "=f"(d[99]), "=f"(d[100]), "=f"(d[101]), "=f"(d[102]), "=f"(d[103]), "=f"(d[104]), "=f"(d[105]), "=f"(d[106]), "=f"(d[107]), "=f"(d[108]), "=f"(d[109]), "=f"(d[110]), "=f"(d[111]), "=f"(d[112]), "=f"(d[113]), "=f"(d[114]), "=f"(d[115]), "=f"(d[116]), "=f"(d[117]), "=f"(d[118]), "=f"(d[119]), "=f"(d[120]), "=f"(d[121]), "=f"(d[122]), "=f"(d[123]), "=f"(d[124]), "=f"(d[125]), "=f"(d[126]), "=f"(d[127])
    : "r"(a[0]), "r"(a[1]), "r"(a[2]), "r"(a[3]), "l"(db));
}

constexpr int SLOT = 16384;
constexpr int VB = 4 * SLOT, PH = 0, XS = 6;
constexpr int SM_SD = 13 * SLOT;
constexpr int SM_BAR = SM_SD + 8192;
constexpr int SM_RS = SM_BAR + 1024;
constexpr int SM_AP = SM_RS + 640;
constexpr int SM_BP = SM_AP + 2048;
constexpr int SM_ID = SM_BP + 6144;
constexpr int SM_TOTAL = SM_ID + 16;
constexpr int FM = 0, FT = 16, FW = 30, CM = 46, CT = 62, CW = 76, B_EF = 92, B_STAT = 93, B_KVF = 94, B_HALO = 95,
              B_KVDONE = 96, B_OH0 = 97, B_OH1 = 98, B_XH0 = 99, B_XDONE = 100, B_WFD = 101, B_XT = 102, B_OF0 = 103, B_KVF1 = 104, B_KVS = 105, B_RAW = 106  , B_X0 = 108, B_KVS0 = 109, B_ID = 110;
constexpr uint64_t BAR_LG = 0x00043333330004ull;
#define BA(i) (bar + (i) * 8)
#define REL2(i) release2c(SB0 + SM_BAR + (i) * 8)
constexpr int NF = 3, ND = 13, NR = 0, NWOP = 48, NAOP = 38;
constexpr bool EF_USED = false;
constexpr uint64_t TL_A = 0x6278627862786ull, TL_B = 0xa9c3ba9c3ba9cull, WO_A = 0x76b24038b51403ffull, WO_B = 0x8c5a197c6a297c8bull;
__constant__ uint32_t c_wop[NWOP + 1] = {0xeb0009, 0x186b8000, 0x6c0112, 0x1aec011a, 0x6c8224, 0x22ec822b, 0x18170330, 0x18178442, 0x18180554, 0x18188660, 0x18190772, 0x18198884, 0x181a0990, 0x181a8aa2, 0x181b0bb4, 0x181b8cc0, 0xaed10fc, 0xa9711e9, 0x181c0dd2, 0xa9792da, 0x129813cb, 0x181c8ee4, 0x181d0ff0, 0x109d94b3, 0x109f15ac, 0x109f9699, 0x10a0178a, 0x10a0987b, 0x10a11963, 0x10a19a5c, 0x10a21b49, 0x10a29c3a, 0x9231e0b, 0x9239f18, 0x1124202c, 0x13242137, 0x1124a249, 0x1324a352, 0x1125246a, 0x13252576, 0x1127268c, 0x1127a797, 0x112828a9, 0x1128a9b1, 0x11292aca, 0x13292bd5, 0x112a2cec, 0x132a2df8, 0};
__constant__ uint32_t c_aop[NAOP + 1] = {0x6d8228, 0x170336, 0x178447, 0x180558, 0x188666, 0x190777, 0x198888, 0x1a0996, 0x1a8aa7, 0x1b0bb8, 0x1b8cc6, 0x1c0dd7, 0x1c8ee8, 0x1d0ff6, 0x1d93c2, 0x1f14b6, 0x1f95a8, 0x201697, 0x209782, 0x211876, 0x219968, 0x221a57, 0x229b42, 0x231c36, 0xa3a023, 0xb12130, 0x2b12244, 0x2b12351, 0x2b12465, 0xa6257b, 0xa6a688, 0xa72793, 0xa7a8a0, 0xa829b4, 0xa8aac2, 0xa9abdb, 0x2a9ace6, 0xaaadf7, 0};
__constant__ uint32_t c_map[64] = {4, 5, 6, 7, 0, 16, 32, 48, 64, 80, 96, 112, 1, 17, 33, 49, 65, 81, 97, 113, 2, 18, 34, 50, 66, 82, 98, 114, 3, 19, 35, 51, 67, 83, 99, 115, 20, 36, 52, 68, 84, 100, 116, 21, 37, 53, 69, 85, 101, 117, 22, 38, 54, 70, 86, 102, 118, 23, 39, 55, 71, 87, 103, 119};
enum { MAP_WF = 0, MAP_WA = 2, MAP_WB = 4, MAP_WOA = 6, MAP_WOB = 8, MAP_X0 = 10, MAP_X = 11, MAP_O = 12, MAP_PHI = 13, NMAP = 14 };
struct Maps { CUtensorMap m[NMAP]; };

#define PL 2
#define PROFL(a, b)
#define SUBS 16
#define SUBS1 16
#define XRAT 10
#define XRN 4
#define BT1 1
#define ST1 8
#define X0AT 2
#define W1DL 400
#define WH 4
#define PFM 3
#define PFS 2
#define SVD 5000
#define NLAYERS 4
constexpr float L2E = 1.4426950408889634f;

#define D128(lo) desc64(lo, 0x40000040u)
struct Ctx { uint32_t zero, boff; const bf16* x0; bf16* out; };
#define BASE_CTX() \
  uint32_t bid_; asm volatile("mov.u32 %0, %%ctaid.x;" : "=r"(bid_)); \
  const int cr = bid_ & 1; \
  const uint32_t sb = SB0 + (cr << 24); \
  const uint32_t bar = sb + SM_BAR; (void)bar;
#define STA_CTX() \
  BASE_CTX(); \
  bid_ -= c.boff; \
  const uint32_t gr_ = c_map[bid_ >> 1]; \
  const int g = gr_ & 7, kf = (gr_ >> 3) + cr; (void)g; (void)kf;
#define DYN_CTX(id) \
  const uint32_t id_ = id; \
  const int g = id_ & 7, rb = (id_ >> 3) & 15, m0 = rb * 128; (void)g; (void)rb; (void)m0;
#define LD_ID() __float_as_uint(lds_f(sb + SM_ID))
extern __shared__ uint8_t smem_raw[];
constexpr uint32_t SB0 = 1024;

#define PHASE_CTX() \
  uint32_t idl_ = idp; asm volatile("" : "+r"(idl_)); \
  DYN_CTX(idl_); \
  const uint32_t sb = SB0 + ((id_ & 8) << 21), bar = sb + SM_BAR; \
  THR_CTX(); \
  const size_t gfr = (size_t)(m0 + wrow0 + gq) * D_ + g * 128 + 8 * t; (void)gfr;
#define THR_CTX() \
  int tid_ = threadIdx.x; asm volatile("" : "+r"(tid_)); \
  const int lane = tid_ & 31, cw = (tid_ >> 5) - 4, wg = cw >> 2, wq = cw & 3, gq = lane >> 2, t = lane & 3, wrow0 = cw * 16; \
  const int lrow = (lane & 7) + ((lane >> 3) & 1) * 8, lchk = lane >> 4; \
  const bool elected = (tid_ & 127) == 0; \
  const uint32_t rowo = (wrow0 + lrow) * 128, X = (lchk ^ (lane & 7)) << 4; \
  const uint32_t Y = (wrow0 + (lane & 7)) * 128 + (((lane >> 3) ^ (lane & 7)) << 4); \
  (void)bar; (void)wq; (void)gq; (void)lrow; (void)lchk; (void)elected; (void)wrow0; (void)wg; (void)rowo; (void)X; (void)t; (void)Y;
#define MMA_CTX() \
  const uint32_t wu = __shfl_sync(0xffffffffu, wg, 0); \
  const uint32_t dA0 = ((SB0 >> 4) | (1u << 16)) + wu * 512, dB0 = (SB0 >> 4) | (512u << 16); \
  const uint32_t par = layer & 1;

__device__ __forceinline__ void slab_out_half(uint32_t slot, bf16* dst, int wrow0, int lane) {
  const int r0 = lane >> 3, ch = lane & 7;
  const uint32_t src = slot + (wrow0 + r0) * 128;
  uint4 v[4];
#pragma unroll
  for (int i = 0; i < 4; ++i) v[i] = lds128(src + i * 512 + (((ch ^ (4 * i + r0)) & 7) << 4));
  dst += (size_t)(wrow0 + r0) * D_ + ch * 8;
#pragma unroll
  for (int i = 0; i < 4; ++i) *reinterpret_cast<uint4*>(dst + (size_t)i * 4 * D_) = v[i];
}

__device__ __forceinline__ void consumer(const Ctx& c) {
  float acc[192];
  uint32_t idp;
  uint32_t xf[4][4];
  uint32_t xp[8][4];
  {
    STA_CTX();
    THR_CTX();
    const unsigned int epoch = ld_relaxed(&g_epoch);
    PROFT(tid_ == 128, 0);
    const uint32_t wu = __shfl_sync(0xffffffffu, wg, 0);
    if (tid_ < 128 + 8) sts128(sb + SM_AP + lane * 16, make_uint4(0x3F803F80u, 0x3F803F80u, 0x3F803F80u, 0x3F803F80u));
#pragma unroll 1
    for (int it = 0; it < 2; ++it) {
      float p[4][16];
      mbar_wait(BA(B_RAW + it), 0);
      PROFT(tid_ == 128, it ? 15 : 2);
      const uint32_t da = ((SB0 >> 4) | (1u << 16)) + (wu ? 9 + it : 2 * it) * 1024, db = (SB0 + SM_SD) >> 4;
      wgmma_fence();
#pragma unroll
      for (int h = 0; h < 4; ++h) wgmma_n32_0(p[h], D128(da + (h >> 1) * 512 + (h & 1) * 4), desc64(db + h * 128, 0x80000020u));
#pragma unroll
      for (int h = 0; h < 4; ++h) wgmma_n32(p[h], D128(da + (h >> 1) * 512 + (h & 1) * 4 + 2), desc64(db + h * 128 + 64, 0x80000020u), 1);
      wgmma_commit();
      wgmma_wait<0>();
#pragma unroll
      for (int i = 0; i < 64; ++i) asm volatile("" : "+f"(p[i >> 4][i & 15]) :: "memory");
      const uint32_t base = sb + (wg ? 9 + it : 2 * it) * SLOT + (wq * 16 + gq) * 128;
      uint32_t w[4][4][2];
#pragma unroll
      for (int i = 0; i < 32; ++i) w[i >> 3][(i >> 1) & 3][i & 1] = pack_bf16(p[i >> 3][2 * (i & 7)], p[i >> 3][2 * (i & 7) + 1]);
      if (wu) {
#pragma unroll
        for (int i = 0; i < 8; ++i)
          sts128(base + (i >> 2) * 8192 + (i & 1) * 1024 + (((((i >> 1) & 1) * 4 + t) ^ gq) << 4), make_uint4(w[i >> 1][0][i & 1], w[i >> 1][1][i & 1], w[i >> 1][2][i & 1], w[i >> 1][3][i & 1]));
      } else {
#pragma unroll
        for (int i = 0; i < 16; ++i)
          sts64(base + (i >> 3) * 8192 + (i & 1) * 1024 + ((((t & 1) * 4 + ((i >> 1) & 3)) ^ gq) << 4) + (t >> 1) * 8, w[(i >> 3) * 2][(i >> 1) & 3][i & 1], w[(i >> 3) * 2 + 1][(i >> 1) & 3][i & 1]);
      }
      fence_async_smem();
      __syncwarp();
      if (it == cr && lane == 0) mbar_arrive(BA(B_WFD));
    }
    mbar_wait(BA(B_ID), 0);
    idp = __shfl_sync(0xffffffffu, LD_ID(), 0);
#pragma unroll
    for (int i = 0; i < 32; ++i) xp[i >> 2][i & 3] = 0u;
    nbar<1, 256>();
    PROFT(tid_ == 128, 13);
    mbar_wait(BA(FM + cr), 0);
    float cs[3][4];
    wgmma_fence();
#pragma unroll
    for (int ks = 0; ks < 4; ++ks)
#pragma unroll
      for (int i = 0; i < 3; ++i) {
        const uint32_t bx = (i == 0 ? 2 * cr * 1024 : i == 1 ? (2 * cr + 1) * 1024 : (9 + cr) * 1024) + wu * 512;
        wgmma_n8_t(cs[i], D128(((SB0 >> 4) | (512u << 16)) + bx + ks * 128), desc64((SB0 + SM_AP) >> 4, 0), ks != 0);
      }
    wgmma_commit();
    mbar_wait(BA(FM), 0);
#pragma unroll
    for (int k = 0; k < 4; ++k) ldsm_x4(xf[k][0], xf[k][1], xf[k][2], xf[k][3], sb + XS * SLOT + rowo + (X ^ (k << 5)));
    wgmma_wait<0>();
#pragma unroll
    for (int i = 0; i < 12; ++i) asm volatile("" : "+f"(cs[i >> 2][i & 3]) :: "memory");
    if (t < 2) {
#pragma unroll
      for (int i = 0; i < 3; ++i) red_add1(g_cs + (epoch & 1) * 6144 + g * 384 + i * 128 + wg * 64 + wq * 16 + gq + t * 8, t ? cs[i][2] : cs[i][0]);
    }
    PROFT(tid_ == 128, 14);
  }
#pragma unroll 1
  for (int layer = 0;; ++layer) {
    {
      wgmma_fence();
      wgmma_n256_rs0(acc, xf[0], D128((SB0 >> 4) | (512u << 16)));
#pragma unroll
      for (int k = 1; k < 4; ++k) wgmma_n256_rs(acc, xf[k], D128(((SB0 >> 4) | (512u << 16)) + k * 128), 1);
      wgmma_commit();
      PHASE_CTX();
      MMA_CTX();
      {
        const uint32_t ep = id_ >> 8;
        if (layer == 0) {
          mbar_wait(BA(B_X0), 0);
#pragma unroll
          for (int i = 0; i < 8; ++i) ldsm_x4(xp[i][0], xp[i][1], xp[i][2], xp[i][3], sb + (11 + (i >> 2)) * SLOT + (Y ^ ((i & 2) << 5)) + (i & 1) * 1024);
          if (lane == ((xp[0][0] ^ xp[1][0] ^ xp[2][0] ^ xp[3][0] ^ xp[7][0]) & c.zero)) REL2(B_XT);
        } else {
#pragma unroll
          for (int i = 0; i < 8; ++i) stsm_x4(sb + (XS + (i >> 2)) * SLOT + (Y ^ ((i & 2) << 5)) + (i & 1) * 1024, xp[i][0], xp[i][1], xp[i][2], xp[i][3]);
        }
        float s0 = 0.f, s1 = 0.f, q0 = 0.f, q1 = 0.f;
        auto stats = [&](int j0, int j1) {
#pragma unroll
          for (int j = j0; j < j1; ++j) {
            const uint32_t u0 = xp[(j >> 2) * 2][j & 3], u1 = xp[(j >> 2) * 2 + 1][j & 3];
            s0 += bf_lo(u0) + bf_hi(u0); s1 += bf_lo(u1) + bf_hi(u1);
            q0 = fmaf(bf_lo(u0), bf_lo(u0), fmaf(bf_hi(u0), bf_hi(u0), q0)); q1 = fmaf(bf_lo(u1), bf_lo(u1), fmaf(bf_hi(u1), bf_hi(u1), q1));
          }
        };
        stats(0, ST1);
        fence_async_smem();
        nbar_dyn(3 + wu + (__float_as_uint(s0 + s1 + q0 + q1) & c.zero), 128);
        mbar_wait(BA(FM + 1), par);
        wgmma_fence();
#pragma unroll
        for (int k = 0; k < 4; ++k) wgmma_n256(acc, D128(dA0 + (XS + 1) * 1024 + k * 2), D128(dB0 + 2048 + k * 128), 1);
        wgmma_commit();
        wgmma_wait<1>();
#pragma unroll
        for (int i = 4; i < 8; ++i) stg128_p(layer, g_x + gfr + (i & 1) * 8 * D_ + (i >> 1) * 32, xp[i][0], xp[i][1], xp[i][2], xp[i][3]);
        {
          uint32_t zc; asm volatile("mov.u32 %0, %%clock;" : "=r"(zc) :: "memory");
          q0 += __uint_as_float(zc & c.zero); q1 += __uint_as_float(zc & c.zero); s0 += __uint_as_float(zc & c.zero); s1 += __uint_as_float(zc & c.zero);
        }
        stats(ST1, 16);
        wgmma_fence();
        wgmma_n128_0(acc, D128(dA0 + XS * 1024), D128(dB0 + 9 * 1024));
#pragma unroll
        for (int k = 1; k < 4; ++k) wgmma_n128(acc, D128(dA0 + XS * 1024 + k * 2), D128(dB0 + 9 * 1024 + k * 128), 1);
        wgmma_commit();
        const bool od = t & 1;
        float sa = od ? s1 : s0, qa = od ? q1 : q0;
        sa += __shfl_xor_sync(0xffffffffu, od ? s0 : s1, 1);
        qa += __shfl_xor_sync(0xffffffffu, od ? q0 : q1, 1);
        wgmma_fence();
#pragma unroll
        for (int k = 0; k < 4; ++k) wgmma_n128(acc, D128(dA0 + (XS + 1) * 1024 + k * 2), D128(dB0 + 10 * 1024 + k * 128), 1);
        wgmma_commit();
        sa += __shfl_xor_sync(0xffffffffu, sa, 2);
        qa += __shfl_xor_sync(0xffffffffu, qa, 2);
        red_add2_p(t < 2, reinterpret_cast<float*>(g_stats + (ep * 4 + layer) * S_ + m0 + wrow0 + gq + t * 8), sa, qa);
        __syncwarp();
        if (lane == 0) mbar_arrive(BA(B_XDONE));
        wgmma_wait<1>();
        if (elected) REL2(CM);
      }
      uint32_t s = 2;
#pragma unroll 1
      for (int i = 2; i < NF; ++i) {
        PROFL(tid_ == 128 && layer == PL + 1, 244 + 2 * i);
        mbar_wait(BA(FM + i), par);
        PROFL(tid_ == 128 && layer == PL + 1, 245 + 2 * i);
        const uint32_t da = dA0 + (XS + s) * 1024, dk = dB0 + s * 2048, dq = dB0 + (9 + s) * 1024;
        wgmma_fence();
#pragma unroll
        for (int k = 0; k < 4; ++k) wgmma_n128(acc, D128(da + k * 2), D128(dq + k * 128), 1);
        wgmma_commit();
        wgmma_wait<1>();
        if (elected) REL2(CM + i - 1);
        wgmma_fence();
#pragma unroll
        for (int k = 0; k < 4; ++k) wgmma_n256(acc, D128(da + k * 2), D128(dk + k * 128), 1);
        wgmma_commit();
        if (++s == 3) s = 0;
      }
#pragma unroll 1
      for (int i = NF; i < 15; ++i) {
        mbar_wait(BA(FM + i), par);
        const uint32_t da = dA0 + (XS + s) * 1024, dk = dB0 + s * 2048;
        wgmma_fence();
#pragma unroll
        for (int k = 0; k < 4; ++k) wgmma_n256(acc, D128(da + k * 2), D128(dk + k * 128), 1);
        wgmma_commit();
        wgmma_wait<1>();
        if (elected) REL2(CM + i - 1);
        if (++s == 3) s = 0;
      }
      {
        const uint64_t dap = desc64(((SB0 + SM_AP) >> 4) + wu * 64, 8), dbp = make_desc_ns(SB0 + SM_BP, 0, 128);
        mbar_wait(BA(B_STAT), par);
        mbar_wait(BA(FM + 15), par);
        PROFT(tid_ == 128, layer * 16 + 9);
        wgmma_fence();
        wgmma_n256_k(acc, dap, dbp, 1);
#pragma unroll
        for (int k = 0; k < 4; ++k) wgmma_n256(acc, D128(dA0 + XS * 1024 + k * 2), D128(dB0 + k * 128), 1);
        wgmma_commit();
        wgmma_wait<1>();
        if (elected) REL2(CM + 14);
        mbar_wait(BA(FT), par);
        wgmma_fence();
        wgmma_n128_k(acc, dap, dbp + 256, 1);
#pragma unroll
        for (int k = 0; k < 4; ++k) wgmma_n128(acc, D128(dA0 + (uint32_t)(TL_A & 15) * 1024 + k * 2), D128(dB0 + (uint32_t)(TL_B & 15) * 1024 + k * 128), 1);
        wgmma_commit();
        wgmma_wait<1>();
        if (elected) REL2(CM + 15);
#pragma unroll
        for (int i = 0; i < 128; ++i) asm volatile("" : "+f"(acc[i]) :: "memory");
      }
    }
    uint32_t of[8][4], o1[4][4];
    {
      PHASE_CTX();
      MMA_CTX();
      PROFT(tid_ == 128, layer * 16 + 1);
      PROFT(lane == 0 && layer == PL, 192 + cw);
      PROFT(tid_ == 128 && layer == PL, 160);
      uint64_t ta = (TL_A >> 4), tw = TL_B >> 4;
      uint32_t da, db, dz = dA0;
      auto sub = [&](int n) {
        const int j = n >> 2, k = n & 3;
        if (k == 0) {
          dz += c.zero;
          da = dz + ((uint32_t)ta & 15) * 1024; db = dB0 + ((uint32_t)tw & 15) * 1024;
          ta >>= 4; tw >>= 4;
          mbar_wait(BA(FT + j), par);
          wgmma_fence();
        }
        wgmma_n128(acc, D128(da + k * 2), D128(db + k * 128), 1);
        if (k == 3) {
          wgmma_commit();
          wgmma_wait<1>();
          if (elected) REL2(CT + j - 1);
        }
      };
      auto run = [&](int j0, int j1) {
#pragma unroll 1
        for (int j = j0; j < j1; ++j) {
          mbar_wait(BA(FT + j), par);
          da = dA0 + ((uint32_t)ta & 15) * 1024; db = dB0 + ((uint32_t)tw & 15) * 1024;
          ta >>= 4; tw >>= 4;
          wgmma_fence();
#pragma unroll
          for (int k = 0; k < 4; ++k) wgmma_n128(acc, D128(da + k * 2), D128(db + k * 128), 1);
          wgmma_commit();
          wgmma_wait<1>();
          if (elected) REL2(CT + j - 1);
        }
        ta = TL_A >> (4 * j1); tw = TL_B >> (4 * j1);
      };
      auto rest = [&](int j0) {
        run(j0, ND);
        wgmma_wait<0>();
        if (elected) REL2(CT + ND - 1);
#pragma unroll
        for (int i = 128; i < 192; ++i) asm volatile("" : "+f"(acc[i]) :: "memory");
      };
      auto wo0 = [&]() {
        wgmma_fence();
        wgmma_n128_rs0(acc, of[0], D128(dB0 + (uint32_t)(WO_B & 15) * 1024));
#pragma unroll
        for (int k = 1; k < 4; ++k) wgmma_n128_rs(acc, of[k], D128(dB0 + (uint32_t)(WO_B & 15) * 1024 + k * 128), 1);
        wgmma_commit();
      };
      const float rs0 = lds_f(sb + SM_RS + (16 + wrow0 + gq) * 4), rs1 = lds_f(sb + SM_RS + (24 + wrow0 + gq) * 4);
      mbar_wait(BA(CM + 14), par);
      if (par) {
        uint32_t kk[8][4], kp[8][4], vf[2][2][4][4];
        int sn = 4;
        float rj[4];
#pragma unroll
        for (int nt = 0; nt < 4; ++nt) rj[nt] = lds_f(sb + SM_RS + (wrow0 + nt * 8 + 2 * t + (gq & 1)) * 4);
#pragma unroll
        for (int i = 0; i < 4 * BT1; ++i) sub(sn++);
        {
          uint32_t vv[8][4];
#pragma unroll
          for (int jp = 0; jp < 8; ++jp) {
            kk[jp][0] = pack_bf16(acc[8 * jp], acc[8 * jp + 1]); kk[jp][1] = pack_bf16(acc[8 * jp + 4], acc[8 * jp + 5]);
            kk[jp][2] = pack_bf16(acc[8 * jp + 2], acc[8 * jp + 3]); kk[jp][3] = pack_bf16(acc[8 * jp + 6], acc[8 * jp + 7]);
#pragma unroll
            for (int i = 0; i < 4; ++i) vv[jp][i] = pack_bf16(acc[64 + 8 * jp + 2 * i], acc[65 + 8 * jp + 2 * i]);
          }
          if (cw == 7) {
            uint32_t* const hbuf = g_halo + (size_t)(((layer >> 1) * 17 + rb + 1) * 8 + g) * 2048;
#pragma unroll
            for (int jp = 0; jp < 8; ++jp) stg128(hbuf + jp * 128 + lane * 4, kk[jp][0], kk[jp][1], kk[jp][2], kk[jp][3]);
#pragma unroll
            for (int i = 0; i < 32; ++i) hbuf[1024 + (i >> 4) * 512 + (gq + (i & 1) * 8) * 32 + ((((i >> 1) & 7) ^ gq) << 2) + t] = vv[i >> 2][i & 3];
            __syncwarp();
            if (lane == 0) mbar_arrive(BA(B_OF0));
          }
#pragma unroll
          for (int jp = 0; jp < 8; ++jp) {
            sub(sn++);
            stsm_x4(sb + VB + (jp >> 2) * SLOT + rowo + (X ^ ((jp & 3) << 5)), vv[jp][0], vv[jp][1], vv[jp][2], vv[jp][3]);
          }
        }
        PROFT(tid_ == 128, layer * 16 + 2);
        const int e = gq & 1;
        float f0[4], f1[4], b0[4], b1[4];
#pragma unroll
        for (int nt = 0; nt < 4; ++nt) {
          const int kx = nt * 8 + 2 * t + e;
          const bool okk = (m0 + wrow0 + kx) >= 16;
          const int d0 = kx - gq, d1 = d0 - 8;
          const bool m0_ = okk && d0 >= 2 && d0 <= 16, m1_ = okk && d1 >= 2 && d1 <= 16;
          f0[nt] = m0_ ? rj[nt] * rs0 * (0.17677669529663687f * L2E) : 0.f;
          f1[nt] = m1_ ? rj[nt] * rs1 * (0.17677669529663687f * L2E) : 0.f;
          b0[nt] = m0_ ? 0.f : -1e30f; b1[nt] = m1_ ? 0.f : -1e30f;
        }
        uint32_t ko = sb + PH + cw * 4096 + lane * 16;
        mbar_wait(BA(CM + 15), par);
#pragma unroll
        for (int jp = 0; jp < 8; ++jp) {
          sub(sn++);
          sts128(ko + jp * 512, make_uint4(kk[jp][0], kk[jp][1], kk[jp][2], kk[jp][3]));
        }
#pragma unroll
        for (int i = 0; i < 4; ++i) sub(sn++);
        nbar<1, 256>();
        PROFT(tid_ == 128, layer * 16 + 3);
        rest(sn >> 2);
        PROFT(lane == 0 && layer == PL, 200 + cw);
        PROFT(tid_ == 128, layer * 16 + 10);
        if (cw == 0) mbar_wait(BA(B_HALO), (layer >> 1) & 1);
        PROFT(tid_ == 128, layer * 16 + 5);
        const uint32_t vs = sb + (cw ? VB + rowo - 2048 : SM_SD + 4096 + rowo), vst = cw ? SLOT : 2048;
        asm volatile("" : "+r"(ko));
        const uint32_t ka = ko + (cw ? -4096 : SM_SD - PH);
        const uint32_t psel = e ? 0x1054u : 0x5410u;
#pragma unroll
        for (int hp = 0; hp < 2; ++hp) {
#pragma unroll
          for (int i = 4 * hp; i < 4 * hp + 4; ++i) {
            const uint4 u = lds128(ka + i * 512);
            kp[i][0] = u.x; kp[i][1] = u.y; kp[i][2] = u.z; kp[i][3] = u.w;
          }
#pragma unroll
          for (int i = 4 * hp; i < 4 * hp + 4; ++i) {
            ldsm_x4_t(vf[0][i & 1][i >> 1][0], vf[0][i & 1][i >> 1][1], vf[0][i & 1][i >> 1][2], vf[0][i & 1][i >> 1][3], vs + (i >> 2) * vst + (X ^ ((i & 3) << 5)));
            ldsm_x4_t(vf[1][i & 1][i >> 1][0], vf[1][i & 1][i >> 1][1], vf[1][i & 1][i >> 1][2], vf[1][i & 1][i >> 1][3], sb + VB + (i >> 2) * SLOT + rowo + (X ^ ((i & 3) << 5)));
          }
          float l0[2][4], l1[2][4];
#pragma unroll
          for (int h = 0; h < 2; ++h) {
            const int H = 2 * hp + h;
            uint32_t qa[8];
#pragma unroll
            for (int i = 0; i < 8; ++i) qa[i] = pack_bf16(acc[128 + 16 * H + 2 * i], acc[129 + 16 * H + 2 * i]);
#pragma unroll
            for (int nt = 3; nt >= 0; --nt) {
              float sc[4] = {0.f, 0.f, 0.f, 0.f};
#pragma unroll
              for (int ks = 0; ks < 2; ++ks) {
                const uint32_t (&kf)[4] = nt < 2 ? kp[2 * H + ks] : kk[2 * H + ks];
                mma_bf16(sc, qa[4 * ks], qa[4 * ks + 1], qa[4 * ks + 2], qa[4 * ks + 3], kf[2 * (nt & 1)], kf[2 * (nt & 1) + 1]);
              }
              l0[h][nt] = fmaf(e ? sc[1] : sc[0], f0[nt], b0[nt]);
              l1[h][nt] = fmaf(e ? sc[3] : sc[2], f1[nt], b1[nt]);
            }
          }
          float mx0[2], mx1[2], s0[2], s1[2];
#pragma unroll
          for (int h = 0; h < 2; ++h) {
            mx0[h] = fmaxf(fmaxf(l0[h][0], l0[h][1]), l0[h][2]);
            mx1[h] = fmaxf(fmaxf(l1[h][1], l1[h][2]), l1[h][3]);
          }
#pragma unroll
          for (int o = 1; o <= 2; o <<= 1)
#pragma unroll
            for (int h = 0; h < 2; ++h) {
              mx0[h] = fmaxf(mx0[h], __shfl_xor_sync(0xffffffffu, mx0[h], o));
              mx1[h] = fmaxf(mx1[h], __shfl_xor_sync(0xffffffffu, mx1[h], o));
            }
#pragma unroll
          for (int h = 0; h < 2; ++h) {
#pragma unroll
            for (int nt = 0; nt < 3; ++nt) { l0[h][nt] = ex2(l0[h][nt] - mx0[h]); l1[h][nt + 1] = ex2(l1[h][nt + 1] - mx1[h]); }
            s0[h] = (l0[h][0] + l0[h][1]) + l0[h][2];
            s1[h] = (l1[h][1] + l1[h][2]) + l1[h][3];
          }
#pragma unroll
          for (int o = 1; o <= 2; o <<= 1)
#pragma unroll
            for (int h = 0; h < 2; ++h) {
              s0[h] += __shfl_xor_sync(0xffffffffu, s0[h], o);
              s1[h] += __shfl_xor_sync(0xffffffffu, s1[h], o);
            }
          uint32_t ow[2][2][4];
#pragma unroll
          for (int h = 0; h < 2; ++h) {
            const int H = 2 * hp + h;
            uint32_t pl[4], ph[4];
            const float i0 = rcp(s0[h]), i1 = rcp(s1[h]);
#pragma unroll
            for (int nt = 0; nt < 4; ++nt) {
              const uint32_t pk = pack_bf16(nt < 3 ? l0[h][nt] * i0 * rj[nt] : 0.f, nt > 0 ? l1[h][nt] * i1 * rj[nt] : 0.f);
              pl[nt] = nt < 3 ? __byte_perm(pk, 0u, psel) : 0u;
              ph[nt] = nt > 0 ? __byte_perm(pk, 0u, psel + 0x2222u) : 0u;
            }
#pragma unroll
            for (int nj = 0; nj < 4; ++nj) {
              float oa[4] = {0.f, 0.f, 0.f, 0.f};
#pragma unroll
              for (int ks = 0; ks < 2; ++ks)
                mma_bf16(oa, pl[2 * ks], ph[2 * ks], pl[2 * ks + 1], ph[2 * ks + 1], vf[ks][nj >> 1][H][2 * (nj & 1)], vf[ks][nj >> 1][H][2 * (nj & 1) + 1]);
              ow[h][0][nj] = pack_bf16(oa[0], oa[1]); ow[h][1][nj] = pack_bf16(oa[2], oa[3]);
            }
          }
          if (hp == 0) {
#pragma unroll
            for (int i = 0; i < 4; ++i) stg128(g_o + gfr + (i & 1) * 8 * D_ + (i >> 1) * 32, ow[i >> 1][i & 1][0], ow[i >> 1][i & 1][1], ow[i >> 1][i & 1][2], ow[i >> 1][i & 1][3]);
            __syncwarp();
            if (lane == 0) mbar_arrive(BA(B_OH0));
          } else {
#pragma unroll
            for (int i = 0; i < 16; ++i) o1[i >> 2][i & 3] = ow[i >> 3][(i >> 2) & 1][i & 3];
          }
#pragma unroll
          for (int i = 0; i < 16; ++i) of[4 * hp + (i >> 2)][i & 3] = ow[i >> 3][i & 1][(i >> 1) & 3];
          if (!hp) { PROFT(tid_ == 128, layer * 16 + 15); mbar_wait(BA(FW), par); }
        }
      } else {
        float sc[2] = {rs0 * L2E, rs1 * L2E};
        {
          const uint32_t vb = sb + VB + (rowo >> 1), X0 = (lchk ^ ((lane & 7) >> 1)) << 4;
          const uint32_t pb = sb + PH + (t & 1) * SLOT + (wrow0 + gq) * 128 + ((((t & 1) * 4 + (t & 2)) ^ gq) << 4);
          float kva[20], en[32], mx[2][2], mn[2][2];
#define PV(hp, j) acc[32 * (hp) + (j)]
          auto mm = [&](int hp, int j) {
            const int r = (j >> 1) & 1;
            if (j < 4 && !(j & 1)) { mx[hp][r] = PV(hp, j); mn[hp][r] = PV(hp, j); }
            else { mx[hp][r] = fmaxf(mx[hp][r], PV(hp, j)); mn[hp][r] = fminf(mn[hp][r], PV(hp, j)); }
          };
          auto mmx = [&](int hp) {
#pragma unroll
            for (int r = 0; r < 2; ++r) {
              mx[hp][r] = fmaxf(mx[hp][r], __shfl_xor_sync(0xffffffffu, mx[hp][r], 2)) * -sc[r];
              mn[hp][r] = fmaf(fminf(mn[hp][r], __shfl_xor_sync(0xffffffffu, mn[hp][r], 2)), sc[r], mx[hp][r]);
            }
          };
          auto stage = [&](int hp) {
#pragma unroll
            for (int i = 0; i < 20; ++i) asm volatile("" : "+f"(kva[i]) :: "memory");
            nbar_dyn(3 + wu, 128);
            const uint32_t ad = sb + VB + hp * SLOT + wg * 8192 + (2 * wq + ((lane >> 3) & 1)) * 640 + (lane & 7) * 16;
#pragma unroll
            for (int i = 0; i < 2; ++i)
              stsm_x4(ad + (2 * i + lchk) * 128, pack_bf16(kva[8 * i], kva[8 * i + 1]), pack_bf16(kva[8 * i + 2], kva[8 * i + 3]),
                      pack_bf16(kva[8 * i + 4], kva[8 * i + 5]), pack_bf16(kva[8 * i + 6], kva[8 * i + 7]));
            stsm_x2(ad + 512, pack_bf16(kva[16], 0.0625f), pack_bf16(kva[18], 0.0625f));
            fence_async_smem();
            __syncwarp();
            if (lane == 0) mbar_arrive(BA(B_KVDONE));
          };
          int sn = 4;
#pragma unroll
          for (int j = 0; j < 32; ++j) mm(0, j);
          mmx(0);
#pragma unroll
          for (int hp = 0; hp < 2; ++hp) {
            float sp[2] = {0.f, 0.f}, sm[2] = {0.f, 0.f};
#pragma unroll
            for (int j = 0; j < 32; ++j) {
              const int r = (j >> 1) & 1, ns = hp ? SUBS1 : SUBS;
              if ((j * ns) / 32 != ((j + 1) * ns) / 32) {
                sub(sn++);
                if (hp && sn == 4 + SUBS + 4) { stage(0); PROFT(tid_ == 128, layer * 16 + 12); }
              }
              const float x = fmaf(PV(hp, j), sc[r], mx[hp][r]);
              PV(hp, j) = ex2(x); en[j] = ex2(mn[hp][r] - x);
              sp[r] += PV(hp, j); sm[r] += en[j];
              if (hp == 0) {
                mm(1, j);
                if ((j & 3) == 0) {
                  const int jp = 8 + (j >> 2);
                  stsm_x4(vb + ((jp - 8) >> 1) * 8192 + (X0 ^ ((jp & 1) << 5)), pack_bf16(acc[8 * jp], acc[8 * jp + 1]), pack_bf16(acc[8 * jp + 2], acc[8 * jp + 3]),
                          pack_bf16(acc[8 * jp + 4], acc[8 * jp + 5]), pack_bf16(acc[8 * jp + 6], acc[8 * jp + 7]));
                }
              }
            }
#pragma unroll
            for (int r = 0; r < 2; ++r) {
              sp[r] = rcp(sp[r] + __shfl_xor_sync(0xffffffffu, sp[r], 2)) * (r ? rs1 : rs0);
              sm[r] = rcp(sm[r] + __shfl_xor_sync(0xffffffffu, sm[r], 2)) * (r ? rs1 : rs0);
            }
            if (hp == 0) { mmx(1); mbar_wait(BA(CM + 15), par); }
            else { PROFT(tid_ == 128, layer * 16 + 11); nbar<1, 256>(); }
#pragma unroll
            for (int i = 0; i < 4; ++i) {
              const int r = i & 1, d = 16 * (i >> 1) + 2 * r;
              sts128((pb + r * 1024) ^ ((i >> 1) << 4), make_uint4(pack_bf16(PV(hp, d) * sp[r], PV(hp, d + 1) * sp[r]), pack_bf16(PV(hp, d + 4) * sp[r], PV(hp, d + 5) * sp[r]),
                                                                    pack_bf16(PV(hp, d + 8) * sp[r], PV(hp, d + 9) * sp[r]), pack_bf16(PV(hp, d + 12) * sp[r], PV(hp, d + 13) * sp[r])));
              sts128((pb + r * 1024) ^ ((i >> 1) << 4) ^ 64, make_uint4(pack_bf16(en[d] * sm[r], en[d + 1] * sm[r]), pack_bf16(en[d + 4] * sm[r], en[d + 5] * sm[r]),
                                                                         pack_bf16(en[d + 8] * sm[r], en[d + 9] * sm[r]), pack_bf16(en[d + 12] * sm[r], en[d + 13] * sm[r])));
            }
            fence_async_smem();
            nbar<1, 256>();
            const uint32_t dP = dB0 + (PH >> 4) + wu * 1024;
            const uint32_t dV = (dB0 & 0xFFFFu) + ((VB + hp * SLOT) >> 4) + (((SM_SD - VB - hp * SLOT) >> 4) << 16) + wu * (512u - (512u << 16));
            wgmma_fence();
#pragma unroll
            for (int ks = 0; ks < 8; ++ks) wgmma_n40_tt(kva, D128(dP + ks * 128), desc64(dV + ks * 64, 0x80000020u), ks != 0);
            wgmma_commit();
          }
#pragma unroll
          for (int i = 0; i < 4; ++i) sub(sn++);
          stage(1);
          PROFT(tid_ == 128, layer * 16 + 3);
          rest(sn >> 2);
          PROFT(lane == 0 && layer == PL, 200 + cw);
          PROFT(tid_ == 128, layer * 16 + 10);
        }
#define QV(H, i) acc[128 + 16 * (H) + (i)]
        float mx[4][2], mn[4][2];
        uint32_t ph[4][4][4];
        auto mnx = [&](int hp) {
#pragma unroll
          for (int H = 2 * hp; H < 2 * hp + 2; ++H)
#pragma unroll
            for (int r = 0; r < 2; ++r) {
              mx[H][r] = fmaxf(fmaxf(fmaxf(QV(H, 2 * r), QV(H, 2 * r + 1)), fmaxf(QV(H, 4 + 2 * r), QV(H, 5 + 2 * r))),
                               fmaxf(fmaxf(QV(H, 8 + 2 * r), QV(H, 9 + 2 * r)), fmaxf(QV(H, 12 + 2 * r), QV(H, 13 + 2 * r))));
              mn[H][r] = fminf(fminf(fminf(QV(H, 2 * r), QV(H, 2 * r + 1)), fminf(QV(H, 4 + 2 * r), QV(H, 5 + 2 * r))),
                               fminf(fminf(QV(H, 8 + 2 * r), QV(H, 9 + 2 * r)), fminf(QV(H, 12 + 2 * r), QV(H, 13 + 2 * r))));
            }
#pragma unroll
          for (int o = 1; o <= 2; o <<= 1)
#pragma unroll
            for (int H = 2 * hp; H < 2 * hp + 2; ++H)
#pragma unroll
              for (int r = 0; r < 2; ++r) {
                mx[H][r] = fmaxf(mx[H][r], __shfl_xor_sync(0xffffffffu, mx[H][r], o));
                mn[H][r] = fminf(mn[H][r], __shfl_xor_sync(0xffffffffu, mn[H][r], o));
              }
#pragma unroll
          for (int H = 2 * hp; H < 2 * hp + 2; ++H)
#pragma unroll
            for (int r = 0; r < 2; ++r) { mx[H][r] *= -sc[r]; mn[H][r] = fmaf(mn[H][r], sc[r], mx[H][r]); }
        };
        auto fm = [&](int H) {
#pragma unroll
          for (int i = 0; i < 8; ++i) {
            const int r = i & 1;
            const float x0 = fmaf(QV(H, 2 * i), sc[r], mx[H][r]), x1 = fmaf(QV(H, 2 * i + 1), sc[r], mx[H][r]);
            ph[H][i >> 2][i & 3] = pack_bf16(ex2(x0), ex2(x1));
            ph[H][2 + (i >> 2)][i & 3] = pack_bf16(ex2(mn[H][r] - x0), ex2(mn[H][r] - x1));
          }
        };
        mnx(0);
        fm(0); fm(1);
#pragma unroll
        for (int hp = 0; hp < 2; ++hp) {
          if (hp) mbar_wait(BA(FW), par);
          mbar_wait(BA(hp ? B_KVF1 : B_KVF), (layer >> 1) & 1);
          PROFT(tid_ == 128, layer * 16 + (hp ? 4 : 5));
          float oa[4][20];
          wgmma_fence();
#pragma unroll
          for (int s = 0; s < 2; ++s)
#pragma unroll
            for (int v = 0; v < 4; ++v) {
              const int h = v >> 1, s4 = 2 * (v & 1) + s;
              wgmma_n40_rs(oa[v], ph[2 * hp + h][s4], desc64((((SB0 + VB + hp * SLOT) >> 4) | (40u << 16)) + h * 512 + (s4 ^ (2 * h)) * 80, 8), s != 0);
            }
          wgmma_commit();
          if (hp == 0) { mnx(1); wgmma_wait<0>(); }
          else wgmma_wait<0>();
#pragma unroll
          for (int i = 0; i < 20; ++i) asm volatile("" : "+f"(oa[0][i]), "+f"(oa[1][i]), "+f"(oa[2][i]), "+f"(oa[3][i]) :: "memory");
          uint32_t ow[2][2][4];
#pragma unroll
          for (int h = 0; h < 2; ++h)
#pragma unroll
            for (int r = 0; r < 2; ++r) {
              const float a = oa[2 * h + 1][17 + 2 * r], b = oa[2 * h][17 + 2 * r];
              const float id = rcp(fmaf(oa[2 * h][16 + 2 * r], a, fmaf(a, 1e-6f, oa[2 * h + 1][16 + 2 * r]) * b));
              const float fa = a * id, fb = b * id;
#pragma unroll
              for (int j = 0; j < 4; ++j)
                ow[h][r][j] = pack_bf16(fmaf(oa[2 * h][4 * j + 2 * r], fa, oa[2 * h + 1][4 * j + 2 * r] * fb),
                                        fmaf(oa[2 * h][4 * j + 2 * r + 1], fa, oa[2 * h + 1][4 * j + 2 * r + 1] * fb));
            }
#pragma unroll
          for (int i = 0; i < 16; ++i) of[4 * hp + (i >> 2)][i & 3] = ow[i >> 3][i & 1][(i >> 1) & 3];
          if (hp == 0) {
#pragma unroll
            for (int i = 0; i < 4; ++i) stg128(g_o + gfr + (i & 1) * 8 * D_ + (i >> 1) * 32, ow[i >> 1][i & 1][0], ow[i >> 1][i & 1][1], ow[i >> 1][i & 1][2], ow[i >> 1][i & 1][3]);
            __syncwarp();
            if (lane == 0) mbar_arrive(BA(B_OH0));
            PROFT(tid_ == 128 && layer, layer * 16 + 15);
            fm(2); fm(3);
          } else {
#pragma unroll
            for (int i = 0; i < 16; ++i) o1[i >> 2][i & 3] = ow[i >> 3][(i >> 2) & 1][i & 3];
          }
        }
      }
      PROFT(tid_ == 128, layer * 16 + 6);
#pragma unroll
      for (int i = 0; i < 4; ++i) stg128(g_o + gfr + (i & 1) * 8 * D_ + (2 + (i >> 1)) * 32, o1[i][0], o1[i][1], o1[i][2], o1[i][3]);
      __syncwarp();
      if (lane == 0) { mbar_arrive(BA(B_OH1)); if (EF_USED) REL2(B_EF); }
      PROFT(lane == 0 && layer == PL, 208 + cw);
      fence_async_smem();
      wo0();
    }
    {
      PHASE_CTX();
      MMA_CTX();
      mbar_wait(BA(FW + 1), par);
      wgmma_fence();
#pragma unroll
      for (int k = 0; k < 4; ++k) wgmma_n128_rs(acc, of[4 + k], D128(dB0 + (uint32_t)((WO_B >> 4) & 15) * 1024 + k * 128), 1);
      wgmma_commit();
      wgmma_wait<1>();
      if (elected) REL2(CW);
      uint64_t ta = WO_A >> 8, tw = WO_B >> 8;
      auto run = [&](int i0, int i1) {
#pragma unroll 1
        for (int i = i0; i < i1; ++i) {
          mbar_wait(BA(FW + i), par);
          PROFL(tid_ == 128 && layer == PL, 160 + i);
          const uint32_t da = dA0 + ((uint32_t)ta & 15) * 1024, db = dB0 + ((uint32_t)tw & 15) * 1024;
          ta >>= 4; tw >>= 4;
          wgmma_fence();
#pragma unroll
          for (int k = 0; k < 4; ++k) wgmma_n128(acc, D128(da + k * 2), D128(db + k * 128), 1);
          wgmma_commit();
          wgmma_wait<1>();
          if (elected) REL2(CW + i - 1);
        }
        ta = WO_A >> (4 * (i1 & 15)); tw = WO_B >> (4 * (i1 & 15));
      };
      run(2, XRAT);
#pragma unroll
      for (int j = 0; j < 8 / XRN; ++j) {
#pragma unroll
        for (int i = j * XRN; i < (j + 1) * XRN; ++i) ldg128((layer ? g_x : c.x0) + gfr + (i & 1) * 8 * D_ + (i >> 1) * 32, xp[i][0], xp[i][1], xp[i][2], xp[i][3]);
        run(XRAT + j, j + 1 < 8 / XRN ? XRAT + j + 1 : 16);
      }
      if (layer == 0) {
#pragma unroll
        for (int o = 1; o <= 2; o <<= 1)
#pragma unroll
          for (int i = 0; i < 16; ++i) {
            const int j = o == 1 ? 2 * (i & 1) : (i & 1);
            uint32_t &a = xp[i >> 1][j], &b = xp[i >> 1][j + o];
            const uint32_t r = __shfl_xor_sync(0xffffffffu, (t & o) ? a : b, o);
            if (t & o) a = r; else b = r;
          }
      }
      if (layer != NLAYERS - 1) mbar_wait(BA(FM), par ^ 1);
      wgmma_wait<0>();
#pragma unroll
      for (int i = 128; i < 192; ++i) asm volatile("" : "+f"(acc[i]) :: "memory");
      if (elected) REL2(CW + 15);
      PROFT(lane == 0 && layer == PL, 216 + cw);
      PROFT(tid_ == 128, layer * 16 + 7);
#pragma unroll
      for (int i = 0; i < 32; ++i)
        xp[i >> 2][i & 3] = add_bf16x2(xp[i >> 2][i & 3], pack_bf16(acc[128 + 16 * (i >> 3) + 4 * (i & 3) + 2 * ((i >> 2) & 1)], acc[129 + 16 * (i >> 3) + 4 * (i & 3) + 2 * ((i >> 2) & 1)]));
      if (layer == NLAYERS - 1) {
#pragma unroll
        for (int i = 0; i < 8; ++i) stsm_x4(sb + (XS + (i >> 2)) * SLOT + (Y ^ ((i & 2) << 5)) + (i & 1) * 1024, xp[i][0], xp[i][1], xp[i][2], xp[i][3]);
        __syncwarp();
        slab_out_half(sb + XS * SLOT, c.out + (size_t)m0 * D_ + g * 128, wrow0, lane);
        slab_out_half(sb + (XS + 1) * SLOT, c.out + (size_t)m0 * D_ + g * 128 + 64, wrow0, lane);
        PROFT(tid_ == 128, layer * 16 + 24);
        break;
      }
#pragma unroll
      for (int i = 0; i < 4; ++i) stg128(g_x + gfr + (i & 1) * 8 * D_ + (i >> 1) * 32, xp[i][0], xp[i][1], xp[i][2], xp[i][3]);
      __syncwarp();
      if (lane == 0) mbar_arrive(BA(B_XH0));
#pragma unroll
      for (int i = 0; i < 16; ++i) xf[i >> 2][i & 3] = xp[2 * (i >> 3) + (i & 1)][(i >> 1) & 3];
      PROFT(tid_ == 128, layer * 16 + 24);
    }
  }
}

__device__ __forceinline__ uint64_t k_order(int o) {
  const uint32_t lo = (1u << (4 * o)) - 1u, h0 = (0xECA86420u & lo) | ((0xECA86420u >> 4) & ~lo);
  return (uint64_t)(2 * o) | ((uint64_t)(2 * o + 1) << 4) | ((uint64_t)(h0 & 0xFFFFFFFu) << 8) | ((uint64_t)((h0 & 0xFFFFFFFu) | 0x1111111u) << 36);
}

__global__ void __cluster_dims__(2, 1, 1) __launch_bounds__(384, 1)
mega_kernel(const __grid_constant__ Maps maps, const __grid_constant__ Ctx c, const bf16* __restrict__ wA, const bf16* __restrict__ wB,
            const bf16* __restrict__ woA, const bf16* __restrict__ woB) {
  if (blockIdx.x - c.boff >= 128u) {
    const unsigned int epoch = ld_relaxed(&g_epoch);
    const int e = (blockIdx.x - c.boff) & 3, tid = threadIdx.x;
    float s[8] = {0.f, 0.f, 0.f, 0.f, 0.f, 0.f, 0.f, 0.f};
    const uint32_t sb = smem_u32(smem_raw), bar = sb + SM_BAR;
    auto issue = [&](int i) {
      mbar_expect_tx(BA(i & 3), 49152);
      bulk_load(sb + (i & 3) * 49152, wB + (size_t)e * 256 * 3072 + i * 24576, 49152, BA(i & 3));
    };
    if (tid == 0) {
      if (SVD) __nanosleep(SVD);
#pragma unroll 1
      for (int i = 0; i < 4; ++i) {
        mbar_init(BA(i), 1);
        fence_async_smem();
        issue(i);
      }
    }
    __syncthreads();
#pragma unroll 1
    for (int i = 0; i < 32; ++i) {
      mbar_wait(BA(i & 3), (i >> 2) & 1);
#pragma unroll 2
      for (int r = 0; r < 8; ++r) {
        const uint4 v = lds128(sb + (i & 3) * 49152 + r * 6144 + tid * 16);
        s[0] += bf_lo(v.x); s[1] += bf_hi(v.x); s[2] += bf_lo(v.y); s[3] += bf_hi(v.y);
        s[4] += bf_lo(v.z); s[5] += bf_hi(v.z); s[6] += bf_lo(v.w); s[7] += bf_hi(v.w);
      }
      __syncthreads();
      if (tid == 0 && i < 28) issue(i + 4);
    }
    float* cd = g_cs + (epoch & 1) * 6144 + 3072 + ((tid >> 4) & 7) * 384 + (tid < 128 ? 256 : (tid >> 7) * 128 - 128) + (tid & 15) * 8;
    red_add4(cd, s[0], s[1], s[2], s[3]);
    red_add4(cd + 4, s[4], s[5], s[6], s[7]);
    __syncthreads();
    if (tid == 0) flag_add(&g_csflag[8].v);
    const int op = (epoch & 1) ^ 1;
    float4* kz = reinterpret_cast<float4*>(g_kv + (size_t)op * (2 * 8 * 10240)) + e * 5120;
#pragma unroll 1
    for (int i = tid; i < 5120; i += 384) kz[i] = make_float4(0.f, 0.f, 0.f, 0.f);
    reinterpret_cast<float4*>(g_cs + op * 6144)[e * 384 + tid] = make_float4(0.f, 0.f, 0.f, 0.f);
#pragma unroll 1
    for (int i = tid; i < 1024; i += 384) reinterpret_cast<float4*>(g_stats + (op * 4 + e) * S_)[i] = make_float4(0.f, 0.f, 0.f, 0.f);
    return;
  }
  const int warp = __shfl_sync(0xffffffffu, threadIdx.x >> 5, 0), lane = threadIdx.x & 31;
  if (smem_u32(smem_raw) != SB0 + ((blockIdx.x & 1) << 24)) __trap();
  uint32_t cx = 0;
  {
  const int cid = (blockIdx.x - c.boff) >> 1, u7 = ((cid - 36) * 37) >> 8, cr = blockIdx.x & 1;
  const int g = cid < 4 ? 4 + cid : cid < 36 ? (cid - 4) >> 3 : 4 + u7, kf = (cid < 4 ? 0 : cid < 36 ? (cid - 4) & 7 : cid - 35 - 7 * u7) * 2 + cr;
  const uint32_t sb = SB0 + (cr << 24), bar = sb + SM_BAR;
  PROFT(lane == 0 && (warp == 0 || warp == 4), 224 + (warp >> 2) * 8);
  if (warp == 2) {
    if (lane < NMAP) asm volatile("prefetch.tensormap [%0];" ::"l"(&maps.m[lane]) : "memory");
    cx = ld_relaxed(&g_epoch);
    if (cid == 4 && cr == 0 && lane == 0) {
      uint32_t smid; asm volatile("mov.u32 %0, %%smid;" : "=r"(smid));
      asm volatile("st.relaxed.gpu.global.u32 [%0], %1;" ::"l"(&g_rot), "r"((cx + 1) * 8 + ((smid >> 1) & 7)) : "memory");
    }
  } else if (warp == 3) {
    cx = c_map[cid] + c_wop[lane] + c_wop[NWOP - lane] + c_aop[lane] + c_aop[NAOP - lane] + (uint32_t)(uintptr_t)g_x;
  } else if (warp >= 4 && warp < 8) {
    const int i = threadIdx.x - 128;
    asm volatile("prefetch.global.L2 [%0];" ::"l"(wA + (size_t)((kf & ~1) * 64 + cr * 32 + ((i >> 1) & 31)) * 3072 + (i >> 6) * 1024 + g * 128 + (i & 1) * 64));
  }
  if (warp < 2) {
    const int s = warp, kb = (kf & ~1) + s;
    if (lane == 0) {
      mbar_init(BA(FM + s), 1u);
      mbar_init(BA(B_RAW + warp), 1u);
      mbar_init(BA(warp ? B_X0 : B_KVS0), 1u);
      if (warp) mbar_init(BA(B_ID), 1u);
      asm volatile("fence.mbarrier_init.release.cluster;" ::: "memory");
    }
    __syncwarp();
    if (warp == 0) tma_2d_e(sb + SM_SD, &maps.m[MAP_PHI], 0, g * 128, BA(B_RAW));
    else if (W1DL) __nanosleep(W1DL);
#pragma unroll
    for (int j = 0; j < 6; ++j)
      tma_5d_e(sb + (j < 2 ? 2 * s : j < 4 ? 9 + s : 2 * s + 1) * SLOT + (j & 1) * 8192, &maps.m[MAP_WA], (j < 2 ? 1024 : j < 4 ? 0 : 2048) + g * 128 + (j & 1) * 64, 2 * kb,
               BA(j < 4 ? B_RAW + warp : FM + s));
    expect_tx_e(BA(B_RAW + warp), warp ? 32768 : 32768 + 8192);
    expect_tx_e(BA(FM + s), 32768);
  } else if (warp >= 4 && lane == 0) {
#pragma unroll 1
    for (int i = 2 + (warp - 4) * 13; i < 15 + (warp - 4) * 13; ++i)
      mbar_init(BA(i), 1u << ((i < CM ? 0u : i < B_EF ? 2u : (uint32_t)(BAR_LG >> (4 * ((i - B_EF) & 15)))) & 7u));
    asm volatile("fence.mbarrier_init.release.cluster;" ::: "memory");
  }
  __syncwarp();
  asm volatile("barrier.cluster.arrive.relaxed.aligned;" ::: "memory");
  if (threadIdx.x == 96 + c.zero) sts_f(sb + SM_ID + 4, __uint_as_float(cx));
  PROFT(lane == 0 && (warp == 0 || warp == 4), 225 + (warp >> 2) * 8);
  __syncwarp();
  PROFT(lane == 0 && (warp == 0 || warp == 4), 226 + (warp >> 2) * 8);
  }

  if (warp < 4) {
    asm volatile("setmaxnreg.dec.sync.aligned.u32 40;");
    PROFT(threadIdx.x == 0, 227);
    cluster_wait();
    PROFT(threadIdx.x == 0, 228);
    if (warp == 0 || warp == 3) {
    if (warp == 0) {
      STA_CTX();
      const unsigned int epoch = __shfl_sync(0xffffffffu, ld_relaxed(&g_epoch), 0), xbase = epoch * NLAYERS;
      (void)xbase;
      const uint64_t ordg = k_order(g);
      mbar_wait_u(BA(B_ID), 0);
      const int rb = (__shfl_sync(0xffffffffu, LD_ID(), 0) >> 3) & 15, m0 = rb * 128;
      tma_2d_e(sb + XS * SLOT, &maps.m[MAP_X0], (kf & ~1) * 64, m0, BA(FM));
      tma_2d_e(sb + (XS + 1) * SLOT, &maps.m[MAP_X0], (kf | 1) * 64, m0, BA(FM + 1));
      if (X0AT) {
        mbar_wait_u(BA(B_RAW + X0AT - 1), 0);
        tma_2d_e(sb + 11 * SLOT, &maps.m[MAP_X0], g * 128, m0, BA(B_X0));
        tma_2d_e(sb + 12 * SLOT, &maps.m[MAP_X0], g * 128 + 64, m0, BA(B_X0));
        expect_tx_e(BA(B_X0), 32768);
      }
#pragma unroll 1
      for (int lp = 0; lp < 2 * NLAYERS; ++lp) {
        const int layer = lp >> 1, n1 = (lp & 1) ? NAOP : NAOP - 14;
        int n = (lp & 1) ? NAOP - 14 : 0;
        const uint64_t ord = lp ? ordg : k_order(kf >> 1);
        uint32_t ready = lp ? 0u : 0xFFFFu, nop = c_aop[n];
        const unsigned int* fl = ((lp & 1) ? g_of : g_xf) + rb * 32;
        const CUtensorMap* tm = &maps.m[(lp & 1) ? MAP_O : lp ? MAP_X : MAP_X0];
        const uint32_t skip = layer ? 1u << 25 : 9u << 22;
        if (lp) mbar_wait_u(BA((lp & 1) ? B_OH0 : B_XH0), ((lp - 1) >> 1) & 1);
#pragma unroll 1
        for (; n < n1; ++n) {
          const uint32_t op = nop;
          nop = c_aop[n + 1];
          const uint32_t kb = (uint32_t)(ord >> ((op >> 2) & 60)) & 15;
          uint32_t dst = sb + (op & 15) * SLOT, kc = kb * 64, fb = bar + ((op >> 5) & 0x3F8), need = ~ready & (1u << kb);
          asm volatile("" : "+r"(dst), "+r"(kc), "+r"(fb), "+r"(need));
          const uint32_t eb = bar + ((op >> 12) & 0x3F8), ep = (layer ^ (op >> 22)) & 1;
          bool fr = op & skip;
          if (need) {
            if (!fr) fr = __all_sync(0xffffffffu, mbar_test_wait(eb, ep));
            PROFT(lane == 0 && (n == 0 || n == NAOP - 14), 64 + layer * 16 + (n ? 2 : 0));
            src_wait<0>(fl, xbase + layer + 1, need, ready, lane);
            fence_async_all();
          }
          if (!fr) mbar_wait_u(eb, ep);
          tma_2d_e(dst, tm, kc, m0, fb);
          PROFT(lane == 0 && (n == 0 || n == NAOP - 14), 64 + layer * 16 + (n ? 3 : 1));
          PROFL(lane == 0 && layer == PL && n >= NAOP - 14, 178 + n - (NAOP - 14));
          PROFL(lane == 0 && layer == PL + 1 && n < 4, 242 + n);
        }
      }
    } else {
      STA_CTX();
      const unsigned int epoch = __shfl_sync(0xffffffffu, ld_relaxed(&g_epoch), 0), xbase = epoch * NLAYERS;
      (void)xbase;
      const uint64_t ordg = k_order(g);
#pragma unroll 1
      for (int layer = 0; layer < NLAYERS; ++layer) {
        const uint64_t ordq = layer ? ordg : k_order(kf >> 1);
        uint32_t ready = layer ? 0xFFFFu : 0u, nop = c_wop[0];
        const CUtensorMap* tq = &maps.m[(layer & 1) ? MAP_WB : MAP_WF];
        const CUtensorMap* tk = &maps.m[(layer & 1) ? MAP_WB : cr ? MAP_WA : MAP_WF];
        const uint32_t skip = layer ? 1u << 25 : 9u << 22, pm = layer ? 0xE0u : 0u;
        int n = 0;
#pragma unroll 1
        for (; n < NWOP - 16; ++n) {
          const uint32_t op = nop;
          nop = c_wop[n + 1];
          const uint32_t isq = (op >> 23) & 1, fb = bar + ((op >> 5) & 0x3F8);
          const uint32_t kb = (uint32_t)(ordq >> ((op >> 2) & 60)) & 15;
          const CUtensorMap* tm = (isq ? tq : tk) + ((op & pm) ? 1 : 0);
          const uint32_t dst = sb + (op & 15) * SLOT + cr * (isq ? 8192 : SLOT);
          const int col = g * 128 + (isq ? cr * 64 : 1024 + cr * 1024);
          if (layer == 0) {
            if ((op & 0x7E00) == 0) continue;
            const uint32_t need = ((isq || !cr) ? 1u << kb : 0u) | (((op >> 22) & 1) ? 0u : (((op >> 15) & 127) == CM ? 1u : 3u) << (kf & ~1));
            if ((ready & need) != need) {
              src_wait<0>(g_wff + g * 32, epoch + 1, need, ready, lane);
              fence_async_all();
            }
            if ((op & 15) >= 11) mbar_wait_u(BA(B_XT), 0);
          }
          wait_tma_5d_mc(!(op & skip), bar + ((op >> 12) & 0x3F8), (layer ^ (op >> 22)) & 1, dst, tm, col, 2 * kb, fb);
          if (!isq) tma_5d_mc_e(dst + 8192, tm, col + 64, 2 * kb, fb);
          if (op >> 26) expect_tx_e(fb, (op >> 26) * 8192);
          PROFL(lane == 0 && layer == PL + 1 && n < 16, 128 + n);
        }
        const CUtensorMap* to = &maps.m[(layer & 1) ? MAP_WOB : MAP_WOA];
#pragma unroll 1
        for (; n < NWOP; ++n) {
          const uint32_t op = nop;
          nop = c_wop[n + 1];
          const uint32_t fb = bar + ((op >> 5) & 0x3F8), kb = (uint32_t)(ordg >> ((op >> 2) & 60)) & 15;
          if (WH < 16 && n == NWOP - 16 + WH && !(layer & 1)) mbar_wait_u(BA(B_KVS), (layer >> 1) & 1);
          wait_tma_5d_mc(!((op >> 25) & 1), bar + ((op >> 12) & 0x3F8), layer & 1, sb + (op & 15) * SLOT + cr * 8192, to + ((op & 0xE0) ? 1 : 0), g * 128 + cr * 64, 2 * kb, fb);
          expect_tx_e(fb, (op >> 26) * 8192);
          PROFL(lane == 0 && layer == PL, 144 + ((op >> 8) & 127) - FW);
        }
      }
    }
    } else if (warp == 1) {
      STA_CTX();
      const unsigned int epoch = __shfl_sync(0xffffffffu, ld_relaxed(&g_epoch), 0), xbase = epoch * NLAYERS;
      (void)xbase;
      if (lane == 0) {
        mbar_wait_s(BA(B_WFD), 0);
        PROFT(true, 229);
#pragma unroll 1
        for (int j = 0; j < 4; ++j) tma_store_5d(&maps.m[MAP_WF], sb + (j < 2 ? 2 * cr : 9 + cr) * SLOT + (j & 1) * 8192, (j < 2 ? 1024 : 0) + g * 128 + (j & 1) * 64, 2 * kf);
        bulk_commit();
        bulk_wait0();
        PROFT(true, 230);
        fence_async_all();
        flag_set(g_wff + g * 32 + kf, epoch + 1);
        mbar_wait_s(BA(B_ID), 0);
        PROFT(true, 64 + 13);
#pragma unroll 1
        for (int e = 0; e < NLAYERS; ++e) {
          BASE_CTX();
          bid_ -= c.boff;
          DYN_CTX(LD_ID());
          if (e > 0) {
            mbar_wait_s(BA(B_XH0), (e - 1) & 1);
            PROFT(e == PL + 1, 240);
            flag_set(g_xf + rb * 32 + 2 * g, xbase + e + 1);
            PROFT(e == PL + 1, 241);
          }
          mbar_wait_s(BA(B_XDONE), e & 1);
          PROFT(true, 64 + e * 16 + 4);
          flag_set(g_xf + rb * 32 + 2 * g + 1, xbase + e + 1);
          if (e == 0) {
            flag_add(&g_csflag[g].v);
#pragma unroll 1
            for (int i = 0; i < 4; ++i) {
              mbar_wait_s(BA(CM + PFM + PFS * i), 0);
              l2_prefetch(i < 3 ? wB + (size_t)(i * 128 + bid_) * 8192 : woA + (size_t)bid_ * 8192, 16384);
            }
          }
          if (e == 1) l2_prefetch(woB + (size_t)bid_ * 8192, 16384);
          PROFT(true, 64 + e * 16 + 7);
          if ((e & 1) == 0) {
            bf16* kvl = g_kv + ((size_t)((epoch & 1) * 2 + (e >> 1)) * 8 + g) * 10240;
#pragma unroll 1
            for (int hp = 0; hp < 2; ++hp) {
              mbar_wait_s(BA(B_KVDONE), hp);
#pragma unroll 1
              for (int i = 0; i < 4; ++i) {
                const int ch = (i + (rb >> 2)) & 3;
                bulk_red_add(kvl + hp * 5120 + ch * 1280, sb + VB + hp * SLOT + (ch >> 1) * 8192 + (ch & 1) * 2560, 2560);
                bulk_commit();
              }
              bulk_wait0();
              PROFT(true, 64 + e * 16 + (hp ? 10 : 6));
              fence_async_all();
              flag_add(&g_kvflag[hp * 8 + g].v);
              mbar_arrive(BA(hp ? B_KVS : B_KVS0));
              PROFT(e > 0 && hp, 64 + e * 16 + 8);
            }
          }
          if (e & 1) {
            mbar_wait_s(BA(B_OF0), (e >> 1) & 1);
            flag_set(g_hf + rb * 32 + g, xbase + e + 1);
            if (rb) flag_wait(g_hf + (rb - 1) * 32 + g, xbase + e + 1);
            fence_async_all();
            mbar_expect_tx(BA(B_HALO), 8192);
            bulk_load(sb + SM_SD, g_halo + (size_t)(((e >> 1) * 17 + rb) * 8 + g) * 2048, 8192, BA(B_HALO));
            PROFT(true, 64 + e * 16 + 15);
          }
          mbar_wait_s(BA(B_OH0), e & 1);
          PROFT(e > 0, 64 + e * 16 + 13);
          flag_set(g_of + rb * 32 + 2 * g, xbase + e + 1);
          PROFT(true, 64 + e * 16 + 9);
          mbar_wait_s(BA(B_OH1), e & 1);
          PROFT(true, 64 + e * 16 + 5);
          flag_set(g_of + rb * 32 + 2 * g + 1, xbase + e + 1);
          PROFT(true, 64 + e * 16 + 11);
        }
        if (bid_ == 0) g_epoch = epoch + 1;
      }
    } else {
      STA_CTX();
      const unsigned int epoch = __shfl_sync(0xffffffffu, cx, 0), xbase = epoch * NLAYERS;
      (void)xbase;
      uint32_t idp = kf >> 1;
      if (g >= 4) {
        uint32_t v, n = 0;
#pragma unroll 1
        do { v = __shfl_sync(0xffffffffu, ld_relaxed(&g_rot), 0); } while ((v >> 3) != ((epoch + 1) & 0x1FFFFFFFu) && ++n < (1u << 20));
        const uint32_t c0 = (8 - v) & 7;
        idp = idp == 0 ? c0 : idp - 1 + (idp - 1 >= c0 ? 1 : 0);
      }
      idp = g | ((2 * idp + cr) << 3) | ((epoch & 1) << 8);
      if (lane == 0) {
        sts_f(sb + SM_ID, __uint_as_float(idp));
        mbar_arrive(BA(B_ID));
      }
      PROFT(lane == 0, 231);
      if (lane < 16) sts_f(sb + SM_RS + lane * 4, 0.f);
#pragma unroll 1
      for (int layer = 0; layer < NLAYERS; ++layer) {
#define HLP_CTX() BASE_CTX(); uint32_t idl_ = idp; asm volatile("" : "+r"(idl_)); DYN_CTX(idl_); int lane = threadIdx.x & 31; asm volatile("" : "+r"(lane)); const bool isB = layer & 1, hal = isB && rb > 0; (void)hal;
#pragma unroll 1
        for (int ph = 0; ph < 2; ++ph) {
          HLP_CTX();
          if (ph == (layer == 0)) {
            const float* cs = g_cs + (epoch & 1) * 6144 + g * 384;
            if (layer) mbar_wait_u(BA(CT), (layer - 1) & 1);
            if (layer < 2) {
              if (lane == 0) flag_wait_slow(&g_csflag[isB ? 8 : g].v, isB ? epoch * 4u + 4u : epoch * 16u + 16u);
              __syncwarp();
            }
#pragma unroll 1
            for (int i0 = 0; i0 < 12; i0 += 4) {
              float a[4];
#pragma unroll
              for (int i = 0; i < 4; ++i) a[i] = __ldcg(cs + isB * 3072 + (i0 + i) * 32 + lane);
#pragma unroll
              for (int i = 0; i < 4; ++i) {
                const float c1 = bf16r(a[i]), c2 = bf16r(a[i] - c1), c3 = (a[i] - c1) - c2;
                sts128(sb + SM_BP + ((i0 + i) * 32 + lane) * 16, make_uint4(pack_bf16(c1, c2), pack_bf16(c3, 0.f), 0u, 0u));
              }
            }
          } else {
            uint32_t rdy = 0u;
            mbar_wait_u(BA(CM + 3), layer & 1);
            src_wait<128>(g_xf + rb * 32, xbase + layer + 1, 0xAAAAu, rdy, lane);
            rdy = 0u;
            if (hal) src_wait<128>(g_xf + (rb - 1) * 32, xbase + layer + 1, 0xAAAAu, rdy, lane);
            const float2* sp = g_stats + ((epoch & 1) * 4 + layer) * S_ + m0 + lane;
            float2 u[5];
#pragma unroll
            for (int i = 0; i < 4; ++i) u[i] = __ldcg(sp + i * 32);
            u[4] = __ldcg(sp - (hal ? 16 : 0));
#pragma unroll 1
            for (int i = 0; i < 5; ++i) {
              const float mean = u[0].x * (1.f / D_);
              const float var = fmaxf(fmaf(-u[0].x, mean, u[0].y) * (1.f / D_), 0.f);
              const float sd = bf16r(sqrtf(bf16r(bf16r(var) + 1e-5f)));
              const int R = i * 32 + lane;
              if (i < 4) {
                const float hm = -0.5f * bf16r(mean);
                if (!isB) sts128(sb + SM_SD + R * 64 + ((R >> 1) & 3) * 16, make_uint4(__float_as_uint(sd) >> 16, __float_as_uint(sd) >> 16, __float_as_uint(sd) >> 16, __float_as_uint(sd) >> 16));
                sts128(sb + SM_AP + R * 16, make_uint4(pack_bf16(hm, hm), pack_bf16(hm, 0.f), 0u, 0u));
              }
              if (i < 4 || (hal && lane < 16)) sts_f(sb + SM_RS + (i < 4 ? 16 + R : lane) * 4, __fdividef(1.f, sd));
#pragma unroll
              for (int j = 0; j < 4; ++j) u[j] = u[j + 1];
            }
            PROFT(lane == 0, 64 + layer * 16 + 12);
          }
        }
        HLP_CTX();
        fence_async_smem();
        __syncwarp();
        if (lane == 0) mbar_arrive(BA(B_STAT));
        PROFT(lane == 0, 64 + layer * 16 + 14);
        if (!isB && lane == 0) {
#pragma unroll 1
          for (int hp = 0; hp < 2; ++hp) {
            mbar_wait_s(BA(hp ? B_KVS : B_KVS0), (layer >> 1) & 1);
            flag_wait(&g_kvflag[hp * 8 + g].v, epoch * (16u * ((NLAYERS + 1) / 2)) + 16u * ((layer >> 1) + 1));
            const bf16* kvl = g_kv + ((size_t)((epoch & 1) * 2 + (layer >> 1)) * 8 + g) * 10240 + hp * 5120;
            const uint32_t kb = BA(hp ? B_KVF1 : B_KVF);
            fence_async_all();
            mbar_expect_tx(kb, 10240);
            bulk_load(sb + VB + hp * SLOT, kvl, 5120, kb);
            bulk_load(sb + VB + hp * SLOT + 8192, kvl + 2560, 5120, kb);
            PROFT(hp == 0, 64 + layer * 16 + 15);
          }
        }
        __syncwarp();
      }
    }
    __syncwarp();
    asm volatile("barrier.cluster.arrive.relaxed.aligned;" ::: "memory");
    cluster_wait();
  } else {
    asm volatile("setmaxnreg.inc.sync.aligned.u32 232;");
    PROFT(threadIdx.x == 128, 235);
    cluster_wait();
    PROFT(threadIdx.x == 128, 236);
    consumer(c);
    asm volatile("bar.warp.sync 0xffffffff;\nbarrier.cluster.arrive.relaxed.aligned;\nbarrier.cluster.wait.aligned;\n" ::: "memory");
  }
}

typedef CUresult (*PFN_encodeTiled)(CUtensorMap*, CUtensorMapDataType, cuuint32_t, void*, const cuuint64_t*, const cuuint64_t*,
                                    const cuuint32_t*, const cuuint32_t*, CUtensorMapInterleave, CUtensorMapSwizzle,
                                    CUtensorMapL2promotion, CUtensorMapFloatOOBfill);

static void make_map2(PFN_encodeTiled enc, CUtensorMap* m, const void* ptr, uint64_t cols, uint64_t rows, uint32_t box_c, uint32_t box_r) {
  cuuint64_t dims[2] = {cols, rows};
  cuuint64_t strides[1] = {cols * 2};
  cuuint32_t box[2] = {box_c, box_r};
  cuuint32_t es[2] = {1, 1};
  CUresult r = enc(m, CU_TENSOR_MAP_DATA_TYPE_BFLOAT16, 2, const_cast<void*>(ptr), dims, strides, box, es, CU_TENSOR_MAP_INTERLEAVE_NONE,
                   box_c == 64 ? CU_TENSOR_MAP_SWIZZLE_128B : CU_TENSOR_MAP_SWIZZLE_64B, CU_TENSOR_MAP_L2_PROMOTION_L2_256B, CU_TENSOR_MAP_FLOAT_OOB_FILL_NONE);
  (void)r;
}
static void make_map5(PFN_encodeTiled enc, CUtensorMap* m, const void* ptr, uint64_t cols) {
  for (int p = 0; p < 2; ++p) {
    cuuint64_t dims[5] = {cols, 2, 4, 4, 32};
    cuuint64_t strides[4] = {cols * 2, cols * (p ? 16 : 4), cols * (p ? 4 : 16), cols * 64};
    cuuint32_t box[5] = {64, 2, 4, 4, 2};
    cuuint32_t es[5] = {1, 1, 1, 1, 1};
    CUresult r = enc(m + p, CU_TENSOR_MAP_DATA_TYPE_BFLOAT16, 5, const_cast<void*>(ptr), dims, strides, box, es, CU_TENSOR_MAP_INTERLEAVE_NONE,
                     CU_TENSOR_MAP_SWIZZLE_128B, CU_TENSOR_MAP_L2_PROMOTION_L2_256B, CU_TENSOR_MAP_FLOAT_OOB_FILL_NONE);
    (void)r;
  }
}

extern "C" void kernel_launch(void* const* d_in, const int* in_sizes, int n_in, void* d_out, int out_size) {
  const bf16* A_x = (const bf16*)d_in[0];
  const bf16* A_wqkv = (const bf16*)d_in[1];
  const bf16* A_wphi = (const bf16*)d_in[2];
  const bf16* A_wo = (const bf16*)d_in[3];
  const bf16* B_wqkv = (const bf16*)d_in[5];
  const bf16* B_wo = (const bf16*)d_in[6];
  bf16* out = (bf16*)d_out;

  static PFN_encodeTiled enc = nullptr;
  static bf16 *p_x, *p_o, *p_wf;
  static uint32_t boff;
  if (!enc) {
    void* fn = nullptr; cudaDriverEntryPointQueryResult qr;
    cudaGetDriverEntryPoint("cuTensorMapEncodeTiled", &fn, cudaEnableDefault, &qr);
    enc = (PFN_encodeTiled)fn;
    cudaGetSymbolAddress((void**)&p_x, g_x);
    cudaGetSymbolAddress((void**)&p_o, g_o);
    cudaGetSymbolAddress((void**)&p_wf, g_wf);
    cudaFuncSetAttribute(mega_kernel, cudaFuncAttributeMaxDynamicSharedMemorySize, SM_TOTAL);
    cudaLaunchConfig_t cfg = {};
    cudaLaunchAttribute at; at.id = cudaLaunchAttributeClusterDimension; at.val.clusterDim.x = 2; at.val.clusterDim.y = 1; at.val.clusterDim.z = 1;
    cfg.gridDim = dim3(132); cfg.blockDim = dim3(384); cfg.dynamicSmemBytes = SM_TOTAL; cfg.attrs = &at; cfg.numAttrs = 1;
    int nc = 0;
    if (cudaOccupancyMaxActiveClusters(&nc, mega_kernel, &cfg) != cudaSuccess) { nc = 0; (void)cudaGetLastError(); }
    boff = nc >= 66 ? 0u : 4u;
  }
  Maps maps;
  make_map5(enc, &maps.m[MAP_WF], p_wf, 2048);
  make_map5(enc, &maps.m[MAP_WA], A_wqkv, 3072);
  make_map5(enc, &maps.m[MAP_WB], B_wqkv, 3072);
  make_map5(enc, &maps.m[MAP_WOA], A_wo, 1024);
  make_map5(enc, &maps.m[MAP_WOB], B_wo, 1024);
  make_map2(enc, &maps.m[MAP_X0], A_x, 1024, 2048, 64, 128);
  make_map2(enc, &maps.m[MAP_X], p_x, 1024, 2048, 64, 128);
  make_map2(enc, &maps.m[MAP_O], p_o, 1024, 2048, 64, 128);
  make_map2(enc, &maps.m[MAP_PHI], A_wphi, 32, 1024, 32, 128);
  Ctx c; c.zero = 0u; c.boff = boff; c.x0 = A_x; c.out = out;
  mega_kernel<<<132, 384, SM_TOTAL, cudaStreamPerThread>>>(maps, c, A_wqkv, B_wqkv, A_wo, B_wo);
}
```

```cpp
#include <cuda_runtime.h>
#include <cuda_bf16.h>
#include <cuda.h>
#include <stdint.h>

typedef __nv_bfloat16 bf16;

constexpr int S_ = 2048, D_ = 1024;

struct __align__(128) Flag { unsigned int v; unsigned int pad[31]; };
__device__ __align__(1024) bf16 g_x[S_ * D_];
__device__ __align__(1024) bf16 g_o[S_ * D_];
__device__ __align__(1024) uint32_t g_halo[2 * 17 * 8 * 2048];
__device__ __align__(1024) bf16 g_kv[2 * 8 * 10240];
__device__ __align__(1024) float2 g_stats[2 * 4 * S_];
__device__ __align__(1024) float g_cs[2 * 2 * 3072];
__device__ __align__(1024) bf16 g_wf[D_ * 2048];
__device__ Flag g_kvflag[16], g_csflag[10];
__device__ __align__(128) unsigned int g_xf[16 * 32], g_of[16 * 32];
__device__ __align__(128) unsigned int g_hf[16 * 32];
__device__ __align__(128) unsigned int g_wff[8 * 32];
__device__ unsigned int g_epoch, g_rot, g_err;
#define PROFT(cond, idx) asm volatile("" ::: "memory")

#define SUSP 20000
__device__ __forceinline__ uint32_t smem_u32(const void* p) { return (uint32_t)__cvta_generic_to_shared(p); }
__device__ __forceinline__ void mbar_init(uint32_t bar, uint32_t count) {
  asm volatile("mbarrier.init.shared::cta.b64 [%0], %1;" ::"r"(bar), "r"(count) : "memory");
}
__device__ __forceinline__ void mbar_expect_tx(uint32_t bar, uint32_t bytes) {
  asm volatile("mbarrier.arrive.expect_tx.shared::cta.b64 _, [%0], %1;" ::"r"(bar), "r"(bytes) : "memory");
}
__device__ __forceinline__ void mbar_arrive(uint32_t bar) {
  asm volatile("mbarrier.arrive.shared::cta.b64 _, [%0];" ::"r"(bar) : "memory");
}
__device__ __forceinline__ bool mbar_try_wait(uint32_t bar, uint32_t parity) {
  uint32_t ok;
  asm volatile("{\n.reg .pred p;\nmbarrier.try_wait.parity.shared::cta.b64 p, [%1], %2;\nselp.b32 %0, 1, 0, p;\n}\n"
               : "=r"(ok) : "r"(bar), "r"(parity) : "memory");
  return ok != 0;
}
__device__ __forceinline__ bool mbar_try_wait_s(uint32_t bar, uint32_t parity) {
  uint32_t ok;
  asm volatile("{\n.reg .pred p;\nmbarrier.try_wait.parity.shared::cta.b64 p, [%1], %2, %3;\nselp.b32 %0, 1, 0, p;\n}\n"
               : "=r"(ok) : "r"(bar), "r"(parity), "r"(SUSP) : "memory");
  return ok != 0;
}
__device__ __forceinline__ void mbar_wait_s(uint32_t bar, uint32_t parity) {
  uint32_t n = 0;
  bool ok;
#pragma unroll 1
  do { ++n; ok = mbar_try_wait_s(bar, parity); } while (!ok && n < (1u << 12));
}
__device__ __forceinline__ bool mbar_test_wait(uint32_t bar, uint32_t parity) {
  uint32_t ok;
  asm volatile("{\n.reg .pred p;\nmbarrier.test_wait.parity.shared::cta.b64 p, [%1], %2;\nselp.b32 %0, 1, 0, p;\n}\n"
               : "=r"(ok) : "r"(bar), "r"(parity) : "memory");
  return ok != 0;
}
__device__ __forceinline__ uint64_t gtimer() {
  uint64_t t; asm volatile("mov.u64 %0, %globaltimer;" : "=l"(t)); return t;
}
__device__ __forceinline__ void mbar_wait(uint32_t bar, uint32_t parity) {
  uint32_t n = 0;
  bool ok;
#pragma unroll 1
  do { ++n; ok = mbar_try_wait(bar, parity); } while (!ok && n < (1u << 22));
}
__device__ __forceinline__ unsigned int ld_acquire(const unsigned int* p) {
  unsigned int v; asm volatile("ld.acquire.gpu.global.u32 %0, [%1];" : "=r"(v) : "l"(p) : "memory"); return v;
}
__device__ __forceinline__ void flag_add(unsigned int* p) {
  asm volatile("red.release.gpu.global.add.u32 [%0], 1;" ::"l"(p) : "memory");
}
__device__ __forceinline__ void flag_set(unsigned int* p, unsigned int v) {
  asm volatile("st.release.gpu.global.u32 [%0], %1;" ::"l"(p), "r"(v) : "memory");
}
template <int SLEEP>
__device__ __forceinline__ void src_wait(const unsigned int* f, unsigned int target, uint32_t need, uint32_t& ready, int lane) {
  uint32_t n = 0;
#pragma unroll 1
  while ((ready & need) != need) {
    const unsigned int v = ld_acquire(f + (lane & 15));
    ready = __ballot_sync(0xffffffffu, (int)(v - target) >= 0);
    if (SLEEP) { if ((ready & need) != need) __nanosleep(SLEEP); }
    if (++n > (1u << 20)) break;
  }
  __syncwarp();
}
__device__ __forceinline__ unsigned int ld_relaxed(const unsigned int* p);
__device__ __forceinline__ unsigned int ld_relaxed(const unsigned int* p) {
  unsigned int v; asm volatile("ld.relaxed.gpu.global.u32 %0, [%1];" : "=r"(v) : "l"(p) : "memory"); return v;
}
template <int SLEEP>
__device__ __forceinline__ void flag_wait_t(const unsigned int* p, unsigned int target) {
  uint32_t n = 0;
#pragma unroll 1
  while ((int)(ld_acquire(p) - target) < 0) {
    if (SLEEP) __nanosleep(SLEEP);
    if (++n > (1u << 20)) break;
  }
}
__device__ __forceinline__ void flag_wait(const unsigned int* p, unsigned int target) { flag_wait_t<0>(p, target); }
__device__ __forceinline__ void flag_wait_slow(const unsigned int* p, unsigned int target) { flag_wait_t<256>(p, target); }
__device__ __forceinline__ void mbar_wait_u(uint32_t bar, uint32_t parity) {
  uint32_t n = 0;
#pragma unroll 1
  while (!__all_sync(0xffffffffu, SUSP ? mbar_try_wait_s(bar, parity) : mbar_try_wait(bar, parity))) {
    if (++n > (SUSP ? 1u << 12 : 1u << 22)) break;
  }
}
__device__ __forceinline__ void expect_tx_e(uint32_t bar, uint32_t bytes) {
  asm volatile("{\n.reg .pred p;\nelect.sync _|p, 0xffffffff;\n@p mbarrier.arrive.expect_tx.shared::cta.b64 _, [%0], %1;\n}\n" ::"r"(bar), "r"(bytes) : "memory");
}
__device__ __forceinline__ void tma_2d_e(uint32_t dst, const CUtensorMap* tm, int c0, int c1, uint32_t bar) {
  asm volatile("{\n.reg .pred p;\nelect.sync _|p, 0xffffffff;\n"
               "@p cp.async.bulk.tensor.2d.shared::cluster.global.mbarrier::complete_tx::bytes [%0], [%1, {%2, %3}], [%4];\n}\n"
               ::"r"(dst), "l"(tm), "r"(c0), "r"(c1), "r"(bar) : "memory");
}
__device__ __forceinline__ void tma_5d_e(uint32_t dst, const CUtensorMap* tm, int c0, int c4, uint32_t bar) {
  asm volatile("{\n.reg .pred p;\nelect.sync _|p, 0xffffffff;\n"
               "@p cp.async.bulk.tensor.5d.shared::cluster.global.mbarrier::complete_tx::bytes [%0], [%1, {%2, %5, %5, %5, %3}], [%4];\n}\n"
               ::"r"(dst), "l"(tm), "r"(c0), "r"(c4), "r"(bar), "r"(0) : "memory");
}
__device__ __forceinline__ void tma_5d_mc_e(uint32_t dst, const CUtensorMap* tm, int c0, int c4, uint32_t bar) {
  asm volatile("{\n.reg .pred p;\nelect.sync _|p, 0xffffffff;\n"
               "@p cp.async.bulk.tensor.5d.shared::cluster.global.mbarrier::complete_tx::bytes.multicast::cluster [%0], [%1, {%2, %6, %6, %6, %3}], [%4], %5;\n}\n"
               ::"r"(dst), "l"(tm), "r"(c0), "r"(c4), "r"(bar), "h"((uint16_t)3), "r"(0) : "memory");
}
__device__ __forceinline__ void wait_tma_5d_mc(bool w, uint32_t eb, uint32_t par, uint32_t dst, const CUtensorMap* tm, int c0, int c4, uint32_t fb) {
  asm volatile("" : "+r"(dst), "+l"(tm), "+r"(c0), "+r"(c4), "+r"(fb));
  if (w) mbar_wait_u(eb, par);
  tma_5d_mc_e(dst, tm, c0, c4, fb);
}
__device__ __forceinline__ void stg128(void* p, uint32_t a, uint32_t b, uint32_t c, uint32_t d) {
  asm volatile("st.global.v4.u32 [%0], {%1,%2,%3,%4};" ::"l"(p), "r"(a), "r"(b), "r"(c), "r"(d) : "memory");
}
__device__ __forceinline__ void stg128_p(bool on, void* p, uint32_t a, uint32_t b, uint32_t c, uint32_t d) {
  asm volatile("{\n.reg .pred p;\nsetp.ne.b32 p, %5, 0;\n@p st.global.v4.u32 [%0], {%1,%2,%3,%4};\n}\n" ::"l"(p), "r"(a), "r"(b), "r"(c), "r"(d), "r"((int)on) : "memory");
}
__device__ __forceinline__ void ldg128(const void* p, uint32_t& a, uint32_t& b, uint32_t& c, uint32_t& d) {
  asm volatile("ld.global.cg.v4.u32 {%0,%1,%2,%3}, [%4];" : "=r"(a), "=r"(b), "=r"(c), "=r"(d) : "l"(p) : "memory");
}
__device__ __forceinline__ void release2c(uint32_t off) {
  asm volatile("mbarrier.arrive.shared::cluster.b64 _, [%0];\nmbarrier.arrive.shared::cluster.b64 _, [%1];" ::"r"(off), "r"(off + (1u << 24)) : "memory");
}
__device__ __forceinline__ void tma_store_5d(const CUtensorMap* tm, uint32_t src, int c0, int c4) {
  asm volatile("cp.async.bulk.tensor.5d.global.shared::cta.bulk_group [%0, {%2, %4, %4, %4, %3}], [%1];"
               ::"l"(tm), "r"(src), "r"(c0), "r"(c4), "r"(0) : "memory");
}
__device__ __forceinline__ void bulk_load(uint32_t dst, const void* src, uint32_t bytes, uint32_t bar) {
  asm volatile("cp.async.bulk.shared::cluster.global.mbarrier::complete_tx::bytes [%0], [%1], %2, [%3];" ::"r"(dst), "l"(src), "r"(bytes), "r"(bar) : "memory");
}
__device__ __forceinline__ void bulk_red_add(void* dst, uint32_t src, uint32_t bytes) {
  asm volatile("cp.reduce.async.bulk.global.shared::cta.bulk_group.add.noftz.bf16 [%0], [%1], %2;" ::"l"(dst), "r"(src), "r"(bytes) : "memory");
}
__device__ __forceinline__ void bulk_commit() { asm volatile("cp.async.bulk.commit_group;" ::: "memory"); }
__device__ __forceinline__ void bulk_wait0() { asm volatile("cp.async.bulk.wait_group 0;" ::: "memory"); }
__device__ __forceinline__ void fence_async_smem() { asm volatile("fence.proxy.async.shared::cta;" ::: "memory"); }
__device__ __forceinline__ void fence_async_all() { asm volatile("fence.proxy.async.global;" ::: "memory"); }
__device__ __forceinline__ void wgmma_fence() { asm volatile("wgmma.fence.sync.aligned;" ::: "memory"); }
__device__ __forceinline__ void wgmma_commit() { asm volatile("wgmma.commit_group.sync.aligned;" ::: "memory"); }
template <int N> __device__ __forceinline__ void wgmma_wait() { asm volatile("wgmma.wait_group.sync.aligned %0;" ::"n"(N) : "memory"); }
__device__ __forceinline__ void cluster_wait() { asm volatile("barrier.cluster.wait.acquire.aligned;" ::: "memory"); }
template <int ID, int N> __device__ __forceinline__ void nbar() { asm volatile("bar.sync %0, %1;" ::"n"(ID), "n"(N) : "memory"); }
__device__ __forceinline__ uint64_t desc64(uint32_t lo, uint32_t hi) { return (uint64_t)lo | ((uint64_t)hi << 32); }
__device__ __forceinline__ uint32_t pack_bf16(float lo, float hi) {
  uint32_t r; asm("cvt.rn.bf16x2.f32 %0, %1, %2;" : "=r"(r) : "f"(hi), "f"(lo)); return r;
}
__device__ __forceinline__ uint32_t add_bf16x2(uint32_t a, uint32_t b) {
  uint32_t r; asm("add.rn.bf16x2 %0, %1, %2;" : "=r"(r) : "r"(a), "r"(b)); return r;
}
__device__ __forceinline__ float bf16r(float x) { return __bfloat162float(__float2bfloat16_rn(x)); }
__device__ __forceinline__ float bf_lo(uint32_t u) { return __uint_as_float(u << 16); }
__device__ __forceinline__ float bf_hi(uint32_t u) { return __uint_as_float(u & 0xFFFF0000u); }
__device__ __forceinline__ float ex2(float x) { float r; asm("ex2.approx.ftz.f32 %0, %1;" : "=f"(r) : "f"(x)); return r; }
__device__ __forceinline__ float rcp(float x) { float r; asm("rcp.approx.ftz.f32 %0, %1;" : "=f"(r) : "f"(x)); return r; }
__device__ __forceinline__ void mma_bf16(float (&d)[4], uint32_t a0, uint32_t a1, uint32_t a2, uint32_t a3, uint32_t b0, uint32_t b1) {
  asm("mma.sync.aligned.m16n8k16.row.col.f32.bf16.bf16.f32 {%0,%1,%2,%3}, {%4,%5,%6,%7}, {%8,%9}, {%0,%1,%2,%3};"
               : "+f"(d[0]), "+f"(d[1]), "+f"(d[2]), "+f"(d[3]) : "r"(a0), "r"(a1), "r"(a2), "r"(a3), "r"(b0), "r"(b1));
}
__device__ __forceinline__ void ldsm_x4(uint32_t& r0, uint32_t& r1, uint32_t& r2, uint32_t& r3, uint32_t addr) {
  asm volatile("ldmatrix.sync.aligned.m8n8.x4.shared.b16 {%0,%1,%2,%3}, [%4];"
               : "=r"(r0), "=r"(r1), "=r"(r2), "=r"(r3) : "r"(addr) : "memory");
}
__device__ __forceinline__ void ldsm_x4_t(uint32_t& r0, uint32_t& r1, uint32_t& r2, uint32_t& r3, uint32_t addr) {
  asm volatile("ldmatrix.sync.aligned.m8n8.x4.trans.shared.b16 {%0,%1,%2,%3}, [%4];"
               : "=r"(r0), "=r"(r1), "=r"(r2), "=r"(r3) : "r"(addr) : "memory");
}
__device__ __forceinline__ void stsm_x4(uint32_t addr, uint32_t r0, uint32_t r1, uint32_t r2, uint32_t r3) {
  asm volatile("stmatrix.sync.aligned.m8n8.x4.shared.b16 [%0], {%1,%2,%3,%4};"
               ::"r"(addr), "r"(r0), "r"(r1), "r"(r2), "r"(r3) : "memory");
}
__device__ __forceinline__ void stsm_x2(uint32_t addr, uint32_t r0, uint32_t r1) {
  asm volatile("stmatrix.sync.aligned.m8n8.x2.shared.b16 [%0], {%1,%2};" ::"r"(addr), "r"(r0), "r"(r1) : "memory");
}
__device__ __forceinline__ uint4 lds128(uint32_t addr) {
  uint4 v; asm volatile("ld.shared.v4.b32 {%0,%1,%2,%3}, [%4];" : "=r"(v.x), "=r"(v.y), "=r"(v.z), "=r"(v.w) : "r"(addr) : "memory"); return v;
}
__device__ __forceinline__ void sts128(uint32_t addr, uint4 v) {
  asm volatile("st.shared.v4.b32 [%0], {%1,%2,%3,%4};" ::"r"(addr), "r"(v.x), "r"(v.y), "r"(v.z), "r"(v.w) : "memory");
}
__device__ __forceinline__ float lds_f(uint32_t addr) {
  float v; asm volatile("ld.shared.f32 %0, [%1];" : "=f"(v) : "r"(addr) : "memory"); return v;
}
__device__ __forceinline__ void nbar_dyn(int id, int n) { asm volatile("bar.sync %0, %1;" ::"r"(id), "r"(n) : "memory"); }
__device__ __forceinline__ uint64_t make_desc_ns(uint32_t addr, uint32_t lbo_bytes, uint32_t sbo_bytes) {
  return (uint64_t)((addr & 0x3FFFF) >> 4) | ((uint64_t)(lbo_bytes >> 4) << 16) | ((uint64_t)(sbo_bytes >> 4) << 32);
}
__device__ __forceinline__ void sts_f(uint32_t addr, float v) { asm volatile("st.shared.f32 [%0], %1;" ::"r"(addr), "f"(v) : "memory"); }
__device__ __forceinline__ void sts64(uint32_t addr, uint32_t a, uint32_t b) {
  asm volatile("st.shared.v2.b32 [%0], {%1,%2};" ::"r"(addr), "r"(a), "r"(b) : "memory");
}
__device__ __forceinline__ void sts_f2(uint32_t addr, float a, float b) {
  asm volatile("st.shared.v2.f32 [%0], {%1,%2};" ::"r"(addr), "f"(a), "f"(b) : "memory");
}
__device__ __forceinline__ void red_add2_p(bool on, float* p, float a, float b) {
  asm volatile("{\n.reg .pred p;\nsetp.ne.b32 p, %3, 0;\n@p red.global.add.v2.f32 [%0], {%1,%2};\n}\n" ::"l"(p), "f"(a), "f"(b), "r"((int)on) : "memory");
}
__device__ __forceinline__ void red_add4(float* p, float a, float b, float c, float d) {
  asm volatile("red.global.add.v4.f32 [%0], {%1,%2,%3,%4};" ::"l"(p), "f"(a), "f"(b), "f"(c), "f"(d) : "memory");
}
__device__ __forceinline__ void red_add1(float* p, float a) {
  asm volatile("red.global.add.f32 [%0], %1;" ::"l"(p), "f"(a) : "memory");
}
__device__ __forceinline__ void l2_prefetch(const void* p, uint32_t bytes) {
  asm volatile("cp.async.bulk.prefetch.L2.global [%0], %1;" ::"l"(p), "r"(bytes) : "memory");
}

__device__ __forceinline__ void wgmma_n256(float (&d)[192], uint64_t da, uint64_t db, int scale_d) {
  asm volatile("{\n.reg .pred p;\nsetp.ne.b32 p, %130, 0;\n"
    "wgmma.mma_async.sync.aligned.m64n256k16.f32.bf16.bf16 {%0, %1, %2, %3, %4, %5, %6, %7, %8, %9, %10, %11, %12, %13, %14, %15, %16, %17, %18, %19, %20, %21, %22, %23, %24, %25, %26, %27, %28, %29, %30, %31, %32, %33, %34, %35, %36, %37, %38, %39, %40, %41, %42, %43, %44, %45, %46, %47, %48, %49, %50, %51, %52, %53, %54, %55, %56, %57, %58, %59, %60, %61, %62, %63, %64, %65, %66, %67, %68, %69, %70, %71, %72, %73, %74, %75, %76, %77, %78, %79, %80, %81, %82, %83, %84, %85, %86, %87, %88, %89, %90, %91, %92, %93, %94, %95, %96, %97, %98, %99, %100, %101, %102, %103, %104, %105, %106, %107, %108, %109, %110, %111, %112, %113, %114, %115, %116, %117, %118, %119, %120, %121, %122, %123, %124, %125, %126, %127}, %128, %129, p, 1, 1, 0, 1;\n}\n"
    : "+f"(d[0]), "+f"(d[1]), "+f"(d[2]), "+f"(d[3]), "+f"(d[4]), "+f"(d[5]), "+f"(d[6]), "+f"(d[7]), "+f"(d[8]), "+f"(d[9]), "+f"(d[10]), "+f"(d[11]), "+f"(d[12]), "+f"(d[13]), "+f"(d[14]), "+f"(d[15]), "+f"(d[16]), "+f"(d[17]), "+f"(d[18]), "+f"(d[19]), "+f"(d[20]), "+f"(d[21]), "+f"(d[22]), "+f"(d[23]), "+f"(d[24]), "+f"(d[25]), "+f"(d[26]), "+f"(d[27]), "+f"(d[28]), "+f"(d[29]), "+f"(d[30]), "+f"(d[31]), "+f"(d[32]), "+f"(d[33]), "+f"(d[34]), "+f"(d[35]), "+f"(d[36]), "+f"(d[37]), "+f"(d[38]), "+f"(d[39]), "+f"(d[40]), "+f"(d[41]), "+f"(d[42]), "+f"(d[43]), "+f"(d[44]), "+f"(d[45]), "+f"(d[46]), "+f"(d[47]), "+f"(d[48]), "+f"(d[49]), "+f"(d[50]), "+f"(d[51]), "+f"(d[52]), "+f"(d[53]), "+f"(d[54]), "+f"(d[55]), "+f"(d[56]), "+f"(d[57]), "+f"(d[58]), "+f"(d[59]), "+f"(d[60]), "+f"(d[61]), "+f"(d[62]), "+f"(d[63]), "+f"(d[64]), "+f"(d[65]), "+f"(d[66]), "+f"(d[67]), "+f"(d[68]), "+f"(d[69]), "+f"(d[70]), "+f"(d[71]), "+f"(d[72]), "+f"(d[73]), "+f"(d[74]), "+f"(d[75]), "+f"(d[76]), "+f"(d[77]), "+f"(d[78]), "+f"(d[79]), "+f"(d[80]), "+f"(d[81]), "+f"(d[82]), "+f"(d[83]), "+f"(d[84]), "+f"(d[85]), "+f"(d[86]), "+f"(d[87]), "+f"(d[88]), "+f"(d[89]), "+f"(d[90]), "+f"(d[91]), "+f"(d[92]), "+f"(d[93]), "+f"(d[94]), "+f"(d[95]), "+f"(d[96]), "+f"(d[97]), "+f"(d[98]), "+f"(d[99]), "+f"(d[100]), "+f"(d[101]), "+f"(d[102]), "+f"(d[103]), "+f"(d[104]), "+f"(d[105]), "+f"(d[106]), "+f"(d[107]), "+f"(d[108]), "+f"(d[109]), "+f"(d[110]), "+f"(d[111]), "+f"(d[112]), "+f"(d[113]), "+f"(d[114]), "+f"(d[115]), "+f"(d[116]), "+f"(d[117]), "+f"(d[118]), "+f"(d[119]), "+f"(d[120]), "+f"(d[121]), "+f"(d[122]), "+f"(d[123]), "+f"(d[124]), "+f"(d[125]), "+f"(d[126]), "+f"(d[127])
    : "l"(da), "l"(db), "r"(scale_d));
}
__device__ __forceinline__ void wgmma_n128(float (&d)[192], uint64_t da, uint64_t db, int scale_d) {
  asm volatile("{\n.reg .pred p;\nsetp.ne.b32 p, %66, 0;\n"
    "wgmma.mma_async.sync.aligned.m64n128k16.f32.bf16.bf16 {%0, %1, %2, %3, %4, %5, %6, %7, %8, %9, %10, %11, %12, %13, %14, %15, %16, %17, %18, %19, %20, %21, %22, %23, %24, %25, %26, %27, %28, %29, %30, %31, %32, %33, %34, %35, %36, %37, %38, %39, %40, %41, %42, %43, %44, %45, %46, %47, %48, %49, %50, %51, %52, %53, %54, %55, %56, %57, %58, %59, %60, %61, %62, %63}, %64, %65, p, 1, 1, 0, 1;\n}\n"
    : "+f"(d[128]), "+f"(d[129]), "+f"(d[130]), "+f"(d[131]), "+f"(d[132]), "+f"(d[133]), "+f"(d[134]), "+f"(d[135]), "+f"(d[136]), "+f"(d[137]), "+f"(d[138]), "+f"(d[139]), "+f"(d[140]), "+f"(d[141]), "+f"(d[142]), "+f"(d[143]), "+f"(d[144]), "+f"(d[145]), "+f"(d[146]), "+f"(d[147]), "+f"(d[148]), "+f"(d[149]), "+f"(d[150]), "+f"(d[151]), "+f"(d[152]), "+f"(d[153]), "+f"(d[154]), "+f"(d[155]), "+f"(d[156]), "+f"(d[157]), "+f"(d[158]), "+f"(d[159]), "+f"(d[160]), "+f"(d[161]), "+f"(d[162]), "+f"(d[163]), "+f"(d[164]), "+f"(d[165]), "+f"(d[166]), "+f"(d[167]), "+f"(d[168]), "+f"(d[169]), "+f"(d[170]), "+f"(d[171]), "+f"(d[172]), "+f"(d[173]), "+f"(d[174]), "+f"(d[175]), "+f"(d[176]), "+f"(d[177]), "+f"(d[178]), "+f"(d[179]), "+f"(d[180]), "+f"(d[181]), "+f"(d[182]), "+f"(d[183]), "+f"(d[184]), "+f"(d[185]), "+f"(d[186]), "+f"(d[187]), "+f"(d[188]), "+f"(d[189]), "+f"(d[190]), "+f"(d[191])
    : "l"(da), "l"(db), "r"(scale_d));
}
__device__ __forceinline__ void wgmma_n256_k(float (&d)[192], uint64_t da, uint64_t db, int scale_d) {
  asm volatile("{\n.reg .pred p;\nsetp.ne.b32 p, %130, 0;\n"
    "wgmma.mma_async.sync.aligned.m64n256k16.f32.bf16.bf16 {%0, %1, %2, %3, %4, %5, %6, %7, %8, %9, %10, %11, %12, %13, %14, %15, %16, %17, %18, %19, %20, %21, %22, %23, %24, %25, %26, %27, %28, %29, %30, %31, %32, %33, %34, %35, %36, %37, %38, %39, %40, %41, %42, %43, %44, %45, %46, %47, %48, %49, %50, %51, %52, %53, %54, %55, %56, %57, %58, %59, %60, %61, %62, %63, %64, %65, %66, %67, %68, %69, %70, %71, %72, %73, %74, %75, %76, %77, %78, %79, %80, %81, %82, %83, %84, %85, %86, %87, %88, %89, %90, %91, %92, %93, %94, %95, %96, %97, %98, %99, %100, %101, %102, %103, %104, %105, %106, %107, %108, %109, %110, %111, %112, %113, %114, %115, %116, %117, %118, %119, %120, %121, %122, %123, %124, %125, %126, %127}, %128, %129, p, 1, 1, 0, 0;\n}\n"
    : "+f"(d[0]), "+f"(d[1]), "+f"(d[2]), "+f"(d[3]), "+f"(d[4]), "+f"(d[5]), "+f"(d[6]), "+f"(d[7]), "+f"(d[8]), "+f"(d[9]), "+f"(d[10]), "+f"(d[11]), "+f"(d[12]), "+f"(d[13]), "+f"(d[14]), "+f"(d[15]), "+f"(d[16]), "+f"(d[17]), "+f"(d[18]), "+f"(d[19]), "+f"(d[20]), "+f"(d[21]), "+f"(d[22]), "+f"(d[23]), "+f"(d[24]), "+f"(d[25]), "+f"(d[26]), "+f"(d[27]), "+f"(d[28]), "+f"(d[29]), "+f"(d[30]), "+f"(d[31]), "+f"(d[32]), "+f"(d[33]), "+f"(d[34]), "+f"(d[35]), "+f"(d[36]), "+f"(d[37]), "+f"(d[38]), "+f"(d[39]), "+f"(d[40]), "+f"(d[41]), "+f"(d[42]), "+f"(d[43]), "+f"(d[44]), "+f"(d[45]), "+f"(d[46]), "+f"(d[47]), "+f"(d[48]), "+f"(d[49]), "+f"(d[50]), "+f"(d[51]), "+f"(d[52]), "+f"(d[53]), "+f"(d[54]), "+f"(d[55]), "+f"(d[56]), "+f"(d[57]), "+f"(d[58]), "+f"(d[59]), "+f"(d[60]), "+f"(d[61]), "+f"(d[62]), "+f"(d[63]), "+f"(d[64]), "+f"(d[65]), "+f"(d[66]), "+f"(d[67]), "+f"(d[68]), "+f"(d[69]), "+f"(d[70]), "+f"(d[71]), "+f"(d[72]), "+f"(d[73]), "+f"(d[74]), "+f"(d[75]), "+f"(d[76]), "+f"(d[77]), "+f"(d[78]), "+f"(d[79]), "+f"(d[80]), "+f"(d[81]), "+f"(d[82]), "+f"(d[83]), "+f"(d[84]), "+f"(d[85]), "+f"(d[86]), "+f"(d[87]), "+f"(d[88]), "+f"(d[89]), "+f"(d[90]), "+f"(d[91]), "+f"(d[92]), "+f"(d[93]), "+f"(d[94]), "+f"(d[95]), "+f"(d[96]), "+f"(d[97]), "+f"(d[98]), "+f"(d[99]), "+f"(d[100]), "+f"(d[101]), "+f"(d[102]), "+f"(d[103]), "+f"(d[104]), "+f"(d[105]), "+f"(d[106]), "+f"(d[107]), "+f"(d[108]), "+f"(d[109]), "+f"(d[110]), "+f"(d[111]), "+f"(d[112]), "+f"(d[113]), "+f"(d[114]), "+f"(d[115]), "+f"(d[116]), "+f"(d[117]), "+f"(d[118]), "+f"(d[119]), "+f"(d[120]), "+f"(d[121]), "+f"(d[122]), "+f"(d[123]), "+f"(d[124]), "+f"(d[125]), "+f"(d[126]), "+f"(d[127])
    : "l"(da), "l"(db), "r"(scale_d));
}
__device__ __forceinline__ void wgmma_n128_k(float (&d)[192], uint64_t da, uint64_t db, int scale_d) {
  asm volatile("{\n.reg .pred p;\nsetp.ne.b32 p, %66, 0;\n"
    "wgmma.mma_async.sync.aligned.m64n128k16.f32.bf16.bf16 {%0, %1, %2, %3, %4, %5, %6, %7, %8, %9, %10, %11, %12, %13, %14, %15, %16, %17, %18, %19, %20, %21, %22, %23, %24, %25, %26, %27, %28, %29, %30, %31, %32, %33, %34, %35, %36, %37, %38, %39, %40, %41, %42, %43, %44, %45, %46, %47, %48, %49, %50, %51, %52, %53, %54, %55, %56, %57, %58, %59, %60, %61, %62, %63}, %64, %65, p, 1, 1, 0, 0;\n}\n"
    : "+f"(d[128]), "+f"(d[129]), "+f"(d[130]), "+f"(d[131]), "+f"(d[132]), "+f"(d[133]), "+f"(d[134]), "+f"(d[135]), "+f"(d[136]), "+f"(d[137]), "+f"(d[138]), "+f"(d[139]), "+f"(d[140]), "+f"(d[141]), "+f"(d[142]), "+f"(d[143]), "+f"(d[144]), "+f"(d[145]), "+f"(d[146]), "+f"(d[147]), "+f"(d[148]), "+f"(d[149]), "+f"(d[150]), "+f"(d[151]), "+f"(d[152]), "+f"(d[153]), "+f"(d[154]), "+f"(d[155]), "+f"(d[156]), "+f"(d[157]), "+f"(d[158]), "+f"(d[159]), "+f"(d[160]), "+f"(d[161]), "+f"(d[162]), "+f"(d[163]), "+f"(d[164]), "+f"(d[165]), "+f"(d[166]), "+f"(d[167]), "+f"(d[168]), "+f"(d[169]), "+f"(d[170]), "+f"(d[171]), "+f"(d[172]), "+f"(d[173]), "+f"(d[174]), "+f"(d[175]), "+f"(d[176]), "+f"(d[177]), "+f"(d[178]), "+f"(d[179]), "+f"(d[180]), "+f"(d[181]), "+f"(d[182]), "+f"(d[183]), "+f"(d[184]), "+f"(d[185]), "+f"(d[186]), "+f"(d[187]), "+f"(d[188]), "+f"(d[189]), "+f"(d[190]), "+f"(d[191])
    : "l"(da), "l"(db), "r"(scale_d));
}
__device__ __forceinline__ void wgmma_n40_tt(float (&d)[20], uint64_t da, uint64_t db, int scale_d) {
  asm volatile("{\n.reg .pred p;\nsetp.ne.b32 p, %22, 0;\n"
    "wgmma.mma_async.sync.aligned.m64n40k16.f32.bf16.bf16 {%0, %1, %2, %3, %4, %5, %6, %7, %8, %9, %10, %11, %12, %13, %14, %15, %16, %17, %18, %19}, %20, %21, p, 1, 1, 1, 1;\n}\n"
    : "+f"(d[0]), "+f"(d[1]), "+f"(d[2]), "+f"(d[3]), "+f"(d[4]), "+f"(d[5]), "+f"(d[6]), "+f"(d[7]), "+f"(d[8]), "+f"(d[9]), "+f"(d[10]), "+f"(d[11]), "+f"(d[12]), "+f"(d[13]), "+f"(d[14]), "+f"(d[15]), "+f"(d[16]), "+f"(d[17]), "+f"(d[18]), "+f"(d[19])
    : "l"(da), "l"(db), "r"(scale_d));
}
__device__ __forceinline__ void wgmma_n40_rs(float (&d)[20], const uint32_t (&a)[4], uint64_t db, int scale_d) {
  asm volatile("{\n.reg .pred p;\nsetp.ne.b32 p, %25, 0;\n"
    "wgmma.mma_async.sync.aligned.m64n40k16.f32.bf16.bf16 {%0, %1, %2, %3, %4, %5, %6, %7, %8, %9, %10, %11, %12, %13, %14, %15, %16, %17, %18, %19}, {%20, %21, %22, %23}, %24, p, 1, 1, 1;\n}\n"
    : "+f"(d[0]), "+f"(d[1]), "+f"(d[2]), "+f"(d[3]), "+f"(d[4]), "+f"(d[5]), "+f"(d[6]), "+f"(d[7]), "+f"(d[8]), "+f"(d[9]), "+f"(d[10]), "+f"(d[11]), "+f"(d[12]), "+f"(d[13]), "+f"(d[14]), "+f"(d[15]), "+f"(d[16]), "+f"(d[17]), "+f"(d[18]), "+f"(d[19])
    : "r"(a[0]), "r"(a[1]), "r"(a[2]), "r"(a[3]), "l"(db), "r"(scale_d));
}
__device__ __forceinline__ void wgmma_n128_0(float (&d)[192], uint64_t da, uint64_t db) {
  asm volatile("{\n.reg .pred p;\nsetp.ne.b32 p, 0, 0;\n"
    "wgmma.mma_async.sync.aligned.m64n128k16.f32.bf16.bf16 {%0, %1, %2, %3, %4, %5, %6, %7, %8, %9, %10, %11, %12, %13, %14, %15, %16, %17, %18, %19, %20, %21, %22, %23, %24, %25, %26, %27, %28, %29, %30, %31, %32, %33, %34, %35, %36, %37, %38, %39, %40, %41, %42, %43, %44, %45, %46, %47, %48, %49, %50, %51, %52, %53, %54, %55, %56, %57, %58, %59, %60, %61, %62, %63}, %64, %65, p, 1, 1, 0, 1;\n}\n"
    : "=f"(d[128]), "=f"(d[129]), "=f"(d[130]), "=f"(d[131]), "=f"(d[132]), "=f"(d[133]), "=f"(d[134]), "=f"(d[135]), "=f"(d[136]), "=f"(d[137]), "=f"(d[138]), "=f"(d[139]), "=f"(d[140]), "=f"(d[141]), "=f"(d[142]), "=f"(d[143]), "=f"(d[144]), "=f"(d[145]), "=f"(d[146]), "=f"(d[147]), "=f"(d[148]), "=f"(d[149]), "=f"(d[150]), "=f"(d[151]), "=f"(d[152]), "=f"(d[153]), "=f"(d[154]), "=f"(d[155]), "=f"(d[156]), "=f"(d[157]), "=f"(d[158]), "=f"(d[159]), "=f"(d[160]), "=f"(d[161]), "=f"(d[162]), "=f"(d[163]), "=f"(d[164]), "=f"(d[165]), "=f"(d[166]), "=f"(d[167]), "=f"(d[168]), "=f"(d[169]), "=f"(d[170]), "=f"(d[171]), "=f"(d[172]), "=f"(d[173]), "=f"(d[174]), "=f"(d[175]), "=f"(d[176]), "=f"(d[177]), "=f"(d[178]), "=f"(d[179]), "=f"(d[180]), "=f"(d[181]), "=f"(d[182]), "=f"(d[183]), "=f"(d[184]), "=f"(d[185]), "=f"(d[186]), "=f"(d[187]), "=f"(d[188]), "=f"(d[189]), "=f"(d[190]), "=f"(d[191])
    : "l"(da), "l"(db));
}
__device__ __forceinline__ void wgmma_n128_rs(float (&d)[192], const uint32_t (&a)[4], uint64_t db, int scale_d) {
  asm volatile("{\n.reg .pred p;\nsetp.ne.b32 p, %69, 0;\n"
    "wgmma.mma_async.sync.aligned.m64n128k16.f32.bf16.bf16 {%0, %1, %2, %3, %4, %5, %6, %7, %8, %9, %10, %11, %12, %13, %14, %15, %16, %17, %18, %19, %20, %21, %22, %23, %24, %25, %26, %27, %28, %29, %30, %31, %32, %33, %34, %35, %36, %37, %38, %39, %40, %41, %42, %43, %44, %45, %46, %47, %48, %49, %50, %51, %52, %53, %54, %55, %56, %57, %58, %59, %60, %61, %62, %63}, {%64, %65, %66, %67}, %68, p, 1, 1, 1;\n}\n"
    : "+f"(d[128]), "+f"(d[129]), "+f"(d[130]), "+f"(d[131]), "+f"(d[132]), "+f"(d[133]), "+f"(d[134]), "+f"(d[135]), "+f"(d[136]), "+f"(d[137]), "+f"(d[138]), "+f"(d[139]), "+f"(d[140]), "+f"(d[141]), "+f"(d[142]), "+f"(d[143]), "+f"(d[144]), "+f"(d[145]), "+f"(d[146]), "+f"(d[147]), "+f"(d[148]), "+f"(d[149]), "+f"(d[150]), "+f"(d[151]), "+f"(d[152]), "+f"(d[153]), "+f"(d[154]), "+f"(d[155]), "+f"(d[156]), "+f"(d[157]), "+f"(d[158]), "+f"(d[159]), "+f"(d[160]), "+f"(d[161]), "+f"(d[162]), "+f"(d[163]), "+f"(d[164]), "+f"(d[165]), "+f"(d[166]), "+f"(d[167]), "+f"(d[168]), "+f"(d[169]), "+f"(d[170]), "+f"(d[171]), "+f"(d[172]), "+f"(d[173]), "+f"(d[174]), "+f"(d[175]), "+f"(d[176]), "+f"(d[177]), "+f"(d[178]), "+f"(d[179]), "+f"(d[180]), "+f"(d[181]), "+f"(d[182]), "+f"(d[183]), "+f"(d[184]), "+f"(d[185]), "+f"(d[186]), "+f"(d[187]), "+f"(d[188]), "+f"(d[189]), "+f"(d[190]), "+f"(d[191])
    : "r"(a[0]), "r"(a[1]), "r"(a[2]), "r"(a[3]), "l"(db), "r"(scale_d));
}
__device__ __forceinline__ void wgmma_n32_0(float (&d)[16], uint64_t da, uint64_t db) {
  asm volatile("{\n.reg .pred p;\nsetp.ne.b32 p, 0, 0;\n"
    "wgmma.mma_async.sync.aligned.m64n32k16.f32.bf16.bf16 {%0, %1, %2, %3, %4, %5, %6, %7, %8, %9, %10, %11, %12, %13, %14, %15}, %16, %17, p, 1, 1, 0, 1;\n}\n"
    : "=f"(d[0]), "=f"(d[1]), "=f"(d[2]), "=f"(d[3]), "=f"(d[4]), "=f"(d[5]), "=f"(d[6]), "=f"(d[7]), "=f"(d[8]), "=f"(d[9]), "=f"(d[10]), "=f"(d[11]), "=f"(d[12]), "=f"(d[13]), "=f"(d[14]), "=f"(d[15])
    : "l"(da), "l"(db));
}
__device__ __forceinline__ void wgmma_n32(float (&d)[16], uint64_t da, uint64_t db, int scale_d) {
  asm volatile("{\n.reg .pred p;\nsetp.ne.b32 p, %18, 0;\n"
    "wgmma.mma_async.sync.aligned.m64n32k16.f32.bf16.bf16 {%0, %1, %2, %3, %4, %5, %6, %7, %8, %9, %10, %11, %12, %13, %14, %15}, %16, %17, p, 1, 1, 0, 1;\n}\n"
    : "+f"(d[0]), "+f"(d[1]), "+f"(d[2]), "+f"(d[3]), "+f"(d[4]), "+f"(d[5]), "+f"(d[6]), "+f"(d[7]), "+f"(d[8]), "+f"(d[9]), "+f"(d[10]), "+f"(d[11]), "+f"(d[12]), "+f"(d[13]), "+f"(d[14]), "+f"(d[15])
    : "l"(da), "l"(db), "r"(scale_d));
}
__device__ __forceinline__ void wgmma_n8_t(float (&d)[4], uint64_t da, uint64_t db, int scale_d) {
  asm volatile("{\n.reg .pred p;\nsetp.ne.b32 p, %6, 0;\n"
    "wgmma.mma_async.sync.aligned.m64n8k16.f32.bf16.bf16 {%0, %1, %2, %3}, %4, %5, p, 1, 1, 1, 0;\n}\n"
    : "+f"(d[0]), "+f"(d[1]), "+f"(d[2]), "+f"(d[3])
    : "l"(da), "l"(db), "r"(scale_d));
}
__device__ __forceinline__ void wgmma_n128_rs0(float (&d)[192], const uint32_t (&a)[4], uint64_t db) {
  asm volatile("{\n.reg .pred p;\nsetp.ne.b32 p, 0, 0;\n"
    "wgmma.mma_async.sync.aligned.m64n128k16.f32.bf16.bf16 {%0, %1, %2, %3, %4, %5, %6, %7, %8, %9, %10, %11, %12, %13, %14, %15, %16, %17, %18, %19, %20, %21, %22, %23, %24, %25, %26, %27, %28, %29, %30, %31, %32, %33, %34, %35, %36, %37, %38, %39, %40, %41, %42, %43, %44, %45, %46, %47, %48, %49, %50, %51, %52, %53, %54, %55, %56, %57, %58, %59, %60, %61, %62, %63}, {%64, %65, %66, %67}, %68, p, 1, 1, 1;\n}\n"
    : "=f"(d[128]), "=f"(d[129]), "=f"(d[130]), "=f"(d[131]), "=f"(d[132]), "=f"(d[133]), "=f"(d[134]), "=f"(d[135]), "=f"(d[136]), "=f"(d[137]), "=f"(d[138]), "=f"(d[139]), "=f"(d[140]), "=f"(d[141]), "=f"(d[142]), "=f"(d[143]), "=f"(d[144]), "=f"(d[145]), "=f"(d[146]), "=f"(d[147]), "=f"(d[148]), "=f"(d[149]), "=f"(d[150]), "=f"(d[151]), "=f"(d[152]), "=f"(d[153]), "=f"(d[154]), "=f"(d[155]), "=f"(d[156]), "=f"(d[157]), "=f"(d[158]), "=f"(d[159]), "=f"(d[160]), "=f"(d[161]), "=f"(d[162]), "=f"(d[163]), "=f"(d[164]), "=f"(d[165]), "=f"(d[166]), "=f"(d[167]), "=f"(d[168]), "=f"(d[169]), "=f"(d[170]), "=f"(d[171]), "=f"(d[172]), "=f"(d[173]), "=f"(d[174]), "=f"(d[175]), "=f"(d[176]), "=f"(d[177]), "=f"(d[178]), "=f"(d[179]), "=f"(d[180]), "=f"(d[181]), "=f"(d[182]), "=f"(d[183]), "=f"(d[184]), "=f"(d[185]), "=f"(d[186]), "=f"(d[187]), "=f"(d[188]), "=f"(d[189]), "=f"(d[190]), "=f"(d[191])
    : "r"(a[0]), "r"(a[1]), "r"(a[2]), "r"(a[3]), "l"(db));
}
__device__ __forceinline__ void wgmma_n256_rs(float (&d)[192], const uint32_t (&a)[4], uint64_t db, int scale_d) {
  asm volatile("{\n.reg .pred p;\nsetp.ne.b32 p, %133, 0;\n"
    "wgmma.mma_async.sync.aligned.m64n256k16.f32.bf16.bf16 {%0, %1, %2, %3, %4, %5, %6, %7, %8, %9, %10, %11, %12, %13, %14, %15, %16, %17, %18, %19, %20, %21, %22, %23, %24, %25, %26, %27, %28, %29, %30, %31, %32, %33, %34, %35, %36, %37, %38, %39, %40, %41, %42, %43, %44, %45, %46, %47, %48, %49, %50, %51, %52, %53, %54, %55, %56, %57, %58, %59, %60, %61, %62, %63, %64, %65, %66, %67, %68, %69, %70, %71, %72, %73, %74, %75, %76, %77, %78, %79, %80, %81, %82, %83, %84, %85, %86, %87, %88, %89, %90, %91, %92, %93, %94, %95, %96, %97, %98, %99, %100, %101, %102, %103, %104, %105, %106, %107, %108, %109, %110, %111, %112, %113, %114, %115, %116, %117, %118, %119, %120, %121, %122, %123, %124, %125, %126, %127}, {%128, %129, %130, %131}, %132, p, 1, 1, 1;\n}\n"
    : "+f"(d[0]), "+f"(d[1]), "+f"(d[2]), "+f"(d[3]), "+f"(d[4]), "+f"(d[5]), "+f"(d[6]), "+f"(d[7]), "+f"(d[8]), "+f"(d[9]), "+f"(d[10]), "+f"(d[11]), "+f"(d[12]), "+f"(d[13]), "+f"(d[14]), "+f"(d[15]), "+f"(d[16]), "+f"(d[17]), "+f"(d[18]), "+f"(d[19]), "+f"(d[20]), "+f"(d[21]), "+f"(d[22]), "+f"(d[23]), "+f"(d[24]), "+f"(d[25]), "+f"(d[26]), "+f"(d[27]), "+f"(d[28]), "+f"(d[29]), "+f"(d[30]), "+f"(d[31]), "+f"(d[32]), "+f"(d[33]), "+f"(d[34]), "+f"(d[35]), "+f"(d[36]), "+f"(d[37]), "+f"(d[38]), "+f"(d[39]), "+f"(d[40]), "+f"(d[41]), "+f"(d[42]), "+f"(d[43]), "+f"(d[44]), "+f"(d[45]), "+f"(d[46]), "+f"(d[47]), "+f"(d[48]), "+f"(d[49]), "+f"(d[50]), "+f"(d[51]), "+f"(d[52]), "+f"(d[53]), "+f"(d[54]), "+f"(d[55]), "+f"(d[56]), "+f"(d[57]), "+f"(d[58]), "+f"(d[59]), "+f"(d[60]), "+f"(d[61]), "+f"(d[62]), "+f"(d[63]), "+f"(d[64]), "+f"(d[65]), "+f"(d[66]), "+f"(d[67]), "+f"(d[68]), "+f"(d[69]), "+f"(d[70]), "+f"(d[71]), "+f"(d[72]), "+f"(d[73]), "+f"(d[74]), "+f"(d[75]), "+f"(d[76]), "+f"(d[77]), "+f"(d[78]), "+f"(d[79]), "+f"(d[80]), "+f"(d[81]), "+f"(d[82]), "+f"(d[83]), "+f"(d[84]), "+f"(d[85]), "+f"(d[86]), "+f"(d[87]), "+f"(d[88]), "+f"(d[89]), "+f"(d[90]), "+f"(d[91]), "+f"(d[92]), "+f"(d[93]), "+f"(d[94]), "+f"(d[95]), "+f"(d[96]), "+f"(d[97]), "+f"(d[98]), "+f"(d[99]), "+f"(d[100]), "+f"(d[101]), "+f"(d[102]), "+f"(d[103]), "+f"(d[104]), "+f"(d[105]), "+f"(d[106]), "+f"(d[107]), "+f"(d[108]), "+f"(d[109]), "+f"(d[110]), "+f"(d[111]), "+f"(d[112]), "+f"(d[113]), "+f"(d[114]), "+f"(d[115]), "+f"(d[116]), "+f"(d[117]), "+f"(d[118]), "+f"(d[119]), "+f"(d[120]), "+f"(d[121]), "+f"(d[122]), "+f"(d[123]), "+f"(d[124]), "+f"(d[125]), "+f"(d[126]), "+f"(d[127])
    : "r"(a[0]), "r"(a[1]), "r"(a[2]), "r"(a[3]), "l"(db), "r"(scale_d));
}
__device__ __forceinline__ void wgmma_n256_rs0(float (&d)[192], const uint32_t (&a)[4], uint64_t db) {
  asm volatile("{\n.reg .pred p;\nsetp.ne.b32 p, 0, 0;\n"
    "wgmma.mma_async.sync.aligned.m64n256k16.f32.bf16.bf16 {%0, %1, %2, %3, %4, %5, %6, %7, %8, %9, %10, %11, %12, %13, %14, %15, %16, %17, %18, %19, %20, %21, %22, %23, %24, %25, %26, %27, %28, %29, %30, %31, %32, %33, %34, %35, %36, %37, %38, %39, %40, %41, %42, %43, %44, %45, %46, %47, %48, %49, %50, %51, %52, %53, %54, %55, %56, %57, %58, %59, %60, %61, %62, %63, %64, %65, %66, %67, %68, %69, %70, %71, %72, %73, %74, %75, %76, %77, %78, %79, %80, %81, %82, %83, %84, %85, %86, %87, %88, %89, %90, %91, %92, %93, %94, %95, %96, %97, %98, %99, %100, %101, %102, %103, %104, %105, %106, %107, %108, %109, %110, %111, %112, %113, %114, %115, %116, %117, %118, %119, %120, %121, %122, %123, %124, %125, %126, %127}, {%128, %129, %130, %131}, %132, p, 1, 1, 1;\n}\n"
    : "=f"(d[0]), "=f"(d[1]), "=f"(d[2]), "=f"(d[3]), "=f"(d[4]), "=f"(d[5]), "=f"(d[6]), "=f"(d[7]), "=f"(d[8]), "=f"(d[9]), "=f"(d[10]), "=f"(d[11]), "=f"(d[12]), "=f"(d[13]), "=f"(d[14]), "=f"(d[15]), "=f"(d[16]), "=f"(d[17]), "=f"(d[18]), "=f"(d[19]), "=f"(d[20]), "=f"(d[21]), "=f"(d[22]), "=f"(d[23]), "=f"(d[24]), "=f"(d[25]), "=f"(d[26]), "=f"(d[27]), "=f"(d[28]), "=f"(d[29]), "=f"(d[30]), "=f"(d[31]), "=f"(d[32]), "=f"(d[33]), "=f"(d[34]), "=f"(d[35]), "=f"(d[36]), "=f"(d[37]), "=f"(d[38]), "=f"(d[39]), "=f"(d[40]), "=f"(d[41]), "=f"(d[42]), "=f"(d[43]), "=f"(d[44]), "=f"(d[45]), "=f"(d[46]), "=f"(d[47]), "=f"(d[48]), "=f"(d[49]), "=f"(d[50]), "=f"(d[51]), "=f"(d[52]), "=f"(d[53]), "=f"(d[54]), "=f"(d[55]), "=f"(d[56]), "=f"(d[57]), "=f"(d[58]), "=f"(d[59]), "=f"(d[60]), "=f"(d[61]), "=f"(d[62]), "=f"(d[63]), "=f"(d[64]), "=f"(d[65]), "=f"(d[66]), "=f"(d[67]), "=f"(d[68]), "=f"(d[69]), "=f"(d[70]), "=f"(d[71]), "=f"(d[72]), "=f"(d[73]), "=f"(d[74]), "=f"(d[75]), "=f"(d[76]), "=f"(d[77]), "=f"(d[78]), "=f"(d[79]), "=f"(d[80]), "=f"(d[81]), "=f"(d[82]), "=f"(d[83]), "=f"(d[84]), "=f"(d[85]), "=f"(d[86]), "=f"(d[87]), "=f"(d[88]), "=f"(d[89]), "=f"(d[90]), "=f"(d[91]), "=f"(d[92]), "=f"(d[93]), "=f"(d[94]), "=f"(d[95]), "=f"(d[96]), "=f"(d[97]), "=f"(d[98]), "=f"(d[99]), "=f"(d[100]), "=f"(d[101]), "=f"(d[102]), "=f"(d[103]), "=f"(d[104]), "=f"(d[105]), "=f"(d[106]), "=f"(d[107]), "=f"(d[108]), "=f"(d[109]), "=f"(d[110]), "=f"(d[111]), "=f"(d[112]), "=f"(d[113]), "=f"(d[114]), "=f"(d[115]), "=f"(d[116]), "=f"(d[117]), "=f"(d[118]), "=f"(d[119]), "=f"(d[120]), "=f"(d[121]), "=f"(d[122]), "=f"(d[123]), "=f"(d[124]), "=f"(d[125]), "=f"(d[126]), "=f"(d[127])
    : "r"(a[0]), "r"(a[1]), "r"(a[2]), "r"(a[3]), "l"(db));
}

constexpr int SLOT = 16384;
constexpr int VB = 4 * SLOT, PH = 0, XS = 6;
constexpr int SM_SD = 13 * SLOT;
constexpr int SM_BAR = SM_SD + 8192;
constexpr int SM_RS = SM_BAR + 1024;
constexpr int SM_AP = SM_RS + 640;
constexpr int SM_BP = SM_AP + 2048;
constexpr int SM_ID = SM_BP + 6144;
constexpr int SM_TOTAL = SM_ID + 16;
constexpr int FM = 0, FT = 16, FW = 30, CM = 46, CT = 62, CW = 76, B_EF = 92, B_STAT = 93, B_KVF = 94, B_HALO = 95,
              B_KVDONE = 96, B_OH0 = 97, B_OH1 = 98, B_XH0 = 99, B_XDONE = 100, B_WFD = 101, B_XT = 102, B_OF0 = 103, B_KVF1 = 104, B_KVS = 105, B_RAW = 106  , B_X0 = 108, B_KVS0 = 109, B_ID = 110;
constexpr uint64_t BAR_LG = 0x00043333330004ull;
#define BA(i) (bar + (i) * 8)
#define REL2(i) release2c(SB0 + SM_BAR + (i) * 8)
constexpr int NF = 3, ND = 13, NR = 0, NWOP = 48, NAOP = 38;
constexpr bool EF_USED = false;
constexpr uint64_t TL_A = 0x6278627862786ull, TL_B = 0xa9c3ba9c3ba9cull, WO_A = 0x76b24038b51403ffull, WO_B = 0x8c5a197c6a297c8bull;
__constant__ uint32_t c_wop[NWOP + 1] = {0xeb0009, 0x186b8000, 0x6c0112, 0x1aec011a, 0x6c8224, 0x22ec822b, 0x18170330, 0x18178442, 0x18180554, 0x18188660, 0x18190772, 0x18198884, 0x181a0990, 0x181a8aa2, 0x181b0bb4, 0x181b8cc0, 0xaed10fc, 0xa9711e9, 0x181c0dd2, 0xa9792da, 0x129813cb, 0x181c8ee4, 0x181d0ff0, 0x109d94b3, 0x109f15ac, 0x109f9699, 0x10a0178a, 0x10a0987b, 0x10a11963, 0x10a19a5c, 0x10a21b49, 0x10a29c3a, 0x9231e0b, 0x9239f18, 0x1124202c, 0x13242137, 0x1124a249, 0x1324a352, 0x1125246a, 0x13252576, 0x1127268c, 0x1127a797, 0x112828a9, 0x1128a9b1, 0x11292aca, 0x13292bd5, 0x112a2cec, 0x132a2df8, 0};
__constant__ uint32_t c_aop[NAOP + 1] = {0x6d8228, 0x170336, 0x178447, 0x180558, 0x188666, 0x190777, 0x198888, 0x1a0996, 0x1a8aa7, 0x1b0bb8, 0x1b8cc6, 0x1c0dd7, 0x1c8ee8, 0x1d0ff6, 0x1d93c2, 0x1f14b6, 0x1f95a8, 0x201697, 0x209782, 0x211876, 0x219968, 0x221a57, 0x229b42, 0x231c36, 0xa3a023, 0xb12130, 0x2b12244, 0x2b12351, 0x2b12465, 0xa6257b, 0xa6a688, 0xa72793, 0xa7a8a0, 0xa829b4, 0xa8aac2, 0xa9abdb, 0x2a9ace6, 0xaaadf7, 0};
__constant__ uint32_t c_map[64] = {4, 5, 6, 7, 0, 16, 32, 48, 64, 80, 96, 112, 1, 17, 33, 49, 65, 81, 97, 113, 2, 18, 34, 50, 66, 82, 98, 114, 3, 19, 35, 51, 67, 83, 99, 115, 20, 36, 52, 68, 84, 100, 116, 21, 37, 53, 69, 85, 101, 117, 22, 38, 54, 70, 86, 102, 118, 23, 39, 55, 71, 87, 103, 119};
enum { MAP_WF = 0, MAP_WA = 2, MAP_WB = 4, MAP_WOA = 6, MAP_WOB = 8, MAP_X0 = 10, MAP_X = 11, MAP_O = 12, MAP_PHI = 13, NMAP = 14 };
struct Maps { CUtensorMap m[NMAP]; };

#define PL 2
#define PROFL(a, b)
#define SUBS 8
#define SUBS1 16
#define XRAT 10
#define XRN 4
#define BT1 1
#define ST1 8
#define X0AT 2
#define W1DL 400
#define WH 4
#define PFM 3
#define PFS 2
#define SVD 5000
#define NLAYERS 4
constexpr float L2E = 1.4426950408889634f;

#define D128(lo) desc64(lo, 0x40000040u)
struct Ctx { uint32_t zero, boff; const bf16* x0; bf16* out; };
#define BASE_CTX() \
  uint32_t bid_; asm volatile("mov.u32 %0, %%ctaid.x;" : "=r"(bid_)); \
  const int cr = bid_ & 1; \
  const uint32_t sb = SB0 + (cr << 24); \
  const uint32_t bar = sb + SM_BAR; (void)bar;
#define STA_CTX() \
  BASE_CTX(); \
  bid_ -= c.boff; \
  const uint32_t gr_ = c_map[bid_ >> 1]; \
  const int g = gr_ & 7, kf = (gr_ >> 3) + cr; (void)g; (void)kf;
#define DYN_CTX(id) \
  const uint32_t id_ = id; \
  const int g = id_ & 7, rb = (id_ >> 3) & 15, m0 = rb * 128; (void)g; (void)rb; (void)m0;
#define LD_ID() __float_as_uint(lds_f(sb + SM_ID))
extern __shared__ uint8_t smem_raw[];
constexpr uint32_t SB0 = 1024;

#define PHASE_CTX() \
  uint32_t idl_ = idp; asm volatile("" : "+r"(idl_)); \
  DYN_CTX(idl_); \
  const uint32_t sb = SB0 + ((id_ & 8) << 21), bar = sb + SM_BAR; \
  THR_CTX(); \
  const size_t gfr = (size_t)(m0 + wrow0 + gq) * D_ + g * 128 + 8 * t; (void)gfr;
#define THR_CTX() \
  int tid_ = threadIdx.x; asm volatile("" : "+r"(tid_)); \
  const int lane = tid_ & 31, cw = (tid_ >> 5) - 4, wg = cw >> 2, wq = cw & 3, gq = lane >> 2, t = lane & 3, wrow0 = cw * 16; \
  const int lrow = (lane & 7) + ((lane >> 3) & 1) * 8, lchk = lane >> 4; \
  const bool elected = (tid_ & 127) == 0; \
  const uint32_t rowo = (wrow0 + lrow) * 128, X = (lchk ^ (lane & 7)) << 4; \
  const uint32_t Y = (wrow0 + (lane & 7)) * 128 + (((lane >> 3) ^ (lane & 7)) << 4); \
  (void)bar; (void)wq; (void)gq; (void)lrow; (void)lchk; (void)elected; (void)wrow0; (void)wg; (void)rowo; (void)X; (void)t; (void)Y;
#define MMA_CTX() \
  const uint32_t wu = __shfl_sync(0xffffffffu, wg, 0); \
  const uint32_t dA0 = ((SB0 >> 4) | (1u << 16)) + wu * 512, dB0 = (SB0 >> 4) | (512u << 16); \
  const uint32_t par = layer & 1;

__device__ __forceinline__ void slab_out_half(uint32_t slot, bf16* dst, int wrow0, int lane) {
  const int r0 = lane >> 3, ch = lane & 7;
  const uint32_t src = slot + (wrow0 + r0) * 128;
  uint4 v[4];
#pragma unroll
  for (int i = 0; i < 4; ++i) v[i] = lds128(src + i * 512 + (((ch ^ (4 * i + r0)) & 7) << 4));
  dst += (size_t)(wrow0 + r0) * D_ + ch * 8;
#pragma unroll
  for (int i = 0; i < 4; ++i) *reinterpret_cast<uint4*>(dst + (size_t)i * 4 * D_) = v[i];
}

__device__ __forceinline__ void consumer(const Ctx& c) {
  float acc[192];
  uint32_t idp;
  uint32_t xf[4][4];
  uint32_t xp[8][4];
  {
    STA_CTX();
    THR_CTX();
    const unsigned int epoch = ld_relaxed(&g_epoch);
    PROFT(tid_ == 128, 0);
    const uint32_t wu = __shfl_sync(0xffffffffu, wg, 0);
    if (tid_ < 128 + 8) sts128(sb + SM_AP + lane * 16, make_uint4(0x3F803F80u, 0x3F803F80u, 0x3F803F80u, 0x3F803F80u));
#pragma unroll 1
    for (int it = 0; it < 2; ++it) {
      float p[4][16];
      mbar_wait(BA(B_RAW + it), 0);
      PROFT(tid_ == 128, it ? 15 : 2);
      const uint32_t da = ((SB0 >> 4) | (1u << 16)) + (wu ? 9 + it : 2 * it) * 1024, db = (SB0 + SM_SD) >> 4;
      wgmma_fence();
#pragma unroll
      for (int h = 0; h < 4; ++h) wgmma_n32_0(p[h], D128(da + (h >> 1) * 512 + (h & 1) * 4), desc64(db + h * 128, 0x80000020u));
#pragma unroll
      for (int h = 0; h < 4; ++h) wgmma_n32(p[h], D128(da + (h >> 1) * 512 + (h & 1) * 4 + 2), desc64(db + h * 128 + 64, 0x80000020u), 1);
      wgmma_commit();
      wgmma_wait<0>();
#pragma unroll
      for (int i = 0; i < 64; ++i) asm volatile("" : "+f"(p[i >> 4][i & 15]) :: "memory");
      const uint32_t base = sb + (wg ? 9 + it : 2 * it) * SLOT + (wq * 16 + gq) * 128;
      uint32_t w[4][4][2];
#pragma unroll
      for (int i = 0; i < 32; ++i) w[i >> 3][(i >> 1) & 3][i & 1] = pack_bf16(p[i >> 3][2 * (i & 7)], p[i >> 3][2 * (i & 7) + 1]);
      if (wu) {
#pragma unroll
        for (int i = 0; i < 8; ++i)
          sts128(base + (i >> 2) * 8192 + (i & 1) * 1024 + (((((i >> 1) & 1) * 4 + t) ^ gq) << 4), make_uint4(w[i >> 1][0][i & 1], w[i >> 1][1][i & 1], w[i >> 1][2][i & 1], w[i >> 1][3][i & 1]));
      } else {
#pragma unroll
        for (int i = 0; i < 16; ++i)
          sts64(base + (i >> 3) * 8192 + (i & 1) * 1024 + ((((t & 1) * 4 + ((i >> 1) & 3)) ^ gq) << 4) + (t >> 1) * 8, w[(i >> 3) * 2][(i >> 1) & 3][i & 1], w[(i >> 3) * 2 + 1][(i >> 1) & 3][i & 1]);
      }
      fence_async_smem();
      __syncwarp();
      if (it == cr && lane == 0) mbar_arrive(BA(B_WFD));
    }
    mbar_wait(BA(B_ID), 0);
    idp = __shfl_sync(0xffffffffu, LD_ID(), 0);
#pragma unroll
    for (int i = 0; i < 32; ++i) xp[i >> 2][i & 3] = 0u;
    nbar<1, 256>();
    PROFT(tid_ == 128, 13);
    mbar_wait(BA(FM + cr), 0);
    float cs[3][4];
    wgmma_fence();
#pragma unroll
    for (int ks = 0; ks < 4; ++ks)
#pragma unroll
      for (int i = 0; i < 3; ++i) {
        const uint32_t bx = (i == 0 ? 2 * cr * 1024 : i == 1 ? (2 * cr + 1) * 1024 : (9 + cr) * 1024) + wu * 512;
        wgmma_n8_t(cs[i], D128(((SB0 >> 4) | (512u << 16)) + bx + ks * 128), desc64((SB0 + SM_AP) >> 4, 0), ks != 0);
      }
    wgmma_commit();
    mbar_wait(BA(FM), 0);
#pragma unroll
    for (int k = 0; k < 4; ++k) ldsm_x4(xf[k][0], xf[k][1], xf[k][2], xf[k][3], sb + XS * SLOT + rowo + (X ^ (k << 5)));
    wgmma_wait<0>();
#pragma unroll
    for (int i = 0; i < 12; ++i) asm volatile("" : "+f"(cs[i >> 2][i & 3]) :: "memory");
    if (t < 2) {
#pragma unroll
      for (int i = 0; i < 3; ++i) red_add1(g_cs + (epoch & 1) * 6144 + g * 384 + i * 128 + wg * 64 + wq * 16 + gq + t * 8, t ? cs[i][2] : cs[i][0]);
    }
    PROFT(tid_ == 128, 14);
  }
#pragma unroll 1
  for (int layer = 0;; ++layer) {
    {
      wgmma_fence();
      wgmma_n256_rs0(acc, xf[0], D128((SB0 >> 4) | (512u << 16)));
#pragma unroll
      for (int k = 1; k < 4; ++k) wgmma_n256_rs(acc, xf[k], D128(((SB0 >> 4) | (512u << 16)) + k * 128), 1);
      wgmma_commit();
      PHASE_CTX();
      MMA_CTX();
      {
        const uint32_t ep = id_ >> 8;
        if (layer == 0) {
          mbar_wait(BA(B_X0), 0);
#pragma unroll
          for (int i = 0; i < 8; ++i) ldsm_x4(xp[i][0], xp[i][1], xp[i][2], xp[i][3], sb + (11 + (i >> 2)) * SLOT + (Y ^ ((i & 2) << 5)) + (i & 1) * 1024);
          if (lane == ((xp[0][0] ^ xp[1][0] ^ xp[2][0] ^ xp[3][0] ^ xp[7][0]) & c.zero)) REL2(B_XT);
        } else {
#pragma unroll
          for (int i = 0; i < 8; ++i) stsm_x4(sb + (XS + (i >> 2)) * SLOT + (Y ^ ((i & 2) << 5)) + (i & 1) * 1024, xp[i][0], xp[i][1], xp[i][2], xp[i][3]);
        }
        float s0 = 0.f, s1 = 0.f, q0 = 0.f, q1 = 0.f;
        auto stats = [&](int j0, int j1) {
#pragma unroll
          for (int j = j0; j < j1; ++j) {
            const uint32_t u0 = xp[(j >> 2) * 2][j & 3], u1 = xp[(j >> 2) * 2 + 1][j & 3];
            s0 += bf_lo(u0) + bf_hi(u0); s1 += bf_lo(u1) + bf_hi(u1);
            q0 = fmaf(bf_lo(u0), bf_lo(u0), fmaf(bf_hi(u0), bf_hi(u0), q0)); q1 = fmaf(bf_lo(u1), bf_lo(u1), fmaf(bf_hi(u1), bf_hi(u1), q1));
          }
        };
        stats(0, ST1);
        fence_async_smem();
        nbar_dyn(3 + wu + (__float_as_uint(s0 + s1 + q0 + q1) & c.zero), 128);
        mbar_wait(BA(FM + 1), par);
        wgmma_fence();
#pragma unroll
        for (int k = 0; k < 4; ++k) wgmma_n256(acc, D128(dA0 + (XS + 1) * 1024 + k * 2), D128(dB0 + 2048 + k * 128), 1);
        wgmma_commit();
        wgmma_wait<1>();
#pragma unroll
        for (int i = 4; i < 8; ++i) stg128_p(layer, g_x + gfr + (i & 1) * 8 * D_ + (i >> 1) * 32, xp[i][0], xp[i][1], xp[i][2], xp[i][3]);
        {
          uint32_t zc; asm volatile("mov.u32 %0, %%clock;" : "=r"(zc) :: "memory");
          q0 += __uint_as_float(zc & c.zero); q1 += __uint_as_float(zc & c.zero); s0 += __uint_as_float(zc & c.zero); s1 += __uint_as_float(zc & c.zero);
        }
        stats(ST1, 16);
        wgmma_fence();
        wgmma_n128_0(acc, D128(dA0 + XS * 1024), D128(dB0 + 9 * 1024));
#pragma unroll
        for (int k = 1; k < 4; ++k) wgmma_n128(acc, D128(dA0 + XS * 1024 + k * 2), D128(dB0 + 9 * 1024 + k * 128), 1);
        wgmma_commit();
        const bool od = t & 1;
        float sa = od ? s1 : s0, qa = od ? q1 : q0;
        sa += __shfl_xor_sync(0xffffffffu, od ? s0 : s1, 1);
        qa += __shfl_xor_sync(0xffffffffu, od ? q0 : q1, 1);
        wgmma_fence();
#pragma unroll
        for (int k = 0; k < 4; ++k) wgmma_n128(acc, D128(dA0 + (XS + 1) * 1024 + k * 2), D128(dB0 + 10 * 1024 + k * 128), 1);
        wgmma_commit();
        sa += __shfl_xor_sync(0xffffffffu, sa, 2);
        qa += __shfl_xor_sync(0xffffffffu, qa, 2);
        red_add2_p(t < 2, reinterpret_cast<float*>(g_stats + (ep * 4 + layer) * S_ + m0 + wrow0 + gq + t * 8), sa, qa);
        __syncwarp();
        if (lane == 0) mbar_arrive(BA(B_XDONE));
        wgmma_wait<1>();
        if (elected) REL2(CM);
      }
      uint32_t s = 2;
#pragma unroll 1
      for (int i = 2; i < NF; ++i) {
        PROFL(tid_ == 128 && layer == PL + 1, 244 + 2 * i);
        mbar_wait(BA(FM + i), par);
        PROFL(tid_ == 128 && layer == PL + 1, 245 + 2 * i);
        const uint32_t da = dA0 + (XS + s) * 1024, dk = dB0 + s * 2048, dq = dB0 + (9 + s) * 1024;
        wgmma_fence();
#pragma unroll
        for (int k = 0; k < 4; ++k) wgmma_n128(acc, D128(da + k * 2), D128(dq + k * 128), 1);
        wgmma_commit();
        wgmma_wait<1>();
        if (elected) REL2(CM + i - 1);
        wgmma_fence();
#pragma unroll
        for (int k = 0; k < 4; ++k) wgmma_n256(acc, D128(da + k * 2), D128(dk + k * 128), 1);
        wgmma_commit();
        if (++s == 3) s = 0;
      }
#pragma unroll 1
      for (int i = NF; i < 15; ++i) {
        mbar_wait(BA(FM + i), par);
        const uint32_t da = dA0 + (XS + s) * 1024, dk = dB0 + s * 2048;
        wgmma_fence();
#pragma unroll
        for (int k = 0; k < 4; ++k) wgmma_n256(acc, D128(da + k * 2), D128(dk + k * 128), 1);
        wgmma_commit();
        wgmma_wait<1>();
        if (elected) REL2(CM + i - 1);
        if (++s == 3) s = 0;
      }
      {
        const uint64_t dap = desc64(((SB0 + SM_AP) >> 4) + wu * 64, 8), dbp = make_desc_ns(SB0 + SM_BP, 0, 128);
        mbar_wait(BA(B_STAT), par);
        mbar_wait(BA(FM + 15), par);
        PROFT(tid_ == 128, layer * 16 + 9);
        wgmma_fence();
        wgmma_n256_k(acc, dap, dbp, 1);
#pragma unroll
        for (int k = 0; k < 4; ++k) wgmma_n256(acc, D128(dA0 + XS * 1024 + k * 2), D128(dB0 + k * 128), 1);
        wgmma_commit();
        wgmma_wait<1>();
        if (elected) REL2(CM + 14);
        mbar_wait(BA(FT), par);
        wgmma_fence();
        wgmma_n128_k(acc, dap, dbp + 256, 1);
#pragma unroll
        for (int k = 0; k < 4; ++k) wgmma_n128(acc, D128(dA0 + (uint32_t)(TL_A & 15) * 1024 + k * 2), D128(dB0 + (uint32_t)(TL_B & 15) * 1024 + k * 128), 1);
        wgmma_commit();
        wgmma_wait<1>();
        if (elected) REL2(CM + 15);
#pragma unroll
        for (int i = 0; i < 128; ++i) asm volatile("" : "+f"(acc[i]) :: "memory");
      }
    }
    uint32_t of[8][4], o1[4][4];
    {
      PHASE_CTX();
      MMA_CTX();
      PROFT(tid_ == 128, layer * 16 + 1);
      PROFT(lane == 0 && layer == PL, 192 + cw);
      PROFT(tid_ == 128 && layer == PL, 160);
      uint64_t ta = (TL_A >> 4), tw = TL_B >> 4;
      uint32_t da, db, dz = dA0;
      auto sub = [&](int n) {
        const int j = n >> 2, k = n & 3;
        if (k == 0) {
          dz += c.zero;
          da = dz + ((uint32_t)ta & 15) * 1024; db = dB0 + ((uint32_t)tw & 15) * 1024;
          ta >>= 4; tw >>= 4;
          mbar_wait(BA(FT + j), par);
          wgmma_fence();
        }
        wgmma_n128(acc, D128(da + k * 2), D128(db + k * 128), 1);
        if (k == 3) {
          wgmma_commit();
          wgmma_wait<1>();
          if (elected) REL2(CT + j - 1);
        }
      };
      auto run = [&](int j0, int j1) {
#pragma unroll 1
        for (int j = j0; j < j1; ++j) {
          mbar_wait(BA(FT + j), par);
          da = dA0 + ((uint32_t)ta & 15) * 1024; db = dB0 + ((uint32_t)tw & 15) * 1024;
          ta >>= 4; tw >>= 4;
          wgmma_fence();
#pragma unroll
          for (int k = 0; k < 4; ++k) wgmma_n128(acc, D128(da + k * 2), D128(db + k * 128), 1);
          wgmma_commit();
          wgmma_wait<1>();
          if (elected) REL2(CT + j - 1);
        }
        ta = TL_A >> (4 * j1); tw = TL_B >> (4 * j1);
      };
      auto rest = [&](int j0) {
        run(j0, ND);
        wgmma_wait<0>();
        if (elected) REL2(CT + ND - 1);
#pragma unroll
        for (int i = 128; i < 192; ++i) asm volatile("" : "+f"(acc[i]) :: "memory");
      };
      auto wo0 = [&]() {
        wgmma_fence();
        wgmma_n128_rs0(acc, of[0], D128(dB0 + (uint32_t)(WO_B & 15) * 1024));
#pragma unroll
        for (int k = 1; k < 4; ++k) wgmma_n128_rs(acc, of[k], D128(dB0 + (uint32_t)(WO_B & 15) * 1024 + k * 128), 1);
        wgmma_commit();
      };
      const float rs0 = lds_f(sb + SM_RS + (16 + wrow0 + gq) * 4), rs1 = lds_f(sb + SM_RS + (24 + wrow0 + gq) * 4);
      mbar_wait(BA(CM + 14), par);
      if (par) {
        uint32_t kk[8][4], kp[8][4], vf[2][2][4][4];
        int sn = 4;
        float rj[4];
#pragma unroll
        for (int nt = 0; nt < 4; ++nt) rj[nt] = lds_f(sb + SM_RS + (wrow0 + nt * 8 + 2 * t + (gq & 1)) * 4);
#pragma unroll
        for (int i = 0; i < 4 * BT1; ++i) sub(sn++);
        {
          uint32_t vv[8][4];
#pragma unroll
          for (int jp = 0; jp < 8; ++jp) {
            kk[jp][0] = pack_bf16(acc[8 * jp], acc[8 * jp + 1]); kk[jp][1] = pack_bf16(acc[8 * jp + 4], acc[8 * jp + 5]);
            kk[jp][2] = pack_bf16(acc[8 * jp + 2], acc[8 * jp + 3]); kk[jp][3] = pack_bf16(acc[8 * jp + 6], acc[8 * jp + 7]);
#pragma unroll
            for (int i = 0; i < 4; ++i) vv[jp][i] = pack_bf16(acc[64 + 8 * jp + 2 * i], acc[65 + 8 * jp + 2 * i]);
          }
          if (cw == 7) {
            uint32_t* const hbuf = g_halo + (size_t)(((layer >> 1) * 17 + rb + 1) * 8 + g) * 2048;
#pragma unroll
            for (int jp = 0; jp < 8; ++jp) stg128(hbuf + jp * 128 + lane * 4, kk[jp][0], kk[jp][1], kk[jp][2], kk[jp][3]);
#pragma unroll
            for (int i = 0; i < 32; ++i) hbuf[1024 + (i >> 4) * 512 + (gq + (i & 1) * 8) * 32 + ((((i >> 1) & 7) ^ gq) << 2) + t] = vv[i >> 2][i & 3];
            __syncwarp();
            if (lane == 0) mbar_arrive(BA(B_OF0));
          }
#pragma unroll
          for (int jp = 0; jp < 8; ++jp) {
            sub(sn++);
            stsm_x4(sb + VB + (jp >> 2) * SLOT + rowo + (X ^ ((jp & 3) << 5)), vv[jp][0], vv[jp][1], vv[jp][2], vv[jp][3]);
          }
        }
        PROFT(tid_ == 128, layer * 16 + 2);
        const int e = gq & 1;
        float f0[4], f1[4], b0[4], b1[4];
#pragma unroll
        for (int nt = 0; nt < 4; ++nt) {
          const int kx = nt * 8 + 2 * t + e;
          const bool okk = (m0 + wrow0 + kx) >= 16;
          const int d0 = kx - gq, d1 = d0 - 8;
          const bool m0_ = okk && d0 >= 2 && d0 <= 16, m1_ = okk && d1 >= 2 && d1 <= 16;
          f0[nt] = m0_ ? rj[nt] * rs0 * (0.17677669529663687f * L2E) : 0.f;
          f1[nt] = m1_ ? rj[nt] * rs1 * (0.17677669529663687f * L2E) : 0.f;
          b0[nt] = m0_ ? 0.f : -1e30f; b1[nt] = m1_ ? 0.f : -1e30f;
        }
        uint32_t ko = sb + PH + cw * 4096 + lane * 16;
        mbar_wait(BA(CM + 15), par);
#pragma unroll
        for (int jp = 0; jp < 8; ++jp) {
          sub(sn++);
          sts128(ko + jp * 512, make_uint4(kk[jp][0], kk[jp][1], kk[jp][2], kk[jp][3]));
        }
#pragma unroll
        for (int i = 0; i < 4; ++i) sub(sn++);
        nbar<1, 256>();
        PROFT(tid_ == 128, layer * 16 + 3);
        rest(sn >> 2);
        PROFT(lane == 0 && layer == PL, 200 + cw);
        PROFT(tid_ == 128, layer * 16 + 10);
        if (cw == 0) mbar_wait(BA(B_HALO), (layer >> 1) & 1);
        PROFT(tid_ == 128, layer * 16 + 5);
        const uint32_t vs = sb + (cw ? VB + rowo - 2048 : SM_SD + 4096 + rowo), vst = cw ? SLOT : 2048;
        asm volatile("" : "+r"(ko));
        const uint32_t ka = ko + (cw ? -4096 : SM_SD - PH);
        const uint32_t psel = e ? 0x1054u : 0x5410u;
#pragma unroll
        for (int hp = 0; hp < 2; ++hp) {
#pragma unroll
          for (int i = 4 * hp; i < 4 * hp + 4; ++i) {
            const uint4 u = lds128(ka + i * 512);
            kp[i][0] = u.x; kp[i][1] = u.y; kp[i][2] = u.z; kp[i][3] = u.w;
          }
#pragma unroll
          for (int i = 4 * hp; i < 4 * hp + 4; ++i) {
            ldsm_x4_t(vf[0][i & 1][i >> 1][0], vf[0][i & 1][i >> 1][1], vf[0][i & 1][i >> 1][2], vf[0][i & 1][i >> 1][3], vs + (i >> 2) * vst + (X ^ ((i & 3) << 5)));
            ldsm_x4_t(vf[1][i & 1][i >> 1][0], vf[1][i & 1][i >> 1][1], vf[1][i & 1][i >> 1][2], vf[1][i & 1][i >> 1][3], sb + VB + (i >> 2) * SLOT + rowo + (X ^ ((i & 3) << 5)));
          }
          float l0[2][4], l1[2][4];
#pragma unroll
          for (int h = 0; h < 2; ++h) {
            const int H = 2 * hp + h;
            uint32_t qa[8];
#pragma unroll
            for (int i = 0; i < 8; ++i) qa[i] = pack_bf16(acc[128 + 16 * H + 2 * i], acc[129 + 16 * H + 2 * i]);
#pragma unroll
            for (int nt = 3; nt >= 0; --nt) {
              float sc[4] = {0.f, 0.f, 0.f, 0.f};
#pragma unroll
              for (int ks = 0; ks < 2; ++ks) {
                const uint32_t (&kf)[4] = nt < 2 ? kp[2 * H + ks] : kk[2 * H + ks];
                mma_bf16(sc, qa[4 * ks], qa[4 * ks + 1], qa[4 * ks + 2], qa[4 * ks + 3], kf[2 * (nt & 1)], kf[2 * (nt & 1) + 1]);
              }
              l0[h][nt] = fmaf(e ? sc[1] : sc[0], f0[nt], b0[nt]);
              l1[h][nt] = fmaf(e ? sc[3] : sc[2], f1[nt], b1[nt]);
            }
          }
          float mx0[2], mx1[2], s0[2], s1[2];
#pragma unroll
          for (int h = 0; h < 2; ++h) {
            mx0[h] = fmaxf(fmaxf(l0[h][0], l0[h][1]), l0[h][2]);
            mx1[h] = fmaxf(fmaxf(l1[h][1], l1[h][2]), l1[h][3]);
          }
#pragma unroll
          for (int o = 1; o <= 2; o <<= 1)
#pragma unroll
            for (int h = 0; h < 2; ++h) {
              mx0[h] = fmaxf(mx0[h], __shfl_xor_sync(0xffffffffu, mx0[h], o));
              mx1[h] = fmaxf(mx1[h], __shfl_xor_sync(0xffffffffu, mx1[h], o));
            }
#pragma unroll
          for (int h = 0; h < 2; ++h) {
#pragma unroll
            for (int nt = 0; nt < 3; ++nt) { l0[h][nt] = ex2(l0[h][nt] - mx0[h]); l1[h][nt + 1] = ex2(l1[h][nt + 1] - mx1[h]); }
            s0[h] = (l0[h][0] + l0[h][1]) + l0[h][2];
            s1[h] = (l1[h][1] + l1[h][2]) + l1[h][3];
          }
#pragma unroll
          for (int o = 1; o <= 2; o <<= 1)
#pragma unroll
            for (int h = 0; h < 2; ++h) {
              s0[h] += __shfl_xor_sync(0xffffffffu, s0[h], o);
              s1[h] += __shfl_xor_sync(0xffffffffu, s1[h], o);
            }
          uint32_t ow[2][2][4];
#pragma unroll
          for (int h = 0; h < 2; ++h) {
            const int H = 2 * hp + h;
            uint32_t pl[4], ph[4];
            const float i0 = rcp(s0[h]), i1 = rcp(s1[h]);
#pragma unroll
            for (int nt = 0; nt < 4; ++nt) {
              const uint32_t pk = pack_bf16(nt < 3 ? l0[h][nt] * i0 * rj[nt] : 0.f, nt > 0 ? l1[h][nt] * i1 * rj[nt] : 0.f);
              pl[nt] = nt < 3 ? __byte_perm(pk, 0u, psel) : 0u;
              ph[nt] = nt > 0 ? __byte_perm(pk, 0u, psel + 0x2222u) : 0u;
            }
#pragma unroll
            for (int nj = 0; nj < 4; ++nj) {
              float oa[4] = {0.f, 0.f, 0.f, 0.f};
#pragma unroll
              for (int ks = 0; ks < 2; ++ks)
                mma_bf16(oa, pl[2 * ks], ph[2 * ks], pl[2 * ks + 1], ph[2 * ks + 1], vf[ks][nj >> 1][H][2 * (nj & 1)], vf[ks][nj >> 1][H][2 * (nj & 1) + 1]);
              ow[h][0][nj] = pack_bf16(oa[0], oa[1]); ow[h][1][nj] = pack_bf16(oa[2], oa[3]);
            }
          }
          if (hp == 0) {
#pragma unroll
            for (int i = 0; i < 4; ++i) stg128(g_o + gfr + (i & 1) * 8 * D_ + (i >> 1) * 32, ow[i >> 1][i & 1][0], ow[i >> 1][i & 1][1], ow[i >> 1][i & 1][2], ow[i >> 1][i & 1][3]);
            __syncwarp();
            if (lane == 0) mbar_arrive(BA(B_OH0));
          } else {
#pragma unroll
            for (int i = 0; i < 16; ++i) o1[i >> 2][i & 3] = ow[i >> 3][(i >> 2) & 1][i & 3];
          }
#pragma unroll
          for (int i = 0; i < 16; ++i) of[4 * hp + (i >> 2)][i & 3] = ow[i >> 3][i & 1][(i >> 1) & 3];
          if (!hp) { PROFT(tid_ == 128, layer * 16 + 15); mbar_wait(BA(FW), par); }
        }
      } else {
        float sc[2] = {rs0 * L2E, rs1 * L2E};
        {
          const uint32_t vb = sb + VB + (rowo >> 1), X0 = (lchk ^ ((lane & 7) >> 1)) << 4;
          const uint32_t pb = sb + PH + (t & 1) * SLOT + (wrow0 + gq) * 128 + ((((t & 1) * 4 + (t & 2)) ^ gq) << 4);
          float kva[20], en[32], mx[2][2], mn[2][2];
#define PV(hp, j) acc[32 * (hp) + (j)]
          auto mm = [&](int hp, int j) {
            const int r = (j >> 1) & 1;
            if (j < 4 && !(j & 1)) { mx[hp][r] = PV(hp, j); mn[hp][r] = PV(hp, j); }
            else { mx[hp][r] = fmaxf(mx[hp][r], PV(hp, j)); mn[hp][r] = fminf(mn[hp][r], PV(hp, j)); }
          };
          auto mmx = [&](int hp) {
#pragma unroll
            for (int r = 0; r < 2; ++r) {
              mx[hp][r] = fmaxf(mx[hp][r], __shfl_xor_sync(0xffffffffu, mx[hp][r], 2)) * -sc[r];
              mn[hp][r] = fmaf(fminf(mn[hp][r], __shfl_xor_sync(0xffffffffu, mn[hp][r], 2)), sc[r], mx[hp][r]);
            }
          };
          auto stage = [&](int hp) {
#pragma unroll
            for (int i = 0; i < 20; ++i) asm volatile("" : "+f"(kva[i]) :: "memory");
            nbar_dyn(3 + wu, 128);
            const uint32_t ad = sb + VB + hp * SLOT + wg * 8192 + (2 * wq + ((lane >> 3) & 1)) * 640 + (lane & 7) * 16;
#pragma unroll
            for (int i = 0; i < 2; ++i)
              stsm_x4(ad + (2 * i + lchk) * 128, pack_bf16(kva[8 * i], kva[8 * i + 1]), pack_bf16(kva[8 * i + 2], kva[8 * i + 3]),
                      pack_bf16(kva[8 * i + 4], kva[8 * i + 5]), pack_bf16(kva[8 * i + 6], kva[8 * i + 7]));
            stsm_x2(ad + 512, pack_bf16(kva[16], 0.0625f), pack_bf16(kva[18], 0.0625f));
            fence_async_smem();
            __syncwarp();
            if (lane == 0) mbar_arrive(BA(B_KVDONE));
          };
          int sn = 4;
#pragma unroll
          for (int j = 0; j < 32; ++j) { if ((j & 7) == 7) sub(sn++); mm(0, j); }
          mmx(0);
#pragma unroll
          for (int hp = 0; hp < 2; ++hp) {
            float sp[2] = {0.f, 0.f}, sm[2] = {0.f, 0.f};
#pragma unroll
            for (int j = 0; j < 32; ++j) {
              const int r = (j >> 1) & 1, ns = hp ? SUBS1 : SUBS;
              if ((j * ns) / 32 != ((j + 1) * ns) / 32) {
                sub(sn++);
                if (hp && sn == 8 + SUBS + 4) { stage(0); PROFT(tid_ == 128, layer * 16 + 12); }
              }
              const float x = fmaf(PV(hp, j), sc[r], mx[hp][r]);
              PV(hp, j) = ex2(x); en[j] = ex2(mn[hp][r] - x);
              sp[r] += PV(hp, j); sm[r] += en[j];
              if (hp == 0) {
                mm(1, j);
                if ((j & 3) == 0) {
                  const int jp = 8 + (j >> 2);
                  stsm_x4(vb + ((jp - 8) >> 1) * 8192 + (X0 ^ ((jp & 1) << 5)), pack_bf16(acc[8 * jp], acc[8 * jp + 1]), pack_bf16(acc[8 * jp + 2], acc[8 * jp + 3]),
                          pack_bf16(acc[8 * jp + 4], acc[8 * jp + 5]), pack_bf16(acc[8 * jp + 6], acc[8 * jp + 7]));
                }
              }
            }
#pragma unroll
            for (int r = 0; r < 2; ++r) {
              sp[r] = rcp(sp[r] + __shfl_xor_sync(0xffffffffu, sp[r], 2)) * (r ? rs1 : rs0);
              sm[r] = rcp(sm[r] + __shfl_xor_sync(0xffffffffu, sm[r], 2)) * (r ? rs1 : rs0);
            }
            if (hp == 0) { mmx(1); mbar_wait(BA(CM + 15), par); }
            else { PROFT(tid_ == 128, layer * 16 + 11); nbar<1, 256>(); }
#pragma unroll
            for (int i = 0; i < 4; ++i) {
              const int r = i & 1, d = 16 * (i >> 1) + 2 * r;
              sts128((pb + r * 1024) ^ ((i >> 1) << 4), make_uint4(pack_bf16(PV(hp, d) * sp[r], PV(hp, d + 1) * sp[r]), pack_bf16(PV(hp, d + 4) * sp[r], PV(hp, d + 5) * sp[r]),
                                                                    pack_bf16(PV(hp, d + 8) * sp[r], PV(hp, d + 9) * sp[r]), pack_bf16(PV(hp, d + 12) * sp[r], PV(hp, d + 13) * sp[r])));
              sts128((pb + r * 1024) ^ ((i >> 1) << 4) ^ 64, make_uint4(pack_bf16(en[d] * sm[r], en[d + 1] * sm[r]), pack_bf16(en[d + 4] * sm[r], en[d + 5] * sm[r]),
                                                                         pack_bf16(en[d + 8] * sm[r], en[d + 9] * sm[r]), pack_bf16(en[d + 12] * sm[r], en[d + 13] * sm[r])));
            }
            fence_async_smem();
            nbar<1, 256>();
            const uint32_t dP = dB0 + (PH >> 4) + wu * 1024;
            const uint32_t dV = (dB0 & 0xFFFFu) + ((VB + hp * SLOT) >> 4) + (((SM_SD - VB - hp * SLOT) >> 4) << 16) + wu * (512u - (512u << 16));
            wgmma_fence();
#pragma unroll
            for (int ks = 0; ks < 8; ++ks) wgmma_n40_tt(kva, D128(dP + ks * 128), desc64(dV + ks * 64, 0x80000020u), ks != 0);
            wgmma_commit();
          }
#pragma unroll
          for (int i = 0; i < 4; ++i) sub(sn++);
          stage(1);
          PROFT(tid_ == 128, layer * 16 + 3);
          rest(sn >> 2);
          PROFT(lane == 0 && layer == PL, 200 + cw);
          PROFT(tid_ == 128, layer * 16 + 10);
        }
#define QV(H, i) acc[128 + 16 * (H) + (i)]
        float mx[4][2], mn[4][2];
        uint32_t ph[4][4][4];
        auto mnx = [&](int hp) {
#pragma unroll
          for (int H = 2 * hp; H < 2 * hp + 2; ++H)
#pragma unroll
            for (int r = 0; r < 2; ++r) {
              mx[H][r] = fmaxf(fmaxf(fmaxf(QV(H, 2 * r), QV(H, 2 * r + 1)), fmaxf(QV(H, 4 + 2 * r), QV(H, 5 + 2 * r))),
                               fmaxf(fmaxf(QV(H, 8 + 2 * r), QV(H, 9 + 2 * r)), fmaxf(QV(H, 12 + 2 * r), QV(H, 13 + 2 * r))));
              mn[H][r] = fminf(fminf(fminf(QV(H, 2 * r), QV(H, 2 * r + 1)), fminf(QV(H, 4 + 2 * r), QV(H, 5 + 2 * r))),
                               fminf(fminf(QV(H, 8 + 2 * r), QV(H, 9 + 2 * r)), fminf(QV(H, 12 + 2 * r), QV(H, 13 + 2 * r))));
            }
#pragma unroll
          for (int o = 1; o <= 2; o <<= 1)
#pragma unroll
            for (int H = 2 * hp; H < 2 * hp + 2; ++H)
#pragma unroll
              for (int r = 0; r < 2; ++r) {
                mx[H][r] = fmaxf(mx[H][r], __shfl_xor_sync(0xffffffffu, mx[H][r], o));
                mn[H][r] = fminf(mn[H][r], __shfl_xor_sync(0xffffffffu, mn[H][r], o));
              }
#pragma unroll
          for (int H = 2 * hp; H < 2 * hp + 2; ++H)
#pragma unroll
            for (int r = 0; r < 2; ++r) { mx[H][r] *= -sc[r]; mn[H][r] = fmaf(mn[H][r], sc[r], mx[H][r]); }
        };
        auto fm = [&](int H) {
#pragma unroll
          for (int i = 0; i < 8; ++i) {
            const int r = i & 1;
            const float x0 = fmaf(QV(H, 2 * i), sc[r], mx[H][r]), x1 = fmaf(QV(H, 2 * i + 1), sc[r], mx[H][r]);
            ph[H][i >> 2][i & 3] = pack_bf16(ex2(x0), ex2(x1));
            ph[H][2 + (i >> 2)][i & 3] = pack_bf16(ex2(mn[H][r] - x0), ex2(mn[H][r] - x1));
          }
        };
        mnx(0);
        fm(0); fm(1);
#pragma unroll
        for (int hp = 0; hp < 2; ++hp) {
          if (hp) mbar_wait(BA(FW), par);
          mbar_wait(BA(hp ? B_KVF1 : B_KVF), (layer >> 1) & 1);
          PROFT(tid_ == 128, layer * 16 + (hp ? 4 : 5));
          float oa[4][20];
          wgmma_fence();
#pragma unroll
          for (int s = 0; s < 2; ++s)
#pragma unroll
            for (int v = 0; v < 4; ++v) {
              const int h = v >> 1, s4 = 2 * (v & 1) + s;
              wgmma_n40_rs(oa[v], ph[2 * hp + h][s4], desc64((((SB0 + VB + hp * SLOT) >> 4) | (40u << 16)) + h * 512 + (s4 ^ (2 * h)) * 80, 8), s != 0);
            }
          wgmma_commit();
          if (hp == 0) { mnx(1); wgmma_wait<0>(); }
          else wgmma_wait<0>();
#pragma unroll
          for (int i = 0; i < 20; ++i) asm volatile("" : "+f"(oa[0][i]), "+f"(oa[1][i]), "+f"(oa[2][i]), "+f"(oa[3][i]) :: "memory");
          uint32_t ow[2][2][4];
#pragma unroll
          for (int h = 0; h < 2; ++h)
#pragma unroll
            for (int r = 0; r < 2; ++r) {
              const float a = oa[2 * h + 1][17 + 2 * r], b = oa[2 * h][17 + 2 * r];
              const float id = rcp(fmaf(oa[2 * h][16 + 2 * r], a, fmaf(a, 1e-6f, oa[2 * h + 1][16 + 2 * r]) * b));
              const float fa = a * id, fb = b * id;
#pragma unroll
              for (int j = 0; j < 4; ++j)
                ow[h][r][j] = pack_bf16(fmaf(oa[2 * h][4 * j + 2 * r], fa, oa[2 * h + 1][4 * j + 2 * r] * fb),
                                        fmaf(oa[2 * h][4 * j + 2 * r + 1], fa, oa[2 * h + 1][4 * j + 2 * r + 1] * fb));
            }
#pragma unroll
          for (int i = 0; i < 16; ++i) of[4 * hp + (i >> 2)][i & 3] = ow[i >> 3][i & 1][(i >> 1) & 3];
          if (hp == 0) {
#pragma unroll
            for (int i = 0; i < 4; ++i) stg128(g_o + gfr + (i & 1) * 8 * D_ + (i >> 1) * 32, ow[i >> 1][i & 1][0], ow[i >> 1][i & 1][1], ow[i >> 1][i & 1][2], ow[i >> 1][i & 1][3]);
            __syncwarp();
            if (lane == 0) mbar_arrive(BA(B_OH0));
            PROFT(tid_ == 128 && layer, layer * 16 + 15);
            fm(2); fm(3);
          } else {
#pragma unroll
            for (int i = 0; i < 16; ++i) o1[i >> 2][i & 3] = ow[i >> 3][(i >> 2) & 1][i & 3];
          }
        }
      }
      PROFT(tid_ == 128, layer * 16 + 6);
#pragma unroll
      for (int i = 0; i < 4; ++i) stg128(g_o + gfr + (i & 1) * 8 * D_ + (2 + (i >> 1)) * 32, o1[i][0], o1[i][1], o1[i][2], o1[i][3]);
      __syncwarp();
      if (lane == 0) { mbar_arrive(BA(B_OH1)); if (EF_USED) REL2(B_EF); }
      PROFT(lane == 0 && layer == PL, 208 + cw);
      fence_async_smem();
      wo0();
    }
    {
      PHASE_CTX();
      MMA_CTX();
      mbar_wait(BA(FW + 1), par);
      wgmma_fence();
#pragma unroll
      for (int k = 0; k < 4; ++k) wgmma_n128_rs(acc, of[4 + k], D128(dB0 + (uint32_t)((WO_B >> 4) & 15) * 1024 + k * 128), 1);
      wgmma_commit();
      wgmma_wait<1>();
      if (elected) REL2(CW);
      uint64_t ta = WO_A >> 8, tw = WO_B >> 8;
      auto run = [&](int i0, int i1) {
#pragma unroll 1
        for (int i = i0; i < i1; ++i) {
          mbar_wait(BA(FW + i), par);
          PROFL(tid_ == 128 && layer == PL, 160 + i);
          const uint32_t da = dA0 + ((uint32_t)ta & 15) * 1024, db = dB0 + ((uint32_t)tw & 15) * 1024;
          ta >>= 4; tw >>= 4;
          wgmma_fence();
#pragma unroll
          for (int k = 0; k < 4; ++k) wgmma_n128(acc, D128(da + k * 2), D128(db + k * 128), 1);
          wgmma_commit();
          wgmma_wait<1>();
          if (elected) REL2(CW + i - 1);
        }
        ta = WO_A >> (4 * (i1 & 15)); tw = WO_B >> (4 * (i1 & 15));
      };
      run(2, XRAT);
#pragma unroll
      for (int j = 0; j < 8 / XRN; ++j) {
#pragma unroll
        for (int i = j * XRN; i < (j + 1) * XRN; ++i) ldg128((layer ? g_x : c.x0) + gfr + (i & 1) * 8 * D_ + (i >> 1) * 32, xp[i][0], xp[i][1], xp[i][2], xp[i][3]);
        run(XRAT + j, j + 1 < 8 / XRN ? XRAT + j + 1 : 16);
      }
      if (layer == 0) {
#pragma unroll
        for (int o = 1; o <= 2; o <<= 1)
#pragma unroll
          for (int i = 0; i < 16; ++i) {
            const int j = o == 1 ? 2 * (i & 1) : (i & 1);
            uint32_t &a = xp[i >> 1][j], &b = xp[i >> 1][j + o];
            const uint32_t r = __shfl_xor_sync(0xffffffffu, (t & o) ? a : b, o);
            if (t & o) a = r; else b = r;
          }
      }
      if (layer != NLAYERS - 1) mbar_wait(BA(FM), par ^ 1);
      wgmma_wait<0>();
#pragma unroll
      for (int i = 128; i < 192; ++i) asm volatile("" : "+f"(acc[i]) :: "memory");
      if (elected) REL2(CW + 15);
      PROFT(lane == 0 && layer == PL, 216 + cw);
      PROFT(tid_ == 128, layer * 16 + 7);
#pragma unroll
      for (int i = 0; i < 32; ++i)
        xp[i >> 2][i & 3] = add_bf16x2(xp[i >> 2][i & 3], pack_bf16(acc[128 + 16 * (i >> 3) + 4 * (i & 3) + 2 * ((i >> 2) & 1)], acc[129 + 16 * (i >> 3) + 4 * (i & 3) + 2 * ((i >> 2) & 1)]));
      if (layer == NLAYERS - 1) {
#pragma unroll
        for (int i = 0; i < 8; ++i) stsm_x4(sb + (XS + (i >> 2)) * SLOT + (Y ^ ((i & 2) << 5)) + (i & 1) * 1024, xp[i][0], xp[i][1], xp[i][2], xp[i][3]);
        __syncwarp();
        slab_out_half(sb + XS * SLOT, c.out + (size_t)m0 * D_ + g * 128, wrow0, lane);
        slab_out_half(sb + (XS + 1) * SLOT, c.out + (size_t)m0 * D_ + g * 128 + 64, wrow0, lane);
        PROFT(tid_ == 128, layer * 16 + 24);
        break;
      }
#pragma unroll
      for (int i = 0; i < 4; ++i) stg128(g_x + gfr + (i & 1) * 8 * D_ + (i >> 1) * 32, xp[i][0], xp[i][1], xp[i][2], xp[i][3]);
      __syncwarp();
      if (lane == 0) mbar_arrive(BA(B_XH0));
#pragma unroll
      for (int i = 0; i < 16; ++i) xf[i >> 2][i & 3] = xp[2 * (i >> 3) + (i & 1)][(i >> 1) & 3];
      PROFT(tid_ == 128, layer * 16 + 24);
    }
  }
}

__device__ __forceinline__ uint64_t k_order(int o) {
  const uint32_t lo = (1u << (4 * o)) - 1u, h0 = (0xECA86420u & lo) | ((0xECA86420u >> 4) & ~lo);
  return (uint64_t)(2 * o) | ((uint64_t)(2 * o + 1) << 4) | ((uint64_t)(h0 & 0xFFFFFFFu) << 8) | ((uint64_t)((h0 & 0xFFFFFFFu) | 0x1111111u) << 36);
}

__global__ void __cluster_dims__(2, 1, 1) __launch_bounds__(384, 1)
mega_kernel(const __grid_constant__ Maps maps, const __grid_constant__ Ctx c, const bf16* __restrict__ wA, const bf16* __restrict__ wB,
            const bf16* __restrict__ woA, const bf16* __restrict__ woB) {
  if (blockIdx.x - c.boff >= 128u) {
    const unsigned int epoch = ld_relaxed(&g_epoch);
    const int e = (blockIdx.x - c.boff) & 3, tid = threadIdx.x;
    float s[8] = {0.f, 0.f, 0.f, 0.f, 0.f, 0.f, 0.f, 0.f};
    const uint32_t sb = smem_u32(smem_raw), bar = sb + SM_BAR;
    auto issue = [&](int i) {
      mbar_expect_tx(BA(i & 3), 49152);
      bulk_load(sb + (i & 3) * 49152, wB + (size_t)e * 256 * 3072 + i * 24576, 49152, BA(i & 3));
    };
#pragma unroll 1
    for (int i = tid; i < 5120; i += 384) reinterpret_cast<float4*>(g_kv)[e * 5120 + i] = make_float4(0.f, 0.f, 0.f, 0.f);
    __syncthreads();
    if (tid == 32) flag_add(&g_csflag[9].v);
    if (tid == 0) {
      if (SVD) __nanosleep(SVD);
#pragma unroll 1
      for (int i = 0; i < 4; ++i) {
        mbar_init(BA(i), 1);
        fence_async_smem();
        issue(i);
      }
    }
    __syncthreads();
#pragma unroll 1
    for (int i = 0; i < 32; ++i) {
      mbar_wait(BA(i & 3), (i >> 2) & 1);
#pragma unroll 2
      for (int r = 0; r < 8; ++r) {
        const uint4 v = lds128(sb + (i & 3) * 49152 + r * 6144 + tid * 16);
        s[0] += bf_lo(v.x); s[1] += bf_hi(v.x); s[2] += bf_lo(v.y); s[3] += bf_hi(v.y);
        s[4] += bf_lo(v.z); s[5] += bf_hi(v.z); s[6] += bf_lo(v.w); s[7] += bf_hi(v.w);
      }
      __syncthreads();
      if (tid == 0 && i < 28) issue(i + 4);
    }
    float* cd = g_cs + (epoch & 1) * 6144 + 3072 + ((tid >> 4) & 7) * 384 + (tid < 128 ? 256 : (tid >> 7) * 128 - 128) + (tid & 15) * 8;
    red_add4(cd, s[0], s[1], s[2], s[3]);
    red_add4(cd + 4, s[4], s[5], s[6], s[7]);
    __syncthreads();
    if (tid == 0) flag_add(&g_csflag[8].v);
    const int op = (epoch & 1) ^ 1;
    reinterpret_cast<float4*>(g_cs + op * 6144)[e * 384 + tid] = make_float4(0.f, 0.f, 0.f, 0.f);
#pragma unroll 1
    for (int i = tid; i < 1024; i += 384) reinterpret_cast<float4*>(g_stats + (op * 4 + e) * S_)[i] = make_float4(0.f, 0.f, 0.f, 0.f);
    return;
  }
  const int warp = __shfl_sync(0xffffffffu, threadIdx.x >> 5, 0), lane = threadIdx.x & 31;
  if (smem_u32(smem_raw) != SB0 + ((blockIdx.x & 1) << 24)) __trap();
  uint32_t cx = 0;
  {
  const int cid = (blockIdx.x - c.boff) >> 1, u7 = ((cid - 36) * 37) >> 8, cr = blockIdx.x & 1;
  const int g = cid < 4 ? 4 + cid : cid < 36 ? (cid - 4) >> 3 : 4 + u7, kf = (cid < 4 ? 0 : cid < 36 ? (cid - 4) & 7 : cid - 35 - 7 * u7) * 2 + cr;
  const uint32_t sb = SB0 + (cr << 24), bar = sb + SM_BAR;
  PROFT(lane == 0 && (warp == 0 || warp == 4), 224 + (warp >> 2) * 8);
  if (warp == 2) {
    if (lane < NMAP) asm volatile("prefetch.tensormap [%0];" ::"l"(&maps.m[lane]) : "memory");
    cx = ld_relaxed(&g_epoch);
    if (cid == 4 && cr == 0 && lane == 0) {
      uint32_t smid; asm volatile("mov.u32 %0, %%smid;" : "=r"(smid));
      asm volatile("st.relaxed.gpu.global.u32 [%0], %1;" ::"l"(&g_rot), "r"((cx + 1) * 8 + ((smid >> 1) & 7)) : "memory");
    }
  } else if (warp == 3) {
    cx = c_map[cid] + c_wop[lane] + c_wop[NWOP - lane] + c_aop[lane] + c_aop[NAOP - lane] + (uint32_t)(uintptr_t)g_x;
  } else if (warp >= 4 && warp < 8) {
    const int i = threadIdx.x - 128;
    asm volatile("prefetch.global.L2 [%0];" ::"l"(wA + (size_t)((kf & ~1) * 64 + cr * 32 + ((i >> 1) & 31)) * 3072 + (i >> 6) * 1024 + g * 128 + (i & 1) * 64));
  }
  if (warp < 2) {
    const int s = warp, kb = (kf & ~1) + s;
    if (lane == 0) {
      mbar_init(BA(FM + s), 1u);
      mbar_init(BA(B_RAW + warp), 1u);
      mbar_init(BA(warp ? B_X0 : B_KVS0), 1u);
      if (warp) mbar_init(BA(B_ID), 1u);
      asm volatile("fence.mbarrier_init.release.cluster;" ::: "memory");
    }
    __syncwarp();
    if (warp == 0) tma_2d_e(sb + SM_SD, &maps.m[MAP_PHI], 0, g * 128, BA(B_RAW));
    else if (W1DL) __nanosleep(W1DL);
#pragma unroll
    for (int j = 0; j < 6; ++j)
      tma_5d_e(sb + (j < 2 ? 2 * s : j < 4 ? 9 + s : 2 * s + 1) * SLOT + (j & 1) * 8192, &maps.m[MAP_WA], (j < 2 ? 1024 : j < 4 ? 0 : 2048) + g * 128 + (j & 1) * 64, 2 * kb,
               BA(j < 4 ? B_RAW + warp : FM + s));
    expect_tx_e(BA(B_RAW + warp), warp ? 32768 : 32768 + 8192);
    expect_tx_e(BA(FM + s), 32768);
  } else if (warp >= 4 && lane == 0) {
#pragma unroll 1
    for (int i = 2 + (warp - 4) * 13; i < 15 + (warp - 4) * 13; ++i)
      mbar_init(BA(i), 1u << ((i < CM ? 0u : i < B_EF ? 2u : (uint32_t)(BAR_LG >> (4 * ((i - B_EF) & 15)))) & 7u));
    asm volatile("fence.mbarrier_init.release.cluster;" ::: "memory");
  }
  __syncwarp();
  asm volatile("barrier.cluster.arrive.relaxed.aligned;" ::: "memory");
  if (threadIdx.x == 96 + c.zero) sts_f(sb + SM_ID + 4, __uint_as_float(cx));
  PROFT(lane == 0 && (warp == 0 || warp == 4), 225 + (warp >> 2) * 8);
  __syncwarp();
  PROFT(lane == 0 && (warp == 0 || warp == 4), 226 + (warp >> 2) * 8);
  }

  if (warp < 4) {
    asm volatile("setmaxnreg.dec.sync.aligned.u32 40;");
    PROFT(threadIdx.x == 0, 227);
    cluster_wait();
    PROFT(threadIdx.x == 0, 228);
    if (warp == 0 || warp == 3) {
    if (warp == 0) {
      STA_CTX();
      const unsigned int epoch = __shfl_sync(0xffffffffu, ld_relaxed(&g_epoch), 0), xbase = epoch * NLAYERS;
      (void)xbase;
      const uint64_t ordg = k_order(g);
      mbar_wait_u(BA(B_ID), 0);
      const int rb = (__shfl_sync(0xffffffffu, LD_ID(), 0) >> 3) & 15, m0 = rb * 128;
      tma_2d_e(sb + XS * SLOT, &maps.m[MAP_X0], (kf & ~1) * 64, m0, BA(FM));
      tma_2d_e(sb + (XS + 1) * SLOT, &maps.m[MAP_X0], (kf | 1) * 64, m0, BA(FM + 1));
      if (X0AT) {
        mbar_wait_u(BA(B_RAW + X0AT - 1), 0);
        tma_2d_e(sb + 11 * SLOT, &maps.m[MAP_X0], g * 128, m0, BA(B_X0));
        tma_2d_e(sb + 12 * SLOT, &maps.m[MAP_X0], g * 128 + 64, m0, BA(B_X0));
        expect_tx_e(BA(B_X0), 32768);
      }
#pragma unroll 1
      for (int lp = 0; lp < 2 * NLAYERS; ++lp) {
        const int layer = lp >> 1, n1 = (lp & 1) ? NAOP : NAOP - 14;
        int n = (lp & 1) ? NAOP - 14 : 0;
        const uint64_t ord = lp ? ordg : k_order(kf >> 1);
        uint32_t ready = lp ? 0u : 0xFFFFu, nop = c_aop[n];
        const unsigned int* fl = ((lp & 1) ? g_of : g_xf) + rb * 32;
        const CUtensorMap* tm = &maps.m[(lp & 1) ? MAP_O : lp ? MAP_X : MAP_X0];
        const uint32_t skip = layer ? 1u << 25 : 9u << 22;
        if (lp) mbar_wait_u(BA((lp & 1) ? B_OH0 : B_XH0), ((lp - 1) >> 1) & 1);
#pragma unroll 1
        for (; n < n1; ++n) {
          const uint32_t op = nop;
          nop = c_aop[n + 1];
          const uint32_t kb = (uint32_t)(ord >> ((op >> 2) & 60)) & 15;
          uint32_t dst = sb + (op & 15) * SLOT, kc = kb * 64, fb = bar + ((op >> 5) & 0x3F8), need = ~ready & (1u << kb);
          asm volatile("" : "+r"(dst), "+r"(kc), "+r"(fb), "+r"(need));
          const uint32_t eb = bar + ((op >> 12) & 0x3F8), ep = (layer ^ (op >> 22)) & 1;
          bool fr = op & skip;
          if (need) {
            if (!fr) fr = __all_sync(0xffffffffu, mbar_test_wait(eb, ep));
            PROFT(lane == 0 && (n == 0 || n == NAOP - 14), 64 + layer * 16 + (n ? 2 : 0));
            src_wait<0>(fl, xbase + layer + 1, need, ready, lane);
            fence_async_all();
          }
          if (!fr) mbar_wait_u(eb, ep);
          tma_2d_e(dst, tm, kc, m0, fb);
          PROFT(lane == 0 && (n == 0 || n == NAOP - 14), 64 + layer * 16 + (n ? 3 : 1));
          PROFL(lane == 0 && layer == PL && n >= NAOP - 14, 178 + n - (NAOP - 14));
          PROFL(lane == 0 && layer == PL + 1 && n < 4, 242 + n);
        }
      }
    } else {
      STA_CTX();
      const unsigned int epoch = __shfl_sync(0xffffffffu, ld_relaxed(&g_epoch), 0), xbase = epoch * NLAYERS;
      (void)xbase;
      const uint64_t ordg = k_order(g);
#pragma unroll 1
      for (int layer = 0; layer < NLAYERS; ++layer) {
        const uint64_t ordq = layer ? ordg : k_order(kf >> 1);
        uint32_t ready = layer ? 0xFFFFu : 0u, nop = c_wop[0];
        const CUtensorMap* tq = &maps.m[(layer & 1) ? MAP_WB : MAP_WF];
        const CUtensorMap* tk = &maps.m[(layer & 1) ? MAP_WB : cr ? MAP_WA : MAP_WF];
        const uint32_t skip = layer ? 1u << 25 : 9u << 22, pm = layer ? 0xE0u : 0u;
        int n = 0;
#pragma unroll 1
        for (; n < NWOP - 16; ++n) {
          const uint32_t op = nop;
          nop = c_wop[n + 1];
          const uint32_t isq = (op >> 23) & 1, fb = bar + ((op >> 5) & 0x3F8);
          const uint32_t kb = (uint32_t)(ordq >> ((op >> 2) & 60)) & 15;
          const CUtensorMap* tm = (isq ? tq : tk) + ((op & pm) ? 1 : 0);
          const uint32_t dst = sb + (op & 15) * SLOT + cr * (isq ? 8192 : SLOT);
          const int col = g * 128 + (isq ? cr * 64 : 1024 + cr * 1024);
          if (layer == 0) {
            if ((op & 0x7E00) == 0) continue;
            const uint32_t need = ((isq || !cr) ? 1u << kb : 0u) | (((op >> 22) & 1) ? 0u : (((op >> 15) & 127) == CM ? 1u : 3u) << (kf & ~1));
            if ((ready & need) != need) {
              src_wait<0>(g_wff + g * 32, epoch + 1, need, ready, lane);
              fence_async_all();
            }
            if ((op & 15) >= 11) mbar_wait_u(BA(B_XT), 0);
          }
          wait_tma_5d_mc(!(op & skip), bar + ((op >> 12) & 0x3F8), (layer ^ (op >> 22)) & 1, dst, tm, col, 2 * kb, fb);
          if (!isq) tma_5d_mc_e(dst + 8192, tm, col + 64, 2 * kb, fb);
          if (op >> 26) expect_tx_e(fb, (op >> 26) * 8192);
          PROFL(lane == 0 && layer == PL + 1 && n < 16, 128 + n);
        }
        const CUtensorMap* to = &maps.m[(layer & 1) ? MAP_WOB : MAP_WOA];
#pragma unroll 1
        for (; n < NWOP; ++n) {
          const uint32_t op = nop;
          nop = c_wop[n + 1];
          const uint32_t fb = bar + ((op >> 5) & 0x3F8), kb = (uint32_t)(ordg >> ((op >> 2) & 60)) & 15;
          if (WH < 16 && n == NWOP - 16 + WH && !(layer & 1)) mbar_wait_u(BA(B_KVS), (layer >> 1) & 1);
          wait_tma_5d_mc(!((op >> 25) & 1), bar + ((op >> 12) & 0x3F8), layer & 1, sb + (op & 15) * SLOT + cr * 8192, to + ((op & 0xE0) ? 1 : 0), g * 128 + cr * 64, 2 * kb, fb);
          expect_tx_e(fb, (op >> 26) * 8192);
          PROFL(lane == 0 && layer == PL, 144 + ((op >> 8) & 127) - FW);
        }
      }
    }
    } else if (warp == 1) {
      STA_CTX();
      const unsigned int epoch = __shfl_sync(0xffffffffu, ld_relaxed(&g_epoch), 0), xbase = epoch * NLAYERS;
      (void)xbase;
      if (lane == 0) {
        mbar_wait_s(BA(B_WFD), 0);
        PROFT(true, 229);
#pragma unroll 1
        for (int j = 0; j < 4; ++j) tma_store_5d(&maps.m[MAP_WF], sb + (j < 2 ? 2 * cr : 9 + cr) * SLOT + (j & 1) * 8192, (j < 2 ? 1024 : 0) + g * 128 + (j & 1) * 64, 2 * kf);
        bulk_commit();
        bulk_wait0();
        PROFT(true, 230);
        fence_async_all();
        flag_set(g_wff + g * 32 + kf, epoch + 1);
        mbar_wait_s(BA(B_ID), 0);
        PROFT(true, 64 + 13);
#pragma unroll 1
        for (int e = 0; e < NLAYERS; ++e) {
          BASE_CTX();
          bid_ -= c.boff;
          DYN_CTX(LD_ID());
          if (e > 0) {
            mbar_wait_s(BA(B_XH0), (e - 1) & 1);
            PROFT(e == PL + 1, 240);
            flag_set(g_xf + rb * 32 + 2 * g, xbase + e + 1);
            PROFT(e == PL + 1, 241);
          }
          mbar_wait_s(BA(B_XDONE), e & 1);
          PROFT(true, 64 + e * 16 + 4);
          flag_set(g_xf + rb * 32 + 2 * g + 1, xbase + e + 1);
          if (e == 0) {
            flag_add(&g_csflag[g].v);
            flag_wait(&g_csflag[9].v, epoch * 4u + 4u);
            fence_async_all();
#pragma unroll 1
            for (int i = 0; i < 4; ++i) {
              mbar_wait_s(BA(CM + PFM + PFS * i), 0);
              l2_prefetch(i < 3 ? wB + (size_t)(i * 128 + bid_) * 8192 : woA + (size_t)bid_ * 8192, 16384);
            }
          }
          if (e == 1) l2_prefetch(woB + (size_t)bid_ * 8192, 16384);
          PROFT(true, 64 + e * 16 + 7);
          if ((e & 1) == 0) {
            bf16* kvl = g_kv + ((e >> 1) * 8 + g) * 10240;
#pragma unroll 1
            for (int hp = 0; hp < 2; ++hp) {
              mbar_wait_s(BA(B_KVDONE), hp);
#pragma unroll 1
              for (int i = 0; i < 4; ++i) {
                const int ch = (i + (rb >> 2)) & 3;
                bulk_red_add(kvl + hp * 5120 + ch * 1280, sb + VB + hp * SLOT + (ch >> 1) * 8192 + (ch & 1) * 2560, 2560);
                bulk_commit();
              }
              bulk_wait0();
              PROFT(true, 64 + e * 16 + (hp ? 10 : 6));
              fence_async_all();
              flag_add(&g_kvflag[hp * 8 + g].v);
              mbar_arrive(BA(hp ? B_KVS : B_KVS0));
              PROFT(e > 0 && hp, 64 + e * 16 + 8);
            }
          }
          if (e & 1) {
            mbar_wait_s(BA(B_OF0), (e >> 1) & 1);
            flag_set(g_hf + rb * 32 + g, xbase + e + 1);
            if (rb) flag_wait(g_hf + (rb - 1) * 32 + g, xbase + e + 1);
            fence_async_all();
            mbar_expect_tx(BA(B_HALO), 8192);
            bulk_load(sb + SM_SD, g_halo + (size_t)(((e >> 1) * 17 + rb) * 8 + g) * 2048, 8192, BA(B_HALO));
            PROFT(true, 64 + e * 16 + 15);
          }
          mbar_wait_s(BA(B_OH0), e & 1);
          PROFT(e > 0, 64 + e * 16 + 13);
          flag_set(g_of + rb * 32 + 2 * g, xbase + e + 1);
          PROFT(true, 64 + e * 16 + 9);
          mbar_wait_s(BA(B_OH1), e & 1);
          PROFT(true, 64 + e * 16 + 5);
          flag_set(g_of + rb * 32 + 2 * g + 1, xbase + e + 1);
          PROFT(true, 64 + e * 16 + 11);
        }
        if (bid_ == 0) g_epoch = epoch + 1;
      }
    } else {
      STA_CTX();
      const unsigned int epoch = __shfl_sync(0xffffffffu, cx, 0), xbase = epoch * NLAYERS;
      (void)xbase;
      uint32_t idp = kf >> 1;
      if (g >= 4) {
        uint32_t v, n = 0;
#pragma unroll 1
        do { v = __shfl_sync(0xffffffffu, ld_relaxed(&g_rot), 0); } while ((v >> 3) != ((epoch + 1) & 0x1FFFFFFFu) && ++n < (1u << 20));
        const uint32_t c0 = (8 - v) & 7;
        idp = idp == 0 ? c0 : idp - 1 + (idp - 1 >= c0 ? 1 : 0);
      }
      idp = g | ((2 * idp + cr) << 3) | ((epoch & 1) << 8);
      if (lane == 0) {
        sts_f(sb + SM_ID, __uint_as_float(idp));
        mbar_arrive(BA(B_ID));
      }
      PROFT(lane == 0, 231);
      if (lane < 16) sts_f(sb + SM_RS + lane * 4, 0.f);
#pragma unroll 1
      for (int layer = 0; layer < NLAYERS; ++layer) {
#define HLP_CTX() BASE_CTX(); uint32_t idl_ = idp; asm volatile("" : "+r"(idl_)); DYN_CTX(idl_); int lane = threadIdx.x & 31; asm volatile("" : "+r"(lane)); const bool isB = layer & 1, hal = isB && rb > 0; (void)hal;
#pragma unroll 1
        for (int ph = 0; ph < 2; ++ph) {
          HLP_CTX();
          if (ph == (layer == 0)) {
            const float* cs = g_cs + (epoch & 1) * 6144 + g * 384;
            if (layer) mbar_wait_u(BA(CT), (layer - 1) & 1);
            if (layer < 2) {
              if (lane == 0) flag_wait_slow(&g_csflag[isB ? 8 : g].v, isB ? epoch * 4u + 4u : epoch * 16u + 16u);
              __syncwarp();
            }
#pragma unroll 1
            for (int i0 = 0; i0 < 12; i0 += 4) {
              float a[4];
#pragma unroll
              for (int i = 0; i < 4; ++i) a[i] = __ldcg(cs + isB * 3072 + (i0 + i) * 32 + lane);
#pragma unroll
              for (int i = 0; i < 4; ++i) {
                const float c1 = bf16r(a[i]), c2 = bf16r(a[i] - c1), c3 = (a[i] - c1) - c2;
                sts128(sb + SM_BP + ((i0 + i) * 32 + lane) * 16, make_uint4(pack_bf16(c1, c2), pack_bf16(c3, 0.f), 0u, 0u));
              }
            }
          } else {
            uint32_t rdy = 0u;
            mbar_wait_u(BA(CM + 3), layer & 1);
            src_wait<128>(g_xf + rb * 32, xbase + layer + 1, 0xAAAAu, rdy, lane);
            rdy = 0u;
            if (hal) src_wait<128>(g_xf + (rb - 1) * 32, xbase + layer + 1, 0xAAAAu, rdy, lane);
            const float2* sp = g_stats + ((epoch & 1) * 4 + layer) * S_ + m0 + lane;
            float2 u[5];
#pragma unroll
            for (int i = 0; i < 4; ++i) u[i] = __ldcg(sp + i * 32);
            u[4] = __ldcg(sp - (hal ? 16 : 0));
#pragma unroll 1
            for (int i = 0; i < 5; ++i) {
              const float mean = u[0].x * (1.f / D_);
              const float var = fmaxf(fmaf(-u[0].x, mean, u[0].y) * (1.f / D_), 0.f);
              const float sd = bf16r(sqrtf(bf16r(bf16r(var) + 1e-5f)));
              const int R = i * 32 + lane;
              if (i < 4) {
                const float hm = -0.5f * bf16r(mean);
                if (!isB) sts128(sb + SM_SD + R * 64 + ((R >> 1) & 3) * 16, make_uint4(__float_as_uint(sd) >> 16, __float_as_uint(sd) >> 16, __float_as_uint(sd) >> 16, __float_as_uint(sd) >> 16));
                sts128(sb + SM_AP + R * 16, make_uint4(pack_bf16(hm, hm), pack_bf16(hm, 0.f), 0u, 0u));
              }
              if (i < 4 || (hal && lane < 16)) sts_f(sb + SM_RS + (i < 4 ? 16 + R : lane) * 4, __fdividef(1.f, sd));
#pragma unroll
              for (int j = 0; j < 4; ++j) u[j] = u[j + 1];
            }
            PROFT(lane == 0, 64 + layer * 16 + 12);
          }
        }
        HLP_CTX();
        fence_async_smem();
        __syncwarp();
        if (lane == 0) mbar_arrive(BA(B_STAT));
        PROFT(lane == 0, 64 + layer * 16 + 14);
        if (!isB && lane == 0) {
#pragma unroll 1
          for (int hp = 0; hp < 2; ++hp) {
            mbar_wait_s(BA(hp ? B_KVS : B_KVS0), (layer >> 1) & 1);
            flag_wait(&g_kvflag[hp * 8 + g].v, epoch * (16u * ((NLAYERS + 1) / 2)) + 16u * ((layer >> 1) + 1));
            const bf16* kvl = g_kv + ((layer >> 1) * 8 + g) * 10240 + hp * 5120;
            const uint32_t kb = BA(hp ? B_KVF1 : B_KVF);
            fence_async_all();
            mbar_expect_tx(kb, 10240);
            bulk_load(sb + VB + hp * SLOT, kvl, 5120, kb);
            bulk_load(sb + VB + hp * SLOT + 8192, kvl + 2560, 5120, kb);
            PROFT(hp == 0, 64 + layer * 16 + 15);
          }
        }
        __syncwarp();
      }
    }
    __syncwarp();
    asm volatile("barrier.cluster.arrive.relaxed.aligned;" ::: "memory");
    cluster_wait();
  } else {
    asm volatile("setmaxnreg.inc.sync.aligned.u32 232;");
    PROFT(threadIdx.x == 128, 235);
    cluster_wait();
    PROFT(threadIdx.x == 128, 236);
    consumer(c);
    asm volatile("bar.warp.sync 0xffffffff;\nbarrier.cluster.arrive.relaxed.aligned;\nbarrier.cluster.wait.aligned;\n" ::: "memory");
  }
}

typedef CUresult (*PFN_encodeTiled)(CUtensorMap*, CUtensorMapDataType, cuuint32_t, void*, const cuuint64_t*, const cuuint64_t*,
                                    const cuuint32_t*, const cuuint32_t*, CUtensorMapInterleave, CUtensorMapSwizzle,
                                    CUtensorMapL2promotion, CUtensorMapFloatOOBfill);

static void make_map2(PFN_encodeTiled enc, CUtensorMap* m, const void* ptr, uint64_t cols, uint64_t rows, uint32_t box_c, uint32_t box_r) {
  cuuint64_t dims[2] = {cols, rows};
  cuuint64_t strides[1] = {cols * 2};
  cuuint32_t box[2] = {box_c, box_r};
  cuuint32_t es[2] = {1, 1};
  CUresult r = enc(m, CU_TENSOR_MAP_DATA_TYPE_BFLOAT16, 2, const_cast<void*>(ptr), dims, strides, box, es, CU_TENSOR_MAP_INTERLEAVE_NONE,
                   box_c == 64 ? CU_TENSOR_MAP_SWIZZLE_128B : CU_TENSOR_MAP_SWIZZLE_64B, CU_TENSOR_MAP_L2_PROMOTION_L2_256B, CU_TENSOR_MAP_FLOAT_OOB_FILL_NONE);
  (void)r;
}
static void make_map5(PFN_encodeTiled enc, CUtensorMap* m, const void* ptr, uint64_t cols) {
  for (int p = 0; p < 2; ++p) {
    cuuint64_t dims[5] = {cols, 2, 4, 4, 32};
    cuuint64_t strides[4] = {cols * 2, cols * (p ? 16 : 4), cols * (p ? 4 : 16), cols * 64};
    cuuint32_t box[5] = {64, 2, 4, 4, 2};
    cuuint32_t es[5] = {1, 1, 1, 1, 1};
    CUresult r = enc(m + p, CU_TENSOR_MAP_DATA_TYPE_BFLOAT16, 5, const_cast<void*>(ptr), dims, strides, box, es, CU_TENSOR_MAP_INTERLEAVE_NONE,
                     CU_TENSOR_MAP_SWIZZLE_128B, CU_TENSOR_MAP_L2_PROMOTION_L2_256B, CU_TENSOR_MAP_FLOAT_OOB_FILL_NONE);
    (void)r;
  }
}

extern "C" void kernel_launch(void* const* d_in, const int* in_sizes, int n_in, void* d_out, int out_size) {
  const bf16* A_x = (const bf16*)d_in[0];
  const bf16* A_wqkv = (const bf16*)d_in[1];
  const bf16* A_wphi = (const bf16*)d_in[2];
  const bf16* A_wo = (const bf16*)d_in[3];
  const bf16* B_wqkv = (const bf16*)d_in[5];
  const bf16* B_wo = (const bf16*)d_in[6];
  bf16* out = (bf16*)d_out;

  static PFN_encodeTiled enc = nullptr;
  static bf16 *p_x, *p_o, *p_wf;
  static uint32_t boff;
  if (!enc) {
    void* fn = nullptr; cudaDriverEntryPointQueryResult qr;
    cudaGetDriverEntryPoint("cuTensorMapEncodeTiled", &fn, cudaEnableDefault, &qr);
    enc = (PFN_encodeTiled)fn;
    cudaGetSymbolAddress((void**)&p_x, g_x);
    cudaGetSymbolAddress((void**)&p_o, g_o);
    cudaGetSymbolAddress((void**)&p_wf, g_wf);
    cudaFuncSetAttribute(mega_kernel, cudaFuncAttributeMaxDynamicSharedMemorySize, SM_TOTAL);
    cudaLaunchConfig_t cfg = {};
    cudaLaunchAttribute at; at.id = cudaLaunchAttributeClusterDimension; at.val.clusterDim.x = 2; at.val.clusterDim.y = 1; at.val.clusterDim.z = 1;
    cfg.gridDim = dim3(132); cfg.blockDim = dim3(384); cfg.dynamicSmemBytes = SM_TOTAL; cfg.attrs = &at; cfg.numAttrs = 1;
    int nc = 0;
    if (cudaOccupancyMaxActiveClusters(&nc, mega_kernel, &cfg) != cudaSuccess) { nc = 0; (void)cudaGetLastError(); }
    boff = nc >= 66 ? 0u : 4u;
  }
  Maps maps;
  make_map5(enc, &maps.m[MAP_WF], p_wf, 2048);
  make_map5(enc, &maps.m[MAP_WA], A_wqkv, 3072);
  make_map5(enc, &maps.m[MAP_WB], B_wqkv, 3072);
  make_map5(enc, &maps.m[MAP_WOA], A_wo, 1024);
  make_map5(enc, &maps.m[MAP_WOB], B_wo, 1024);
  make_map2(enc, &maps.m[MAP_X0], A_x, 1024, 2048, 64, 128);
  make_map2(enc, &maps.m[MAP_X], p_x, 1024, 2048, 64, 128);
  make_map2(enc, &maps.m[MAP_O], p_o, 1024, 2048, 64, 128);
  make_map2(enc, &maps.m[MAP_PHI], A_wphi, 32, 1024, 32, 128);
  Ctx c; c.zero = 0u; c.boff = boff; c.x0 = A_x; c.out = out;
  mega_kernel<<<132, 384, SM_TOTAL, cudaStreamPerThread>>>(maps, c, A_wqkv, B_wqkv, A_wo, B_wo);
}
```

```cpp
#include <cuda_runtime.h>
#include <cuda_bf16.h>
#include <cuda.h>
#include <stdint.h>

typedef __nv_bfloat16 bf16;

constexpr int S_ = 2048, D_ = 1024;

struct __align__(128) Flag { unsigned int v; unsigned int pad[31]; };
__device__ __align__(1024) bf16 g_x[S_ * D_];
__device__ __align__(1024) bf16 g_o[S_ * D_];
__device__ __align__(1024) uint32_t g_halo[2 * 17 * 8 * 2048];
__device__ __align__(1024) bf16 g_kv[2 * 8 * 10240];
__device__ __align__(1024) float2 g_stats[2 * 4 * S_];
__device__ __align__(1024) float g_cs[2 * 2 * 3072];
__device__ __align__(1024) bf16 g_wf[D_ * 2048];
__device__ Flag g_kvflag[16], g_csflag[10];
__device__ __align__(128) unsigned int g_xf[16 * 32], g_of[16 * 32];
__device__ __align__(128) unsigned int g_hf[16 * 32];
__device__ __align__(128) unsigned int g_wff[8 * 32];
__device__ unsigned int g_epoch, g_rot, g_err;
#define PROFT(cond, idx) asm volatile("" ::: "memory")

#define SUSP 20000
__device__ __forceinline__ uint32_t smem_u32(const void* p) { return (uint32_t)__cvta_generic_to_shared(p); }
__device__ __forceinline__ void mbar_init(uint32_t bar, uint32_t count) {
  asm volatile("mbarrier.init.shared::cta.b64 [%0], %1;" ::"r"(bar), "r"(count) : "memory");
}
__device__ __forceinline__ void mbar_expect_tx(uint32_t bar, uint32_t bytes) {
  asm volatile("mbarrier.arrive.expect_tx.shared::cta.b64 _, [%0], %1;" ::"r"(bar), "r"(bytes) : "memory");
}
__device__ __forceinline__ void mbar_arrive(uint32_t bar) {
  asm volatile("mbarrier.arrive.shared::cta.b64 _, [%0];" ::"r"(bar) : "memory");
}
__device__ __forceinline__ bool mbar_try_wait(uint32_t bar, uint32_t parity) {
  uint32_t ok;
  asm volatile("{\n.reg .pred p;\nmbarrier.try_wait.parity.shared::cta.b64 p, [%1], %2;\nselp.b32 %0, 1, 0, p;\n}\n"
               : "=r"(ok) : "r"(bar), "r"(parity) : "memory");
  return ok != 0;
}
__device__ __forceinline__ bool mbar_try_wait_s(uint32_t bar, uint32_t parity) {
  uint32_t ok;
  asm volatile("{\n.reg .pred p;\nmbarrier.try_wait.parity.shared::cta.b64 p, [%1], %2, %3;\nselp.b32 %0, 1, 0, p;\n}\n"
               : "=r"(ok) : "r"(bar), "r"(parity), "r"(SUSP) : "memory");
  return ok != 0;
}
__device__ __forceinline__ void mbar_wait_s(uint32_t bar, uint32_t parity) {
  uint32_t n = 0;
  bool ok;
#pragma unroll 1
  do { ++n; ok = mbar_try_wait_s(bar, parity); } while (!ok && n < (1u << 12));
}
__device__ __forceinline__ bool mbar_test_wait(uint32_t bar, uint32_t parity) {
  uint32_t ok;
  asm volatile("{\n.reg .pred p;\nmbarrier.test_wait.parity.shared::cta.b64 p, [%1], %2;\nselp.b32 %0, 1, 0, p;\n}\n"
               : "=r"(ok) : "r"(bar), "r"(parity) : "memory");
  return ok != 0;
}
__device__ __forceinline__ uint64_t gtimer() {
  uint64_t t; asm volatile("mov.u64 %0, %globaltimer;" : "=l"(t)); return t;
}
__device__ __forceinline__ void mbar_wait(uint32_t bar, uint32_t parity) {
  uint32_t n = 0;
  bool ok;
#pragma unroll 1
  do { ++n; ok = mbar_try_wait(bar, parity); } while (!ok && n < (1u << 22));
}
__device__ __forceinline__ unsigned int ld_acquire(const unsigned int* p) {
  unsigned int v; asm volatile("ld.acquire.gpu.global.u32 %0, [%1];" : "=r"(v) : "l"(p) : "memory"); return v;
}
__device__ __forceinline__ void flag_add(unsigned int* p) {
  asm volatile("red.release.gpu.global.add.u32 [%0], 1;" ::"l"(p) : "memory");
}
__device__ __forceinline__ void flag_set(unsigned int* p, unsigned int v) {
  asm volatile("st.release.gpu.global.u32 [%0], %1;" ::"l"(p), "r"(v) : "memory");
}
template <int SLEEP>
__device__ __forceinline__ void src_wait(const unsigned int* f, unsigned int target, uint32_t need, uint32_t& ready, int lane) {
  uint32_t n = 0;
#pragma unroll 1
  while ((ready & need) != need) {
    const unsigned int v = ld_acquire(f + (lane & 15));
    ready = __ballot_sync(0xffffffffu, (int)(v - target) >= 0);
    if (SLEEP) { if ((ready & need) != need) __nanosleep(SLEEP); }
    if (++n > (1u << 20)) break;
  }
  __syncwarp();
}
__device__ __forceinline__ unsigned int ld_relaxed(const unsigned int* p);
__device__ __forceinline__ unsigned int ld_relaxed(const unsigned int* p) {
  unsigned int v; asm volatile("ld.relaxed.gpu.global.u32 %0, [%1];" : "=r"(v) : "l"(p) : "memory"); return v;
}
template <int SLEEP>
__device__ __forceinline__ void flag_wait_t(const unsigned int* p, unsigned int target) {
  uint32_t n = 0;
#pragma unroll 1
  while ((int)(ld_acquire(p) - target) < 0) {
    if (SLEEP) __nanosleep(SLEEP);
    if (++n > (1u << 20)) break;
  }
}
__device__ __forceinline__ void flag_wait(const unsigned int* p, unsigned int target) { flag_wait_t<0>(p, target); }
__device__ __forceinline__ void flag_wait_slow(const unsigned int* p, unsigned int target) { flag_wait_t<256>(p, target); }
__device__ __forceinline__ void mbar_wait_u(uint32_t bar, uint32_t parity) {
  uint32_t n = 0;
#pragma unroll 1
  while (!__all_sync(0xffffffffu, SUSP ? mbar_try_wait_s(bar, parity) : mbar_try_wait(bar, parity))) {
    if (++n > (SUSP ? 1u << 12 : 1u << 22)) break;
  }
}
__device__ __forceinline__ void expect_tx_e(uint32_t bar, uint32_t bytes) {
  asm volatile("{\n.reg .pred p;\nelect.sync _|p, 0xffffffff;\n@p mbarrier.arrive.expect_tx.shared::cta.b64 _, [%0], %1;\n}\n" ::"r"(bar), "r"(bytes) : "memory");
}
__device__ __forceinline__ void tma_2d_e(uint32_t dst, const CUtensorMap* tm, int c0, int c1, uint32_t bar) {
  asm volatile("{\n.reg .pred p;\nelect.sync _|p, 0xffffffff;\n"
               "@p cp.async.bulk.tensor.2d.shared::cluster.global.mbarrier::complete_tx::bytes [%0], [%1, {%2, %3}], [%4];\n}\n"
               ::"r"(dst), "l"(tm), "r"(c0), "r"(c1), "r"(bar) : "memory");
}
__device__ __forceinline__ void tma_5d_e(uint32_t dst, const CUtensorMap* tm, int c0, int c4, uint32_t bar) {
  asm volatile("{\n.reg .pred p;\nelect.sync _|p, 0xffffffff;\n"
               "@p cp.async.bulk.tensor.5d.shared::cluster.global.mbarrier::complete_tx::bytes [%0], [%1, {%2, %5, %5, %5, %3}], [%4];\n}\n"
               ::"r"(dst), "l"(tm), "r"(c0), "r"(c4), "r"(bar), "r"(0) : "memory");
}
__device__ __forceinline__ void tma_5d_mc_e(uint32_t dst, const CUtensorMap* tm, int c0, int c4, uint32_t bar) {
  asm volatile("{\n.reg .pred p;\nelect.sync _|p, 0xffffffff;\n"
               "@p cp.async.bulk.tensor.5d.shared::cluster.global.mbarrier::complete_tx::bytes.multicast::cluster [%0], [%1, {%2, %6, %6, %6, %3}], [%4], %5;\n}\n"
               ::"r"(dst), "l"(tm), "r"(c0), "r"(c4), "r"(bar), "h"((uint16_t)3), "r"(0) : "memory");
}
__device__ __forceinline__ void wait_tma_5d_mc(bool w, uint32_t eb, uint32_t par, uint32_t dst, const CUtensorMap* tm, int c0, int c4, uint32_t fb) {
  asm volatile("" : "+r"(dst), "+l"(tm), "+r"(c0), "+r"(c4), "+r"(fb));
  if (w) mbar_wait_u(eb, par);
  tma_5d_mc_e(dst, tm, c0, c4, fb);
}
__device__ __forceinline__ void stg128(void* p, uint32_t a, uint32_t b, uint32_t c, uint32_t d) {
  asm volatile("st.global.v4.u32 [%0], {%1,%2,%3,%4};" ::"l"(p), "r"(a), "r"(b), "r"(c), "r"(d) : "memory");
}
__device__ __forceinline__ void stg128_p(bool on, void* p, uint32_t a, uint32_t b, uint32_t c, uint32_t d) {
  asm volatile("{\n.reg .pred p;\nsetp.ne.b32 p, %5, 0;\n@p st.global.v4.u32 [%0], {%1,%2,%3,%4};\n}\n" ::"l"(p), "r"(a), "r"(b), "r"(c), "r"(d), "r"((int)on) : "memory");
}
__device__ __forceinline__ void ldg128(const void* p, uint32_t& a, uint32_t& b, uint32_t& c, uint32_t& d) {
  asm volatile("ld.global.cg.v4.u32 {%0,%1,%2,%3}, [%4];" : "=r"(a), "=r"(b), "=r"(c), "=r"(d) : "l"(p) : "memory");
}
__device__ __forceinline__ void release2c(uint32_t off) {
  asm volatile("mbarrier.arrive.shared::cluster.b64 _, [%0];\nmbarrier.arrive.shared::cluster.b64 _, [%1];" ::"r"(off), "r"(off + (1u << 24)) : "memory");
}
__device__ __forceinline__ void tma_store_5d(const CUtensorMap* tm, uint32_t src, int c0, int c4) {
  asm volatile("cp.async.bulk.tensor.5d.global.shared::cta.bulk_group [%0, {%2, %4, %4, %4, %3}], [%1];"
               ::"l"(tm), "r"(src), "r"(c0), "r"(c4), "r"(0) : "memory");
}
__device__ __forceinline__ void bulk_load(uint32_t dst, const void* src, uint32_t bytes, uint32_t bar) {
  asm volatile("cp.async.bulk.shared::cluster.global.mbarrier::complete_tx::bytes [%0], [%1], %2, [%3];" ::"r"(dst), "l"(src), "r"(bytes), "r"(bar) : "memory");
}
__device__ __forceinline__ void bulk_red_add(void* dst, uint32_t src, uint32_t bytes) {
  asm volatile("cp.reduce.async.bulk.global.shared::cta.bulk_group.add.noftz.bf16 [%0], [%1], %2;" ::"l"(dst), "r"(src), "r"(bytes) : "memory");
}
__device__ __forceinline__ void bulk_commit() { asm volatile("cp.async.bulk.commit_group;" ::: "memory"); }
__device__ __forceinline__ void bulk_wait0() { asm volatile("cp.async.bulk.wait_group 0;" ::: "memory"); }
__device__ __forceinline__ void fence_async_smem() { asm volatile("fence.proxy.async.shared::cta;" ::: "memory"); }
__device__ __forceinline__ void fence_async_all() { asm volatile("fence.proxy.async.global;" ::: "memory"); }
__device__ __forceinline__ void wgmma_fence() { asm volatile("wgmma.fence.sync.aligned;" ::: "memory"); }
__device__ __forceinline__ void wgmma_commit() { asm volatile("wgmma.commit_group.sync.aligned;" ::: "memory"); }
template <int N> __device__ __forceinline__ void wgmma_wait() { asm volatile("wgmma.wait_group.sync.aligned %0;" ::"n"(N) : "memory"); }
__device__ __forceinline__ void cluster_wait() { asm volatile("barrier.cluster.wait.acquire.aligned;" ::: "memory"); }
template <int ID, int N> __device__ __forceinline__ void nbar() { asm volatile("bar.sync %0, %1;" ::"n"(ID), "n"(N) : "memory"); }
__device__ __forceinline__ uint64_t desc64(uint32_t lo, uint32_t hi) { return (uint64_t)lo | ((uint64_t)hi << 32); }
__device__ __forceinline__ uint32_t pack_bf16(float lo, float hi) {
  uint32_t r; asm("cvt.rn.bf16x2.f32 %0, %1, %2;" : "=r"(r) : "f"(hi), "f"(lo)); return r;
}
__device__ __forceinline__ uint32_t add_bf16x2(uint32_t a, uint32_t b) {
  uint32_t r; asm("add.rn.bf16x2 %0, %1, %2;" : "=r"(r) : "r"(a), "r"(b)); return r;
}
__device__ __forceinline__ float bf16r(float x) { return __bfloat162float(__float2bfloat16_rn(x)); }
__device__ __forceinline__ float bf_lo(uint32_t u) { return __uint_as_float(u << 16); }
__device__ __forceinline__ float bf_hi(uint32_t u) { return __uint_as_float(u & 0xFFFF0000u); }
__device__ __forceinline__ float ex2(float x) { float r; asm("ex2.approx.ftz.f32 %0, %1;" : "=f"(r) : "f"(x)); return r; }
__device__ __forceinline__ float rcp(float x) { float r; asm("rcp.approx.ftz.f32 %0, %1;" : "=f"(r) : "f"(x)); return r; }
__device__ __forceinline__ void mma_bf16(float (&d)[4], uint32_t a0, uint32_t a1, uint32_t a2, uint32_t a3, uint32_t b0, uint32_t b1) {
  asm("mma.sync.aligned.m16n8k16.row.col.f32.bf16.bf16.f32 {%0,%1,%2,%3}, {%4,%5,%6,%7}, {%8,%9}, {%0,%1,%2,%3};"
               : "+f"(d[0]), "+f"(d[1]), "+f"(d[2]), "+f"(d[3]) : "r"(a0), "r"(a1), "r"(a2), "r"(a3), "r"(b0), "r"(b1));
}
__device__ __forceinline__ void ldsm_x4(uint32_t& r0, uint32_t& r1, uint32_t& r2, uint32_t& r3, uint32_t addr) {
  asm volatile("ldmatrix.sync.aligned.m8n8.x4.shared.b16 {%0,%1,%2,%3}, [%4];"
               : "=r"(r0), "=r"(r1), "=r"(r2), "=r"(r3) : "r"(addr) : "memory");
}
__device__ __forceinline__ void ldsm_x4_t(uint32_t& r0, uint32_t& r1, uint32_t& r2, uint32_t& r3, uint32_t addr) {
  asm volatile("ldmatrix.sync.aligned.m8n8.x4.trans.shared.b16 {%0,%1,%2,%3}, [%4];"
               : "=r"(r0), "=r"(r1), "=r"(r2), "=r"(r3) : "r"(addr) : "memory");
}
__device__ __forceinline__ void stsm_x4(uint32_t addr, uint32_t r0, uint32_t r1, uint32_t r2, uint32_t r3) {
  asm volatile("stmatrix.sync.aligned.m8n8.x4.shared.b16 [%0], {%1,%2,%3,%4};"
               ::"r"(addr), "r"(r0), "r"(r1), "r"(r2), "r"(r3) : "memory");
}
__device__ __forceinline__ void stsm_x2(uint32_t addr, uint32_t r0, uint32_t r1) {
  asm volatile("stmatrix.sync.aligned.m8n8.x2.shared.b16 [%0], {%1,%2};" ::"r"(addr), "r"(r0), "r"(r1) : "memory");
}
__device__ __forceinline__ uint4 lds128(uint32_t addr) {
  uint4 v; asm volatile("ld.shared.v4.b32 {%0,%1,%2,%3}, [%4];" : "=r"(v.x), "=r"(v.y), "=r"(v.z), "=r"(v.w) : "r"(addr) : "memory"); return v;
}
__device__ __forceinline__ void sts128(uint32_t addr, uint4 v) {
  asm volatile("st.shared.v4.b32 [%0], {%1,%2,%3,%4};" ::"r"(addr), "r"(v.x), "r"(v.y), "r"(v.z), "r"(v.w) : "memory");
}
__device__ __forceinline__ float lds_f(uint32_t addr) {
  float v; asm volatile("ld.shared.f32 %0, [%1];" : "=f"(v) : "r"(addr) : "memory"); return v;
}
__device__ __forceinline__ void nbar_dyn(int id, int n) { asm volatile("bar.sync %0, %1;" ::"r"(id), "r"(n) : "memory"); }
__device__ __forceinline__ uint64_t make_desc_ns(uint32_t addr, uint32_t lbo_bytes, uint32_t sbo_bytes) {
  return (uint64_t)((addr & 0x3FFFF) >> 4) | ((uint64_t)(lbo_bytes >> 4) << 16) | ((uint64_t)(sbo_bytes >> 4) << 32);
}
__device__ __forceinline__ void sts_f(uint32_t addr, float v) { asm volatile("st.shared.f32 [%0], %1;" ::"r"(addr), "f"(v) : "memory"); }
__device__ __forceinline__ void sts64(uint32_t addr, uint32_t a, uint32_t b) {
  asm volatile("st.shared.v2.b32 [%0], {%1,%2};" ::"r"(addr), "r"(a), "r"(b) : "memory");
}
__device__ __forceinline__ void sts_f2(uint32_t addr, float a, float b) {
  asm volatile("st.shared.v2.f32 [%0], {%1,%2};" ::"r"(addr), "f"(a), "f"(b) : "memory");
}
__device__ __forceinline__ void red_add2_p(bool on, float* p, float a, float b) {
  asm volatile("{\n.reg .pred p;\nsetp.ne.b32 p, %3, 0;\n@p red.global.add.v2.f32 [%0], {%1,%2};\n}\n" ::"l"(p), "f"(a), "f"(b), "r"((int)on) : "memory");
}
__device__ __forceinline__ void red_add4(float* p, float a, float b, float c, float d) {
  asm volatile("red.global.add.v4.f32 [%0], {%1,%2,%3,%4};" ::"l"(p), "f"(a), "f"(b), "f"(c), "f"(d) : "memory");
}
__device__ __forceinline__ void red_add1(float* p, float a) {
  asm volatile("red.global.add.f32 [%0], %1;" ::"l"(p), "f"(a) : "memory");
}
__device__ __forceinline__ void l2_prefetch(const void* p, uint32_t bytes) {
  asm volatile("cp.async.bulk.prefetch.L2.global [%0], %1;" ::"l"(p), "r"(bytes) : "memory");
}

__device__ __forceinline__ void wgmma_n256(float (&d)[192], uint64_t da, uint64_t db, int scale_d) {
  asm volatile("{\n.reg .pred p;\nsetp.ne.b32 p, %130, 0;\n"
    "wgmma.mma_async.sync.aligned.m64n256k16.f32.bf16.bf16 {%0, %1, %2, %3, %4, %5, %6, %7, %8, %9, %10, %11, %12, %13, %14, %15, %16, %17, %18, %19, %20, %21, %22, %23, %24, %25, %26, %27, %28, %29, %30, %31, %32, %33, %34, %35, %36, %37, %38, %39, %40, %41, %42, %43, %44, %45, %46, %47, %48, %49, %50, %51, %52, %53, %54, %55, %56, %57, %58, %59, %60, %61, %62, %63, %64, %65, %66, %67, %68, %69, %70, %71, %72, %73, %74, %75, %76, %77, %78, %79, %80, %81, %82, %83, %84, %85, %86, %87, %88, %89, %90, %91, %92, %93, %94, %95, %96, %97, %98, %99, %100, %101, %102, %103, %104, %105, %106, %107, %108, %109, %110, %111, %112, %113, %114, %115, %116, %117, %118, %119, %120, %121, %122, %123, %124, %125, %126, %127}, %128, %129, p, 1, 1, 0, 1;\n}\n"
    : "+f"(d[0]), "+f"(d[1]), "+f"(d[2]), "+f"(d[3]), "+f"(d[4]), "+f"(d[5]), "+f"(d[6]), "+f"(d[7]), "+f"(d[8]), "+f"(d[9]), "+f"(d[10]), "+f"(d[11]), "+f"(d[12]), "+f"(d[13]), "+f"(d[14]), "+f"(d[15]), "+f"(d[16]), "+f"(d[17]), "+f"(d[18]), "+f"(d[19]), "+f"(d[20]), "+f"(d[21]), "+f"(d[22]), "+f"(d[23]), "+f"(d[24]), "+f"(d[25]), "+f"(d[26]), "+f"(d[27]), "+f"(d[28]), "+f"(d[29]), "+f"(d[30]), "+f"(d[31]), "+f"(d[32]), "+f"(d[33]), "+f"(d[34]), "+f"(d[35]), "+f"(d[36]), "+f"(d[37]), "+f"(d[38]), "+f"(d[39]), "+f"(d[40]), "+f"(d[41]), "+f"(d[42]), "+f"(d[43]), "+f"(d[44]), "+f"(d[45]), "+f"(d[46]), "+f"(d[47]), "+f"(d[48]), "+f"(d[49]), "+f"(d[50]), "+f"(d[51]), "+f"(d[52]), "+f"(d[53]), "+f"(d[54]), "+f"(d[55]), "+f"(d[56]), "+f"(d[57]), "+f"(d[58]), "+f"(d[59]), "+f"(d[60]), "+f"(d[61]), "+f"(d[62]), "+f"(d[63]), "+f"(d[64]), "+f"(d[65]), "+f"(d[66]), "+f"(d[67]), "+f"(d[68]), "+f"(d[69]), "+f"(d[70]), "+f"(d[71]), "+f"(d[72]), "+f"(d[73]), "+f"(d[74]), "+f"(d[75]), "+f"(d[76]), "+f"(d[77]), "+f"(d[78]), "+f"(d[79]), "+f"(d[80]), "+f"(d[81]), "+f"(d[82]), "+f"(d[83]), "+f"(d[84]), "+f"(d[85]), "+f"(d[86]), "+f"(d[87]), "+f"(d[88]), "+f"(d[89]), "+f"(d[90]), "+f"(d[91]), "+f"(d[92]), "+f"(d[93]), "+f"(d[94]), "+f"(d[95]), "+f"(d[96]), "+f"(d[97]), "+f"(d[98]), "+f"(d[99]), "+f"(d[100]), "+f"(d[101]), "+f"(d[102]), "+f"(d[103]), "+f"(d[104]), "+f"(d[105]), "+f"(d[106]), "+f"(d[107]), "+f"(d[108]), "+f"(d[109]), "+f"(d[110]), "+f"(d[111]), "+f"(d[112]), "+f"(d[113]), "+f"(d[114]), "+f"(d[115]), "+f"(d[116]), "+f"(d[117]), "+f"(d[118]), "+f"(d[119]), "+f"(d[120]), "+f"(d[121]), "+f"(d[122]), "+f"(d[123]), "+f"(d[124]), "+f"(d[125]), "+f"(d[126]), "+f"(d[127])
    : "l"(da), "l"(db), "r"(scale_d));
}
__device__ __forceinline__ void wgmma_n128(float (&d)[192], uint64_t da, uint64_t db, int scale_d) {
  asm volatile("{\n.reg .pred p;\nsetp.ne.b32 p, %66, 0;\n"
    "wgmma.mma_async.sync.aligned.m64n128k16.f32.bf16.bf16 {%0, %1, %2, %3, %4, %5, %6, %7, %8, %9, %10, %11, %12, %13, %14, %15, %16, %17, %18, %19, %20, %21, %22, %23, %24, %25, %26, %27, %28, %29, %30, %31, %32, %33, %34, %35, %36, %37, %38, %39, %40, %41, %42, %43, %44, %45, %46, %47, %48, %49, %50, %51, %52, %53, %54, %55, %56, %57, %58, %59, %60, %61, %62, %63}, %64, %65, p, 1, 1, 0, 1;\n}\n"
    : "+f"(d[128]), "+f"(d[129]), "+f"(d[130]), "+f"(d[131]), "+f"(d[132]), "+f"(d[133]), "+f"(d[134]), "+f"(d[135]), "+f"(d[136]), "+f"(d[137]), "+f"(d[138]), "+f"(d[139]), "+f"(d[140]), "+f"(d[141]), "+f"(d[142]), "+f"(d[143]), "+f"(d[144]), "+f"(d[145]), "+f"(d[146]), "+f"(d[147]), "+f"(d[148]), "+f"(d[149]), "+f"(d[150]), "+f"(d[151]), "+f"(d[152]), "+f"(d[153]), "+f"(d[154]), "+f"(d[155]), "+f"(d[156]), "+f"(d[157]), "+f"(d[158]), "+f"(d[159]), "+f"(d[160]), "+f"(d[161]), "+f"(d[162]), "+f"(d[163]), "+f"(d[164]), "+f"(d[165]), "+f"(d[166]), "+f"(d[167]), "+f"(d[168]), "+f"(d[169]), "+f"(d[170]), "+f"(d[171]), "+f"(d[172]), "+f"(d[173]), "+f"(d[174]), "+f"(d[175]), "+f"(d[176]), "+f"(d[177]), "+f"(d[178]), "+f"(d[179]), "+f"(d[180]), "+f"(d[181]), "+f"(d[182]), "+f"(d[183]), "+f"(d[184]), "+f"(d[185]), "+f"(d[186]), "+f"(d[187]), "+f"(d[188]), "+f"(d[189]), "+f"(d[190]), "+f"(d[191])
    : "l"(da), "l"(db), "r"(scale_d));
}
__device__ __forceinline__ void wgmma_n256_k(float (&d)[192], uint64_t da, uint64_t db, int scale_d) {
  asm volatile("{\n.reg .pred p;\nsetp.ne.b32 p, %130, 0;\n"
    "wgmma.mma_async.sync.aligned.m64n256k16.f32.bf16.bf16 {%0, %1, %2, %3, %4, %5, %6, %7, %8, %9, %10, %11, %12, %13, %14, %15, %16, %17, %18, %19, %20, %21, %22, %23, %24, %25, %26, %27, %28, %29, %30, %31, %32, %33, %34, %35, %36, %37, %38, %39, %40, %41, %42, %43, %44, %45, %46, %47, %48, %49, %50, %51, %52, %53, %54, %55, %56, %57, %58, %59, %60, %61, %62, %63, %64, %65, %66, %67, %68, %69, %70, %71, %72, %73, %74, %75, %76, %77, %78, %79, %80, %81, %82, %83, %84, %85, %86, %87, %88, %89, %90, %91, %92, %93, %94, %95, %96, %97, %98, %99, %100, %101, %102, %103, %104, %105, %106, %107, %108, %109, %110, %111, %112, %113, %114, %115, %116, %117, %118, %119, %120, %121, %122, %123, %124, %125, %126, %127}, %128, %129, p, 1, 1, 0, 0;\n}\n"
    : "+f"(d[0]), "+f"(d[1]), "+f"(d[2]), "+f"(d[3]), "+f"(d[4]), "+f"(d[5]), "+f"(d[6]), "+f"(d[7]), "+f"(d[8]), "+f"(d[9]), "+f"(d[10]), "+f"(d[11]), "+f"(d[12]), "+f"(d[13]), "+f"(d[14]), "+f"(d[15]), "+f"(d[16]), "+f"(d[17]), "+f"(d[18]), "+f"(d[19]), "+f"(d[20]), "+f"(d[21]), "+f"(d[22]), "+f"(d[23]), "+f"(d[24]), "+f"(d[25]), "+f"(d[26]), "+f"(d[27]), "+f"(d[28]), "+f"(d[29]), "+f"(d[30]), "+f"(d[31]), "+f"(d[32]), "+f"(d[33]), "+f"(d[34]), "+f"(d[35]), "+f"(d[36]), "+f"(d[37]), "+f"(d[38]), "+f"(d[39]), "+f"(d[40]), "+f"(d[41]), "+f"(d[42]), "+f"(d[43]), "+f"(d[44]), "+f"(d[45]), "+f"(d[46]), "+f"(d[47]), "+f"(d[48]), "+f"(d[49]), "+f"(d[50]), "+f"(d[51]), "+f"(d[52]), "+f"(d[53]), "+f"(d[54]), "+f"(d[55]), "+f"(d[56]), "+f"(d[57]), "+f"(d[58]), "+f"(d[59]), "+f"(d[60]), "+f"(d[61]), "+f"(d[62]), "+f"(d[63]), "+f"(d[64]), "+f"(d[65]), "+f"(d[66]), "+f"(d[67]), "+f"(d[68]), "+f"(d[69]), "+f"(d[70]), "+f"(d[71]), "+f"(d[72]), "+f"(d[73]), "+f"(d[74]), "+f"(d[75]), "+f"(d[76]), "+f"(d[77]), "+f"(d[78]), "+f"(d[79]), "+f"(d[80]), "+f"(d[81]), "+f"(d[82]), "+f"(d[83]), "+f"(d[84]), "+f"(d[85]), "+f"(d[86]), "+f"(d[87]), "+f"(d[88]), "+f"(d[89]), "+f"(d[90]), "+f"(d[91]), "+f"(d[92]), "+f"(d[93]), "+f"(d[94]), "+f"(d[95]), "+f"(d[96]), "+f"(d[97]), "+f"(d[98]), "+f"(d[99]), "+f"(d[100]), "+f"(d[101]), "+f"(d[102]), "+f"(d[103]), "+f"(d[104]), "+f"(d[105]), "+f"(d[106]), "+f"(d[107]), "+f"(d[108]), "+f"(d[109]), "+f"(d[110]), "+f"(d[111]), "+f"(d[112]), "+f"(d[113]), "+f"(d[114]), "+f"(d[115]), "+f"(d[116]), "+f"(d[117]), "+f"(d[118]), "+f"(d[119]), "+f"(d[120]), "+f"(d[121]), "+f"(d[122]), "+f"(d[123]), "+f"(d[124]), "+f"(d[125]), "+f"(d[126]), "+f"(d[127])
    : "l"(da), "l"(db), "r"(scale_d));
}
__device__ __forceinline__ void wgmma_n128_k(float (&d)[192], uint64_t da, uint64_t db, int scale_d) {
  asm volatile("{\n.reg .pred p;\nsetp.ne.b32 p, %66, 0;\n"
    "wgmma.mma_async.sync.aligned.m64n128k16.f32.bf16.bf16 {%0, %1, %2, %3, %4, %5, %6, %7, %8, %9, %10, %11, %12, %13, %14, %15, %16, %17, %18, %19, %20, %21, %22, %23, %24, %25, %26, %27, %28, %29, %30, %31, %32, %33, %34, %35, %36, %37, %38, %39, %40, %41, %42, %43, %44, %45, %46, %47, %48, %49, %50, %51, %52, %53, %54, %55, %56, %57, %58, %59, %60, %61, %62, %63}, %64, %65, p, 1, 1, 0, 0;\n}\n"
    : "+f"(d[128]), "+f"(d[129]), "+f"(d[130]), "+f"(d[131]), "+f"(d[132]), "+f"(d[133]), "+f"(d[134]), "+f"(d[135]), "+f"(d[136]), "+f"(d[137]), "+f"(d[138]), "+f"(d[139]), "+f"(d[140]), "+f"(d[141]), "+f"(d[142]), "+f"(d[143]), "+f"(d[144]), "+f"(d[145]), "+f"(d[146]), "+f"(d[147]), "+f"(d[148]), "+f"(d[149]), "+f"(d[150]), "+f"(d[151]), "+f"(d[152]), "+f"(d[153]), "+f"(d[154]), "+f"(d[155]), "+f"(d[156]), "+f"(d[157]), "+f"(d[158]), "+f"(d[159]), "+f"(d[160]), "+f"(d[161]), "+f"(d[162]), "+f"(d[163]), "+f"(d[164]), "+f"(d[165]), "+f"(d[166]), "+f"(d[167]), "+f"(d[168]), "+f"(d[169]), "+f"(d[170]), "+f"(d[171]), "+f"(d[172]), "+f"(d[173]), "+f"(d[174]), "+f"(d[175]), "+f"(d[176]), "+f"(d[177]), "+f"(d[178]), "+f"(d[179]), "+f"(d[180]), "+f"(d[181]), "+f"(d[182]), "+f"(d[183]), "+f"(d[184]), "+f"(d[185]), "+f"(d[186]), "+f"(d[187]), "+f"(d[188]), "+f"(d[189]), "+f"(d[190]), "+f"(d[191])
    : "l"(da), "l"(db), "r"(scale_d));
}
__device__ __forceinline__ void wgmma_n40_tt(float (&d)[20], uint64_t da, uint64_t db, int scale_d) {
  asm volatile("{\n.reg .pred p;\nsetp.ne.b32 p, %22, 0;\n"
    "wgmma.mma_async.sync.aligned.m64n40k16.f32.bf16.bf16 {%0, %1, %2, %3, %4, %5, %6, %7, %8, %9, %10, %11, %12, %13, %14, %15, %16, %17, %18, %19}, %20, %21, p, 1, 1, 1, 1;\n}\n"
    : "+f"(d[0]), "+f"(d[1]), "+f"(d[2]), "+f"(d[3]), "+f"(d[4]), "+f"(d[5]), "+f"(d[6]), "+f"(d[7]), "+f"(d[8]), "+f"(d[9]), "+f"(d[10]), "+f"(d[11]), "+f"(d[12]), "+f"(d[13]), "+f"(d[14]), "+f"(d[15]), "+f"(d[16]), "+f"(d[17]), "+f"(d[18]), "+f"(d[19])
    : "l"(da), "l"(db), "r"(scale_d));
}
__device__ __forceinline__ void wgmma_n40_rs(float (&d)[20], const uint32_t (&a)[4], uint64_t db, int scale_d) {
  asm volatile("{\n.reg .pred p;\nsetp.ne.b32 p, %25, 0;\n"
    "wgmma.mma_async.sync.aligned.m64n40k16.f32.bf16.bf16 {%0, %1, %2, %3, %4, %5, %6, %7, %8, %9, %10, %11, %12, %13, %14, %15, %16, %17, %18, %19}, {%20, %21, %22, %23}, %24, p, 1, 1, 1;\n}\n"
    : "+f"(d[0]), "+f"(d[1]), "+f"(d[2]), "+f"(d[3]), "+f"(d[4]), "+f"(d[5]), "+f"(d[6]), "+f"(d[7]), "+f"(d[8]), "+f"(d[9]), "+f"(d[10]), "+f"(d[11]), "+f"(d[12]), "+f"(d[13]), "+f"(d[14]), "+f"(d[15]), "+f"(d[16]), "+f"(d[17]), "+f"(d[18]), "+f"(d[19])
    : "r"(a[0]), "r"(a[1]), "r"(a[2]), "r"(a[3]), "l"(db), "r"(scale_d));
}
__device__ __forceinline__ void wgmma_n128_0(float (&d)[192], uint64_t da, uint64_t db) {
  asm volatile("{\n.reg .pred p;\nsetp.ne.b32 p, 0, 0;\n"
    "wgmma.mma_async.sync.aligned.m64n128k16.f32.bf16.bf16 {%0, %1, %2, %3, %4, %5, %6, %7, %8, %9, %10, %11, %12, %13, %14, %15, %16, %17, %18, %19, %20, %21, %22, %23, %24, %25, %26, %27, %28, %29, %30, %31, %32, %33, %34, %35, %36, %37, %38, %39, %40, %41, %42, %43, %44, %45, %46, %47, %48, %49, %50, %51, %52, %53, %54, %55, %56, %57, %58, %59, %60, %61, %62, %63}, %64, %65, p, 1, 1, 0, 1;\n}\n"
    : "=f"(d[128]), "=f"(d[129]), "=f"(d[130]), "=f"(d[131]), "=f"(d[132]), "=f"(d[133]), "=f"(d[134]), "=f"(d[135]), "=f"(d[136]), "=f"(d[137]), "=f"(d[138]), "=f"(d[139]), "=f"(d[140]), "=f"(d[141]), "=f"(d[142]), "=f"(d[143]), "=f"(d[144]), "=f"(d[145]), "=f"(d[146]), "=f"(d[147]), "=f"(d[148]), "=f"(d[149]), "=f"(d[150]), "=f"(d[151]), "=f"(d[152]), "=f"(d[153]), "=f"(d[154]), "=f"(d[155]), "=f"(d[156]), "=f"(d[157]), "=f"(d[158]), "=f"(d[159]), "=f"(d[160]), "=f"(d[161]), "=f"(d[162]), "=f"(d[163]), "=f"(d[164]), "=f"(d[165]), "=f"(d[166]), "=f"(d[167]), "=f"(d[168]), "=f"(d[169]), "=f"(d[170]), "=f"(d[171]), "=f"(d[172]), "=f"(d[173]), "=f"(d[174]), "=f"(d[175]), "=f"(d[176]), "=f"(d[177]), "=f"(d[178]), "=f"(d[179]), "=f"(d[180]), "=f"(d[181]), "=f"(d[182]), "=f"(d[183]), "=f"(d[184]), "=f"(d[185]), "=f"(d[186]), "=f"(d[187]), "=f"(d[188]), "=f"(d[189]), "=f"(d[190]), "=f"(d[191])
    : "l"(da), "l"(db));
}
__device__ __forceinline__ void wgmma_n128_rs(float (&d)[192], const uint32_t (&a)[4], uint64_t db, int scale_d) {
  asm volatile("{\n.reg .pred p;\nsetp.ne.b32 p, %69, 0;\n"
    "wgmma.mma_async.sync.aligned.m64n128k16.f32.bf16.bf16 {%0, %1, %2, %3, %4, %5, %6, %7, %8, %9, %10, %11, %12, %13, %14, %15, %16, %17, %18, %19, %20, %21, %22, %23, %24, %25, %26, %27, %28, %29, %30, %31, %32, %33, %34, %35, %36, %37, %38, %39, %40, %41, %42, %43, %44, %45, %46, %47, %48, %49, %50, %51, %52, %53, %54, %55, %56, %57, %58, %59, %60, %61, %62, %63}, {%64, %65, %66, %67}, %68, p, 1, 1, 1;\n}\n"
    : "+f"(d[128]), "+f"(d[129]), "+f"(d[130]), "+f"(d[131]), "+f"(d[132]), "+f"(d[133]), "+f"(d[134]), "+f"(d[135]), "+f"(d[136]), "+f"(d[137]), "+f"(d[138]), "+f"(d[139]), "+f"(d[140]), "+f"(d[141]), "+f"(d[142]), "+f"(d[143]), "+f"(d[144]), "+f"(d[145]), "+f"(d[146]), "+f"(d[147]), "+f"(d[148]), "+f"(d[149]), "+f"(d[150]), "+f"(d[151]), "+f"(d[152]), "+f"(d[153]), "+f"(d[154]), "+f"(d[155]), "+f"(d[156]), "+f"(d[157]), "+f"(d[158]), "+f"(d[159]), "+f"(d[160]), "+f"(d[161]), "+f"(d[162]), "+f"(d[163]), "+f"(d[164]), "+f"(d[165]), "+f"(d[166]), "+f"(d[167]), "+f"(d[168]), "+f"(d[169]), "+f"(d[170]), "+f"(d[171]), "+f"(d[172]), "+f"(d[173]), "+f"(d[174]), "+f"(d[175]), "+f"(d[176]), "+f"(d[177]), "+f"(d[178]), "+f"(d[179]), "+f"(d[180]), "+f"(d[181]), "+f"(d[182]), "+f"(d[183]), "+f"(d[184]), "+f"(d[185]), "+f"(d[186]), "+f"(d[187]), "+f"(d[188]), "+f"(d[189]), "+f"(d[190]), "+f"(d[191])
    : "r"(a[0]), "r"(a[1]), "r"(a[2]), "r"(a[3]), "l"(db), "r"(scale_d));
}
__device__ __forceinline__ void wgmma_n32_0(float (&d)[16], uint64_t da, uint64_t db) {
  asm volatile("{\n.reg .pred p;\nsetp.ne.b32 p, 0, 0;\n"
    "wgmma.mma_async.sync.aligned.m64n32k16.f32.bf16.bf16 {%0, %1, %2, %3, %4, %5, %6, %7, %8, %9, %10, %11, %12, %13, %14, %15}, %16, %17, p, 1, 1, 0, 1;\n}\n"
    : "=f"(d[0]), "=f"(d[1]), "=f"(d[2]), "=f"(d[3]), "=f"(d[4]), "=f"(d[5]), "=f"(d[6]), "=f"(d[7]), "=f"(d[8]), "=f"(d[9]), "=f"(d[10]), "=f"(d[11]), "=f"(d[12]), "=f"(d[13]), "=f"(d[14]), "=f"(d[15])
    : "l"(da), "l"(db));
}
__device__ __forceinline__ void wgmma_n32(float (&d)[16], uint64_t da, uint64_t db, int scale_d) {
  asm volatile("{\n.reg .pred p;\nsetp.ne.b32 p, %18, 0;\n"
    "wgmma.mma_async.sync.aligned.m64n32k16.f32.bf16.bf16 {%0, %1, %2, %3, %4, %5, %6, %7, %8, %9, %10, %11, %12, %13, %14, %15}, %16, %17, p, 1, 1, 0, 1;\n}\n"
    : "+f"(d[0]), "+f"(d[1]), "+f"(d[2]), "+f"(d[3]), "+f"(d[4]), "+f"(d[5]), "+f"(d[6]), "+f"(d[7]), "+f"(d[8]), "+f"(d[9]), "+f"(d[10]), "+f"(d[11]), "+f"(d[12]), "+f"(d[13]), "+f"(d[14]), "+f"(d[15])
    : "l"(da), "l"(db), "r"(scale_d));
}
__device__ __forceinline__ void wgmma_n8_t(float (&d)[4], uint64_t da, uint64_t db, int scale_d) {
  asm volatile("{\n.reg .pred p;\nsetp.ne.b32 p, %6, 0;\n"
    "wgmma.mma_async.sync.aligned.m64n8k16.f32.bf16.bf16 {%0, %1, %2, %3}, %4, %5, p, 1, 1, 1, 0;\n}\n"
    : "+f"(d[0]), "+f"(d[1]), "+f"(d[2]), "+f"(d[3])
    : "l"(da), "l"(db), "r"(scale_d));
}
__device__ __forceinline__ void wgmma_n128_rs0(float (&d)[192], const uint32_t (&a)[4], uint64_t db) {
  asm volatile("{\n.reg .pred p;\nsetp.ne.b32 p, 0, 0;\n"
    "wgmma.mma_async.sync.aligned.m64n128k16.f32.bf16.bf16 {%0, %1, %2, %3, %4, %5, %6, %7, %8, %9, %10, %11, %12, %13, %14, %15, %16, %17, %18, %19, %20, %21, %22, %23, %24, %25, %26, %27, %28, %29, %30, %31, %32, %33, %34, %35, %36, %37, %38, %39, %40, %41, %42, %43, %44, %45, %46, %47, %48, %49, %50, %51, %52, %53, %54, %55, %56, %57, %58, %59, %60, %61, %62, %63}, {%64, %65, %66, %67}, %68, p, 1, 1, 1;\n}\n"
    : "=f"(d[128]), "=f"(d[129]), "=f"(d[130]), "=f"(d[131]), "=f"(d[132]), "=f"(d[133]), "=f"(d[134]), "=f"(d[135]), "=f"(d[136]), "=f"(d[137]), "=f"(d[138]), "=f"(d[139]), "=f"(d[140]), "=f"(d[141]), "=f"(d[142]), "=f"(d[143]), "=f"(d[144]), "=f"(d[145]), "=f"(d[146]), "=f"(d[147]), "=f"(d[148]), "=f"(d[149]), "=f"(d[150]), "=f"(d[151]), "=f"(d[152]), "=f"(d[153]), "=f"(d[154]), "=f"(d[155]), "=f"(d[156]), "=f"(d[157]), "=f"(d[158]), "=f"(d[159]), "=f"(d[160]), "=f"(d[161]), "=f"(d[162]), "=f"(d[163]), "=f"(d[164]), "=f"(d[165]), "=f"(d[166]), "=f"(d[167]), "=f"(d[168]), "=f"(d[169]), "=f"(d[170]), "=f"(d[171]), "=f"(d[172]), "=f"(d[173]), "=f"(d[174]), "=f"(d[175]), "=f"(d[176]), "=f"(d[177]), "=f"(d[178]), "=f"(d[179]), "=f"(d[180]), "=f"(d[181]), "=f"(d[182]), "=f"(d[183]), "=f"(d[184]), "=f"(d[185]), "=f"(d[186]), "=f"(d[187]), "=f"(d[188]), "=f"(d[189]), "=f"(d[190]), "=f"(d[191])
    : "r"(a[0]), "r"(a[1]), "r"(a[2]), "r"(a[3]), "l"(db));
}
__device__ __forceinline__ void wgmma_n256_rs(float (&d)[192], const uint32_t (&a)[4], uint64_t db, int scale_d) {
  asm volatile("{\n.reg .pred p;\nsetp.ne.b32 p, %133, 0;\n"
    "wgmma.mma_async.sync.aligned.m64n256k16.f32.bf16.bf16 {%0, %1, %2, %3, %4, %5, %6, %7, %8, %9, %10, %11, %12, %13, %14, %15, %16, %17, %18, %19, %20, %21, %22, %23, %24, %25, %26, %27, %28, %29, %30, %31, %32, %33, %34, %35, %36, %37, %38, %39, %40, %41, %42, %43, %44, %45, %46, %47, %48, %49, %50, %51, %52, %53, %54, %55, %56, %57, %58, %59, %60, %61, %62, %63, %64, %65, %66, %67, %68, %69, %70, %71, %72, %73, %74, %75, %76, %77, %78, %79, %80, %81, %82, %83, %84, %85, %86, %87, %88, %89, %90, %91, %92, %93, %94, %95, %96, %97, %98, %99, %100, %101, %102, %103, %104, %105, %106, %107, %108, %109, %110, %111, %112, %113, %114, %115, %116, %117, %118, %119, %120, %121, %122, %123, %124, %125, %126, %127}, {%128, %129, %130, %131}, %132, p, 1, 1, 1;\n}\n"
    : "+f"(d[0]), "+f"(d[1]), "+f"(d[2]), "+f"(d[3]), "+f"(d[4]), "+f"(d[5]), "+f"(d[6]), "+f"(d[7]), "+f"(d[8]), "+f"(d[9]), "+f"(d[10]), "+f"(d[11]), "+f"(d[12]), "+f"(d[13]), "+f"(d[14]), "+f"(d[15]), "+f"(d[16]), "+f"(d[17]), "+f"(d[18]), "+f"(d[19]), "+f"(d[20]), "+f"(d[21]), "+f"(d[22]), "+f"(d[23]), "+f"(d[24]), "+f"(d[25]), "+f"(d[26]), "+f"(d[27]), "+f"(d[28]), "+f"(d[29]), "+f"(d[30]), "+f"(d[31]), "+f"(d[32]), "+f"(d[33]), "+f"(d[34]), "+f"(d[35]), "+f"(d[36]), "+f"(d[37]), "+f"(d[38]), "+f"(d[39]), "+f"(d[40]), "+f"(d[41]), "+f"(d[42]), "+f"(d[43]), "+f"(d[44]), "+f"(d[45]), "+f"(d[46]), "+f"(d[47]), "+f"(d[48]), "+f"(d[49]), "+f"(d[50]), "+f"(d[51]), "+f"(d[52]), "+f"(d[53]), "+f"(d[54]), "+f"(d[55]), "+f"(d[56]), "+f"(d[57]), "+f"(d[58]), "+f"(d[59]), "+f"(d[60]), "+f"(d[61]), "+f"(d[62]), "+f"(d[63]), "+f"(d[64]), "+f"(d[65]), "+f"(d[66]), "+f"(d[67]), "+f"(d[68]), "+f"(d[69]), "+f"(d[70]), "+f"(d[71]), "+f"(d[72]), "+f"(d[73]), "+f"(d[74]), "+f"(d[75]), "+f"(d[76]), "+f"(d[77]), "+f"(d[78]), "+f"(d[79]), "+f"(d[80]), "+f"(d[81]), "+f"(d[82]), "+f"(d[83]), "+f"(d[84]), "+f"(d[85]), "+f"(d[86]), "+f"(d[87]), "+f"(d[88]), "+f"(d[89]), "+f"(d[90]), "+f"(d[91]), "+f"(d[92]), "+f"(d[93]), "+f"(d[94]), "+f"(d[95]), "+f"(d[96]), "+f"(d[97]), "+f"(d[98]), "+f"(d[99]), "+f"(d[100]), "+f"(d[101]), "+f"(d[102]), "+f"(d[103]), "+f"(d[104]), "+f"(d[105]), "+f"(d[106]), "+f"(d[107]), "+f"(d[108]), "+f"(d[109]), "+f"(d[110]), "+f"(d[111]), "+f"(d[112]), "+f"(d[113]), "+f"(d[114]), "+f"(d[115]), "+f"(d[116]), "+f"(d[117]), "+f"(d[118]), "+f"(d[119]), "+f"(d[120]), "+f"(d[121]), "+f"(d[122]), "+f"(d[123]), "+f"(d[124]), "+f"(d[125]), "+f"(d[126]), "+f"(d[127])
    : "r"(a[0]), "r"(a[1]), "r"(a[2]), "r"(a[3]), "l"(db), "r"(scale_d));
}
__device__ __forceinline__ void wgmma_n256_rs0(float (&d)[192], const uint32_t (&a)[4], uint64_t db) {
  asm volatile("{\n.reg .pred p;\nsetp.ne.b32 p, 0, 0;\n"
    "wgmma.mma_async.sync.aligned.m64n256k16.f32.bf16.bf16 {%0, %1, %2, %3, %4, %5, %6, %7, %8, %9, %10, %11, %12, %13, %14, %15, %16, %17, %18, %19, %20, %21, %22, %23, %24, %25, %26, %27, %28, %29, %30, %31, %32, %33, %34, %35, %36, %37, %38, %39, %40, %41, %42, %43, %44, %45, %46, %47, %48, %49, %50, %51, %52, %53, %54, %55, %56, %57, %58, %59, %60, %61, %62, %63, %64, %65, %66, %67, %68, %69, %70, %71, %72, %73, %74, %75, %76, %77, %78, %79, %80, %81, %82, %83, %84, %85, %86, %87, %88, %89, %90, %91, %92, %93, %94, %95, %96, %97, %98, %99, %100, %101, %102, %103, %104, %105, %106, %107, %108, %109, %110, %111, %112, %113, %114, %115, %116, %117, %118, %119, %120, %121, %122, %123, %124, %125, %126, %127}, {%128, %129, %130, %131}, %132, p, 1, 1, 1;\n}\n"
    : "=f"(d[0]), "=f"(d[1]), "=f"(d[2]), "=f"(d[3]), "=f"(d[4]), "=f"(d[5]), "=f"(d[6]), "=f"(d[7]), "=f"(d[8]), "=f"(d[9]), "=f"(d[10]), "=f"(d[11]), "=f"(d[12]), "=f"(d[13]), "=f"(d[14]), "=f"(d[15]), "=f"(d[16]), "=f"(d[17]), "=f"(d[18]), "=f"(d[19]), "=f"(d[20]), "=f"(d[21]), "=f"(d[22]), "=f"(d[23]), "=f"(d[24]), "=f"(d[25]), "=f"(d[26]), "=f"(d[27]), "=f"(d[28]), "=f"(d[29]), "=f"(d[30]), "=f"(d[31]), "=f"(d[32]), "=f"(d[33]), "=f"(d[34]), "=f"(d[35]), "=f"(d[36]), "=f"(d[37]), "=f"(d[38]), "=f"(d[39]), "=f"(d[40]), "=f"(d[41]), "=f"(d[42]), "=f"(d[43]), "=f"(d[44]), "=f"(d[45]), "=f"(d[46]), "=f"(d[47]), "=f"(d[48]), "=f"(d[49]), "=f"(d[50]), "=f"(d[51]), "=f"(d[52]), "=f"(d[53]), "=f"(d[54]), "=f"(d[55]), "=f"(d[56]), "=f"(d[57]), "=f"(d[58]), "=f"(d[59]), "=f"(d[60]), "=f"(d[61]), "=f"(d[62]), "=f"(d[63]), "=f"(d[64]), "=f"(d[65]), "=f"(d[66]), "=f"(d[67]), "=f"(d[68]), "=f"(d[69]), "=f"(d[70]), "=f"(d[71]), "=f"(d[72]), "=f"(d[73]), "=f"(d[74]), "=f"(d[75]), "=f"(d[76]), "=f"(d[77]), "=f"(d[78]), "=f"(d[79]), "=f"(d[80]), "=f"(d[81]), "=f"(d[82]), "=f"(d[83]), "=f"(d[84]), "=f"(d[85]), "=f"(d[86]), "=f"(d[87]), "=f"(d[88]), "=f"(d[89]), "=f"(d[90]), "=f"(d[91]), "=f"(d[92]), "=f"(d[93]), "=f"(d[94]), "=f"(d[95]), "=f"(d[96]), "=f"(d[97]), "=f"(d[98]), "=f"(d[99]), "=f"(d[100]), "=f"(d[101]), "=f"(d[102]), "=f"(d[103]), "=f"(d[104]), "=f"(d[105]), "=f"(d[106]), "=f"(d[107]), "=f"(d[108]), "=f"(d[109]), "=f"(d[110]), "=f"(d[111]), "=f"(d[112]), "=f"(d[113]), "=f"(d[114]), "=f"(d[115]), "=f"(d[116]), "=f"(d[117]), "=f"(d[118]), "=f"(d[119]), "=f"(d[120]), "=f"(d[121]), "=f"(d[122]), "=f"(d[123]), "=f"(d[124]), "=f"(d[125]), "=f"(d[126]), "=f"(d[127])
    : "r"(a[0]), "r"(a[1]), "r"(a[2]), "r"(a[3]), "l"(db));
}

constexpr int SLOT = 16384;
constexpr int VB = 4 * SLOT, PH = 0, XS = 6;
constexpr int SM_SD = 13 * SLOT;
constexpr int SM_BAR = SM_SD + 8192;
constexpr int SM_RS = SM_BAR + 1024;
constexpr int SM_AP = SM_RS + 640;
constexpr int SM_BP = SM_AP + 2048;
constexpr int SM_ID = SM_BP + 6144;
constexpr int SM_TOTAL = SM_ID + 16;
constexpr int FM = 0, FT = 16, FW = 30, CM = 46, CT = 62, CW = 76, B_EF = 92, B_STAT = 93, B_KVF = 94, B_HALO = 95,
              B_KVDONE = 96, B_OH0 = 97, B_OH1 = 98, B_XH0 = 99, B_XDONE = 100, B_WFD = 101, B_XT = 102, B_OF0 = 103, B_KVF1 = 104, B_KVS = 105, B_RAW = 106  , B_X0 = 108, B_KVS0 = 109, B_ID = 110;
constexpr uint64_t BAR_LG = 0x00043333330004ull;
#define BA(i) (bar + (i) * 8)
#define REL2(i) release2c(SB0 + SM_BAR + (i) * 8)
constexpr int NF = 3, ND = 13, NR = 0, NWOP = 48, NAOP = 38;
constexpr bool EF_USED = false;
constexpr uint64_t TL_A = 0x6278627862786ull, TL_B = 0xa9c3ba9c3ba9cull, WO_A = 0x76b24038b51403ffull, WO_B = 0x8c5a197c6a297c8bull;
__constant__ uint32_t c_wop[NWOP + 1] = {0xeb0009, 0x186b8000, 0x6c0112, 0x1aec011a, 0x6c8224, 0x22ec822b, 0x18170330, 0x18178442, 0x18180554, 0x18188660, 0x18190772, 0x18198884, 0x181a0990, 0x181a8aa2, 0x181b0bb4, 0x181b8cc0, 0xaed10fc, 0xa9711e9, 0x181c0dd2, 0xa9792da, 0x129813cb, 0x181c8ee4, 0x181d0ff0, 0x109d94b3, 0x109f15ac, 0x109f9699, 0x10a0178a, 0x10a0987b, 0x10a11963, 0x10a19a5c, 0x10a21b49, 0x10a29c3a, 0x9231e0b, 0x9239f18, 0x1124202c, 0x13242137, 0x1124a249, 0x1324a352, 0x1125246a, 0x13252576, 0x1127268c, 0x1127a797, 0x112828a9, 0x1128a9b1, 0x11292aca, 0x13292bd5, 0x112a2cec, 0x132a2df8, 0};
__constant__ uint32_t c_aop[NAOP + 1] = {0x6d8228, 0x170336, 0x178447, 0x180558, 0x188666, 0x190777, 0x198888, 0x1a0996, 0x1a8aa7, 0x1b0bb8, 0x1b8cc6, 0x1c0dd7, 0x1c8ee8, 0x1d0ff6, 0x1d93c2, 0x1f14b6, 0x1f95a8, 0x201697, 0x209782, 0x211876, 0x219968, 0x221a57, 0x229b42, 0x231c36, 0xa3a023, 0xb12130, 0x2b12244, 0x2b12351, 0x2b12465, 0xa6257b, 0xa6a688, 0xa72793, 0xa7a8a0, 0xa829b4, 0xa8aac2, 0xa9abdb, 0x2a9ace6, 0xaaadf7, 0};
__constant__ uint32_t c_map[64] = {4, 5, 6, 7, 0, 16, 32, 48, 64, 80, 96, 112, 1, 17, 33, 49, 65, 81, 97, 113, 2, 18, 34, 50, 66, 82, 98, 114, 3, 19, 35, 51, 67, 83, 99, 115, 20, 36, 52, 68, 84, 100, 116, 21, 37, 53, 69, 85, 101, 117, 22, 38, 54, 70, 86, 102, 118, 23, 39, 55, 71, 87, 103, 119};
enum { MAP_WF = 0, MAP_WA = 2, MAP_WB = 4, MAP_WOA = 6, MAP_WOB = 8, MAP_X0 = 10, MAP_X = 11, MAP_O = 12, MAP_PHI = 13, NMAP = 14 };
struct Maps { CUtensorMap m[NMAP]; };

#define PL 2
#define PROFL(a, b)
#define SUBS 8
#define SUBS1 16
#define XRAT 10
#define XRN 4
#define BT1 1
#define ST1 8
#define X0AT 2
#define W1DL 100
#define WH 4
#define PFM 3
#define PFS 2
#define SVD 5000
#define NLAYERS 4
constexpr float L2E = 1.4426950408889634f;

#define D128(lo) desc64(lo, 0x40000040u)
struct Ctx { uint32_t zero, boff; const bf16* x0; bf16* out; };
#define BASE_CTX() \
  uint32_t bid_; asm volatile("mov.u32 %0, %%ctaid.x;" : "=r"(bid_)); \
  const int cr = bid_ & 1; \
  const uint32_t sb = SB0 + (cr << 24); \
  const uint32_t bar = sb + SM_BAR; (void)bar;
#define STA_CTX() \
  BASE_CTX(); \
  bid_ -= c.boff; \
  const uint32_t gr_ = c_map[bid_ >> 1]; \
  const int g = gr_ & 7, kf = (gr_ >> 3) + cr; (void)g; (void)kf;
#define DYN_CTX(id) \
  const uint32_t id_ = id; \
  const int g = id_ & 7, rb = (id_ >> 3) & 15, m0 = rb * 128; (void)g; (void)rb; (void)m0;
#define LD_ID() __float_as_uint(lds_f(sb + SM_ID))
extern __shared__ uint8_t smem_raw[];
constexpr uint32_t SB0 = 1024;

#define PHASE_CTX() \
  uint32_t idl_ = idp; asm volatile("" : "+r"(idl_)); \
  DYN_CTX(idl_); \
  const uint32_t sb = SB0 + ((id_ & 8) << 21), bar = sb + SM_BAR; \
  THR_CTX(); \
  const size_t gfr = (size_t)(m0 + wrow0 + gq) * D_ + g * 128 + 8 * t; (void)gfr;
#define THR_CTX() \
  int tid_ = threadIdx.x; asm volatile("" : "+r"(tid_)); \
  const int lane = tid_ & 31, cw = (tid_ >> 5) - 4, wg = cw >> 2, wq = cw & 3, gq = lane >> 2, t = lane & 3, wrow0 = cw * 16; \
  const int lrow = (lane & 7) + ((lane >> 3) & 1) * 8, lchk = lane >> 4; \
  const bool elected = (tid_ & 127) == 0; \
  const uint32_t rowo = (wrow0 + lrow) * 128, X = (lchk ^ (lane & 7)) << 4; \
  const uint32_t Y = (wrow0 + (lane & 7)) * 128 + (((lane >> 3) ^ (lane & 7)) << 4); \
  (void)bar; (void)wq; (void)gq; (void)lrow; (void)lchk; (void)elected; (void)wrow0; (void)wg; (void)rowo; (void)X; (void)t; (void)Y;
#define MMA_CTX() \
  const uint32_t wu = __shfl_sync(0xffffffffu, wg, 0); \
  const uint32_t dA0 = ((SB0 >> 4) | (1u << 16)) + wu * 512, dB0 = (SB0 >> 4) | (512u << 16); \
  const uint32_t par = layer & 1;

__device__ __forceinline__ void slab_out_half(uint32_t slot, bf16* dst, int wrow0, int lane) {
  const int r0 = lane >> 3, ch = lane & 7;
  const uint32_t src = slot + (wrow0 + r0) * 128;
  uint4 v[4];
#pragma unroll
  for (int i = 0; i < 4; ++i) v[i] = lds128(src + i * 512 + (((ch ^ (4 * i + r0)) & 7) << 4));
  dst += (size_t)(wrow0 + r0) * D_ + ch * 8;
#pragma unroll
  for (int i = 0; i < 4; ++i) *reinterpret_cast<uint4*>(dst + (size_t)i * 4 * D_) = v[i];
}

__device__ __forceinline__ void consumer(const Ctx& c) {
  float acc[192];
  uint32_t idp;
  uint32_t xf[4][4];
  uint32_t xp[8][4];
  {
    STA_CTX();
    THR_CTX();
    const unsigned int epoch = ld_relaxed(&g_epoch);
    PROFT(tid_ == 128, 0);
    const uint32_t wu = __shfl_sync(0xffffffffu, wg, 0);
    if (tid_ < 128 + 8) sts128(sb + SM_AP + lane * 16, make_uint4(0x3F803F80u, 0x3F803F80u, 0x3F803F80u, 0x3F803F80u));
#pragma unroll 1
    for (int it = 0; it < 2; ++it) {
      float p[4][16];
      mbar_wait(BA(B_RAW + it), 0);
      PROFT(tid_ == 128, it ? 15 : 2);
      const uint32_t da = ((SB0 >> 4) | (1u << 16)) + (wu ? 9 + it : 2 * it) * 1024, db = (SB0 + SM_SD) >> 4;
      wgmma_fence();
#pragma unroll
      for (int h = 0; h < 4; ++h) wgmma_n32_0(p[h], D128(da + (h >> 1) * 512 + (h & 1) * 4), desc64(db + h * 128, 0x80000020u));
#pragma unroll
      for (int h = 0; h < 4; ++h) wgmma_n32(p[h], D128(da + (h >> 1) * 512 + (h & 1) * 4 + 2), desc64(db + h * 128 + 64, 0x80000020u), 1);
      wgmma_commit();
      wgmma_wait<0>();
#pragma unroll
      for (int i = 0; i < 64; ++i) asm volatile("" : "+f"(p[i >> 4][i & 15]) :: "memory");
      const uint32_t base = sb + (wg ? 9 + it : 2 * it) * SLOT + (wq * 16 + gq) * 128;
      uint32_t w[4][4][2];
#pragma unroll
      for (int i = 0; i < 32; ++i) w[i >> 3][(i >> 1) & 3][i & 1] = pack_bf16(p[i >> 3][2 * (i & 7)], p[i >> 3][2 * (i & 7) + 1]);
      if (wu) {
#pragma unroll
        for (int i = 0; i < 8; ++i)
          sts128(base + (i >> 2) * 8192 + (i & 1) * 1024 + (((((i >> 1) & 1) * 4 + t) ^ gq) << 4), make_uint4(w[i >> 1][0][i & 1], w[i >> 1][1][i & 1], w[i >> 1][2][i & 1], w[i >> 1][3][i & 1]));
      } else {
#pragma unroll
        for (int i = 0; i < 16; ++i)
          sts64(base + (i >> 3) * 8192 + (i & 1) * 1024 + ((((t & 1) * 4 + ((i >> 1) & 3)) ^ gq) << 4) + (t >> 1) * 8, w[(i >> 3) * 2][(i >> 1) & 3][i & 1], w[(i >> 3) * 2 + 1][(i >> 1) & 3][i & 1]);
      }
      fence_async_smem();
      __syncwarp();
      if (it == cr && lane == 0) mbar_arrive(BA(B_WFD));
    }
    mbar_wait(BA(B_ID), 0);
    idp = __shfl_sync(0xffffffffu, LD_ID(), 0);
#pragma unroll
    for (int i = 0; i < 32; ++i) xp[i >> 2][i & 3] = 0u;
    nbar<1, 256>();
    PROFT(tid_ == 128, 13);
    mbar_wait(BA(FM + cr), 0);
    float cs[3][4];
    wgmma_fence();
#pragma unroll
    for (int ks = 0; ks < 4; ++ks)
#pragma unroll
      for (int i = 0; i < 3; ++i) {
        const uint32_t bx = (i == 0 ? 2 * cr * 1024 : i == 1 ? (2 * cr + 1) * 1024 : (9 + cr) * 1024) + wu * 512;
        wgmma_n8_t(cs[i], D128(((SB0 >> 4) | (512u << 16)) + bx + ks * 128), desc64((SB0 + SM_AP) >> 4, 0), ks != 0);
      }
    wgmma_commit();
    mbar_wait(BA(FM), 0);
#pragma unroll
    for (int k = 0; k < 4; ++k) ldsm_x4(xf[k][0], xf[k][1], xf[k][2], xf[k][3], sb + XS * SLOT + rowo + (X ^ (k << 5)));
    wgmma_wait<0>();
#pragma unroll
    for (int i = 0; i < 12; ++i) asm volatile("" : "+f"(cs[i >> 2][i & 3]) :: "memory");
    if (t < 2) {
#pragma unroll
      for (int i = 0; i < 3; ++i) red_add1(g_cs + (epoch & 1) * 6144 + g * 384 + i * 128 + wg * 64 + wq * 16 + gq + t * 8, t ? cs[i][2] : cs[i][0]);
    }
    PROFT(tid_ == 128, 14);
  }
#pragma unroll 1
  for (int layer = 0;; ++layer) {
    {
      wgmma_fence();
      wgmma_n256_rs0(acc, xf[0], D128((SB0 >> 4) | (512u << 16)));
#pragma unroll
      for (int k = 1; k < 4; ++k) wgmma_n256_rs(acc, xf[k], D128(((SB0 >> 4) | (512u << 16)) + k * 128), 1);
      wgmma_commit();
      PHASE_CTX();
      MMA_CTX();
      {
        const uint32_t ep = id_ >> 8;
        if (layer == 0) {
          mbar_wait(BA(B_X0), 0);
#pragma unroll
          for (int i = 0; i < 8; ++i) ldsm_x4(xp[i][0], xp[i][1], xp[i][2], xp[i][3], sb + (11 + (i >> 2)) * SLOT + (Y ^ ((i & 2) << 5)) + (i & 1) * 1024);
          if (lane == ((xp[0][0] ^ xp[1][0] ^ xp[2][0] ^ xp[3][0] ^ xp[7][0]) & c.zero)) REL2(B_XT);
        } else {
#pragma unroll
          for (int i = 0; i < 8; ++i) stsm_x4(sb + (XS + (i >> 2)) * SLOT + (Y ^ ((i & 2) << 5)) + (i & 1) * 1024, xp[i][0], xp[i][1], xp[i][2], xp[i][3]);
        }
        float s0 = 0.f, s1 = 0.f, q0 = 0.f, q1 = 0.f;
        auto stats = [&](int j0, int j1) {
#pragma unroll
          for (int j = j0; j < j1; ++j) {
            const uint32_t u0 = xp[(j >> 2) * 2][j & 3], u1 = xp[(j >> 2) * 2 + 1][j & 3];
            s0 += bf_lo(u0) + bf_hi(u0); s1 += bf_lo(u1) + bf_hi(u1);
            q0 = fmaf(bf_lo(u0), bf_lo(u0), fmaf(bf_hi(u0), bf_hi(u0), q0)); q1 = fmaf(bf_lo(u1), bf_lo(u1), fmaf(bf_hi(u1), bf_hi(u1), q1));
          }
        };
        stats(0, ST1);
        fence_async_smem();
        nbar_dyn(3 + wu + (__float_as_uint(s0 + s1 + q0 + q1) & c.zero), 128);
        mbar_wait(BA(FM + 1), par);
        wgmma_fence();
#pragma unroll
        for (int k = 0; k < 4; ++k) wgmma_n256(acc, D128(dA0 + (XS + 1) * 1024 + k * 2), D128(dB0 + 2048 + k * 128), 1);
        wgmma_commit();
        wgmma_wait<1>();
#pragma unroll
        for (int i = 4; i < 8; ++i) stg128_p(layer, g_x + gfr + (i & 1) * 8 * D_ + (i >> 1) * 32, xp[i][0], xp[i][1], xp[i][2], xp[i][3]);
        {
          uint32_t zc; asm volatile("mov.u32 %0, %%clock;" : "=r"(zc) :: "memory");
          q0 += __uint_as_float(zc & c.zero); q1 += __uint_as_float(zc & c.zero); s0 += __uint_as_float(zc & c.zero); s1 += __uint_as_float(zc & c.zero);
        }
        stats(ST1, 16);
        wgmma_fence();
        wgmma_n128_0(acc, D128(dA0 + XS * 1024), D128(dB0 + 9 * 1024));
#pragma unroll
        for (int k = 1; k < 4; ++k) wgmma_n128(acc, D128(dA0 + XS * 1024 + k * 2), D128(dB0 + 9 * 1024 + k * 128), 1);
        wgmma_commit();
        const bool od = t & 1;
        float sa = od ? s1 : s0, qa = od ? q1 : q0;
        sa += __shfl_xor_sync(0xffffffffu, od ? s0 : s1, 1);
        qa += __shfl_xor_sync(0xffffffffu, od ? q0 : q1, 1);
        wgmma_fence();
#pragma unroll
        for (int k = 0; k < 4; ++k) wgmma_n128(acc, D128(dA0 + (XS + 1) * 1024 + k * 2), D128(dB0 + 10 * 1024 + k * 128), 1);
        wgmma_commit();
        sa += __shfl_xor_sync(0xffffffffu, sa, 2);
        qa += __shfl_xor_sync(0xffffffffu, qa, 2);
        red_add2_p(t < 2, reinterpret_cast<float*>(g_stats + (ep * 4 + layer) * S_ + m0 + wrow0 + gq + t * 8), sa, qa);
        __syncwarp();
        if (lane == 0) mbar_arrive(BA(B_XDONE));
        wgmma_wait<1>();
        if (elected) REL2(CM);
      }
      uint32_t s = 2;
#pragma unroll 1
      for (int i = 2; i < NF; ++i) {
        PROFL(tid_ == 128 && layer == PL + 1, 244 + 2 * i);
        mbar_wait(BA(FM + i), par);
        PROFL(tid_ == 128 && layer == PL + 1, 245 + 2 * i);
        const uint32_t da = dA0 + (XS + s) * 1024, dk = dB0 + s * 2048, dq = dB0 + (9 + s) * 1024;
        wgmma_fence();
#pragma unroll
        for (int k = 0; k < 4; ++k) wgmma_n128(acc, D128(da + k * 2), D128(dq + k * 128), 1);
        wgmma_commit();
        wgmma_wait<1>();
        if (elected) REL2(CM + i - 1);
        wgmma_fence();
#pragma unroll
        for (int k = 0; k < 4; ++k) wgmma_n256(acc, D128(da + k * 2), D128(dk + k * 128), 1);
        wgmma_commit();
        if (++s == 3) s = 0;
      }
#pragma unroll 1
      for (int i = NF; i < 15; ++i) {
        mbar_wait(BA(FM + i), par);
        const uint32_t da = dA0 + (XS + s) * 1024, dk = dB0 + s * 2048;
        wgmma_fence();
#pragma unroll
        for (int k = 0; k < 4; ++k) wgmma_n256(acc, D128(da + k * 2), D128(dk + k * 128), 1);
        wgmma_commit();
        wgmma_wait<1>();
        if (elected) REL2(CM + i - 1);
        if (++s == 3) s = 0;
      }
      {
        const uint64_t dap = desc64(((SB0 + SM_AP) >> 4) + wu * 64, 8), dbp = make_desc_ns(SB0 + SM_BP, 0, 128);
        mbar_wait(BA(B_STAT), par);
        mbar_wait(BA(FM + 15), par);
        PROFT(tid_ == 128, layer * 16 + 9);
        wgmma_fence();
        wgmma_n256_k(acc, dap, dbp, 1);
#pragma unroll
        for (int k = 0; k < 4; ++k) wgmma_n256(acc, D128(dA0 + XS * 1024 + k * 2), D128(dB0 + k * 128), 1);
        wgmma_commit();
        wgmma_wait<1>();
        if (elected) REL2(CM + 14);
        mbar_wait(BA(FT), par);
        wgmma_fence();
        wgmma_n128_k(acc, dap, dbp + 256, 1);
#pragma unroll
        for (int k = 0; k < 4; ++k) wgmma_n128(acc, D128(dA0 + (uint32_t)(TL_A & 15) * 1024 + k * 2), D128(dB0 + (uint32_t)(TL_B & 15) * 1024 + k * 128), 1);
        wgmma_commit();
        wgmma_wait<1>();
        if (elected) REL2(CM + 15);
#pragma unroll
        for (int i = 0; i < 128; ++i) asm volatile("" : "+f"(acc[i]) :: "memory");
      }
    }
    uint32_t of[8][4], o1[4][4];
    {
      PHASE_CTX();
      MMA_CTX();
      PROFT(tid_ == 128, layer * 16 + 1);
      PROFT(lane == 0 && layer == PL, 192 + cw);
      PROFT(tid_ == 128 && layer == PL, 160);
      uint64_t ta = (TL_A >> 4), tw = TL_B >> 4;
      uint32_t da, db, dz = dA0;
      auto sub = [&](int n) {
        const int j = n >> 2, k = n & 3;
        if (k == 0) {
          dz += c.zero;
          da = dz + ((uint32_t)ta & 15) * 1024; db = dB0 + ((uint32_t)tw & 15) * 1024;
          ta >>= 4; tw >>= 4;
          mbar_wait(BA(FT + j), par);
          wgmma_fence();
        }
        wgmma_n128(acc, D128(da + k * 2), D128(db + k * 128), 1);
        if (k == 3) {
          wgmma_commit();
          wgmma_wait<1>();
          if (elected) REL2(CT + j - 1);
        }
      };
      auto run = [&](int j0, int j1) {
#pragma unroll 1
        for (int j = j0; j < j1; ++j) {
          mbar_wait(BA(FT + j), par);
          da = dA0 + ((uint32_t)ta & 15) * 1024; db = dB0 + ((uint32_t)tw & 15) * 1024;
          ta >>= 4; tw >>= 4;
          wgmma_fence();
#pragma unroll
          for (int k = 0; k < 4; ++k) wgmma_n128(acc, D128(da + k * 2), D128(db + k * 128), 1);
          wgmma_commit();
          wgmma_wait<1>();
          if (elected) REL2(CT + j - 1);
        }
        ta = TL_A >> (4 * j1); tw = TL_B >> (4 * j1);
      };
      auto rest = [&](int j0) {
        run(j0, ND);
        wgmma_wait<0>();
        if (elected) REL2(CT + ND - 1);
#pragma unroll
        for (int i = 128; i < 192; ++i) asm volatile("" : "+f"(acc[i]) :: "memory");
      };
      auto wo0 = [&]() {
        wgmma_fence();
        wgmma_n128_rs0(acc, of[0], D128(dB0 + (uint32_t)(WO_B & 15) * 1024));
#pragma unroll
        for (int k = 1; k < 4; ++k) wgmma_n128_rs(acc, of[k], D128(dB0 + (uint32_t)(WO_B & 15) * 1024 + k * 128), 1);
        wgmma_commit();
      };
      const float rs0 = lds_f(sb + SM_RS + (16 + wrow0 + gq) * 4), rs1 = lds_f(sb + SM_RS + (24 + wrow0 + gq) * 4);
      mbar_wait(BA(CM + 14), par);
      if (par) {
        uint32_t kk[8][4], kp[8][4], vf[2][2][4][4];
        int sn = 4;
        float rj[4];
#pragma unroll
        for (int nt = 0; nt < 4; ++nt) rj[nt] = lds_f(sb + SM_RS + (wrow0 + nt * 8 + 2 * t + (gq & 1)) * 4);
#pragma unroll
        for (int i = 0; i < 4 * BT1; ++i) sub(sn++);
        {
          uint32_t vv[8][4];
#pragma unroll
          for (int jp = 0; jp < 8; ++jp) {
            kk[jp][0] = pack_bf16(acc[8 * jp], acc[8 * jp + 1]); kk[jp][1] = pack_bf16(acc[8 * jp + 4], acc[8 * jp + 5]);
            kk[jp][2] = pack_bf16(acc[8 * jp + 2], acc[8 * jp + 3]); kk[jp][3] = pack_bf16(acc[8 * jp + 6], acc[8 * jp + 7]);
#pragma unroll
            for (int i = 0; i < 4; ++i) vv[jp][i] = pack_bf16(acc[64 + 8 * jp + 2 * i], acc[65 + 8 * jp + 2 * i]);
          }
          if (cw == 7) {
            uint32_t* const hbuf = g_halo + (size_t)(((layer >> 1) * 17 + rb + 1) * 8 + g) * 2048;
#pragma unroll
            for (int jp = 0; jp < 8; ++jp) stg128(hbuf + jp * 128 + lane * 4, kk[jp][0], kk[jp][1], kk[jp][2], kk[jp][3]);
#pragma unroll
            for (int i = 0; i < 32; ++i) hbuf[1024 + (i >> 4) * 512 + (gq + (i & 1) * 8) * 32 + ((((i >> 1) & 7) ^ gq) << 2) + t] = vv[i >> 2][i & 3];
            __syncwarp();
            if (lane == 0) mbar_arrive(BA(B_OF0));
          }
#pragma unroll
          for (int jp = 0; jp < 8; ++jp) {
            sub(sn++);
            stsm_x4(sb + VB + (jp >> 2) * SLOT + rowo + (X ^ ((jp & 3) << 5)), vv[jp][0], vv[jp][1], vv[jp][2], vv[jp][3]);
          }
        }
        PROFT(tid_ == 128, layer * 16 + 2);
        const int e = gq & 1;
        float f0[4], f1[4], b0[4], b1[4];
#pragma unroll
        for (int nt = 0; nt < 4; ++nt) {
          const int kx = nt * 8 + 2 * t + e;
          const bool okk = (m0 + wrow0 + kx) >= 16;
          const int d0 = kx - gq, d1 = d0 - 8;
          const bool m0_ = okk && d0 >= 2 && d0 <= 16, m1_ = okk && d1 >= 2 && d1 <= 16;
          f0[nt] = m0_ ? rj[nt] * rs0 * (0.17677669529663687f * L2E) : 0.f;
          f1[nt] = m1_ ? rj[nt] * rs1 * (0.17677669529663687f * L2E) : 0.f;
          b0[nt] = m0_ ? 0.f : -1e30f; b1[nt] = m1_ ? 0.f : -1e30f;
        }
        uint32_t ko = sb + PH + cw * 4096 + lane * 16;
        mbar_wait(BA(CM + 15), par);
#pragma unroll
        for (int jp = 0; jp < 8; ++jp) {
          sub(sn++);
          sts128(ko + jp * 512, make_uint4(kk[jp][0], kk[jp][1], kk[jp][2], kk[jp][3]));
        }
#pragma unroll
        for (int i = 0; i < 4; ++i) sub(sn++);
        nbar<1, 256>();
        PROFT(tid_ == 128, layer * 16 + 3);
        rest(sn >> 2);
        PROFT(lane == 0 && layer == PL, 200 + cw);
        PROFT(tid_ == 128, layer * 16 + 10);
        if (cw == 0) mbar_wait(BA(B_HALO), (layer >> 1) & 1);
        PROFT(tid_ == 128, layer * 16 + 5);
        const uint32_t vs = sb + (cw ? VB + rowo - 2048 : SM_SD + 4096 + rowo), vst = cw ? SLOT : 2048;
        asm volatile("" : "+r"(ko));
        const uint32_t ka = ko + (cw ? -4096 : SM_SD - PH);
        const uint32_t psel = e ? 0x1054u : 0x5410u;
#pragma unroll
        for (int hp = 0; hp < 2; ++hp) {
#pragma unroll
          for (int i = 4 * hp; i < 4 * hp + 4; ++i) {
            const uint4 u = lds128(ka + i * 512);
            kp[i][0] = u.x; kp[i][1] = u.y; kp[i][2] = u.z; kp[i][3] = u.w;
          }
#pragma unroll
          for (int i = 4 * hp; i < 4 * hp + 4; ++i) {
            ldsm_x4_t(vf[0][i & 1][i >> 1][0], vf[0][i & 1][i >> 1][1], vf[0][i & 1][i >> 1][2], vf[0][i & 1][i >> 1][3], vs + (i >> 2) * vst + (X ^ ((i & 3) << 5)));
            ldsm_x4_t(vf[1][i & 1][i >> 1][0], vf[1][i & 1][i >> 1][1], vf[1][i & 1][i >> 1][2], vf[1][i & 1][i >> 1][3], sb + VB + (i >> 2) * SLOT + rowo + (X ^ ((i & 3) << 5)));
          }
          float l0[2][4], l1[2][4];
#pragma unroll
          for (int h = 0; h < 2; ++h) {
            const int H = 2 * hp + h;
            uint32_t qa[8];
#pragma unroll
            for (int i = 0; i < 8; ++i) qa[i] = pack_bf16(acc[128 + 16 * H + 2 * i], acc[129 + 16 * H + 2 * i]);
#pragma unroll
            for (int nt = 3; nt >= 0; --nt) {
              float sc[4] = {0.f, 0.f, 0.f, 0.f};
#pragma unroll
              for (int ks = 0; ks < 2; ++ks) {
                const uint32_t (&kf)[4] = nt < 2 ? kp[2 * H + ks] : kk[2 * H + ks];
                mma_bf16(sc, qa[4 * ks], qa[4 * ks + 1], qa[4 * ks + 2], qa[4 * ks + 3], kf[2 * (nt & 1)], kf[2 * (nt & 1) + 1]);
              }
              l0[h][nt] = fmaf(e ? sc[1] : sc[0], f0[nt], b0[nt]);
              l1[h][nt] = fmaf(e ? sc[3] : sc[2], f1[nt], b1[nt]);
            }
          }
          float mx0[2], mx1[2], s0[2], s1[2];
#pragma unroll
          for (int h = 0; h < 2; ++h) {
            mx0[h] = fmaxf(fmaxf(l0[h][0], l0[h][1]), l0[h][2]);
            mx1[h] = fmaxf(fmaxf(l1[h][1], l1[h][2]), l1[h][3]);
          }
#pragma unroll
          for (int o = 1; o <= 2; o <<= 1)
#pragma unroll
            for (int h = 0; h < 2; ++h) {
              mx0[h] = fmaxf(mx0[h], __shfl_xor_sync(0xffffffffu, mx0[h], o));
              mx1[h] = fmaxf(mx1[h], __shfl_xor_sync(0xffffffffu, mx1[h], o));
            }
#pragma unroll
          for (int h = 0; h < 2; ++h) {
#pragma unroll
            for (int nt = 0; nt < 3; ++nt) { l0[h][nt] = ex2(l0[h][nt] - mx0[h]); l1[h][nt + 1] = ex2(l1[h][nt + 1] - mx1[h]); }
            s0[h] = (l0[h][0] + l0[h][1]) + l0[h][2];
            s1[h] = (l1[h][1] + l1[h][2]) + l1[h][3];
          }
#pragma unroll
          for (int o = 1; o <= 2; o <<= 1)
#pragma unroll
            for (int h = 0; h < 2; ++h) {
              s0[h] += __shfl_xor_sync(0xffffffffu, s0[h], o);
              s1[h] += __shfl_xor_sync(0xffffffffu, s1[h], o);
            }
          uint32_t ow[2][2][4];
#pragma unroll
          for (int h = 0; h < 2; ++h) {
            const int H = 2 * hp + h;
            uint32_t pl[4], ph[4];
            const float i0 = rcp(s0[h]), i1 = rcp(s1[h]);
#pragma unroll
            for (int nt = 0; nt < 4; ++nt) {
              const uint32_t pk = pack_bf16(nt < 3 ? l0[h][nt] * i0 * rj[nt] : 0.f, nt > 0 ? l1[h][nt] * i1 * rj[nt] : 0.f);
              pl[nt] = nt < 3 ? __byte_perm(pk, 0u, psel) : 0u;
              ph[nt] = nt > 0 ? __byte_perm(pk, 0u, psel + 0x2222u) : 0u;
            }
#pragma unroll
            for (int nj = 0; nj < 4; ++nj) {
              float oa[4] = {0.f, 0.f, 0.f, 0.f};
#pragma unroll
              for (int ks = 0; ks < 2; ++ks)
                mma_bf16(oa, pl[2 * ks], ph[2 * ks], pl[2 * ks + 1], ph[2 * ks + 1], vf[ks][nj >> 1][H][2 * (nj & 1)], vf[ks][nj >> 1][H][2 * (nj & 1) + 1]);
              ow[h][0][nj] = pack_bf16(oa[0], oa[1]); ow[h][1][nj] = pack_bf16(oa[2], oa[3]);
            }
          }
          if (hp == 0) {
#pragma unroll
            for (int i = 0; i < 4; ++i) stg128(g_o + gfr + (i & 1) * 8 * D_ + (i >> 1) * 32, ow[i >> 1][i & 1][0], ow[i >> 1][i & 1][1], ow[i >> 1][i & 1][2], ow[i >> 1][i & 1][3]);
            __syncwarp();
            if (lane == 0) mbar_arrive(BA(B_OH0));
          } else {
#pragma unroll
            for (int i = 0; i < 16; ++i) o1[i >> 2][i & 3] = ow[i >> 3][(i >> 2) & 1][i & 3];
          }
#pragma unroll
          for (int i = 0; i < 16; ++i) of[4 * hp + (i >> 2)][i & 3] = ow[i >> 3][i & 1][(i >> 1) & 3];
          if (!hp) { PROFT(tid_ == 128, layer * 16 + 15); mbar_wait(BA(FW), par); }
        }
      } else {
        float sc[2] = {rs0 * L2E, rs1 * L2E};
        {
          const uint32_t vb = sb + VB + (rowo >> 1), X0 = (lchk ^ ((lane & 7) >> 1)) << 4;
          const uint32_t pb = sb + PH + (t & 1) * SLOT + (wrow0 + gq) * 128 + ((((t & 1) * 4 + (t & 2)) ^ gq) << 4);
          float kva[20], en[32], mx[2][2], mn[2][2];
#define PV(hp, j) acc[32 * (hp) + (j)]
          auto mm = [&](int hp, int j) {
            const int r = (j >> 1) & 1;
            if (j < 4 && !(j & 1)) { mx[hp][r] = PV(hp, j); mn[hp][r] = PV(hp, j); }
            else { mx[hp][r] = fmaxf(mx[hp][r], PV(hp, j)); mn[hp][r] = fminf(mn[hp][r], PV(hp, j)); }
          };
          auto mmx = [&](int hp) {
#pragma unroll
            for (int r = 0; r < 2; ++r) {
              mx[hp][r] = fmaxf(mx[hp][r], __shfl_xor_sync(0xffffffffu, mx[hp][r], 2)) * -sc[r];
              mn[hp][r] = fmaf(fminf(mn[hp][r], __shfl_xor_sync(0xffffffffu, mn[hp][r], 2)), sc[r], mx[hp][r]);
            }
          };
          auto stage = [&](int hp) {
#pragma unroll
            for (int i = 0; i < 20; ++i) asm volatile("" : "+f"(kva[i]) :: "memory");
            nbar_dyn(3 + wu, 128);
            const uint32_t ad = sb + VB + hp * SLOT + wg * 8192 + (2 * wq + ((lane >> 3) & 1)) * 640 + (lane & 7) * 16;
#pragma unroll
            for (int i = 0; i < 2; ++i)
              stsm_x4(ad + (2 * i + lchk) * 128, pack_bf16(kva[8 * i], kva[8 * i + 1]), pack_bf16(kva[8 * i + 2], kva[8 * i + 3]),
                      pack_bf16(kva[8 * i + 4], kva[8 * i + 5]), pack_bf16(kva[8 * i + 6], kva[8 * i + 7]));
            stsm_x2(ad + 512, pack_bf16(kva[16], 0.0625f), pack_bf16(kva[18], 0.0625f));
            fence_async_smem();
            __syncwarp();
            if (lane == 0) mbar_arrive(BA(B_KVDONE));
          };
          int sn = 4;
#pragma unroll
          for (int j = 0; j < 32; ++j) { if ((j & 7) == 7) sub(sn++); mm(0, j); }
          mmx(0);
#pragma unroll
          for (int hp = 0; hp < 2; ++hp) {
            float sp[2] = {0.f, 0.f}, sm[2] = {0.f, 0.f};
#pragma unroll
            for (int j = 0; j < 32; ++j) {
              const int r = (j >> 1) & 1, ns = hp ? SUBS1 : SUBS;
              if ((j * ns) / 32 != ((j + 1) * ns) / 32) {
                sub(sn++);
                if (hp && sn == 8 + SUBS + 4) { stage(0); PROFT(tid_ == 128, layer * 16 + 12); }
              }
              const float x = fmaf(PV(hp, j), sc[r], mx[hp][r]);
              PV(hp, j) = ex2(x); en[j] = ex2(mn[hp][r] - x);
              sp[r] += PV(hp, j); sm[r] += en[j];
              if (hp == 0) {
                mm(1, j);
                if ((j & 3) == 0) {
                  const int jp = 8 + (j >> 2);
                  stsm_x4(vb + ((jp - 8) >> 1) * 8192 + (X0 ^ ((jp & 1) << 5)), pack_bf16(acc[8 * jp], acc[8 * jp + 1]), pack_bf16(acc[8 * jp + 2], acc[8 * jp + 3]),
                          pack_bf16(acc[8 * jp + 4], acc[8 * jp + 5]), pack_bf16(acc[8 * jp + 6], acc[8 * jp + 7]));
                }
              }
            }
#pragma unroll
            for (int r = 0; r < 2; ++r) {
              sp[r] = rcp(sp[r] + __shfl_xor_sync(0xffffffffu, sp[r], 2)) * (r ? rs1 : rs0);
              sm[r] = rcp(sm[r] + __shfl_xor_sync(0xffffffffu, sm[r], 2)) * (r ? rs1 : rs0);
            }
            if (hp == 0) { mmx(1); mbar_wait(BA(CM + 15), par); }
            else { PROFT(tid_ == 128, layer * 16 + 11); nbar<1, 256>(); }
#pragma unroll
            for (int i = 0; i < 4; ++i) {
              const int r = i & 1, d = 16 * (i >> 1) + 2 * r;
              sts128((pb + r * 1024) ^ ((i >> 1) << 4), make_uint4(pack_bf16(PV(hp, d) * sp[r], PV(hp, d + 1) * sp[r]), pack_bf16(PV(hp, d + 4) * sp[r], PV(hp, d + 5) * sp[r]),
                                                                    pack_bf16(PV(hp, d + 8) * sp[r], PV(hp, d + 9) * sp[r]), pack_bf16(PV(hp, d + 12) * sp[r], PV(hp, d + 13) * sp[r])));
              sts128((pb + r * 1024) ^ ((i >> 1) << 4) ^ 64, make_uint4(pack_bf16(en[d] * sm[r], en[d + 1] * sm[r]), pack_bf16(en[d + 4] * sm[r], en[d + 5] * sm[r]),
                                                                         pack_bf16(en[d + 8] * sm[r], en[d + 9] * sm[r]), pack_bf16(en[d + 12] * sm[r], en[d + 13] * sm[r])));
            }
            fence_async_smem();
            nbar<1, 256>();
            const uint32_t dP = dB0 + (PH >> 4) + wu * 1024;
            const uint32_t dV = (dB0 & 0xFFFFu) + ((VB + hp * SLOT) >> 4) + (((SM_SD - VB - hp * SLOT) >> 4) << 16) + wu * (512u - (512u << 16));
            wgmma_fence();
#pragma unroll
            for (int ks = 0; ks < 8; ++ks) wgmma_n40_tt(kva, D128(dP + ks * 128), desc64(dV + ks * 64, 0x80000020u), ks != 0);
            wgmma_commit();
          }
#pragma unroll
          for (int i = 0; i < 4; ++i) sub(sn++);
          stage(1);
          PROFT(tid_ == 128, layer * 16 + 3);
          rest(sn >> 2);
          PROFT(lane == 0 && layer == PL, 200 + cw);
          PROFT(tid_ == 128, layer * 16 + 10);
        }
#define QV(H, i) acc[128 + 16 * (H) + (i)]
        float mx[4][2], mn[4][2];
        uint32_t ph[4][4][4];
        auto mnx = [&](int hp) {
#pragma unroll
          for (int H = 2 * hp; H < 2 * hp + 2; ++H)
#pragma unroll
            for (int r = 0; r < 2; ++r) {
              mx[H][r] = fmaxf(fmaxf(fmaxf(QV(H, 2 * r), QV(H, 2 * r + 1)), fmaxf(QV(H, 4 + 2 * r), QV(H, 5 + 2 * r))),
                               fmaxf(fmaxf(QV(H, 8 + 2 * r), QV(H, 9 + 2 * r)), fmaxf(QV(H, 12 + 2 * r), QV(H, 13 + 2 * r))));
              mn[H][r] = fminf(fminf(fminf(QV(H, 2 * r), QV(H, 2 * r + 1)), fminf(QV(H, 4 + 2 * r), QV(H, 5 + 2 * r))),
                               fminf(fminf(QV(H, 8 + 2 * r), QV(H, 9 + 2 * r)), fminf(QV(H, 12 + 2 * r), QV(H, 13 + 2 * r))));
            }
#pragma unroll
          for (int o = 1; o <= 2; o <<= 1)
#pragma unroll
            for (int H = 2 * hp; H < 2 * hp + 2; ++H)
#pragma unroll
              for (int r = 0; r < 2; ++r) {
                mx[H][r] = fmaxf(mx[H][r], __shfl_xor_sync(0xffffffffu, mx[H][r], o));
                mn[H][r] = fminf(mn[H][r], __shfl_xor_sync(0xffffffffu, mn[H][r], o));
              }
#pragma unroll
          for (int H = 2 * hp; H < 2 * hp + 2; ++H)
#pragma unroll
            for (int r = 0; r < 2; ++r) { mx[H][r] *= -sc[r]; mn[H][r] = fmaf(mn[H][r], sc[r], mx[H][r]); }
        };
        auto fm = [&](int H) {
#pragma unroll
          for (int i = 0; i < 8; ++i) {
            const int r = i & 1;
            const float x0 = fmaf(QV(H, 2 * i), sc[r], mx[H][r]), x1 = fmaf(QV(H, 2 * i + 1), sc[r], mx[H][r]);
            ph[H][i >> 2][i & 3] = pack_bf16(ex2(x0), ex2(x1));
            ph[H][2 + (i >> 2)][i & 3] = pack_bf16(ex2(mn[H][r] - x0), ex2(mn[H][r] - x1));
          }
        };
        mnx(0);
        fm(0); fm(1);
#pragma unroll
        for (int hp = 0; hp < 2; ++hp) {
          if (hp) mbar_wait(BA(FW), par);
          mbar_wait(BA(hp ? B_KVF1 : B_KVF), (layer >> 1) & 1);
          PROFT(tid_ == 128, layer * 16 + (hp ? 4 : 5));
          float oa[4][20];
          wgmma_fence();
#pragma unroll
          for (int s = 0; s < 2; ++s)
#pragma unroll
            for (int v = 0; v < 4; ++v) {
              const int h = v >> 1, s4 = 2 * (v & 1) + s;
              wgmma_n40_rs(oa[v], ph[2 * hp + h][s4], desc64((((SB0 + VB + hp * SLOT) >> 4) | (40u << 16)) + h * 512 + (s4 ^ (2 * h)) * 80, 8), s != 0);
            }
          wgmma_commit();
          if (hp == 0) { mnx(1); wgmma_wait<0>(); }
          else wgmma_wait<0>();
#pragma unroll
          for (int i = 0; i < 20; ++i) asm volatile("" : "+f"(oa[0][i]), "+f"(oa[1][i]), "+f"(oa[2][i]), "+f"(oa[3][i]) :: "memory");
          uint32_t ow[2][2][4];
#pragma unroll
          for (int h = 0; h < 2; ++h)
#pragma unroll
            for (int r = 0; r < 2; ++r) {
              const float a = oa[2 * h + 1][17 + 2 * r], b = oa[2 * h][17 + 2 * r];
              const float id = rcp(fmaf(oa[2 * h][16 + 2 * r], a, fmaf(a, 1e-6f, oa[2 * h + 1][16 + 2 * r]) * b));
              const float fa = a * id, fb = b * id;
#pragma unroll
              for (int j = 0; j < 4; ++j)
                ow[h][r][j] = pack_bf16(fmaf(oa[2 * h][4 * j + 2 * r], fa, oa[2 * h + 1][4 * j + 2 * r] * fb),
                                        fmaf(oa[2 * h][4 * j + 2 * r + 1], fa, oa[2 * h + 1][4 * j + 2 * r + 1] * fb));
            }
#pragma unroll
          for (int i = 0; i < 16; ++i) of[4 * hp + (i >> 2)][i & 3] = ow[i >> 3][i & 1][(i >> 1) & 3];
          if (hp == 0) {
#pragma unroll
            for (int i = 0; i < 4; ++i) stg128(g_o + gfr + (i & 1) * 8 * D_ + (i >> 1) * 32, ow[i >> 1][i & 1][0], ow[i >> 1][i & 1][1], ow[i >> 1][i & 1][2], ow[i >> 1][i & 1][3]);
            __syncwarp();
            if (lane == 0) mbar_arrive(BA(B_OH0));
            PROFT(tid_ == 128 && layer, layer * 16 + 15);
            fm(2); fm(3);
          } else {
#pragma unroll
            for (int i = 0; i < 16; ++i) o1[i >> 2][i & 3] = ow[i >> 3][(i >> 2) & 1][i & 3];
          }
        }
      }
      PROFT(tid_ == 128, layer * 16 + 6);
#pragma unroll
      for (int i = 0; i < 4; ++i) stg128(g_o + gfr + (i & 1) * 8 * D_ + (2 + (i >> 1)) * 32, o1[i][0], o1[i][1], o1[i][2], o1[i][3]);
      __syncwarp();
      if (lane == 0) { mbar_arrive(BA(B_OH1)); if (EF_USED) REL2(B_EF); }
      PROFT(lane == 0 && layer == PL, 208 + cw);
      fence_async_smem();
      wo0();
    }
    {
      PHASE_CTX();
      MMA_CTX();
      mbar_wait(BA(FW + 1), par);
      wgmma_fence();
#pragma unroll
      for (int k = 0; k < 4; ++k) wgmma_n128_rs(acc, of[4 + k], D128(dB0 + (uint32_t)((WO_B >> 4) & 15) * 1024 + k * 128), 1);
      wgmma_commit();
      wgmma_wait<1>();
      if (elected) REL2(CW);
      uint64_t ta = WO_A >> 8, tw = WO_B >> 8;
      auto run = [&](int i0, int i1) {
#pragma unroll 1
        for (int i = i0; i < i1; ++i) {
          mbar_wait(BA(FW + i), par);
          PROFL(tid_ == 128 && layer == PL, 160 + i);
          const uint32_t da = dA0 + ((uint32_t)ta & 15) * 1024, db = dB0 + ((uint32_t)tw & 15) * 1024;
          ta >>= 4; tw >>= 4;
          wgmma_fence();
#pragma unroll
          for (int k = 0; k < 4; ++k) wgmma_n128(acc, D128(da + k * 2), D128(db + k * 128), 1);
          wgmma_commit();
          wgmma_wait<1>();
          if (elected) REL2(CW + i - 1);
        }
        ta = WO_A >> (4 * (i1 & 15)); tw = WO_B >> (4 * (i1 & 15));
      };
      run(2, XRAT);
#pragma unroll
      for (int j = 0; j < 8 / XRN; ++j) {
#pragma unroll
        for (int i = j * XRN; i < (j + 1) * XRN; ++i) ldg128((layer ? g_x : c.x0) + gfr + (i & 1) * 8 * D_ + (i >> 1) * 32, xp[i][0], xp[i][1], xp[i][2], xp[i][3]);
        run(XRAT + j, j + 1 < 8 / XRN ? XRAT + j + 1 : 16);
      }
      if (layer == 0) {
#pragma unroll
        for (int o = 1; o <= 2; o <<= 1)
#pragma unroll
          for (int i = 0; i < 16; ++i) {
            const int j = o == 1 ? 2 * (i & 1) : (i & 1);
            uint32_t &a = xp[i >> 1][j], &b = xp[i >> 1][j + o];
            const uint32_t r = __shfl_xor_sync(0xffffffffu, (t & o) ? a : b, o);
            if (t & o) a = r; else b = r;
          }
      }
      if (layer != NLAYERS - 1) mbar_wait(BA(FM), par ^ 1);
      wgmma_wait<0>();
#pragma unroll
      for (int i = 128; i < 192; ++i) asm volatile("" : "+f"(acc[i]) :: "memory");
      if (elected) REL2(CW + 15);
      PROFT(lane == 0 && layer == PL, 216 + cw);
      PROFT(tid_ == 128, layer * 16 + 7);
#pragma unroll
      for (int i = 0; i < 32; ++i)
        xp[i >> 2][i & 3] = add_bf16x2(xp[i >> 2][i & 3], pack_bf16(acc[128 + 16 * (i >> 3) + 4 * (i & 3) + 2 * ((i >> 2) & 1)], acc[129 + 16 * (i >> 3) + 4 * (i & 3) + 2 * ((i >> 2) & 1)]));
      if (layer == NLAYERS - 1) {
#pragma unroll
        for (int i = 0; i < 8; ++i) stsm_x4(sb + (XS + (i >> 2)) * SLOT + (Y ^ ((i & 2) << 5)) + (i & 1) * 1024, xp[i][0], xp[i][1], xp[i][2], xp[i][3]);
        __syncwarp();
        slab_out_half(sb + XS * SLOT, c.out + (size_t)m0 * D_ + g * 128, wrow0, lane);
        slab_out_half(sb + (XS + 1) * SLOT, c.out + (size_t)m0 * D_ + g * 128 + 64, wrow0, lane);
        PROFT(tid_ == 128, layer * 16 + 24);
        break;
      }
#pragma unroll
      for (int i = 0; i < 4; ++i) stg128(g_x + gfr + (i & 1) * 8 * D_ + (i >> 1) * 32, xp[i][0], xp[i][1], xp[i][2], xp[i][3]);
      __syncwarp();
      if (lane == 0) mbar_arrive(BA(B_XH0));
#pragma unroll
      for (int i = 0; i < 16; ++i) xf[i >> 2][i & 3] = xp[2 * (i >> 3) + (i & 1)][(i >> 1) & 3];
      PROFT(tid_ == 128, layer * 16 + 24);
    }
  }
}

__device__ __forceinline__ uint64_t k_order(int o) {
  const uint32_t lo = (1u << (4 * o)) - 1u, h0 = (0xECA86420u & lo) | ((0xECA86420u >> 4) & ~lo);
  return (uint64_t)(2 * o) | ((uint64_t)(2 * o + 1) << 4) | ((uint64_t)(h0 & 0xFFFFFFFu) << 8) | ((uint64_t)((h0 & 0xFFFFFFFu) | 0x1111111u) << 36);
}

__global__ void __cluster_dims__(2, 1, 1) __launch_bounds__(384, 1)
mega_kernel(const __grid_constant__ Maps maps, const __grid_constant__ Ctx c, const bf16* __restrict__ wA, const bf16* __restrict__ wB,
            const bf16* __restrict__ woA, const bf16* __restrict__ woB, const bf16* __restrict__ wphi) {
  if (blockIdx.x - c.boff >= 128u) {
    const unsigned int epoch = ld_relaxed(&g_epoch);
    const int e = (blockIdx.x - c.boff) & 3, tid = threadIdx.x;
    float s[8] = {0.f, 0.f, 0.f, 0.f, 0.f, 0.f, 0.f, 0.f};
    const uint32_t sb = smem_u32(smem_raw), bar = sb + SM_BAR;
    auto issue = [&](int i) {
      mbar_expect_tx(BA(i & 3), 49152);
      bulk_load(sb + (i & 3) * 49152, wB + (size_t)e * 256 * 3072 + i * 24576, 49152, BA(i & 3));
    };
#pragma unroll 1
    for (int i = tid; i < 5120; i += 384) reinterpret_cast<float4*>(g_kv)[e * 5120 + i] = make_float4(0.f, 0.f, 0.f, 0.f);
    __syncthreads();
    if (tid == 32) flag_add(&g_csflag[9].v);
    if (tid == 0) {
      if (SVD) __nanosleep(SVD);
#pragma unroll 1
      for (int i = 0; i < 4; ++i) {
        mbar_init(BA(i), 1);
        fence_async_smem();
        issue(i);
      }
    }
    __syncthreads();
#pragma unroll 1
    for (int i = 0; i < 32; ++i) {
      mbar_wait(BA(i & 3), (i >> 2) & 1);
#pragma unroll 2
      for (int r = 0; r < 8; ++r) {
        const uint4 v = lds128(sb + (i & 3) * 49152 + r * 6144 + tid * 16);
        s[0] += bf_lo(v.x); s[1] += bf_hi(v.x); s[2] += bf_lo(v.y); s[3] += bf_hi(v.y);
        s[4] += bf_lo(v.z); s[5] += bf_hi(v.z); s[6] += bf_lo(v.w); s[7] += bf_hi(v.w);
      }
      __syncthreads();
      if (tid == 0 && i < 28) issue(i + 4);
    }
    float* cd = g_cs + (epoch & 1) * 6144 + 3072 + ((tid >> 4) & 7) * 384 + (tid < 128 ? 256 : (tid >> 7) * 128 - 128) + (tid & 15) * 8;
    red_add4(cd, s[0], s[1], s[2], s[3]);
    red_add4(cd + 4, s[4], s[5], s[6], s[7]);
    __syncthreads();
    if (tid == 0) flag_add(&g_csflag[8].v);
    const int op = (epoch & 1) ^ 1;
    reinterpret_cast<float4*>(g_cs + op * 6144)[e * 384 + tid] = make_float4(0.f, 0.f, 0.f, 0.f);
#pragma unroll 1
    for (int i = tid; i < 1024; i += 384) reinterpret_cast<float4*>(g_stats + (op * 4 + e) * S_)[i] = make_float4(0.f, 0.f, 0.f, 0.f);
    return;
  }
  const int warp = __shfl_sync(0xffffffffu, threadIdx.x >> 5, 0), lane = threadIdx.x & 31;
  if (smem_u32(smem_raw) != SB0 + ((blockIdx.x & 1) << 24)) __trap();
  uint32_t cx = 0;
  {
  const int cid = (blockIdx.x - c.boff) >> 1, u7 = ((cid - 36) * 37) >> 8, cr = blockIdx.x & 1;
  const int g = cid < 4 ? 4 + cid : cid < 36 ? (cid - 4) >> 3 : 4 + u7, kf = (cid < 4 ? 0 : cid < 36 ? (cid - 4) & 7 : cid - 35 - 7 * u7) * 2 + cr;
  const uint32_t sb = SB0 + (cr << 24), bar = sb + SM_BAR;
  PROFT(lane == 0 && (warp == 0 || warp == 4), 224 + (warp >> 2) * 8);
  if (warp == 2) {
    if (lane < NMAP) asm volatile("prefetch.tensormap [%0];" ::"l"(&maps.m[lane]) : "memory");
    cx = ld_relaxed(&g_epoch);
    if (cid == 4 && cr == 0 && lane == 0) {
      uint32_t smid; asm volatile("mov.u32 %0, %%smid;" : "=r"(smid));
      asm volatile("st.relaxed.gpu.global.u32 [%0], %1;" ::"l"(&g_rot), "r"((cx + 1) * 8 + ((smid >> 1) & 7)) : "memory");
    }
  } else if (warp == 3) {
    cx = c_map[cid] + c_wop[lane] + c_wop[NWOP - lane] + c_aop[lane] + c_aop[NAOP - lane] + (uint32_t)(uintptr_t)g_x;
  } else if (warp == 8) {
    asm volatile("prefetch.global.L2 [%0];" ::"l"(wphi + g * 4096 + (cr * 32 + lane) * 64));
  } else if (warp >= 4 && warp < 8) {
    const int i = threadIdx.x - 128;
    asm volatile("prefetch.global.L2 [%0];" ::"l"(wA + (size_t)((kf & ~1) * 64 + cr * 32 + ((i >> 1) & 31)) * 3072 + (i >> 6) * 1024 + g * 128 + (i & 1) * 64));
  }
  if (warp < 2) {
    const int s = warp, kb = (kf & ~1) + s;
    if (lane == 0) {
      mbar_init(BA(FM + s), 1u);
      mbar_init(BA(B_RAW + warp), 1u);
      mbar_init(BA(warp ? B_X0 : B_KVS0), 1u);
      if (warp) mbar_init(BA(B_ID), 1u);
      asm volatile("fence.mbarrier_init.release.cluster;" ::: "memory");
    }
    __syncwarp();
    if (warp) __nanosleep(W1DL);
#pragma unroll
    for (int j = 0; j < 6; ++j) {
      if (j == 4 && warp == 0) tma_2d_e(sb + SM_SD, &maps.m[MAP_PHI], 0, g * 128, BA(B_RAW));
      tma_5d_e(sb + (j < 2 ? 2 * s : j < 4 ? 9 + s : 2 * s + 1) * SLOT + (j & 1) * 8192, &maps.m[MAP_WA], (j < 2 ? 1024 : j < 4 ? 0 : 2048) + g * 128 + (j & 1) * 64, 2 * kb,
               BA(j < 4 ? B_RAW + warp : FM + s));
    }
    expect_tx_e(BA(B_RAW + warp), warp ? 32768 : 32768 + 8192);
    expect_tx_e(BA(FM + s), 32768);
  } else if (warp >= 4 && lane == 0) {
#pragma unroll 1
    for (int i = 2 + (warp - 4) * 13; i < 15 + (warp - 4) * 13; ++i)
      mbar_init(BA(i), 1u << ((i < CM ? 0u : i < B_EF ? 2u : (uint32_t)(BAR_LG >> (4 * ((i - B_EF) & 15)))) & 7u));
    asm volatile("fence.mbarrier_init.release.cluster;" ::: "memory");
  }
  __syncwarp();
  asm volatile("barrier.cluster.arrive.relaxed.aligned;" ::: "memory");
  if (threadIdx.x == 96 + c.zero) sts_f(sb + SM_ID + 4, __uint_as_float(cx));
  PROFT(lane == 0 && (warp == 0 || warp == 4), 225 + (warp >> 2) * 8);
  __syncwarp();
  PROFT(lane == 0 && (warp == 0 || warp == 4), 226 + (warp >> 2) * 8);
  }

  if (warp < 4) {
    asm volatile("setmaxnreg.dec.sync.aligned.u32 40;");
    PROFT(threadIdx.x == 0, 227);
    cluster_wait();
    PROFT(threadIdx.x == 0, 228);
    if (warp == 0 || warp == 3) {
    if (warp == 0) {
      STA_CTX();
      const unsigned int epoch = __shfl_sync(0xffffffffu, ld_relaxed(&g_epoch), 0), xbase = epoch * NLAYERS;
      (void)xbase;
      const uint64_t ordg = k_order(g);
      mbar_wait_u(BA(B_ID), 0);
      const int rb = (__shfl_sync(0xffffffffu, LD_ID(), 0) >> 3) & 15, m0 = rb * 128;
      tma_2d_e(sb + XS * SLOT, &maps.m[MAP_X0], (kf & ~1) * 64, m0, BA(FM));
      tma_2d_e(sb + (XS + 1) * SLOT, &maps.m[MAP_X0], (kf | 1) * 64, m0, BA(FM + 1));
      if (X0AT) {
        mbar_wait_u(BA(B_RAW + X0AT - 1), 0);
        tma_2d_e(sb + 11 * SLOT, &maps.m[MAP_X0], g * 128, m0, BA(B_X0));
        tma_2d_e(sb + 12 * SLOT, &maps.m[MAP_X0], g * 128 + 64, m0, BA(B_X0));
        expect_tx_e(BA(B_X0), 32768);
      }
#pragma unroll 1
      for (int lp = 0; lp < 2 * NLAYERS; ++lp) {
        const int layer = lp >> 1, n1 = (lp & 1) ? NAOP : NAOP - 14;
        int n = (lp & 1) ? NAOP - 14 : 0;
        const uint64_t ord = lp ? ordg : k_order(kf >> 1);
        uint32_t ready = lp ? 0u : 0xFFFFu, nop = c_aop[n];
        const unsigned int* fl = ((lp & 1) ? g_of : g_xf) + rb * 32;
        const CUtensorMap* tm = &maps.m[(lp & 1) ? MAP_O : lp ? MAP_X : MAP_X0];
        const uint32_t skip = layer ? 1u << 25 : 9u << 22;
        if (lp) mbar_wait_u(BA((lp & 1) ? B_OH0 : B_XH0), ((lp - 1) >> 1) & 1);
#pragma unroll 1
        for (; n < n1; ++n) {
          const uint32_t op = nop;
          nop = c_aop[n + 1];
          const uint32_t kb = (uint32_t)(ord >> ((op >> 2) & 60)) & 15;
          uint32_t dst = sb + (op & 15) * SLOT, kc = kb * 64, fb = bar + ((op >> 5) & 0x3F8), need = ~ready & (1u << kb);
          asm volatile("" : "+r"(dst), "+r"(kc), "+r"(fb), "+r"(need));
          const uint32_t eb = bar + ((op >> 12) & 0x3F8), ep = (layer ^ (op >> 22)) & 1;
          bool fr = op & skip;
          if (need) {
            if (!fr) fr = __all_sync(0xffffffffu, mbar_test_wait(eb, ep));
            PROFT(lane == 0 && (n == 0 || n == NAOP - 14), 64 + layer * 16 + (n ? 2 : 0));
            src_wait<0>(fl, xbase + layer + 1, need, ready, lane);
            fence_async_all();
          }
          if (!fr) mbar_wait_u(eb, ep);
          tma_2d_e(dst, tm, kc, m0, fb);
          PROFT(lane == 0 && (n == 0 || n == NAOP - 14), 64 + layer * 16 + (n ? 3 : 1));
          PROFL(lane == 0 && layer == PL && n >= NAOP - 14, 178 + n - (NAOP - 14));
          PROFL(lane == 0 && layer == PL + 1 && n < 4, 242 + n);
        }
      }
    } else {
      STA_CTX();
      const unsigned int epoch = __shfl_sync(0xffffffffu, ld_relaxed(&g_epoch), 0), xbase = epoch * NLAYERS;
      (void)xbase;
      const uint64_t ordg = k_order(g);
#pragma unroll 1
      for (int layer = 0; layer < NLAYERS; ++layer) {
        const uint64_t ordq = layer ? ordg : k_order(kf >> 1);
        uint32_t ready = layer ? 0xFFFFu : 0u, nop = c_wop[0];
        const CUtensorMap* tq = &maps.m[(layer & 1) ? MAP_WB : MAP_WF];
        const CUtensorMap* tk = &maps.m[(layer & 1) ? MAP_WB : cr ? MAP_WA : MAP_WF];
        const uint32_t skip = layer ? 1u << 25 : 9u << 22, pm = layer ? 0xE0u : 0u;
        int n = 0;
#pragma unroll 1
        for (; n < NWOP - 16; ++n) {
          const uint32_t op = nop;
          nop = c_wop[n + 1];
          const uint32_t isq = (op >> 23) & 1, fb = bar + ((op >> 5) & 0x3F8);
          const uint32_t kb = (uint32_t)(ordq >> ((op >> 2) & 60)) & 15;
          const CUtensorMap* tm = (isq ? tq : tk) + ((op & pm) ? 1 : 0);
          const uint32_t dst = sb + (op & 15) * SLOT + cr * (isq ? 8192 : SLOT);
          const int col = g * 128 + (isq ? cr * 64 : 1024 + cr * 1024);
          if (layer == 0) {
            if ((op & 0x7E00) == 0) continue;
            const uint32_t need = ((isq || !cr) ? 1u << kb : 0u) | (((op >> 22) & 1) ? 0u : (((op >> 15) & 127) == CM ? 1u : 3u) << (kf & ~1));
            if ((ready & need) != need) {
              src_wait<0>(g_wff + g * 32, epoch + 1, need, ready, lane);
              fence_async_all();
            }
            if ((op & 15) >= 11) mbar_wait_u(BA(B_XT), 0);
          }
          wait_tma_5d_mc(!(op & skip), bar + ((op >> 12) & 0x3F8), (layer ^ (op >> 22)) & 1, dst, tm, col, 2 * kb, fb);
          if (!isq) tma_5d_mc_e(dst + 8192, tm, col + 64, 2 * kb, fb);
          if (op >> 26) expect_tx_e(fb, (op >> 26) * 8192);
          PROFL(lane == 0 && layer == PL + 1 && n < 16, 128 + n);
        }
        const CUtensorMap* to = &maps.m[(layer & 1) ? MAP_WOB : MAP_WOA];
#pragma unroll 1
        for (; n < NWOP; ++n) {
          const uint32_t op = nop;
          nop = c_wop[n + 1];
          const uint32_t fb = bar + ((op >> 5) & 0x3F8), kb = (uint32_t)(ordg >> ((op >> 2) & 60)) & 15;
          if (WH < 16 && n == NWOP - 16 + WH && !(layer & 1)) mbar_wait_u(BA(B_KVS), (layer >> 1) & 1);
          wait_tma_5d_mc(!((op >> 25) & 1), bar + ((op >> 12) & 0x3F8), layer & 1, sb + (op & 15) * SLOT + cr * 8192, to + ((op & 0xE0) ? 1 : 0), g * 128 + cr * 64, 2 * kb, fb);
          expect_tx_e(fb, (op >> 26) * 8192);
          PROFL(lane == 0 && layer == PL, 144 + ((op >> 8) & 127) - FW);
        }
      }
    }
    } else if (warp == 1) {
      STA_CTX();
      const unsigned int epoch = __shfl_sync(0xffffffffu, ld_relaxed(&g_epoch), 0), xbase = epoch * NLAYERS;
      (void)xbase;
      if (lane == 0) {
        mbar_wait_s(BA(B_WFD), 0);
        PROFT(true, 229);
#pragma unroll 1
        for (int j = 0; j < 4; ++j) tma_store_5d(&maps.m[MAP_WF], sb + (j < 2 ? 2 * cr : 9 + cr) * SLOT + (j & 1) * 8192, (j < 2 ? 1024 : 0) + g * 128 + (j & 1) * 64, 2 * kf);
        bulk_commit();
        bulk_wait0();
        PROFT(true, 230);
        fence_async_all();
        flag_set(g_wff + g * 32 + kf, epoch + 1);
        mbar_wait_s(BA(B_ID), 0);
        PROFT(true, 64 + 13);
#pragma unroll 1
        for (int e = 0; e < NLAYERS; ++e) {
          BASE_CTX();
          bid_ -= c.boff;
          DYN_CTX(LD_ID());
          if (e > 0) {
            mbar_wait_s(BA(B_XH0), (e - 1) & 1);
            PROFT(e == PL + 1, 240);
            flag_set(g_xf + rb * 32 + 2 * g, xbase + e + 1);
            PROFT(e == PL + 1, 241);
          }
          mbar_wait_s(BA(B_XDONE), e & 1);
          PROFT(true, 64 + e * 16 + 4);
          flag_set(g_xf + rb * 32 + 2 * g + 1, xbase + e + 1);
          if (e == 0) {
            flag_add(&g_csflag[g].v);
            flag_wait(&g_csflag[9].v, epoch * 4u + 4u);
            fence_async_all();
#pragma unroll 1
            for (int i = 0; i < 4; ++i) {
              mbar_wait_s(BA(CM + PFM + PFS * i), 0);
              l2_prefetch(i < 3 ? wB + (size_t)(i * 128 + bid_) * 8192 : woA + (size_t)bid_ * 8192, 16384);
            }
          }
          if (e == 1) l2_prefetch(woB + (size_t)bid_ * 8192, 16384);
          PROFT(true, 64 + e * 16 + 7);
          if ((e & 1) == 0) {
            bf16* kvl = g_kv + ((e >> 1) * 8 + g) * 10240;
#pragma unroll 1
            for (int hp = 0; hp < 2; ++hp) {
              mbar_wait_s(BA(B_KVDONE), hp);
#pragma unroll 1
              for (int i = 0; i < 4; ++i) {
                const int ch = (i + (rb >> 2)) & 3;
                bulk_red_add(kvl + hp * 5120 + ch * 1280, sb + VB + hp * SLOT + (ch >> 1) * 8192 + (ch & 1) * 2560, 2560);
                bulk_commit();
              }
              bulk_wait0();
              PROFT(true, 64 + e * 16 + (hp ? 10 : 6));
              fence_async_all();
              flag_add(&g_kvflag[hp * 8 + g].v);
              mbar_arrive(BA(hp ? B_KVS : B_KVS0));
              PROFT(e > 0 && hp, 64 + e * 16 + 8);
            }
          }
          if (e & 1) {
            mbar_wait_s(BA(B_OF0), (e >> 1) & 1);
            flag_set(g_hf + rb * 32 + g, xbase + e + 1);
            if (rb) flag_wait(g_hf + (rb - 1) * 32 + g, xbase + e + 1);
            fence_async_all();
            mbar_expect_tx(BA(B_HALO), 8192);
            bulk_load(sb + SM_SD, g_halo + (size_t)(((e >> 1) * 17 + rb) * 8 + g) * 2048, 8192, BA(B_HALO));
            PROFT(true, 64 + e * 16 + 15);
          }
          mbar_wait_s(BA(B_OH0), e & 1);
          PROFT(e > 0, 64 + e * 16 + 13);
          flag_set(g_of + rb * 32 + 2 * g, xbase + e + 1);
          PROFT(true, 64 + e * 16 + 9);
          mbar_wait_s(BA(B_OH1), e & 1);
          PROFT(true, 64 + e * 16 + 5);
          flag_set(g_of + rb * 32 + 2 * g + 1, xbase + e + 1);
          PROFT(true, 64 + e * 16 + 11);
        }
        if (bid_ == 0) g_epoch = epoch + 1;
      }
    } else {
      STA_CTX();
      const unsigned int epoch = __shfl_sync(0xffffffffu, cx, 0), xbase = epoch * NLAYERS;
      (void)xbase;
      uint32_t idp = kf >> 1;
      if (g >= 4) {
        uint32_t v, n = 0;
#pragma unroll 1
        do { v = __shfl_sync(0xffffffffu, ld_relaxed(&g_rot), 0); } while ((v >> 3) != ((epoch + 1) & 0x1FFFFFFFu) && ++n < (1u << 20));
        const uint32_t c0 = (8 - v) & 7;
        idp = idp == 0 ? c0 : idp - 1 + (idp - 1 >= c0 ? 1 : 0);
      }
      idp = g | ((2 * idp + cr) << 3) | ((epoch & 1) << 8);
      if (lane == 0) {
        sts_f(sb + SM_ID, __uint_as_float(idp));
        mbar_arrive(BA(B_ID));
      }
      PROFT(lane == 0, 231);
      if (lane < 16) sts_f(sb + SM_RS + lane * 4, 0.f);
#pragma unroll 1
      for (int layer = 0; layer < NLAYERS; ++layer) {
#define HLP_CTX() BASE_CTX(); uint32_t idl_ = idp; asm volatile("" : "+r"(idl_)); DYN_CTX(idl_); int lane = threadIdx.x & 31; asm volatile("" : "+r"(lane)); const bool isB = layer & 1, hal = isB && rb > 0; (void)hal;
#pragma unroll 1
        for (int ph = 0; ph < 2; ++ph) {
          HLP_CTX();
          if (ph == (layer == 0)) {
            const float* cs = g_cs + (epoch & 1) * 6144 + g * 384;
            if (layer) mbar_wait_u(BA(CT), (layer - 1) & 1);
            if (layer < 2) {
              if (lane == 0) flag_wait_slow(&g_csflag[isB ? 8 : g].v, isB ? epoch * 4u + 4u : epoch * 16u + 16u);
              __syncwarp();
            }
#pragma unroll 1
            for (int i0 = 0; i0 < 12; i0 += 4) {
              float a[4];
#pragma unroll
              for (int i = 0; i < 4; ++i) a[i] = __ldcg(cs + isB * 3072 + (i0 + i) * 32 + lane);
#pragma unroll
              for (int i = 0; i < 4; ++i) {
                const float c1 = bf16r(a[i]), c2 = bf16r(a[i] - c1), c3 = (a[i] - c1) - c2;
                sts128(sb + SM_BP + ((i0 + i) * 32 + lane) * 16, make_uint4(pack_bf16(c1, c2), pack_bf16(c3, 0.f), 0u, 0u));
              }
            }
          } else {
            uint32_t rdy = 0u;
            mbar_wait_u(BA(CM + 3), layer & 1);
            src_wait<128>(g_xf + rb * 32, xbase + layer + 1, 0xAAAAu, rdy, lane);
            rdy = 0u;
            if (hal) src_wait<128>(g_xf + (rb - 1) * 32, xbase + layer + 1, 0xAAAAu, rdy, lane);
            const float2* sp = g_stats + ((epoch & 1) * 4 + layer) * S_ + m0 + lane;
            float2 u[5];
#pragma unroll
            for (int i = 0; i < 4; ++i) u[i] = __ldcg(sp + i * 32);
            u[4] = __ldcg(sp - (hal ? 16 : 0));
#pragma unroll 1
            for (int i = 0; i < 5; ++i) {
              const float mean = u[0].x * (1.f / D_);
              const float var = fmaxf(fmaf(-u[0].x, mean, u[0].y) * (1.f / D_), 0.f);
              const float sd = bf16r(sqrtf(bf16r(bf16r(var) + 1e-5f)));
              const int R = i * 32 + lane;
              if (i < 4) {
                const float hm = -0.5f * bf16r(mean);
                if (!isB) sts128(sb + SM_SD + R * 64 + ((R >> 1) & 3) * 16, make_uint4(__float_as_uint(sd) >> 16, __float_as_uint(sd) >> 16, __float_as_uint(sd) >> 16, __float_as_uint(sd) >> 16));
                sts128(sb + SM_AP + R * 16, make_uint4(pack_bf16(hm, hm), pack_bf16(hm, 0.f), 0u, 0u));
              }
              if (i < 4 || (hal && lane < 16)) sts_f(sb + SM_RS + (i < 4 ? 16 + R : lane) * 4, __fdividef(1.f, sd));
#pragma unroll
              for (int j = 0; j < 4; ++j) u[j] = u[j + 1];
            }
            PROFT(lane == 0, 64 + layer * 16 + 12);
          }
        }
        HLP_CTX();
        fence_async_smem();
        __syncwarp();
        if (lane == 0) mbar_arrive(BA(B_STAT));
        PROFT(lane == 0, 64 + layer * 16 + 14);
        if (!isB && lane == 0) {
#pragma unroll 1
          for (int hp = 0; hp < 2; ++hp) {
            mbar_wait_s(BA(hp ? B_KVS : B_KVS0), (layer >> 1) & 1);
            flag_wait(&g_kvflag[hp * 8 + g].v, epoch * (16u * ((NLAYERS + 1) / 2)) + 16u * ((layer >> 1) + 1));
            const bf16* kvl = g_kv + ((layer >> 1) * 8 + g) * 10240 + hp * 5120;
            const uint32_t kb = BA(hp ? B_KVF1 : B_KVF);
            fence_async_all();
            mbar_expect_tx(kb, 10240);
            bulk_load(sb + VB + hp * SLOT, kvl, 5120, kb);
            bulk_load(sb + VB + hp * SLOT + 8192, kvl + 2560, 5120, kb);
            PROFT(hp == 0, 64 + layer * 16 + 15);
          }
        }
        __syncwarp();
      }
    }
    __syncwarp();
    asm volatile("barrier.cluster.arrive.relaxed.aligned;" ::: "memory");
    cluster_wait();
  } else {
    asm volatile("setmaxnreg.inc.sync.aligned.u32 232;");
    PROFT(threadIdx.x == 128, 235);
    cluster_wait();
    PROFT(threadIdx.x == 128, 236);
    consumer(c);
    asm volatile("bar.warp.sync 0xffffffff;\nbarrier.cluster.arrive.relaxed.aligned;\nbarrier.cluster.wait.aligned;\n" ::: "memory");
  }
}

typedef CUresult (*PFN_encodeTiled)(CUtensorMap*, CUtensorMapDataType, cuuint32_t, void*, const cuuint64_t*, const cuuint64_t*,
                                    const cuuint32_t*, const cuuint32_t*, CUtensorMapInterleave, CUtensorMapSwizzle,
                                    CUtensorMapL2promotion, CUtensorMapFloatOOBfill);

static void make_map2(PFN_encodeTiled enc, CUtensorMap* m, const void* ptr, uint64_t cols, uint64_t rows, uint32_t box_c, uint32_t box_r) {
  cuuint64_t dims[2] = {cols, rows};
  cuuint64_t strides[1] = {cols * 2};
  cuuint32_t box[2] = {box_c, box_r};
  cuuint32_t es[2] = {1, 1};
  CUresult r = enc(m, CU_TENSOR_MAP_DATA_TYPE_BFLOAT16, 2, const_cast<void*>(ptr), dims, strides, box, es, CU_TENSOR_MAP_INTERLEAVE_NONE,
                   box_c == 64 ? CU_TENSOR_MAP_SWIZZLE_128B : CU_TENSOR_MAP_SWIZZLE_64B, CU_TENSOR_MAP_L2_PROMOTION_L2_256B, CU_TENSOR_MAP_FLOAT_OOB_FILL_NONE);
  (void)r;
}
static void make_map5(PFN_encodeTiled enc, CUtensorMap* m, const void* ptr, uint64_t cols) {
  for (int p = 0; p < 2; ++p) {
    cuuint64_t dims[5] = {cols, 2, 4, 4, 32};
    cuuint64_t strides[4] = {cols * 2, cols * (p ? 16 : 4), cols * (p ? 4 : 16), cols * 64};
    cuuint32_t box[5] = {64, 2, 4, 4, 2};
    cuuint32_t es[5] = {1, 1, 1, 1, 1};
    CUresult r = enc(m + p, CU_TENSOR_MAP_DATA_TYPE_BFLOAT16, 5, const_cast<void*>(ptr), dims, strides, box, es, CU_TENSOR_MAP_INTERLEAVE_NONE,
                     CU_TENSOR_MAP_SWIZZLE_128B, CU_TENSOR_MAP_L2_PROMOTION_L2_256B, CU_TENSOR_MAP_FLOAT_OOB_FILL_NONE);
    (void)r;
  }
}

extern "C" void kernel_launch(void* const* d_in, const int* in_sizes, int n_in, void* d_out, int out_size) {
  const bf16* A_x = (const bf16*)d_in[0];
  const bf16* A_wqkv = (const bf16*)d_in[1];
  const bf16* A_wphi = (const bf16*)d_in[2];
  const bf16* A_wo = (const bf16*)d_in[3];
  const bf16* B_wqkv = (const bf16*)d_in[5];
  const bf16* B_wo = (const bf16*)d_in[6];
  bf16* out = (bf16*)d_out;

  static PFN_encodeTiled enc = nullptr;
  static bf16 *p_x, *p_o, *p_wf;
  static uint32_t boff;
  if (!enc) {
    void* fn = nullptr; cudaDriverEntryPointQueryResult qr;
    cudaGetDriverEntryPoint("cuTensorMapEncodeTiled", &fn, cudaEnableDefault, &qr);
    enc = (PFN_encodeTiled)fn;
    cudaGetSymbolAddress((void**)&p_x, g_x);
    cudaGetSymbolAddress((void**)&p_o, g_o);
    cudaGetSymbolAddress((void**)&p_wf, g_wf);
    cudaFuncSetAttribute(mega_kernel, cudaFuncAttributeMaxDynamicSharedMemorySize, SM_TOTAL);
    cudaLaunchConfig_t cfg = {};
    cudaLaunchAttribute at; at.id = cudaLaunchAttributeClusterDimension; at.val.clusterDim.x = 2; at.val.clusterDim.y = 1; at.val.clusterDim.z = 1;
    cfg.gridDim = dim3(132); cfg.blockDim = dim3(384); cfg.dynamicSmemBytes = SM_TOTAL; cfg.attrs = &at; cfg.numAttrs = 1;
    int nc = 0;
    if (cudaOccupancyMaxActiveClusters(&nc, mega_kernel, &cfg) != cudaSuccess) { nc = 0; (void)cudaGetLastError(); }
    boff = nc >= 66 ? 0u : 4u;
  }
  Maps maps;
  make_map5(enc, &maps.m[MAP_WF], p_wf, 2048);
  make_map5(enc, &maps.m[MAP_WA], A_wqkv, 3072);
  make_map5(enc, &maps.m[MAP_WB], B_wqkv, 3072);
  make_map5(enc, &maps.m[MAP_WOA], A_wo, 1024);
  make_map5(enc, &maps.m[MAP_WOB], B_wo, 1024);
  make_map2(enc, &maps.m[MAP_X0], A_x, 1024, 2048, 64, 128);
  make_map2(enc, &maps.m[MAP_X], p_x, 1024, 2048, 64, 128);
  make_map2(enc, &maps.m[MAP_O], p_o, 1024, 2048, 64, 128);
  make_map2(enc, &maps.m[MAP_PHI], A_wphi, 32, 1024, 32, 128);
  Ctx c; c.zero = 0u; c.boff = boff; c.x0 = A_x; c.out = out;
  mega_kernel<<<132, 384, SM_TOTAL, cudaStreamPerThread>>>(maps, c, A_wqkv, B_wqkv, A_wo, B_wo, A_wphi);
}
```
